```python
import torch

def _softmax(x, axis=-1):
    return torch.softmax(x, dim=axis)
def _gelu(x):
    return torch.nn.functional.gelu(x, approximate="tanh")
def _silu(x):
    return torch.nn.functional.silu(x)
def _sigmoid(x):
    return torch.sigmoid(x)
def _layernorm(x, axis=-1, eps=1e-5):
    m = x.mean(dim=axis, keepdim=True)
    v = x.var(dim=axis, keepdim=True, unbiased=False)
    return (x - m) / torch.sqrt(v + eps)
def _scatter_add(tgt, idx, src, axis=0):
    return tgt.clone().index_add_(axis, idx, src)
def _segment_sum(src, seg, n):
    out = torch.zeros((n,) + src.shape[1:], dtype=src.dtype)
    return out.index_add_(0, seg, src)
def _pad(x, pw):
    flat = tuple(v for pair in reversed(pw) for v in pair)
    return torch.nn.functional.pad(x, flat)

kernel_name = 'recurrent_scan__linear_kernel_hedgehog__moe_arch_mod__prompt'

def setup_inputs():

    _w = (lambda a: (lambda t: t.to(torch.bfloat16) if t.is_floating_point() else t)(torch.as_tensor(a)))
    def _A_setup():
        B, S, D, H = 1, 2048, 1024, 32
        Dh = D // H
        return {
            "x": _w((lambda *s: torch.randn(*s, dtype=torch.bfloat16) * 0.05)(B, S, D)),
            "wqkv": _w((lambda *s: torch.randn(*s, dtype=torch.bfloat16) * 0.2)(D, 3 * D)),
            "w_phi": _w((lambda *s: torch.randn(*s, dtype=torch.bfloat16) * 0.2)(H, Dh, Dh) * (Dh ** -0.5)),
            "wo": _w((lambda *s: torch.randn(*s, dtype=torch.bfloat16) * 0.05)(D, D)),
        }
    _A_in = _A_setup()

    def _B_setup():
        B, S, D, F, C = 1, 2048, 1024, 3584, 1
        return {
            "x": _w((lambda *s: torch.randn(*s, dtype=torch.bfloat16) * 0.05)(B, S, D)),
            "w_r": _w((lambda *s: torch.randn(*s, dtype=torch.bfloat16) * 0.05)(D)),
            "w_gate": _w((lambda *s: torch.randn(*s, dtype=torch.bfloat16) * 0.05)(D, F)),
            "w_up": _w((lambda *s: torch.randn(*s, dtype=torch.bfloat16) * 0.05)(D, F)),
            "w_down": _w((lambda *s: torch.randn(*s, dtype=torch.bfloat16) * 0.05)(F, D)),
        }
    _B_in = _B_setup()

    return {
        "A_x": _A_in["x"],
        "A_wqkv": _A_in["wqkv"],
        "A_w_phi": _A_in["w_phi"],
        "A_wo": _A_in["wo"],
        "B_x": _B_in["x"],
        "B_w_r": _B_in["w_r"],
        "B_w_gate": _B_in["w_gate"],
        "B_w_up": _B_in["w_up"],
        "B_w_down": _B_in["w_down"],
    }

def reference(A_x, A_wqkv, A_w_phi, A_wo, B_x, B_w_r, B_w_gate, B_w_up, B_w_down):
    def _A_ref(x, wqkv, w_phi, wo):
        B, S, D = x.shape
        H = 32; Dh = D // H
        qkv = (lambda x, *d: x.permute(*d))((x @ wqkv).reshape(B, S, 3, H, Dh), 2, 0, 3, 1, 4)
        q, k, v = qkv[0], qkv[1], qkv[2]
        pq = torch.einsum("bhsd,hdf->bhsf", q, w_phi)
        pk = torch.einsum("bhsd,hdf->bhsf", k, w_phi)
        phi_q = torch.concatenate([_softmax(pq, axis=-1), _softmax(-pq, axis=-1)], axis=-1)
        phi_k = torch.concatenate([_softmax(pk, axis=-1), _softmax(-pk, axis=-1)], axis=-1)
        kv = torch.einsum("bhsf,bhsd->bhfd", phi_k, v)
        z  = torch.einsum("bhsf->bhf", phi_k)
        num = torch.einsum("bhqf,bhfd->bhqd", phi_q, kv)
        den = torch.einsum("bhqf,bhf->bhq", phi_q, z)[..., None] + 1e-6
        o = num / den
        return (lambda x, *d: x.permute(*d))(o, 0, 2, 1, 3).reshape(B, S, D) @ wo

    def _B_ref(x, w_r, w_gate, w_up, w_down):
        B, S, D = x.shape
        C = 1
        r = x @ w_r
        idx = torch.argsort(-r, axis=-1)[:, :C]
        idx_e = (lambda x, n, axis: torch.repeat_interleave(x, n, dim=axis))(idx.reshape(B, C, 1), D, axis=2)
        x_sel = (lambda x, i, axis: torch.take_along_dim(x, i, dim=axis))(x, idx_e, axis=1)
        g = _silu(x_sel @ w_gate)
        u = x_sel @ w_up
        y = (g * u) @ w_down
        r_sel = _sigmoid((lambda x, i, axis: torch.take_along_dim(x, i, dim=axis))(r, idx, axis=1))
        y = y * r_sel.reshape(B, C, 1)
        b_off = (torch.arange(B) * S).reshape(B, 1)
        flat_idx = (idx + b_off).reshape(B * C)
        zero = (x * 0.0).reshape(B * S, D)
        upd = _scatter_add(zero, flat_idx, y.reshape(B * C, D), axis=0)
        return x + upd.reshape(B, S, D)

    x = A_x
    xn = _layernorm(x, axis=-1)
    s = _A_ref(xn, A_wqkv, A_w_phi, A_wo)
    g = _silu(_B_ref(xn, B_w_r, B_w_gate, B_w_up, B_w_down))
    return x + s * g
```

```cpp
#include <cuda_runtime.h>
#include <cuda_bf16.h>
#include <cuda.h>
#include <stdint.h>

namespace {

constexpr int SEQ = 2048, DM = 1024, FF = 3584;
constexpr int NCTA = 128;
constexpr int NSPARE = 4;
constexpr int NFFN = FF / 32;
#define GN 6
#define G8 4
constexpr int GROWS = (3 * GN + G8) * 32;
#define TAILN 2
#define KTAIL 1
#define XS_EARLY 1
#define PF_FIRST 2
#define PF_W 5
#define PF_PRE 1
#define PFG 0
#define PFD 80
#define BY_SM 1
#define PTAB 0x73216540u
#define ROWSPLIT 1
#define WOT 1
#define PSPLIT 1
#define KSTEPS 4
#define NOVAL 0
#define KCH 1
#define REG_C 224
#define REG_H 56
#define ORDER_ALL 1
#define AM_NS 100
constexpr bool FFN_OFF = false;

static_assert(2 * REG_C + REG_H <= 3 * 168, "the register pool of the CTA is 384 x 168");

__device__ uint32_t g_epoch[(NCTA + NSPARE) * 32];
__device__ unsigned long long g_stat[SEQ];
__device__ __align__(128) unsigned long long g_best[NCTA];
__device__ __align__(16) float g_y[2][8][DM];
__device__ __align__(128) uint32_t g_ycnt[64];
__device__ __align__(128) uint32_t g_xcnt[8 * 64];
__device__ __align__(128) uint4 g_res[2][32 * 256];
__device__ __align__(16) float g_cs[5 * DM];
__device__ __align__(128) float g_gp[2 * FF];
__device__ uint4 g_part[8 * 2 * 16 * 16 * 32];
__device__ __align__(16) float g_zpart[8 * 2 * 16 * 16 * 8];
__device__ __align__(128) float g_zres[32 * 64];
__device__ __align__(1024) uint4 g_ofr[16 * 16 * 1024];
#define PROF(i)
#define PROFT(i)
#define PROFC(i)
#define PROF_DUMP
#define PW0(J)
#define PW1(J)

constexpr uint32_t KV_STAGE = 49152, Q_STAGE = 32768;
constexpr uint32_t SM_V = 147456;
constexpr uint32_t SM_PHI = 163840;
constexpr uint32_t SM_XST = 147456;
constexpr uint32_t SM_FST = 172032;
constexpr uint32_t SM_PST0 = 196608, SM_PST1 = SM_PHI + 8192;
constexpr uint32_t SM_X0 = 131072, SM_X1 = SM_PHI + 16384;
constexpr uint32_t SM_WPHI = 204800;
constexpr uint32_t SM_ZT = 212992;
constexpr uint32_t SM_SDT = 217088;
constexpr uint32_t SM_CST = 219136;
constexpr uint32_t SM_HT = 222720;
constexpr uint32_t SM_STAT = 223232;
constexpr uint32_t SM_XSEL = 224256;
constexpr uint32_t SM_RED = 228352;
constexpr uint32_t SM_ROWS = SM_RED + 832;
constexpr uint32_t SM_GRED = SM_XSEL + 3072;
static_assert(GROWS <= 768, "xsel area");
constexpr uint32_t SM_UPD = 229632;
constexpr uint32_t SM_BAR = 230016;
constexpr uint32_t SM_PROF = 230464;
constexpr uint32_t SM_SINK = 231104;
constexpr uint32_t SM_TOTAL = 231616;
constexpr uint32_t SB = 1024;
constexpr uint32_t B_FULLKV = 0  , B_FST = 24  , B_XFULL = 88  , B_XST = 104  , B_WPHI = 120, B_CS = 128, B_CSQ = 136, B_UPD = 144,
                   B_H = 152, B_DN = 160, B_XS = 168, B_TILE = 176  , B_RES = 192  , B_PART = 208  ,
B_AIN = 224  ,
                   B_FULLQ = 288  ,
                   B_FFN = 320,
                   B_EMPTYKV = 328  , B_EMPTYQ = 352  , B_KVST = 384  , B_YD = 400, B_PHI = 408  , B_DND = 424, B_END = 432;

__device__ __forceinline__ uint32_t smem_u32(const void* p) { return (uint32_t)__cvta_generic_to_shared(p); }
__device__ __forceinline__ void mbar_init(uint32_t bar, uint32_t cnt) { asm volatile("mbarrier.init.shared::cta.b64 [%0], %1;" ::"r"(bar), "r"(cnt) : "memory"); }
__device__ __forceinline__ void mbar_expect_tx(uint32_t bar, uint32_t bytes) { asm volatile("mbarrier.arrive.expect_tx.shared::cta.b64 _, [%0], %1;" ::"r"(bar), "r"(bytes) : "memory"); }
__device__ __forceinline__ void mbar_arrive2(uint32_t bar) { asm volatile("mbarrier.arrive.shared::cta.b64 _, [%0], 2;" ::"r"(bar) : "memory"); }
__device__ __forceinline__ void mbar_arrive(uint32_t bar) { asm volatile("mbarrier.arrive.shared::cta.b64 _, [%0];" ::"r"(bar) : "memory"); }
__device__ __forceinline__ void mbar_wait(uint32_t bar, uint32_t parity) {
  asm volatile("{\n.reg .pred p;\nLW:\nmbarrier.try_wait.parity.shared::cta.b64 p, [%0], %1;\n@!p bra LW;\n}" ::"r"(bar), "r"(parity) : "memory");
}
__device__ __forceinline__ bool mbar_test(uint32_t bar, uint32_t parity) {
  uint32_t ok;
  asm volatile("{\n.reg .pred p;\nmbarrier.test_wait.parity.shared::cta.b64 p, [%1], %2;\nselp.u32 %0, 1, 0, p;\n}" : "=r"(ok) : "r"(bar), "r"(parity) : "memory");
  return ok;
}
__device__ __forceinline__ int lane_id() { int l; asm volatile("mov.u32 %0, %%laneid;" : "=r"(l)); return l; }
template <int C> __device__ __forceinline__ void sched_fence_(int zero) {
  asm volatile("{\n.reg .pred p;\nsetp.eq.s32 p, %0, %1;\nSF:\npmevent 1;\n@p bra SF;\n}" ::"r"(zero), "n"(C) : "memory");
}
#define SCHED_FENCE() sched_fence_<1000 + __COUNTER__>(zero)
#define SCHED_PIN(V) sched_fence_<1000 + __COUNTER__>(zero & __float_as_int(V))
__device__ __forceinline__ bool elect_one() {
  uint32_t p; asm volatile("{ .reg .pred P; elect.sync _|P, 0xffffffff; selp.u32 %0, 1, 0, P; }" : "=r"(p)); return p;
}
__device__ __forceinline__ void tma2d(uint32_t dst, const CUtensorMap* m, int x, int y, uint32_t bar) {
  asm volatile("cp.async.bulk.tensor.2d.shared::cluster.global.mbarrier::complete_tx::bytes [%0], [%1, {%3, %4}], [%2];" ::"r"(dst), "l"(m), "r"(bar), "r"(x), "r"(y) : "memory");
}
__device__ __forceinline__ void tma3d(uint32_t dst, const CUtensorMap* m, int x, int y, int z, uint32_t bar) {
  asm volatile("cp.async.bulk.tensor.3d.shared::cluster.global.mbarrier::complete_tx::bytes [%0], [%1, {%3, %4, %5}], [%2];" ::"r"(dst), "l"(m), "r"(bar), "r"(x), "r"(y), "r"(z) : "memory");
}
__device__ __forceinline__ void tma4d(uint32_t dst, const CUtensorMap* m, int x, int y, int z, int w, uint32_t bar) {
  asm volatile("cp.async.bulk.tensor.4d.shared::cluster.global.mbarrier::complete_tx::bytes [%0], [%1, {%3, %4, %5, %6}], [%2];" ::"r"(dst), "l"(m), "r"(bar), "r"(x), "r"(y), "r"(z), "r"(w) : "memory");
}
__device__ __forceinline__ void tma5d(uint32_t dst, const CUtensorMap* m, int x, int v, uint32_t bar) {
  asm volatile("cp.async.bulk.tensor.5d.shared::cluster.global.mbarrier::complete_tx::bytes [%0], [%1, {%3, %5, %5, %5, %4}], [%2];" ::"r"(dst), "l"(m), "r"(bar), "r"(x), "r"(v), "r"(0) : "memory");
}
__device__ __forceinline__ void tma_store2d(const CUtensorMap* m, uint32_t src, int x, int y) {
  asm volatile("cp.async.bulk.tensor.2d.global.shared::cta.bulk_group [%0, {%2, %3}], [%1];" ::"l"(m), "r"(src), "r"(x), "r"(y) : "memory");
}
__device__ __forceinline__ void bulk_load(uint32_t dst, const void* src, uint32_t bytes, uint32_t bar) {
  asm volatile("cp.async.bulk.shared::cluster.global.mbarrier::complete_tx::bytes [%0], [%1], %2, [%3];" ::"r"(dst), "l"(src), "r"(bytes), "r"(bar) : "memory");
}
__device__ __forceinline__ void bulk_commit() { asm volatile("cp.async.bulk.commit_group;" ::: "memory"); }
__device__ __forceinline__ void bulk_wait0() { asm volatile("cp.async.bulk.wait_group 0;" ::: "memory"); }
__device__ __forceinline__ void bulk_wait_read0() { asm volatile("cp.async.bulk.wait_group.read 0;" ::: "memory"); }
__device__ __forceinline__ void prefetch_l2(const void* p) { asm volatile("prefetch.global.L2 [%0];" ::"l"(p) : "memory"); }
__device__ __forceinline__ void touch_l2(const void* p, int lane) { asm volatile("cp.async.cg.shared.global.L2::128B [%0], [%1], 16;" ::"r"(SB + SM_SINK + lane * 16), "l"(p) : "memory"); }
__device__ __forceinline__ void prefetch_map(const CUtensorMap* m) { asm volatile("prefetch.tensormap [%0];" ::"l"(m) : "memory"); }
__device__ __forceinline__ void fence_async_smem() { asm volatile("fence.proxy.async.shared::cta;" ::: "memory"); }
__device__ __forceinline__ void fence_async_global() { asm volatile("fence.proxy.async.global;" ::: "memory"); }
__device__ __forceinline__ void bar_sync(int id, int n) { asm volatile("bar.sync %0, %1;" ::"r"(id), "r"(n) : "memory"); }
__device__ __forceinline__ void wg_fence() { asm volatile("wgmma.fence.sync.aligned;" ::: "memory"); }
__device__ __forceinline__ void wg_commit() { asm volatile("wgmma.commit_group.sync.aligned;" ::: "memory"); }
template <int N> __device__ __forceinline__ void wg_wait() { asm volatile("wgmma.wait_group.sync.aligned %0;" ::"n"(N) : "memory"); }
template <int N> __device__ __forceinline__ void reg_fence(uint32_t* r) {
#pragma unroll
  for (int i = 0; i < N; i++) asm volatile("" : "+r"(r[i])::"memory");
}
template <int N> __device__ __forceinline__ void reg_fence(float* r) {
#pragma unroll
  for (int i = 0; i < N; i++) asm volatile("" : "+f"(r[i])::"memory");
}
__device__ __forceinline__ uint64_t mkdesc(uint32_t addr, uint32_t lbo, uint32_t sbo, uint32_t swz, uint32_t dyn = 0) {
  const uint32_t lo = ((addr >> 4) | ((lbo >> 4) << 16)) + dyn;
  const uint32_t hi = (sbo >> 4) | (swz << 30);
  uint64_t d;
  asm("mov.b64 %0, {%1, %2};" : "=l"(d) : "r"(lo), "r"(hi));
  return d;
}
__device__ __forceinline__ void stsm4(uint32_t addr, uint32_t a, uint32_t b, uint32_t c, uint32_t d) {
  asm volatile("stmatrix.sync.aligned.m8n8.x4.shared.b16 [%0], {%1, %2, %3, %4};" ::"r"(addr), "r"(a), "r"(b), "r"(c), "r"(d) : "memory");
}
__device__ __forceinline__ void ldsm4(uint32_t addr, uint32_t& a, uint32_t& b, uint32_t& c, uint32_t& d) {
  asm volatile("ldmatrix.sync.aligned.m8n8.x4.shared.b16 {%0, %1, %2, %3}, [%4];" : "=r"(a), "=r"(b), "=r"(c), "=r"(d) : "r"(addr) : "memory");
}
__device__ __forceinline__ uint32_t pack2(float lo, float hi) { uint32_t r; asm("cvt.rn.bf16x2.f32 %0, %1, %2;" : "=r"(r) : "f"(hi), "f"(lo)); return r; }
__device__ __forceinline__ uint32_t bsub2(uint32_t a, uint32_t b) { uint32_t r; asm("sub.rn.bf16x2 %0, %1, %2;" : "=r"(r) : "r"(a), "r"(b)); return r; }
__device__ __forceinline__ uint32_t badd2(uint32_t a, uint32_t b) { uint32_t r; asm("add.rn.bf16x2 %0, %1, %2;" : "=r"(r) : "r"(a), "r"(b)); return r; }
__device__ __forceinline__ uint32_t bmul2(uint32_t a, uint32_t b) { uint32_t r; asm("mul.rn.bf16x2 %0, %1, %2;" : "=r"(r) : "r"(a), "r"(b)); return r; }
__device__ __forceinline__ float bf_lo(uint32_t v) { return __uint_as_float(v << 16); }
__device__ __forceinline__ float bf_hi(uint32_t v) { return __uint_as_float(v & 0xffff0000u); }
__device__ __forceinline__ float bf_round(float v) { return bf_lo(pack2(v, 0.f)); }
__device__ __forceinline__ float ex2(float v) { float r; asm("ex2.approx.ftz.f32 %0, %1;" : "=f"(r) : "f"(v)); return r; }
__device__ __forceinline__ float rcp(float v) { float r; asm("rcp.approx.ftz.f32 %0, %1;" : "=f"(r) : "f"(v)); return r; }
__device__ __forceinline__ float sqrt_approx(float v) { float r; asm("sqrt.approx.f32 %0, %1;" : "=f"(r) : "f"(v)); return r; }
__device__ __forceinline__ float4 lds128(uint32_t a) { float4 v; asm volatile("ld.shared.v4.f32 {%0, %1, %2, %3}, [%4];" : "=f"(v.x), "=f"(v.y), "=f"(v.z), "=f"(v.w) : "r"(a) : "memory"); return v; }
__device__ __forceinline__ uint4 lds128u(uint32_t a) { uint4 v; asm volatile("ld.shared.v4.u32 {%0, %1, %2, %3}, [%4];" : "=r"(v.x), "=r"(v.y), "=r"(v.z), "=r"(v.w) : "r"(a) : "memory"); return v; }
__device__ __forceinline__ float2 lds64(uint32_t a) { float2 v; asm volatile("ld.shared.v2.f32 {%0, %1}, [%2];" : "=f"(v.x), "=f"(v.y) : "r"(a) : "memory"); return v; }
__device__ __forceinline__ float lds32(uint32_t a) { float v; asm volatile("ld.shared.f32 %0, [%1];" : "=f"(v) : "r"(a) : "memory"); return v; }
__device__ __forceinline__ void sts32(uint32_t a, float v) { asm volatile("st.shared.f32 [%0], %1;" ::"r"(a), "f"(v) : "memory"); }
__device__ __forceinline__ void sts64(uint32_t a, float x, float y) { asm volatile("st.shared.v2.f32 [%0], {%1, %2};" ::"r"(a), "f"(x), "f"(y) : "memory"); }
__device__ __forceinline__ void sts128(uint32_t a, float x, float y, float z, float w) { asm volatile("st.shared.v4.f32 [%0], {%1, %2, %3, %4};" ::"r"(a), "f"(x), "f"(y), "f"(z), "f"(w) : "memory"); }
__device__ __forceinline__ void sts64u(uint32_t a, uint32_t x, uint32_t y) { asm volatile("st.shared.v2.u32 [%0], {%1, %2};" ::"r"(a), "r"(x), "r"(y) : "memory"); }
__device__ __forceinline__ void sts128u(uint32_t a, uint32_t x, uint32_t y, uint32_t z, uint32_t w) { asm volatile("st.shared.v4.u32 [%0], {%1, %2, %3, %4};" ::"r"(a), "r"(x), "r"(y), "r"(z), "r"(w) : "memory"); }
__device__ __forceinline__ uint4 ldg_nc(const void* p) { uint4 v; asm volatile("ld.global.nc.L1::no_allocate.v4.u32 {%0, %1, %2, %3}, [%4];" : "=r"(v.x), "=r"(v.y), "=r"(v.z), "=r"(v.w) : "l"(p)); return v; }
__device__ __forceinline__ float4 ldg_cg4(const float* p) { float4 v; asm volatile("ld.global.cg.v4.f32 {%0, %1, %2, %3}, [%4];" : "=f"(v.x), "=f"(v.y), "=f"(v.z), "=f"(v.w) : "l"(p) : "memory"); return v; }
__device__ __forceinline__ uint32_t ld_acq(const uint32_t* p) { uint32_t v; asm volatile("ld.acquire.gpu.global.u32 %0, [%1];" : "=r"(v) : "l"(p) : "memory"); return v; }
__device__ __forceinline__ uint32_t ld_acq_cta(uint32_t a) { uint32_t v; asm volatile("ld.acquire.cta.shared.u32 %0, [%1];" : "=r"(v) : "r"(a) : "memory"); return v; }
__device__ __forceinline__ void st_rel_cta(uint32_t a, uint32_t v) { asm volatile("st.release.cta.shared.u32 [%0], %1;" ::"r"(a), "r"(v) : "memory"); }
__device__ __forceinline__ unsigned long long ld_rlx64(const unsigned long long* p) { unsigned long long v; asm volatile("ld.relaxed.gpu.global.u64 %0, [%1];" : "=l"(v) : "l"(p) : "memory"); return v; }
__device__ __forceinline__ void st_rlx64(unsigned long long* p, unsigned long long v) { asm volatile("st.relaxed.gpu.global.u64 [%0], %1;" ::"l"(p), "l"(v) : "memory"); }
__device__ __forceinline__ uint4 ld_rlx128(const void* p) {
  uint4 v;
  asm volatile("{ .reg .b128 t; .reg .b64 a, b; ld.relaxed.gpu.global.b128 t, [%4]; mov.b128 {a, b}, t; mov.b64 {%0, %1}, a; mov.b64 {%2, %3}, b; }"
               : "=r"(v.x), "=r"(v.y), "=r"(v.z), "=r"(v.w) : "l"(p) : "memory");
  return v;
}
__device__ __forceinline__ void st_rlx128(void* p, uint32_t x, uint32_t y, uint32_t z, uint32_t w) {
  asm volatile("{ .reg .b128 t; .reg .b64 a, b; mov.b64 a, {%1, %2}; mov.b64 b, {%3, %4}; mov.b128 t, {a, b}; st.relaxed.gpu.global.b128 [%0], t; }"
               ::"l"(p), "r"(x), "r"(y), "r"(z), "r"(w) : "memory");
}
__device__ __forceinline__ void stg128(void* p, uint32_t x, uint32_t y, uint32_t z, uint32_t w) { asm volatile("st.global.v4.u32 [%0], {%1, %2, %3, %4};" ::"l"(p), "r"(x), "r"(y), "r"(z), "r"(w) : "memory"); }
__device__ __forceinline__ void st_rlx(void* p, uint32_t v) { asm volatile("st.relaxed.gpu.global.u32 [%0], %1;" ::"l"(p), "r"(v) : "memory"); }
__device__ __forceinline__ uint32_t lop_select(uint32_t a, uint32_t b, uint32_t m) { uint32_t r; asm("lop3.b32 %0, %1, %2, %3, 0xd8;" : "=r"(r) : "r"(a), "r"(b), "r"(m)); return r; }
__device__ __forceinline__ float unmark(uint32_t v) { return __uint_as_float(v & ~1u); }
__device__ __forceinline__ uint32_t mark(uint32_t v, uint32_t par) { return (v & ~1u) | par; }
__device__ __forceinline__ float tanh_approx(float v) { float r; asm("tanh.approx.f32 %0, %1;" : "=f"(r) : "f"(v)); return r; }
__device__ __forceinline__ void flag_rel(uint32_t* p, uint32_t v) { asm volatile("red.release.gpu.global.max.u32 [%0], %1;" ::"l"(p), "r"(v) : "memory"); }
__device__ __forceinline__ void red1(float* p, float a) { asm volatile("red.global.add.f32 [%0], %1;" ::"l"(p), "f"(a) : "memory"); }
__device__ __forceinline__ void red_inc(uint32_t* p) { asm volatile("red.relaxed.gpu.global.add.u32 [%0], 1;" ::"l"(p) : "memory"); }
__device__ __forceinline__ void red_rel(uint32_t* p) { asm volatile("red.release.gpu.global.add.u32 [%0], 1;" ::"l"(p) : "memory"); }
__device__ __forceinline__ void red4(float* p, float a, float b, float c, float d) { asm volatile("red.global.add.v4.f32 [%0], {%1, %2, %3, %4};" ::"l"(p), "f"(a), "f"(b), "f"(c), "f"(d) : "memory"); }
constexpr int SPIN_MAX = 100000;
__device__ __forceinline__ uint32_t ld_rlx(const uint32_t* p) { uint32_t v; asm volatile("ld.relaxed.gpu.global.u32 %0, [%1];" : "=r"(v) : "l"(p) : "memory"); return v; }
template <int NS = 0> __device__ __forceinline__ void wait_hint(const uint32_t* p, uint32_t target) {
#pragma unroll 1
  for (int i = 0; i < SPIN_MAX; i++) { if ((int)(ld_rlx(p) - target) >= 0) break; if (NS) __nanosleep(NS); }
}
template <int NS> __device__ __forceinline__ void wait_cnt(const uint32_t* p, uint32_t target) {
#pragma unroll 1
  for (int i = 0; i < SPIN_MAX; i++) { if ((int)(ld_rlx(p) - target) >= 0) break; if (NS) __nanosleep(NS); }
  (void)ld_acq(p);
}
template <int NS> __device__ __forceinline__ unsigned long long wait_tag(const unsigned long long* p, uint32_t tag) {
  unsigned long long v = 0;
#pragma unroll 1
  for (int i = 0; i < SPIN_MAX; i++) { v = ld_rlx64(p); if ((uint32_t)(v >> 32) == tag) break; if (NS) __nanosleep(NS); }
  return v;
}
__device__ __forceinline__ float silu_f(float v) { return v * rcp(1.f + ex2(-1.4426950408889634f * v)); }

__device__ __forceinline__ void wgmma_n8_ss_ta1_tb0(float* d, uint64_t da, uint64_t db, bool accumulate) {
  if (accumulate) {
    asm volatile("{\n.reg .pred p;\nsetp.ne.b32 p, 1, 0;\n"
      "wgmma.mma_async.sync.aligned.m64n8k16.f32.bf16.bf16 "
      "{%0, %1, %2, %3}, "
      "%4, %5, p, 1, 1, 1, 0;\n}\n"
      : "+f"(d[0]), "+f"(d[1]), "+f"(d[2]), "+f"(d[3])
      : "l"(da), "l"(db));
  } else {
    asm volatile("{\n.reg .pred p;\nsetp.ne.b32 p, 0, 0;\n"
      "wgmma.mma_async.sync.aligned.m64n8k16.f32.bf16.bf16 "
      "{%0, %1, %2, %3}, "
      "%4, %5, p, 1, 1, 1, 0;\n}\n"
      : "=f"(d[0]), "=f"(d[1]), "=f"(d[2]), "=f"(d[3])
      : "l"(da), "l"(db));
  }
}
__device__ __forceinline__ void wgmma_n8_ss_ta1_tb1(float* d, uint64_t da, uint64_t db, bool accumulate) {
  if (accumulate) {
    asm volatile("{\n.reg .pred p;\nsetp.ne.b32 p, 1, 0;\n"
      "wgmma.mma_async.sync.aligned.m64n8k16.f32.bf16.bf16 "
      "{%0, %1, %2, %3}, "
      "%4, %5, p, 1, 1, 1, 1;\n}\n"
      : "+f"(d[0]), "+f"(d[1]), "+f"(d[2]), "+f"(d[3])
      : "l"(da), "l"(db));
  } else {
    asm volatile("{\n.reg .pred p;\nsetp.ne.b32 p, 0, 0;\n"
      "wgmma.mma_async.sync.aligned.m64n8k16.f32.bf16.bf16 "
      "{%0, %1, %2, %3}, "
      "%4, %5, p, 1, 1, 1, 1;\n}\n"
      : "=f"(d[0]), "=f"(d[1]), "=f"(d[2]), "=f"(d[3])
      : "l"(da), "l"(db));
  }
}
__device__ __forceinline__ void wgmma_n32_rs_ta0_tb1(float* d, uint32_t a0, uint32_t a1, uint32_t a2, uint32_t a3, uint64_t db, bool accumulate) {
  if (accumulate) {
    asm volatile("{\n.reg .pred p;\nsetp.ne.b32 p, 1, 0;\n"
      "wgmma.mma_async.sync.aligned.m64n32k16.f32.bf16.bf16 "
      "{%0, %1, %2, %3, %4, %5, %6, %7, %8, %9, %10, %11, %12, %13, %14, %15}, "
      "{%16, %17, %18, %19}, %20, p, 1, 1, 1;\n}\n"
      : "+f"(d[0]), "+f"(d[1]), "+f"(d[2]), "+f"(d[3]), "+f"(d[4]), "+f"(d[5]), "+f"(d[6]), "+f"(d[7]), "+f"(d[8]), "+f"(d[9]), "+f"(d[10]), "+f"(d[11]), "+f"(d[12]), "+f"(d[13]), "+f"(d[14]), "+f"(d[15])
      : "r"(a0), "r"(a1), "r"(a2), "r"(a3), "l"(db));
  } else {
    asm volatile("{\n.reg .pred p;\nsetp.ne.b32 p, 0, 0;\n"
      "wgmma.mma_async.sync.aligned.m64n32k16.f32.bf16.bf16 "
      "{%0, %1, %2, %3, %4, %5, %6, %7, %8, %9, %10, %11, %12, %13, %14, %15}, "
      "{%16, %17, %18, %19}, %20, p, 1, 1, 1;\n}\n"
      : "=f"(d[0]), "=f"(d[1]), "=f"(d[2]), "=f"(d[3]), "=f"(d[4]), "=f"(d[5]), "=f"(d[6]), "=f"(d[7]), "=f"(d[8]), "=f"(d[9]), "=f"(d[10]), "=f"(d[11]), "=f"(d[12]), "=f"(d[13]), "=f"(d[14]), "=f"(d[15])
      : "r"(a0), "r"(a1), "r"(a2), "r"(a3), "l"(db));
  }
}
__device__ __forceinline__ void wgmma_n40_rs_ta0_tb1(float* d, uint32_t a0, uint32_t a1, uint32_t a2, uint32_t a3, uint64_t db, bool accumulate) {
  if (accumulate) {
    asm volatile("{\n.reg .pred p;\nsetp.ne.b32 p, 1, 0;\n"
      "wgmma.mma_async.sync.aligned.m64n40k16.f32.bf16.bf16 "
      "{%0, %1, %2, %3, %4, %5, %6, %7, %8, %9, %10, %11, %12, %13, %14, %15, %16, %17, %18, %19}, "
      "{%20, %21, %22, %23}, %24, p, 1, 1, 1;\n}\n"
      : "+f"(d[0]), "+f"(d[1]), "+f"(d[2]), "+f"(d[3]), "+f"(d[4]), "+f"(d[5]), "+f"(d[6]), "+f"(d[7]), "+f"(d[8]), "+f"(d[9]), "+f"(d[10]), "+f"(d[11]), "+f"(d[12]), "+f"(d[13]), "+f"(d[14]), "+f"(d[15]), "+f"(d[16]), "+f"(d[17]), "+f"(d[18]), "+f"(d[19])
      : "r"(a0), "r"(a1), "r"(a2), "r"(a3), "l"(db));
  } else {
    asm volatile("{\n.reg .pred p;\nsetp.ne.b32 p, 0, 0;\n"
      "wgmma.mma_async.sync.aligned.m64n40k16.f32.bf16.bf16 "
      "{%0, %1, %2, %3, %4, %5, %6, %7, %8, %9, %10, %11, %12, %13, %14, %15, %16, %17, %18, %19}, "
      "{%20, %21, %22, %23}, %24, p, 1, 1, 1;\n}\n"
      : "=f"(d[0]), "=f"(d[1]), "=f"(d[2]), "=f"(d[3]), "=f"(d[4]), "=f"(d[5]), "=f"(d[6]), "=f"(d[7]), "=f"(d[8]), "=f"(d[9]), "=f"(d[10]), "=f"(d[11]), "=f"(d[12]), "=f"(d[13]), "=f"(d[14]), "=f"(d[15]), "=f"(d[16]), "=f"(d[17]), "=f"(d[18]), "=f"(d[19])
      : "r"(a0), "r"(a1), "r"(a2), "r"(a3), "l"(db));
  }
}
__device__ __forceinline__ void wgmma_n40_ss_ta1_tb1(float* d, uint64_t da, uint64_t db, bool accumulate) {
  if (accumulate) {
    asm volatile("{\n.reg .pred p;\nsetp.ne.b32 p, 1, 0;\n"
      "wgmma.mma_async.sync.aligned.m64n40k16.f32.bf16.bf16 "
      "{%0, %1, %2, %3, %4, %5, %6, %7, %8, %9, %10, %11, %12, %13, %14, %15, %16, %17, %18, %19}, "
      "%20, %21, p, 1, 1, 1, 1;\n}\n"
      : "+f"(d[0]), "+f"(d[1]), "+f"(d[2]), "+f"(d[3]), "+f"(d[4]), "+f"(d[5]), "+f"(d[6]), "+f"(d[7]), "+f"(d[8]), "+f"(d[9]), "+f"(d[10]), "+f"(d[11]), "+f"(d[12]), "+f"(d[13]), "+f"(d[14]), "+f"(d[15]), "+f"(d[16]), "+f"(d[17]), "+f"(d[18]), "+f"(d[19])
      : "l"(da), "l"(db));
  } else {
    asm volatile("{\n.reg .pred p;\nsetp.ne.b32 p, 0, 0;\n"
      "wgmma.mma_async.sync.aligned.m64n40k16.f32.bf16.bf16 "
      "{%0, %1, %2, %3, %4, %5, %6, %7, %8, %9, %10, %11, %12, %13, %14, %15, %16, %17, %18, %19}, "
      "%20, %21, p, 1, 1, 1, 1;\n}\n"
      : "=f"(d[0]), "=f"(d[1]), "=f"(d[2]), "=f"(d[3]), "=f"(d[4]), "=f"(d[5]), "=f"(d[6]), "=f"(d[7]), "=f"(d[8]), "=f"(d[9]), "=f"(d[10]), "=f"(d[11]), "=f"(d[12]), "=f"(d[13]), "=f"(d[14]), "=f"(d[15]), "=f"(d[16]), "=f"(d[17]), "=f"(d[18]), "=f"(d[19])
      : "l"(da), "l"(db));
  }
}
__device__ __forceinline__ void wgmma_n128_rs_ta0_tb1(float* d, uint32_t a0, uint32_t a1, uint32_t a2, uint32_t a3, uint64_t db, bool accumulate) {
  if (accumulate) {
    asm volatile("{\n.reg .pred p;\nsetp.ne.b32 p, 1, 0;\n"
      "wgmma.mma_async.sync.aligned.m64n128k16.f32.bf16.bf16 "
      "{%0, %1, %2, %3, %4, %5, %6, %7, %8, %9, %10, %11, %12, %13, %14, %15, %16, %17, %18, %19, %20, %21, %22, %23, %24, %25, %26, %27, %28, %29, %30, %31, %32, %33, %34, %35, %36, %37, %38, %39, %40, %41, %42, %43, %44, %45, %46, %47, %48, %49, %50, %51, %52, %53, %54, %55, %56, %57, %58, %59, %60, %61, %62, %63}, "
      "{%64, %65, %66, %67}, %68, p, 1, 1, 1;\n}\n"
      : "+f"(d[0]), "+f"(d[1]), "+f"(d[2]), "+f"(d[3]), "+f"(d[4]), "+f"(d[5]), "+f"(d[6]), "+f"(d[7]), "+f"(d[8]), "+f"(d[9]), "+f"(d[10]), "+f"(d[11]), "+f"(d[12]), "+f"(d[13]), "+f"(d[14]), "+f"(d[15]), "+f"(d[16]), "+f"(d[17]), "+f"(d[18]), "+f"(d[19]), "+f"(d[20]), "+f"(d[21]), "+f"(d[22]), "+f"(d[23]), "+f"(d[24]), "+f"(d[25]), "+f"(d[26]), "+f"(d[27]), "+f"(d[28]), "+f"(d[29]), "+f"(d[30]), "+f"(d[31]), "+f"(d[32]), "+f"(d[33]), "+f"(d[34]), "+f"(d[35]), "+f"(d[36]), "+f"(d[37]), "+f"(d[38]), "+f"(d[39]), "+f"(d[40]), "+f"(d[41]), "+f"(d[42]), "+f"(d[43]), "+f"(d[44]), "+f"(d[45]), "+f"(d[46]), "+f"(d[47]), "+f"(d[48]), "+f"(d[49]), "+f"(d[50]), "+f"(d[51]), "+f"(d[52]), "+f"(d[53]), "+f"(d[54]), "+f"(d[55]), "+f"(d[56]), "+f"(d[57]), "+f"(d[58]), "+f"(d[59]), "+f"(d[60]), "+f"(d[61]), "+f"(d[62]), "+f"(d[63])
      : "r"(a0), "r"(a1), "r"(a2), "r"(a3), "l"(db));
  } else {
    asm volatile("{\n.reg .pred p;\nsetp.ne.b32 p, 0, 0;\n"
      "wgmma.mma_async.sync.aligned.m64n128k16.f32.bf16.bf16 "
      "{%0, %1, %2, %3, %4, %5, %6, %7, %8, %9, %10, %11, %12, %13, %14, %15, %16, %17, %18, %19, %20, %21, %22, %23, %24, %25, %26, %27, %28, %29, %30, %31, %32, %33, %34, %35, %36, %37, %38, %39, %40, %41, %42, %43, %44, %45, %46, %47, %48, %49, %50, %51, %52, %53, %54, %55, %56, %57, %58, %59, %60, %61, %62, %63}, "
      "{%64, %65, %66, %67}, %68, p, 1, 1, 1;\n}\n"
      : "=f"(d[0]), "=f"(d[1]), "=f"(d[2]), "=f"(d[3]), "=f"(d[4]), "=f"(d[5]), "=f"(d[6]), "=f"(d[7]), "=f"(d[8]), "=f"(d[9]), "=f"(d[10]), "=f"(d[11]), "=f"(d[12]), "=f"(d[13]), "=f"(d[14]), "=f"(d[15]), "=f"(d[16]), "=f"(d[17]), "=f"(d[18]), "=f"(d[19]), "=f"(d[20]), "=f"(d[21]), "=f"(d[22]), "=f"(d[23]), "=f"(d[24]), "=f"(d[25]), "=f"(d[26]), "=f"(d[27]), "=f"(d[28]), "=f"(d[29]), "=f"(d[30]), "=f"(d[31]), "=f"(d[32]), "=f"(d[33]), "=f"(d[34]), "=f"(d[35]), "=f"(d[36]), "=f"(d[37]), "=f"(d[38]), "=f"(d[39]), "=f"(d[40]), "=f"(d[41]), "=f"(d[42]), "=f"(d[43]), "=f"(d[44]), "=f"(d[45]), "=f"(d[46]), "=f"(d[47]), "=f"(d[48]), "=f"(d[49]), "=f"(d[50]), "=f"(d[51]), "=f"(d[52]), "=f"(d[53]), "=f"(d[54]), "=f"(d[55]), "=f"(d[56]), "=f"(d[57]), "=f"(d[58]), "=f"(d[59]), "=f"(d[60]), "=f"(d[61]), "=f"(d[62]), "=f"(d[63])
      : "r"(a0), "r"(a1), "r"(a2), "r"(a3), "l"(db));
  }
}
__device__ __forceinline__ void wgmma_n128_ss_ta0_tb1(float* d, uint64_t da, uint64_t db, bool accumulate) {
  if (accumulate) {
    asm volatile("{\n.reg .pred p;\nsetp.ne.b32 p, 1, 0;\n"
      "wgmma.mma_async.sync.aligned.m64n128k16.f32.bf16.bf16 "
      "{%0, %1, %2, %3, %4, %5, %6, %7, %8, %9, %10, %11, %12, %13, %14, %15, %16, %17, %18, %19, %20, %21, %22, %23, %24, %25, %26, %27, %28, %29, %30, %31, %32, %33, %34, %35, %36, %37, %38, %39, %40, %41, %42, %43, %44, %45, %46, %47, %48, %49, %50, %51, %52, %53, %54, %55, %56, %57, %58, %59, %60, %61, %62, %63}, "
      "%64, %65, p, 1, 1, 0, 1;\n}\n"
      : "+f"(d[0]), "+f"(d[1]), "+f"(d[2]), "+f"(d[3]), "+f"(d[4]), "+f"(d[5]), "+f"(d[6]), "+f"(d[7]), "+f"(d[8]), "+f"(d[9]), "+f"(d[10]), "+f"(d[11]), "+f"(d[12]), "+f"(d[13]), "+f"(d[14]), "+f"(d[15]), "+f"(d[16]), "+f"(d[17]), "+f"(d[18]), "+f"(d[19]), "+f"(d[20]), "+f"(d[21]), "+f"(d[22]), "+f"(d[23]), "+f"(d[24]), "+f"(d[25]), "+f"(d[26]), "+f"(d[27]), "+f"(d[28]), "+f"(d[29]), "+f"(d[30]), "+f"(d[31]), "+f"(d[32]), "+f"(d[33]), "+f"(d[34]), "+f"(d[35]), "+f"(d[36]), "+f"(d[37]), "+f"(d[38]), "+f"(d[39]), "+f"(d[40]), "+f"(d[41]), "+f"(d[42]), "+f"(d[43]), "+f"(d[44]), "+f"(d[45]), "+f"(d[46]), "+f"(d[47]), "+f"(d[48]), "+f"(d[49]), "+f"(d[50]), "+f"(d[51]), "+f"(d[52]), "+f"(d[53]), "+f"(d[54]), "+f"(d[55]), "+f"(d[56]), "+f"(d[57]), "+f"(d[58]), "+f"(d[59]), "+f"(d[60]), "+f"(d[61]), "+f"(d[62]), "+f"(d[63])
      : "l"(da), "l"(db));
  } else {
    asm volatile("{\n.reg .pred p;\nsetp.ne.b32 p, 0, 0;\n"
      "wgmma.mma_async.sync.aligned.m64n128k16.f32.bf16.bf16 "
      "{%0, %1, %2, %3, %4, %5, %6, %7, %8, %9, %10, %11, %12, %13, %14, %15, %16, %17, %18, %19, %20, %21, %22, %23, %24, %25, %26, %27, %28, %29, %30, %31, %32, %33, %34, %35, %36, %37, %38, %39, %40, %41, %42, %43, %44, %45, %46, %47, %48, %49, %50, %51, %52, %53, %54, %55, %56, %57, %58, %59, %60, %61, %62, %63}, "
      "%64, %65, p, 1, 1, 0, 1;\n}\n"
      : "=f"(d[0]), "=f"(d[1]), "=f"(d[2]), "=f"(d[3]), "=f"(d[4]), "=f"(d[5]), "=f"(d[6]), "=f"(d[7]), "=f"(d[8]), "=f"(d[9]), "=f"(d[10]), "=f"(d[11]), "=f"(d[12]), "=f"(d[13]), "=f"(d[14]), "=f"(d[15]), "=f"(d[16]), "=f"(d[17]), "=f"(d[18]), "=f"(d[19]), "=f"(d[20]), "=f"(d[21]), "=f"(d[22]), "=f"(d[23]), "=f"(d[24]), "=f"(d[25]), "=f"(d[26]), "=f"(d[27]), "=f"(d[28]), "=f"(d[29]), "=f"(d[30]), "=f"(d[31]), "=f"(d[32]), "=f"(d[33]), "=f"(d[34]), "=f"(d[35]), "=f"(d[36]), "=f"(d[37]), "=f"(d[38]), "=f"(d[39]), "=f"(d[40]), "=f"(d[41]), "=f"(d[42]), "=f"(d[43]), "=f"(d[44]), "=f"(d[45]), "=f"(d[46]), "=f"(d[47]), "=f"(d[48]), "=f"(d[49]), "=f"(d[50]), "=f"(d[51]), "=f"(d[52]), "=f"(d[53]), "=f"(d[54]), "=f"(d[55]), "=f"(d[56]), "=f"(d[57]), "=f"(d[58]), "=f"(d[59]), "=f"(d[60]), "=f"(d[61]), "=f"(d[62]), "=f"(d[63])
      : "l"(da), "l"(db));
  }
}
__device__ __forceinline__ void wgmma_n256_rs_ta0_tb1(float* d, uint32_t a0, uint32_t a1, uint32_t a2, uint32_t a3, uint64_t db, bool accumulate) {
  if (accumulate) {
    asm volatile("{\n.reg .pred p;\nsetp.ne.b32 p, 1, 0;\n"
      "wgmma.mma_async.sync.aligned.m64n256k16.f32.bf16.bf16 "
      "{%0, %1, %2, %3, %4, %5, %6, %7, %8, %9, %10, %11, %12, %13, %14, %15, %16, %17, %18, %19, %20, %21, %22, %23, %24, %25, %26, %27, %28, %29, %30, %31, %32, %33, %34, %35, %36, %37, %38, %39, %40, %41, %42, %43, %44, %45, %46, %47, %48, %49, %50, %51, %52, %53, %54, %55, %56, %57, %58, %59, %60, %61, %62, %63, %64, %65, %66, %67, %68, %69, %70, %71, %72, %73, %74, %75, %76, %77, %78, %79, %80, %81, %82, %83, %84, %85, %86, %87, %88, %89, %90, %91, %92, %93, %94, %95, %96, %97, %98, %99, %100, %101, %102, %103, %104, %105, %106, %107, %108, %109, %110, %111, %112, %113, %114, %115, %116, %117, %118, %119, %120, %121, %122, %123, %124, %125, %126, %127}, "
      "{%128, %129, %130, %131}, %132, p, 1, 1, 1;\n}\n"
      : "+f"(d[0]), "+f"(d[1]), "+f"(d[2]), "+f"(d[3]), "+f"(d[4]), "+f"(d[5]), "+f"(d[6]), "+f"(d[7]), "+f"(d[8]), "+f"(d[9]), "+f"(d[10]), "+f"(d[11]), "+f"(d[12]), "+f"(d[13]), "+f"(d[14]), "+f"(d[15]), "+f"(d[16]), "+f"(d[17]), "+f"(d[18]), "+f"(d[19]), "+f"(d[20]), "+f"(d[21]), "+f"(d[22]), "+f"(d[23]), "+f"(d[24]), "+f"(d[25]), "+f"(d[26]), "+f"(d[27]), "+f"(d[28]), "+f"(d[29]), "+f"(d[30]), "+f"(d[31]), "+f"(d[32]), "+f"(d[33]), "+f"(d[34]), "+f"(d[35]), "+f"(d[36]), "+f"(d[37]), "+f"(d[38]), "+f"(d[39]), "+f"(d[40]), "+f"(d[41]), "+f"(d[42]), "+f"(d[43]), "+f"(d[44]), "+f"(d[45]), "+f"(d[46]), "+f"(d[47]), "+f"(d[48]), "+f"(d[49]), "+f"(d[50]), "+f"(d[51]), "+f"(d[52]), "+f"(d[53]), "+f"(d[54]), "+f"(d[55]), "+f"(d[56]), "+f"(d[57]), "+f"(d[58]), "+f"(d[59]), "+f"(d[60]), "+f"(d[61]), "+f"(d[62]), "+f"(d[63]), "+f"(d[64]), "+f"(d[65]), "+f"(d[66]), "+f"(d[67]), "+f"(d[68]), "+f"(d[69]), "+f"(d[70]), "+f"(d[71]), "+f"(d[72]), "+f"(d[73]), "+f"(d[74]), "+f"(d[75]), "+f"(d[76]), "+f"(d[77]), "+f"(d[78]), "+f"(d[79]), "+f"(d[80]), "+f"(d[81]), "+f"(d[82]), "+f"(d[83]), "+f"(d[84]), "+f"(d[85]), "+f"(d[86]), "+f"(d[87]), "+f"(d[88]), "+f"(d[89]), "+f"(d[90]), "+f"(d[91]), "+f"(d[92]), "+f"(d[93]), "+f"(d[94]), "+f"(d[95]), "+f"(d[96]), "+f"(d[97]), "+f"(d[98]), "+f"(d[99]), "+f"(d[100]), "+f"(d[101]), "+f"(d[102]), "+f"(d[103]), "+f"(d[104]), "+f"(d[105]), "+f"(d[106]), "+f"(d[107]), "+f"(d[108]), "+f"(d[109]), "+f"(d[110]), "+f"(d[111]), "+f"(d[112]), "+f"(d[113]), "+f"(d[114]), "+f"(d[115]), "+f"(d[116]), "+f"(d[117]), "+f"(d[118]), "+f"(d[119]), "+f"(d[120]), "+f"(d[121]), "+f"(d[122]), "+f"(d[123]), "+f"(d[124]), "+f"(d[125]), "+f"(d[126]), "+f"(d[127])
      : "r"(a0), "r"(a1), "r"(a2), "r"(a3), "l"(db));
  } else {
    asm volatile("{\n.reg .pred p;\nsetp.ne.b32 p, 0, 0;\n"
      "wgmma.mma_async.sync.aligned.m64n256k16.f32.bf16.bf16 "
      "{%0, %1, %2, %3, %4, %5, %6, %7, %8, %9, %10, %11, %12, %13, %14, %15, %16, %17, %18, %19, %20, %21, %22, %23, %24, %25, %26, %27, %28, %29, %30, %31, %32, %33, %34, %35, %36, %37, %38, %39, %40, %41, %42, %43, %44, %45, %46, %47, %48, %49, %50, %51, %52, %53, %54, %55, %56, %57, %58, %59, %60, %61, %62, %63, %64, %65, %66, %67, %68, %69, %70, %71, %72, %73, %74, %75, %76, %77, %78, %79, %80, %81, %82, %83, %84, %85, %86, %87, %88, %89, %90, %91, %92, %93, %94, %95, %96, %97, %98, %99, %100, %101, %102, %103, %104, %105, %106, %107, %108, %109, %110, %111, %112, %113, %114, %115, %116, %117, %118, %119, %120, %121, %122, %123, %124, %125, %126, %127}, "
      "{%128, %129, %130, %131}, %132, p, 1, 1, 1;\n}\n"
      : "=f"(d[0]), "=f"(d[1]), "=f"(d[2]), "=f"(d[3]), "=f"(d[4]), "=f"(d[5]), "=f"(d[6]), "=f"(d[7]), "=f"(d[8]), "=f"(d[9]), "=f"(d[10]), "=f"(d[11]), "=f"(d[12]), "=f"(d[13]), "=f"(d[14]), "=f"(d[15]), "=f"(d[16]), "=f"(d[17]), "=f"(d[18]), "=f"(d[19]), "=f"(d[20]), "=f"(d[21]), "=f"(d[22]), "=f"(d[23]), "=f"(d[24]), "=f"(d[25]), "=f"(d[26]), "=f"(d[27]), "=f"(d[28]), "=f"(d[29]), "=f"(d[30]), "=f"(d[31]), "=f"(d[32]), "=f"(d[33]), "=f"(d[34]), "=f"(d[35]), "=f"(d[36]), "=f"(d[37]), "=f"(d[38]), "=f"(d[39]), "=f"(d[40]), "=f"(d[41]), "=f"(d[42]), "=f"(d[43]), "=f"(d[44]), "=f"(d[45]), "=f"(d[46]), "=f"(d[47]), "=f"(d[48]), "=f"(d[49]), "=f"(d[50]), "=f"(d[51]), "=f"(d[52]), "=f"(d[53]), "=f"(d[54]), "=f"(d[55]), "=f"(d[56]), "=f"(d[57]), "=f"(d[58]), "=f"(d[59]), "=f"(d[60]), "=f"(d[61]), "=f"(d[62]), "=f"(d[63]), "=f"(d[64]), "=f"(d[65]), "=f"(d[66]), "=f"(d[67]), "=f"(d[68]), "=f"(d[69]), "=f"(d[70]), "=f"(d[71]), "=f"(d[72]), "=f"(d[73]), "=f"(d[74]), "=f"(d[75]), "=f"(d[76]), "=f"(d[77]), "=f"(d[78]), "=f"(d[79]), "=f"(d[80]), "=f"(d[81]), "=f"(d[82]), "=f"(d[83]), "=f"(d[84]), "=f"(d[85]), "=f"(d[86]), "=f"(d[87]), "=f"(d[88]), "=f"(d[89]), "=f"(d[90]), "=f"(d[91]), "=f"(d[92]), "=f"(d[93]), "=f"(d[94]), "=f"(d[95]), "=f"(d[96]), "=f"(d[97]), "=f"(d[98]), "=f"(d[99]), "=f"(d[100]), "=f"(d[101]), "=f"(d[102]), "=f"(d[103]), "=f"(d[104]), "=f"(d[105]), "=f"(d[106]), "=f"(d[107]), "=f"(d[108]), "=f"(d[109]), "=f"(d[110]), "=f"(d[111]), "=f"(d[112]), "=f"(d[113]), "=f"(d[114]), "=f"(d[115]), "=f"(d[116]), "=f"(d[117]), "=f"(d[118]), "=f"(d[119]), "=f"(d[120]), "=f"(d[121]), "=f"(d[122]), "=f"(d[123]), "=f"(d[124]), "=f"(d[125]), "=f"(d[126]), "=f"(d[127])
      : "r"(a0), "r"(a1), "r"(a2), "r"(a3), "l"(db));
  }
}
__device__ __forceinline__ void wgmma_n256_ss_ta0_tb1(float* d, uint64_t da, uint64_t db, bool accumulate) {
  if (accumulate) {
    asm volatile("{\n.reg .pred p;\nsetp.ne.b32 p, 1, 0;\n"
      "wgmma.mma_async.sync.aligned.m64n256k16.f32.bf16.bf16 "
      "{%0, %1, %2, %3, %4, %5, %6, %7, %8, %9, %10, %11, %12, %13, %14, %15, %16, %17, %18, %19, %20, %21, %22, %23, %24, %25, %26, %27, %28, %29, %30, %31, %32, %33, %34, %35, %36, %37, %38, %39, %40, %41, %42, %43, %44, %45, %46, %47, %48, %49, %50, %51, %52, %53, %54, %55, %56, %57, %58, %59, %60, %61, %62, %63, %64, %65, %66, %67, %68, %69, %70, %71, %72, %73, %74, %75, %76, %77, %78, %79, %80, %81, %82, %83, %84, %85, %86, %87, %88, %89, %90, %91, %92, %93, %94, %95, %96, %97, %98, %99, %100, %101, %102, %103, %104, %105, %106, %107, %108, %109, %110, %111, %112, %113, %114, %115, %116, %117, %118, %119, %120, %121, %122, %123, %124, %125, %126, %127}, "
      "%128, %129, p, 1, 1, 0, 1;\n}\n"
      : "+f"(d[0]), "+f"(d[1]), "+f"(d[2]), "+f"(d[3]), "+f"(d[4]), "+f"(d[5]), "+f"(d[6]), "+f"(d[7]), "+f"(d[8]), "+f"(d[9]), "+f"(d[10]), "+f"(d[11]), "+f"(d[12]), "+f"(d[13]), "+f"(d[14]), "+f"(d[15]), "+f"(d[16]), "+f"(d[17]), "+f"(d[18]), "+f"(d[19]), "+f"(d[20]), "+f"(d[21]), "+f"(d[22]), "+f"(d[23]), "+f"(d[24]), "+f"(d[25]), "+f"(d[26]), "+f"(d[27]), "+f"(d[28]), "+f"(d[29]), "+f"(d[30]), "+f"(d[31]), "+f"(d[32]), "+f"(d[33]), "+f"(d[34]), "+f"(d[35]), "+f"(d[36]), "+f"(d[37]), "+f"(d[38]), "+f"(d[39]), "+f"(d[40]), "+f"(d[41]), "+f"(d[42]), "+f"(d[43]), "+f"(d[44]), "+f"(d[45]), "+f"(d[46]), "+f"(d[47]), "+f"(d[48]), "+f"(d[49]), "+f"(d[50]), "+f"(d[51]), "+f"(d[52]), "+f"(d[53]), "+f"(d[54]), "+f"(d[55]), "+f"(d[56]), "+f"(d[57]), "+f"(d[58]), "+f"(d[59]), "+f"(d[60]), "+f"(d[61]), "+f"(d[62]), "+f"(d[63]), "+f"(d[64]), "+f"(d[65]), "+f"(d[66]), "+f"(d[67]), "+f"(d[68]), "+f"(d[69]), "+f"(d[70]), "+f"(d[71]), "+f"(d[72]), "+f"(d[73]), "+f"(d[74]), "+f"(d[75]), "+f"(d[76]), "+f"(d[77]), "+f"(d[78]), "+f"(d[79]), "+f"(d[80]), "+f"(d[81]), "+f"(d[82]), "+f"(d[83]), "+f"(d[84]), "+f"(d[85]), "+f"(d[86]), "+f"(d[87]), "+f"(d[88]), "+f"(d[89]), "+f"(d[90]), "+f"(d[91]), "+f"(d[92]), "+f"(d[93]), "+f"(d[94]), "+f"(d[95]), "+f"(d[96]), "+f"(d[97]), "+f"(d[98]), "+f"(d[99]), "+f"(d[100]), "+f"(d[101]), "+f"(d[102]), "+f"(d[103]), "+f"(d[104]), "+f"(d[105]), "+f"(d[106]), "+f"(d[107]), "+f"(d[108]), "+f"(d[109]), "+f"(d[110]), "+f"(d[111]), "+f"(d[112]), "+f"(d[113]), "+f"(d[114]), "+f"(d[115]), "+f"(d[116]), "+f"(d[117]), "+f"(d[118]), "+f"(d[119]), "+f"(d[120]), "+f"(d[121]), "+f"(d[122]), "+f"(d[123]), "+f"(d[124]), "+f"(d[125]), "+f"(d[126]), "+f"(d[127])
      : "l"(da), "l"(db));
  } else {
    asm volatile("{\n.reg .pred p;\nsetp.ne.b32 p, 0, 0;\n"
      "wgmma.mma_async.sync.aligned.m64n256k16.f32.bf16.bf16 "
      "{%0, %1, %2, %3, %4, %5, %6, %7, %8, %9, %10, %11, %12, %13, %14, %15, %16, %17, %18, %19, %20, %21, %22, %23, %24, %25, %26, %27, %28, %29, %30, %31, %32, %33, %34, %35, %36, %37, %38, %39, %40, %41, %42, %43, %44, %45, %46, %47, %48, %49, %50, %51, %52, %53, %54, %55, %56, %57, %58, %59, %60, %61, %62, %63, %64, %65, %66, %67, %68, %69, %70, %71, %72, %73, %74, %75, %76, %77, %78, %79, %80, %81, %82, %83, %84, %85, %86, %87, %88, %89, %90, %91, %92, %93, %94, %95, %96, %97, %98, %99, %100, %101, %102, %103, %104, %105, %106, %107, %108, %109, %110, %111, %112, %113, %114, %115, %116, %117, %118, %119, %120, %121, %122, %123, %124, %125, %126, %127}, "
      "%128, %129, p, 1, 1, 0, 1;\n}\n"
      : "=f"(d[0]), "=f"(d[1]), "=f"(d[2]), "=f"(d[3]), "=f"(d[4]), "=f"(d[5]), "=f"(d[6]), "=f"(d[7]), "=f"(d[8]), "=f"(d[9]), "=f"(d[10]), "=f"(d[11]), "=f"(d[12]), "=f"(d[13]), "=f"(d[14]), "=f"(d[15]), "=f"(d[16]), "=f"(d[17]), "=f"(d[18]), "=f"(d[19]), "=f"(d[20]), "=f"(d[21]), "=f"(d[22]), "=f"(d[23]), "=f"(d[24]), "=f"(d[25]), "=f"(d[26]), "=f"(d[27]), "=f"(d[28]), "=f"(d[29]), "=f"(d[30]), "=f"(d[31]), "=f"(d[32]), "=f"(d[33]), "=f"(d[34]), "=f"(d[35]), "=f"(d[36]), "=f"(d[37]), "=f"(d[38]), "=f"(d[39]), "=f"(d[40]), "=f"(d[41]), "=f"(d[42]), "=f"(d[43]), "=f"(d[44]), "=f"(d[45]), "=f"(d[46]), "=f"(d[47]), "=f"(d[48]), "=f"(d[49]), "=f"(d[50]), "=f"(d[51]), "=f"(d[52]), "=f"(d[53]), "=f"(d[54]), "=f"(d[55]), "=f"(d[56]), "=f"(d[57]), "=f"(d[58]), "=f"(d[59]), "=f"(d[60]), "=f"(d[61]), "=f"(d[62]), "=f"(d[63]), "=f"(d[64]), "=f"(d[65]), "=f"(d[66]), "=f"(d[67]), "=f"(d[68]), "=f"(d[69]), "=f"(d[70]), "=f"(d[71]), "=f"(d[72]), "=f"(d[73]), "=f"(d[74]), "=f"(d[75]), "=f"(d[76]), "=f"(d[77]), "=f"(d[78]), "=f"(d[79]), "=f"(d[80]), "=f"(d[81]), "=f"(d[82]), "=f"(d[83]), "=f"(d[84]), "=f"(d[85]), "=f"(d[86]), "=f"(d[87]), "=f"(d[88]), "=f"(d[89]), "=f"(d[90]), "=f"(d[91]), "=f"(d[92]), "=f"(d[93]), "=f"(d[94]), "=f"(d[95]), "=f"(d[96]), "=f"(d[97]), "=f"(d[98]), "=f"(d[99]), "=f"(d[100]), "=f"(d[101]), "=f"(d[102]), "=f"(d[103]), "=f"(d[104]), "=f"(d[105]), "=f"(d[106]), "=f"(d[107]), "=f"(d[108]), "=f"(d[109]), "=f"(d[110]), "=f"(d[111]), "=f"(d[112]), "=f"(d[113]), "=f"(d[114]), "=f"(d[115]), "=f"(d[116]), "=f"(d[117]), "=f"(d[118]), "=f"(d[119]), "=f"(d[120]), "=f"(d[121]), "=f"(d[122]), "=f"(d[123]), "=f"(d[124]), "=f"(d[125]), "=f"(d[126]), "=f"(d[127])
      : "l"(da), "l"(db));
  }
}
__device__ __forceinline__ void wgmma_n256_ssp_ta0_tb1(float* d, uint64_t da, uint64_t db, int accumulate) {
    asm volatile("{\n.reg .pred p;\nsetp.ne.b32 p, %130, 0;\n"
      "wgmma.mma_async.sync.aligned.m64n256k16.f32.bf16.bf16 "
      "{%0, %1, %2, %3, %4, %5, %6, %7, %8, %9, %10, %11, %12, %13, %14, %15, %16, %17, %18, %19, %20, %21, %22, %23, %24, %25, %26, %27, %28, %29, %30, %31, %32, %33, %34, %35, %36, %37, %38, %39, %40, %41, %42, %43, %44, %45, %46, %47, %48, %49, %50, %51, %52, %53, %54, %55, %56, %57, %58, %59, %60, %61, %62, %63, %64, %65, %66, %67, %68, %69, %70, %71, %72, %73, %74, %75, %76, %77, %78, %79, %80, %81, %82, %83, %84, %85, %86, %87, %88, %89, %90, %91, %92, %93, %94, %95, %96, %97, %98, %99, %100, %101, %102, %103, %104, %105, %106, %107, %108, %109, %110, %111, %112, %113, %114, %115, %116, %117, %118, %119, %120, %121, %122, %123, %124, %125, %126, %127}, "
      "%128, %129, p, 1, 1, 0, 1;\n}\n"
      : "+f"(d[0]), "+f"(d[1]), "+f"(d[2]), "+f"(d[3]), "+f"(d[4]), "+f"(d[5]), "+f"(d[6]), "+f"(d[7]), "+f"(d[8]), "+f"(d[9]), "+f"(d[10]), "+f"(d[11]), "+f"(d[12]), "+f"(d[13]), "+f"(d[14]), "+f"(d[15]), "+f"(d[16]), "+f"(d[17]), "+f"(d[18]), "+f"(d[19]), "+f"(d[20]), "+f"(d[21]), "+f"(d[22]), "+f"(d[23]), "+f"(d[24]), "+f"(d[25]), "+f"(d[26]), "+f"(d[27]), "+f"(d[28]), "+f"(d[29]), "+f"(d[30]), "+f"(d[31]), "+f"(d[32]), "+f"(d[33]), "+f"(d[34]), "+f"(d[35]), "+f"(d[36]), "+f"(d[37]), "+f"(d[38]), "+f"(d[39]), "+f"(d[40]), "+f"(d[41]), "+f"(d[42]), "+f"(d[43]), "+f"(d[44]), "+f"(d[45]), "+f"(d[46]), "+f"(d[47]), "+f"(d[48]), "+f"(d[49]), "+f"(d[50]), "+f"(d[51]), "+f"(d[52]), "+f"(d[53]), "+f"(d[54]), "+f"(d[55]), "+f"(d[56]), "+f"(d[57]), "+f"(d[58]), "+f"(d[59]), "+f"(d[60]), "+f"(d[61]), "+f"(d[62]), "+f"(d[63]), "+f"(d[64]), "+f"(d[65]), "+f"(d[66]), "+f"(d[67]), "+f"(d[68]), "+f"(d[69]), "+f"(d[70]), "+f"(d[71]), "+f"(d[72]), "+f"(d[73]), "+f"(d[74]), "+f"(d[75]), "+f"(d[76]), "+f"(d[77]), "+f"(d[78]), "+f"(d[79]), "+f"(d[80]), "+f"(d[81]), "+f"(d[82]), "+f"(d[83]), "+f"(d[84]), "+f"(d[85]), "+f"(d[86]), "+f"(d[87]), "+f"(d[88]), "+f"(d[89]), "+f"(d[90]), "+f"(d[91]), "+f"(d[92]), "+f"(d[93]), "+f"(d[94]), "+f"(d[95]), "+f"(d[96]), "+f"(d[97]), "+f"(d[98]), "+f"(d[99]), "+f"(d[100]), "+f"(d[101]), "+f"(d[102]), "+f"(d[103]), "+f"(d[104]), "+f"(d[105]), "+f"(d[106]), "+f"(d[107]), "+f"(d[108]), "+f"(d[109]), "+f"(d[110]), "+f"(d[111]), "+f"(d[112]), "+f"(d[113]), "+f"(d[114]), "+f"(d[115]), "+f"(d[116]), "+f"(d[117]), "+f"(d[118]), "+f"(d[119]), "+f"(d[120]), "+f"(d[121]), "+f"(d[122]), "+f"(d[123]), "+f"(d[124]), "+f"(d[125]), "+f"(d[126]), "+f"(d[127])
      : "l"(da), "l"(db), "r"(accumulate));
}

template <int N> __device__ __forceinline__ void quad_sum(float* m) {
#pragma unroll
  for (int o = 1; o <= 2; o <<= 1) {
    float t[N];
#pragma unroll
    for (int i = 0; i < N; i++) t[i] = __shfl_xor_sync(~0u, m[i], o);
#pragma unroll
    for (int i = 0; i < N; i++) m[i] += t[i];
  }
}
__device__ __forceinline__ bool softmax_unsafe(const uint32_t* t, float l0, float l1) {
  const float m0 = fmaxf(bf_lo(t[0]) + bf_hi(t[0]), bf_lo(t[2]) + bf_hi(t[2])), m1 = fmaxf(bf_lo(t[1]) + bf_hi(t[1]), bf_lo(t[3]) + bf_hi(t[3]));
  return __any_sync(~0u, !(m0 * l0 < 2500.f) | !(m1 * l1 < 2500.f));
}
__device__ __forceinline__ void softmax_shift(float* p, float c0, float c1) {
#pragma unroll 1
  for (int it = 0; it < 8; it++) {
    float mx = p[0], mn = p[0];
#pragma unroll
    for (int j = 1; j < 8; j++) { mx = fmaxf(mx, p[(j >> 1) * 4 + (j & 1)]); mn = fminf(mn, p[(j >> 1) * 4 + (j & 1)]); }
#pragma unroll
    for (int o = 1; o <= 2; o <<= 1) { mx = fmaxf(mx, __shfl_xor_sync(~0u, mx, o)); mn = fminf(mn, __shfl_xor_sync(~0u, mn, o)); }
    const float half = fminf(0.5f * (mx - mn), 50.f * rcp(it & 1 ? c1 : c0));
    float r[8];
#pragma unroll
    for (int j = 0; j < 8; j++) {
      const float v = p[(j >> 1) * 4 + (j & 1)];
      r[j] = fmaxf(v - mx + half, 0.f) + fminf(v - mn - half, 0.f) + (v - v);
    }
#pragma unroll
    for (int k = 0; k < 7; k++)
#pragma unroll
      for (int j = 0; j < 8; j++) p[(k >> 1) * 16 + (k & 1) * 2 + (j >> 1) * 4 + (j & 1)] = p[((k + 1) >> 1) * 16 + ((k + 1) & 1) * 2 + (j >> 1) * 4 + (j & 1)];
#pragma unroll
    for (int j = 0; j < 8; j++) p[50 + (j >> 1) * 4 + (j & 1)] = r[j];
  }
}
template <int J0 = 0, int J1 = 8> __device__ __forceinline__ void k_exp(const float* p, float c0, float c1, float* e, float* s) {
#pragma unroll
  for (int j = J0; j < J1; j++) {
    e[2 * j] = ex2(p[2 * j] * (j & 1 ? c1 : c0));
    e[2 * j + 1] = ex2(p[2 * j + 1] * (j & 1 ? c1 : c0));
    e[16 + j] = rcp(e[2 * j] * e[2 * j + 1]);
    const float t = e[2 * j] + e[2 * j + 1];
    s[j & 1] = j < 2 ? t : s[j & 1] + t;
    s[2 + (j & 1)] = j < 2 ? e[16 + j] * t : fmaf(e[16 + j], t, s[2 + (j & 1)]);
  }
}
template <int J0 = 0, int J1 = 8> __device__ __forceinline__ void q_exp(const float* p, float c0, float c1, uint32_t* f) {
#pragma unroll
  for (int j = J0; j < J1; j++) {
    const float e0 = ex2(p[2 * j] * (j & 1 ? c1 : c0)), e1 = ex2(p[2 * j + 1] * (j & 1 ? c1 : c0)), r = rcp(e0 * e1);
    f[j] = pack2(e0, e1);
    f[8 + j] = bmul2(f[j], pack2(r, r));
  }
}

#define FMA8(A, U, X)                                                                                        \
  A[0] = fmaf(bf_lo(U.x), X, A[0]); A[1] = fmaf(bf_hi(U.x), X, A[1]); A[2] = fmaf(bf_lo(U.y), X, A[2]); A[3] = fmaf(bf_hi(U.y), X, A[3]); \
  A[4] = fmaf(bf_lo(U.z), X, A[4]); A[5] = fmaf(bf_hi(U.z), X, A[5]); A[6] = fmaf(bf_lo(U.w), X, A[6]); A[7] = fmaf(bf_hi(U.w), X, A[7])

__device__ __forceinline__ uint32_t routed_row(const __nv_bfloat16* x, uint32_t tag, int lane, uint4* xr) {
  uint32_t best = 0, sv = 0;
#pragma unroll 1
  for (int it = 0; it < SPIN_MAX; it++) {
    const uint4 h = ld_rlx128(g_ycnt + 32);
    best = h.x;
    if (__all_sync(~0u, (int)(h.z - tag * NCTA) >= 0)) break;
    __nanosleep(AM_NS);
  }
#pragma unroll 1
  for (int it = 0; it < SPIN_MAX; it++) {
    const int sel = 2047 - (best & 0x7ff);
#pragma unroll
    for (int i = 0; i < 4; i++) xr[i] = ldg_nc(x + (size_t)sel * DM + i * 256 + lane * 8);
    const unsigned long long st = ld_rlx64(g_stat + sel);
    const uint4 b0 = ld_rlx128(g_best + lane * 2), b1 = ld_rlx128(g_best + 64 + lane * 2);
    const uint32_t m = __reduce_max_sync(~0u, max(max(b0.x, b0.z), max(b1.x, b1.z)));
    sv = (uint32_t)st;
    if (__all_sync(~0u, b0.y == tag && b0.w == tag && b1.y == tag && b1.w == tag && m == best && (uint32_t)(st >> 32) == tag)) break;
    best = m;
  }
  const uint32_t m2 = (sv & 0xffff0000u) | (sv >> 16);
  const float rs = rcp(bf_lo(sv));
#pragma unroll
  for (int i = 0; i < 4; i++) {
    const uint32_t d0 = bsub2(xr[i].x, m2), d1 = bsub2(xr[i].y, m2), d2 = bsub2(xr[i].z, m2), d3 = bsub2(xr[i].w, m2);
    xr[i] = make_uint4(pack2(bf_lo(d0) * rs, bf_hi(d0) * rs), pack2(bf_lo(d1) * rs, bf_hi(d1) * rs), pack2(bf_lo(d2) * rs, bf_hi(d2) * rs),
                       pack2(bf_lo(d3) * rs, bf_hi(d3) * rs));
  }
  return best;
}

struct Params {
  const __nv_bfloat16 *x, *wqkv, *wo, *w_r, *w_gate, *w_up, *w_down;
  int by_sm;
};

__global__ void __launch_bounds__(384, 1)
fused_kernel(const __grid_constant__ CUtensorMap mX, const __grid_constant__ CUtensorMap mWkv, const __grid_constant__ CUtensorMap mWq,
             const __grid_constant__ CUtensorMap mWo, const __grid_constant__ CUtensorMap mPhi, const __grid_constant__ CUtensorMap mWp,
             const __grid_constant__ CUtensorMap mOut, const __grid_constant__ CUtensorMap mWc,
             const __grid_constant__ CUtensorMap mG, const __grid_constant__ CUtensorMap mU, const __grid_constant__ CUtensorMap mD,
             const __grid_constant__ CUtensorMap mXs, const __grid_constant__ CUtensorMap mG2, const __grid_constant__ CUtensorMap mU2, const Params P) {
  extern __shared__ __align__(1024) uint8_t smem[];
  if (smem_u32(smem) != SB) return;
  constexpr uint32_t sb = SB, bar = SB + SM_BAR;
  int bid = blockIdx.x;
  if (P.by_sm) {
    uint32_t sm;
    asm volatile("mov.u32 %0, %%smid;" : "=r"(sm));
    const uint32_t tq = (sm - 64) >> 1, q7 = (tq * 37) >> 8;
    const uint32_t gpc = sm < 64 ? (sm >> 1) & 7 : 1 + tq - 7 * q7, idx = (sm < 64 ? sm >> 4 : 4 + q7) * 2 + (sm & 1);
    bid = sm < 120 ? ((PTAB >> (4 * gpc)) & 7) * 16 + idx : sm < 124 ? sm + 8 : sm - 116;
  }
  const int hg = ((bid >> 2) & 3) + 4 * ((bid >> 4) & 1), mb = (bid & 3) + 4 * ((bid >> 5) & 3);
  const int warp = __shfl_sync(~0u, threadIdx.x >> 5, 0);

  if (bid >= NCTA) {
    constexpr uint32_t XV = SM_WPHI, ONES = SM_ZT, BF = bar, BE = bar + 48, BX = bar + 96;
    constexpr int NJ = (DM - GROWS) / 64;
    const int lane = lane_id(), sp = bid - NCTA;
    const uint32_t tag = ld_rlx(g_epoch + bid * 32 + lane) + 1;
    if (warp == 8 && elect_one()) {
#pragma unroll 1
      for (int i = 0; i < 13; i++) mbar_init(bar + 8 * i, i >= 6 && i < 12 ? 8 : 1);
    }
    if (warp == 9) { sts64u(sb + ONES + lane * 8, 0x3f803f80u, 0x3f803f80u); fence_async_smem(); }
    __syncthreads();
    if (warp == 8) {
      if (elect_one()) {
        uint32_t s = 0, ph = 1;
#pragma unroll 1
        for (int job = 0; job < 8; job++) {
          const CUtensorMap* m = job == 0 ? &mWq : sp & 2 ? &mU2 : &mG2;
          const int g0 = job ? (sp & 1) * 28 + job * 4 - 4 : sp * 4;
#pragma unroll 1
          for (int row = job ? GROWS : 0; row < DM; row += 64) {
            mbar_wait(BE + 8 * s, ph);
            mbar_expect_tx(BF + 8 * s, Q_STAGE);
            tma4d(sb + s * Q_STAGE, m, 0, row, g0, 0, BF + 8 * s);
            tma4d(sb + s * Q_STAGE + 16384, m, 0, row, g0 + 2, 0, BF + 8 * s);
            if (++s == 6) { s = 0; ph ^= 1; }
          }
        }
      }
    } else if (warp == 9) {
      uint4 xr[4];
      routed_row(P.x, tag, lane, xr);
#pragma unroll
      for (int i = 0; i < 4; i++) sts128u(sb + XV + i * 512 + lane * 16, xr[i].x, xr[i].y, xr[i].z, xr[i].w);
      fence_async_smem();
      __syncwarp();
      if (lane == 0) mbar_arrive(BX);
    } else if (warp < 8) {
      uint32_t s = 0, ph = 0;
#pragma unroll 1
      for (int job = 0; job < 8; job++) {
        float d[8] = {0.f, 0.f, 0.f, 0.f, 0.f, 0.f, 0.f, 0.f};
        if (job == 1) mbar_wait(BX, 0);
#pragma unroll 1
        for (int i = 0; i < (job ? NJ : 16); i++) {
          mbar_wait(BF + 8 * s, ph);
          wg_fence();
#pragma unroll
          for (int k = 0; k < 8; k++)
            wgmma_n8_ss_ta1_tb0(d + 4 * (k >> 2), mkdesc(sb + k * 2048, 16, 1024, 1, s * (Q_STAGE / 16) + (warp >> 2) * 1024),
                                mkdesc(sb, 16, 128, 0, job ? (XV + GROWS * 2) / 16 + i * 8 + (k & 3) * 2 : ONES / 16), 1);
          wg_commit();
          wg_wait<0>();
          if (lane == 0) mbar_arrive(BE + 8 * s);
          if (++s == 6) { s = 0; ph ^= 1; }
        }
        reg_fence<8>(d);
        float* dst = (job ? g_gp + sp * 1792 + job * 256 - 256 : g_cs + sp * 256) + (warp >> 2) * 128 + (warp & 3) * 16 + (lane >> 2);
        if ((lane & 3) == 0) {
#pragma unroll
          for (int i = 0; i < 4; i++) st_rlx(dst + (i >> 1) * 64 + (i & 1) * 8, mark(__float_as_uint(d[2 * i]), tag & 1));
        }
        __syncwarp();
      }
      if (warp == 0) g_epoch[bid * 32 + lane] = tag;
    }
    return;
  }
#define Q_SLAB(J) ((J) < 8 ? ((J) + 8 - 2 * (hg & 4)) & 15 : 2 * (hg & 4) + 2 * ((J) & 3) + ((J) >> 2 & 1))
#define Q_AOFF(J) ((J) == 8 + (hg & 3) ? SM_X0 : (J) == 12 + (hg & 3) ? SM_X1 : ((J) & 3) * Q_STAGE)
#define Q_LOAD(J)                                                                                            \
  do {                                                                                                       \
    const uint32_t fb_ = bar + B_FULLQ + 8 * ((J) & 3);                                                      \
    const int k_ = Q_SLAB(J) * 64;                                                                           \
    mbar_expect_tx(fb_, Q_STAGE);                                                                            \
    mbar_arrive2(fb_);                                                                                       \
    tma2d(sb + Q_AOFF(J), &mX, k_, mb * 128, fb_);                                                           \
    tma4d(sb + ((J) & 3) * Q_STAGE + 16384, &mWq, 0, k_, hg * 2, 0, fb_);                                    \
  } while (0)
  if (warp >= 8) {
    asm volatile("setmaxnreg.dec.sync.aligned.u32 %0;" ::"n"(REG_H));
    const int lane = lane_id();
    const int f = (warp - 9) & 3;
    const uint32_t ep = ld_rlx(g_epoch + bid * 32 + lane);
    if (f == 3) {
      if (elect_one()) {
        PROF(0); PROFT(32);
#pragma unroll
        for (int j = 0; j < 3; j++) {
          const int s = (j + 2) % 3;
          mbar_init(bar + B_FULLKV + 8 * s, 1);
          mbar_expect_tx(bar + B_FULLKV + 8 * s, KV_STAGE);
          tma2d(sb + s * KV_STAGE, &mX, j * 64, mb * 128, bar + B_FULLKV + 8 * s);
          tma4d(sb + s * KV_STAGE + 16384, &mWkv, 0, j * 64, hg * 2, 1, bar + B_FULLKV + 8 * s);
        }
      }
    } else if (f < 2) {
#pragma unroll
      for (int i = 0; i < 2; i++) {
        const uint4 u = __ldg((const uint4*)P.w_r + (f * 2 + i) * 32 + lane);
        sts128u(sb + SM_XSEL + (f * 2 + i) * 512 + lane * 16, u.x, u.y, u.z, u.w);
      }
    }
    __syncwarp();
    bar_sync(0, 384);
    const uint32_t tag = ep + 1, par = tag & 1;
    const bool ffn = bid < NFFN;
    const int fb = bid, cu = bid >> 1, ch = bid & 1;
#define CS_STORE(SEC, C)                                                                                     \
  _Pragma("unroll") for (int r = 0; r < 3; r++) {                                                            \
    const uint32_t h0 = pack2(C.x, C.y), h1 = pack2(C.z, C.w);                                               \
    sts64u(sb + SM_CST + (SEC) * 1024 + (lane >> 4) * 512 + (lane & 1) * 8 + r * 128 + ((((lane & 15) >> 1) ^ (r + (lane >> 4) * 4)) << 4), h0, h1); \
    C.x -= bf_lo(h0); C.y -= bf_hi(h0); C.z -= bf_lo(h1); C.w -= bf_hi(h1);                                  \
  }
#define BAD4(U) ((U.x ^ par) | (U.y ^ par) | (U.z ^ par) | (U.w ^ par))
    const int n0 = f < 2 ? 0 : 2 * f - 3, ne = FFN_OFF || !ffn ? 3 : f == 3 ? 3 + G8 : 3 + GN;
    const uint32_t fsb = sb + SM_FST + ((f + 1) & 3) * 8192, fbar = bar + B_FST + f * 16, fst = fsb + (lane >> 4) * 2048 + (lane & 15) * 16;
    const CUtensorMap *ma = &mWc, *mc = &mWc;
    int sx = 1024 + cu * 32, sy = ch * 512 + f * 192, sdy = 32;
#define STAGEG(N)                                                                                            \
  do {                                                                                                       \
    if ((N) == 3) { ma = &mG; mc = &mU; sx = fb * 32; sy = f * (GN * 32);  sdy = 0; }                        \
    if ((N) < ne && elect_one()) {                                                                           \
      const uint32_t dst_ = fsb + ((N) & 1) * 4096, b_ = fbar + ((N) & 1) * 8;                               \
      mbar_expect_tx(b_, 4096);                                                                              \
      tma2d(dst_, ma, sx, sy, b_);                                                                           \
      tma2d(dst_ + 2048, mc, sx, sy + sdy, b_);                                                              \
    }                                                                                                        \
    sy += 32 + sdy;                                                                                          \
  } while (0)
    float a[8], gsum = 0.f, usum = 0.f;
    {
      if (f == 3) {
        if (elect_one()) {
          if (XS_EARLY) { mbar_expect_tx(bar + B_XST, 16384); tma3d(sb + SM_XST, &mXs, 0, bid * 16, 0, bar + B_XST); }
          mbar_expect_tx(bar + B_WPHI, 8192);
          tma2d(sb + SM_WPHI, &mPhi, 0, hg * 128, bar + B_WPHI);
          prefetch_map(&mWq); prefetch_map(&mWo); prefetch_map(&mWp); prefetch_map(&mD);
          PROF(31);
        }
        __syncwarp();
      } else {
        if (lane == 0) prefetch_map(f == 0 ? &mWc : f == 1 ? &mG : &mU);
        if (f == 2) ((float2*)g_y[par])[bid * 32 + lane] = make_float2(0.f, 0.f);
      }
      float st[13];
#pragma unroll
      for (int i = 0; i < 13; i++) st[i] = 0.f;
#pragma unroll 1
      for (int i = 0; i < 4; i++) {
        mbar_wait(bar + B_XST + 8 * (i >> 1), 0);
        if (f == 0 && lane == 0 && i == 0) PROF(1);
        const uint4 wu = lds128u(sb + SM_XSEL + i * 512 + lane * 16);
        const float wf[8] = {bf_lo(wu.x), bf_hi(wu.x), bf_lo(wu.y), bf_hi(wu.y), bf_lo(wu.z), bf_hi(wu.z), bf_lo(wu.w), bf_hi(wu.w)};
        st[12] += ((wf[0] + wf[1]) + (wf[2] + wf[3])) + ((wf[4] + wf[5]) + (wf[6] + wf[7]));
#pragma unroll
        for (int r = 0; r < 4; r++) {
          const uint4 u = lds128u(sb + SM_XST + i * 8192 + (4 * f + r) * 512 + lane * 16);
          const float xf[8] = {bf_lo(u.x), bf_hi(u.x), bf_lo(u.y), bf_hi(u.y), bf_lo(u.z), bf_hi(u.z), bf_lo(u.w), bf_hi(u.w)};
#pragma unroll
          for (int k = 0; k < 8; k++) { st[r] += xf[k]; st[4 + r] = fmaf(xf[k], xf[k], st[4 + r]); st[8 + r] = fmaf(xf[k], wf[k], st[8 + r]); }
        }
        if (i >= 2 && f < 3) STAGEG(n0 + i - 2);
      }
      const bool up = lane & 16, up2 = lane & 8;
#pragma unroll
      for (int q = 0; q < 3; q++) {
        const float k0 = up ? st[4 * q + 2] : st[4 * q], k1 = up ? st[4 * q + 3] : st[4 * q + 1];
        const float o0 = up ? st[4 * q] : st[4 * q + 2], o1 = up ? st[4 * q + 1] : st[4 * q + 3];
        const float m0 = k0 + __shfl_xor_sync(~0u, o0, 16), m1 = k1 + __shfl_xor_sync(~0u, o1, 16);
        a[q] = (up2 ? m1 : m0) + __shfl_xor_sync(~0u, up2 ? m0 : m1, 8);
      }
      a[3] = st[12] + __shfl_xor_sync(~0u, st[12], 16);
      a[3] += __shfl_xor_sync(~0u, a[3], 8);
#pragma unroll
      for (int o = 4; o; o >>= 1)
#pragma unroll
        for (int q = 0; q < 4; q++) a[q] += __shfl_xor_sync(~0u, a[q], o);
      if ((lane & 7) == 0) sts128(sb + SM_ROWS + (4 * f + (lane >> 3)) * 16, a[0], a[1], a[2], a[3]);
      if (f < 3) asm volatile("bar.arrive 7, 128;" ::: "memory");
    }
    if (f == 3) {
      bar_sync(7, 128);
      const int row = bid * 16 + (lane & 15);
      const float4 v = lds128(sb + SM_ROWS + (lane & 15) * 16);
      const float mf = v.x * (1.f / DM), mean = bf_round(mf), var = fmaxf(fmaf(-mf, mf, v.y * (1.f / DM)), 0.f);
      const float sd = bf_round(sqrt_approx(bf_round(bf_round(var) + 1e-5f)));
      const uint32_t rb = pack2(fmaf(-mean, v.w, v.z) * rcp(sd), 0.f) & 0xffffu, ord = (rb & 0x8000u) ? (~rb & 0xffffu) : (rb | 0x8000u);
      uint32_t best = __reduce_max_sync(~0u, (ord << 16) | (uint32_t)(2047 - row));
      if (lane < 16) st_rlx64(g_stat + row, ((unsigned long long)tag << 32) | __float_as_uint(mean) | (__float_as_uint(sd) >> 16));
      if (lane < 2) asm volatile("red.relaxed.gpu.global.max.u64 [%0], %1;" ::"l"(lane ? (void*)(g_ycnt + 32) : (void*)(g_best + bid)), "l"(((unsigned long long)tag << 32) | best) : "memory");
      if (lane == 1) { red_inc(g_ycnt + 34); PROF(17); }
#pragma unroll 1
      for (int n = 3; n < 5; n++) STAGEG(n);
      {
        mbar_wait(bar + B_WPHI, 0);
        float nq[8] = {0.f, 0.f, 0.f, 0.f, 0.f, 0.f, 0.f, 0.f};
#pragma unroll 2
        for (int r = 0; r < 16; r++) {
          const uint4 u = lds128u(sb + SM_WPHI + ((lane >> 2) * 16 + r) * 64 + (((lane ^ (r >> 1)) & 3) << 4));
          nq[0] = fmaf(bf_lo(u.x), bf_lo(u.x), nq[0]); nq[1] = fmaf(bf_hi(u.x), bf_hi(u.x), nq[1]); nq[2] = fmaf(bf_lo(u.y), bf_lo(u.y), nq[2]);
          nq[3] = fmaf(bf_hi(u.y), bf_hi(u.y), nq[3]); nq[4] = fmaf(bf_lo(u.z), bf_lo(u.z), nq[4]); nq[5] = fmaf(bf_hi(u.z), bf_hi(u.z), nq[5]);
          nq[6] = fmaf(bf_lo(u.w), bf_lo(u.w), nq[6]); nq[7] = fmaf(bf_hi(u.w), bf_hi(u.w), nq[7]);
        }
        uint32_t m = 0;
#pragma unroll
        for (int i = 0; i < 8; i++) m = max(m, __float_as_uint(nq[i] + __shfl_xor_sync(~0u, nq[i], 4)) & 0x7fffffffu);
        sts32(sb + SM_RED + 24, 4.2f * __uint_as_float(__reduce_max_sync(~0u, m)));
      }
      {
        uint4 xr[4];
        best = routed_row(P.x, tag, lane, xr);
#pragma unroll
        for (int i = 0; i < (GROWS + 255) / 256; i++) {
          const uint32_t dst = sb + SM_XSEL + i * 1024 + (lane >> 2) * 128 + (lane & 3) * 8;
          sts64(dst, bf_lo(xr[i].x), bf_lo(xr[i].z)); sts64(dst + 32, bf_hi(xr[i].x), bf_hi(xr[i].z));
          sts64(dst + 64, bf_lo(xr[i].y), bf_lo(xr[i].w)); sts64(dst + 96, bf_hi(xr[i].y), bf_hi(xr[i].w));
        }
        sts64u(sb + SM_RED + 16, tag, best);
        __syncwarp();
        if (lane == 0) { mbar_arrive(bar + B_XS); PROF(19); }
      }
      unsigned long long sv4[4];
      uint4 u[4];
#pragma unroll 1
      for (int it = 0; it < SPIN_MAX; it++) {
#pragma unroll
        for (int i = 0; i < 4; i++) { u[i] = ld_rlx128(g_cs + (1 + i) * 1024 + hg * 128 + lane * 4); sv4[i] = ld_rlx64(g_stat + mb * 128 + i * 32 + lane); }
        bool ok = ((BAD4(u[0]) | BAD4(u[1]) | BAD4(u[2]) | BAD4(u[3])) & 1) == 0;
#pragma unroll
        for (int i = 0; i < 4; i++) ok = ok && (uint32_t)(sv4[i] >> 32) == tag;
        if (__all_sync(~0u, ok)) break;
        __nanosleep(200);
      }
#pragma unroll
      for (int i = 0; i < 4; i++) {
        const uint32_t sv = (uint32_t)sv4[i], sd2 = (sv << 16) | (sv & 0xffffu);
        sts64(sb + SM_STAT + (i * 32 + lane) * 8, -bf_hi(sv), rcp(bf_lo(sv)));
        sts128u(sb + SM_SDT + lane * 64 + ((i ^ ((lane >> 1) & 3)) << 4), sd2, sd2, sd2, sd2);
      }
#pragma unroll
      for (int i = 0; i < 2; i++) {
        float4 c = make_float4(unmark(u[i].x) + unmark(u[i + 2].x), unmark(u[i].y) + unmark(u[i + 2].y), unmark(u[i].z) + unmark(u[i + 2].z),
                               unmark(u[i].w) + unmark(u[i + 2].w));
        CS_STORE(i, c);
      }
      fence_async_smem();
      __syncwarp();
      if (lane == 0) { mbar_arrive(bar + B_CS); PROF(10); }
    }
    {
      uint32_t xa = sb + SM_RED + 32, xstep = 0;
      const uint32_t zero = __float_as_uint(lds32(sb + SM_RED + 12));
#pragma unroll 1
      for (int ph = f == 3; ph < 2; ph++) {
#pragma unroll
        for (int j = 0; j < 8; j++) a[j] = 0.f;
        if (ph) { mbar_wait(bar + B_XS, 0); xa = sb + SM_XSEL + f * (GN * 128) + ((lane >> 2) & 3) * 32; xstep = 128; }
#pragma unroll 1
        for (int n = ph ? 3 : n0; n < (ph ? ne : 3); n++) {
          const float4 x0 = lds128(xa), x1 = lds128(xa + 16);
          xa += xstep;
          mbar_wait(fbar + (n & 1) * 8, ((n - n0) >> 1) & 1);
          uint4 u[8];
#pragma unroll
          for (int j = 0; j < 8; j++) u[j] = lds128u(fst + (n & 1) * 4096 + j * 256);
          FMA8(a, u[0], x0.x); FMA8(a, u[1], x0.y); FMA8(a, u[2], x0.z); FMA8(a, u[3], x0.w);
          if (__any_sync(~0u, ((u[4].x | u[5].x | u[6].x | u[7].x | __float_as_uint(a[0]) | __float_as_uint(a[7])) & zero) == 0)) STAGEG(n + 2);
          FMA8(a, u[4], x1.x); FMA8(a, u[5], x1.y); FMA8(a, u[6], x1.z); FMA8(a, u[7], x1.w);
        }
#pragma unroll
        for (int o = 4; o <= 8; o <<= 1)
#pragma unroll
          for (int j = 0; j < 8; j++) a[j] += __shfl_xor_sync(~0u, a[j], o);
        if (ph && lane == 0) mbar_arrive(bar + B_FFN);
        const uint32_t red = ph ? sb + SM_GRED : sb + SM_RED + 64;
        if ((lane & 12) == 0) {
          const uint32_t d = red + f * 256 + (lane >> 4) * 128 + (lane & 3) * 32;
          sts128(d, a[0], a[1], a[2], a[3]); sts128(d + 16, a[4], a[5], a[6], a[7]);
        }
        if (f != 2) {
          asm volatile("bar.arrive %0, %1;" ::"r"(4 + ph), "r"(96 + 32 * ph) : "memory");
        } else {
          bar_sync(4 + ph, 96 + 32 * ph);
          const uint32_t ra = red + lane * 4;
          gsum = lds32(ra) + lds32(ra + 256) + lds32(ra + 512);
          usum = lds32(ra + 128) + lds32(ra + 384) + lds32(ra + 640);
          if (!ph) st_rlx(g_cs + 1024 + ch * 2048 + cu * 32 + lane, mark(__float_as_uint(gsum + usum), par));
          else { gsum += lds32(ra + 768); usum += lds32(ra + 896); }
          if (lane == 0) PROF(ph ? 34 : 18);
        }
      }
    }
    if (f == 3) {
      if (elect_one()) {
        PROF(7);
        mbar_wait(bar + B_FULLQ, 0);
#pragma unroll 1
        for (int j = 3; j < 16; j++) {
          mbar_wait(bar + (j < 4 ? B_EMPTYKV + 16 : B_EMPTYQ + 8 * (j & 3)), ((j >> 2) & 1) ^ 1);
          if (j == 12 + (hg & 3)) mbar_wait(bar + B_KVST + 8, 0);
          Q_LOAD(j);
        }
        PROF(47);
        mbar_expect_tx(bar + B_DN, 65536);
#pragma unroll 1
        for (int i = 0; i < 4; i++) {
          mbar_wait(bar + B_EMPTYQ + 8 * i, 1);
          tma3d(sb + i * Q_STAGE, &mD, 0, fb * 32, i * 4, bar + B_DN);
        }
        PROF(48);
#pragma unroll 1
        for (int i = 0; i < 16; i++) {
          const int s = i & 3, n = i < 9 ? i - 2 : i - 9, kb = i < 2 ? 2 * hg + i : 2 * (n + (n >= hg)) + (i >= 9);
          if (i >= 4) mbar_wait(bar + B_EMPTYQ + 8 * s, ((i >> 2) & 1) ^ 1);
          mbar_expect_tx(bar + B_FULLQ + 8 * s, 16384);
          if (i < 2) {
            mbar_arrive2(bar + B_FULLQ + 8 * s);
            tma3d(sb + s * Q_STAGE + 16384, &mWo, 0, kb * 64, hg * 2, bar + B_FULLQ + 8 * s);
          } else {
            tma5d(sb + s * Q_STAGE + 16384, &mWp, hg * 128, kb * 2, bar + B_FULLQ + 8 * s);
            tma5d(sb + s * Q_STAGE + 24576, &mWp, hg * 128 + 64, kb * 2, bar + B_FULLQ + 8 * s);
            if (i >= 3) {
              if (i == 3) { mbar_wait(bar + B_DND, 0); PROF(14); }
#pragma unroll 1
              for (int a = i == 3 ? 2 : i; a <= i; a++) {
                const uint4* src = g_ofr + (mb * 16 + (a == 2 ? (hg == 0 ? 2 : 0) : kb)) * 1024;
#pragma unroll
                for (int h = 0; h < 2; h++) {
                  mbar_expect_tx(bar + B_AIN + (a & 3) * 16 + h * 8, 8192);
                  bulk_load(sb + (a & 3) * Q_STAGE + h * 8192, src + h * 512, 8192, bar + B_AIN + (a & 3) * 16 + h * 8);
                }
              }
            }
          }
        }
      }
    } else {
      if (f == 2) {
        if (PFD && ffn) {
#pragma unroll 1
          for (int i = 0; i < 16; i++) { touch_l2((const char*)P.w_down + fb * 65536 + i * 4096 + lane * 128, lane); __nanosleep(PFD); }
        }
        if (WOT) {
#pragma unroll 1
          for (int i = 0; i < 8; i++) { touch_l2((const char*)P.wo + ((mb & 7) * 128 + i * 16 + (lane >> 1)) * 2048 + hg * 256 + (lane & 1) * 128, lane); __nanosleep(PFD); }
        }
        asm volatile("cp.async.wait_all;" ::: "memory");
        uint4 u;
#pragma unroll 1
        for (int it = 0; it < SPIN_MAX; it++) {
          u = ld_rlx128(g_cs + hg * 128 + lane * 4);
          if (__all_sync(~0u, !(BAD4(u) & 1))) break;
          __nanosleep(200);
        }
        mbar_wait(bar + B_PHI, 0);
        float4 c = make_float4(unmark(u.x), unmark(u.y), unmark(u.z), unmark(u.w));
        CS_STORE(2, c);
        fence_async_smem();
        __syncwarp();
        if (lane == 0) mbar_arrive(bar + B_CSQ);
        if (ffn && !FFN_OFF) {
#pragma unroll 1
          for (int it = 0; it < SPIN_MAX; it++) {
            const uint32_t pg = ld_rlx((const uint32_t*)g_gp + fb * 32 + lane), pu = ld_rlx((const uint32_t*)g_gp + FF + fb * 32 + lane);
            if (__all_sync(~0u, !(((pg ^ par) | (pu ^ par)) & 1))) { gsum += unmark(pg); usum += unmark(pu); break; }
            __nanosleep(200);
          }
        }
        const float h = bf_round(silu_f(bf_round(gsum))) * bf_round(usum);
        const uint32_t h2 = pack2(h, h);
        sts128u(sb + SM_HT + lane * 16, h2, h2, h2, h2);
        fence_async_smem();
        __syncwarp();
        if (lane == 0) { mbar_arrive(bar + B_H); PROF(20); }
      }
      if (f < 2) {
        const uint32_t own = (hg * 2 + f) * 16 + mb, target = __shfl_sync(~0u, tag, 0) * 16;
        mbar_wait(bar + B_KVST + 8 * f, 0);
        if (f == 1 && lane == 0) PROF(11);
        wait_hint(g_xcnt + hg * 64 + f * 16 + mb, target);
        if (elect_one()) {
          PROF(35 + f);
          fence_async_global();
          mbar_expect_tx(bar + B_PART + 8 * f, 8192);
          bulk_load(sb + (f ? SM_PST1 : SM_PST0), g_part + own * 512, 8192, bar + B_PART + 8 * f);
        }
        __syncwarp();
        {
          uint4 uz;
#pragma unroll 1
          for (int it = 0; it < SPIN_MAX; it++) {
            uz = ld_rlx128(g_zpart + own * 128 + lane * 4);
            if (__all_sync(~0u, !(BAD4(uz) & 1))) break;
          }
          const bool b1 = lane & 2, b2 = lane & 4;
          const float z0 = unmark(b1 ? uz.z : uz.x) + __shfl_xor_sync(~0u, unmark(b1 ? uz.x : uz.z), 2);
          const float z1 = unmark(b1 ? uz.w : uz.y) + __shfl_xor_sync(~0u, unmark(b1 ? uz.y : uz.w), 2);
          float z = (b2 ? z1 : z0) + __shfl_xor_sync(~0u, b2 ? z0 : z1, 4);
          z += __shfl_xor_sync(~0u, z, 8);
          z += __shfl_xor_sync(~0u, z, 16);
          if (lane < 8) st_rlx(g_zres + own * 8 + (lane & 1) * 4 + (lane & 2) + (lane >> 2), mark(__float_as_uint(z), par));
          if (lane == 0) red_inc(g_xcnt + hg * 64 + 32 + f * 16);
          __syncwarp();
        }
        wait_hint(g_xcnt + hg * 64 + 32 + f * 16, 5 * target);
        mbar_wait(bar + B_KVST + 8, 0);
        if (lane == 0) PROF(40 + f);
#pragma unroll 1
        for (int it = 0; it < SPIN_MAX; it++) {
          if (elect_one()) {
            fence_async_global();
            mbar_expect_tx(bar + B_RES + 8 * f, 8192);
            bulk_load(sb + SM_V + f * 8192, g_res[par] + (hg * 4 + f * 2) * 256, 8192, bar + B_RES + 8 * f);
          }
          __syncwarp();
          const uint4 uz = ld_rlx128(g_zres + (hg * 4 + f * 2) * 64 + lane * 4);
          const uint32_t zw[4] = {uz.x, uz.y, uz.z, uz.w};
#pragma unroll
          for (int j = 0; j < 4; j++) {
            const uint32_t zz = pack2(unmark(zw[j]), 1.f), row = (lane & 3) * 4 + j;
            sts128u(sb + SM_ZT + (2 * f + (lane >> 4)) * 1024 + row * 64 + ((((lane >> 2) ^ (row >> 1)) & 3) << 4), zz, zz, zz, zz);
          }
          uint32_t bad = BAD4(uz);
          mbar_wait(bar + B_RES + 8 * f, it & 1);
#pragma unroll
          for (int i = 0; i < 16; i++) bad |= ~__float_as_uint(lds32(sb + SM_V + f * 8192 + i * 512 + lane * 16));
          if (__all_sync(~0u, !(bad & 1))) break;
        }
        fence_async_smem();
        __syncwarp();
        if (lane == 0) { mbar_arrive(bar + B_TILE + 8 * f); PROF(f ? 13 : 27); }
      }
      if (f < 2) {
        uint32_t phases = 0;
#pragma unroll 1
        for (int i = 2; i < 16; i++) {
          const int s = i & 3;
          const uint32_t ab = bar + B_AIN + s * 16 + f * 8, slot = sb + s * Q_STAGE + f * 8192;
#pragma unroll 1
          for (int it = 0; it < SPIN_MAX; it++) {
            mbar_wait(ab, (phases >> s) & 1);
            phases ^= 1u << s;
            uint32_t bad = 0;
#pragma unroll
            for (int n = 0; n < (NOVAL ? 0 : 8); n++) bad |= __float_as_uint(lds32(slot + n * 1024 + lane * 32 + (lane >> 2) * 4)) ^ par;
            if (__all_sync(~0u, !(bad & 1))) break;
            if (elect_one()) {
              const int n = i < 9 ? i - 2 : i - 9, kb = 2 * (n + (n >= hg)) + (i >= 9);
              PROF(49);
              mbar_expect_tx(ab, 8192);
              bulk_load(slot, g_ofr + (mb * 16 + kb) * 1024 + f * 512, 8192, ab);
            }
            __syncwarp();
          }
          if (lane == 0) { mbar_arrive(bar + B_FULLQ + 8 * s); if (i == 2 && f == 0) PROF(15); }
        }
        if (f == 0) g_epoch[bid * 32 + lane] = tag;
      } else {
        if (elect_one()) {
          prefetch_map(&mOut);
          if (ffn) { mbar_wait(bar + B_YD, 0); red_rel(g_ycnt); PROF(21); }
        }
        __syncwarp();
        if (f == 2) {
          const uint32_t best = __float_as_uint(lds32(sb + SM_RED + 20));
          const int sel = 2047 - (best & 0x7ff) - mb * 128;
          if (sel >= 0 && sel < 128) {
            const uint2 xr = __ldg((const uint2*)(P.x + (size_t)(mb * 128 + sel) * DM + hg * 128 + lane * 4));
            const float2 st = lds64(sb + SM_STAT + sel * 8);
            const uint32_t ord = best >> 16, rb = (ord & 0x8000u) ? (ord & 0x7fffu) : (~ord & 0xffffu);
            const float sg = rcp(1.f + ex2(-1.4426950408889634f * bf_lo(rb)));
            const uint32_t sg2 = pack2(sg, sg), nm2 = pack2(st.x, st.x);
            wait_cnt<0>(g_ycnt, tag * NFFN);
            float4 y = make_float4(0.f, 0.f, 0.f, 0.f);
#pragma unroll
            for (int i = 0; i < 8; i++) {
              const float4 c = ldg_cg4(g_y[par ^ 1][i] + hg * 128 + lane * 4);
              y.x += c.x; y.y += c.y; y.z += c.z; y.w += c.w;
            }
            uint32_t o[2];
#pragma unroll
            for (int i = 0; i < 2; i++) {
              const uint32_t d = badd2(i ? xr.y : xr.x, nm2);
              const uint32_t tt = badd2(pack2(bf_lo(d) * st.y, bf_hi(d) * st.y), bmul2(i ? pack2(y.z, y.w) : pack2(y.x, y.y), sg2));
              o[i] = pack2(silu_f(bf_lo(tt)), silu_f(bf_hi(tt)));
            }
            sts64u(sb + SM_UPD + lane * 8, o[0], o[1]);
          }
          if (lane == 0) sts32(sb + SM_UPD + 256, __int_as_float(sel));
          __syncwarp();
          if (lane == 0) { mbar_arrive(bar + B_UPD); PROF(22); }
        }
      }
    }
  } else {
    const int t7 = threadIdx.x & 127;
    const char* pfa = warp < 4 ? (const char*)P.x + bid * 32768 + (t7 & 15) * 2048 + (t7 >> 4) * 128
                               : (const char*)P.wqkv + (size_t)((t7 >> 4) * 64 + (bid >> 1)) * 6144 + 2048 + (bid & 1) * 2048 + (t7 & 15) * 128;
    if (t7 < 16 * PF_FIRST) prefetch_l2(pfa);
    if (warp < 7) sts128(sb + SM_CST + threadIdx.x * 16, 0.f, 0.f, 0.f, 0.f);
    else sts32(sb + SM_RED + (threadIdx.x & 15) * 4, threadIdx.x & 8 ? 1.f : 0.f);
    fence_async_smem();
    if (elect_one()) {
#pragma unroll 1
      for (uint32_t b = B_FST + warp * 8; b < B_END; b += 64)
        mbar_init(bar + b, b < B_FULLQ ? 1 : b < B_FFN ? 3 : b < B_EMPTYKV ? 4 : 8);
    }
    __syncwarp();
    asm volatile("setmaxnreg.inc.sync.aligned.u32 %0;" ::"n"(REG_C));
    if (PF_PRE && t7 >= 16 * PF_FIRST && threadIdx.x < 128 + 16 * PF_W) prefetch_l2(pfa);
    bar_sync(0, 384);
    if (!PF_PRE && t7 >= 16 * PF_FIRST && threadIdx.x < 128 + 16 * PF_W) prefetch_l2(pfa);
    const int lane = lane_id();
    const int wg = warp >> 2, w = warp & 3, g = lane >> 2, t = lane & 3;
    float kv[128];
    {
      uint32_t s = 2, ph = 0, sp = 0, php = 0;
#pragma unroll 1
      for (int j = 0; j < 15; j++) {
        PW0(32 + j); mbar_wait(bar + B_FULLKV + 8 * s, ph); PW1(32 + j);
        if (wg == 1 && (ORDER_ALL || j == 0)) bar_sync(10 + s, 256);
        wg_fence();
        wgmma_n256_ssp_ta0_tb1(kv, mkdesc(sb, 16, 1024, 1, wg * 512 + s * (KV_STAGE / 16)), mkdesc(sb + 16384, 8192, 1024, 1, s * (KV_STAGE / 16)), j);
#pragma unroll
        for (int k = 1; k < 4; k++)
          wgmma_n256_ss_ta0_tb1(kv, mkdesc(sb + k * 32, 16, 1024, 1, wg * 512 + s * (KV_STAGE / 16)),
                                mkdesc(sb + 16384 + k * 2048, 8192, 1024, 1, s * (KV_STAGE / 16)), 1);
        wg_commit();
        if (wg == 0 && (ORDER_ALL || j == 0)) asm volatile("bar.arrive %0, 256;" ::"r"(10 + s) : "memory");
        if (warp == 0 && j) {
          mbar_wait(bar + B_EMPTYKV + 8 * sp, php);
          if (elect_one()) {
            if (j < 14) {
              mbar_expect_tx(bar + B_FULLKV + 8 * sp, KV_STAGE);
              tma2d(sb + sp * KV_STAGE, &mX, (j + 2) * 64, mb * 128, bar + B_FULLKV + 8 * sp);
              tma4d(sb + sp * KV_STAGE + 16384, &mWkv, 0, (j + 2) * 64, hg * 2, 1, bar + B_FULLKV + 8 * sp);
            } else {
              Q_LOAD(0);
            }
            if (j < 3 - XS_EARLY) {
              const int xh = j - 1 + XS_EARLY;
              mbar_expect_tx(bar + B_XST + 8 * xh, 16384);
              tma3d(sb + SM_XST + xh * 16384, &mXs, 0, bid * 16, 2 * xh, bar + B_XST + 8 * xh);
            }
          }
          __syncwarp();
        }
        if (j == 0) {
          if (wg == 0) prefetch_l2(pfa + 1024);
        } else if (wg == 1) {
          if (j < 3) {
            if (j == 2 || t7 >= 16 * PF_W) prefetch_l2(pfa + (j - 1) * (8 * 393216));
          } else if (j == 13) {
            prefetch_l2((const char*)P.wo + bid * 16384 + t7 * 128);
          }
          if (PFG && !FFN_OFF && bid < NFFN && j >= 2 && j < 2 + GROWS / 64 && w < 2)
            touch_l2((const char*)((bid & 1) ? P.w_up : P.w_gate) + (size_t)((0x852a7419630ull >> (4 * j - 8) & 15) * 64 + t7) * 7168 + (bid >> 1) * 128, lane);
        }
        wg_wait<0>();
        if (lane == 0) mbar_arrive(bar + B_EMPTYKV + 8 * s);
        sp = s; php = ph;
        ph ^= s == 1;
        s = s == 2 ? 0 : s + 1;
      }
    }
    const int lrow = wg * 64 + w * 16 + (lane & 15);
    const uint32_t sw128 = lrow * 128, x128 = (lrow & 7), hi16 = lane >> 4;
    mbar_wait(bar + B_CS, 0);
    const uint32_t tag = __float_as_uint(lds32(sb + SM_RED + 16));
    const int zero = __float_as_int(lds32(sb + SM_RED + 12));
    const float wn = lds32(sb + SM_RED + 24);
    const float2 st0 = lds64(sb + SM_STAT + (wg * 64 + w * 16 + g) * 8), st1 = lds64(sb + SM_STAT + (wg * 64 + w * 16 + g + 8) * 8);
    const float c0 = st0.y * 1.4426950408889634f, c1 = st1.y * 1.4426950408889634f;
    const uint32_t nm20 = pack2(st0.x, st0.x), nm21 = pack2(st1.x, st1.x), fmask = t == 0 ? ~0u : t == 1 ? 0xffffu : 0u;
    const uint32_t fa0 = nm20 & fmask, fa1 = nm21 & fmask;
    asm volatile("cp.async.wait_all;" ::: "memory");
    PW0(47); mbar_wait(bar + B_FULLKV + 16, 1); PW1(47);
    wg_fence();
    wgmma_n256_rs_ta0_tb1(kv, fa0, fa1, 0u, 0u, mkdesc(sb + SM_CST, 512, 0, 1), 1);
#pragma unroll
    for (int k = 0; k < 4; k++)
      wgmma_n256_ss_ta0_tb1(kv, mkdesc(sb + 2 * KV_STAGE + k * 32, 16, 1024, 1, wg * 512), mkdesc(sb + 2 * KV_STAGE + 16384 + k * 2048, 8192, 1024, 1), 1);
    wg_commit();
    if (warp == 0) {
      mbar_wait(bar + B_EMPTYKV + 8, 0);
      if (elect_one()) {
#pragma unroll 1
        for (int j = 1; j < 3; j++) Q_LOAD(j);
      }
      __syncwarp();
    }
    wg_wait<0>();
    reg_fence<128>(kv);
    if (lane == 0) mbar_arrive(bar + B_EMPTYKV + 16);
    PROFC(2);
    float q[64];
#define QMMA(J, AOFF16, ACCUM)                                                                                     \
  _Pragma("unroll") for (int k = 0; k < 4; k++)                                                                    \
      wgmma_n128_ss_ta0_tb1(q, mkdesc(sb + k * 32, 16, 1024, 1, wg * 512 + (AOFF16)),                              \
                            mkdesc(sb + 16384 + k * 2048, 8192, 1024, 1, ((J) & 3) * (Q_STAGE / 16)), k ? 1 : (ACCUM))
#define QWAIT(J) do { PW0(J); mbar_wait(bar + B_FULLQ + 8 * ((J) & 3), ((J) >> 2) & 1); PW1(J); } while (0)
#define QSTEP_A(J, AOFF16, ACCUM) do { QWAIT(J); wg_fence(); QMMA(J, AOFF16, ACCUM); wg_commit(); } while (0)
#define QREL(J) do { if (lane == 0) mbar_arrive(bar + B_EMPTYQ + 8 * ((J) & 3)); } while (0)
#define Q_OFF16(J) ((J) >= 8 && (J) < 16 ? Q_AOFF(J) / 16 : ((J) & 3) * (Q_STAGE / 16))
#define QPLAIN(J) do { QSTEP_A(J, Q_OFF16(J), 1); wg_wait<1>(); QREL((J) - 1); } while (0)
#define QNEXT(J) do { QPLAIN(J); SCHED_FENCE(); } while (0)
#define PHI_PROJ(DST, SRC, H0, H1)                                                                                 \
  do {                                                                                                             \
    uint32_t a_[32];                                                                                               \
    _Pragma("unroll") for (int j = 8 * (H0); j < 8 * (H1); j++) {                                                  \
      a_[j] = pack2(SRC[2 * j], SRC[2 * j + 1]);                                                                   \
      asm volatile("fma.rn.bf16x2 %0, %1, %1, %0;" : "+r"(nq[(j >> 4) * 2 + (j & 1)]) : "r"(a_[j]));               \
    }                                                                                                              \
    wg_fence();                                                                                                    \
    _Pragma("unroll") for (int hk = 2 * (H0); hk < 2 * (H1); hk++)                                                 \
        wgmma_n32_rs_ta0_tb1(DST + 16 * (hk >> 1), a_[4 * hk], a_[4 * hk + 1], a_[4 * hk + 2], a_[4 * hk + 3],     \
                             mkdesc(sb + SM_WPHI + hk * 1024, 16, 512, 2), hk & 1);                                \
    wg_commit();                                                                                                   \
  } while (0)
    {
      float p[64], ea[24], eb[24], sa[4], sc[4], kz[20];
      uint32_t vp[32];
#pragma unroll
      for (int j = 0; j < 32; j++) vp[j] = pack2(kv[64 + 2 * j], kv[65 + 2 * j]);
      const uint32_t vr = w * 16 + (lane & 15), vb = sb + SM_V + wg * 4096 + vr * 64, x64 = (vr >> 1) & 3;
#define V_STORE(R)                                                                                           \
  _Pragma("unroll") for (int j = 0; j < 4; j++)                                                              \
      stsm4(vb + (j >> 1) * 8192 + ((((j & 1) * 2 + hi16) ^ x64) << 4), vp[16 * (R) + 4 * j], vp[16 * (R) + 4 * j + 1], vp[16 * (R) + 4 * j + 2], vp[16 * (R) + 4 * j + 3])
      V_STORE(0);
      mbar_wait(bar + B_WPHI, 0);
      {
        uint32_t nq[4] = {0u, 0u, 0u, 0u};
        PHI_PROJ(p, kv, 0, 4);
        QSTEP_A(0, 0, 0);
        const bool unsafe = softmax_unsafe(nq, c0 * c0 * wn, c1 * c1 * wn);
        wg_wait<1>();
        reg_fence<64>(p);
        if (__builtin_expect(unsafe, 0)) softmax_shift(p, c0, c1);
      }
#define K_NORM(S) do { quad_sum<4>(S); _Pragma("unroll") for (int i = 0; i < 4; i++) S[i] = rcp(S[i]) * ((i & 1) ? st1.y : st0.y); } while (0)
#define K_STORE(SLOT, E, S) K_STORE_(SLOT, E, S, 0, 2)
#define K_STORE_(SLOT, E, S, J0, J1)                                                                         \
  _Pragma("unroll") for (int j = (J0); j < (J1); j++) {                                                      \
    uint32_t fp[4], fm[4];                                                                                   \
    _Pragma("unroll") for (int i = 0; i < 4; i++) {                                                          \
      const float e0 = E[8 * j + 2 * i], e1 = E[8 * j + 2 * i + 1], r = E[16 + 4 * j + i] * S[2 + (i & 1)];  \
      const uint32_t e2 = pack2(e0, e1);                                                                     \
      fp[i] = bmul2(e2, pack2(S[i & 1], S[i & 1]));                                                          \
      fm[i] = bmul2(e2, pack2(r, r));                                                                        \
    }                                                                                                        \
    stsm4(sb + SM_PHI + (SLOT) * 16384 + sw128 + (((2 * j + hi16) ^ x128) << 4), fp[0], fp[1], fp[2], fp[3]); \
    stsm4(sb + SM_PHI + (SLOT) * 16384 + sw128 + (((4 + 2 * j + hi16) ^ x128) << 4), fm[0], fm[1], fm[2], fm[3]); \
  }
#define KV_MMA(R)                                                                                            \
  do {                                                                                                       \
    mbar_wait(bar + B_PHI + 8 * (R), 0);                                                                     \
    wg_fence();                                                                                              \
    _Pragma("unroll") for (int k = 0; k < 8; k++) {                                                          \
      const uint32_t vs = SM_V + (k >> 2) * 4096 + (k & 3) * 1024;                                           \
      wgmma_n40_ss_ta1_tb1(kz, mkdesc(sb + SM_PHI + k * 2048, 16, 1024, 1, wg * 1024),                       \
                           mkdesc(sb + vs, SM_SDT + (k & 1) * 1024 + (k >> 1) * 16 - vs, 512, 2, wg * (512u - (512u << 16))), k); \
    }                                                                                                        \
    wg_commit();                                                                                             \
  } while (0)
#define QKV(J, R) do { KV_MMA(R); QSTEP_A(J, Q_OFF16(J), 1); wg_wait<2>(); QREL((J) - 1); SCHED_FENCE(); } while (0)
#define KV_SEND(R)                                                                                           \
  do {                                                                                                       \
    reg_fence<20>(kz);                                                                                       \
    if (lane == 0) mbar_arrive(bar + B_KVST + 8 * (R));                                                      \
    const uint32_t slot = ((hg * 2 + (R)) * 16 + warp * 2) * 16 + mb;                                        \
    _Pragma("unroll") for (int u = 0; u < 2; u++)                                                            \
      st_rlx128(g_part + (slot + u * 16) * 32 + lane, mark(pack2(kz[2 * u], kz[2 * u + 1]), tag & 1), pack2(kz[2 * u + 4], kz[2 * u + 5]), \
                pack2(kz[2 * u + 8], kz[2 * u + 9]), pack2(kz[2 * u + 12], kz[2 * u + 13]));                 \
    if (t < 2) st_rlx(g_zpart + (slot + t * 16) * 8 + g, mark(__float_as_uint(t ? kz[18] : kz[16]), tag & 1)); \
    if (lane < 2) red_inc(g_xcnt + hg * 64 + (R) * 16 + warp * 2 + lane);                                    \
  } while (0)
#define K_PUB(R) do { fence_async_smem(); __syncwarp(); if (lane == 0) mbar_arrive(bar + B_PHI + 8 * (R)); } while (0)
#define S_PIN(S) SCHED_PIN(S[0] + S[1] + S[2] + S[3])
      k_exp(p, c0, c1, ea, sa);
      S_PIN(sa);
      QNEXT(1);
      K_NORM(sa);
      k_exp<0, 4>(p + 16, c0, c1, eb, sc);
      mbar_wait(bar + B_FFN, 0);
      K_STORE_(0, ea, sa, 0, 1);
      S_PIN(sc);
      QNEXT(2);
      K_STORE_(0, ea, sa, 1, 2);
      k_exp<4, 8>(p + 16, c0, c1, eb, sc);
      K_NORM(sc);
      S_PIN(sc);
      QNEXT(3);
      K_STORE(1, eb, sc);
      K_PUB(0);
      k_exp<0, 4>(p + 32, c0, c1, ea, sa);
      S_PIN(sa);
      QKV(4, 0);
      k_exp<4, 8>(p + 32, c0, c1, ea, sa);
      K_NORM(sa);
      k_exp<0, 4>(p + 48, c0, c1, eb, sc);
      SCHED_PIN(sa[0] + sa[1] + sa[2] + sa[3] + sc[2] + sc[3]);
      QNEXT(5);
      KV_SEND(0);
      k_exp<4, 8>(p + 48, c0, c1, eb, sc);
      S_PIN(sc);
      QNEXT(6);
      K_NORM(sc);
      mbar_wait(bar + B_KVST, 0);
      V_STORE(1);
      K_STORE(0, ea, sa);
      QNEXT(7);
      K_STORE(1, eb, sc);
      K_PUB(1);
      QKV(8, 1);
      QNEXT(9);
      KV_SEND(1);
    }
#define JQ0 10
    PROFC(3);
    {
      bool todo = true;
#pragma unroll 1
      for (int j = JQ0; j < 15 || todo; j++) {
        if (j < 15) { QSTEP_A(j, Q_AOFF(j) / 16, 1); wg_wait<1>(); QREL(j - 1); }
        if (todo && __any_sync(~0u, mbar_test(bar + B_PART + 8 * wg, 0))) {
          todo = false;
          const uint32_t own = (hg * 2 + wg) * 16 + mb, word = w * 32 + lane;
          uint32_t u[16], bad = 0;
#pragma unroll
          for (int i = 0; i < 16; i++) { u[i] = __float_as_uint(lds32(sb + (wg ? SM_PST1 : SM_PST0) + i * 512 + word * 4)); bad |= u[i] ^ tag; }
#pragma unroll 1
          for (int it = 0; it < SPIN_MAX && __any_sync(~0u, t == 0 && (bad & 1)); it++) {
            bad = 0;
#pragma unroll
            for (int i = 0; i < 16; i++) { u[i] = ld_rlx((const uint32_t*)g_part + own * 2048 + i * 128 + word); bad |= u[i] ^ tag; }
          }
          float s0 = 0.f, s1 = 0.f, s2 = 0.f, s3 = 0.f;
#pragma unroll
          for (int i = 0; i < 16; i += 2) { s0 += bf_lo(u[i] | !t); s1 += bf_hi(u[i]); s2 += bf_lo(u[i + 1] & (t ? ~0u : ~1u)); s3 += bf_hi(u[i + 1]); }
          const uint32_t r = pack2(s0 + s2, s1 + s3);
          st_rlx((uint32_t*)g_res[tag & 1] + own * 128 + w * 32 + (lane & 16) + ((t ^ w) << 2) + ((lane >> 2) & 3), lane & 12 ? r : r | 1);
          ((uint32_t*)g_res[~tag & 1])[own * 128 + word] = 0;
          __syncwarp();
          if (lane == 0) { red_inc(g_xcnt + hg * 64 + 32 + wg * 16); if (w == 0) PROF(wg ? 12 : 30); }
          __syncwarp();
        }
      }
    }
    mbar_wait(bar + B_CSQ, 0);
    QWAIT(15);
    if (wg == 1) bar_sync(6, 256);
    wg_fence();
    wgmma_n128_rs_ta0_tb1(q, fa0, fa1, 0u, 0u, mkdesc(sb + SM_CST + 2048, 512, 0, 1), 1);
    QMMA(15, Q_AOFF(15) / 16, 1);
    wg_commit();
    if (wg == 0) asm volatile("bar.arrive 6, 256;" ::: "memory");
    wg_wait<1>();
    QREL(14);
    wg_wait<0>();
    QREL(15);
    reg_fence<64>(q);
    PROFC(5);
    float yp[4];
    const uint32_t par = tag & 1;
    uint4* ofr = g_ofr + (mb * 16 + hg * 2) * 1024 + (warp * 16 + g) * 8;
#define O_MMA(H, F, N)                                                                                       \
  do {                                                                                                       \
    wg_fence();                                                                                              \
    _Pragma("unroll") for (int k = 0; k < 4; k++) {                                                          \
      const uint32_t ks = SM_V + (H) * 4096 + k * 1024;                                                      \
      wgmma_n40_rs_ta0_tb1(N + 20 * (k >> 1), F[4 * k], F[4 * k + 1], F[4 * k + 2], F[4 * k + 3],            \
                           mkdesc(sb + ks, SM_ZT + (H) * 1024 + k * 16 - ks, 512, 2), k & 1);                \
    }                                                                                                        \
    wg_commit();                                                                                             \
  } while (0)
#define O_FIN(H, N, o)                                                                                        \
  do {                                                                                                       \
    reg_fence<40>(N);                                                                                        \
    const float *np = N, *nm = N + 20;                                                                       \
    const float d0 = rcp(fmaf(np[16], nm[17], fmaf(nm[16], np[17], 1e-6f * np[17] * nm[17])));               \
    const float d1 = rcp(fmaf(np[18], nm[19], fmaf(nm[18], np[19], 1e-6f * np[19] * nm[19])));               \
    const float bp0 = nm[17] * d0, bm0 = np[17] * d0, bp1 = nm[19] * d1, bm1 = np[19] * d1;                  \
    _Pragma("unroll") for (int j = 0; j < 4; j++) {                                                          \
      o[2 * j] = pack2(fmaf(np[4 * j], bp0, nm[4 * j] * bm0), fmaf(np[4 * j + 1], bp0, nm[4 * j + 1] * bm0)); \
      o[2 * j + 1] = pack2(fmaf(np[4 * j + 2], bp1, nm[4 * j + 2] * bm1), fmaf(np[4 * j + 3], bp1, nm[4 * j + 3] * bm1)); \
    }                                                                                                        \
  } while (0)
#define O_STG(H, o)                                                                                          \
  _Pragma("unroll") for (int u = 0; u < 2; u++) {                                                            \
    uint32_t v_[4];                                                                                          \
    _Pragma("unroll") for (int j = 0; j < 4; j++) v_[j] = lop_select(o[2 * j + u], parm, vword == j);        \
    st_rlx128(ofr + ((H) >> 1) * 1024 + u * 64 + ((((H) & 1) * 4 + t) ^ g), v_[0], v_[1], v_[2], v_[3]);     \
  }
    uint32_t gf[32], ao[16];
    const uint32_t parm = 0u - par, vword = ((t ^ g) & 1) == (g >> 2) ? g & 3 : 4;
    const float rh0 = 0.5f * st0.y, rh1 = 0.5f * st1.y, mh0 = st0.x * rh0, mh1 = st1.x * rh1;
#define GATE_LD(J) ldsm4(sb + ((J) >> 2 ? SM_X1 : SM_X0) + sw128 + (((((J) & 3) * 2 + hi16) ^ x128) << 4), gf[4 * (J)], gf[4 * (J) + 1], gf[4 * (J) + 2], gf[4 * (J) + 3])
#define GATE(I0, I1)                                                                                         \
  _Pragma("unroll") for (int i = (I0); i < (I1); i++) {                                                      \
    const float rs = (i & 1) ? rh1 : rh0, mh = (i & 1) ? mh1 : mh0;                                          \
    const float h0 = fmaf(bf_lo(gf[i]), rs, mh), h1 = fmaf(bf_hi(gf[i]), rs, mh);                            \
    gf[i] = pack2(fmaf(h0, tanh_approx(h0), h0), fmaf(h1, tanh_approx(h1), h1));                             \
  }
#define GATE_PIN(I0, I1) do { uint32_t o_ = 0; _Pragma("unroll") for (int i = (I0); i < (I1); i++) o_ |= gf[i]; SCHED_PIN(__uint_as_float(o_)); } while (0)
    {
      float p[64], na[40], nb[40];
      uint32_t fa[16], fb[16];
      {
        uint32_t nq[4] = {0u, 0u, 0u, 0u};
        PHI_PROJ(p, q, 0, 2);
        SCHED_FENCE();
        PHI_PROJ(p, q, 2, 4);
        const bool unsafe = softmax_unsafe(nq, c0 * c0 * wn, c1 * c1 * wn);
        mbar_wait(bar + B_TILE, 0);
        wg_wait<0>();
        reg_fence<64>(p);
        PROFC(24);
        if (__builtin_expect(unsafe, 0)) softmax_shift(p, c0, c1);
      }
      float dn[32];
#define DN_PART(A, B)                                                                                        \
  do {                                                                                                       \
    wg_fence();                                                                                              \
    _Pragma("unroll") for (int i = (A); i < (B); i++)                                                        \
      wgmma_n8_ss_ta1_tb1(dn + 4 * (i >> 1), mkdesc(sb + (i >> 3) * Q_STAGE + (i & 7) * 2048, 16, 1024, 1, wg * (2 * Q_STAGE / 16)), \
                          mkdesc(sb + SM_HT + (i & 1) * 256, 128, 128, 0), i & 1);                           \
  } while (0)
#define F_PIN(F, A, B) do { uint32_t o_ = 0; _Pragma("unroll") for (int i = (A); i < (B); i++) o_ |= F[8 + i]; SCHED_PIN(__uint_as_float(o_)); } while (0)
#define RMMA(J, A, ACCUM)                                                                                    \
  do {                                                                                                       \
    wg_fence();                                                                                              \
    _Pragma("unroll") for (int k = 0; k < 4; k++)                                                            \
      wgmma_n128_rs_ta0_tb1(q, (A)[4 * k], (A)[4 * k + 1], (A)[4 * k + 2], (A)[4 * k + 3],                   \
                            mkdesc(sb + 16384 + k * 2048, 8192, 1024, 1, ((J) & 3) * (Q_STAGE / 16)), k ? 1 : (ACCUM)); \
    wg_commit();                                                                                             \
  } while (0)
#define RSTEP(J, A, ACCUM) do { QWAIT(J); RMMA(J, A, ACCUM); } while (0)
      PROFC(4);
      q_exp(p, c0, c1, fa);
      O_MMA(0, fa, na);
      q_exp(p + 16, c0, c1, fb);
      O_MMA(1, fb, nb);
      PROFC(25);
      wg_wait<1>();
      O_FIN(0, na, ao);
      O_STG(0, ao);
      wg_wait<0>();
      O_FIN(1, nb, (ao + 8));
      O_STG(1, (ao + 8));
      PROFC(28);
      RSTEP(16, ao, 0);
      SCHED_FENCE();
      q_exp(p + 32, c0, c1, fa);
      F_PIN(fa, 0, 8);
      mbar_wait(bar + B_H, 0);
      mbar_wait(bar + B_DN, 0);
      PROFC(45);
      DN_PART(0, 4);
      SCHED_FENCE();
      q_exp<0, 2>(p + 48, c0, c1, fb);
      F_PIN(fb, 0, 2);
      DN_PART(4, 8);
      SCHED_FENCE();
      q_exp<2, 4>(p + 48, c0, c1, fb);
      F_PIN(fb, 2, 4);
      DN_PART(8, 12);
      SCHED_FENCE();
      q_exp<4, 6>(p + 48, c0, c1, fb);
      F_PIN(fb, 4, 6);
      DN_PART(12, 16);
      wg_commit();
      SCHED_FENCE();
      q_exp<6, 8>(p + 48, c0, c1, fb);
      F_PIN(fb, 6, 8);
      wg_wait<0>();
      reg_fence<32>(dn);
      if (lane == 0) mbar_arrive(bar + B_DND);
      QREL(16);
#pragma unroll
      for (int i = 0; i < 4; i++) yp[i] = t & 2 ? (t & 1 ? dn[24 + 2 * i] : dn[16 + 2 * i]) : (t & 1 ? dn[8 + 2 * i] : dn[2 * i]);
      PROFC(29);
      mbar_wait(bar + B_TILE + 8, 0);
      PROFC(23);
      if (bid < NFFN) {
        float* y = g_y[par ^ 1][bid & 7] + wg * 512 + t * 128 + w * 16 + g;
#pragma unroll
        for (int i = 0; i < 4; i++) red1(y + (i >> 1) * 64 + (i & 1) * 8, yp[i]);
      }
      SCHED_FENCE();
      O_MMA(2, fa, na);
      O_MMA(3, fb, nb);
      __syncwarp();
      if (lane == 0) mbar_arrive(bar + B_YD);
      wg_wait<1>();
      O_FIN(2, na, ao);
      O_STG(2, ao);
      wg_wait<0>();
      O_FIN(3, nb, (ao + 8));
      O_STG(3, (ao + 8));
      PROFC(6);
    }
    RSTEP(17, ao, 1);
    SCHED_FENCE();
    GATE_LD(0); GATE_LD(1);
    GATE(0, 3);
    GATE_PIN(0, 3);
#define GSTEP(J, I0, I1, LD) do { QNEXT(J); if ((LD) < 8) GATE_LD((LD) & 7); GATE(I0, I1); GATE_PIN(I0, I1); } while (0)
    GSTEP(18, 3, 6, 2); GSTEP(19, 6, 9, 3); GSTEP(20, 9, 12, 4); GSTEP(21, 12, 15, 8); GSTEP(22, 15, 18, 5); GSTEP(23, 18, 21, 6);
    GSTEP(24, 21, 24, 8); GSTEP(25, 24, 27, 7); GSTEP(26, 27, 30, 8); GSTEP(27, 30, 32, 8);
#pragma unroll 1
    for (int j = 28; j < 32 - TAILN; j++) QPLAIN(j);
    if (wg == 1) bar_sync(6, 256);
#pragma unroll 1
    for (int j = 32 - TAILN; j < 32; j++) QSTEP_A(j, (j & 3) * (Q_STAGE / 16), 1);
    if (wg == 0) asm volatile("bar.arrive 6, 256;" ::: "memory");
    mbar_wait(bar + B_UPD, 0);
    {
      const int sel = __float_as_int(lds32(sb + SM_UPD + 256)) - (wg * 64 + w * 16 + g);
      if (sel == 0 || sel == 8) {
#pragma unroll
        for (int j = 0; j < 16; j++) {
          const uint32_t u = __float_as_uint(lds32(sb + SM_UPD + j * 16 + t * 4));
          if (sel) gf[2 * j + 1] = u; else gf[2 * j] = u;
        }
      }
      __syncwarp();
      uint32_t xf[32];
#pragma unroll
      for (int j = 0; j < 8; j++)
        ldsm4(sb + (j >> 2 ? SM_X1 : SM_X0) + sw128 + ((((j & 3) * 2 + hi16) ^ x128) << 4), xf[4 * j], xf[4 * j + 1], xf[4 * j + 2], xf[4 * j + 3]);
      wg_wait<0>();
      reg_fence<64>(q);
      PROFC(8);
#pragma unroll
      for (int j = 0; j < 8; j++) {
        uint32_t o[4];
#pragma unroll
        for (int i = 0; i < 4; i++) o[i] = badd2(xf[4 * j + i], bmul2(pack2(q[8 * j + 2 * i], q[8 * j + 2 * i + 1]), gf[4 * j + i]));
        stsm4(sb + (j >> 2 ? SM_X1 : SM_X0) + sw128 + ((((j & 3) * 2 + hi16) ^ x128) << 4), o[0], o[1], o[2], o[3]);
      }
    }
    fence_async_smem();
    bar_sync(2 + wg, 128);
    if (w == 0 && elect_one()) {
      tma_store2d(&mOut, sb + SM_X0 + wg * 8192, hg * 128, mb * 128 + wg * 64);
      tma_store2d(&mOut, sb + SM_X1 + wg * 8192, hg * 128 + 64, mb * 128 + wg * 64);
      bulk_commit();
      bulk_wait_read0();
      if (wg == 1) { PROF(9); PROFT(33); PROF_DUMP; }
    }
  }
}

typedef CUresult (*EncodeFn)(CUtensorMap*, CUtensorMapDataType, cuuint32_t, void*, const cuuint64_t*, const cuuint64_t*, const cuuint32_t*,
                             const cuuint32_t*, CUtensorMapInterleave, CUtensorMapSwizzle, CUtensorMapL2promotion, CUtensorMapFloatOOBfill);

CUtensorMap make_map(EncodeFn enc, const void* ptr, int rank, const cuuint64_t* dims, const cuuint64_t* strides, const cuuint32_t* box, CUtensorMapSwizzle sw) {
  CUtensorMap m;
  const cuuint32_t es[5] = {1, 1, 1, 1, 1};
  enc(&m, CU_TENSOR_MAP_DATA_TYPE_BFLOAT16, rank, (void*)ptr, dims, strides, box, es, CU_TENSOR_MAP_INTERLEAVE_NONE, sw,
      CU_TENSOR_MAP_L2_PROMOTION_L2_128B, CU_TENSOR_MAP_FLOAT_OOB_FILL_NONE);
  return m;
}

}

extern "C" void kernel_launch(void* const* d_in, const int* in_sizes, int n_in, void* d_out, int out_size) {
  static EncodeFn enc = nullptr;
  static int by_sm = 0;
  if (!enc) {
    void* fn = nullptr;
    cudaDriverEntryPointQueryResult qr;
    cudaGetDriverEntryPoint("cuTensorMapEncodeTiled", &fn, cudaEnableDefault, &qr);
    enc = (EncodeFn)fn;
    cudaFuncSetAttribute(fused_kernel, cudaFuncAttributeMaxDynamicSharedMemorySize, SM_TOTAL);
    int dev = 0, sms = 0;
    cudaGetDevice(&dev);
    cudaDeviceGetAttribute(&sms, cudaDevAttrMultiProcessorCount, dev);
    by_sm = BY_SM && sms == NCTA + NSPARE;
  }
  Params P;
  P.by_sm = by_sm;
  P.x = (const __nv_bfloat16*)d_in[0];
  P.wqkv = (const __nv_bfloat16*)d_in[1];
  const void* wphi = d_in[2];
  P.wo = (const __nv_bfloat16*)d_in[3];
  P.w_r = (const __nv_bfloat16*)d_in[5];
  P.w_gate = (const __nv_bfloat16*)d_in[6];
  P.w_up = (const __nv_bfloat16*)d_in[7];
  P.w_down = (const __nv_bfloat16*)d_in[8];

  const cuuint64_t dX[2] = {DM, SEQ}, sX[1] = {DM * 2};
  const cuuint32_t b128[2] = {64, 128}, b64[2] = {64, 64};
  const cuuint64_t dW[4] = {64, DM, 16, 3}, sW[3] = {3 * DM * 2, 128, DM * 2};
  const cuuint32_t bKV[4] = {64, 64, 2, 2}, bQ[4] = {64, 64, 2, 1};
  const cuuint64_t dO[3] = {64, DM, 16}, sO[2] = {DM * 2, 128};
  const cuuint32_t bO[3] = {64, 64, 2};
  const cuuint64_t dP[2] = {32, 1024}, sP[1] = {64};
  const cuuint32_t bP[2] = {32, 128};
  CUtensorMap mX = make_map(enc, P.x, 2, dX, sX, b128, CU_TENSOR_MAP_SWIZZLE_128B);
  CUtensorMap mWkv = make_map(enc, P.wqkv, 4, dW, sW, bKV, CU_TENSOR_MAP_SWIZZLE_128B);
  CUtensorMap mWq = make_map(enc, P.wqkv, 4, dW, sW, bQ, CU_TENSOR_MAP_SWIZZLE_128B);
  CUtensorMap mWo = make_map(enc, P.wo, 3, dO, sO, bO, CU_TENSOR_MAP_SWIZZLE_128B);
  CUtensorMap mPhi = make_map(enc, wphi, 2, dP, sP, bP, CU_TENSOR_MAP_SWIZZLE_64B);
  const cuuint64_t dWp[5] = {DM, 2, 4, 4, DM / 32}, sWp[4] = {DM * 2, 8 * DM * 2, 2 * DM * 2, 32 * DM * 2};
  const cuuint32_t bWp[5] = {64, 2, 4, 4, 2};
  CUtensorMap mWp = make_map(enc, P.wo, 5, dWp, sWp, bWp, CU_TENSOR_MAP_SWIZZLE_128B);
  CUtensorMap mOut = make_map(enc, d_out, 2, dX, sX, b64, CU_TENSOR_MAP_SWIZZLE_128B);
  const cuuint64_t dWc[2] = {3 * DM, DM}, sWc[1] = {3 * DM * 2}, dG[2] = {FF, DM}, sG[1] = {FF * 2}, dD[3] = {64, FF, 16};
  const cuuint32_t b32[2] = {32, 32}, bD[3] = {64, 32, 4};
  CUtensorMap mWc = make_map(enc, P.wqkv, 2, dWc, sWc, b32, CU_TENSOR_MAP_SWIZZLE_NONE);
  CUtensorMap mG = make_map(enc, P.w_gate, 2, dG, sG, b32, CU_TENSOR_MAP_SWIZZLE_NONE);
  CUtensorMap mU = make_map(enc, P.w_up, 2, dG, sG, b32, CU_TENSOR_MAP_SWIZZLE_NONE);
  CUtensorMap mD = make_map(enc, P.w_down, 3, dD, sO, bD, CU_TENSOR_MAP_SWIZZLE_128B);
  const cuuint64_t dXs[3] = {256, SEQ, 4}, sXs[2] = {DM * 2, 512};
  const cuuint32_t bXs[3] = {256, 16, 2};
  CUtensorMap mXs = make_map(enc, P.x, 3, dXs, sXs, bXs, CU_TENSOR_MAP_SWIZZLE_NONE);
  const cuuint64_t dG2[4] = {64, DM, FF / 64, 1}, sG2[3] = {FF * 2, 128, (cuuint64_t)FF * DM * 2};
  CUtensorMap mG2 = make_map(enc, P.w_gate, 4, dG2, sG2, bQ, CU_TENSOR_MAP_SWIZZLE_128B);
  CUtensorMap mU2 = make_map(enc, P.w_up, 4, dG2, sG2, bQ, CU_TENSOR_MAP_SWIZZLE_128B);
  fused_kernel<<<NCTA + NSPARE, 384, SM_TOTAL, cudaStreamPerThread>>>(mX, mWkv, mWq, mWo, mPhi, mWp, mOut, mWc, mG, mU, mD, mXs, mG2, mU2, P);
}
```

```cpp
#include <cuda_runtime.h>
#include <cuda_bf16.h>
#include <cuda.h>
#include <stdint.h>

namespace {

constexpr int SEQ = 2048, DM = 1024, FF = 3584;
constexpr int NCTA = 128;
constexpr int NSPARE = 4;
constexpr int NFFN = FF / 32;
#define GN 6
#define G8 4
constexpr int GROWS = (3 * GN + G8) * 32;
#define TAILN 2
#define KTAIL 1
#define XS_EARLY 1
#define PF_FIRST 2
#define PF_W 5
#define PF_PRE 1
#define PFG 0
#define PFD 80
#define BY_SM 1
#define PTAB 0x73216540u
#define ROWSPLIT 1
#define WOT 1
#define PSPLIT 1
#define KSTEPS 4
#define NOVAL 0
#define KCH 1
#define REG_C 224
#define REG_H 56
#define TW 1
#define ORDER_ALL 1
#define AM_NS 100
constexpr bool FFN_OFF = false;

static_assert(2 * REG_C + REG_H <= 3 * 168, "the register pool of the CTA is 384 x 168");

__device__ uint32_t g_epoch[(NCTA + NSPARE) * 32];
__device__ unsigned long long g_stat[SEQ];
__device__ __align__(128) unsigned long long g_best[NCTA];
__device__ __align__(16) float g_y[2][8][DM];
__device__ __align__(128) uint32_t g_ycnt[64];
__device__ __align__(128) uint32_t g_xcnt[8 * 64];
__device__ __align__(128) uint4 g_res[2][32 * 256];
__device__ __align__(16) float g_cs[5 * DM];
__device__ __align__(128) float g_gp[2 * FF];
__device__ uint4 g_part[8 * 2 * 16 * 16 * 32];
__device__ __align__(16) float g_zpart[8 * 2 * 16 * 16 * 8];
__device__ __align__(128) float g_zres[32 * 64];
__device__ __align__(1024) uint4 g_ofr[16 * 16 * 1024];
#define PROF(i)
#define PROFT(i)
#define PROFC(i)
#define PROF_DUMP
#define PW0(J)
#define PW1(J)

constexpr uint32_t KV_STAGE = 49152, Q_STAGE = 32768;
constexpr uint32_t SM_V = 147456;
constexpr uint32_t SM_PHI = 163840;
constexpr uint32_t SM_XST = 147456;
constexpr uint32_t SM_FST = 172032;
constexpr uint32_t SM_PST0 = 196608, SM_PST1 = SM_PHI + 8192;
constexpr uint32_t SM_X0 = 131072, SM_X1 = SM_PHI + 16384;
constexpr uint32_t SM_WPHI = 204800;
constexpr uint32_t SM_ZT = 212992;
constexpr uint32_t SM_SDT = 217088;
constexpr uint32_t SM_CST = 219136;
constexpr uint32_t SM_HT = 222720;
constexpr uint32_t SM_STAT = 223232;
constexpr uint32_t SM_XSEL = 224256;
constexpr uint32_t SM_RED = 228352;
constexpr uint32_t SM_ROWS = SM_RED + 832;
constexpr uint32_t SM_GRED = SM_XSEL + 3072;
static_assert(GROWS <= 768, "xsel area");
constexpr uint32_t SM_UPD = 229632;
constexpr uint32_t SM_BAR = 230016;
constexpr uint32_t SM_PROF = 230464;
constexpr uint32_t SM_SINK = 231104;
constexpr uint32_t SM_TOTAL = 231616;
constexpr uint32_t SB = 1024;
constexpr uint32_t B_FULLKV = 0  , B_FST = 24  , B_XFULL = 88  , B_XST = 104  , B_WPHI = 120, B_CS = 128, B_CSQ = 136, B_UPD = 144,
                   B_H = 152, B_DN = 160, B_XS = 168, B_TILE = 176  , B_RES = 192  , B_PART = 208  ,
B_AIN = 224  ,
                   B_FULLQ = 288  ,
                   B_FFN = 320,
                   B_EMPTYKV = 328  , B_EMPTYQ = 352  , B_KVST = 384  , B_YD = 400, B_PHI = 408  , B_DND = 424, B_END = 432;

__device__ __forceinline__ uint32_t smem_u32(const void* p) { return (uint32_t)__cvta_generic_to_shared(p); }
__device__ __forceinline__ void mbar_init(uint32_t bar, uint32_t cnt) { asm volatile("mbarrier.init.shared::cta.b64 [%0], %1;" ::"r"(bar), "r"(cnt) : "memory"); }
__device__ __forceinline__ void mbar_expect_tx(uint32_t bar, uint32_t bytes) { asm volatile("mbarrier.arrive.expect_tx.shared::cta.b64 _, [%0], %1;" ::"r"(bar), "r"(bytes) : "memory"); }
__device__ __forceinline__ void mbar_arrive2(uint32_t bar) { asm volatile("mbarrier.arrive.shared::cta.b64 _, [%0], 2;" ::"r"(bar) : "memory"); }
__device__ __forceinline__ void mbar_arrive(uint32_t bar) { asm volatile("mbarrier.arrive.shared::cta.b64 _, [%0];" ::"r"(bar) : "memory"); }
__device__ __forceinline__ void mbar_wait(uint32_t bar, uint32_t parity) {
  asm volatile("{\n.reg .pred p;\nLW:\nmbarrier.try_wait.parity.shared::cta.b64 p, [%0], %1;\n@!p bra LW;\n}" ::"r"(bar), "r"(parity) : "memory");
}
__device__ __forceinline__ bool mbar_test(uint32_t bar, uint32_t parity) {
  uint32_t ok;
  asm volatile("{\n.reg .pred p;\nmbarrier.test_wait.parity.shared::cta.b64 p, [%1], %2;\nselp.u32 %0, 1, 0, p;\n}" : "=r"(ok) : "r"(bar), "r"(parity) : "memory");
  return ok;
}
__device__ __forceinline__ int lane_id() { int l; asm volatile("mov.u32 %0, %%laneid;" : "=r"(l)); return l; }
template <int C> __device__ __forceinline__ void sched_fence_(int zero) {
  asm volatile("{\n.reg .pred p;\nsetp.eq.s32 p, %0, %1;\nSF:\npmevent 1;\n@p bra SF;\n}" ::"r"(zero), "n"(C) : "memory");
}
#define SCHED_FENCE() sched_fence_<1000 + __COUNTER__>(zero)
#define SCHED_PIN(V) sched_fence_<1000 + __COUNTER__>(zero & __float_as_int(V))
__device__ __forceinline__ bool elect_one() {
  uint32_t p; asm volatile("{ .reg .pred P; elect.sync _|P, 0xffffffff; selp.u32 %0, 1, 0, P; }" : "=r"(p)); return p;
}
__device__ __forceinline__ void tma2d(uint32_t dst, const CUtensorMap* m, int x, int y, uint32_t bar) {
  asm volatile("cp.async.bulk.tensor.2d.shared::cluster.global.mbarrier::complete_tx::bytes [%0], [%1, {%3, %4}], [%2];" ::"r"(dst), "l"(m), "r"(bar), "r"(x), "r"(y) : "memory");
}
__device__ __forceinline__ void tma3d(uint32_t dst, const CUtensorMap* m, int x, int y, int z, uint32_t bar) {
  asm volatile("cp.async.bulk.tensor.3d.shared::cluster.global.mbarrier::complete_tx::bytes [%0], [%1, {%3, %4, %5}], [%2];" ::"r"(dst), "l"(m), "r"(bar), "r"(x), "r"(y), "r"(z) : "memory");
}
__device__ __forceinline__ void tma4d(uint32_t dst, const CUtensorMap* m, int x, int y, int z, int w, uint32_t bar) {
  asm volatile("cp.async.bulk.tensor.4d.shared::cluster.global.mbarrier::complete_tx::bytes [%0], [%1, {%3, %4, %5, %6}], [%2];" ::"r"(dst), "l"(m), "r"(bar), "r"(x), "r"(y), "r"(z), "r"(w) : "memory");
}
__device__ __forceinline__ void tma5d(uint32_t dst, const CUtensorMap* m, int x, int v, uint32_t bar) {
  asm volatile("cp.async.bulk.tensor.5d.shared::cluster.global.mbarrier::complete_tx::bytes [%0], [%1, {%3, %5, %5, %5, %4}], [%2];" ::"r"(dst), "l"(m), "r"(bar), "r"(x), "r"(v), "r"(0) : "memory");
}
__device__ __forceinline__ void tma_store2d(const CUtensorMap* m, uint32_t src, int x, int y) {
  asm volatile("cp.async.bulk.tensor.2d.global.shared::cta.bulk_group [%0, {%2, %3}], [%1];" ::"l"(m), "r"(src), "r"(x), "r"(y) : "memory");
}
__device__ __forceinline__ void bulk_load(uint32_t dst, const void* src, uint32_t bytes, uint32_t bar) {
  asm volatile("cp.async.bulk.shared::cluster.global.mbarrier::complete_tx::bytes [%0], [%1], %2, [%3];" ::"r"(dst), "l"(src), "r"(bytes), "r"(bar) : "memory");
}
__device__ __forceinline__ void bulk_commit() { asm volatile("cp.async.bulk.commit_group;" ::: "memory"); }
__device__ __forceinline__ void bulk_wait0() { asm volatile("cp.async.bulk.wait_group 0;" ::: "memory"); }
__device__ __forceinline__ void bulk_wait_read0() { asm volatile("cp.async.bulk.wait_group.read 0;" ::: "memory"); }
__device__ __forceinline__ void prefetch_l2(const void* p) { asm volatile("prefetch.global.L2 [%0];" ::"l"(p) : "memory"); }
__device__ __forceinline__ void touch_l2(const void* p, int lane) { asm volatile("cp.async.cg.shared.global.L2::128B [%0], [%1], 16;" ::"r"(SB + SM_SINK + lane * 16), "l"(p) : "memory"); }
__device__ __forceinline__ void prefetch_map(const CUtensorMap* m) { asm volatile("prefetch.tensormap [%0];" ::"l"(m) : "memory"); }
__device__ __forceinline__ void fence_async_smem() { asm volatile("fence.proxy.async.shared::cta;" ::: "memory"); }
__device__ __forceinline__ void fence_async_global() { asm volatile("fence.proxy.async.global;" ::: "memory"); }
__device__ __forceinline__ void bar_sync(int id, int n) { asm volatile("bar.sync %0, %1;" ::"r"(id), "r"(n) : "memory"); }
__device__ __forceinline__ void wg_fence() { asm volatile("wgmma.fence.sync.aligned;" ::: "memory"); }
__device__ __forceinline__ void wg_commit() { asm volatile("wgmma.commit_group.sync.aligned;" ::: "memory"); }
template <int N> __device__ __forceinline__ void wg_wait() { asm volatile("wgmma.wait_group.sync.aligned %0;" ::"n"(N) : "memory"); }
template <int N> __device__ __forceinline__ void reg_fence(uint32_t* r) {
#pragma unroll
  for (int i = 0; i < N; i++) asm volatile("" : "+r"(r[i])::"memory");
}
template <int N> __device__ __forceinline__ void reg_fence(float* r) {
#pragma unroll
  for (int i = 0; i < N; i++) asm volatile("" : "+f"(r[i])::"memory");
}
__device__ __forceinline__ uint64_t mkdesc(uint32_t addr, uint32_t lbo, uint32_t sbo, uint32_t swz, uint32_t dyn = 0) {
  const uint32_t lo = ((addr >> 4) | ((lbo >> 4) << 16)) + dyn;
  const uint32_t hi = (sbo >> 4) | (swz << 30);
  uint64_t d;
  asm("mov.b64 %0, {%1, %2};" : "=l"(d) : "r"(lo), "r"(hi));
  return d;
}
__device__ __forceinline__ void stsm4(uint32_t addr, uint32_t a, uint32_t b, uint32_t c, uint32_t d) {
  asm volatile("stmatrix.sync.aligned.m8n8.x4.shared.b16 [%0], {%1, %2, %3, %4};" ::"r"(addr), "r"(a), "r"(b), "r"(c), "r"(d) : "memory");
}
__device__ __forceinline__ void ldsm4(uint32_t addr, uint32_t& a, uint32_t& b, uint32_t& c, uint32_t& d) {
  asm volatile("ldmatrix.sync.aligned.m8n8.x4.shared.b16 {%0, %1, %2, %3}, [%4];" : "=r"(a), "=r"(b), "=r"(c), "=r"(d) : "r"(addr) : "memory");
}
__device__ __forceinline__ uint32_t pack2(float lo, float hi) { uint32_t r; asm("cvt.rn.bf16x2.f32 %0, %1, %2;" : "=r"(r) : "f"(hi), "f"(lo)); return r; }
__device__ __forceinline__ uint32_t bsub2(uint32_t a, uint32_t b) { uint32_t r; asm("sub.rn.bf16x2 %0, %1, %2;" : "=r"(r) : "r"(a), "r"(b)); return r; }
__device__ __forceinline__ uint32_t badd2(uint32_t a, uint32_t b) { uint32_t r; asm("add.rn.bf16x2 %0, %1, %2;" : "=r"(r) : "r"(a), "r"(b)); return r; }
__device__ __forceinline__ uint32_t bmul2(uint32_t a, uint32_t b) { uint32_t r; asm("mul.rn.bf16x2 %0, %1, %2;" : "=r"(r) : "r"(a), "r"(b)); return r; }
__device__ __forceinline__ float bf_lo(uint32_t v) { return __uint_as_float(v << 16); }
__device__ __forceinline__ float bf_hi(uint32_t v) { return __uint_as_float(v & 0xffff0000u); }
__device__ __forceinline__ float bf_round(float v) { return bf_lo(pack2(v, 0.f)); }
__device__ __forceinline__ float ex2(float v) { float r; asm("ex2.approx.ftz.f32 %0, %1;" : "=f"(r) : "f"(v)); return r; }
__device__ __forceinline__ float rcp(float v) { float r; asm("rcp.approx.ftz.f32 %0, %1;" : "=f"(r) : "f"(v)); return r; }
__device__ __forceinline__ float sqrt_approx(float v) { float r; asm("sqrt.approx.f32 %0, %1;" : "=f"(r) : "f"(v)); return r; }
__device__ __forceinline__ float4 lds128(uint32_t a) { float4 v; asm volatile("ld.shared.v4.f32 {%0, %1, %2, %3}, [%4];" : "=f"(v.x), "=f"(v.y), "=f"(v.z), "=f"(v.w) : "r"(a) : "memory"); return v; }
__device__ __forceinline__ uint4 lds128u(uint32_t a) { uint4 v; asm volatile("ld.shared.v4.u32 {%0, %1, %2, %3}, [%4];" : "=r"(v.x), "=r"(v.y), "=r"(v.z), "=r"(v.w) : "r"(a) : "memory"); return v; }
__device__ __forceinline__ float2 lds64(uint32_t a) { float2 v; asm volatile("ld.shared.v2.f32 {%0, %1}, [%2];" : "=f"(v.x), "=f"(v.y) : "r"(a) : "memory"); return v; }
__device__ __forceinline__ float lds32(uint32_t a) { float v; asm volatile("ld.shared.f32 %0, [%1];" : "=f"(v) : "r"(a) : "memory"); return v; }
__device__ __forceinline__ void sts32(uint32_t a, float v) { asm volatile("st.shared.f32 [%0], %1;" ::"r"(a), "f"(v) : "memory"); }
__device__ __forceinline__ void sts64(uint32_t a, float x, float y) { asm volatile("st.shared.v2.f32 [%0], {%1, %2};" ::"r"(a), "f"(x), "f"(y) : "memory"); }
__device__ __forceinline__ void sts128(uint32_t a, float x, float y, float z, float w) { asm volatile("st.shared.v4.f32 [%0], {%1, %2, %3, %4};" ::"r"(a), "f"(x), "f"(y), "f"(z), "f"(w) : "memory"); }
__device__ __forceinline__ void sts64u(uint32_t a, uint32_t x, uint32_t y) { asm volatile("st.shared.v2.u32 [%0], {%1, %2};" ::"r"(a), "r"(x), "r"(y) : "memory"); }
__device__ __forceinline__ void sts128u(uint32_t a, uint32_t x, uint32_t y, uint32_t z, uint32_t w) { asm volatile("st.shared.v4.u32 [%0], {%1, %2, %3, %4};" ::"r"(a), "r"(x), "r"(y), "r"(z), "r"(w) : "memory"); }
__device__ __forceinline__ uint4 ldg_nc(const void* p) { uint4 v; asm volatile("ld.global.nc.L1::no_allocate.v4.u32 {%0, %1, %2, %3}, [%4];" : "=r"(v.x), "=r"(v.y), "=r"(v.z), "=r"(v.w) : "l"(p)); return v; }
__device__ __forceinline__ float4 ldg_cg4(const float* p) { float4 v; asm volatile("ld.global.cg.v4.f32 {%0, %1, %2, %3}, [%4];" : "=f"(v.x), "=f"(v.y), "=f"(v.z), "=f"(v.w) : "l"(p) : "memory"); return v; }
__device__ __forceinline__ uint32_t ld_acq(const uint32_t* p) { uint32_t v; asm volatile("ld.acquire.gpu.global.u32 %0, [%1];" : "=r"(v) : "l"(p) : "memory"); return v; }
__device__ __forceinline__ uint32_t ld_acq_cta(uint32_t a) { uint32_t v; asm volatile("ld.acquire.cta.shared.u32 %0, [%1];" : "=r"(v) : "r"(a) : "memory"); return v; }
__device__ __forceinline__ void st_rel_cta(uint32_t a, uint32_t v) { asm volatile("st.release.cta.shared.u32 [%0], %1;" ::"r"(a), "r"(v) : "memory"); }
__device__ __forceinline__ unsigned long long ld_rlx64(const unsigned long long* p) { unsigned long long v; asm volatile("ld.relaxed.gpu.global.u64 %0, [%1];" : "=l"(v) : "l"(p) : "memory"); return v; }
__device__ __forceinline__ void st_rlx64(unsigned long long* p, unsigned long long v) { asm volatile("st.relaxed.gpu.global.u64 [%0], %1;" ::"l"(p), "l"(v) : "memory"); }
__device__ __forceinline__ uint4 ld_rlx128(const void* p) {
  uint4 v;
  asm volatile("{ .reg .b128 t; .reg .b64 a, b; ld.relaxed.gpu.global.b128 t, [%4]; mov.b128 {a, b}, t; mov.b64 {%0, %1}, a; mov.b64 {%2, %3}, b; }"
               : "=r"(v.x), "=r"(v.y), "=r"(v.z), "=r"(v.w) : "l"(p) : "memory");
  return v;
}
__device__ __forceinline__ void st_rlx128(void* p, uint32_t x, uint32_t y, uint32_t z, uint32_t w) {
  asm volatile("{ .reg .b128 t; .reg .b64 a, b; mov.b64 a, {%1, %2}; mov.b64 b, {%3, %4}; mov.b128 t, {a, b}; st.relaxed.gpu.global.b128 [%0], t; }"
               ::"l"(p), "r"(x), "r"(y), "r"(z), "r"(w) : "memory");
}
__device__ __forceinline__ void stg128(void* p, uint32_t x, uint32_t y, uint32_t z, uint32_t w) { asm volatile("st.global.v4.u32 [%0], {%1, %2, %3, %4};" ::"l"(p), "r"(x), "r"(y), "r"(z), "r"(w) : "memory"); }
__device__ __forceinline__ void st_rlx(void* p, uint32_t v) { asm volatile("st.relaxed.gpu.global.u32 [%0], %1;" ::"l"(p), "r"(v) : "memory"); }
__device__ __forceinline__ uint32_t lop_select(uint32_t a, uint32_t b, uint32_t m) { uint32_t r; asm("lop3.b32 %0, %1, %2, %3, 0xd8;" : "=r"(r) : "r"(a), "r"(b), "r"(m)); return r; }
__device__ __forceinline__ float unmark(uint32_t v) { return __uint_as_float(v & ~1u); }
__device__ __forceinline__ uint32_t mark(uint32_t v, uint32_t par) { return (v & ~1u) | par; }
__device__ __forceinline__ float tanh_approx(float v) { float r; asm("tanh.approx.f32 %0, %1;" : "=f"(r) : "f"(v)); return r; }
__device__ __forceinline__ void flag_rel(uint32_t* p, uint32_t v) { asm volatile("red.release.gpu.global.max.u32 [%0], %1;" ::"l"(p), "r"(v) : "memory"); }
__device__ __forceinline__ void red1(float* p, float a) { asm volatile("red.global.add.f32 [%0], %1;" ::"l"(p), "f"(a) : "memory"); }
__device__ __forceinline__ void red_inc(uint32_t* p) { asm volatile("red.relaxed.gpu.global.add.u32 [%0], 1;" ::"l"(p) : "memory"); }
__device__ __forceinline__ void red_rel(uint32_t* p) { asm volatile("red.release.gpu.global.add.u32 [%0], 1;" ::"l"(p) : "memory"); }
__device__ __forceinline__ void red4(float* p, float a, float b, float c, float d) { asm volatile("red.global.add.v4.f32 [%0], {%1, %2, %3, %4};" ::"l"(p), "f"(a), "f"(b), "f"(c), "f"(d) : "memory"); }
constexpr int SPIN_MAX = 100000;
__device__ __forceinline__ uint32_t ld_rlx(const uint32_t* p) { uint32_t v; asm volatile("ld.relaxed.gpu.global.u32 %0, [%1];" : "=r"(v) : "l"(p) : "memory"); return v; }
template <int NS = 0> __device__ __forceinline__ void wait_hint(const uint32_t* p, uint32_t target) {
#pragma unroll 1
  for (int i = 0; i < SPIN_MAX; i++) { if ((int)(ld_rlx(p) - target) >= 0) break; if (NS) __nanosleep(NS); }
}
template <int NS> __device__ __forceinline__ void wait_cnt(const uint32_t* p, uint32_t target) {
#pragma unroll 1
  for (int i = 0; i < SPIN_MAX; i++) { if ((int)(ld_rlx(p) - target) >= 0) break; if (NS) __nanosleep(NS); }
  (void)ld_acq(p);
}
template <int NS> __device__ __forceinline__ unsigned long long wait_tag(const unsigned long long* p, uint32_t tag) {
  unsigned long long v = 0;
#pragma unroll 1
  for (int i = 0; i < SPIN_MAX; i++) { v = ld_rlx64(p); if ((uint32_t)(v >> 32) == tag) break; if (NS) __nanosleep(NS); }
  return v;
}
__device__ __forceinline__ float silu_f(float v) { return v * rcp(1.f + ex2(-1.4426950408889634f * v)); }

__device__ __forceinline__ void wgmma_n8_ss_ta1_tb0(float* d, uint64_t da, uint64_t db, bool accumulate) {
  if (accumulate) {
    asm volatile("{\n.reg .pred p;\nsetp.ne.b32 p, 1, 0;\n"
      "wgmma.mma_async.sync.aligned.m64n8k16.f32.bf16.bf16 "
      "{%0, %1, %2, %3}, "
      "%4, %5, p, 1, 1, 1, 0;\n}\n"
      : "+f"(d[0]), "+f"(d[1]), "+f"(d[2]), "+f"(d[3])
      : "l"(da), "l"(db));
  } else {
    asm volatile("{\n.reg .pred p;\nsetp.ne.b32 p, 0, 0;\n"
      "wgmma.mma_async.sync.aligned.m64n8k16.f32.bf16.bf16 "
      "{%0, %1, %2, %3}, "
      "%4, %5, p, 1, 1, 1, 0;\n}\n"
      : "=f"(d[0]), "=f"(d[1]), "=f"(d[2]), "=f"(d[3])
      : "l"(da), "l"(db));
  }
}
__device__ __forceinline__ void wgmma_n8_ss_ta1_tb1(float* d, uint64_t da, uint64_t db, bool accumulate) {
  if (accumulate) {
    asm volatile("{\n.reg .pred p;\nsetp.ne.b32 p, 1, 0;\n"
      "wgmma.mma_async.sync.aligned.m64n8k16.f32.bf16.bf16 "
      "{%0, %1, %2, %3}, "
      "%4, %5, p, 1, 1, 1, 1;\n}\n"
      : "+f"(d[0]), "+f"(d[1]), "+f"(d[2]), "+f"(d[3])
      : "l"(da), "l"(db));
  } else {
    asm volatile("{\n.reg .pred p;\nsetp.ne.b32 p, 0, 0;\n"
      "wgmma.mma_async.sync.aligned.m64n8k16.f32.bf16.bf16 "
      "{%0, %1, %2, %3}, "
      "%4, %5, p, 1, 1, 1, 1;\n}\n"
      : "=f"(d[0]), "=f"(d[1]), "=f"(d[2]), "=f"(d[3])
      : "l"(da), "l"(db));
  }
}
__device__ __forceinline__ void wgmma_n32_rs_ta0_tb1(float* d, uint32_t a0, uint32_t a1, uint32_t a2, uint32_t a3, uint64_t db, bool accumulate) {
  if (accumulate) {
    asm volatile("{\n.reg .pred p;\nsetp.ne.b32 p, 1, 0;\n"
      "wgmma.mma_async.sync.aligned.m64n32k16.f32.bf16.bf16 "
      "{%0, %1, %2, %3, %4, %5, %6, %7, %8, %9, %10, %11, %12, %13, %14, %15}, "
      "{%16, %17, %18, %19}, %20, p, 1, 1, 1;\n}\n"
      : "+f"(d[0]), "+f"(d[1]), "+f"(d[2]), "+f"(d[3]), "+f"(d[4]), "+f"(d[5]), "+f"(d[6]), "+f"(d[7]), "+f"(d[8]), "+f"(d[9]), "+f"(d[10]), "+f"(d[11]), "+f"(d[12]), "+f"(d[13]), "+f"(d[14]), "+f"(d[15])
      : "r"(a0), "r"(a1), "r"(a2), "r"(a3), "l"(db));
  } else {
    asm volatile("{\n.reg .pred p;\nsetp.ne.b32 p, 0, 0;\n"
      "wgmma.mma_async.sync.aligned.m64n32k16.f32.bf16.bf16 "
      "{%0, %1, %2, %3, %4, %5, %6, %7, %8, %9, %10, %11, %12, %13, %14, %15}, "
      "{%16, %17, %18, %19}, %20, p, 1, 1, 1;\n}\n"
      : "=f"(d[0]), "=f"(d[1]), "=f"(d[2]), "=f"(d[3]), "=f"(d[4]), "=f"(d[5]), "=f"(d[6]), "=f"(d[7]), "=f"(d[8]), "=f"(d[9]), "=f"(d[10]), "=f"(d[11]), "=f"(d[12]), "=f"(d[13]), "=f"(d[14]), "=f"(d[15])
      : "r"(a0), "r"(a1), "r"(a2), "r"(a3), "l"(db));
  }
}
__device__ __forceinline__ void wgmma_n40_rs_ta0_tb1(float* d, uint32_t a0, uint32_t a1, uint32_t a2, uint32_t a3, uint64_t db, bool accumulate) {
  if (accumulate) {
    asm volatile("{\n.reg .pred p;\nsetp.ne.b32 p, 1, 0;\n"
      "wgmma.mma_async.sync.aligned.m64n40k16.f32.bf16.bf16 "
      "{%0, %1, %2, %3, %4, %5, %6, %7, %8, %9, %10, %11, %12, %13, %14, %15, %16, %17, %18, %19}, "
      "{%20, %21, %22, %23}, %24, p, 1, 1, 1;\n}\n"
      : "+f"(d[0]), "+f"(d[1]), "+f"(d[2]), "+f"(d[3]), "+f"(d[4]), "+f"(d[5]), "+f"(d[6]), "+f"(d[7]), "+f"(d[8]), "+f"(d[9]), "+f"(d[10]), "+f"(d[11]), "+f"(d[12]), "+f"(d[13]), "+f"(d[14]), "+f"(d[15]), "+f"(d[16]), "+f"(d[17]), "+f"(d[18]), "+f"(d[19])
      : "r"(a0), "r"(a1), "r"(a2), "r"(a3), "l"(db));
  } else {
    asm volatile("{\n.reg .pred p;\nsetp.ne.b32 p, 0, 0;\n"
      "wgmma.mma_async.sync.aligned.m64n40k16.f32.bf16.bf16 "
      "{%0, %1, %2, %3, %4, %5, %6, %7, %8, %9, %10, %11, %12, %13, %14, %15, %16, %17, %18, %19}, "
      "{%20, %21, %22, %23}, %24, p, 1, 1, 1;\n}\n"
      : "=f"(d[0]), "=f"(d[1]), "=f"(d[2]), "=f"(d[3]), "=f"(d[4]), "=f"(d[5]), "=f"(d[6]), "=f"(d[7]), "=f"(d[8]), "=f"(d[9]), "=f"(d[10]), "=f"(d[11]), "=f"(d[12]), "=f"(d[13]), "=f"(d[14]), "=f"(d[15]), "=f"(d[16]), "=f"(d[17]), "=f"(d[18]), "=f"(d[19])
      : "r"(a0), "r"(a1), "r"(a2), "r"(a3), "l"(db));
  }
}
__device__ __forceinline__ void wgmma_n40_ss_ta1_tb1(float* d, uint64_t da, uint64_t db, bool accumulate) {
  if (accumulate) {
    asm volatile("{\n.reg .pred p;\nsetp.ne.b32 p, 1, 0;\n"
      "wgmma.mma_async.sync.aligned.m64n40k16.f32.bf16.bf16 "
      "{%0, %1, %2, %3, %4, %5, %6, %7, %8, %9, %10, %11, %12, %13, %14, %15, %16, %17, %18, %19}, "
      "%20, %21, p, 1, 1, 1, 1;\n}\n"
      : "+f"(d[0]), "+f"(d[1]), "+f"(d[2]), "+f"(d[3]), "+f"(d[4]), "+f"(d[5]), "+f"(d[6]), "+f"(d[7]), "+f"(d[8]), "+f"(d[9]), "+f"(d[10]), "+f"(d[11]), "+f"(d[12]), "+f"(d[13]), "+f"(d[14]), "+f"(d[15]), "+f"(d[16]), "+f"(d[17]), "+f"(d[18]), "+f"(d[19])
      : "l"(da), "l"(db));
  } else {
    asm volatile("{\n.reg .pred p;\nsetp.ne.b32 p, 0, 0;\n"
      "wgmma.mma_async.sync.aligned.m64n40k16.f32.bf16.bf16 "
      "{%0, %1, %2, %3, %4, %5, %6, %7, %8, %9, %10, %11, %12, %13, %14, %15, %16, %17, %18, %19}, "
      "%20, %21, p, 1, 1, 1, 1;\n}\n"
      : "=f"(d[0]), "=f"(d[1]), "=f"(d[2]), "=f"(d[3]), "=f"(d[4]), "=f"(d[5]), "=f"(d[6]), "=f"(d[7]), "=f"(d[8]), "=f"(d[9]), "=f"(d[10]), "=f"(d[11]), "=f"(d[12]), "=f"(d[13]), "=f"(d[14]), "=f"(d[15]), "=f"(d[16]), "=f"(d[17]), "=f"(d[18]), "=f"(d[19])
      : "l"(da), "l"(db));
  }
}
__device__ __forceinline__ void wgmma_n128_rs_ta0_tb1(float* d, uint32_t a0, uint32_t a1, uint32_t a2, uint32_t a3, uint64_t db, bool accumulate) {
  if (accumulate) {
    asm volatile("{\n.reg .pred p;\nsetp.ne.b32 p, 1, 0;\n"
      "wgmma.mma_async.sync.aligned.m64n128k16.f32.bf16.bf16 "
      "{%0, %1, %2, %3, %4, %5, %6, %7, %8, %9, %10, %11, %12, %13, %14, %15, %16, %17, %18, %19, %20, %21, %22, %23, %24, %25, %26, %27, %28, %29, %30, %31, %32, %33, %34, %35, %36, %37, %38, %39, %40, %41, %42, %43, %44, %45, %46, %47, %48, %49, %50, %51, %52, %53, %54, %55, %56, %57, %58, %59, %60, %61, %62, %63}, "
      "{%64, %65, %66, %67}, %68, p, 1, 1, 1;\n}\n"
      : "+f"(d[0]), "+f"(d[1]), "+f"(d[2]), "+f"(d[3]), "+f"(d[4]), "+f"(d[5]), "+f"(d[6]), "+f"(d[7]), "+f"(d[8]), "+f"(d[9]), "+f"(d[10]), "+f"(d[11]), "+f"(d[12]), "+f"(d[13]), "+f"(d[14]), "+f"(d[15]), "+f"(d[16]), "+f"(d[17]), "+f"(d[18]), "+f"(d[19]), "+f"(d[20]), "+f"(d[21]), "+f"(d[22]), "+f"(d[23]), "+f"(d[24]), "+f"(d[25]), "+f"(d[26]), "+f"(d[27]), "+f"(d[28]), "+f"(d[29]), "+f"(d[30]), "+f"(d[31]), "+f"(d[32]), "+f"(d[33]), "+f"(d[34]), "+f"(d[35]), "+f"(d[36]), "+f"(d[37]), "+f"(d[38]), "+f"(d[39]), "+f"(d[40]), "+f"(d[41]), "+f"(d[42]), "+f"(d[43]), "+f"(d[44]), "+f"(d[45]), "+f"(d[46]), "+f"(d[47]), "+f"(d[48]), "+f"(d[49]), "+f"(d[50]), "+f"(d[51]), "+f"(d[52]), "+f"(d[53]), "+f"(d[54]), "+f"(d[55]), "+f"(d[56]), "+f"(d[57]), "+f"(d[58]), "+f"(d[59]), "+f"(d[60]), "+f"(d[61]), "+f"(d[62]), "+f"(d[63])
      : "r"(a0), "r"(a1), "r"(a2), "r"(a3), "l"(db));
  } else {
    asm volatile("{\n.reg .pred p;\nsetp.ne.b32 p, 0, 0;\n"
      "wgmma.mma_async.sync.aligned.m64n128k16.f32.bf16.bf16 "
      "{%0, %1, %2, %3, %4, %5, %6, %7, %8, %9, %10, %11, %12, %13, %14, %15, %16, %17, %18, %19, %20, %21, %22, %23, %24, %25, %26, %27, %28, %29, %30, %31, %32, %33, %34, %35, %36, %37, %38, %39, %40, %41, %42, %43, %44, %45, %46, %47, %48, %49, %50, %51, %52, %53, %54, %55, %56, %57, %58, %59, %60, %61, %62, %63}, "
      "{%64, %65, %66, %67}, %68, p, 1, 1, 1;\n}\n"
      : "=f"(d[0]), "=f"(d[1]), "=f"(d[2]), "=f"(d[3]), "=f"(d[4]), "=f"(d[5]), "=f"(d[6]), "=f"(d[7]), "=f"(d[8]), "=f"(d[9]), "=f"(d[10]), "=f"(d[11]), "=f"(d[12]), "=f"(d[13]), "=f"(d[14]), "=f"(d[15]), "=f"(d[16]), "=f"(d[17]), "=f"(d[18]), "=f"(d[19]), "=f"(d[20]), "=f"(d[21]), "=f"(d[22]), "=f"(d[23]), "=f"(d[24]), "=f"(d[25]), "=f"(d[26]), "=f"(d[27]), "=f"(d[28]), "=f"(d[29]), "=f"(d[30]), "=f"(d[31]), "=f"(d[32]), "=f"(d[33]), "=f"(d[34]), "=f"(d[35]), "=f"(d[36]), "=f"(d[37]), "=f"(d[38]), "=f"(d[39]), "=f"(d[40]), "=f"(d[41]), "=f"(d[42]), "=f"(d[43]), "=f"(d[44]), "=f"(d[45]), "=f"(d[46]), "=f"(d[47]), "=f"(d[48]), "=f"(d[49]), "=f"(d[50]), "=f"(d[51]), "=f"(d[52]), "=f"(d[53]), "=f"(d[54]), "=f"(d[55]), "=f"(d[56]), "=f"(d[57]), "=f"(d[58]), "=f"(d[59]), "=f"(d[60]), "=f"(d[61]), "=f"(d[62]), "=f"(d[63])
      : "r"(a0), "r"(a1), "r"(a2), "r"(a3), "l"(db));
  }
}
__device__ __forceinline__ void wgmma_n128_ss_ta0_tb1(float* d, uint64_t da, uint64_t db, bool accumulate) {
  if (accumulate) {
    asm volatile("{\n.reg .pred p;\nsetp.ne.b32 p, 1, 0;\n"
      "wgmma.mma_async.sync.aligned.m64n128k16.f32.bf16.bf16 "
      "{%0, %1, %2, %3, %4, %5, %6, %7, %8, %9, %10, %11, %12, %13, %14, %15, %16, %17, %18, %19, %20, %21, %22, %23, %24, %25, %26, %27, %28, %29, %30, %31, %32, %33, %34, %35, %36, %37, %38, %39, %40, %41, %42, %43, %44, %45, %46, %47, %48, %49, %50, %51, %52, %53, %54, %55, %56, %57, %58, %59, %60, %61, %62, %63}, "
      "%64, %65, p, 1, 1, 0, 1;\n}\n"
      : "+f"(d[0]), "+f"(d[1]), "+f"(d[2]), "+f"(d[3]), "+f"(d[4]), "+f"(d[5]), "+f"(d[6]), "+f"(d[7]), "+f"(d[8]), "+f"(d[9]), "+f"(d[10]), "+f"(d[11]), "+f"(d[12]), "+f"(d[13]), "+f"(d[14]), "+f"(d[15]), "+f"(d[16]), "+f"(d[17]), "+f"(d[18]), "+f"(d[19]), "+f"(d[20]), "+f"(d[21]), "+f"(d[22]), "+f"(d[23]), "+f"(d[24]), "+f"(d[25]), "+f"(d[26]), "+f"(d[27]), "+f"(d[28]), "+f"(d[29]), "+f"(d[30]), "+f"(d[31]), "+f"(d[32]), "+f"(d[33]), "+f"(d[34]), "+f"(d[35]), "+f"(d[36]), "+f"(d[37]), "+f"(d[38]), "+f"(d[39]), "+f"(d[40]), "+f"(d[41]), "+f"(d[42]), "+f"(d[43]), "+f"(d[44]), "+f"(d[45]), "+f"(d[46]), "+f"(d[47]), "+f"(d[48]), "+f"(d[49]), "+f"(d[50]), "+f"(d[51]), "+f"(d[52]), "+f"(d[53]), "+f"(d[54]), "+f"(d[55]), "+f"(d[56]), "+f"(d[57]), "+f"(d[58]), "+f"(d[59]), "+f"(d[60]), "+f"(d[61]), "+f"(d[62]), "+f"(d[63])
      : "l"(da), "l"(db));
  } else {
    asm volatile("{\n.reg .pred p;\nsetp.ne.b32 p, 0, 0;\n"
      "wgmma.mma_async.sync.aligned.m64n128k16.f32.bf16.bf16 "
      "{%0, %1, %2, %3, %4, %5, %6, %7, %8, %9, %10, %11, %12, %13, %14, %15, %16, %17, %18, %19, %20, %21, %22, %23, %24, %25, %26, %27, %28, %29, %30, %31, %32, %33, %34, %35, %36, %37, %38, %39, %40, %41, %42, %43, %44, %45, %46, %47, %48, %49, %50, %51, %52, %53, %54, %55, %56, %57, %58, %59, %60, %61, %62, %63}, "
      "%64, %65, p, 1, 1, 0, 1;\n}\n"
      : "=f"(d[0]), "=f"(d[1]), "=f"(d[2]), "=f"(d[3]), "=f"(d[4]), "=f"(d[5]), "=f"(d[6]), "=f"(d[7]), "=f"(d[8]), "=f"(d[9]), "=f"(d[10]), "=f"(d[11]), "=f"(d[12]), "=f"(d[13]), "=f"(d[14]), "=f"(d[15]), "=f"(d[16]), "=f"(d[17]), "=f"(d[18]), "=f"(d[19]), "=f"(d[20]), "=f"(d[21]), "=f"(d[22]), "=f"(d[23]), "=f"(d[24]), "=f"(d[25]), "=f"(d[26]), "=f"(d[27]), "=f"(d[28]), "=f"(d[29]), "=f"(d[30]), "=f"(d[31]), "=f"(d[32]), "=f"(d[33]), "=f"(d[34]), "=f"(d[35]), "=f"(d[36]), "=f"(d[37]), "=f"(d[38]), "=f"(d[39]), "=f"(d[40]), "=f"(d[41]), "=f"(d[42]), "=f"(d[43]), "=f"(d[44]), "=f"(d[45]), "=f"(d[46]), "=f"(d[47]), "=f"(d[48]), "=f"(d[49]), "=f"(d[50]), "=f"(d[51]), "=f"(d[52]), "=f"(d[53]), "=f"(d[54]), "=f"(d[55]), "=f"(d[56]), "=f"(d[57]), "=f"(d[58]), "=f"(d[59]), "=f"(d[60]), "=f"(d[61]), "=f"(d[62]), "=f"(d[63])
      : "l"(da), "l"(db));
  }
}
__device__ __forceinline__ void wgmma_n256_rs_ta0_tb1(float* d, uint32_t a0, uint32_t a1, uint32_t a2, uint32_t a3, uint64_t db, bool accumulate) {
  if (accumulate) {
    asm volatile("{\n.reg .pred p;\nsetp.ne.b32 p, 1, 0;\n"
      "wgmma.mma_async.sync.aligned.m64n256k16.f32.bf16.bf16 "
      "{%0, %1, %2, %3, %4, %5, %6, %7, %8, %9, %10, %11, %12, %13, %14, %15, %16, %17, %18, %19, %20, %21, %22, %23, %24, %25, %26, %27, %28, %29, %30, %31, %32, %33, %34, %35, %36, %37, %38, %39, %40, %41, %42, %43, %44, %45, %46, %47, %48, %49, %50, %51, %52, %53, %54, %55, %56, %57, %58, %59, %60, %61, %62, %63, %64, %65, %66, %67, %68, %69, %70, %71, %72, %73, %74, %75, %76, %77, %78, %79, %80, %81, %82, %83, %84, %85, %86, %87, %88, %89, %90, %91, %92, %93, %94, %95, %96, %97, %98, %99, %100, %101, %102, %103, %104, %105, %106, %107, %108, %109, %110, %111, %112, %113, %114, %115, %116, %117, %118, %119, %120, %121, %122, %123, %124, %125, %126, %127}, "
      "{%128, %129, %130, %131}, %132, p, 1, 1, 1;\n}\n"
      : "+f"(d[0]), "+f"(d[1]), "+f"(d[2]), "+f"(d[3]), "+f"(d[4]), "+f"(d[5]), "+f"(d[6]), "+f"(d[7]), "+f"(d[8]), "+f"(d[9]), "+f"(d[10]), "+f"(d[11]), "+f"(d[12]), "+f"(d[13]), "+f"(d[14]), "+f"(d[15]), "+f"(d[16]), "+f"(d[17]), "+f"(d[18]), "+f"(d[19]), "+f"(d[20]), "+f"(d[21]), "+f"(d[22]), "+f"(d[23]), "+f"(d[24]), "+f"(d[25]), "+f"(d[26]), "+f"(d[27]), "+f"(d[28]), "+f"(d[29]), "+f"(d[30]), "+f"(d[31]), "+f"(d[32]), "+f"(d[33]), "+f"(d[34]), "+f"(d[35]), "+f"(d[36]), "+f"(d[37]), "+f"(d[38]), "+f"(d[39]), "+f"(d[40]), "+f"(d[41]), "+f"(d[42]), "+f"(d[43]), "+f"(d[44]), "+f"(d[45]), "+f"(d[46]), "+f"(d[47]), "+f"(d[48]), "+f"(d[49]), "+f"(d[50]), "+f"(d[51]), "+f"(d[52]), "+f"(d[53]), "+f"(d[54]), "+f"(d[55]), "+f"(d[56]), "+f"(d[57]), "+f"(d[58]), "+f"(d[59]), "+f"(d[60]), "+f"(d[61]), "+f"(d[62]), "+f"(d[63]), "+f"(d[64]), "+f"(d[65]), "+f"(d[66]), "+f"(d[67]), "+f"(d[68]), "+f"(d[69]), "+f"(d[70]), "+f"(d[71]), "+f"(d[72]), "+f"(d[73]), "+f"(d[74]), "+f"(d[75]), "+f"(d[76]), "+f"(d[77]), "+f"(d[78]), "+f"(d[79]), "+f"(d[80]), "+f"(d[81]), "+f"(d[82]), "+f"(d[83]), "+f"(d[84]), "+f"(d[85]), "+f"(d[86]), "+f"(d[87]), "+f"(d[88]), "+f"(d[89]), "+f"(d[90]), "+f"(d[91]), "+f"(d[92]), "+f"(d[93]), "+f"(d[94]), "+f"(d[95]), "+f"(d[96]), "+f"(d[97]), "+f"(d[98]), "+f"(d[99]), "+f"(d[100]), "+f"(d[101]), "+f"(d[102]), "+f"(d[103]), "+f"(d[104]), "+f"(d[105]), "+f"(d[106]), "+f"(d[107]), "+f"(d[108]), "+f"(d[109]), "+f"(d[110]), "+f"(d[111]), "+f"(d[112]), "+f"(d[113]), "+f"(d[114]), "+f"(d[115]), "+f"(d[116]), "+f"(d[117]), "+f"(d[118]), "+f"(d[119]), "+f"(d[120]), "+f"(d[121]), "+f"(d[122]), "+f"(d[123]), "+f"(d[124]), "+f"(d[125]), "+f"(d[126]), "+f"(d[127])
      : "r"(a0), "r"(a1), "r"(a2), "r"(a3), "l"(db));
  } else {
    asm volatile("{\n.reg .pred p;\nsetp.ne.b32 p, 0, 0;\n"
      "wgmma.mma_async.sync.aligned.m64n256k16.f32.bf16.bf16 "
      "{%0, %1, %2, %3, %4, %5, %6, %7, %8, %9, %10, %11, %12, %13, %14, %15, %16, %17, %18, %19, %20, %21, %22, %23, %24, %25, %26, %27, %28, %29, %30, %31, %32, %33, %34, %35, %36, %37, %38, %39, %40, %41, %42, %43, %44, %45, %46, %47, %48, %49, %50, %51, %52, %53, %54, %55, %56, %57, %58, %59, %60, %61, %62, %63, %64, %65, %66, %67, %68, %69, %70, %71, %72, %73, %74, %75, %76, %77, %78, %79, %80, %81, %82, %83, %84, %85, %86, %87, %88, %89, %90, %91, %92, %93, %94, %95, %96, %97, %98, %99, %100, %101, %102, %103, %104, %105, %106, %107, %108, %109, %110, %111, %112, %113, %114, %115, %116, %117, %118, %119, %120, %121, %122, %123, %124, %125, %126, %127}, "
      "{%128, %129, %130, %131}, %132, p, 1, 1, 1;\n}\n"
      : "=f"(d[0]), "=f"(d[1]), "=f"(d[2]), "=f"(d[3]), "=f"(d[4]), "=f"(d[5]), "=f"(d[6]), "=f"(d[7]), "=f"(d[8]), "=f"(d[9]), "=f"(d[10]), "=f"(d[11]), "=f"(d[12]), "=f"(d[13]), "=f"(d[14]), "=f"(d[15]), "=f"(d[16]), "=f"(d[17]), "=f"(d[18]), "=f"(d[19]), "=f"(d[20]), "=f"(d[21]), "=f"(d[22]), "=f"(d[23]), "=f"(d[24]), "=f"(d[25]), "=f"(d[26]), "=f"(d[27]), "=f"(d[28]), "=f"(d[29]), "=f"(d[30]), "=f"(d[31]), "=f"(d[32]), "=f"(d[33]), "=f"(d[34]), "=f"(d[35]), "=f"(d[36]), "=f"(d[37]), "=f"(d[38]), "=f"(d[39]), "=f"(d[40]), "=f"(d[41]), "=f"(d[42]), "=f"(d[43]), "=f"(d[44]), "=f"(d[45]), "=f"(d[46]), "=f"(d[47]), "=f"(d[48]), "=f"(d[49]), "=f"(d[50]), "=f"(d[51]), "=f"(d[52]), "=f"(d[53]), "=f"(d[54]), "=f"(d[55]), "=f"(d[56]), "=f"(d[57]), "=f"(d[58]), "=f"(d[59]), "=f"(d[60]), "=f"(d[61]), "=f"(d[62]), "=f"(d[63]), "=f"(d[64]), "=f"(d[65]), "=f"(d[66]), "=f"(d[67]), "=f"(d[68]), "=f"(d[69]), "=f"(d[70]), "=f"(d[71]), "=f"(d[72]), "=f"(d[73]), "=f"(d[74]), "=f"(d[75]), "=f"(d[76]), "=f"(d[77]), "=f"(d[78]), "=f"(d[79]), "=f"(d[80]), "=f"(d[81]), "=f"(d[82]), "=f"(d[83]), "=f"(d[84]), "=f"(d[85]), "=f"(d[86]), "=f"(d[87]), "=f"(d[88]), "=f"(d[89]), "=f"(d[90]), "=f"(d[91]), "=f"(d[92]), "=f"(d[93]), "=f"(d[94]), "=f"(d[95]), "=f"(d[96]), "=f"(d[97]), "=f"(d[98]), "=f"(d[99]), "=f"(d[100]), "=f"(d[101]), "=f"(d[102]), "=f"(d[103]), "=f"(d[104]), "=f"(d[105]), "=f"(d[106]), "=f"(d[107]), "=f"(d[108]), "=f"(d[109]), "=f"(d[110]), "=f"(d[111]), "=f"(d[112]), "=f"(d[113]), "=f"(d[114]), "=f"(d[115]), "=f"(d[116]), "=f"(d[117]), "=f"(d[118]), "=f"(d[119]), "=f"(d[120]), "=f"(d[121]), "=f"(d[122]), "=f"(d[123]), "=f"(d[124]), "=f"(d[125]), "=f"(d[126]), "=f"(d[127])
      : "r"(a0), "r"(a1), "r"(a2), "r"(a3), "l"(db));
  }
}
__device__ __forceinline__ void wgmma_n256_ss_ta0_tb1(float* d, uint64_t da, uint64_t db, bool accumulate) {
  if (accumulate) {
    asm volatile("{\n.reg .pred p;\nsetp.ne.b32 p, 1, 0;\n"
      "wgmma.mma_async.sync.aligned.m64n256k16.f32.bf16.bf16 "
      "{%0, %1, %2, %3, %4, %5, %6, %7, %8, %9, %10, %11, %12, %13, %14, %15, %16, %17, %18, %19, %20, %21, %22, %23, %24, %25, %26, %27, %28, %29, %30, %31, %32, %33, %34, %35, %36, %37, %38, %39, %40, %41, %42, %43, %44, %45, %46, %47, %48, %49, %50, %51, %52, %53, %54, %55, %56, %57, %58, %59, %60, %61, %62, %63, %64, %65, %66, %67, %68, %69, %70, %71, %72, %73, %74, %75, %76, %77, %78, %79, %80, %81, %82, %83, %84, %85, %86, %87, %88, %89, %90, %91, %92, %93, %94, %95, %96, %97, %98, %99, %100, %101, %102, %103, %104, %105, %106, %107, %108, %109, %110, %111, %112, %113, %114, %115, %116, %117, %118, %119, %120, %121, %122, %123, %124, %125, %126, %127}, "
      "%128, %129, p, 1, 1, 0, 1;\n}\n"
      : "+f"(d[0]), "+f"(d[1]), "+f"(d[2]), "+f"(d[3]), "+f"(d[4]), "+f"(d[5]), "+f"(d[6]), "+f"(d[7]), "+f"(d[8]), "+f"(d[9]), "+f"(d[10]), "+f"(d[11]), "+f"(d[12]), "+f"(d[13]), "+f"(d[14]), "+f"(d[15]), "+f"(d[16]), "+f"(d[17]), "+f"(d[18]), "+f"(d[19]), "+f"(d[20]), "+f"(d[21]), "+f"(d[22]), "+f"(d[23]), "+f"(d[24]), "+f"(d[25]), "+f"(d[26]), "+f"(d[27]), "+f"(d[28]), "+f"(d[29]), "+f"(d[30]), "+f"(d[31]), "+f"(d[32]), "+f"(d[33]), "+f"(d[34]), "+f"(d[35]), "+f"(d[36]), "+f"(d[37]), "+f"(d[38]), "+f"(d[39]), "+f"(d[40]), "+f"(d[41]), "+f"(d[42]), "+f"(d[43]), "+f"(d[44]), "+f"(d[45]), "+f"(d[46]), "+f"(d[47]), "+f"(d[48]), "+f"(d[49]), "+f"(d[50]), "+f"(d[51]), "+f"(d[52]), "+f"(d[53]), "+f"(d[54]), "+f"(d[55]), "+f"(d[56]), "+f"(d[57]), "+f"(d[58]), "+f"(d[59]), "+f"(d[60]), "+f"(d[61]), "+f"(d[62]), "+f"(d[63]), "+f"(d[64]), "+f"(d[65]), "+f"(d[66]), "+f"(d[67]), "+f"(d[68]), "+f"(d[69]), "+f"(d[70]), "+f"(d[71]), "+f"(d[72]), "+f"(d[73]), "+f"(d[74]), "+f"(d[75]), "+f"(d[76]), "+f"(d[77]), "+f"(d[78]), "+f"(d[79]), "+f"(d[80]), "+f"(d[81]), "+f"(d[82]), "+f"(d[83]), "+f"(d[84]), "+f"(d[85]), "+f"(d[86]), "+f"(d[87]), "+f"(d[88]), "+f"(d[89]), "+f"(d[90]), "+f"(d[91]), "+f"(d[92]), "+f"(d[93]), "+f"(d[94]), "+f"(d[95]), "+f"(d[96]), "+f"(d[97]), "+f"(d[98]), "+f"(d[99]), "+f"(d[100]), "+f"(d[101]), "+f"(d[102]), "+f"(d[103]), "+f"(d[104]), "+f"(d[105]), "+f"(d[106]), "+f"(d[107]), "+f"(d[108]), "+f"(d[109]), "+f"(d[110]), "+f"(d[111]), "+f"(d[112]), "+f"(d[113]), "+f"(d[114]), "+f"(d[115]), "+f"(d[116]), "+f"(d[117]), "+f"(d[118]), "+f"(d[119]), "+f"(d[120]), "+f"(d[121]), "+f"(d[122]), "+f"(d[123]), "+f"(d[124]), "+f"(d[125]), "+f"(d[126]), "+f"(d[127])
      : "l"(da), "l"(db));
  } else {
    asm volatile("{\n.reg .pred p;\nsetp.ne.b32 p, 0, 0;\n"
      "wgmma.mma_async.sync.aligned.m64n256k16.f32.bf16.bf16 "
      "{%0, %1, %2, %3, %4, %5, %6, %7, %8, %9, %10, %11, %12, %13, %14, %15, %16, %17, %18, %19, %20, %21, %22, %23, %24, %25, %26, %27, %28, %29, %30, %31, %32, %33, %34, %35, %36, %37, %38, %39, %40, %41, %42, %43, %44, %45, %46, %47, %48, %49, %50, %51, %52, %53, %54, %55, %56, %57, %58, %59, %60, %61, %62, %63, %64, %65, %66, %67, %68, %69, %70, %71, %72, %73, %74, %75, %76, %77, %78, %79, %80, %81, %82, %83, %84, %85, %86, %87, %88, %89, %90, %91, %92, %93, %94, %95, %96, %97, %98, %99, %100, %101, %102, %103, %104, %105, %106, %107, %108, %109, %110, %111, %112, %113, %114, %115, %116, %117, %118, %119, %120, %121, %122, %123, %124, %125, %126, %127}, "
      "%128, %129, p, 1, 1, 0, 1;\n}\n"
      : "=f"(d[0]), "=f"(d[1]), "=f"(d[2]), "=f"(d[3]), "=f"(d[4]), "=f"(d[5]), "=f"(d[6]), "=f"(d[7]), "=f"(d[8]), "=f"(d[9]), "=f"(d[10]), "=f"(d[11]), "=f"(d[12]), "=f"(d[13]), "=f"(d[14]), "=f"(d[15]), "=f"(d[16]), "=f"(d[17]), "=f"(d[18]), "=f"(d[19]), "=f"(d[20]), "=f"(d[21]), "=f"(d[22]), "=f"(d[23]), "=f"(d[24]), "=f"(d[25]), "=f"(d[26]), "=f"(d[27]), "=f"(d[28]), "=f"(d[29]), "=f"(d[30]), "=f"(d[31]), "=f"(d[32]), "=f"(d[33]), "=f"(d[34]), "=f"(d[35]), "=f"(d[36]), "=f"(d[37]), "=f"(d[38]), "=f"(d[39]), "=f"(d[40]), "=f"(d[41]), "=f"(d[42]), "=f"(d[43]), "=f"(d[44]), "=f"(d[45]), "=f"(d[46]), "=f"(d[47]), "=f"(d[48]), "=f"(d[49]), "=f"(d[50]), "=f"(d[51]), "=f"(d[52]), "=f"(d[53]), "=f"(d[54]), "=f"(d[55]), "=f"(d[56]), "=f"(d[57]), "=f"(d[58]), "=f"(d[59]), "=f"(d[60]), "=f"(d[61]), "=f"(d[62]), "=f"(d[63]), "=f"(d[64]), "=f"(d[65]), "=f"(d[66]), "=f"(d[67]), "=f"(d[68]), "=f"(d[69]), "=f"(d[70]), "=f"(d[71]), "=f"(d[72]), "=f"(d[73]), "=f"(d[74]), "=f"(d[75]), "=f"(d[76]), "=f"(d[77]), "=f"(d[78]), "=f"(d[79]), "=f"(d[80]), "=f"(d[81]), "=f"(d[82]), "=f"(d[83]), "=f"(d[84]), "=f"(d[85]), "=f"(d[86]), "=f"(d[87]), "=f"(d[88]), "=f"(d[89]), "=f"(d[90]), "=f"(d[91]), "=f"(d[92]), "=f"(d[93]), "=f"(d[94]), "=f"(d[95]), "=f"(d[96]), "=f"(d[97]), "=f"(d[98]), "=f"(d[99]), "=f"(d[100]), "=f"(d[101]), "=f"(d[102]), "=f"(d[103]), "=f"(d[104]), "=f"(d[105]), "=f"(d[106]), "=f"(d[107]), "=f"(d[108]), "=f"(d[109]), "=f"(d[110]), "=f"(d[111]), "=f"(d[112]), "=f"(d[113]), "=f"(d[114]), "=f"(d[115]), "=f"(d[116]), "=f"(d[117]), "=f"(d[118]), "=f"(d[119]), "=f"(d[120]), "=f"(d[121]), "=f"(d[122]), "=f"(d[123]), "=f"(d[124]), "=f"(d[125]), "=f"(d[126]), "=f"(d[127])
      : "l"(da), "l"(db));
  }
}
__device__ __forceinline__ void wgmma_n256_ssp_ta0_tb1(float* d, uint64_t da, uint64_t db, int accumulate) {
    asm volatile("{\n.reg .pred p;\nsetp.ne.b32 p, %130, 0;\n"
      "wgmma.mma_async.sync.aligned.m64n256k16.f32.bf16.bf16 "
      "{%0, %1, %2, %3, %4, %5, %6, %7, %8, %9, %10, %11, %12, %13, %14, %15, %16, %17, %18, %19, %20, %21, %22, %23, %24, %25, %26, %27, %28, %29, %30, %31, %32, %33, %34, %35, %36, %37, %38, %39, %40, %41, %42, %43, %44, %45, %46, %47, %48, %49, %50, %51, %52, %53, %54, %55, %56, %57, %58, %59, %60, %61, %62, %63, %64, %65, %66, %67, %68, %69, %70, %71, %72, %73, %74, %75, %76, %77, %78, %79, %80, %81, %82, %83, %84, %85, %86, %87, %88, %89, %90, %91, %92, %93, %94, %95, %96, %97, %98, %99, %100, %101, %102, %103, %104, %105, %106, %107, %108, %109, %110, %111, %112, %113, %114, %115, %116, %117, %118, %119, %120, %121, %122, %123, %124, %125, %126, %127}, "
      "%128, %129, p, 1, 1, 0, 1;\n}\n"
      : "+f"(d[0]), "+f"(d[1]), "+f"(d[2]), "+f"(d[3]), "+f"(d[4]), "+f"(d[5]), "+f"(d[6]), "+f"(d[7]), "+f"(d[8]), "+f"(d[9]), "+f"(d[10]), "+f"(d[11]), "+f"(d[12]), "+f"(d[13]), "+f"(d[14]), "+f"(d[15]), "+f"(d[16]), "+f"(d[17]), "+f"(d[18]), "+f"(d[19]), "+f"(d[20]), "+f"(d[21]), "+f"(d[22]), "+f"(d[23]), "+f"(d[24]), "+f"(d[25]), "+f"(d[26]), "+f"(d[27]), "+f"(d[28]), "+f"(d[29]), "+f"(d[30]), "+f"(d[31]), "+f"(d[32]), "+f"(d[33]), "+f"(d[34]), "+f"(d[35]), "+f"(d[36]), "+f"(d[37]), "+f"(d[38]), "+f"(d[39]), "+f"(d[40]), "+f"(d[41]), "+f"(d[42]), "+f"(d[43]), "+f"(d[44]), "+f"(d[45]), "+f"(d[46]), "+f"(d[47]), "+f"(d[48]), "+f"(d[49]), "+f"(d[50]), "+f"(d[51]), "+f"(d[52]), "+f"(d[53]), "+f"(d[54]), "+f"(d[55]), "+f"(d[56]), "+f"(d[57]), "+f"(d[58]), "+f"(d[59]), "+f"(d[60]), "+f"(d[61]), "+f"(d[62]), "+f"(d[63]), "+f"(d[64]), "+f"(d[65]), "+f"(d[66]), "+f"(d[67]), "+f"(d[68]), "+f"(d[69]), "+f"(d[70]), "+f"(d[71]), "+f"(d[72]), "+f"(d[73]), "+f"(d[74]), "+f"(d[75]), "+f"(d[76]), "+f"(d[77]), "+f"(d[78]), "+f"(d[79]), "+f"(d[80]), "+f"(d[81]), "+f"(d[82]), "+f"(d[83]), "+f"(d[84]), "+f"(d[85]), "+f"(d[86]), "+f"(d[87]), "+f"(d[88]), "+f"(d[89]), "+f"(d[90]), "+f"(d[91]), "+f"(d[92]), "+f"(d[93]), "+f"(d[94]), "+f"(d[95]), "+f"(d[96]), "+f"(d[97]), "+f"(d[98]), "+f"(d[99]), "+f"(d[100]), "+f"(d[101]), "+f"(d[102]), "+f"(d[103]), "+f"(d[104]), "+f"(d[105]), "+f"(d[106]), "+f"(d[107]), "+f"(d[108]), "+f"(d[109]), "+f"(d[110]), "+f"(d[111]), "+f"(d[112]), "+f"(d[113]), "+f"(d[114]), "+f"(d[115]), "+f"(d[116]), "+f"(d[117]), "+f"(d[118]), "+f"(d[119]), "+f"(d[120]), "+f"(d[121]), "+f"(d[122]), "+f"(d[123]), "+f"(d[124]), "+f"(d[125]), "+f"(d[126]), "+f"(d[127])
      : "l"(da), "l"(db), "r"(accumulate));
}

template <int N> __device__ __forceinline__ void quad_sum(float* m) {
#pragma unroll
  for (int o = 1; o <= 2; o <<= 1) {
    float t[N];
#pragma unroll
    for (int i = 0; i < N; i++) t[i] = __shfl_xor_sync(~0u, m[i], o);
#pragma unroll
    for (int i = 0; i < N; i++) m[i] += t[i];
  }
}
__device__ __forceinline__ bool softmax_unsafe(const uint32_t* t, float l0, float l1) {
  const float m0 = fmaxf(bf_lo(t[0]) + bf_hi(t[0]), bf_lo(t[2]) + bf_hi(t[2])), m1 = fmaxf(bf_lo(t[1]) + bf_hi(t[1]), bf_lo(t[3]) + bf_hi(t[3]));
  return __any_sync(~0u, !(m0 * l0 < 2500.f) | !(m1 * l1 < 2500.f));
}
__device__ __forceinline__ void softmax_shift(float* p, float c0, float c1) {
#pragma unroll 1
  for (int it = 0; it < 8; it++) {
    float mx = p[0], mn = p[0];
#pragma unroll
    for (int j = 1; j < 8; j++) { mx = fmaxf(mx, p[(j >> 1) * 4 + (j & 1)]); mn = fminf(mn, p[(j >> 1) * 4 + (j & 1)]); }
#pragma unroll
    for (int o = 1; o <= 2; o <<= 1) { mx = fmaxf(mx, __shfl_xor_sync(~0u, mx, o)); mn = fminf(mn, __shfl_xor_sync(~0u, mn, o)); }
    const float half = fminf(0.5f * (mx - mn), 50.f * rcp(it & 1 ? c1 : c0));
    float r[8];
#pragma unroll
    for (int j = 0; j < 8; j++) {
      const float v = p[(j >> 1) * 4 + (j & 1)];
      r[j] = fmaxf(v - mx + half, 0.f) + fminf(v - mn - half, 0.f) + (v - v);
    }
#pragma unroll
    for (int k = 0; k < 7; k++)
#pragma unroll
      for (int j = 0; j < 8; j++) p[(k >> 1) * 16 + (k & 1) * 2 + (j >> 1) * 4 + (j & 1)] = p[((k + 1) >> 1) * 16 + ((k + 1) & 1) * 2 + (j >> 1) * 4 + (j & 1)];
#pragma unroll
    for (int j = 0; j < 8; j++) p[50 + (j >> 1) * 4 + (j & 1)] = r[j];
  }
}
template <int J0 = 0, int J1 = 8> __device__ __forceinline__ void k_exp(const float* p, float c0, float c1, float* e, float* s) {
#pragma unroll
  for (int j = J0; j < J1; j++) {
    e[2 * j] = ex2(p[2 * j] * (j & 1 ? c1 : c0));
    e[2 * j + 1] = ex2(p[2 * j + 1] * (j & 1 ? c1 : c0));
    e[16 + j] = rcp(e[2 * j] * e[2 * j + 1]);
    const float t = e[2 * j] + e[2 * j + 1];
    s[j & 1] = j < 2 ? t : s[j & 1] + t;
    s[2 + (j & 1)] = j < 2 ? e[16 + j] * t : fmaf(e[16 + j], t, s[2 + (j & 1)]);
  }
}
template <int J0 = 0, int J1 = 8> __device__ __forceinline__ void q_exp(const float* p, float c0, float c1, uint32_t* f) {
#pragma unroll
  for (int j = J0; j < J1; j++) {
    const float e0 = ex2(p[2 * j] * (j & 1 ? c1 : c0)), e1 = ex2(p[2 * j + 1] * (j & 1 ? c1 : c0)), r = rcp(e0 * e1);
    f[j] = pack2(e0, e1);
    f[8 + j] = bmul2(f[j], pack2(r, r));
  }
}

#define FMA8(A, U, X)                                                                                        \
  A[0] = fmaf(bf_lo(U.x), X, A[0]); A[1] = fmaf(bf_hi(U.x), X, A[1]); A[2] = fmaf(bf_lo(U.y), X, A[2]); A[3] = fmaf(bf_hi(U.y), X, A[3]); \
  A[4] = fmaf(bf_lo(U.z), X, A[4]); A[5] = fmaf(bf_hi(U.z), X, A[5]); A[6] = fmaf(bf_lo(U.w), X, A[6]); A[7] = fmaf(bf_hi(U.w), X, A[7])

__device__ __forceinline__ uint32_t routed_row(const __nv_bfloat16* x, uint32_t tag, int lane, uint4* xr) {
  uint32_t best = 0, sv = 0;
#pragma unroll 1
  for (int it = 0; it < SPIN_MAX; it++) {
    const uint4 h = ld_rlx128(g_ycnt + 32);
    best = h.x;
    if (__all_sync(~0u, (int)(h.z - tag * NCTA) >= 0)) break;
    __nanosleep(AM_NS);
  }
#pragma unroll 1
  for (int it = 0; it < SPIN_MAX; it++) {
    const int sel = 2047 - (best & 0x7ff);
#pragma unroll
    for (int i = 0; i < 4; i++) xr[i] = ldg_nc(x + (size_t)sel * DM + i * 256 + lane * 8);
    const unsigned long long st = ld_rlx64(g_stat + sel);
    const uint4 b0 = ld_rlx128(g_best + lane * 2), b1 = ld_rlx128(g_best + 64 + lane * 2);
    const uint32_t m = __reduce_max_sync(~0u, max(max(b0.x, b0.z), max(b1.x, b1.z)));
    sv = (uint32_t)st;
    if (__all_sync(~0u, b0.y == tag && b0.w == tag && b1.y == tag && b1.w == tag && m == best && (uint32_t)(st >> 32) == tag)) break;
    best = m;
  }
  const uint32_t m2 = (sv & 0xffff0000u) | (sv >> 16);
  const float rs = rcp(bf_lo(sv));
#pragma unroll
  for (int i = 0; i < 4; i++) {
    const uint32_t d0 = bsub2(xr[i].x, m2), d1 = bsub2(xr[i].y, m2), d2 = bsub2(xr[i].z, m2), d3 = bsub2(xr[i].w, m2);
    xr[i] = make_uint4(pack2(bf_lo(d0) * rs, bf_hi(d0) * rs), pack2(bf_lo(d1) * rs, bf_hi(d1) * rs), pack2(bf_lo(d2) * rs, bf_hi(d2) * rs),
                       pack2(bf_lo(d3) * rs, bf_hi(d3) * rs));
  }
  return best;
}

struct Params {
  const __nv_bfloat16 *x, *wqkv, *wo, *w_r, *w_gate, *w_up, *w_down;
  int by_sm;
};

__global__ void __launch_bounds__(384, 1)
fused_kernel(const __grid_constant__ CUtensorMap mX, const __grid_constant__ CUtensorMap mWkv, const __grid_constant__ CUtensorMap mWq,
             const __grid_constant__ CUtensorMap mWo, const __grid_constant__ CUtensorMap mPhi, const __grid_constant__ CUtensorMap mWp,
             const __grid_constant__ CUtensorMap mOut, const __grid_constant__ CUtensorMap mWc,
             const __grid_constant__ CUtensorMap mG, const __grid_constant__ CUtensorMap mU, const __grid_constant__ CUtensorMap mD,
             const __grid_constant__ CUtensorMap mXs, const __grid_constant__ CUtensorMap mG2, const __grid_constant__ CUtensorMap mU2, const Params P) {
  extern __shared__ __align__(1024) uint8_t smem[];
  if (smem_u32(smem) != SB) return;
  constexpr uint32_t sb = SB, bar = SB + SM_BAR;
  int bid = blockIdx.x;
  if (P.by_sm) {
    uint32_t sm;
    asm volatile("mov.u32 %0, %%smid;" : "=r"(sm));
    const uint32_t tq = (sm - 64) >> 1, q7 = (tq * 37) >> 8;
    const uint32_t gpc = sm < 64 ? (sm >> 1) & 7 : 1 + tq - 7 * q7, idx = (sm < 64 ? sm >> 4 : 4 + q7) * 2 + (sm & 1);
    bid = sm < 120 ? ((PTAB >> (4 * gpc)) & 7) * 16 + idx : sm < 124 ? sm + 8 : sm - 116;
  }
  const int hg = ((bid >> 2) & 3) + 4 * ((bid >> 4) & 1), mb = (bid & 3) + 4 * ((bid >> 5) & 3);
  const int warp = __shfl_sync(~0u, threadIdx.x >> 5, 0);

  if (bid >= NCTA) {
    constexpr uint32_t XV = SM_WPHI, ONES = SM_ZT, BF = bar, BE = bar + 48, BX = bar + 96;
    constexpr int NJ = (DM - GROWS) / 64;
    const int lane = lane_id(), sp = bid - NCTA;
    const uint32_t tag = ld_rlx(g_epoch + bid * 32 + lane) + 1;
    if (warp == 8 && elect_one()) {
#pragma unroll 1
      for (int i = 0; i < 13; i++) mbar_init(bar + 8 * i, i >= 6 && i < 12 ? 8 : 1);
    }
    if (warp == 9) { sts64u(sb + ONES + lane * 8, 0x3f803f80u, 0x3f803f80u); fence_async_smem(); }
    __syncthreads();
    if (warp == 8) {
      if (elect_one()) {
        uint32_t s = 0, ph = 1;
#pragma unroll 1
        for (int job = 0; job < 8; job++) {
          const CUtensorMap* m = job == 0 ? &mWq : sp & 2 ? &mU2 : &mG2;
          const int g0 = job ? (sp & 1) * 28 + job * 4 - 4 : sp * 4;
#pragma unroll 1
          for (int row = job ? GROWS : 0; row < DM; row += 64) {
            mbar_wait(BE + 8 * s, ph);
            mbar_expect_tx(BF + 8 * s, Q_STAGE);
            tma4d(sb + s * Q_STAGE, m, 0, row, g0, 0, BF + 8 * s);
            tma4d(sb + s * Q_STAGE + 16384, m, 0, row, g0 + 2, 0, BF + 8 * s);
            if (++s == 6) { s = 0; ph ^= 1; }
          }
        }
      }
    } else if (warp == 9) {
      uint4 xr[4];
      routed_row(P.x, tag, lane, xr);
#pragma unroll
      for (int i = 0; i < 4; i++) sts128u(sb + XV + i * 512 + lane * 16, xr[i].x, xr[i].y, xr[i].z, xr[i].w);
      fence_async_smem();
      __syncwarp();
      if (lane == 0) mbar_arrive(BX);
    } else if (warp < 8) {
      uint32_t s = 0, ph = 0;
#pragma unroll 1
      for (int job = 0; job < 8; job++) {
        float d[8] = {0.f, 0.f, 0.f, 0.f, 0.f, 0.f, 0.f, 0.f};
        if (job == 1) mbar_wait(BX, 0);
#pragma unroll 1
        for (int i = 0; i < (job ? NJ : 16); i++) {
          mbar_wait(BF + 8 * s, ph);
          wg_fence();
#pragma unroll
          for (int k = 0; k < 8; k++)
            wgmma_n8_ss_ta1_tb0(d + 4 * (k >> 2), mkdesc(sb + k * 2048, 16, 1024, 1, s * (Q_STAGE / 16) + (warp >> 2) * 1024),
                                mkdesc(sb, 16, 128, 0, job ? (XV + GROWS * 2) / 16 + i * 8 + (k & 3) * 2 : ONES / 16), 1);
          wg_commit();
          wg_wait<0>();
          if (lane == 0) mbar_arrive(BE + 8 * s);
          if (++s == 6) { s = 0; ph ^= 1; }
        }
        reg_fence<8>(d);
        float* dst = (job ? g_gp + sp * 1792 + job * 256 - 256 : g_cs + sp * 256) + (warp >> 2) * 128 + (warp & 3) * 16 + (lane >> 2);
        if ((lane & 3) == 0) {
#pragma unroll
          for (int i = 0; i < 4; i++) st_rlx(dst + (i >> 1) * 64 + (i & 1) * 8, mark(__float_as_uint(d[2 * i]), tag & 1));
        }
        __syncwarp();
      }
      if (warp == 0) g_epoch[bid * 32 + lane] = tag;
    }
    return;
  }
#define Q_SLAB(J) ((J) < 8 ? ((J) + 8 - 2 * (hg & 4)) & 15 : 2 * (hg & 4) + 2 * ((J) & 3) + ((J) >> 2 & 1))
#define Q_AOFF(J) ((J) == 8 + (hg & 3) ? SM_X0 : (J) == 12 + (hg & 3) ? SM_X1 : ((J) & 3) * Q_STAGE)
#define Q_LOAD(J)                                                                                            \
  do {                                                                                                       \
    const uint32_t fb_ = bar + B_FULLQ + 8 * ((J) & 3);                                                      \
    const int k_ = Q_SLAB(J) * 64;                                                                           \
    mbar_expect_tx(fb_, Q_STAGE);                                                                            \
    mbar_arrive2(fb_);                                                                                       \
    tma2d(sb + Q_AOFF(J), &mX, k_, mb * 128, fb_);                                                           \
    tma4d(sb + ((J) & 3) * Q_STAGE + 16384, &mWq, 0, k_, hg * 2, 0, fb_);                                    \
  } while (0)
  if (warp >= 8) {
    asm volatile("setmaxnreg.dec.sync.aligned.u32 %0;" ::"n"(REG_H));
    const int lane = lane_id();
    const int f = (warp - 9) & 3;
    const uint32_t ep = ld_rlx(g_epoch + bid * 32 + lane);
    if (f == 3) {
      if (elect_one()) {
        PROF(0); PROFT(32);
#pragma unroll
        for (int j = 0; j < 3; j++) {
          const int s = (j + 2) % 3;
          mbar_init(bar + B_FULLKV + 8 * s, 1);
          mbar_expect_tx(bar + B_FULLKV + 8 * s, KV_STAGE);
          tma2d(sb + s * KV_STAGE, &mX, j * 64, mb * 128, bar + B_FULLKV + 8 * s);
          tma4d(sb + s * KV_STAGE + 16384, &mWkv, 0, j * 64, hg * 2, 1, bar + B_FULLKV + 8 * s);
        }
      }
    } else if (f < 2) {
#pragma unroll
      for (int i = 0; i < 2; i++) {
        const uint4 u = __ldg((const uint4*)P.w_r + (f * 2 + i) * 32 + lane);
        sts128u(sb + SM_XSEL + (f * 2 + i) * 512 + lane * 16, u.x, u.y, u.z, u.w);
      }
    }
    __syncwarp();
    bar_sync(0, 384);
    const uint32_t tag = ep + 1, par = tag & 1;
    const bool ffn = bid < NFFN;
    const int fb = bid, cu = bid >> 1, ch = bid & 1;
#define CS_STORE(SEC, C)                                                                                     \
  _Pragma("unroll") for (int r = 0; r < 3; r++) {                                                            \
    const uint32_t h0 = pack2(C.x, C.y), h1 = pack2(C.z, C.w);                                               \
    sts64u(sb + SM_CST + (SEC) * 1024 + (lane >> 4) * 512 + (lane & 1) * 8 + r * 128 + ((((lane & 15) >> 1) ^ (r + (lane >> 4) * 4)) << 4), h0, h1); \
    C.x -= bf_lo(h0); C.y -= bf_hi(h0); C.z -= bf_lo(h1); C.w -= bf_hi(h1);                                  \
  }
#define BAD4(U) ((U.x ^ par) | (U.y ^ par) | (U.z ^ par) | (U.w ^ par))
    const int n0 = f < 2 ? 0 : 2 * f - 3, ne = FFN_OFF || !ffn ? 3 : f == 3 ? 3 + G8 : 3 + GN;
    const uint32_t fsb = sb + SM_FST + ((f + 1) & 3) * 8192, fbar = bar + B_FST + f * 16, fst = fsb + (lane >> 4) * 2048 + (lane & 15) * 16;
    const CUtensorMap *ma = &mWc, *mc = &mWc;
    int sx = 1024 + cu * 32, sy = ch * 512 + f * 192, sdy = 32;
#define STAGEG(N)                                                                                            \
  do {                                                                                                       \
    if ((N) == 3) { ma = &mG; mc = &mU; sx = fb * 32; sy = f * (GN * 32);  sdy = 0; }                        \
    if ((N) < ne && elect_one()) {                                                                           \
      const uint32_t dst_ = fsb + ((N) & 1) * 4096, b_ = fbar + ((N) & 1) * 8;                               \
      mbar_expect_tx(b_, 4096);                                                                              \
      tma2d(dst_, ma, sx, sy, b_);                                                                           \
      tma2d(dst_ + 2048, mc, sx, sy + sdy, b_);                                                              \
    }                                                                                                        \
    sy += 32 + sdy;                                                                                          \
  } while (0)
    float a[8], gsum = 0.f, usum = 0.f;
    {
      if (f == 3) {
        if (elect_one()) {
          if (XS_EARLY) { mbar_expect_tx(bar + B_XST, 16384); tma3d(sb + SM_XST, &mXs, 0, bid * 16, 0, bar + B_XST); }
          mbar_expect_tx(bar + B_WPHI, 8192);
          tma2d(sb + SM_WPHI, &mPhi, 0, hg * 128, bar + B_WPHI);
          prefetch_map(&mWq); prefetch_map(&mWo); prefetch_map(&mWp); prefetch_map(&mD);
          PROF(31);
        }
        __syncwarp();
      } else {
        if (lane == 0) prefetch_map(f == 0 ? &mWc : f == 1 ? &mG : &mU);
        if (f == 2) ((float2*)g_y[par])[bid * 32 + lane] = make_float2(0.f, 0.f);
      }
      float st[13];
#pragma unroll
      for (int i = 0; i < 13; i++) st[i] = 0.f;
#pragma unroll 1
      for (int i = 0; i < 4; i++) {
        mbar_wait(bar + B_XST + 8 * (i >> 1), 0);
        if (f == 0 && lane == 0 && i == 0) PROF(1);
        const uint4 wu = lds128u(sb + SM_XSEL + i * 512 + lane * 16);
        const float wf[8] = {bf_lo(wu.x), bf_hi(wu.x), bf_lo(wu.y), bf_hi(wu.y), bf_lo(wu.z), bf_hi(wu.z), bf_lo(wu.w), bf_hi(wu.w)};
        st[12] += ((wf[0] + wf[1]) + (wf[2] + wf[3])) + ((wf[4] + wf[5]) + (wf[6] + wf[7]));
#pragma unroll
        for (int r = 0; r < 4; r++) {
          const uint4 u = lds128u(sb + SM_XST + i * 8192 + (4 * f + r) * 512 + lane * 16);
          const float xf[8] = {bf_lo(u.x), bf_hi(u.x), bf_lo(u.y), bf_hi(u.y), bf_lo(u.z), bf_hi(u.z), bf_lo(u.w), bf_hi(u.w)};
#pragma unroll
          for (int k = 0; k < 8; k++) { st[r] += xf[k]; st[4 + r] = fmaf(xf[k], xf[k], st[4 + r]); st[8 + r] = fmaf(xf[k], wf[k], st[8 + r]); }
        }
        if (i >= 2 && f < 3) STAGEG(n0 + i - 2);
      }
      const bool up = lane & 16, up2 = lane & 8;
#pragma unroll
      for (int q = 0; q < 3; q++) {
        const float k0 = up ? st[4 * q + 2] : st[4 * q], k1 = up ? st[4 * q + 3] : st[4 * q + 1];
        const float o0 = up ? st[4 * q] : st[4 * q + 2], o1 = up ? st[4 * q + 1] : st[4 * q + 3];
        const float m0 = k0 + __shfl_xor_sync(~0u, o0, 16), m1 = k1 + __shfl_xor_sync(~0u, o1, 16);
        a[q] = (up2 ? m1 : m0) + __shfl_xor_sync(~0u, up2 ? m0 : m1, 8);
      }
      a[3] = st[12] + __shfl_xor_sync(~0u, st[12], 16);
      a[3] += __shfl_xor_sync(~0u, a[3], 8);
#pragma unroll
      for (int o = 4; o; o >>= 1)
#pragma unroll
        for (int q = 0; q < 4; q++) a[q] += __shfl_xor_sync(~0u, a[q], o);
      if ((lane & 7) == 0) sts128(sb + SM_ROWS + (4 * f + (lane >> 3)) * 16, a[0], a[1], a[2], a[3]);
      if (f < 3) asm volatile("bar.arrive 7, 128;" ::: "memory");
    }
    if (f == 3) {
      bar_sync(7, 128);
      const int row = bid * 16 + (lane & 15);
      const float4 v = lds128(sb + SM_ROWS + (lane & 15) * 16);
      const float mf = v.x * (1.f / DM), mean = bf_round(mf), var = fmaxf(fmaf(-mf, mf, v.y * (1.f / DM)), 0.f);
      const float sd = bf_round(sqrt_approx(bf_round(bf_round(var) + 1e-5f)));
      const uint32_t rb = pack2(fmaf(-mean, v.w, v.z) * rcp(sd), 0.f) & 0xffffu, ord = (rb & 0x8000u) ? (~rb & 0xffffu) : (rb | 0x8000u);
      uint32_t best = __reduce_max_sync(~0u, (ord << 16) | (uint32_t)(2047 - row));
      if (lane < 16) st_rlx64(g_stat + row, ((unsigned long long)tag << 32) | __float_as_uint(mean) | (__float_as_uint(sd) >> 16));
      if (lane < 2) asm volatile("red.relaxed.gpu.global.max.u64 [%0], %1;" ::"l"(lane ? (void*)(g_ycnt + 32) : (void*)(g_best + bid)), "l"(((unsigned long long)tag << 32) | best) : "memory");
      if (lane == 1) { red_inc(g_ycnt + 34); PROF(17); }
#pragma unroll 1
      for (int n = 3; n < 5; n++) STAGEG(n);
      {
        mbar_wait(bar + B_WPHI, 0);
        float nq[8] = {0.f, 0.f, 0.f, 0.f, 0.f, 0.f, 0.f, 0.f};
#pragma unroll 2
        for (int r = 0; r < 16; r++) {
          const uint4 u = lds128u(sb + SM_WPHI + ((lane >> 2) * 16 + r) * 64 + (((lane ^ (r >> 1)) & 3) << 4));
          nq[0] = fmaf(bf_lo(u.x), bf_lo(u.x), nq[0]); nq[1] = fmaf(bf_hi(u.x), bf_hi(u.x), nq[1]); nq[2] = fmaf(bf_lo(u.y), bf_lo(u.y), nq[2]);
          nq[3] = fmaf(bf_hi(u.y), bf_hi(u.y), nq[3]); nq[4] = fmaf(bf_lo(u.z), bf_lo(u.z), nq[4]); nq[5] = fmaf(bf_hi(u.z), bf_hi(u.z), nq[5]);
          nq[6] = fmaf(bf_lo(u.w), bf_lo(u.w), nq[6]); nq[7] = fmaf(bf_hi(u.w), bf_hi(u.w), nq[7]);
        }
        uint32_t m = 0;
#pragma unroll
        for (int i = 0; i < 8; i++) m = max(m, __float_as_uint(nq[i] + __shfl_xor_sync(~0u, nq[i], 4)) & 0x7fffffffu);
        sts32(sb + SM_RED + 24, 4.2f * __uint_as_float(__reduce_max_sync(~0u, m)));
      }
      {
        uint4 xr[4];
        best = routed_row(P.x, tag, lane, xr);
#pragma unroll
        for (int i = 0; i < (GROWS + 255) / 256; i++) {
          const uint32_t dst = sb + SM_XSEL + i * 1024 + (lane >> 2) * 128 + (lane & 3) * 8;
          sts64(dst, bf_lo(xr[i].x), bf_lo(xr[i].z)); sts64(dst + 32, bf_hi(xr[i].x), bf_hi(xr[i].z));
          sts64(dst + 64, bf_lo(xr[i].y), bf_lo(xr[i].w)); sts64(dst + 96, bf_hi(xr[i].y), bf_hi(xr[i].w));
        }
        sts64u(sb + SM_RED + 16, tag, best);
        __syncwarp();
        if (lane == 0) { mbar_arrive(bar + B_XS); PROF(19); }
      }
      unsigned long long sv4[4];
      uint4 u[4];
#pragma unroll 1
      for (int it = 0; it < SPIN_MAX; it++) {
#pragma unroll
        for (int i = 0; i < 4; i++) { u[i] = ld_rlx128(g_cs + (1 + i) * 1024 + hg * 128 + lane * 4); sv4[i] = ld_rlx64(g_stat + mb * 128 + i * 32 + lane); }
        bool ok = ((BAD4(u[0]) | BAD4(u[1]) | BAD4(u[2]) | BAD4(u[3])) & 1) == 0;
#pragma unroll
        for (int i = 0; i < 4; i++) ok = ok && (uint32_t)(sv4[i] >> 32) == tag;
        if (__all_sync(~0u, ok)) break;
        __nanosleep(200);
      }
#pragma unroll
      for (int i = 0; i < 4; i++) {
        const uint32_t sv = (uint32_t)sv4[i], sd2 = (sv << 16) | (sv & 0xffffu);
        sts64(sb + SM_STAT + (i * 32 + lane) * 8, -bf_hi(sv), rcp(bf_lo(sv)));
        sts128u(sb + SM_SDT + lane * 64 + ((i ^ ((lane >> 1) & 3)) << 4), sd2, sd2, sd2, sd2);
      }
#pragma unroll
      for (int i = 0; i < 2; i++) {
        float4 c = make_float4(unmark(u[i].x) + unmark(u[i + 2].x), unmark(u[i].y) + unmark(u[i + 2].y), unmark(u[i].z) + unmark(u[i + 2].z),
                               unmark(u[i].w) + unmark(u[i + 2].w));
        CS_STORE(i, c);
      }
      fence_async_smem();
      __syncwarp();
      if (lane == 0) { mbar_arrive(bar + B_CS); PROF(10); }
    }
    {
      uint32_t xa = sb + SM_RED + 32, xstep = 0;
      const uint32_t zero = __float_as_uint(lds32(sb + SM_RED + 12));
#pragma unroll 1
      for (int ph = f == 3; ph < 2; ph++) {
#pragma unroll
        for (int j = 0; j < 8; j++) a[j] = 0.f;
        if (ph) { mbar_wait(bar + B_XS, 0); xa = sb + SM_XSEL + f * (GN * 128) + ((lane >> 2) & 3) * 32; xstep = 128; }
#pragma unroll 1
        for (int n = ph ? 3 : n0; n < (ph ? ne : 3); n++) {
          const float4 x0 = lds128(xa), x1 = lds128(xa + 16);
          xa += xstep;
          mbar_wait(fbar + (n & 1) * 8, ((n - n0) >> 1) & 1);
          uint4 u[8];
#pragma unroll
          for (int j = 0; j < 8; j++) u[j] = lds128u(fst + (n & 1) * 4096 + j * 256);
          FMA8(a, u[0], x0.x); FMA8(a, u[1], x0.y); FMA8(a, u[2], x0.z); FMA8(a, u[3], x0.w);
          if (__any_sync(~0u, ((u[4].x | u[5].x | u[6].x | u[7].x | __float_as_uint(a[0]) | __float_as_uint(a[7])) & zero) == 0)) STAGEG(n + 2);
          FMA8(a, u[4], x1.x); FMA8(a, u[5], x1.y); FMA8(a, u[6], x1.z); FMA8(a, u[7], x1.w);
        }
#pragma unroll
        for (int o = 4; o <= 8; o <<= 1)
#pragma unroll
          for (int j = 0; j < 8; j++) a[j] += __shfl_xor_sync(~0u, a[j], o);
        if (ph && lane == 0) mbar_arrive(bar + B_FFN);
        const uint32_t red = ph ? sb + SM_GRED : sb + SM_RED + 64;
        if ((lane & 12) == 0) {
          const uint32_t d = red + f * 256 + (lane >> 4) * 128 + (lane & 3) * 32;
          sts128(d, a[0], a[1], a[2], a[3]); sts128(d + 16, a[4], a[5], a[6], a[7]);
        }
        if (f != 2) {
          asm volatile("bar.arrive %0, %1;" ::"r"(4 + ph), "r"(96 + 32 * ph) : "memory");
        } else {
          bar_sync(4 + ph, 96 + 32 * ph);
          const uint32_t ra = red + lane * 4;
          gsum = lds32(ra) + lds32(ra + 256) + lds32(ra + 512);
          usum = lds32(ra + 128) + lds32(ra + 384) + lds32(ra + 640);
          if (!ph) st_rlx(g_cs + 1024 + ch * 2048 + cu * 32 + lane, mark(__float_as_uint(gsum + usum), par));
          else { gsum += lds32(ra + 768); usum += lds32(ra + 896); }
          if (lane == 0) PROF(ph ? 34 : 18);
        }
      }
    }
    if (f == 3) {
      if (elect_one()) {
        PROF(7);
        mbar_wait(bar + B_FULLQ, 0);
#pragma unroll 1
        for (int j = 3; j < 16; j++) {
          mbar_wait(bar + (j < 4 ? B_EMPTYKV + 16 : B_EMPTYQ + 8 * (j & 3)), ((j >> 2) & 1) ^ 1);
          if (j == 12 + (hg & 3)) mbar_wait(bar + B_KVST + 8, 0);
          Q_LOAD(j);
        }
        PROF(47);
        mbar_expect_tx(bar + B_DN, 65536);
#pragma unroll 1
        for (int i = 0; i < 4; i++) {
          mbar_wait(bar + B_EMPTYQ + 8 * i, 1);
          tma3d(sb + i * Q_STAGE, &mD, 0, fb * 32, i * 4, bar + B_DN);
        }
        PROF(48);
#pragma unroll 1
        for (int i = 0; i < 16; i++) {
          const int s = i & 3, n = i < 9 ? i - 2 : i - 9, kb = i < 2 ? 2 * hg + i : 2 * (n + (n >= hg)) + (i >= 9);
          if (i >= 4) mbar_wait(bar + B_EMPTYQ + 8 * s, ((i >> 2) & 1) ^ 1);
          mbar_expect_tx(bar + B_FULLQ + 8 * s, 16384);
          if (i < 2) {
            mbar_arrive2(bar + B_FULLQ + 8 * s);
            tma3d(sb + s * Q_STAGE + 16384, &mWo, 0, kb * 64, hg * 2, bar + B_FULLQ + 8 * s);
          } else {
            tma5d(sb + s * Q_STAGE + 16384, &mWp, hg * 128, kb * 2, bar + B_FULLQ + 8 * s);
            tma5d(sb + s * Q_STAGE + 24576, &mWp, hg * 128 + 64, kb * 2, bar + B_FULLQ + 8 * s);
            if (i >= 3) {
              if (i == 3) { mbar_wait(bar + B_DND, 0); PROF(14); }
#pragma unroll 1
              for (int a = i == 3 ? 2 : i; a <= i; a++) {
                const uint4* src = g_ofr + (mb * 16 + (a == 2 ? (hg == 0 ? 2 : 0) : kb)) * 1024;
#pragma unroll
                for (int h = 0; h < 2; h++) {
                  mbar_expect_tx(bar + B_AIN + (a & 3) * 16 + h * 8, 8192);
                  bulk_load(sb + (a & 3) * Q_STAGE + h * 8192, src + h * 512, 8192, bar + B_AIN + (a & 3) * 16 + h * 8);
                }
              }
            }
          }
        }
      }
    } else {
      if (f == 2) {
        if (PFD && ffn) {
#pragma unroll 1
          for (int i = 0; i < 16; i++) { touch_l2((const char*)P.w_down + fb * 65536 + i * 4096 + lane * 128, lane); __nanosleep(PFD); }
        }
        if (WOT) {
#pragma unroll 1
          for (int i = 0; i < 8; i++) { touch_l2((const char*)P.wo + ((mb & 7) * 128 + i * 16 + (lane >> 1)) * 2048 + hg * 256 + (lane & 1) * 128, lane); __nanosleep(PFD); }
        }
        asm volatile("cp.async.wait_all;" ::: "memory");
        uint4 u;
#pragma unroll 1
        for (int it = 0; it < SPIN_MAX; it++) {
          u = ld_rlx128(g_cs + hg * 128 + lane * 4);
          if (__all_sync(~0u, !(BAD4(u) & 1))) break;
          __nanosleep(200);
        }
        mbar_wait(bar + B_PHI, 0);
        float4 c = make_float4(unmark(u.x), unmark(u.y), unmark(u.z), unmark(u.w));
        CS_STORE(2, c);
        fence_async_smem();
        __syncwarp();
        if (lane == 0) mbar_arrive(bar + B_CSQ);
        if (ffn && !FFN_OFF) {
#pragma unroll 1
          for (int it = 0; it < SPIN_MAX; it++) {
            const uint32_t pg = ld_rlx((const uint32_t*)g_gp + fb * 32 + lane), pu = ld_rlx((const uint32_t*)g_gp + FF + fb * 32 + lane);
            if (__all_sync(~0u, !(((pg ^ par) | (pu ^ par)) & 1))) { gsum += unmark(pg); usum += unmark(pu); break; }
            __nanosleep(200);
          }
        }
        const float h = bf_round(silu_f(bf_round(gsum))) * bf_round(usum);
        const uint32_t h2 = pack2(h, h);
        sts128u(sb + SM_HT + lane * 16, h2, h2, h2, h2);
        fence_async_smem();
        __syncwarp();
        if (lane == 0) { mbar_arrive(bar + B_H); PROF(20); }
      }
      if (f < 2) {
        const uint32_t own = (hg * 2 + f) * 16 + mb, target = __shfl_sync(~0u, tag, 0) * 16;
        mbar_wait(bar + B_KVST + 8 * f, 0);
        if (f == 1 && lane == 0) PROF(11);
        wait_hint(g_xcnt + hg * 64 + f * 16 + mb, target);
        if (elect_one()) {
          PROF(35 + f);
          fence_async_global();
          mbar_expect_tx(bar + B_PART + 8 * f, 8192);
          bulk_load(sb + (f ? SM_PST1 : SM_PST0), g_part + own * 512, 8192, bar + B_PART + 8 * f);
        }
        __syncwarp();
        {
          uint4 uz;
#pragma unroll 1
          for (int it = 0; it < SPIN_MAX; it++) {
            uz = ld_rlx128(g_zpart + own * 128 + lane * 4);
            if (__all_sync(~0u, !(BAD4(uz) & 1))) break;
          }
          const bool b1 = lane & 2, b2 = lane & 4;
          const float z0 = unmark(b1 ? uz.z : uz.x) + __shfl_xor_sync(~0u, unmark(b1 ? uz.x : uz.z), 2);
          const float z1 = unmark(b1 ? uz.w : uz.y) + __shfl_xor_sync(~0u, unmark(b1 ? uz.y : uz.w), 2);
          float z = (b2 ? z1 : z0) + __shfl_xor_sync(~0u, b2 ? z0 : z1, 4);
          z += __shfl_xor_sync(~0u, z, 8);
          z += __shfl_xor_sync(~0u, z, 16);
          if (lane < 8) st_rlx(g_zres + own * 8 + (lane & 1) * 4 + (lane & 2) + (lane >> 2), mark(__float_as_uint(z), par));
          if (lane == 0) red_inc(g_xcnt + hg * 64 + 32 + f * 16);
          __syncwarp();
        }
        wait_hint(g_xcnt + hg * 64 + 32 + f * 16, 5 * target);
        mbar_wait(bar + B_KVST + 8, 0);
        if (lane == 0) PROF(40 + f);
#pragma unroll 1
        for (int it = 0; it < SPIN_MAX; it++) {
          if (elect_one()) {
            fence_async_global();
            mbar_expect_tx(bar + B_RES + 8 * f, 8192);
            bulk_load(sb + SM_V + f * 8192, g_res[par] + (hg * 4 + f * 2) * 256, 8192, bar + B_RES + 8 * f);
          }
          __syncwarp();
          const uint4 uz = ld_rlx128(g_zres + (hg * 4 + f * 2) * 64 + lane * 4);
          const uint32_t zw[4] = {uz.x, uz.y, uz.z, uz.w};
#pragma unroll
          for (int j = 0; j < 4; j++) {
            const uint32_t zz = pack2(unmark(zw[j]), 1.f), row = (lane & 3) * 4 + j;
            sts128u(sb + SM_ZT + (2 * f + (lane >> 4)) * 1024 + row * 64 + ((((lane >> 2) ^ (row >> 1)) & 3) << 4), zz, zz, zz, zz);
          }
          uint32_t bad = BAD4(uz);
          mbar_wait(bar + B_RES + 8 * f, it & 1);
#pragma unroll
          for (int i = 0; i < 16; i++) bad |= ~__float_as_uint(lds32(sb + SM_V + f * 8192 + i * 512 + lane * 16));
          if (__all_sync(~0u, !(bad & 1))) break;
        }
        fence_async_smem();
        __syncwarp();
        if (lane == 0) { mbar_arrive(bar + B_TILE + 8 * f); PROF(f ? 13 : 27); }
      }
      if (f < 2) {
        uint32_t phases = 0;
#pragma unroll 1
        for (int i = 2; i < 16; i++) {
          const int s = i & 3;
          const uint32_t ab = bar + B_AIN + s * 16 + f * 8, slot = sb + s * Q_STAGE + f * 8192;
#pragma unroll 1
          for (int it = 0; it < SPIN_MAX; it++) {
            mbar_wait(ab, (phases >> s) & 1);
            phases ^= 1u << s;
            uint32_t bad = 0;
#pragma unroll
            for (int n = 0; n < (NOVAL ? 0 : 8); n++) bad |= __float_as_uint(lds32(slot + n * 1024 + lane * 32 + (lane >> 2) * 4)) ^ par;
            if (__all_sync(~0u, !(bad & 1))) break;
            if (elect_one()) {
              const int n = i < 9 ? i - 2 : i - 9, kb = 2 * (n + (n >= hg)) + (i >= 9);
              PROF(49);
              mbar_expect_tx(ab, 8192);
              bulk_load(slot, g_ofr + (mb * 16 + kb) * 1024 + f * 512, 8192, ab);
            }
            __syncwarp();
          }
          if (lane == 0) { mbar_arrive(bar + B_FULLQ + 8 * s); if (i == 2 && f == 0) PROF(15); }
        }
        if (f == 0) g_epoch[bid * 32 + lane] = tag;
      } else {
        if (elect_one()) {
          prefetch_map(&mOut);
          if (ffn) { mbar_wait(bar + B_YD, 0); red_rel(g_ycnt); PROF(21); }
        }
        __syncwarp();
        if (f == 2) {
          const uint32_t best = __float_as_uint(lds32(sb + SM_RED + 20));
          const int sel = 2047 - (best & 0x7ff) - mb * 128;
          if (sel >= 0 && sel < 128) {
            const uint2 xr = __ldg((const uint2*)(P.x + (size_t)(mb * 128 + sel) * DM + hg * 128 + lane * 4));
            const float2 st = lds64(sb + SM_STAT + sel * 8);
            const uint32_t ord = best >> 16, rb = (ord & 0x8000u) ? (ord & 0x7fffu) : (~ord & 0xffffu);
            const float sg = rcp(1.f + ex2(-1.4426950408889634f * bf_lo(rb)));
            const uint32_t sg2 = pack2(sg, sg), nm2 = pack2(st.x, st.x);
            wait_cnt<0>(g_ycnt, tag * NFFN);
            float4 y = make_float4(0.f, 0.f, 0.f, 0.f);
#pragma unroll
            for (int i = 0; i < 8; i++) {
              const float4 c = ldg_cg4(g_y[par ^ 1][i] + hg * 128 + lane * 4);
              y.x += c.x; y.y += c.y; y.z += c.z; y.w += c.w;
            }
            uint32_t o[2];
#pragma unroll
            for (int i = 0; i < 2; i++) {
              const uint32_t d = badd2(i ? xr.y : xr.x, nm2);
              const uint32_t tt = badd2(pack2(bf_lo(d) * st.y, bf_hi(d) * st.y), bmul2(i ? pack2(y.z, y.w) : pack2(y.x, y.y), sg2));
              o[i] = pack2(silu_f(bf_lo(tt)), silu_f(bf_hi(tt)));
            }
            sts64u(sb + SM_UPD + lane * 8, o[0], o[1]);
          }
          if (lane == 0) sts32(sb + SM_UPD + 256, __int_as_float(sel));
          __syncwarp();
          if (lane == 0) { mbar_arrive(bar + B_UPD); PROF(22); }
        }
      }
    }
  } else {
    const int t7 = threadIdx.x & 127;
    const char* pfa = warp < 4 ? (const char*)P.x + bid * 32768 + (t7 & 15) * 2048 + (t7 >> 4) * 128
                               : (const char*)P.wqkv + (size_t)((t7 >> 4) * 64 + (bid >> 1)) * 6144 + 2048 + (bid & 1) * 2048 + (t7 & 15) * 128;
    if (t7 < 16 * PF_FIRST) prefetch_l2(pfa);
    if (warp < 7) sts128(sb + SM_CST + threadIdx.x * 16, 0.f, 0.f, 0.f, 0.f);
    else sts32(sb + SM_RED + (threadIdx.x & 15) * 4, threadIdx.x & 8 ? 1.f : 0.f);
    fence_async_smem();
    if (elect_one()) {
#pragma unroll 1
      for (uint32_t b = B_FST + warp * 8; b < B_END; b += 64)
        mbar_init(bar + b, b < B_FULLQ ? 1 : b < B_FFN ? 3 : b < B_EMPTYKV ? 4 : 8);
    }
    __syncwarp();
    asm volatile("setmaxnreg.inc.sync.aligned.u32 %0;" ::"n"(REG_C));
    if (PF_PRE && t7 >= 16 * PF_FIRST && threadIdx.x < 128 + 16 * PF_W) prefetch_l2(pfa);
    bar_sync(0, 384);
    if (!PF_PRE && t7 >= 16 * PF_FIRST && threadIdx.x < 128 + 16 * PF_W) prefetch_l2(pfa);
    const int lane = lane_id();
    const int wg = warp >> 2, w = warp & 3, g = lane >> 2, t = lane & 3;
    float kv[128];
    {
      uint32_t s = 2, ph = 0, sp = 0, php = 0;
#pragma unroll 1
      for (int j = 0; j < 15; j++) {
        PW0(32 + j); mbar_wait(bar + B_FULLKV + 8 * s, ph); PW1(32 + j);
        if (wg == 1 && (ORDER_ALL || j == 0)) bar_sync(10 + s, 256);
        wg_fence();
        wgmma_n256_ssp_ta0_tb1(kv, mkdesc(sb, 16, 1024, 1, wg * 512 + s * (KV_STAGE / 16)), mkdesc(sb + 16384, 8192, 1024, 1, s * (KV_STAGE / 16)), j);
#pragma unroll
        for (int k = 1; k < 4; k++)
          wgmma_n256_ss_ta0_tb1(kv, mkdesc(sb + k * 32, 16, 1024, 1, wg * 512 + s * (KV_STAGE / 16)),
                                mkdesc(sb + 16384 + k * 2048, 8192, 1024, 1, s * (KV_STAGE / 16)), 1);
        wg_commit();
        if (wg == 0 && (ORDER_ALL || j == 0)) asm volatile("bar.arrive %0, 256;" ::"r"(10 + s) : "memory");
        if (warp == 0 && j) {
          mbar_wait(bar + B_EMPTYKV + 8 * sp, php);
          if (elect_one()) {
            if (j < 14) {
              mbar_expect_tx(bar + B_FULLKV + 8 * sp, KV_STAGE);
              tma2d(sb + sp * KV_STAGE, &mX, (j + 2) * 64, mb * 128, bar + B_FULLKV + 8 * sp);
              tma4d(sb + sp * KV_STAGE + 16384, &mWkv, 0, (j + 2) * 64, hg * 2, 1, bar + B_FULLKV + 8 * sp);
            } else {
              Q_LOAD(0);
            }
            if (j < 3 - XS_EARLY) {
              const int xh = j - 1 + XS_EARLY;
              mbar_expect_tx(bar + B_XST + 8 * xh, 16384);
              tma3d(sb + SM_XST + xh * 16384, &mXs, 0, bid * 16, 2 * xh, bar + B_XST + 8 * xh);
            }
          }
          __syncwarp();
        }
        if (j == 0) {
          if (wg == 0) prefetch_l2(pfa + 1024);
        } else if (wg == 1) {
          if (j < 3) {
            if (j == 2 || t7 >= 16 * PF_W) prefetch_l2(pfa + (j - 1) * (8 * 393216));
          } else if (j == 13) {
            prefetch_l2((const char*)P.wo + bid * 16384 + t7 * 128);
          }
          if (PFG && !FFN_OFF && bid < NFFN && j >= 2 && j < 2 + GROWS / 64 && w < 2)
            touch_l2((const char*)((bid & 1) ? P.w_up : P.w_gate) + (size_t)((0x852a7419630ull >> (4 * j - 8) & 15) * 64 + t7) * 7168 + (bid >> 1) * 128, lane);
        }
        wg_wait<0>();
        if (lane == 0) mbar_arrive(bar + B_EMPTYKV + 8 * s);
        sp = s; php = ph;
        ph ^= s == 1;
        s = s == 2 ? 0 : s + 1;
      }
    }
    const int lrow = wg * 64 + w * 16 + (lane & 15);
    const uint32_t sw128 = lrow * 128, x128 = (lrow & 7), hi16 = lane >> 4;
    mbar_wait(bar + B_CS, 0);
    const uint32_t tag = __float_as_uint(lds32(sb + SM_RED + 16));
    const int zero = __float_as_int(lds32(sb + SM_RED + 12));
    const float wn = lds32(sb + SM_RED + 24);
    const float2 st0 = lds64(sb + SM_STAT + (wg * 64 + w * 16 + g) * 8), st1 = lds64(sb + SM_STAT + (wg * 64 + w * 16 + g + 8) * 8);
    const float c0 = st0.y * 1.4426950408889634f, c1 = st1.y * 1.4426950408889634f;
    const uint32_t nm20 = pack2(st0.x, st0.x), nm21 = pack2(st1.x, st1.x), fmask = t == 0 ? ~0u : t == 1 ? 0xffffu : 0u;
    const uint32_t fa0 = nm20 & fmask, fa1 = nm21 & fmask;
    asm volatile("cp.async.wait_all;" ::: "memory");
    PW0(47); mbar_wait(bar + B_FULLKV + 16, 1); PW1(47);
    wg_fence();
    wgmma_n256_rs_ta0_tb1(kv, fa0, fa1, 0u, 0u, mkdesc(sb + SM_CST, 512, 0, 1), 1);
#pragma unroll
    for (int k = 0; k < 4; k++)
      wgmma_n256_ss_ta0_tb1(kv, mkdesc(sb + 2 * KV_STAGE + k * 32, 16, 1024, 1, wg * 512), mkdesc(sb + 2 * KV_STAGE + 16384 + k * 2048, 8192, 1024, 1), 1);
    wg_commit();
    if (warp == 0) {
      mbar_wait(bar + B_EMPTYKV + 8, 0);
      if (elect_one()) {
#pragma unroll 1
        for (int j = 1; j < 3; j++) Q_LOAD(j);
      }
      __syncwarp();
    }
    wg_wait<0>();
    reg_fence<128>(kv);
    if (lane == 0) mbar_arrive(bar + B_EMPTYKV + 16);
    PROFC(2);
    float q[64];
#define QMMA(J, AOFF16, ACCUM)                                                                                     \
  _Pragma("unroll") for (int k = 0; k < 4; k++)                                                                    \
      wgmma_n128_ss_ta0_tb1(q, mkdesc(sb + k * 32, 16, 1024, 1, wg * 512 + (AOFF16)),                              \
                            mkdesc(sb + 16384 + k * 2048, 8192, 1024, 1, ((J) & 3) * (Q_STAGE / 16)), k ? 1 : (ACCUM))
#define QWAIT(J) do { PW0(J); mbar_wait(bar + B_FULLQ + 8 * ((J) & 3), ((J) >> 2) & 1); PW1(J); } while (0)
#define QSTEP_A(J, AOFF16, ACCUM) do { QWAIT(J); wg_fence(); QMMA(J, AOFF16, ACCUM); wg_commit(); } while (0)
#define QREL(J) do { if (lane == 0) mbar_arrive(bar + B_EMPTYQ + 8 * ((J) & 3)); } while (0)
#define Q_OFF16(J) ((J) >= 8 && (J) < 16 ? Q_AOFF(J) / 16 : ((J) & 3) * (Q_STAGE / 16))
#define QPLAIN(J) do { QSTEP_A(J, Q_OFF16(J), 1); wg_wait<1>(); QREL((J) - 1); } while (0)
#define QNEXT(J) do { QPLAIN(J); SCHED_FENCE(); } while (0)
#define PHI_PROJ(DST, SRC, H0, H1)                                                                                 \
  do {                                                                                                             \
    uint32_t a_[32];                                                                                               \
    _Pragma("unroll") for (int j = 8 * (H0); j < 8 * (H1); j++) {                                                  \
      a_[j] = pack2(SRC[2 * j], SRC[2 * j + 1]);                                                                   \
      asm volatile("fma.rn.bf16x2 %0, %1, %1, %0;" : "+r"(nq[(j >> 4) * 2 + (j & 1)]) : "r"(a_[j]));               \
    }                                                                                                              \
    wg_fence();                                                                                                    \
    _Pragma("unroll") for (int hk = 2 * (H0); hk < 2 * (H1); hk++)                                                 \
        wgmma_n32_rs_ta0_tb1(DST + 16 * (hk >> 1), a_[4 * hk], a_[4 * hk + 1], a_[4 * hk + 2], a_[4 * hk + 3],     \
                             mkdesc(sb + SM_WPHI + hk * 1024, 16, 512, 2), hk & 1);                                \
    wg_commit();                                                                                                   \
  } while (0)
    {
      float p[64], ea[24], eb[24], sa[4], sc[4], kz[20];
      uint32_t vp[32];
#pragma unroll
      for (int j = 0; j < 32; j++) vp[j] = pack2(kv[64 + 2 * j], kv[65 + 2 * j]);
      const uint32_t vr = w * 16 + (lane & 15), vb = sb + SM_V + wg * 4096 + vr * 64, x64 = (vr >> 1) & 3;
#define V_STORE(R)                                                                                           \
  _Pragma("unroll") for (int j = 0; j < 4; j++)                                                              \
      stsm4(vb + (j >> 1) * 8192 + ((((j & 1) * 2 + hi16) ^ x64) << 4), vp[16 * (R) + 4 * j], vp[16 * (R) + 4 * j + 1], vp[16 * (R) + 4 * j + 2], vp[16 * (R) + 4 * j + 3])
      V_STORE(0);
      mbar_wait(bar + B_WPHI, 0);
      {
        uint32_t nq[4] = {0u, 0u, 0u, 0u};
        PHI_PROJ(p, kv, 0, 4);
        QSTEP_A(0, 0, 0);
        const bool unsafe = softmax_unsafe(nq, c0 * c0 * wn, c1 * c1 * wn);
        wg_wait<1>();
        reg_fence<64>(p);
        if (__builtin_expect(unsafe, 0)) softmax_shift(p, c0, c1);
      }
#define K_NORM(S) do { quad_sum<4>(S); _Pragma("unroll") for (int i = 0; i < 4; i++) S[i] = rcp(S[i]) * ((i & 1) ? st1.y : st0.y); } while (0)
#define K_STORE(SLOT, E, S) K_STORE_(SLOT, E, S, 0, 2)
#define K_STORE_(SLOT, E, S, J0, J1)                                                                         \
  _Pragma("unroll") for (int j = (J0); j < (J1); j++) {                                                      \
    uint32_t fp[4], fm[4];                                                                                   \
    _Pragma("unroll") for (int i = 0; i < 4; i++) {                                                          \
      const float e0 = E[8 * j + 2 * i], e1 = E[8 * j + 2 * i + 1], r = E[16 + 4 * j + i] * S[2 + (i & 1)];  \
      const uint32_t e2 = pack2(e0, e1);                                                                     \
      fp[i] = bmul2(e2, pack2(S[i & 1], S[i & 1]));                                                          \
      fm[i] = bmul2(e2, pack2(r, r));                                                                        \
    }                                                                                                        \
    stsm4(sb + SM_PHI + (SLOT) * 16384 + sw128 + (((2 * j + hi16) ^ x128) << 4), fp[0], fp[1], fp[2], fp[3]); \
    stsm4(sb + SM_PHI + (SLOT) * 16384 + sw128 + (((4 + 2 * j + hi16) ^ x128) << 4), fm[0], fm[1], fm[2], fm[3]); \
  }
#define KV_MMA(R)                                                                                            \
  do {                                                                                                       \
    mbar_wait(bar + B_PHI + 8 * (R), 0);                                                                     \
    wg_fence();                                                                                              \
    _Pragma("unroll") for (int k = 0; k < 8; k++) {                                                          \
      const uint32_t vs = SM_V + (k >> 2) * 4096 + (k & 3) * 1024;                                           \
      wgmma_n40_ss_ta1_tb1(kz, mkdesc(sb + SM_PHI + k * 2048, 16, 1024, 1, wg * 1024),                       \
                           mkdesc(sb + vs, SM_SDT + (k & 1) * 1024 + (k >> 1) * 16 - vs, 512, 2, wg * (512u - (512u << 16))), k); \
    }                                                                                                        \
    wg_commit();                                                                                             \
  } while (0)
#define QKV(J, R) do { KV_MMA(R); QSTEP_A(J, Q_OFF16(J), 1); wg_wait<2>(); QREL((J) - 1); SCHED_FENCE(); } while (0)
#define KV_SEND(R)                                                                                           \
  do {                                                                                                       \
    reg_fence<20>(kz);                                                                                       \
    if (lane == 0) mbar_arrive(bar + B_KVST + 8 * (R));                                                      \
    const uint32_t slot = ((hg * 2 + (R)) * 16 + warp * 2) * 16 + mb;                                        \
    _Pragma("unroll") for (int u = 0; u < 2; u++)                                                            \
      st_rlx128(g_part + (slot + u * 16) * 32 + lane, mark(pack2(kz[2 * u], kz[2 * u + 1]), tag & 1), pack2(kz[2 * u + 4], kz[2 * u + 5]), \
                pack2(kz[2 * u + 8], kz[2 * u + 9]), pack2(kz[2 * u + 12], kz[2 * u + 13]));                 \
    if (t < 2) st_rlx(g_zpart + (slot + t * 16) * 8 + g, mark(__float_as_uint(t ? kz[18] : kz[16]), tag & 1)); \
    if (lane < 2) red_inc(g_xcnt + hg * 64 + (R) * 16 + warp * 2 + lane);                                    \
  } while (0)
#define K_PUB(R) do { fence_async_smem(); __syncwarp(); if (lane == 0) mbar_arrive(bar + B_PHI + 8 * (R)); } while (0)
#define S_PIN(S) SCHED_PIN(S[0] + S[1] + S[2] + S[3])
      k_exp(p, c0, c1, ea, sa);
      S_PIN(sa);
      QNEXT(1);
      K_NORM(sa);
      k_exp<0, 4>(p + 16, c0, c1, eb, sc);
      mbar_wait(bar + B_FFN, 0);
      K_STORE_(0, ea, sa, 0, 1);
      S_PIN(sc);
      QNEXT(2);
      K_STORE_(0, ea, sa, 1, 2);
      k_exp<4, 8>(p + 16, c0, c1, eb, sc);
      K_NORM(sc);
      S_PIN(sc);
      QNEXT(3);
      K_STORE(1, eb, sc);
      K_PUB(0);
      k_exp<0, 4>(p + 32, c0, c1, ea, sa);
      S_PIN(sa);
      QKV(4, 0);
      k_exp<4, 8>(p + 32, c0, c1, ea, sa);
      K_NORM(sa);
      k_exp<0, 4>(p + 48, c0, c1, eb, sc);
      SCHED_PIN(sa[0] + sa[1] + sa[2] + sa[3] + sc[2] + sc[3]);
      QNEXT(5);
      KV_SEND(0);
      k_exp<4, 8>(p + 48, c0, c1, eb, sc);
      S_PIN(sc);
      QNEXT(6);
      K_NORM(sc);
      mbar_wait(bar + B_KVST, 0);
      V_STORE(1);
      K_STORE(0, ea, sa);
      QNEXT(7);
      K_STORE(1, eb, sc);
      K_PUB(1);
      QKV(8, 1);
      QNEXT(9);
      KV_SEND(1);
    }
#define JQ0 10
    PROFC(3);
    {
      bool todo = true;
#pragma unroll 1
      for (int j = JQ0; j < 15 || todo; j++) {
        if (j < 15) { QSTEP_A(j, Q_AOFF(j) / 16, 1); wg_wait<1>(); QREL(j - 1); }
        if (todo && __any_sync(~0u, mbar_test(bar + B_PART + 8 * wg, 0))) {
          todo = false;
          const uint32_t own = (hg * 2 + wg) * 16 + mb, word = w * 32 + lane;
          uint32_t u[16], bad = 0;
#pragma unroll
          for (int i = 0; i < 16; i++) { u[i] = __float_as_uint(lds32(sb + (wg ? SM_PST1 : SM_PST0) + i * 512 + word * 4)); bad |= u[i] ^ tag; }
#pragma unroll 1
          for (int it = 0; it < SPIN_MAX && __any_sync(~0u, t == 0 && (bad & 1)); it++) {
            bad = 0;
#pragma unroll
            for (int i = 0; i < 16; i++) { u[i] = ld_rlx((const uint32_t*)g_part + own * 2048 + i * 128 + word); bad |= u[i] ^ tag; }
          }
          float s0 = 0.f, s1 = 0.f, s2 = 0.f, s3 = 0.f;
#pragma unroll
          for (int i = 0; i < 16; i += 2) { s0 += bf_lo(u[i] | !t); s1 += bf_hi(u[i]); s2 += bf_lo(u[i + 1] & (t ? ~0u : ~1u)); s3 += bf_hi(u[i + 1]); }
          const uint32_t r = pack2(s0 + s2, s1 + s3);
          st_rlx((uint32_t*)g_res[tag & 1] + own * 128 + w * 32 + (lane & 16) + ((t ^ w) << 2) + ((lane >> 2) & 3), lane & 12 ? r : r | 1);
          ((uint32_t*)g_res[~tag & 1])[own * 128 + word] = 0;
          __syncwarp();
          if (lane == 0) { red_inc(g_xcnt + hg * 64 + 32 + wg * 16); if (w == 0) PROF(wg ? 12 : 30); }
          __syncwarp();
        }
      }
    }
    mbar_wait(bar + B_CSQ, 0);
    QWAIT(15);
    if (wg == 1) bar_sync(6, 256);
    wg_fence();
    wgmma_n128_rs_ta0_tb1(q, fa0, fa1, 0u, 0u, mkdesc(sb + SM_CST + 2048, 512, 0, 1), 1);
    QMMA(15, Q_AOFF(15) / 16, 1);
    wg_commit();
    if (wg == 0) asm volatile("bar.arrive 6, 256;" ::: "memory");
    wg_wait<1>();
    QREL(14);
    wg_wait<0>();
    QREL(15);
    reg_fence<64>(q);
    PROFC(5);
    float yp[4];
    const uint32_t par = tag & 1;
    uint4* ofr = g_ofr + (mb * 16 + hg * 2) * 1024 + (warp * 16 + g) * 8;
#define O_MMA(H, F, N)                                                                                       \
  do {                                                                                                       \
    wg_fence();                                                                                              \
    _Pragma("unroll") for (int k = 0; k < 4; k++) {                                                          \
      const uint32_t ks = SM_V + (H) * 4096 + k * 1024;                                                      \
      wgmma_n40_rs_ta0_tb1(N + 20 * (k >> 1), F[4 * k], F[4 * k + 1], F[4 * k + 2], F[4 * k + 3],            \
                           mkdesc(sb + ks, SM_ZT + (H) * 1024 + k * 16 - ks, 512, 2), k & 1);                \
    }                                                                                                        \
    wg_commit();                                                                                             \
  } while (0)
#define O_FIN(H, N, o)                                                                                        \
  do {                                                                                                       \
    reg_fence<40>(N);                                                                                        \
    const float *np = N, *nm = N + 20;                                                                       \
    const float d0 = rcp(fmaf(np[16], nm[17], fmaf(nm[16], np[17], 1e-6f * np[17] * nm[17])));               \
    const float d1 = rcp(fmaf(np[18], nm[19], fmaf(nm[18], np[19], 1e-6f * np[19] * nm[19])));               \
    const float bp0 = nm[17] * d0, bm0 = np[17] * d0, bp1 = nm[19] * d1, bm1 = np[19] * d1;                  \
    _Pragma("unroll") for (int j = 0; j < 4; j++) {                                                          \
      o[2 * j] = pack2(fmaf(np[4 * j], bp0, nm[4 * j] * bm0), fmaf(np[4 * j + 1], bp0, nm[4 * j + 1] * bm0)); \
      o[2 * j + 1] = pack2(fmaf(np[4 * j + 2], bp1, nm[4 * j + 2] * bm1), fmaf(np[4 * j + 3], bp1, nm[4 * j + 3] * bm1)); \
    }                                                                                                        \
  } while (0)
#define O_STG(H, o)                                                                                          \
  _Pragma("unroll") for (int u = 0; u < 2; u++) {                                                            \
    uint32_t v_[4];                                                                                          \
    _Pragma("unroll") for (int j = 0; j < 4; j++) v_[j] = lop_select(o[2 * j + u], parm, vword == j);        \
    st_rlx128(ofr + ((H) >> 1) * 1024 + u * 64 + ((((H) & 1) * 4 + t) ^ g), v_[0], v_[1], v_[2], v_[3]);     \
  }
    uint32_t gf[32], ao[16];
    const uint32_t parm = 0u - par, vword = ((t ^ g) & 1) == (g >> 2) ? g & 3 : 4;
    const float rh0 = 0.5f * st0.y, rh1 = 0.5f * st1.y, mh0 = st0.x * rh0, mh1 = st1.x * rh1;
#define GATE_LD(J) ldsm4(sb + ((J) >> 2 ? SM_X1 : SM_X0) + sw128 + (((((J) & 3) * 2 + hi16) ^ x128) << 4), gf[4 * (J)], gf[4 * (J) + 1], gf[4 * (J) + 2], gf[4 * (J) + 3])
#define GATE(I0, I1)                                                                                         \
  _Pragma("unroll") for (int i = (I0); i < (I1); i++) {                                                      \
    const float rs = (i & 1) ? rh1 : rh0, mh = (i & 1) ? mh1 : mh0;                                          \
    const float h0 = fmaf(bf_lo(gf[i]), rs, mh), h1 = fmaf(bf_hi(gf[i]), rs, mh);                            \
    gf[i] = pack2(fmaf(h0, tanh_approx(h0), h0), fmaf(h1, tanh_approx(h1), h1));                             \
  }
#define GATE_PIN(I0, I1) do { uint32_t o_ = 0; _Pragma("unroll") for (int i = (I0); i < (I1); i++) o_ |= gf[i]; SCHED_PIN(__uint_as_float(o_)); } while (0)
    {
      float p[64], na[40], nb[40];
      uint32_t fa[16], fb[16];
      {
        uint32_t nq[4] = {0u, 0u, 0u, 0u};
        PHI_PROJ(p, q, 0, 2);
        SCHED_FENCE();
        PHI_PROJ(p, q, 2, 4);
        const bool unsafe = softmax_unsafe(nq, c0 * c0 * wn, c1 * c1 * wn);
        if (TW == 0) mbar_wait(bar + B_TILE, 0);
        wg_wait<0>();
        reg_fence<64>(p);
        PROFC(24);
        if (__builtin_expect(unsafe, 0)) softmax_shift(p, c0, c1);
      }
      float dn[32];
#define DN_PART(A, B)                                                                                        \
  do {                                                                                                       \
    wg_fence();                                                                                              \
    _Pragma("unroll") for (int i = (A); i < (B); i++)                                                        \
      wgmma_n8_ss_ta1_tb1(dn + 4 * (i >> 1), mkdesc(sb + (i >> 3) * Q_STAGE + (i & 7) * 2048, 16, 1024, 1, wg * (2 * Q_STAGE / 16)), \
                          mkdesc(sb + SM_HT + (i & 1) * 256, 128, 128, 0), i & 1);                           \
  } while (0)
#define F_PIN(F, A, B) do { uint32_t o_ = 0; _Pragma("unroll") for (int i = (A); i < (B); i++) o_ |= F[8 + i]; SCHED_PIN(__uint_as_float(o_)); } while (0)
#define RMMA(J, A, ACCUM)                                                                                    \
  do {                                                                                                       \
    wg_fence();                                                                                              \
    _Pragma("unroll") for (int k = 0; k < 4; k++)                                                            \
      wgmma_n128_rs_ta0_tb1(q, (A)[4 * k], (A)[4 * k + 1], (A)[4 * k + 2], (A)[4 * k + 3],                   \
                            mkdesc(sb + 16384 + k * 2048, 8192, 1024, 1, ((J) & 3) * (Q_STAGE / 16)), k ? 1 : (ACCUM)); \
    wg_commit();                                                                                             \
  } while (0)
#define RSTEP(J, A, ACCUM) do { QWAIT(J); RMMA(J, A, ACCUM); } while (0)
      PROFC(4);
      q_exp(p, c0, c1, fa);
      if (TW == 1) { F_PIN(fa, 0, 8); mbar_wait(bar + B_TILE, 0); }
      if (TW == 2) { q_exp(p + 16, c0, c1, fb); F_PIN(fb, 0, 8); mbar_wait(bar + B_TILE, 0); }
      O_MMA(0, fa, na);
      if (TW != 2) q_exp(p + 16, c0, c1, fb);
      O_MMA(1, fb, nb);
      PROFC(25);
      wg_wait<1>();
      O_FIN(0, na, ao);
      O_STG(0, ao);
      wg_wait<0>();
      O_FIN(1, nb, (ao + 8));
      O_STG(1, (ao + 8));
      PROFC(28);
      RSTEP(16, ao, 0);
      SCHED_FENCE();
      q_exp(p + 32, c0, c1, fa);
      F_PIN(fa, 0, 8);
      mbar_wait(bar + B_H, 0);
      mbar_wait(bar + B_DN, 0);
      PROFC(45);
      DN_PART(0, 4);
      SCHED_FENCE();
      q_exp<0, 2>(p + 48, c0, c1, fb);
      F_PIN(fb, 0, 2);
      DN_PART(4, 8);
      SCHED_FENCE();
      q_exp<2, 4>(p + 48, c0, c1, fb);
      F_PIN(fb, 2, 4);
      DN_PART(8, 12);
      SCHED_FENCE();
      q_exp<4, 6>(p + 48, c0, c1, fb);
      F_PIN(fb, 4, 6);
      DN_PART(12, 16);
      wg_commit();
      SCHED_FENCE();
      q_exp<6, 8>(p + 48, c0, c1, fb);
      F_PIN(fb, 6, 8);
      wg_wait<0>();
      reg_fence<32>(dn);
      if (lane == 0) mbar_arrive(bar + B_DND);
      QREL(16);
#pragma unroll
      for (int i = 0; i < 4; i++) yp[i] = t & 2 ? (t & 1 ? dn[24 + 2 * i] : dn[16 + 2 * i]) : (t & 1 ? dn[8 + 2 * i] : dn[2 * i]);
      PROFC(29);
      mbar_wait(bar + B_TILE + 8, 0);
      PROFC(23);
      if (bid < NFFN) {
        float* y = g_y[par ^ 1][bid & 7] + wg * 512 + t * 128 + w * 16 + g;
#pragma unroll
        for (int i = 0; i < 4; i++) red1(y + (i >> 1) * 64 + (i & 1) * 8, yp[i]);
      }
      SCHED_FENCE();
      O_MMA(2, fa, na);
      O_MMA(3, fb, nb);
      __syncwarp();
      if (lane == 0) mbar_arrive(bar + B_YD);
      wg_wait<1>();
      O_FIN(2, na, ao);
      O_STG(2, ao);
      wg_wait<0>();
      O_FIN(3, nb, (ao + 8));
      O_STG(3, (ao + 8));
      PROFC(6);
    }
    RSTEP(17, ao, 1);
    SCHED_FENCE();
    GATE_LD(0); GATE_LD(1);
    GATE(0, 3);
    GATE_PIN(0, 3);
#define GSTEP(J, I0, I1, LD) do { QNEXT(J); if ((LD) < 8) GATE_LD((LD) & 7); GATE(I0, I1); GATE_PIN(I0, I1); } while (0)
    GSTEP(18, 3, 6, 2); GSTEP(19, 6, 9, 3); GSTEP(20, 9, 12, 4); GSTEP(21, 12, 15, 8); GSTEP(22, 15, 18, 5); GSTEP(23, 18, 21, 6);
    GSTEP(24, 21, 24, 8); GSTEP(25, 24, 27, 7); GSTEP(26, 27, 30, 8); GSTEP(27, 30, 32, 8);
#pragma unroll 1
    for (int j = 28; j < 32 - TAILN; j++) QPLAIN(j);
    if (wg == 1) bar_sync(6, 256);
#pragma unroll 1
    for (int j = 32 - TAILN; j < 32; j++) QSTEP_A(j, (j & 3) * (Q_STAGE / 16), 1);
    if (wg == 0) asm volatile("bar.arrive 6, 256;" ::: "memory");
    mbar_wait(bar + B_UPD, 0);
    {
      const int sel = __float_as_int(lds32(sb + SM_UPD + 256)) - (wg * 64 + w * 16 + g);
      if (sel == 0 || sel == 8) {
#pragma unroll
        for (int j = 0; j < 16; j++) {
          const uint32_t u = __float_as_uint(lds32(sb + SM_UPD + j * 16 + t * 4));
          if (sel) gf[2 * j + 1] = u; else gf[2 * j] = u;
        }
      }
      __syncwarp();
      uint32_t xf[32];
#pragma unroll
      for (int j = 0; j < 8; j++)
        ldsm4(sb + (j >> 2 ? SM_X1 : SM_X0) + sw128 + ((((j & 3) * 2 + hi16) ^ x128) << 4), xf[4 * j], xf[4 * j + 1], xf[4 * j + 2], xf[4 * j + 3]);
      wg_wait<0>();
      reg_fence<64>(q);
      PROFC(8);
#pragma unroll
      for (int j = 0; j < 8; j++) {
        uint32_t o[4];
#pragma unroll
        for (int i = 0; i < 4; i++) o[i] = badd2(xf[4 * j + i], bmul2(pack2(q[8 * j + 2 * i], q[8 * j + 2 * i + 1]), gf[4 * j + i]));
        stsm4(sb + (j >> 2 ? SM_X1 : SM_X0) + sw128 + ((((j & 3) * 2 + hi16) ^ x128) << 4), o[0], o[1], o[2], o[3]);
      }
    }
    fence_async_smem();
    bar_sync(2 + wg, 128);
    if (w == 0 && elect_one()) {
      tma_store2d(&mOut, sb + SM_X0 + wg * 8192, hg * 128, mb * 128 + wg * 64);
      tma_store2d(&mOut, sb + SM_X1 + wg * 8192, hg * 128 + 64, mb * 128 + wg * 64);
      bulk_commit();
      bulk_wait_read0();
      if (wg == 1) { PROF(9); PROFT(33); PROF_DUMP; }
    }
  }
}

typedef CUresult (*EncodeFn)(CUtensorMap*, CUtensorMapDataType, cuuint32_t, void*, const cuuint64_t*, const cuuint64_t*, const cuuint32_t*,
                             const cuuint32_t*, CUtensorMapInterleave, CUtensorMapSwizzle, CUtensorMapL2promotion, CUtensorMapFloatOOBfill);

CUtensorMap make_map(EncodeFn enc, const void* ptr, int rank, const cuuint64_t* dims, const cuuint64_t* strides, const cuuint32_t* box, CUtensorMapSwizzle sw) {
  CUtensorMap m;
  const cuuint32_t es[5] = {1, 1, 1, 1, 1};
  enc(&m, CU_TENSOR_MAP_DATA_TYPE_BFLOAT16, rank, (void*)ptr, dims, strides, box, es, CU_TENSOR_MAP_INTERLEAVE_NONE, sw,
      CU_TENSOR_MAP_L2_PROMOTION_L2_128B, CU_TENSOR_MAP_FLOAT_OOB_FILL_NONE);
  return m;
}

}

extern "C" void kernel_launch(void* const* d_in, const int* in_sizes, int n_in, void* d_out, int out_size) {
  static EncodeFn enc = nullptr;
  static int by_sm = 0;
  if (!enc) {
    void* fn = nullptr;
    cudaDriverEntryPointQueryResult qr;
    cudaGetDriverEntryPoint("cuTensorMapEncodeTiled", &fn, cudaEnableDefault, &qr);
    enc = (EncodeFn)fn;
    cudaFuncSetAttribute(fused_kernel, cudaFuncAttributeMaxDynamicSharedMemorySize, SM_TOTAL);
    int dev = 0, sms = 0;
    cudaGetDevice(&dev);
    cudaDeviceGetAttribute(&sms, cudaDevAttrMultiProcessorCount, dev);
    by_sm = BY_SM && sms == NCTA + NSPARE;
  }
  Params P;
  P.by_sm = by_sm;
  P.x = (const __nv_bfloat16*)d_in[0];
  P.wqkv = (const __nv_bfloat16*)d_in[1];
  const void* wphi = d_in[2];
  P.wo = (const __nv_bfloat16*)d_in[3];
  P.w_r = (const __nv_bfloat16*)d_in[5];
  P.w_gate = (const __nv_bfloat16*)d_in[6];
  P.w_up = (const __nv_bfloat16*)d_in[7];
  P.w_down = (const __nv_bfloat16*)d_in[8];

  const cuuint64_t dX[2] = {DM, SEQ}, sX[1] = {DM * 2};
  const cuuint32_t b128[2] = {64, 128}, b64[2] = {64, 64};
  const cuuint64_t dW[4] = {64, DM, 16, 3}, sW[3] = {3 * DM * 2, 128, DM * 2};
  const cuuint32_t bKV[4] = {64, 64, 2, 2}, bQ[4] = {64, 64, 2, 1};
  const cuuint64_t dO[3] = {64, DM, 16}, sO[2] = {DM * 2, 128};
  const cuuint32_t bO[3] = {64, 64, 2};
  const cuuint64_t dP[2] = {32, 1024}, sP[1] = {64};
  const cuuint32_t bP[2] = {32, 128};
  CUtensorMap mX = make_map(enc, P.x, 2, dX, sX, b128, CU_TENSOR_MAP_SWIZZLE_128B);
  CUtensorMap mWkv = make_map(enc, P.wqkv, 4, dW, sW, bKV, CU_TENSOR_MAP_SWIZZLE_128B);
  CUtensorMap mWq = make_map(enc, P.wqkv, 4, dW, sW, bQ, CU_TENSOR_MAP_SWIZZLE_128B);
  CUtensorMap mWo = make_map(enc, P.wo, 3, dO, sO, bO, CU_TENSOR_MAP_SWIZZLE_128B);
  CUtensorMap mPhi = make_map(enc, wphi, 2, dP, sP, bP, CU_TENSOR_MAP_SWIZZLE_64B);
  const cuuint64_t dWp[5] = {DM, 2, 4, 4, DM / 32}, sWp[4] = {DM * 2, 8 * DM * 2, 2 * DM * 2, 32 * DM * 2};
  const cuuint32_t bWp[5] = {64, 2, 4, 4, 2};
  CUtensorMap mWp = make_map(enc, P.wo, 5, dWp, sWp, bWp, CU_TENSOR_MAP_SWIZZLE_128B);
  CUtensorMap mOut = make_map(enc, d_out, 2, dX, sX, b64, CU_TENSOR_MAP_SWIZZLE_128B);
  const cuuint64_t dWc[2] = {3 * DM, DM}, sWc[1] = {3 * DM * 2}, dG[2] = {FF, DM}, sG[1] = {FF * 2}, dD[3] = {64, FF, 16};
  const cuuint32_t b32[2] = {32, 32}, bD[3] = {64, 32, 4};
  CUtensorMap mWc = make_map(enc, P.wqkv, 2, dWc, sWc, b32, CU_TENSOR_MAP_SWIZZLE_NONE);
  CUtensorMap mG = make_map(enc, P.w_gate, 2, dG, sG, b32, CU_TENSOR_MAP_SWIZZLE_NONE);
  CUtensorMap mU = make_map(enc, P.w_up, 2, dG, sG, b32, CU_TENSOR_MAP_SWIZZLE_NONE);
  CUtensorMap mD = make_map(enc, P.w_down, 3, dD, sO, bD, CU_TENSOR_MAP_SWIZZLE_128B);
  const cuuint64_t dXs[3] = {256, SEQ, 4}, sXs[2] = {DM * 2, 512};
  const cuuint32_t bXs[3] = {256, 16, 2};
  CUtensorMap mXs = make_map(enc, P.x, 3, dXs, sXs, bXs, CU_TENSOR_MAP_SWIZZLE_NONE);
  const cuuint64_t dG2[4] = {64, DM, FF / 64, 1}, sG2[3] = {FF * 2, 128, (cuuint64_t)FF * DM * 2};
  CUtensorMap mG2 = make_map(enc, P.w_gate, 4, dG2, sG2, bQ, CU_TENSOR_MAP_SWIZZLE_128B);
  CUtensorMap mU2 = make_map(enc, P.w_up, 4, dG2, sG2, bQ, CU_TENSOR_MAP_SWIZZLE_128B);
  fused_kernel<<<NCTA + NSPARE, 384, SM_TOTAL, cudaStreamPerThread>>>(mX, mWkv, mWq, mWo, mPhi, mWp, mOut, mWc, mG, mU, mD, mXs, mG2, mU2, P);
}
```

```cpp
#include <cuda_runtime.h>
#include <cuda_bf16.h>
#include <cuda.h>
#include <stdint.h>

namespace {

constexpr int SEQ = 2048, DM = 1024, FF = 3584;
constexpr int NCTA = 128;
constexpr int NSPARE = 4;
constexpr int NFFN = FF / 32;
#define GN 6
#define G8 2
constexpr int GROWS = (3 * GN + G8) * 32;
#define TAILN 2
#define KTAIL 1
#define XS_EARLY 1
#define PF_FIRST 2
#define PF_W 5
#define PF_PRE 1
#define PFG 0
#define PFD 80
#define BY_SM 1
#define PTAB 0x73216540u
#define ROWSPLIT 1
#define WOT 1
#define PSPLIT 1
#define KSTEPS 4
#define NOVAL 0
#define KCH 1
#define REG_C 224
#define REG_H 56
#define TW 1
#define ORDER_ALL 1
#define AM_NS 100
constexpr bool FFN_OFF = false;

static_assert(2 * REG_C + REG_H <= 3 * 168, "the register pool of the CTA is 384 x 168");

__device__ uint32_t g_epoch[(NCTA + NSPARE) * 32];
__device__ unsigned long long g_stat[SEQ];
__device__ __align__(128) unsigned long long g_best[NCTA];
__device__ __align__(16) float g_y[2][8][DM];
__device__ __align__(128) uint32_t g_ycnt[64];
__device__ __align__(128) uint32_t g_xcnt[8 * 64];
__device__ __align__(128) uint4 g_res[2][32 * 256];
__device__ __align__(16) float g_cs[5 * DM];
__device__ __align__(128) float g_gp[2 * FF];
__device__ uint4 g_part[8 * 2 * 16 * 16 * 32];
__device__ __align__(16) float g_zpart[8 * 2 * 16 * 16 * 8];
__device__ __align__(128) float g_zres[32 * 64];
__device__ __align__(1024) uint4 g_ofr[16 * 16 * 1024];
#define PROF(i)
#define PROFT(i)
#define PROFC(i)
#define PROF_DUMP
#define PW0(J)
#define PW1(J)

constexpr uint32_t KV_STAGE = 49152, Q_STAGE = 32768;
constexpr uint32_t SM_V = 147456;
constexpr uint32_t SM_PHI = 163840;
constexpr uint32_t SM_XST = 147456;
constexpr uint32_t SM_FST = 172032;
constexpr uint32_t SM_PST0 = 196608, SM_PST1 = SM_PHI + 8192;
constexpr uint32_t SM_X0 = 131072, SM_X1 = SM_PHI + 16384;
constexpr uint32_t SM_WPHI = 204800;
constexpr uint32_t SM_ZT = 212992;
constexpr uint32_t SM_SDT = 217088;
constexpr uint32_t SM_CST = 219136;
constexpr uint32_t SM_HT = 222720;
constexpr uint32_t SM_STAT = 223232;
constexpr uint32_t SM_XSEL = 224256;
constexpr uint32_t SM_RED = 228352;
constexpr uint32_t SM_ROWS = SM_RED + 832;
constexpr uint32_t SM_GRED = SM_XSEL + 3072;
static_assert(GROWS <= 768, "xsel area");
constexpr uint32_t SM_UPD = 229632;
constexpr uint32_t SM_BAR = 230016;
constexpr uint32_t SM_PROF = 230464;
constexpr uint32_t SM_SINK = 231104;
constexpr uint32_t SM_TOTAL = 231616;
constexpr uint32_t SB = 1024;
constexpr uint32_t B_FULLKV = 0  , B_FST = 24  , B_XFULL = 88  , B_XST = 104  , B_WPHI = 120, B_CS = 128, B_CSQ = 136, B_UPD = 144,
                   B_H = 152, B_DN = 160, B_XS = 168, B_TILE = 176  , B_RES = 192  , B_PART = 208  ,
B_AIN = 224  ,
                   B_FULLQ = 288  ,
                   B_FFN = 320,
                   B_EMPTYKV = 328  , B_EMPTYQ = 352  , B_KVST = 384  , B_YD = 400, B_PHI = 408  , B_DND = 424, B_END = 432;

__device__ __forceinline__ uint32_t smem_u32(const void* p) { return (uint32_t)__cvta_generic_to_shared(p); }
__device__ __forceinline__ void mbar_init(uint32_t bar, uint32_t cnt) { asm volatile("mbarrier.init.shared::cta.b64 [%0], %1;" ::"r"(bar), "r"(cnt) : "memory"); }
__device__ __forceinline__ void mbar_expect_tx(uint32_t bar, uint32_t bytes) { asm volatile("mbarrier.arrive.expect_tx.shared::cta.b64 _, [%0], %1;" ::"r"(bar), "r"(bytes) : "memory"); }
__device__ __forceinline__ void mbar_arrive2(uint32_t bar) { asm volatile("mbarrier.arrive.shared::cta.b64 _, [%0], 2;" ::"r"(bar) : "memory"); }
__device__ __forceinline__ void mbar_arrive(uint32_t bar) { asm volatile("mbarrier.arrive.shared::cta.b64 _, [%0];" ::"r"(bar) : "memory"); }
__device__ __forceinline__ void mbar_wait(uint32_t bar, uint32_t parity) {
  asm volatile("{\n.reg .pred p;\nLW:\nmbarrier.try_wait.parity.shared::cta.b64 p, [%0], %1;\n@!p bra LW;\n}" ::"r"(bar), "r"(parity) : "memory");
}
__device__ __forceinline__ bool mbar_test(uint32_t bar, uint32_t parity) {
  uint32_t ok;
  asm volatile("{\n.reg .pred p;\nmbarrier.test_wait.parity.shared::cta.b64 p, [%1], %2;\nselp.u32 %0, 1, 0, p;\n}" : "=r"(ok) : "r"(bar), "r"(parity) : "memory");
  return ok;
}
__device__ __forceinline__ int lane_id() { int l; asm volatile("mov.u32 %0, %%laneid;" : "=r"(l)); return l; }
template <int C> __device__ __forceinline__ void sched_fence_(int zero) {
  asm volatile("{\n.reg .pred p;\nsetp.eq.s32 p, %0, %1;\nSF:\npmevent 1;\n@p bra SF;\n}" ::"r"(zero), "n"(C) : "memory");
}
#define SCHED_FENCE() sched_fence_<1000 + __COUNTER__>(zero)
#define SCHED_PIN(V) sched_fence_<1000 + __COUNTER__>(zero & __float_as_int(V))
__device__ __forceinline__ bool elect_one() {
  uint32_t p; asm volatile("{ .reg .pred P; elect.sync _|P, 0xffffffff; selp.u32 %0, 1, 0, P; }" : "=r"(p)); return p;
}
__device__ __forceinline__ void tma2d(uint32_t dst, const CUtensorMap* m, int x, int y, uint32_t bar) {
  asm volatile("cp.async.bulk.tensor.2d.shared::cluster.global.mbarrier::complete_tx::bytes [%0], [%1, {%3, %4}], [%2];" ::"r"(dst), "l"(m), "r"(bar), "r"(x), "r"(y) : "memory");
}
__device__ __forceinline__ void tma3d(uint32_t dst, const CUtensorMap* m, int x, int y, int z, uint32_t bar) {
  asm volatile("cp.async.bulk.tensor.3d.shared::cluster.global.mbarrier::complete_tx::bytes [%0], [%1, {%3, %4, %5}], [%2];" ::"r"(dst), "l"(m), "r"(bar), "r"(x), "r"(y), "r"(z) : "memory");
}
__device__ __forceinline__ void tma4d(uint32_t dst, const CUtensorMap* m, int x, int y, int z, int w, uint32_t bar) {
  asm volatile("cp.async.bulk.tensor.4d.shared::cluster.global.mbarrier::complete_tx::bytes [%0], [%1, {%3, %4, %5, %6}], [%2];" ::"r"(dst), "l"(m), "r"(bar), "r"(x), "r"(y), "r"(z), "r"(w) : "memory");
}
__device__ __forceinline__ void tma5d(uint32_t dst, const CUtensorMap* m, int x, int v, uint32_t bar) {
  asm volatile("cp.async.bulk.tensor.5d.shared::cluster.global.mbarrier::complete_tx::bytes [%0], [%1, {%3, %5, %5, %5, %4}], [%2];" ::"r"(dst), "l"(m), "r"(bar), "r"(x), "r"(v), "r"(0) : "memory");
}
__device__ __forceinline__ void tma_store2d(const CUtensorMap* m, uint32_t src, int x, int y) {
  asm volatile("cp.async.bulk.tensor.2d.global.shared::cta.bulk_group [%0, {%2, %3}], [%1];" ::"l"(m), "r"(src), "r"(x), "r"(y) : "memory");
}
__device__ __forceinline__ void bulk_load(uint32_t dst, const void* src, uint32_t bytes, uint32_t bar) {
  asm volatile("cp.async.bulk.shared::cluster.global.mbarrier::complete_tx::bytes [%0], [%1], %2, [%3];" ::"r"(dst), "l"(src), "r"(bytes), "r"(bar) : "memory");
}
__device__ __forceinline__ void bulk_commit() { asm volatile("cp.async.bulk.commit_group;" ::: "memory"); }
__device__ __forceinline__ void bulk_wait0() { asm volatile("cp.async.bulk.wait_group 0;" ::: "memory"); }
__device__ __forceinline__ void bulk_wait_read0() { asm volatile("cp.async.bulk.wait_group.read 0;" ::: "memory"); }
__device__ __forceinline__ void prefetch_l2(const void* p) { asm volatile("prefetch.global.L2 [%0];" ::"l"(p) : "memory"); }
__device__ __forceinline__ void touch_l2(const void* p, int lane) { asm volatile("cp.async.cg.shared.global.L2::128B [%0], [%1], 16;" ::"r"(SB + SM_SINK + lane * 16), "l"(p) : "memory"); }
__device__ __forceinline__ void prefetch_map(const CUtensorMap* m) { asm volatile("prefetch.tensormap [%0];" ::"l"(m) : "memory"); }
__device__ __forceinline__ void fence_async_smem() { asm volatile("fence.proxy.async.shared::cta;" ::: "memory"); }
__device__ __forceinline__ void fence_async_global() { asm volatile("fence.proxy.async.global;" ::: "memory"); }
__device__ __forceinline__ void bar_sync(int id, int n) { asm volatile("bar.sync %0, %1;" ::"r"(id), "r"(n) : "memory"); }
__device__ __forceinline__ void wg_fence() { asm volatile("wgmma.fence.sync.aligned;" ::: "memory"); }
__device__ __forceinline__ void wg_commit() { asm volatile("wgmma.commit_group.sync.aligned;" ::: "memory"); }
template <int N> __device__ __forceinline__ void wg_wait() { asm volatile("wgmma.wait_group.sync.aligned %0;" ::"n"(N) : "memory"); }
template <int N> __device__ __forceinline__ void reg_fence(uint32_t* r) {
#pragma unroll
  for (int i = 0; i < N; i++) asm volatile("" : "+r"(r[i])::"memory");
}
template <int N> __device__ __forceinline__ void reg_fence(float* r) {
#pragma unroll
  for (int i = 0; i < N; i++) asm volatile("" : "+f"(r[i])::"memory");
}
__device__ __forceinline__ uint64_t mkdesc(uint32_t addr, uint32_t lbo, uint32_t sbo, uint32_t swz, uint32_t dyn = 0) {
  const uint32_t lo = ((addr >> 4) | ((lbo >> 4) << 16)) + dyn;
  const uint32_t hi = (sbo >> 4) | (swz << 30);
  uint64_t d;
  asm("mov.b64 %0, {%1, %2};" : "=l"(d) : "r"(lo), "r"(hi));
  return d;
}
__device__ __forceinline__ void stsm4(uint32_t addr, uint32_t a, uint32_t b, uint32_t c, uint32_t d) {
  asm volatile("stmatrix.sync.aligned.m8n8.x4.shared.b16 [%0], {%1, %2, %3, %4};" ::"r"(addr), "r"(a), "r"(b), "r"(c), "r"(d) : "memory");
}
__device__ __forceinline__ void ldsm4(uint32_t addr, uint32_t& a, uint32_t& b, uint32_t& c, uint32_t& d) {
  asm volatile("ldmatrix.sync.aligned.m8n8.x4.shared.b16 {%0, %1, %2, %3}, [%4];" : "=r"(a), "=r"(b), "=r"(c), "=r"(d) : "r"(addr) : "memory");
}
__device__ __forceinline__ uint32_t pack2(float lo, float hi) { uint32_t r; asm("cvt.rn.bf16x2.f32 %0, %1, %2;" : "=r"(r) : "f"(hi), "f"(lo)); return r; }
__device__ __forceinline__ uint32_t bsub2(uint32_t a, uint32_t b) { uint32_t r; asm("sub.rn.bf16x2 %0, %1, %2;" : "=r"(r) : "r"(a), "r"(b)); return r; }
__device__ __forceinline__ uint32_t badd2(uint32_t a, uint32_t b) { uint32_t r; asm("add.rn.bf16x2 %0, %1, %2;" : "=r"(r) : "r"(a), "r"(b)); return r; }
__device__ __forceinline__ uint32_t bmul2(uint32_t a, uint32_t b) { uint32_t r; asm("mul.rn.bf16x2 %0, %1, %2;" : "=r"(r) : "r"(a), "r"(b)); return r; }
__device__ __forceinline__ float bf_lo(uint32_t v) { return __uint_as_float(v << 16); }
__device__ __forceinline__ float bf_hi(uint32_t v) { return __uint_as_float(v & 0xffff0000u); }
__device__ __forceinline__ float bf_round(float v) { return bf_lo(pack2(v, 0.f)); }
__device__ __forceinline__ float ex2(float v) { float r; asm("ex2.approx.ftz.f32 %0, %1;" : "=f"(r) : "f"(v)); return r; }
__device__ __forceinline__ float rcp(float v) { float r; asm("rcp.approx.ftz.f32 %0, %1;" : "=f"(r) : "f"(v)); return r; }
__device__ __forceinline__ float sqrt_approx(float v) { float r; asm("sqrt.approx.f32 %0, %1;" : "=f"(r) : "f"(v)); return r; }
__device__ __forceinline__ float4 lds128(uint32_t a) { float4 v; asm volatile("ld.shared.v4.f32 {%0, %1, %2, %3}, [%4];" : "=f"(v.x), "=f"(v.y), "=f"(v.z), "=f"(v.w) : "r"(a) : "memory"); return v; }
__device__ __forceinline__ uint4 lds128u(uint32_t a) { uint4 v; asm volatile("ld.shared.v4.u32 {%0, %1, %2, %3}, [%4];" : "=r"(v.x), "=r"(v.y), "=r"(v.z), "=r"(v.w) : "r"(a) : "memory"); return v; }
__device__ __forceinline__ float2 lds64(uint32_t a) { float2 v; asm volatile("ld.shared.v2.f32 {%0, %1}, [%2];" : "=f"(v.x), "=f"(v.y) : "r"(a) : "memory"); return v; }
__device__ __forceinline__ float lds32(uint32_t a) { float v; asm volatile("ld.shared.f32 %0, [%1];" : "=f"(v) : "r"(a) : "memory"); return v; }
__device__ __forceinline__ void sts32(uint32_t a, float v) { asm volatile("st.shared.f32 [%0], %1;" ::"r"(a), "f"(v) : "memory"); }
__device__ __forceinline__ void sts64(uint32_t a, float x, float y) { asm volatile("st.shared.v2.f32 [%0], {%1, %2};" ::"r"(a), "f"(x), "f"(y) : "memory"); }
__device__ __forceinline__ void sts128(uint32_t a, float x, float y, float z, float w) { asm volatile("st.shared.v4.f32 [%0], {%1, %2, %3, %4};" ::"r"(a), "f"(x), "f"(y), "f"(z), "f"(w) : "memory"); }
__device__ __forceinline__ void sts64u(uint32_t a, uint32_t x, uint32_t y) { asm volatile("st.shared.v2.u32 [%0], {%1, %2};" ::"r"(a), "r"(x), "r"(y) : "memory"); }
__device__ __forceinline__ void sts128u(uint32_t a, uint32_t x, uint32_t y, uint32_t z, uint32_t w) { asm volatile("st.shared.v4.u32 [%0], {%1, %2, %3, %4};" ::"r"(a), "r"(x), "r"(y), "r"(z), "r"(w) : "memory"); }
__device__ __forceinline__ uint4 ldg_nc(const void* p) { uint4 v; asm volatile("ld.global.nc.L1::no_allocate.v4.u32 {%0, %1, %2, %3}, [%4];" : "=r"(v.x), "=r"(v.y), "=r"(v.z), "=r"(v.w) : "l"(p)); return v; }
__device__ __forceinline__ float4 ldg_cg4(const float* p) { float4 v; asm volatile("ld.global.cg.v4.f32 {%0, %1, %2, %3}, [%4];" : "=f"(v.x), "=f"(v.y), "=f"(v.z), "=f"(v.w) : "l"(p) : "memory"); return v; }
__device__ __forceinline__ uint32_t ld_acq(const uint32_t* p) { uint32_t v; asm volatile("ld.acquire.gpu.global.u32 %0, [%1];" : "=r"(v) : "l"(p) : "memory"); return v; }
__device__ __forceinline__ uint32_t ld_acq_cta(uint32_t a) { uint32_t v; asm volatile("ld.acquire.cta.shared.u32 %0, [%1];" : "=r"(v) : "r"(a) : "memory"); return v; }
__device__ __forceinline__ void st_rel_cta(uint32_t a, uint32_t v) { asm volatile("st.release.cta.shared.u32 [%0], %1;" ::"r"(a), "r"(v) : "memory"); }
__device__ __forceinline__ unsigned long long ld_rlx64(const unsigned long long* p) { unsigned long long v; asm volatile("ld.relaxed.gpu.global.u64 %0, [%1];" : "=l"(v) : "l"(p) : "memory"); return v; }
__device__ __forceinline__ void st_rlx64(unsigned long long* p, unsigned long long v) { asm volatile("st.relaxed.gpu.global.u64 [%0], %1;" ::"l"(p), "l"(v) : "memory"); }
__device__ __forceinline__ uint4 ld_rlx128(const void* p) {
  uint4 v;
  asm volatile("{ .reg .b128 t; .reg .b64 a, b; ld.relaxed.gpu.global.b128 t, [%4]; mov.b128 {a, b}, t; mov.b64 {%0, %1}, a; mov.b64 {%2, %3}, b; }"
               : "=r"(v.x), "=r"(v.y), "=r"(v.z), "=r"(v.w) : "l"(p) : "memory");
  return v;
}
__device__ __forceinline__ void st_rlx128(void* p, uint32_t x, uint32_t y, uint32_t z, uint32_t w) {
  asm volatile("{ .reg .b128 t; .reg .b64 a, b; mov.b64 a, {%1, %2}; mov.b64 b, {%3, %4}; mov.b128 t, {a, b}; st.relaxed.gpu.global.b128 [%0], t; }"
               ::"l"(p), "r"(x), "r"(y), "r"(z), "r"(w) : "memory");
}
__device__ __forceinline__ void stg128(void* p, uint32_t x, uint32_t y, uint32_t z, uint32_t w) { asm volatile("st.global.v4.u32 [%0], {%1, %2, %3, %4};" ::"l"(p), "r"(x), "r"(y), "r"(z), "r"(w) : "memory"); }
__device__ __forceinline__ void st_rlx(void* p, uint32_t v) { asm volatile("st.relaxed.gpu.global.u32 [%0], %1;" ::"l"(p), "r"(v) : "memory"); }
__device__ __forceinline__ uint32_t lop_select(uint32_t a, uint32_t b, uint32_t m) { uint32_t r; asm("lop3.b32 %0, %1, %2, %3, 0xd8;" : "=r"(r) : "r"(a), "r"(b), "r"(m)); return r; }
__device__ __forceinline__ float unmark(uint32_t v) { return __uint_as_float(v & ~1u); }
__device__ __forceinline__ uint32_t mark(uint32_t v, uint32_t par) { return (v & ~1u) | par; }
__device__ __forceinline__ float tanh_approx(float v) { float r; asm("tanh.approx.f32 %0, %1;" : "=f"(r) : "f"(v)); return r; }
__device__ __forceinline__ void flag_rel(uint32_t* p, uint32_t v) { asm volatile("red.release.gpu.global.max.u32 [%0], %1;" ::"l"(p), "r"(v) : "memory"); }
__device__ __forceinline__ void red1(float* p, float a) { asm volatile("red.global.add.f32 [%0], %1;" ::"l"(p), "f"(a) : "memory"); }
__device__ __forceinline__ void red_inc(uint32_t* p) { asm volatile("red.relaxed.gpu.global.add.u32 [%0], 1;" ::"l"(p) : "memory"); }
__device__ __forceinline__ void red_rel(uint32_t* p) { asm volatile("red.release.gpu.global.add.u32 [%0], 1;" ::"l"(p) : "memory"); }
__device__ __forceinline__ void red4(float* p, float a, float b, float c, float d) { asm volatile("red.global.add.v4.f32 [%0], {%1, %2, %3, %4};" ::"l"(p), "f"(a), "f"(b), "f"(c), "f"(d) : "memory"); }
constexpr int SPIN_MAX = 100000;
__device__ __forceinline__ uint32_t ld_rlx(const uint32_t* p) { uint32_t v; asm volatile("ld.relaxed.gpu.global.u32 %0, [%1];" : "=r"(v) : "l"(p) : "memory"); return v; }
template <int NS = 0> __device__ __forceinline__ void wait_hint(const uint32_t* p, uint32_t target) {
#pragma unroll 1
  for (int i = 0; i < SPIN_MAX; i++) { if ((int)(ld_rlx(p) - target) >= 0) break; if (NS) __nanosleep(NS); }
}
template <int NS> __device__ __forceinline__ void wait_cnt(const uint32_t* p, uint32_t target) {
#pragma unroll 1
  for (int i = 0; i < SPIN_MAX; i++) { if ((int)(ld_rlx(p) - target) >= 0) break; if (NS) __nanosleep(NS); }
  (void)ld_acq(p);
}
template <int NS> __device__ __forceinline__ unsigned long long wait_tag(const unsigned long long* p, uint32_t tag) {
  unsigned long long v = 0;
#pragma unroll 1
  for (int i = 0; i < SPIN_MAX; i++) { v = ld_rlx64(p); if ((uint32_t)(v >> 32) == tag) break; if (NS) __nanosleep(NS); }
  return v;
}
__device__ __forceinline__ float silu_f(float v) { return v * rcp(1.f + ex2(-1.4426950408889634f * v)); }

__device__ __forceinline__ void wgmma_n8_ss_ta1_tb0(float* d, uint64_t da, uint64_t db, bool accumulate) {
  if (accumulate) {
    asm volatile("{\n.reg .pred p;\nsetp.ne.b32 p, 1, 0;\n"
      "wgmma.mma_async.sync.aligned.m64n8k16.f32.bf16.bf16 "
      "{%0, %1, %2, %3}, "
      "%4, %5, p, 1, 1, 1, 0;\n}\n"
      : "+f"(d[0]), "+f"(d[1]), "+f"(d[2]), "+f"(d[3])
      : "l"(da), "l"(db));
  } else {
    asm volatile("{\n.reg .pred p;\nsetp.ne.b32 p, 0, 0;\n"
      "wgmma.mma_async.sync.aligned.m64n8k16.f32.bf16.bf16 "
      "{%0, %1, %2, %3}, "
      "%4, %5, p, 1, 1, 1, 0;\n}\n"
      : "=f"(d[0]), "=f"(d[1]), "=f"(d[2]), "=f"(d[3])
      : "l"(da), "l"(db));
  }
}
__device__ __forceinline__ void wgmma_n8_ss_ta1_tb1(float* d, uint64_t da, uint64_t db, bool accumulate) {
  if (accumulate) {
    asm volatile("{\n.reg .pred p;\nsetp.ne.b32 p, 1, 0;\n"
      "wgmma.mma_async.sync.aligned.m64n8k16.f32.bf16.bf16 "
      "{%0, %1, %2, %3}, "
      "%4, %5, p, 1, 1, 1, 1;\n}\n"
      : "+f"(d[0]), "+f"(d[1]), "+f"(d[2]), "+f"(d[3])
      : "l"(da), "l"(db));
  } else {
    asm volatile("{\n.reg .pred p;\nsetp.ne.b32 p, 0, 0;\n"
      "wgmma.mma_async.sync.aligned.m64n8k16.f32.bf16.bf16 "
      "{%0, %1, %2, %3}, "
      "%4, %5, p, 1, 1, 1, 1;\n}\n"
      : "=f"(d[0]), "=f"(d[1]), "=f"(d[2]), "=f"(d[3])
      : "l"(da), "l"(db));
  }
}
__device__ __forceinline__ void wgmma_n32_rs_ta0_tb1(float* d, uint32_t a0, uint32_t a1, uint32_t a2, uint32_t a3, uint64_t db, bool accumulate) {
  if (accumulate) {
    asm volatile("{\n.reg .pred p;\nsetp.ne.b32 p, 1, 0;\n"
      "wgmma.mma_async.sync.aligned.m64n32k16.f32.bf16.bf16 "
      "{%0, %1, %2, %3, %4, %5, %6, %7, %8, %9, %10, %11, %12, %13, %14, %15}, "
      "{%16, %17, %18, %19}, %20, p, 1, 1, 1;\n}\n"
      : "+f"(d[0]), "+f"(d[1]), "+f"(d[2]), "+f"(d[3]), "+f"(d[4]), "+f"(d[5]), "+f"(d[6]), "+f"(d[7]), "+f"(d[8]), "+f"(d[9]), "+f"(d[10]), "+f"(d[11]), "+f"(d[12]), "+f"(d[13]), "+f"(d[14]), "+f"(d[15])
      : "r"(a0), "r"(a1), "r"(a2), "r"(a3), "l"(db));
  } else {
    asm volatile("{\n.reg .pred p;\nsetp.ne.b32 p, 0, 0;\n"
      "wgmma.mma_async.sync.aligned.m64n32k16.f32.bf16.bf16 "
      "{%0, %1, %2, %3, %4, %5, %6, %7, %8, %9, %10, %11, %12, %13, %14, %15}, "
      "{%16, %17, %18, %19}, %20, p, 1, 1, 1;\n}\n"
      : "=f"(d[0]), "=f"(d[1]), "=f"(d[2]), "=f"(d[3]), "=f"(d[4]), "=f"(d[5]), "=f"(d[6]), "=f"(d[7]), "=f"(d[8]), "=f"(d[9]), "=f"(d[10]), "=f"(d[11]), "=f"(d[12]), "=f"(d[13]), "=f"(d[14]), "=f"(d[15])
      : "r"(a0), "r"(a1), "r"(a2), "r"(a3), "l"(db));
  }
}
__device__ __forceinline__ void wgmma_n40_rs_ta0_tb1(float* d, uint32_t a0, uint32_t a1, uint32_t a2, uint32_t a3, uint64_t db, bool accumulate) {
  if (accumulate) {
    asm volatile("{\n.reg .pred p;\nsetp.ne.b32 p, 1, 0;\n"
      "wgmma.mma_async.sync.aligned.m64n40k16.f32.bf16.bf16 "
      "{%0, %1, %2, %3, %4, %5, %6, %7, %8, %9, %10, %11, %12, %13, %14, %15, %16, %17, %18, %19}, "
      "{%20, %21, %22, %23}, %24, p, 1, 1, 1;\n}\n"
      : "+f"(d[0]), "+f"(d[1]), "+f"(d[2]), "+f"(d[3]), "+f"(d[4]), "+f"(d[5]), "+f"(d[6]), "+f"(d[7]), "+f"(d[8]), "+f"(d[9]), "+f"(d[10]), "+f"(d[11]), "+f"(d[12]), "+f"(d[13]), "+f"(d[14]), "+f"(d[15]), "+f"(d[16]), "+f"(d[17]), "+f"(d[18]), "+f"(d[19])
      : "r"(a0), "r"(a1), "r"(a2), "r"(a3), "l"(db));
  } else {
    asm volatile("{\n.reg .pred p;\nsetp.ne.b32 p, 0, 0;\n"
      "wgmma.mma_async.sync.aligned.m64n40k16.f32.bf16.bf16 "
      "{%0, %1, %2, %3, %4, %5, %6, %7, %8, %9, %10, %11, %12, %13, %14, %15, %16, %17, %18, %19}, "
      "{%20, %21, %22, %23}, %24, p, 1, 1, 1;\n}\n"
      : "=f"(d[0]), "=f"(d[1]), "=f"(d[2]), "=f"(d[3]), "=f"(d[4]), "=f"(d[5]), "=f"(d[6]), "=f"(d[7]), "=f"(d[8]), "=f"(d[9]), "=f"(d[10]), "=f"(d[11]), "=f"(d[12]), "=f"(d[13]), "=f"(d[14]), "=f"(d[15]), "=f"(d[16]), "=f"(d[17]), "=f"(d[18]), "=f"(d[19])
      : "r"(a0), "r"(a1), "r"(a2), "r"(a3), "l"(db));
  }
}
__device__ __forceinline__ void wgmma_n40_ss_ta1_tb1(float* d, uint64_t da, uint64_t db, bool accumulate) {
  if (accumulate) {
    asm volatile("{\n.reg .pred p;\nsetp.ne.b32 p, 1, 0;\n"
      "wgmma.mma_async.sync.aligned.m64n40k16.f32.bf16.bf16 "
      "{%0, %1, %2, %3, %4, %5, %6, %7, %8, %9, %10, %11, %12, %13, %14, %15, %16, %17, %18, %19}, "
      "%20, %21, p, 1, 1, 1, 1;\n}\n"
      : "+f"(d[0]), "+f"(d[1]), "+f"(d[2]), "+f"(d[3]), "+f"(d[4]), "+f"(d[5]), "+f"(d[6]), "+f"(d[7]), "+f"(d[8]), "+f"(d[9]), "+f"(d[10]), "+f"(d[11]), "+f"(d[12]), "+f"(d[13]), "+f"(d[14]), "+f"(d[15]), "+f"(d[16]), "+f"(d[17]), "+f"(d[18]), "+f"(d[19])
      : "l"(da), "l"(db));
  } else {
    asm volatile("{\n.reg .pred p;\nsetp.ne.b32 p, 0, 0;\n"
      "wgmma.mma_async.sync.aligned.m64n40k16.f32.bf16.bf16 "
      "{%0, %1, %2, %3, %4, %5, %6, %7, %8, %9, %10, %11, %12, %13, %14, %15, %16, %17, %18, %19}, "
      "%20, %21, p, 1, 1, 1, 1;\n}\n"
      : "=f"(d[0]), "=f"(d[1]), "=f"(d[2]), "=f"(d[3]), "=f"(d[4]), "=f"(d[5]), "=f"(d[6]), "=f"(d[7]), "=f"(d[8]), "=f"(d[9]), "=f"(d[10]), "=f"(d[11]), "=f"(d[12]), "=f"(d[13]), "=f"(d[14]), "=f"(d[15]), "=f"(d[16]), "=f"(d[17]), "=f"(d[18]), "=f"(d[19])
      : "l"(da), "l"(db));
  }
}
__device__ __forceinline__ void wgmma_n128_rs_ta0_tb1(float* d, uint32_t a0, uint32_t a1, uint32_t a2, uint32_t a3, uint64_t db, bool accumulate) {
  if (accumulate) {
    asm volatile("{\n.reg .pred p;\nsetp.ne.b32 p, 1, 0;\n"
      "wgmma.mma_async.sync.aligned.m64n128k16.f32.bf16.bf16 "
      "{%0, %1, %2, %3, %4, %5, %6, %7, %8, %9, %10, %11, %12, %13, %14, %15, %16, %17, %18, %19, %20, %21, %22, %23, %24, %25, %26, %27, %28, %29, %30, %31, %32, %33, %34, %35, %36, %37, %38, %39, %40, %41, %42, %43, %44, %45, %46, %47, %48, %49, %50, %51, %52, %53, %54, %55, %56, %57, %58, %59, %60, %61, %62, %63}, "
      "{%64, %65, %66, %67}, %68, p, 1, 1, 1;\n}\n"
      : "+f"(d[0]), "+f"(d[1]), "+f"(d[2]), "+f"(d[3]), "+f"(d[4]), "+f"(d[5]), "+f"(d[6]), "+f"(d[7]), "+f"(d[8]), "+f"(d[9]), "+f"(d[10]), "+f"(d[11]), "+f"(d[12]), "+f"(d[13]), "+f"(d[14]), "+f"(d[15]), "+f"(d[16]), "+f"(d[17]), "+f"(d[18]), "+f"(d[19]), "+f"(d[20]), "+f"(d[21]), "+f"(d[22]), "+f"(d[23]), "+f"(d[24]), "+f"(d[25]), "+f"(d[26]), "+f"(d[27]), "+f"(d[28]), "+f"(d[29]), "+f"(d[30]), "+f"(d[31]), "+f"(d[32]), "+f"(d[33]), "+f"(d[34]), "+f"(d[35]), "+f"(d[36]), "+f"(d[37]), "+f"(d[38]), "+f"(d[39]), "+f"(d[40]), "+f"(d[41]), "+f"(d[42]), "+f"(d[43]), "+f"(d[44]), "+f"(d[45]), "+f"(d[46]), "+f"(d[47]), "+f"(d[48]), "+f"(d[49]), "+f"(d[50]), "+f"(d[51]), "+f"(d[52]), "+f"(d[53]), "+f"(d[54]), "+f"(d[55]), "+f"(d[56]), "+f"(d[57]), "+f"(d[58]), "+f"(d[59]), "+f"(d[60]), "+f"(d[61]), "+f"(d[62]), "+f"(d[63])
      : "r"(a0), "r"(a1), "r"(a2), "r"(a3), "l"(db));
  } else {
    asm volatile("{\n.reg .pred p;\nsetp.ne.b32 p, 0, 0;\n"
      "wgmma.mma_async.sync.aligned.m64n128k16.f32.bf16.bf16 "
      "{%0, %1, %2, %3, %4, %5, %6, %7, %8, %9, %10, %11, %12, %13, %14, %15, %16, %17, %18, %19, %20, %21, %22, %23, %24, %25, %26, %27, %28, %29, %30, %31, %32, %33, %34, %35, %36, %37, %38, %39, %40, %41, %42, %43, %44, %45, %46, %47, %48, %49, %50, %51, %52, %53, %54, %55, %56, %57, %58, %59, %60, %61, %62, %63}, "
      "{%64, %65, %66, %67}, %68, p, 1, 1, 1;\n}\n"
      : "=f"(d[0]), "=f"(d[1]), "=f"(d[2]), "=f"(d[3]), "=f"(d[4]), "=f"(d[5]), "=f"(d[6]), "=f"(d[7]), "=f"(d[8]), "=f"(d[9]), "=f"(d[10]), "=f"(d[11]), "=f"(d[12]), "=f"(d[13]), "=f"(d[14]), "=f"(d[15]), "=f"(d[16]), "=f"(d[17]), "=f"(d[18]), "=f"(d[19]), "=f"(d[20]), "=f"(d[21]), "=f"(d[22]), "=f"(d[23]), "=f"(d[24]), "=f"(d[25]), "=f"(d[26]), "=f"(d[27]), "=f"(d[28]), "=f"(d[29]), "=f"(d[30]), "=f"(d[31]), "=f"(d[32]), "=f"(d[33]), "=f"(d[34]), "=f"(d[35]), "=f"(d[36]), "=f"(d[37]), "=f"(d[38]), "=f"(d[39]), "=f"(d[40]), "=f"(d[41]), "=f"(d[42]), "=f"(d[43]), "=f"(d[44]), "=f"(d[45]), "=f"(d[46]), "=f"(d[47]), "=f"(d[48]), "=f"(d[49]), "=f"(d[50]), "=f"(d[51]), "=f"(d[52]), "=f"(d[53]), "=f"(d[54]), "=f"(d[55]), "=f"(d[56]), "=f"(d[57]), "=f"(d[58]), "=f"(d[59]), "=f"(d[60]), "=f"(d[61]), "=f"(d[62]), "=f"(d[63])
      : "r"(a0), "r"(a1), "r"(a2), "r"(a3), "l"(db));
  }
}
__device__ __forceinline__ void wgmma_n128_ss_ta0_tb1(float* d, uint64_t da, uint64_t db, bool accumulate) {
  if (accumulate) {
    asm volatile("{\n.reg .pred p;\nsetp.ne.b32 p, 1, 0;\n"
      "wgmma.mma_async.sync.aligned.m64n128k16.f32.bf16.bf16 "
      "{%0, %1, %2, %3, %4, %5, %6, %7, %8, %9, %10, %11, %12, %13, %14, %15, %16, %17, %18, %19, %20, %21, %22, %23, %24, %25, %26, %27, %28, %29, %30, %31, %32, %33, %34, %35, %36, %37, %38, %39, %40, %41, %42, %43, %44, %45, %46, %47, %48, %49, %50, %51, %52, %53, %54, %55, %56, %57, %58, %59, %60, %61, %62, %63}, "
      "%64, %65, p, 1, 1, 0, 1;\n}\n"
      : "+f"(d[0]), "+f"(d[1]), "+f"(d[2]), "+f"(d[3]), "+f"(d[4]), "+f"(d[5]), "+f"(d[6]), "+f"(d[7]), "+f"(d[8]), "+f"(d[9]), "+f"(d[10]), "+f"(d[11]), "+f"(d[12]), "+f"(d[13]), "+f"(d[14]), "+f"(d[15]), "+f"(d[16]), "+f"(d[17]), "+f"(d[18]), "+f"(d[19]), "+f"(d[20]), "+f"(d[21]), "+f"(d[22]), "+f"(d[23]), "+f"(d[24]), "+f"(d[25]), "+f"(d[26]), "+f"(d[27]), "+f"(d[28]), "+f"(d[29]), "+f"(d[30]), "+f"(d[31]), "+f"(d[32]), "+f"(d[33]), "+f"(d[34]), "+f"(d[35]), "+f"(d[36]), "+f"(d[37]), "+f"(d[38]), "+f"(d[39]), "+f"(d[40]), "+f"(d[41]), "+f"(d[42]), "+f"(d[43]), "+f"(d[44]), "+f"(d[45]), "+f"(d[46]), "+f"(d[47]), "+f"(d[48]), "+f"(d[49]), "+f"(d[50]), "+f"(d[51]), "+f"(d[52]), "+f"(d[53]), "+f"(d[54]), "+f"(d[55]), "+f"(d[56]), "+f"(d[57]), "+f"(d[58]), "+f"(d[59]), "+f"(d[60]), "+f"(d[61]), "+f"(d[62]), "+f"(d[63])
      : "l"(da), "l"(db));
  } else {
    asm volatile("{\n.reg .pred p;\nsetp.ne.b32 p, 0, 0;\n"
      "wgmma.mma_async.sync.aligned.m64n128k16.f32.bf16.bf16 "
      "{%0, %1, %2, %3, %4, %5, %6, %7, %8, %9, %10, %11, %12, %13, %14, %15, %16, %17, %18, %19, %20, %21, %22, %23, %24, %25, %26, %27, %28, %29, %30, %31, %32, %33, %34, %35, %36, %37, %38, %39, %40, %41, %42, %43, %44, %45, %46, %47, %48, %49, %50, %51, %52, %53, %54, %55, %56, %57, %58, %59, %60, %61, %62, %63}, "
      "%64, %65, p, 1, 1, 0, 1;\n}\n"
      : "=f"(d[0]), "=f"(d[1]), "=f"(d[2]), "=f"(d[3]), "=f"(d[4]), "=f"(d[5]), "=f"(d[6]), "=f"(d[7]), "=f"(d[8]), "=f"(d[9]), "=f"(d[10]), "=f"(d[11]), "=f"(d[12]), "=f"(d[13]), "=f"(d[14]), "=f"(d[15]), "=f"(d[16]), "=f"(d[17]), "=f"(d[18]), "=f"(d[19]), "=f"(d[20]), "=f"(d[21]), "=f"(d[22]), "=f"(d[23]), "=f"(d[24]), "=f"(d[25]), "=f"(d[26]), "=f"(d[27]), "=f"(d[28]), "=f"(d[29]), "=f"(d[30]), "=f"(d[31]), "=f"(d[32]), "=f"(d[33]), "=f"(d[34]), "=f"(d[35]), "=f"(d[36]), "=f"(d[37]), "=f"(d[38]), "=f"(d[39]), "=f"(d[40]), "=f"(d[41]), "=f"(d[42]), "=f"(d[43]), "=f"(d[44]), "=f"(d[45]), "=f"(d[46]), "=f"(d[47]), "=f"(d[48]), "=f"(d[49]), "=f"(d[50]), "=f"(d[51]), "=f"(d[52]), "=f"(d[53]), "=f"(d[54]), "=f"(d[55]), "=f"(d[56]), "=f"(d[57]), "=f"(d[58]), "=f"(d[59]), "=f"(d[60]), "=f"(d[61]), "=f"(d[62]), "=f"(d[63])
      : "l"(da), "l"(db));
  }
}
__device__ __forceinline__ void wgmma_n256_rs_ta0_tb1(float* d, uint32_t a0, uint32_t a1, uint32_t a2, uint32_t a3, uint64_t db, bool accumulate) {
  if (accumulate) {
    asm volatile("{\n.reg .pred p;\nsetp.ne.b32 p, 1, 0;\n"
      "wgmma.mma_async.sync.aligned.m64n256k16.f32.bf16.bf16 "
      "{%0, %1, %2, %3, %4, %5, %6, %7, %8, %9, %10, %11, %12, %13, %14, %15, %16, %17, %18, %19, %20, %21, %22, %23, %24, %25, %26, %27, %28, %29, %30, %31, %32, %33, %34, %35, %36, %37, %38, %39, %40, %41, %42, %43, %44, %45, %46, %47, %48, %49, %50, %51, %52, %53, %54, %55, %56, %57, %58, %59, %60, %61, %62, %63, %64, %65, %66, %67, %68, %69, %70, %71, %72, %73, %74, %75, %76, %77, %78, %79, %80, %81, %82, %83, %84, %85, %86, %87, %88, %89, %90, %91, %92, %93, %94, %95, %96, %97, %98, %99, %100, %101, %102, %103, %104, %105, %106, %107, %108, %109, %110, %111, %112, %113, %114, %115, %116, %117, %118, %119, %120, %121, %122, %123, %124, %125, %126, %127}, "
      "{%128, %129, %130, %131}, %132, p, 1, 1, 1;\n}\n"
      : "+f"(d[0]), "+f"(d[1]), "+f"(d[2]), "+f"(d[3]), "+f"(d[4]), "+f"(d[5]), "+f"(d[6]), "+f"(d[7]), "+f"(d[8]), "+f"(d[9]), "+f"(d[10]), "+f"(d[11]), "+f"(d[12]), "+f"(d[13]), "+f"(d[14]), "+f"(d[15]), "+f"(d[16]), "+f"(d[17]), "+f"(d[18]), "+f"(d[19]), "+f"(d[20]), "+f"(d[21]), "+f"(d[22]), "+f"(d[23]), "+f"(d[24]), "+f"(d[25]), "+f"(d[26]), "+f"(d[27]), "+f"(d[28]), "+f"(d[29]), "+f"(d[30]), "+f"(d[31]), "+f"(d[32]), "+f"(d[33]), "+f"(d[34]), "+f"(d[35]), "+f"(d[36]), "+f"(d[37]), "+f"(d[38]), "+f"(d[39]), "+f"(d[40]), "+f"(d[41]), "+f"(d[42]), "+f"(d[43]), "+f"(d[44]), "+f"(d[45]), "+f"(d[46]), "+f"(d[47]), "+f"(d[48]), "+f"(d[49]), "+f"(d[50]), "+f"(d[51]), "+f"(d[52]), "+f"(d[53]), "+f"(d[54]), "+f"(d[55]), "+f"(d[56]), "+f"(d[57]), "+f"(d[58]), "+f"(d[59]), "+f"(d[60]), "+f"(d[61]), "+f"(d[62]), "+f"(d[63]), "+f"(d[64]), "+f"(d[65]), "+f"(d[66]), "+f"(d[67]), "+f"(d[68]), "+f"(d[69]), "+f"(d[70]), "+f"(d[71]), "+f"(d[72]), "+f"(d[73]), "+f"(d[74]), "+f"(d[75]), "+f"(d[76]), "+f"(d[77]), "+f"(d[78]), "+f"(d[79]), "+f"(d[80]), "+f"(d[81]), "+f"(d[82]), "+f"(d[83]), "+f"(d[84]), "+f"(d[85]), "+f"(d[86]), "+f"(d[87]), "+f"(d[88]), "+f"(d[89]), "+f"(d[90]), "+f"(d[91]), "+f"(d[92]), "+f"(d[93]), "+f"(d[94]), "+f"(d[95]), "+f"(d[96]), "+f"(d[97]), "+f"(d[98]), "+f"(d[99]), "+f"(d[100]), "+f"(d[101]), "+f"(d[102]), "+f"(d[103]), "+f"(d[104]), "+f"(d[105]), "+f"(d[106]), "+f"(d[107]), "+f"(d[108]), "+f"(d[109]), "+f"(d[110]), "+f"(d[111]), "+f"(d[112]), "+f"(d[113]), "+f"(d[114]), "+f"(d[115]), "+f"(d[116]), "+f"(d[117]), "+f"(d[118]), "+f"(d[119]), "+f"(d[120]), "+f"(d[121]), "+f"(d[122]), "+f"(d[123]), "+f"(d[124]), "+f"(d[125]), "+f"(d[126]), "+f"(d[127])
      : "r"(a0), "r"(a1), "r"(a2), "r"(a3), "l"(db));
  } else {
    asm volatile("{\n.reg .pred p;\nsetp.ne.b32 p, 0, 0;\n"
      "wgmma.mma_async.sync.aligned.m64n256k16.f32.bf16.bf16 "
      "{%0, %1, %2, %3, %4, %5, %6, %7, %8, %9, %10, %11, %12, %13, %14, %15, %16, %17, %18, %19, %20, %21, %22, %23, %24, %25, %26, %27, %28, %29, %30, %31, %32, %33, %34, %35, %36, %37, %38, %39, %40, %41, %42, %43, %44, %45, %46, %47, %48, %49, %50, %51, %52, %53, %54, %55, %56, %57, %58, %59, %60, %61, %62, %63, %64, %65, %66, %67, %68, %69, %70, %71, %72, %73, %74, %75, %76, %77, %78, %79, %80, %81, %82, %83, %84, %85, %86, %87, %88, %89, %90, %91, %92, %93, %94, %95, %96, %97, %98, %99, %100, %101, %102, %103, %104, %105, %106, %107, %108, %109, %110, %111, %112, %113, %114, %115, %116, %117, %118, %119, %120, %121, %122, %123, %124, %125, %126, %127}, "
      "{%128, %129, %130, %131}, %132, p, 1, 1, 1;\n}\n"
      : "=f"(d[0]), "=f"(d[1]), "=f"(d[2]), "=f"(d[3]), "=f"(d[4]), "=f"(d[5]), "=f"(d[6]), "=f"(d[7]), "=f"(d[8]), "=f"(d[9]), "=f"(d[10]), "=f"(d[11]), "=f"(d[12]), "=f"(d[13]), "=f"(d[14]), "=f"(d[15]), "=f"(d[16]), "=f"(d[17]), "=f"(d[18]), "=f"(d[19]), "=f"(d[20]), "=f"(d[21]), "=f"(d[22]), "=f"(d[23]), "=f"(d[24]), "=f"(d[25]), "=f"(d[26]), "=f"(d[27]), "=f"(d[28]), "=f"(d[29]), "=f"(d[30]), "=f"(d[31]), "=f"(d[32]), "=f"(d[33]), "=f"(d[34]), "=f"(d[35]), "=f"(d[36]), "=f"(d[37]), "=f"(d[38]), "=f"(d[39]), "=f"(d[40]), "=f"(d[41]), "=f"(d[42]), "=f"(d[43]), "=f"(d[44]), "=f"(d[45]), "=f"(d[46]), "=f"(d[47]), "=f"(d[48]), "=f"(d[49]), "=f"(d[50]), "=f"(d[51]), "=f"(d[52]), "=f"(d[53]), "=f"(d[54]), "=f"(d[55]), "=f"(d[56]), "=f"(d[57]), "=f"(d[58]), "=f"(d[59]), "=f"(d[60]), "=f"(d[61]), "=f"(d[62]), "=f"(d[63]), "=f"(d[64]), "=f"(d[65]), "=f"(d[66]), "=f"(d[67]), "=f"(d[68]), "=f"(d[69]), "=f"(d[70]), "=f"(d[71]), "=f"(d[72]), "=f"(d[73]), "=f"(d[74]), "=f"(d[75]), "=f"(d[76]), "=f"(d[77]), "=f"(d[78]), "=f"(d[79]), "=f"(d[80]), "=f"(d[81]), "=f"(d[82]), "=f"(d[83]), "=f"(d[84]), "=f"(d[85]), "=f"(d[86]), "=f"(d[87]), "=f"(d[88]), "=f"(d[89]), "=f"(d[90]), "=f"(d[91]), "=f"(d[92]), "=f"(d[93]), "=f"(d[94]), "=f"(d[95]), "=f"(d[96]), "=f"(d[97]), "=f"(d[98]), "=f"(d[99]), "=f"(d[100]), "=f"(d[101]), "=f"(d[102]), "=f"(d[103]), "=f"(d[104]), "=f"(d[105]), "=f"(d[106]), "=f"(d[107]), "=f"(d[108]), "=f"(d[109]), "=f"(d[110]), "=f"(d[111]), "=f"(d[112]), "=f"(d[113]), "=f"(d[114]), "=f"(d[115]), "=f"(d[116]), "=f"(d[117]), "=f"(d[118]), "=f"(d[119]), "=f"(d[120]), "=f"(d[121]), "=f"(d[122]), "=f"(d[123]), "=f"(d[124]), "=f"(d[125]), "=f"(d[126]), "=f"(d[127])
      : "r"(a0), "r"(a1), "r"(a2), "r"(a3), "l"(db));
  }
}
__device__ __forceinline__ void wgmma_n256_ss_ta0_tb1(float* d, uint64_t da, uint64_t db, bool accumulate) {
  if (accumulate) {
    asm volatile("{\n.reg .pred p;\nsetp.ne.b32 p, 1, 0;\n"
      "wgmma.mma_async.sync.aligned.m64n256k16.f32.bf16.bf16 "
      "{%0, %1, %2, %3, %4, %5, %6, %7, %8, %9, %10, %11, %12, %13, %14, %15, %16, %17, %18, %19, %20, %21, %22, %23, %24, %25, %26, %27, %28, %29, %30, %31, %32, %33, %34, %35, %36, %37, %38, %39, %40, %41, %42, %43, %44, %45, %46, %47, %48, %49, %50, %51, %52, %53, %54, %55, %56, %57, %58, %59, %60, %61, %62, %63, %64, %65, %66, %67, %68, %69, %70, %71, %72, %73, %74, %75, %76, %77, %78, %79, %80, %81, %82, %83, %84, %85, %86, %87, %88, %89, %90, %91, %92, %93, %94, %95, %96, %97, %98, %99, %100, %101, %102, %103, %104, %105, %106, %107, %108, %109, %110, %111, %112, %113, %114, %115, %116, %117, %118, %119, %120, %121, %122, %123, %124, %125, %126, %127}, "
      "%128, %129, p, 1, 1, 0, 1;\n}\n"
      : "+f"(d[0]), "+f"(d[1]), "+f"(d[2]), "+f"(d[3]), "+f"(d[4]), "+f"(d[5]), "+f"(d[6]), "+f"(d[7]), "+f"(d[8]), "+f"(d[9]), "+f"(d[10]), "+f"(d[11]), "+f"(d[12]), "+f"(d[13]), "+f"(d[14]), "+f"(d[15]), "+f"(d[16]), "+f"(d[17]), "+f"(d[18]), "+f"(d[19]), "+f"(d[20]), "+f"(d[21]), "+f"(d[22]), "+f"(d[23]), "+f"(d[24]), "+f"(d[25]), "+f"(d[26]), "+f"(d[27]), "+f"(d[28]), "+f"(d[29]), "+f"(d[30]), "+f"(d[31]), "+f"(d[32]), "+f"(d[33]), "+f"(d[34]), "+f"(d[35]), "+f"(d[36]), "+f"(d[37]), "+f"(d[38]), "+f"(d[39]), "+f"(d[40]), "+f"(d[41]), "+f"(d[42]), "+f"(d[43]), "+f"(d[44]), "+f"(d[45]), "+f"(d[46]), "+f"(d[47]), "+f"(d[48]), "+f"(d[49]), "+f"(d[50]), "+f"(d[51]), "+f"(d[52]), "+f"(d[53]), "+f"(d[54]), "+f"(d[55]), "+f"(d[56]), "+f"(d[57]), "+f"(d[58]), "+f"(d[59]), "+f"(d[60]), "+f"(d[61]), "+f"(d[62]), "+f"(d[63]), "+f"(d[64]), "+f"(d[65]), "+f"(d[66]), "+f"(d[67]), "+f"(d[68]), "+f"(d[69]), "+f"(d[70]), "+f"(d[71]), "+f"(d[72]), "+f"(d[73]), "+f"(d[74]), "+f"(d[75]), "+f"(d[76]), "+f"(d[77]), "+f"(d[78]), "+f"(d[79]), "+f"(d[80]), "+f"(d[81]), "+f"(d[82]), "+f"(d[83]), "+f"(d[84]), "+f"(d[85]), "+f"(d[86]), "+f"(d[87]), "+f"(d[88]), "+f"(d[89]), "+f"(d[90]), "+f"(d[91]), "+f"(d[92]), "+f"(d[93]), "+f"(d[94]), "+f"(d[95]), "+f"(d[96]), "+f"(d[97]), "+f"(d[98]), "+f"(d[99]), "+f"(d[100]), "+f"(d[101]), "+f"(d[102]), "+f"(d[103]), "+f"(d[104]), "+f"(d[105]), "+f"(d[106]), "+f"(d[107]), "+f"(d[108]), "+f"(d[109]), "+f"(d[110]), "+f"(d[111]), "+f"(d[112]), "+f"(d[113]), "+f"(d[114]), "+f"(d[115]), "+f"(d[116]), "+f"(d[117]), "+f"(d[118]), "+f"(d[119]), "+f"(d[120]), "+f"(d[121]), "+f"(d[122]), "+f"(d[123]), "+f"(d[124]), "+f"(d[125]), "+f"(d[126]), "+f"(d[127])
      : "l"(da), "l"(db));
  } else {
    asm volatile("{\n.reg .pred p;\nsetp.ne.b32 p, 0, 0;\n"
      "wgmma.mma_async.sync.aligned.m64n256k16.f32.bf16.bf16 "
      "{%0, %1, %2, %3, %4, %5, %6, %7, %8, %9, %10, %11, %12, %13, %14, %15, %16, %17, %18, %19, %20, %21, %22, %23, %24, %25, %26, %27, %28, %29, %30, %31, %32, %33, %34, %35, %36, %37, %38, %39, %40, %41, %42, %43, %44, %45, %46, %47, %48, %49, %50, %51, %52, %53, %54, %55, %56, %57, %58, %59, %60, %61, %62, %63, %64, %65, %66, %67, %68, %69, %70, %71, %72, %73, %74, %75, %76, %77, %78, %79, %80, %81, %82, %83, %84, %85, %86, %87, %88, %89, %90, %91, %92, %93, %94, %95, %96, %97, %98, %99, %100, %101, %102, %103, %104, %105, %106, %107, %108, %109, %110, %111, %112, %113, %114, %115, %116, %117, %118, %119, %120, %121, %122, %123, %124, %125, %126, %127}, "
      "%128, %129, p, 1, 1, 0, 1;\n}\n"
      : "=f"(d[0]), "=f"(d[1]), "=f"(d[2]), "=f"(d[3]), "=f"(d[4]), "=f"(d[5]), "=f"(d[6]), "=f"(d[7]), "=f"(d[8]), "=f"(d[9]), "=f"(d[10]), "=f"(d[11]), "=f"(d[12]), "=f"(d[13]), "=f"(d[14]), "=f"(d[15]), "=f"(d[16]), "=f"(d[17]), "=f"(d[18]), "=f"(d[19]), "=f"(d[20]), "=f"(d[21]), "=f"(d[22]), "=f"(d[23]), "=f"(d[24]), "=f"(d[25]), "=f"(d[26]), "=f"(d[27]), "=f"(d[28]), "=f"(d[29]), "=f"(d[30]), "=f"(d[31]), "=f"(d[32]), "=f"(d[33]), "=f"(d[34]), "=f"(d[35]), "=f"(d[36]), "=f"(d[37]), "=f"(d[38]), "=f"(d[39]), "=f"(d[40]), "=f"(d[41]), "=f"(d[42]), "=f"(d[43]), "=f"(d[44]), "=f"(d[45]), "=f"(d[46]), "=f"(d[47]), "=f"(d[48]), "=f"(d[49]), "=f"(d[50]), "=f"(d[51]), "=f"(d[52]), "=f"(d[53]), "=f"(d[54]), "=f"(d[55]), "=f"(d[56]), "=f"(d[57]), "=f"(d[58]), "=f"(d[59]), "=f"(d[60]), "=f"(d[61]), "=f"(d[62]), "=f"(d[63]), "=f"(d[64]), "=f"(d[65]), "=f"(d[66]), "=f"(d[67]), "=f"(d[68]), "=f"(d[69]), "=f"(d[70]), "=f"(d[71]), "=f"(d[72]), "=f"(d[73]), "=f"(d[74]), "=f"(d[75]), "=f"(d[76]), "=f"(d[77]), "=f"(d[78]), "=f"(d[79]), "=f"(d[80]), "=f"(d[81]), "=f"(d[82]), "=f"(d[83]), "=f"(d[84]), "=f"(d[85]), "=f"(d[86]), "=f"(d[87]), "=f"(d[88]), "=f"(d[89]), "=f"(d[90]), "=f"(d[91]), "=f"(d[92]), "=f"(d[93]), "=f"(d[94]), "=f"(d[95]), "=f"(d[96]), "=f"(d[97]), "=f"(d[98]), "=f"(d[99]), "=f"(d[100]), "=f"(d[101]), "=f"(d[102]), "=f"(d[103]), "=f"(d[104]), "=f"(d[105]), "=f"(d[106]), "=f"(d[107]), "=f"(d[108]), "=f"(d[109]), "=f"(d[110]), "=f"(d[111]), "=f"(d[112]), "=f"(d[113]), "=f"(d[114]), "=f"(d[115]), "=f"(d[116]), "=f"(d[117]), "=f"(d[118]), "=f"(d[119]), "=f"(d[120]), "=f"(d[121]), "=f"(d[122]), "=f"(d[123]), "=f"(d[124]), "=f"(d[125]), "=f"(d[126]), "=f"(d[127])
      : "l"(da), "l"(db));
  }
}
__device__ __forceinline__ void wgmma_n256_ssp_ta0_tb1(float* d, uint64_t da, uint64_t db, int accumulate) {
    asm volatile("{\n.reg .pred p;\nsetp.ne.b32 p, %130, 0;\n"
      "wgmma.mma_async.sync.aligned.m64n256k16.f32.bf16.bf16 "
      "{%0, %1, %2, %3, %4, %5, %6, %7, %8, %9, %10, %11, %12, %13, %14, %15, %16, %17, %18, %19, %20, %21, %22, %23, %24, %25, %26, %27, %28, %29, %30, %31, %32, %33, %34, %35, %36, %37, %38, %39, %40, %41, %42, %43, %44, %45, %46, %47, %48, %49, %50, %51, %52, %53, %54, %55, %56, %57, %58, %59, %60, %61, %62, %63, %64, %65, %66, %67, %68, %69, %70, %71, %72, %73, %74, %75, %76, %77, %78, %79, %80, %81, %82, %83, %84, %85, %86, %87, %88, %89, %90, %91, %92, %93, %94, %95, %96, %97, %98, %99, %100, %101, %102, %103, %104, %105, %106, %107, %108, %109, %110, %111, %112, %113, %114, %115, %116, %117, %118, %119, %120, %121, %122, %123, %124, %125, %126, %127}, "
      "%128, %129, p, 1, 1, 0, 1;\n}\n"
      : "+f"(d[0]), "+f"(d[1]), "+f"(d[2]), "+f"(d[3]), "+f"(d[4]), "+f"(d[5]), "+f"(d[6]), "+f"(d[7]), "+f"(d[8]), "+f"(d[9]), "+f"(d[10]), "+f"(d[11]), "+f"(d[12]), "+f"(d[13]), "+f"(d[14]), "+f"(d[15]), "+f"(d[16]), "+f"(d[17]), "+f"(d[18]), "+f"(d[19]), "+f"(d[20]), "+f"(d[21]), "+f"(d[22]), "+f"(d[23]), "+f"(d[24]), "+f"(d[25]), "+f"(d[26]), "+f"(d[27]), "+f"(d[28]), "+f"(d[29]), "+f"(d[30]), "+f"(d[31]), "+f"(d[32]), "+f"(d[33]), "+f"(d[34]), "+f"(d[35]), "+f"(d[36]), "+f"(d[37]), "+f"(d[38]), "+f"(d[39]), "+f"(d[40]), "+f"(d[41]), "+f"(d[42]), "+f"(d[43]), "+f"(d[44]), "+f"(d[45]), "+f"(d[46]), "+f"(d[47]), "+f"(d[48]), "+f"(d[49]), "+f"(d[50]), "+f"(d[51]), "+f"(d[52]), "+f"(d[53]), "+f"(d[54]), "+f"(d[55]), "+f"(d[56]), "+f"(d[57]), "+f"(d[58]), "+f"(d[59]), "+f"(d[60]), "+f"(d[61]), "+f"(d[62]), "+f"(d[63]), "+f"(d[64]), "+f"(d[65]), "+f"(d[66]), "+f"(d[67]), "+f"(d[68]), "+f"(d[69]), "+f"(d[70]), "+f"(d[71]), "+f"(d[72]), "+f"(d[73]), "+f"(d[74]), "+f"(d[75]), "+f"(d[76]), "+f"(d[77]), "+f"(d[78]), "+f"(d[79]), "+f"(d[80]), "+f"(d[81]), "+f"(d[82]), "+f"(d[83]), "+f"(d[84]), "+f"(d[85]), "+f"(d[86]), "+f"(d[87]), "+f"(d[88]), "+f"(d[89]), "+f"(d[90]), "+f"(d[91]), "+f"(d[92]), "+f"(d[93]), "+f"(d[94]), "+f"(d[95]), "+f"(d[96]), "+f"(d[97]), "+f"(d[98]), "+f"(d[99]), "+f"(d[100]), "+f"(d[101]), "+f"(d[102]), "+f"(d[103]), "+f"(d[104]), "+f"(d[105]), "+f"(d[106]), "+f"(d[107]), "+f"(d[108]), "+f"(d[109]), "+f"(d[110]), "+f"(d[111]), "+f"(d[112]), "+f"(d[113]), "+f"(d[114]), "+f"(d[115]), "+f"(d[116]), "+f"(d[117]), "+f"(d[118]), "+f"(d[119]), "+f"(d[120]), "+f"(d[121]), "+f"(d[122]), "+f"(d[123]), "+f"(d[124]), "+f"(d[125]), "+f"(d[126]), "+f"(d[127])
      : "l"(da), "l"(db), "r"(accumulate));
}

template <int N> __device__ __forceinline__ void quad_sum(float* m) {
#pragma unroll
  for (int o = 1; o <= 2; o <<= 1) {
    float t[N];
#pragma unroll
    for (int i = 0; i < N; i++) t[i] = __shfl_xor_sync(~0u, m[i], o);
#pragma unroll
    for (int i = 0; i < N; i++) m[i] += t[i];
  }
}
__device__ __forceinline__ bool softmax_unsafe(const uint32_t* t, float l0, float l1) {
  const float m0 = fmaxf(bf_lo(t[0]) + bf_hi(t[0]), bf_lo(t[2]) + bf_hi(t[2])), m1 = fmaxf(bf_lo(t[1]) + bf_hi(t[1]), bf_lo(t[3]) + bf_hi(t[3]));
  return __any_sync(~0u, !(m0 * l0 < 2500.f) | !(m1 * l1 < 2500.f));
}
__device__ __forceinline__ void softmax_shift(float* p, float c0, float c1) {
#pragma unroll 1
  for (int it = 0; it < 8; it++) {
    float mx = p[0], mn = p[0];
#pragma unroll
    for (int j = 1; j < 8; j++) { mx = fmaxf(mx, p[(j >> 1) * 4 + (j & 1)]); mn = fminf(mn, p[(j >> 1) * 4 + (j & 1)]); }
#pragma unroll
    for (int o = 1; o <= 2; o <<= 1) { mx = fmaxf(mx, __shfl_xor_sync(~0u, mx, o)); mn = fminf(mn, __shfl_xor_sync(~0u, mn, o)); }
    const float half = fminf(0.5f * (mx - mn), 50.f * rcp(it & 1 ? c1 : c0));
    float r[8];
#pragma unroll
    for (int j = 0; j < 8; j++) {
      const float v = p[(j >> 1) * 4 + (j & 1)];
      r[j] = fmaxf(v - mx + half, 0.f) + fminf(v - mn - half, 0.f) + (v - v);
    }
#pragma unroll
    for (int k = 0; k < 7; k++)
#pragma unroll
      for (int j = 0; j < 8; j++) p[(k >> 1) * 16 + (k & 1) * 2 + (j >> 1) * 4 + (j & 1)] = p[((k + 1) >> 1) * 16 + ((k + 1) & 1) * 2 + (j >> 1) * 4 + (j & 1)];
#pragma unroll
    for (int j = 0; j < 8; j++) p[50 + (j >> 1) * 4 + (j & 1)] = r[j];
  }
}
template <int J0 = 0, int J1 = 8> __device__ __forceinline__ void k_exp(const float* p, float c0, float c1, float* e, float* s) {
#pragma unroll
  for (int j = J0; j < J1; j++) {
    e[2 * j] = ex2(p[2 * j] * (j & 1 ? c1 : c0));
    e[2 * j + 1] = ex2(p[2 * j + 1] * (j & 1 ? c1 : c0));
    e[16 + j] = rcp(e[2 * j] * e[2 * j + 1]);
    const float t = e[2 * j] + e[2 * j + 1];
    s[j & 1] = j < 2 ? t : s[j & 1] + t;
    s[2 + (j & 1)] = j < 2 ? e[16 + j] * t : fmaf(e[16 + j], t, s[2 + (j & 1)]);
  }
}
template <int J0 = 0, int J1 = 8> __device__ __forceinline__ void q_exp(const float* p, float c0, float c1, uint32_t* f) {
#pragma unroll
  for (int j = J0; j < J1; j++) {
    const float e0 = ex2(p[2 * j] * (j & 1 ? c1 : c0)), e1 = ex2(p[2 * j + 1] * (j & 1 ? c1 : c0)), r = rcp(e0 * e1);
    f[j] = pack2(e0, e1);
    f[8 + j] = bmul2(f[j], pack2(r, r));
  }
}

#define FMA8(A, U, X)                                                                                        \
  A[0] = fmaf(bf_lo(U.x), X, A[0]); A[1] = fmaf(bf_hi(U.x), X, A[1]); A[2] = fmaf(bf_lo(U.y), X, A[2]); A[3] = fmaf(bf_hi(U.y), X, A[3]); \
  A[4] = fmaf(bf_lo(U.z), X, A[4]); A[5] = fmaf(bf_hi(U.z), X, A[5]); A[6] = fmaf(bf_lo(U.w), X, A[6]); A[7] = fmaf(bf_hi(U.w), X, A[7])

__device__ __forceinline__ uint32_t routed_row(const __nv_bfloat16* x, uint32_t tag, int lane, uint4* xr) {
  uint32_t best = 0, sv = 0;
#pragma unroll 1
  for (int it = 0; it < SPIN_MAX; it++) {
    const uint4 h = ld_rlx128(g_ycnt + 32);
    best = h.x;
    if (__all_sync(~0u, (int)(h.z - tag * NCTA) >= 0)) break;
    __nanosleep(AM_NS);
  }
#pragma unroll 1
  for (int it = 0; it < SPIN_MAX; it++) {
    const int sel = 2047 - (best & 0x7ff);
#pragma unroll
    for (int i = 0; i < 4; i++) xr[i] = ldg_nc(x + (size_t)sel * DM + i * 256 + lane * 8);
    const unsigned long long st = ld_rlx64(g_stat + sel);
    const uint4 b0 = ld_rlx128(g_best + lane * 2), b1 = ld_rlx128(g_best + 64 + lane * 2);
    const uint32_t m = __reduce_max_sync(~0u, max(max(b0.x, b0.z), max(b1.x, b1.z)));
    sv = (uint32_t)st;
    if (__all_sync(~0u, b0.y == tag && b0.w == tag && b1.y == tag && b1.w == tag && m == best && (uint32_t)(st >> 32) == tag)) break;
    best = m;
  }
  const uint32_t m2 = (sv & 0xffff0000u) | (sv >> 16);
  const float rs = rcp(bf_lo(sv));
#pragma unroll
  for (int i = 0; i < 4; i++) {
    const uint32_t d0 = bsub2(xr[i].x, m2), d1 = bsub2(xr[i].y, m2), d2 = bsub2(xr[i].z, m2), d3 = bsub2(xr[i].w, m2);
    xr[i] = make_uint4(pack2(bf_lo(d0) * rs, bf_hi(d0) * rs), pack2(bf_lo(d1) * rs, bf_hi(d1) * rs), pack2(bf_lo(d2) * rs, bf_hi(d2) * rs),
                       pack2(bf_lo(d3) * rs, bf_hi(d3) * rs));
  }
  return best;
}

struct Params {
  const __nv_bfloat16 *x, *wqkv, *wo, *w_r, *w_gate, *w_up, *w_down;
  int by_sm;
};

__global__ void __launch_bounds__(384, 1)
fused_kernel(const __grid_constant__ CUtensorMap mX, const __grid_constant__ CUtensorMap mWkv, const __grid_constant__ CUtensorMap mWq,
             const __grid_constant__ CUtensorMap mWo, const __grid_constant__ CUtensorMap mPhi, const __grid_constant__ CUtensorMap mWp,
             const __grid_constant__ CUtensorMap mOut, const __grid_constant__ CUtensorMap mWc,
             const __grid_constant__ CUtensorMap mG, const __grid_constant__ CUtensorMap mU, const __grid_constant__ CUtensorMap mD,
             const __grid_constant__ CUtensorMap mXs, const __grid_constant__ CUtensorMap mG2, const __grid_constant__ CUtensorMap mU2, const Params P) {
  extern __shared__ __align__(1024) uint8_t smem[];
  if (smem_u32(smem) != SB) return;
  constexpr uint32_t sb = SB, bar = SB + SM_BAR;
  int bid = blockIdx.x;
  if (P.by_sm) {
    uint32_t sm;
    asm volatile("mov.u32 %0, %%smid;" : "=r"(sm));
    const uint32_t tq = (sm - 64) >> 1, q7 = (tq * 37) >> 8;
    const uint32_t gpc = sm < 64 ? (sm >> 1) & 7 : 1 + tq - 7 * q7, idx = (sm < 64 ? sm >> 4 : 4 + q7) * 2 + (sm & 1);
    bid = sm < 120 ? ((PTAB >> (4 * gpc)) & 7) * 16 + idx : sm < 124 ? sm + 8 : sm - 116;
  }
  const int hg = ((bid >> 2) & 3) + 4 * ((bid >> 4) & 1), mb = (bid & 3) + 4 * ((bid >> 5) & 3);
  const int warp = __shfl_sync(~0u, threadIdx.x >> 5, 0);

  if (bid >= NCTA) {
    constexpr uint32_t XV = SM_WPHI, ONES = SM_ZT, BF = bar, BE = bar + 48, BX = bar + 96;
    constexpr int NJ = (DM - GROWS) / 64;
    const int lane = lane_id(), sp = bid - NCTA;
    const uint32_t tag = ld_rlx(g_epoch + bid * 32 + lane) + 1;
    if (warp == 8 && elect_one()) {
#pragma unroll 1
      for (int i = 0; i < 13; i++) mbar_init(bar + 8 * i, i >= 6 && i < 12 ? 8 : 1);
    }
    if (warp == 9) { sts64u(sb + ONES + lane * 8, 0x3f803f80u, 0x3f803f80u); fence_async_smem(); }
    __syncthreads();
    if (warp == 8) {
      if (elect_one()) {
        uint32_t s = 0, ph = 1;
#pragma unroll 1
        for (int job = 0; job < 8; job++) {
          const CUtensorMap* m = job == 0 ? &mWq : sp & 2 ? &mU2 : &mG2;
          const int g0 = job ? (sp & 1) * 28 + job * 4 - 4 : sp * 4;
#pragma unroll 1
          for (int row = job ? GROWS : 0; row < DM; row += 64) {
            mbar_wait(BE + 8 * s, ph);
            mbar_expect_tx(BF + 8 * s, Q_STAGE);
            tma4d(sb + s * Q_STAGE, m, 0, row, g0, 0, BF + 8 * s);
            tma4d(sb + s * Q_STAGE + 16384, m, 0, row, g0 + 2, 0, BF + 8 * s);
            if (++s == 6) { s = 0; ph ^= 1; }
          }
        }
      }
    } else if (warp == 9) {
      uint4 xr[4];
      routed_row(P.x, tag, lane, xr);
#pragma unroll
      for (int i = 0; i < 4; i++) sts128u(sb + XV + i * 512 + lane * 16, xr[i].x, xr[i].y, xr[i].z, xr[i].w);
      fence_async_smem();
      __syncwarp();
      if (lane == 0) mbar_arrive(BX);
    } else if (warp < 8) {
      uint32_t s = 0, ph = 0;
#pragma unroll 1
      for (int job = 0; job < 8; job++) {
        float d[8] = {0.f, 0.f, 0.f, 0.f, 0.f, 0.f, 0.f, 0.f};
        if (job == 1) mbar_wait(BX, 0);
#pragma unroll 1
        for (int i = 0; i < (job ? NJ : 16); i++) {
          mbar_wait(BF + 8 * s, ph);
          wg_fence();
#pragma unroll
          for (int k = 0; k < 8; k++)
            wgmma_n8_ss_ta1_tb0(d + 4 * (k >> 2), mkdesc(sb + k * 2048, 16, 1024, 1, s * (Q_STAGE / 16) + (warp >> 2) * 1024),
                                mkdesc(sb, 16, 128, 0, job ? (XV + GROWS * 2) / 16 + i * 8 + (k & 3) * 2 : ONES / 16), 1);
          wg_commit();
          wg_wait<0>();
          if (lane == 0) mbar_arrive(BE + 8 * s);
          if (++s == 6) { s = 0; ph ^= 1; }
        }
        reg_fence<8>(d);
        float* dst = (job ? g_gp + sp * 1792 + job * 256 - 256 : g_cs + sp * 256) + (warp >> 2) * 128 + (warp & 3) * 16 + (lane >> 2);
        if ((lane & 3) == 0) {
#pragma unroll
          for (int i = 0; i < 4; i++) st_rlx(dst + (i >> 1) * 64 + (i & 1) * 8, mark(__float_as_uint(d[2 * i]), tag & 1));
        }
        __syncwarp();
      }
      if (warp == 0) g_epoch[bid * 32 + lane] = tag;
    }
    return;
  }
#define Q_SLAB(J) ((J) < 8 ? ((J) + 8 - 2 * (hg & 4)) & 15 : 2 * (hg & 4) + 2 * ((J) & 3) + ((J) >> 2 & 1))
#define Q_AOFF(J) ((J) == 8 + (hg & 3) ? SM_X0 : (J) == 12 + (hg & 3) ? SM_X1 : ((J) & 3) * Q_STAGE)
#define Q_LOAD(J)                                                                                            \
  do {                                                                                                       \
    const uint32_t fb_ = bar + B_FULLQ + 8 * ((J) & 3);                                                      \
    const int k_ = Q_SLAB(J) * 64;                                                                           \
    mbar_expect_tx(fb_, Q_STAGE);                                                                            \
    mbar_arrive2(fb_);                                                                                       \
    tma2d(sb + Q_AOFF(J), &mX, k_, mb * 128, fb_);                                                           \
    tma4d(sb + ((J) & 3) * Q_STAGE + 16384, &mWq, 0, k_, hg * 2, 0, fb_);                                    \
  } while (0)
  if (warp >= 8) {
    asm volatile("setmaxnreg.dec.sync.aligned.u32 %0;" ::"n"(REG_H));
    const int lane = lane_id();
    const int f = (warp - 9) & 3;
    const uint32_t ep = ld_rlx(g_epoch + bid * 32 + lane);
    if (f == 3) {
      if (elect_one()) {
        PROF(0); PROFT(32);
#pragma unroll
        for (int j = 0; j < 3; j++) {
          const int s = (j + 2) % 3;
          mbar_init(bar + B_FULLKV + 8 * s, 1);
          mbar_expect_tx(bar + B_FULLKV + 8 * s, KV_STAGE);
          tma2d(sb + s * KV_STAGE, &mX, j * 64, mb * 128, bar + B_FULLKV + 8 * s);
          tma4d(sb + s * KV_STAGE + 16384, &mWkv, 0, j * 64, hg * 2, 1, bar + B_FULLKV + 8 * s);
        }
      }
    } else if (f < 2) {
#pragma unroll
      for (int i = 0; i < 2; i++) {
        const uint4 u = __ldg((const uint4*)P.w_r + (f * 2 + i) * 32 + lane);
        sts128u(sb + SM_XSEL + (f * 2 + i) * 512 + lane * 16, u.x, u.y, u.z, u.w);
      }
    }
    __syncwarp();
    bar_sync(0, 384);
    const uint32_t tag = ep + 1, par = tag & 1;
    const bool ffn = bid < NFFN;
    const int fb = bid, cu = bid >> 1, ch = bid & 1;
#define CS_STORE(SEC, C)                                                                                     \
  _Pragma("unroll") for (int r = 0; r < 3; r++) {                                                            \
    const uint32_t h0 = pack2(C.x, C.y), h1 = pack2(C.z, C.w);                                               \
    sts64u(sb + SM_CST + (SEC) * 1024 + (lane >> 4) * 512 + (lane & 1) * 8 + r * 128 + ((((lane & 15) >> 1) ^ (r + (lane >> 4) * 4)) << 4), h0, h1); \
    C.x -= bf_lo(h0); C.y -= bf_hi(h0); C.z -= bf_lo(h1); C.w -= bf_hi(h1);                                  \
  }
#define BAD4(U) ((U.x ^ par) | (U.y ^ par) | (U.z ^ par) | (U.w ^ par))
    const int n0 = f < 2 ? 0 : 2 * f - 3, ne = FFN_OFF || !ffn ? 3 : f == 3 ? 3 + G8 : 3 + GN;
    const uint32_t fsb = sb + SM_FST + ((f + 1) & 3) * 8192, fbar = bar + B_FST + f * 16, fst = fsb + (lane >> 4) * 2048 + (lane & 15) * 16;
    const CUtensorMap *ma = &mWc, *mc = &mWc;
    int sx = 1024 + cu * 32, sy = ch * 512 + f * 192, sdy = 32;
#define STAGEG(N)                                                                                            \
  do {                                                                                                       \
    if ((N) == 3) { ma = &mG; mc = &mU; sx = fb * 32; sy = f * (GN * 32);  sdy = 0; }                        \
    if ((N) < ne && elect_one()) {                                                                           \
      const uint32_t dst_ = fsb + ((N) & 1) * 4096, b_ = fbar + ((N) & 1) * 8;                               \
      mbar_expect_tx(b_, 4096);                                                                              \
      tma2d(dst_, ma, sx, sy, b_);                                                                           \
      tma2d(dst_ + 2048, mc, sx, sy + sdy, b_);                                                              \
    }                                                                                                        \
    sy += 32 + sdy;                                                                                          \
  } while (0)
    float a[8], gsum = 0.f, usum = 0.f;
    {
      if (f == 3) {
        if (elect_one()) {
          if (XS_EARLY) { mbar_expect_tx(bar + B_XST, 16384); tma3d(sb + SM_XST, &mXs, 0, bid * 16, 0, bar + B_XST); }
          mbar_expect_tx(bar + B_WPHI, 8192);
          tma2d(sb + SM_WPHI, &mPhi, 0, hg * 128, bar + B_WPHI);
          prefetch_map(&mWq); prefetch_map(&mWo); prefetch_map(&mWp); prefetch_map(&mD);
          PROF(31);
        }
        __syncwarp();
      } else {
        if (lane == 0) prefetch_map(f == 0 ? &mWc : f == 1 ? &mG : &mU);
        if (f == 2) ((float2*)g_y[par])[bid * 32 + lane] = make_float2(0.f, 0.f);
      }
      float st[13];
#pragma unroll
      for (int i = 0; i < 13; i++) st[i] = 0.f;
#pragma unroll 1
      for (int i = 0; i < 4; i++) {
        mbar_wait(bar + B_XST + 8 * (i >> 1), 0);
        if (f == 0 && lane == 0 && i == 0) PROF(1);
        const uint4 wu = lds128u(sb + SM_XSEL + i * 512 + lane * 16);
        const float wf[8] = {bf_lo(wu.x), bf_hi(wu.x), bf_lo(wu.y), bf_hi(wu.y), bf_lo(wu.z), bf_hi(wu.z), bf_lo(wu.w), bf_hi(wu.w)};
        st[12] += ((wf[0] + wf[1]) + (wf[2] + wf[3])) + ((wf[4] + wf[5]) + (wf[6] + wf[7]));
#pragma unroll
        for (int r = 0; r < 4; r++) {
          const uint4 u = lds128u(sb + SM_XST + i * 8192 + (4 * f + r) * 512 + lane * 16);
          const float xf[8] = {bf_lo(u.x), bf_hi(u.x), bf_lo(u.y), bf_hi(u.y), bf_lo(u.z), bf_hi(u.z), bf_lo(u.w), bf_hi(u.w)};
#pragma unroll
          for (int k = 0; k < 8; k++) { st[r] += xf[k]; st[4 + r] = fmaf(xf[k], xf[k], st[4 + r]); st[8 + r] = fmaf(xf[k], wf[k], st[8 + r]); }
        }
        if (i >= 2 && f < 3) STAGEG(n0 + i - 2);
      }
      const bool up = lane & 16, up2 = lane & 8;
#pragma unroll
      for (int q = 0; q < 3; q++) {
        const float k0 = up ? st[4 * q + 2] : st[4 * q], k1 = up ? st[4 * q + 3] : st[4 * q + 1];
        const float o0 = up ? st[4 * q] : st[4 * q + 2], o1 = up ? st[4 * q + 1] : st[4 * q + 3];
        const float m0 = k0 + __shfl_xor_sync(~0u, o0, 16), m1 = k1 + __shfl_xor_sync(~0u, o1, 16);
        a[q] = (up2 ? m1 : m0) + __shfl_xor_sync(~0u, up2 ? m0 : m1, 8);
      }
      a[3] = st[12] + __shfl_xor_sync(~0u, st[12], 16);
      a[3] += __shfl_xor_sync(~0u, a[3], 8);
#pragma unroll
      for (int o = 4; o; o >>= 1)
#pragma unroll
        for (int q = 0; q < 4; q++) a[q] += __shfl_xor_sync(~0u, a[q], o);
      if ((lane & 7) == 0) sts128(sb + SM_ROWS + (4 * f + (lane >> 3)) * 16, a[0], a[1], a[2], a[3]);
      if (f < 3) asm volatile("bar.arrive 7, 128;" ::: "memory");
    }
    if (f == 3) {
      bar_sync(7, 128);
      const int row = bid * 16 + (lane & 15);
      const float4 v = lds128(sb + SM_ROWS + (lane & 15) * 16);
      const float mf = v.x * (1.f / DM), mean = bf_round(mf), var = fmaxf(fmaf(-mf, mf, v.y * (1.f / DM)), 0.f);
      const float sd = bf_round(sqrt_approx(bf_round(bf_round(var) + 1e-5f)));
      const uint32_t rb = pack2(fmaf(-mean, v.w, v.z) * rcp(sd), 0.f) & 0xffffu, ord = (rb & 0x8000u) ? (~rb & 0xffffu) : (rb | 0x8000u);
      uint32_t best = __reduce_max_sync(~0u, (ord << 16) | (uint32_t)(2047 - row));
      if (lane < 16) st_rlx64(g_stat + row, ((unsigned long long)tag << 32) | __float_as_uint(mean) | (__float_as_uint(sd) >> 16));
      if (lane < 2) asm volatile("red.relaxed.gpu.global.max.u64 [%0], %1;" ::"l"(lane ? (void*)(g_ycnt + 32) : (void*)(g_best + bid)), "l"(((unsigned long long)tag << 32) | best) : "memory");
      if (lane == 1) { red_inc(g_ycnt + 34); PROF(17); }
#pragma unroll 1
      for (int n = 3; n < 5; n++) STAGEG(n);
      {
        uint4 xr[4];
        best = routed_row(P.x, tag, lane, xr);
#pragma unroll
        for (int i = 0; i < (GROWS + 255) / 256; i++) {
          const uint32_t dst = sb + SM_XSEL + i * 1024 + (lane >> 2) * 128 + (lane & 3) * 8;
          sts64(dst, bf_lo(xr[i].x), bf_lo(xr[i].z)); sts64(dst + 32, bf_hi(xr[i].x), bf_hi(xr[i].z));
          sts64(dst + 64, bf_lo(xr[i].y), bf_lo(xr[i].w)); sts64(dst + 96, bf_hi(xr[i].y), bf_hi(xr[i].w));
        }
        sts64u(sb + SM_RED + 16, tag, best);
        __syncwarp();
        if (lane == 0) { mbar_arrive(bar + B_XS); PROF(19); }
      }
      unsigned long long sv4[4];
      uint4 u[4];
#pragma unroll 1
      for (int it = 0; it < SPIN_MAX; it++) {
#pragma unroll
        for (int i = 0; i < 4; i++) { u[i] = ld_rlx128(g_cs + (1 + i) * 1024 + hg * 128 + lane * 4); sv4[i] = ld_rlx64(g_stat + mb * 128 + i * 32 + lane); }
        bool ok = ((BAD4(u[0]) | BAD4(u[1]) | BAD4(u[2]) | BAD4(u[3])) & 1) == 0;
#pragma unroll
        for (int i = 0; i < 4; i++) ok = ok && (uint32_t)(sv4[i] >> 32) == tag;
        if (__all_sync(~0u, ok)) break;
        __nanosleep(200);
      }
#pragma unroll
      for (int i = 0; i < 4; i++) {
        const uint32_t sv = (uint32_t)sv4[i], sd2 = (sv << 16) | (sv & 0xffffu);
        sts64(sb + SM_STAT + (i * 32 + lane) * 8, -bf_hi(sv), rcp(bf_lo(sv)));
        sts128u(sb + SM_SDT + lane * 64 + ((i ^ ((lane >> 1) & 3)) << 4), sd2, sd2, sd2, sd2);
      }
#pragma unroll
      for (int i = 0; i < 2; i++) {
        float4 c = make_float4(unmark(u[i].x) + unmark(u[i + 2].x), unmark(u[i].y) + unmark(u[i + 2].y), unmark(u[i].z) + unmark(u[i + 2].z),
                               unmark(u[i].w) + unmark(u[i + 2].w));
        CS_STORE(i, c);
      }
      fence_async_smem();
      bar_sync(8, 64);
      if (lane == 0) { mbar_arrive(bar + B_CS); PROF(10); }
    }
    {
      uint32_t xa = sb + SM_RED + 32, xstep = 0;
      const uint32_t zero = __float_as_uint(lds32(sb + SM_RED + 12));
#pragma unroll 1
      for (int ph = f == 3; ph < 2; ph++) {
#pragma unroll
        for (int j = 0; j < 8; j++) a[j] = 0.f;
        if (ph && f == 0) {
        {
          mbar_wait(bar + B_WPHI, 0);
          float nq[8] = {0.f, 0.f, 0.f, 0.f, 0.f, 0.f, 0.f, 0.f};
  #pragma unroll 2
          for (int r = 0; r < 16; r++) {
            const uint4 u = lds128u(sb + SM_WPHI + ((lane >> 2) * 16 + r) * 64 + (((lane ^ (r >> 1)) & 3) << 4));
            nq[0] = fmaf(bf_lo(u.x), bf_lo(u.x), nq[0]); nq[1] = fmaf(bf_hi(u.x), bf_hi(u.x), nq[1]); nq[2] = fmaf(bf_lo(u.y), bf_lo(u.y), nq[2]);
            nq[3] = fmaf(bf_hi(u.y), bf_hi(u.y), nq[3]); nq[4] = fmaf(bf_lo(u.z), bf_lo(u.z), nq[4]); nq[5] = fmaf(bf_hi(u.z), bf_hi(u.z), nq[5]);
            nq[6] = fmaf(bf_lo(u.w), bf_lo(u.w), nq[6]); nq[7] = fmaf(bf_hi(u.w), bf_hi(u.w), nq[7]);
          }
          uint32_t m = 0;
  #pragma unroll
          for (int i = 0; i < 8; i++) m = max(m, __float_as_uint(nq[i] + __shfl_xor_sync(~0u, nq[i], 4)) & 0x7fffffffu);
          sts32(sb + SM_RED + 24, 4.2f * __uint_as_float(__reduce_max_sync(~0u, m)));
        }
          asm volatile("bar.arrive 8, 64;" ::: "memory");
        }
        if (ph) { mbar_wait(bar + B_XS, 0); xa = sb + SM_XSEL + f * (GN * 128) + ((lane >> 2) & 3) * 32; xstep = 128; }
#pragma unroll 1
        for (int n = ph ? 3 : n0; n < (ph ? ne : 3); n++) {
          const float4 x0 = lds128(xa), x1 = lds128(xa + 16);
          xa += xstep;
          mbar_wait(fbar + (n & 1) * 8, ((n - n0) >> 1) & 1);
          uint4 u[8];
#pragma unroll
          for (int j = 0; j < 8; j++) u[j] = lds128u(fst + (n & 1) * 4096 + j * 256);
          FMA8(a, u[0], x0.x); FMA8(a, u[1], x0.y); FMA8(a, u[2], x0.z); FMA8(a, u[3], x0.w);
          if (__any_sync(~0u, ((u[4].x | u[5].x | u[6].x | u[7].x | __float_as_uint(a[0]) | __float_as_uint(a[7])) & zero) == 0)) STAGEG(n + 2);
          FMA8(a, u[4], x1.x); FMA8(a, u[5], x1.y); FMA8(a, u[6], x1.z); FMA8(a, u[7], x1.w);
        }
#pragma unroll
        for (int o = 4; o <= 8; o <<= 1)
#pragma unroll
          for (int j = 0; j < 8; j++) a[j] += __shfl_xor_sync(~0u, a[j], o);
        if (ph && lane == 0) mbar_arrive(bar + B_FFN);
        const uint32_t red = ph ? sb + SM_GRED : sb + SM_RED + 64;
        if ((lane & 12) == 0) {
          const uint32_t d = red + f * 256 + (lane >> 4) * 128 + (lane & 3) * 32;
          sts128(d, a[0], a[1], a[2], a[3]); sts128(d + 16, a[4], a[5], a[6], a[7]);
        }
        if (f != 2) {
          asm volatile("bar.arrive %0, %1;" ::"r"(4 + ph), "r"(96 + 32 * ph) : "memory");
        } else {
          bar_sync(4 + ph, 96 + 32 * ph);
          const uint32_t ra = red + lane * 4;
          gsum = lds32(ra) + lds32(ra + 256) + lds32(ra + 512);
          usum = lds32(ra + 128) + lds32(ra + 384) + lds32(ra + 640);
          if (!ph) st_rlx(g_cs + 1024 + ch * 2048 + cu * 32 + lane, mark(__float_as_uint(gsum + usum), par));
          else { gsum += lds32(ra + 768); usum += lds32(ra + 896); }
          if (lane == 0) PROF(ph ? 34 : 18);
        }
      }
    }
    if (f == 3) {
      if (elect_one()) {
        PROF(7);
        mbar_wait(bar + B_FULLQ, 0);
#pragma unroll 1
        for (int j = 3; j < 16; j++) {
          mbar_wait(bar + (j < 4 ? B_EMPTYKV + 16 : B_EMPTYQ + 8 * (j & 3)), ((j >> 2) & 1) ^ 1);
          if (j == 12 + (hg & 3)) mbar_wait(bar + B_KVST + 8, 0);
          Q_LOAD(j);
        }
        PROF(47);
        mbar_expect_tx(bar + B_DN, 65536);
#pragma unroll 1
        for (int i = 0; i < 4; i++) {
          mbar_wait(bar + B_EMPTYQ + 8 * i, 1);
          tma3d(sb + i * Q_STAGE, &mD, 0, fb * 32, i * 4, bar + B_DN);
        }
        PROF(48);
#pragma unroll 1
        for (int i = 0; i < 16; i++) {
          const int s = i & 3, n = i < 9 ? i - 2 : i - 9, kb = i < 2 ? 2 * hg + i : 2 * (n + (n >= hg)) + (i >= 9);
          if (i >= 4) mbar_wait(bar + B_EMPTYQ + 8 * s, ((i >> 2) & 1) ^ 1);
          mbar_expect_tx(bar + B_FULLQ + 8 * s, 16384);
          if (i < 2) {
            mbar_arrive2(bar + B_FULLQ + 8 * s);
            tma3d(sb + s * Q_STAGE + 16384, &mWo, 0, kb * 64, hg * 2, bar + B_FULLQ + 8 * s);
          } else {
            tma5d(sb + s * Q_STAGE + 16384, &mWp, hg * 128, kb * 2, bar + B_FULLQ + 8 * s);
            tma5d(sb + s * Q_STAGE + 24576, &mWp, hg * 128 + 64, kb * 2, bar + B_FULLQ + 8 * s);
            if (i >= 3) {
              if (i == 3) { mbar_wait(bar + B_DND, 0); PROF(14); }
#pragma unroll 1
              for (int a = i == 3 ? 2 : i; a <= i; a++) {
                const uint4* src = g_ofr + (mb * 16 + (a == 2 ? (hg == 0 ? 2 : 0) : kb)) * 1024;
#pragma unroll
                for (int h = 0; h < 2; h++) {
                  mbar_expect_tx(bar + B_AIN + (a & 3) * 16 + h * 8, 8192);
                  bulk_load(sb + (a & 3) * Q_STAGE + h * 8192, src + h * 512, 8192, bar + B_AIN + (a & 3) * 16 + h * 8);
                }
              }
            }
          }
        }
      }
    } else {
      if (f == 2) {
        if (PFD && ffn) {
#pragma unroll 1
          for (int i = 0; i < 16; i++) { touch_l2((const char*)P.w_down + fb * 65536 + i * 4096 + lane * 128, lane); __nanosleep(PFD); }
        }
        if (WOT) {
#pragma unroll 1
          for (int i = 0; i < 8; i++) { touch_l2((const char*)P.wo + ((mb & 7) * 128 + i * 16 + (lane >> 1)) * 2048 + hg * 256 + (lane & 1) * 128, lane); __nanosleep(PFD); }
        }
        asm volatile("cp.async.wait_all;" ::: "memory");
        uint4 u;
#pragma unroll 1
        for (int it = 0; it < SPIN_MAX; it++) {
          u = ld_rlx128(g_cs + hg * 128 + lane * 4);
          if (__all_sync(~0u, !(BAD4(u) & 1))) break;
          __nanosleep(200);
        }
        mbar_wait(bar + B_PHI, 0);
        float4 c = make_float4(unmark(u.x), unmark(u.y), unmark(u.z), unmark(u.w));
        CS_STORE(2, c);
        fence_async_smem();
        __syncwarp();
        if (lane == 0) mbar_arrive(bar + B_CSQ);
        if (ffn && !FFN_OFF) {
#pragma unroll 1
          for (int it = 0; it < SPIN_MAX; it++) {
            const uint32_t pg = ld_rlx((const uint32_t*)g_gp + fb * 32 + lane), pu = ld_rlx((const uint32_t*)g_gp + FF + fb * 32 + lane);
            if (__all_sync(~0u, !(((pg ^ par) | (pu ^ par)) & 1))) { gsum += unmark(pg); usum += unmark(pu); break; }
            __nanosleep(200);
          }
        }
        const float h = bf_round(silu_f(bf_round(gsum))) * bf_round(usum);
        const uint32_t h2 = pack2(h, h);
        sts128u(sb + SM_HT + lane * 16, h2, h2, h2, h2);
        fence_async_smem();
        __syncwarp();
        if (lane == 0) { mbar_arrive(bar + B_H); PROF(20); }
      }
      if (f < 2) {
        const uint32_t own = (hg * 2 + f) * 16 + mb, target = __shfl_sync(~0u, tag, 0) * 16;
        mbar_wait(bar + B_KVST + 8 * f, 0);
        if (f == 1 && lane == 0) PROF(11);
        wait_hint(g_xcnt + hg * 64 + f * 16 + mb, target);
        if (elect_one()) {
          PROF(35 + f);
          fence_async_global();
          mbar_expect_tx(bar + B_PART + 8 * f, 8192);
          bulk_load(sb + (f ? SM_PST1 : SM_PST0), g_part + own * 512, 8192, bar + B_PART + 8 * f);
        }
        __syncwarp();
        {
          uint4 uz;
#pragma unroll 1
          for (int it = 0; it < SPIN_MAX; it++) {
            uz = ld_rlx128(g_zpart + own * 128 + lane * 4);
            if (__all_sync(~0u, !(BAD4(uz) & 1))) break;
          }
          const bool b1 = lane & 2, b2 = lane & 4;
          const float z0 = unmark(b1 ? uz.z : uz.x) + __shfl_xor_sync(~0u, unmark(b1 ? uz.x : uz.z), 2);
          const float z1 = unmark(b1 ? uz.w : uz.y) + __shfl_xor_sync(~0u, unmark(b1 ? uz.y : uz.w), 2);
          float z = (b2 ? z1 : z0) + __shfl_xor_sync(~0u, b2 ? z0 : z1, 4);
          z += __shfl_xor_sync(~0u, z, 8);
          z += __shfl_xor_sync(~0u, z, 16);
          if (lane < 8) st_rlx(g_zres + own * 8 + (lane & 1) * 4 + (lane & 2) + (lane >> 2), mark(__float_as_uint(z), par));
          if (lane == 0) red_inc(g_xcnt + hg * 64 + 32 + f * 16);
          __syncwarp();
        }
        wait_hint(g_xcnt + hg * 64 + 32 + f * 16, 5 * target);
        mbar_wait(bar + B_KVST + 8, 0);
        if (lane == 0) PROF(40 + f);
#pragma unroll 1
        for (int it = 0; it < SPIN_MAX; it++) {
          if (elect_one()) {
            fence_async_global();
            mbar_expect_tx(bar + B_RES + 8 * f, 8192);
            bulk_load(sb + SM_V + f * 8192, g_res[par] + (hg * 4 + f * 2) * 256, 8192, bar + B_RES + 8 * f);
          }
          __syncwarp();
          const uint4 uz = ld_rlx128(g_zres + (hg * 4 + f * 2) * 64 + lane * 4);
          const uint32_t zw[4] = {uz.x, uz.y, uz.z, uz.w};
#pragma unroll
          for (int j = 0; j < 4; j++) {
            const uint32_t zz = pack2(unmark(zw[j]), 1.f), row = (lane & 3) * 4 + j;
            sts128u(sb + SM_ZT + (2 * f + (lane >> 4)) * 1024 + row * 64 + ((((lane >> 2) ^ (row >> 1)) & 3) << 4), zz, zz, zz, zz);
          }
          uint32_t bad = BAD4(uz);
          mbar_wait(bar + B_RES + 8 * f, it & 1);
#pragma unroll
          for (int i = 0; i < 16; i++) bad |= ~__float_as_uint(lds32(sb + SM_V + f * 8192 + i * 512 + lane * 16));
          if (__all_sync(~0u, !(bad & 1))) break;
        }
        fence_async_smem();
        __syncwarp();
        if (lane == 0) { mbar_arrive(bar + B_TILE + 8 * f); PROF(f ? 13 : 27); }
      }
      if (f < 2) {
        uint32_t phases = 0;
#pragma unroll 1
        for (int i = 2; i < 16; i++) {
          const int s = i & 3;
          const uint32_t ab = bar + B_AIN + s * 16 + f * 8, slot = sb + s * Q_STAGE + f * 8192;
#pragma unroll 1
          for (int it = 0; it < SPIN_MAX; it++) {
            mbar_wait(ab, (phases >> s) & 1);
            phases ^= 1u << s;
            uint32_t bad = 0;
#pragma unroll
            for (int n = 0; n < (NOVAL ? 0 : 8); n++) bad |= __float_as_uint(lds32(slot + n * 1024 + lane * 32 + (lane >> 2) * 4)) ^ par;
            if (__all_sync(~0u, !(bad & 1))) break;
            if (elect_one()) {
              const int n = i < 9 ? i - 2 : i - 9, kb = 2 * (n + (n >= hg)) + (i >= 9);
              PROF(49);
              mbar_expect_tx(ab, 8192);
              bulk_load(slot, g_ofr + (mb * 16 + kb) * 1024 + f * 512, 8192, ab);
            }
            __syncwarp();
          }
          if (lane == 0) { mbar_arrive(bar + B_FULLQ + 8 * s); if (i == 2 && f == 0) PROF(15); }
        }
        if (f == 0) g_epoch[bid * 32 + lane] = tag;
      } else {
        if (elect_one()) {
          prefetch_map(&mOut);
          if (ffn) { mbar_wait(bar + B_YD, 0); red_rel(g_ycnt); PROF(21); }
        }
        __syncwarp();
        if (f == 2) {
          const uint32_t best = __float_as_uint(lds32(sb + SM_RED + 20));
          const int sel = 2047 - (best & 0x7ff) - mb * 128;
          if (sel >= 0 && sel < 128) {
            const uint2 xr = __ldg((const uint2*)(P.x + (size_t)(mb * 128 + sel) * DM + hg * 128 + lane * 4));
            const float2 st = lds64(sb + SM_STAT + sel * 8);
            const uint32_t ord = best >> 16, rb = (ord & 0x8000u) ? (ord & 0x7fffu) : (~ord & 0xffffu);
            const float sg = rcp(1.f + ex2(-1.4426950408889634f * bf_lo(rb)));
            const uint32_t sg2 = pack2(sg, sg), nm2 = pack2(st.x, st.x);
            wait_cnt<0>(g_ycnt, tag * NFFN);
            float4 y = make_float4(0.f, 0.f, 0.f, 0.f);
#pragma unroll
            for (int i = 0; i < 8; i++) {
              const float4 c = ldg_cg4(g_y[par ^ 1][i] + hg * 128 + lane * 4);
              y.x += c.x; y.y += c.y; y.z += c.z; y.w += c.w;
            }
            uint32_t o[2];
#pragma unroll
            for (int i = 0; i < 2; i++) {
              const uint32_t d = badd2(i ? xr.y : xr.x, nm2);
              const uint32_t tt = badd2(pack2(bf_lo(d) * st.y, bf_hi(d) * st.y), bmul2(i ? pack2(y.z, y.w) : pack2(y.x, y.y), sg2));
              o[i] = pack2(silu_f(bf_lo(tt)), silu_f(bf_hi(tt)));
            }
            sts64u(sb + SM_UPD + lane * 8, o[0], o[1]);
          }
          if (lane == 0) sts32(sb + SM_UPD + 256, __int_as_float(sel));
          __syncwarp();
          if (lane == 0) { mbar_arrive(bar + B_UPD); PROF(22); }
        }
      }
    }
  } else {
    const int t7 = threadIdx.x & 127;
    const char* pfa = warp < 4 ? (const char*)P.x + bid * 32768 + (t7 & 15) * 2048 + (t7 >> 4) * 128
                               : (const char*)P.wqkv + (size_t)((t7 >> 4) * 64 + (bid >> 1)) * 6144 + 2048 + (bid & 1) * 2048 + (t7 & 15) * 128;
    if (t7 < 16 * PF_FIRST) prefetch_l2(pfa);
    if (warp < 7) sts128(sb + SM_CST + threadIdx.x * 16, 0.f, 0.f, 0.f, 0.f);
    else sts32(sb + SM_RED + (threadIdx.x & 15) * 4, threadIdx.x & 8 ? 1.f : 0.f);
    fence_async_smem();
    if (elect_one()) {
#pragma unroll 1
      for (uint32_t b = B_FST + warp * 8; b < B_END; b += 64)
        mbar_init(bar + b, b < B_FULLQ ? 1 : b < B_FFN ? 3 : b < B_EMPTYKV ? 4 : 8);
    }
    __syncwarp();
    asm volatile("setmaxnreg.inc.sync.aligned.u32 %0;" ::"n"(REG_C));
    if (PF_PRE && t7 >= 16 * PF_FIRST && threadIdx.x < 128 + 16 * PF_W) prefetch_l2(pfa);
    bar_sync(0, 384);
    if (!PF_PRE && t7 >= 16 * PF_FIRST && threadIdx.x < 128 + 16 * PF_W) prefetch_l2(pfa);
    const int lane = lane_id();
    const int wg = warp >> 2, w = warp & 3, g = lane >> 2, t = lane & 3;
    float kv[128];
    {
      uint32_t s = 2, ph = 0, sp = 0, php = 0;
#pragma unroll 1
      for (int j = 0; j < 15; j++) {
        PW0(32 + j); mbar_wait(bar + B_FULLKV + 8 * s, ph); PW1(32 + j);
        if (wg == 1 && (ORDER_ALL || j == 0)) bar_sync(10 + s, 256);
        wg_fence();
        wgmma_n256_ssp_ta0_tb1(kv, mkdesc(sb, 16, 1024, 1, wg * 512 + s * (KV_STAGE / 16)), mkdesc(sb + 16384, 8192, 1024, 1, s * (KV_STAGE / 16)), j);
#pragma unroll
        for (int k = 1; k < 4; k++)
          wgmma_n256_ss_ta0_tb1(kv, mkdesc(sb + k * 32, 16, 1024, 1, wg * 512 + s * (KV_STAGE / 16)),
                                mkdesc(sb + 16384 + k * 2048, 8192, 1024, 1, s * (KV_STAGE / 16)), 1);
        wg_commit();
        if (wg == 0 && (ORDER_ALL || j == 0)) asm volatile("bar.arrive %0, 256;" ::"r"(10 + s) : "memory");
        if (warp == 0 && j) {
          mbar_wait(bar + B_EMPTYKV + 8 * sp, php);
          if (elect_one()) {
            if (j < 14) {
              mbar_expect_tx(bar + B_FULLKV + 8 * sp, KV_STAGE);
              tma2d(sb + sp * KV_STAGE, &mX, (j + 2) * 64, mb * 128, bar + B_FULLKV + 8 * sp);
              tma4d(sb + sp * KV_STAGE + 16384, &mWkv, 0, (j + 2) * 64, hg * 2, 1, bar + B_FULLKV + 8 * sp);
            } else {
              Q_LOAD(0);
            }
            if (j < 3 - XS_EARLY) {
              const int xh = j - 1 + XS_EARLY;
              mbar_expect_tx(bar + B_XST + 8 * xh, 16384);
              tma3d(sb + SM_XST + xh * 16384, &mXs, 0, bid * 16, 2 * xh, bar + B_XST + 8 * xh);
            }
          }
          __syncwarp();
        }
        if (j == 0) {
          if (wg == 0) prefetch_l2(pfa + 1024);
        } else if (wg == 1) {
          if (j < 3) {
            if (j == 2 || t7 >= 16 * PF_W) prefetch_l2(pfa + (j - 1) * (8 * 393216));
          } else if (j == 13) {
            prefetch_l2((const char*)P.wo + bid * 16384 + t7 * 128);
          }
          if (PFG && !FFN_OFF && bid < NFFN && j >= 2 && j < 2 + GROWS / 64 && w < 2)
            touch_l2((const char*)((bid & 1) ? P.w_up : P.w_gate) + (size_t)((0x852a7419630ull >> (4 * j - 8) & 15) * 64 + t7) * 7168 + (bid >> 1) * 128, lane);
        }
        wg_wait<0>();
        if (lane == 0) mbar_arrive(bar + B_EMPTYKV + 8 * s);
        sp = s; php = ph;
        ph ^= s == 1;
        s = s == 2 ? 0 : s + 1;
      }
    }
    const int lrow = wg * 64 + w * 16 + (lane & 15);
    const uint32_t sw128 = lrow * 128, x128 = (lrow & 7), hi16 = lane >> 4;
    mbar_wait(bar + B_CS, 0);
    const uint32_t tag = __float_as_uint(lds32(sb + SM_RED + 16));
    const int zero = __float_as_int(lds32(sb + SM_RED + 12));
    const float wn = lds32(sb + SM_RED + 24);
    const float2 st0 = lds64(sb + SM_STAT + (wg * 64 + w * 16 + g) * 8), st1 = lds64(sb + SM_STAT + (wg * 64 + w * 16 + g + 8) * 8);
    const float c0 = st0.y * 1.4426950408889634f, c1 = st1.y * 1.4426950408889634f;
    const uint32_t nm20 = pack2(st0.x, st0.x), nm21 = pack2(st1.x, st1.x), fmask = t == 0 ? ~0u : t == 1 ? 0xffffu : 0u;
    const uint32_t fa0 = nm20 & fmask, fa1 = nm21 & fmask;
    asm volatile("cp.async.wait_all;" ::: "memory");
    PW0(47); mbar_wait(bar + B_FULLKV + 16, 1); PW1(47);
    wg_fence();
    wgmma_n256_rs_ta0_tb1(kv, fa0, fa1, 0u, 0u, mkdesc(sb + SM_CST, 512, 0, 1), 1);
#pragma unroll
    for (int k = 0; k < 4; k++)
      wgmma_n256_ss_ta0_tb1(kv, mkdesc(sb + 2 * KV_STAGE + k * 32, 16, 1024, 1, wg * 512), mkdesc(sb + 2 * KV_STAGE + 16384 + k * 2048, 8192, 1024, 1), 1);
    wg_commit();
    if (warp == 0) {
      mbar_wait(bar + B_EMPTYKV + 8, 0);
      if (elect_one()) {
#pragma unroll 1
        for (int j = 1; j < 3; j++) Q_LOAD(j);
      }
      __syncwarp();
    }
    wg_wait<0>();
    reg_fence<128>(kv);
    if (lane == 0) mbar_arrive(bar + B_EMPTYKV + 16);
    PROFC(2);
    float q[64];
#define QMMA(J, AOFF16, ACCUM)                                                                                     \
  _Pragma("unroll") for (int k = 0; k < 4; k++)                                                                    \
      wgmma_n128_ss_ta0_tb1(q, mkdesc(sb + k * 32, 16, 1024, 1, wg * 512 + (AOFF16)),                              \
                            mkdesc(sb + 16384 + k * 2048, 8192, 1024, 1, ((J) & 3) * (Q_STAGE / 16)), k ? 1 : (ACCUM))
#define QWAIT(J) do { PW0(J); mbar_wait(bar + B_FULLQ + 8 * ((J) & 3), ((J) >> 2) & 1); PW1(J); } while (0)
#define QSTEP_A(J, AOFF16, ACCUM) do { QWAIT(J); wg_fence(); QMMA(J, AOFF16, ACCUM); wg_commit(); } while (0)
#define QREL(J) do { if (lane == 0) mbar_arrive(bar + B_EMPTYQ + 8 * ((J) & 3)); } while (0)
#define Q_OFF16(J) ((J) >= 8 && (J) < 16 ? Q_AOFF(J) / 16 : ((J) & 3) * (Q_STAGE / 16))
#define QPLAIN(J) do { QSTEP_A(J, Q_OFF16(J), 1); wg_wait<1>(); QREL((J) - 1); } while (0)
#define QNEXT(J) do { QPLAIN(J); SCHED_FENCE(); } while (0)
#define PHI_PROJ(DST, SRC, H0, H1)                                                                                 \
  do {                                                                                                             \
    uint32_t a_[32];                                                                                               \
    _Pragma("unroll") for (int j = 8 * (H0); j < 8 * (H1); j++) {                                                  \
      a_[j] = pack2(SRC[2 * j], SRC[2 * j + 1]);                                                                   \
      asm volatile("fma.rn.bf16x2 %0, %1, %1, %0;" : "+r"(nq[(j >> 4) * 2 + (j & 1)]) : "r"(a_[j]));               \
    }                                                                                                              \
    wg_fence();                                                                                                    \
    _Pragma("unroll") for (int hk = 2 * (H0); hk < 2 * (H1); hk++)                                                 \
        wgmma_n32_rs_ta0_tb1(DST + 16 * (hk >> 1), a_[4 * hk], a_[4 * hk + 1], a_[4 * hk + 2], a_[4 * hk + 3],     \
                             mkdesc(sb + SM_WPHI + hk * 1024, 16, 512, 2), hk & 1);                                \
    wg_commit();                                                                                                   \
  } while (0)
    {
      float p[64], ea[24], eb[24], sa[4], sc[4], kz[20];
      uint32_t vp[32];
#pragma unroll
      for (int j = 0; j < 32; j++) vp[j] = pack2(kv[64 + 2 * j], kv[65 + 2 * j]);
      const uint32_t vr = w * 16 + (lane & 15), vb = sb + SM_V + wg * 4096 + vr * 64, x64 = (vr >> 1) & 3;
#define V_STORE(R)                                                                                           \
  _Pragma("unroll") for (int j = 0; j < 4; j++)                                                              \
      stsm4(vb + (j >> 1) * 8192 + ((((j & 1) * 2 + hi16) ^ x64) << 4), vp[16 * (R) + 4 * j], vp[16 * (R) + 4 * j + 1], vp[16 * (R) + 4 * j + 2], vp[16 * (R) + 4 * j + 3])
      V_STORE(0);
      mbar_wait(bar + B_WPHI, 0);
      {
        uint32_t nq[4] = {0u, 0u, 0u, 0u};
        PHI_PROJ(p, kv, 0, 4);
        QSTEP_A(0, 0, 0);
        const bool unsafe = softmax_unsafe(nq, c0 * c0 * wn, c1 * c1 * wn);
        wg_wait<1>();
        reg_fence<64>(p);
        if (__builtin_expect(unsafe, 0)) softmax_shift(p, c0, c1);
      }
#define K_NORM(S) do { quad_sum<4>(S); _Pragma("unroll") for (int i = 0; i < 4; i++) S[i] = rcp(S[i]) * ((i & 1) ? st1.y : st0.y); } while (0)
#define K_STORE(SLOT, E, S) K_STORE_(SLOT, E, S, 0, 2)
#define K_STORE_(SLOT, E, S, J0, J1)                                                                         \
  _Pragma("unroll") for (int j = (J0); j < (J1); j++) {                                                      \
    uint32_t fp[4], fm[4];                                                                                   \
    _Pragma("unroll") for (int i = 0; i < 4; i++) {                                                          \
      const float e0 = E[8 * j + 2 * i], e1 = E[8 * j + 2 * i + 1], r = E[16 + 4 * j + i] * S[2 + (i & 1)];  \
      const uint32_t e2 = pack2(e0, e1);                                                                     \
      fp[i] = bmul2(e2, pack2(S[i & 1], S[i & 1]));                                                          \
      fm[i] = bmul2(e2, pack2(r, r));                                                                        \
    }                                                                                                        \
    stsm4(sb + SM_PHI + (SLOT) * 16384 + sw128 + (((2 * j + hi16) ^ x128) << 4), fp[0], fp[1], fp[2], fp[3]); \
    stsm4(sb + SM_PHI + (SLOT) * 16384 + sw128 + (((4 + 2 * j + hi16) ^ x128) << 4), fm[0], fm[1], fm[2], fm[3]); \
  }
#define KV_MMA(R)                                                                                            \
  do {                                                                                                       \
    mbar_wait(bar + B_PHI + 8 * (R), 0);                                                                     \
    wg_fence();                                                                                              \
    _Pragma("unroll") for (int k = 0; k < 8; k++) {                                                          \
      const uint32_t vs = SM_V + (k >> 2) * 4096 + (k & 3) * 1024;                                           \
      wgmma_n40_ss_ta1_tb1(kz, mkdesc(sb + SM_PHI + k * 2048, 16, 1024, 1, wg * 1024),                       \
                           mkdesc(sb + vs, SM_SDT + (k & 1) * 1024 + (k >> 1) * 16 - vs, 512, 2, wg * (512u - (512u << 16))), k); \
    }                                                                                                        \
    wg_commit();                                                                                             \
  } while (0)
#define QKV(J, R) do { KV_MMA(R); QSTEP_A(J, Q_OFF16(J), 1); wg_wait<2>(); QREL((J) - 1); SCHED_FENCE(); } while (0)
#define KV_SEND(R)                                                                                           \
  do {                                                                                                       \
    reg_fence<20>(kz);                                                                                       \
    if (lane == 0) mbar_arrive(bar + B_KVST + 8 * (R));                                                      \
    const uint32_t slot = ((hg * 2 + (R)) * 16 + warp * 2) * 16 + mb;                                        \
    _Pragma("unroll") for (int u = 0; u < 2; u++)                                                            \
      st_rlx128(g_part + (slot + u * 16) * 32 + lane, mark(pack2(kz[2 * u], kz[2 * u + 1]), tag & 1), pack2(kz[2 * u + 4], kz[2 * u + 5]), \
                pack2(kz[2 * u + 8], kz[2 * u + 9]), pack2(kz[2 * u + 12], kz[2 * u + 13]));                 \
    if (t < 2) st_rlx(g_zpart + (slot + t * 16) * 8 + g, mark(__float_as_uint(t ? kz[18] : kz[16]), tag & 1)); \
    if (lane < 2) red_inc(g_xcnt + hg * 64 + (R) * 16 + warp * 2 + lane);                                    \
  } while (0)
#define K_PUB(R) do { fence_async_smem(); __syncwarp(); if (lane == 0) mbar_arrive(bar + B_PHI + 8 * (R)); } while (0)
#define S_PIN(S) SCHED_PIN(S[0] + S[1] + S[2] + S[3])
      k_exp(p, c0, c1, ea, sa);
      S_PIN(sa);
      QNEXT(1);
      K_NORM(sa);
      k_exp<0, 4>(p + 16, c0, c1, eb, sc);
      mbar_wait(bar + B_FFN, 0);
      K_STORE_(0, ea, sa, 0, 1);
      S_PIN(sc);
      QNEXT(2);
      K_STORE_(0, ea, sa, 1, 2);
      k_exp<4, 8>(p + 16, c0, c1, eb, sc);
      K_NORM(sc);
      S_PIN(sc);
      QNEXT(3);
      K_STORE(1, eb, sc);
      K_PUB(0);
      k_exp<0, 4>(p + 32, c0, c1, ea, sa);
      S_PIN(sa);
      QKV(4, 0);
      k_exp<4, 8>(p + 32, c0, c1, ea, sa);
      K_NORM(sa);
      k_exp<0, 4>(p + 48, c0, c1, eb, sc);
      SCHED_PIN(sa[0] + sa[1] + sa[2] + sa[3] + sc[2] + sc[3]);
      QNEXT(5);
      KV_SEND(0);
      k_exp<4, 8>(p + 48, c0, c1, eb, sc);
      S_PIN(sc);
      QNEXT(6);
      K_NORM(sc);
      mbar_wait(bar + B_KVST, 0);
      V_STORE(1);
      K_STORE(0, ea, sa);
      QNEXT(7);
      K_STORE(1, eb, sc);
      K_PUB(1);
      QKV(8, 1);
      QNEXT(9);
      KV_SEND(1);
    }
#define JQ0 10
    PROFC(3);
    {
      bool todo = true;
#pragma unroll 1
      for (int j = JQ0; j < 15 || todo; j++) {
        if (j < 15) { QSTEP_A(j, Q_AOFF(j) / 16, 1); wg_wait<1>(); QREL(j - 1); }
        if (todo && __any_sync(~0u, mbar_test(bar + B_PART + 8 * wg, 0))) {
          todo = false;
          const uint32_t own = (hg * 2 + wg) * 16 + mb, word = w * 32 + lane;
          uint32_t u[16], bad = 0;
#pragma unroll
          for (int i = 0; i < 16; i++) { u[i] = __float_as_uint(lds32(sb + (wg ? SM_PST1 : SM_PST0) + i * 512 + word * 4)); bad |= u[i] ^ tag; }
#pragma unroll 1
          for (int it = 0; it < SPIN_MAX && __any_sync(~0u, t == 0 && (bad & 1)); it++) {
            bad = 0;
#pragma unroll
            for (int i = 0; i < 16; i++) { u[i] = ld_rlx((const uint32_t*)g_part + own * 2048 + i * 128 + word); bad |= u[i] ^ tag; }
          }
          float s0 = 0.f, s1 = 0.f, s2 = 0.f, s3 = 0.f;
#pragma unroll
          for (int i = 0; i < 16; i += 2) { s0 += bf_lo(u[i] | !t); s1 += bf_hi(u[i]); s2 += bf_lo(u[i + 1] & (t ? ~0u : ~1u)); s3 += bf_hi(u[i + 1]); }
          const uint32_t r = pack2(s0 + s2, s1 + s3);
          st_rlx((uint32_t*)g_res[tag & 1] + own * 128 + w * 32 + (lane & 16) + ((t ^ w) << 2) + ((lane >> 2) & 3), lane & 12 ? r : r | 1);
          ((uint32_t*)g_res[~tag & 1])[own * 128 + word] = 0;
          __syncwarp();
          if (lane == 0) { red_inc(g_xcnt + hg * 64 + 32 + wg * 16); if (w == 0) PROF(wg ? 12 : 30); }
          __syncwarp();
        }
      }
    }
    mbar_wait(bar + B_CSQ, 0);
    QWAIT(15);
    if (wg == 1) bar_sync(6, 256);
    wg_fence();
    wgmma_n128_rs_ta0_tb1(q, fa0, fa1, 0u, 0u, mkdesc(sb + SM_CST + 2048, 512, 0, 1), 1);
    QMMA(15, Q_AOFF(15) / 16, 1);
    wg_commit();
    if (wg == 0) asm volatile("bar.arrive 6, 256;" ::: "memory");
    wg_wait<1>();
    QREL(14);
    wg_wait<0>();
    QREL(15);
    reg_fence<64>(q);
    PROFC(5);
    float yp[4];
    const uint32_t par = tag & 1;
    uint4* ofr = g_ofr + (mb * 16 + hg * 2) * 1024 + (warp * 16 + g) * 8;
#define O_MMA(H, F, N)                                                                                       \
  do {                                                                                                       \
    wg_fence();                                                                                              \
    _Pragma("unroll") for (int k = 0; k < 4; k++) {                                                          \
      const uint32_t ks = SM_V + (H) * 4096 + k * 1024;                                                      \
      wgmma_n40_rs_ta0_tb1(N + 20 * (k >> 1), F[4 * k], F[4 * k + 1], F[4 * k + 2], F[4 * k + 3],            \
                           mkdesc(sb + ks, SM_ZT + (H) * 1024 + k * 16 - ks, 512, 2), k & 1);                \
    }                                                                                                        \
    wg_commit();                                                                                             \
  } while (0)
#define O_FIN(H, N, o)                                                                                        \
  do {                                                                                                       \
    reg_fence<40>(N);                                                                                        \
    const float *np = N, *nm = N + 20;                                                                       \
    const float d0 = rcp(fmaf(np[16], nm[17], fmaf(nm[16], np[17], 1e-6f * np[17] * nm[17])));               \
    const float d1 = rcp(fmaf(np[18], nm[19], fmaf(nm[18], np[19], 1e-6f * np[19] * nm[19])));               \
    const float bp0 = nm[17] * d0, bm0 = np[17] * d0, bp1 = nm[19] * d1, bm1 = np[19] * d1;                  \
    _Pragma("unroll") for (int j = 0; j < 4; j++) {                                                          \
      o[2 * j] = pack2(fmaf(np[4 * j], bp0, nm[4 * j] * bm0), fmaf(np[4 * j + 1], bp0, nm[4 * j + 1] * bm0)); \
      o[2 * j + 1] = pack2(fmaf(np[4 * j + 2], bp1, nm[4 * j + 2] * bm1), fmaf(np[4 * j + 3], bp1, nm[4 * j + 3] * bm1)); \
    }                                                                                                        \
  } while (0)
#define O_STG(H, o)                                                                                          \
  _Pragma("unroll") for (int u = 0; u < 2; u++) {                                                            \
    uint32_t v_[4];                                                                                          \
    _Pragma("unroll") for (int j = 0; j < 4; j++) v_[j] = lop_select(o[2 * j + u], parm, vword == j);        \
    st_rlx128(ofr + ((H) >> 1) * 1024 + u * 64 + ((((H) & 1) * 4 + t) ^ g), v_[0], v_[1], v_[2], v_[3]);     \
  }
    uint32_t gf[32], ao[16];
    const uint32_t parm = 0u - par, vword = ((t ^ g) & 1) == (g >> 2) ? g & 3 : 4;
    const float rh0 = 0.5f * st0.y, rh1 = 0.5f * st1.y, mh0 = st0.x * rh0, mh1 = st1.x * rh1;
#define GATE_LD(J) ldsm4(sb + ((J) >> 2 ? SM_X1 : SM_X0) + sw128 + (((((J) & 3) * 2 + hi16) ^ x128) << 4), gf[4 * (J)], gf[4 * (J) + 1], gf[4 * (J) + 2], gf[4 * (J) + 3])
#define GATE(I0, I1)                                                                                         \
  _Pragma("unroll") for (int i = (I0); i < (I1); i++) {                                                      \
    const float rs = (i & 1) ? rh1 : rh0, mh = (i & 1) ? mh1 : mh0;                                          \
    const float h0 = fmaf(bf_lo(gf[i]), rs, mh), h1 = fmaf(bf_hi(gf[i]), rs, mh);                            \
    gf[i] = pack2(fmaf(h0, tanh_approx(h0), h0), fmaf(h1, tanh_approx(h1), h1));                             \
  }
#define GATE_PIN(I0, I1) do { uint32_t o_ = 0; _Pragma("unroll") for (int i = (I0); i < (I1); i++) o_ |= gf[i]; SCHED_PIN(__uint_as_float(o_)); } while (0)
    {
      float p[64], na[40], nb[40];
      uint32_t fa[16], fb[16];
      {
        uint32_t nq[4] = {0u, 0u, 0u, 0u};
        PHI_PROJ(p, q, 0, 2);
        SCHED_FENCE();
        PHI_PROJ(p, q, 2, 4);
        const bool unsafe = softmax_unsafe(nq, c0 * c0 * wn, c1 * c1 * wn);
        if (TW == 0) mbar_wait(bar + B_TILE, 0);
        wg_wait<0>();
        reg_fence<64>(p);
        PROFC(24);
        if (__builtin_expect(unsafe, 0)) softmax_shift(p, c0, c1);
      }
      float dn[32];
#define DN_PART(A, B)                                                                                        \
  do {                                                                                                       \
    wg_fence();                                                                                              \
    _Pragma("unroll") for (int i = (A); i < (B); i++)                                                        \
      wgmma_n8_ss_ta1_tb1(dn + 4 * (i >> 1), mkdesc(sb + (i >> 3) * Q_STAGE + (i & 7) * 2048, 16, 1024, 1, wg * (2 * Q_STAGE / 16)), \
                          mkdesc(sb + SM_HT + (i & 1) * 256, 128, 128, 0), i & 1);                           \
  } while (0)
#define F_PIN(F, A, B) do { uint32_t o_ = 0; _Pragma("unroll") for (int i = (A); i < (B); i++) o_ |= F[8 + i]; SCHED_PIN(__uint_as_float(o_)); } while (0)
#define RMMA(J, A, ACCUM)                                                                                    \
  do {                                                                                                       \
    wg_fence();                                                                                              \
    _Pragma("unroll") for (int k = 0; k < 4; k++)                                                            \
      wgmma_n128_rs_ta0_tb1(q, (A)[4 * k], (A)[4 * k + 1], (A)[4 * k + 2], (A)[4 * k + 3],                   \
                            mkdesc(sb + 16384 + k * 2048, 8192, 1024, 1, ((J) & 3) * (Q_STAGE / 16)), k ? 1 : (ACCUM)); \
    wg_commit();                                                                                             \
  } while (0)
#define RSTEP(J, A, ACCUM) do { QWAIT(J); RMMA(J, A, ACCUM); } while (0)
      PROFC(4);
      q_exp(p, c0, c1, fa);
      if (TW == 1) { F_PIN(fa, 0, 8); mbar_wait(bar + B_TILE, 0); }
      if (TW == 2) { q_exp(p + 16, c0, c1, fb); F_PIN(fb, 0, 8); mbar_wait(bar + B_TILE, 0); }
      O_MMA(0, fa, na);
      if (TW != 2) q_exp(p + 16, c0, c1, fb);
      O_MMA(1, fb, nb);
      PROFC(25);
      wg_wait<1>();
      O_FIN(0, na, ao);
      O_STG(0, ao);
      wg_wait<0>();
      O_FIN(1, nb, (ao + 8));
      O_STG(1, (ao + 8));
      PROFC(28);
      RSTEP(16, ao, 0);
      SCHED_FENCE();
      q_exp(p + 32, c0, c1, fa);
      F_PIN(fa, 0, 8);
      mbar_wait(bar + B_H, 0);
      mbar_wait(bar + B_DN, 0);
      PROFC(45);
      DN_PART(0, 4);
      SCHED_FENCE();
      q_exp<0, 2>(p + 48, c0, c1, fb);
      F_PIN(fb, 0, 2);
      DN_PART(4, 8);
      SCHED_FENCE();
      q_exp<2, 4>(p + 48, c0, c1, fb);
      F_PIN(fb, 2, 4);
      DN_PART(8, 12);
      SCHED_FENCE();
      q_exp<4, 6>(p + 48, c0, c1, fb);
      F_PIN(fb, 4, 6);
      DN_PART(12, 16);
      wg_commit();
      SCHED_FENCE();
      q_exp<6, 8>(p + 48, c0, c1, fb);
      F_PIN(fb, 6, 8);
      wg_wait<0>();
      reg_fence<32>(dn);
      if (lane == 0) mbar_arrive(bar + B_DND);
      QREL(16);
#pragma unroll
      for (int i = 0; i < 4; i++) yp[i] = t & 2 ? (t & 1 ? dn[24 + 2 * i] : dn[16 + 2 * i]) : (t & 1 ? dn[8 + 2 * i] : dn[2 * i]);
      PROFC(29);
      mbar_wait(bar + B_TILE + 8, 0);
      PROFC(23);
      if (bid < NFFN) {
        float* y = g_y[par ^ 1][bid & 7] + wg * 512 + t * 128 + w * 16 + g;
#pragma unroll
        for (int i = 0; i < 4; i++) red1(y + (i >> 1) * 64 + (i & 1) * 8, yp[i]);
      }
      SCHED_FENCE();
      O_MMA(2, fa, na);
      O_MMA(3, fb, nb);
      __syncwarp();
      if (lane == 0) mbar_arrive(bar + B_YD);
      wg_wait<1>();
      O_FIN(2, na, ao);
      O_STG(2, ao);
      wg_wait<0>();
      O_FIN(3, nb, (ao + 8));
      O_STG(3, (ao + 8));
      PROFC(6);
    }
    RSTEP(17, ao, 1);
    SCHED_FENCE();
    GATE_LD(0); GATE_LD(1);
    GATE(0, 3);
    GATE_PIN(0, 3);
#define GSTEP(J, I0, I1, LD) do { QNEXT(J); if ((LD) < 8) GATE_LD((LD) & 7); GATE(I0, I1); GATE_PIN(I0, I1); } while (0)
    GSTEP(18, 3, 6, 2); GSTEP(19, 6, 9, 3); GSTEP(20, 9, 12, 4); GSTEP(21, 12, 15, 8); GSTEP(22, 15, 18, 5); GSTEP(23, 18, 21, 6);
    GSTEP(24, 21, 24, 8); GSTEP(25, 24, 27, 7); GSTEP(26, 27, 30, 8); GSTEP(27, 30, 32, 8);
#pragma unroll 1
    for (int j = 28; j < 32 - TAILN; j++) QPLAIN(j);
    if (wg == 1) bar_sync(6, 256);
#pragma unroll 1
    for (int j = 32 - TAILN; j < 32; j++) QSTEP_A(j, (j & 3) * (Q_STAGE / 16), 1);
    if (wg == 0) asm volatile("bar.arrive 6, 256;" ::: "memory");
    mbar_wait(bar + B_UPD, 0);
    {
      const int sel = __float_as_int(lds32(sb + SM_UPD + 256)) - (wg * 64 + w * 16 + g);
      if (sel == 0 || sel == 8) {
#pragma unroll
        for (int j = 0; j < 16; j++) {
          const uint32_t u = __float_as_uint(lds32(sb + SM_UPD + j * 16 + t * 4));
          if (sel) gf[2 * j + 1] = u; else gf[2 * j] = u;
        }
      }
      __syncwarp();
      uint32_t xf[32];
#pragma unroll
      for (int j = 0; j < 8; j++)
        ldsm4(sb + (j >> 2 ? SM_X1 : SM_X0) + sw128 + ((((j & 3) * 2 + hi16) ^ x128) << 4), xf[4 * j], xf[4 * j + 1], xf[4 * j + 2], xf[4 * j + 3]);
      wg_wait<0>();
      reg_fence<64>(q);
      PROFC(8);
#pragma unroll
      for (int j = 0; j < 8; j++) {
        uint32_t o[4];
#pragma unroll
        for (int i = 0; i < 4; i++) o[i] = badd2(xf[4 * j + i], bmul2(pack2(q[8 * j + 2 * i], q[8 * j + 2 * i + 1]), gf[4 * j + i]));
        stsm4(sb + (j >> 2 ? SM_X1 : SM_X0) + sw128 + ((((j & 3) * 2 + hi16) ^ x128) << 4), o[0], o[1], o[2], o[3]);
      }
    }
    fence_async_smem();
    bar_sync(2 + wg, 128);
    if (w == 0 && elect_one()) {
      tma_store2d(&mOut, sb + SM_X0 + wg * 8192, hg * 128, mb * 128 + wg * 64);
      tma_store2d(&mOut, sb + SM_X1 + wg * 8192, hg * 128 + 64, mb * 128 + wg * 64);
      bulk_commit();
      bulk_wait_read0();
      if (wg == 1) { PROF(9); PROFT(33); PROF_DUMP; }
    }
  }
}

typedef CUresult (*EncodeFn)(CUtensorMap*, CUtensorMapDataType, cuuint32_t, void*, const cuuint64_t*, const cuuint64_t*, const cuuint32_t*,
                             const cuuint32_t*, CUtensorMapInterleave, CUtensorMapSwizzle, CUtensorMapL2promotion, CUtensorMapFloatOOBfill);

CUtensorMap make_map(EncodeFn enc, const void* ptr, int rank, const cuuint64_t* dims, const cuuint64_t* strides, const cuuint32_t* box, CUtensorMapSwizzle sw) {
  CUtensorMap m;
  const cuuint32_t es[5] = {1, 1, 1, 1, 1};
  enc(&m, CU_TENSOR_MAP_DATA_TYPE_BFLOAT16, rank, (void*)ptr, dims, strides, box, es, CU_TENSOR_MAP_INTERLEAVE_NONE, sw,
      CU_TENSOR_MAP_L2_PROMOTION_L2_128B, CU_TENSOR_MAP_FLOAT_OOB_FILL_NONE);
  return m;
}

}

extern "C" void kernel_launch(void* const* d_in, const int* in_sizes, int n_in, void* d_out, int out_size) {
  static EncodeFn enc = nullptr;
  static int by_sm = 0;
  if (!enc) {
    void* fn = nullptr;
    cudaDriverEntryPointQueryResult qr;
    cudaGetDriverEntryPoint("cuTensorMapEncodeTiled", &fn, cudaEnableDefault, &qr);
    enc = (EncodeFn)fn;
    cudaFuncSetAttribute(fused_kernel, cudaFuncAttributeMaxDynamicSharedMemorySize, SM_TOTAL);
    int dev = 0, sms = 0;
    cudaGetDevice(&dev);
    cudaDeviceGetAttribute(&sms, cudaDevAttrMultiProcessorCount, dev);
    by_sm = BY_SM && sms == NCTA + NSPARE;
  }
  Params P;
  P.by_sm = by_sm;
  P.x = (const __nv_bfloat16*)d_in[0];
  P.wqkv = (const __nv_bfloat16*)d_in[1];
  const void* wphi = d_in[2];
  P.wo = (const __nv_bfloat16*)d_in[3];
  P.w_r = (const __nv_bfloat16*)d_in[5];
  P.w_gate = (const __nv_bfloat16*)d_in[6];
  P.w_up = (const __nv_bfloat16*)d_in[7];
  P.w_down = (const __nv_bfloat16*)d_in[8];

  const cuuint64_t dX[2] = {DM, SEQ}, sX[1] = {DM * 2};
  const cuuint32_t b128[2] = {64, 128}, b64[2] = {64, 64};
  const cuuint64_t dW[4] = {64, DM, 16, 3}, sW[3] = {3 * DM * 2, 128, DM * 2};
  const cuuint32_t bKV[4] = {64, 64, 2, 2}, bQ[4] = {64, 64, 2, 1};
  const cuuint64_t dO[3] = {64, DM, 16}, sO[2] = {DM * 2, 128};
  const cuuint32_t bO[3] = {64, 64, 2};
  const cuuint64_t dP[2] = {32, 1024}, sP[1] = {64};
  const cuuint32_t bP[2] = {32, 128};
  CUtensorMap mX = make_map(enc, P.x, 2, dX, sX, b128, CU_TENSOR_MAP_SWIZZLE_128B);
  CUtensorMap mWkv = make_map(enc, P.wqkv, 4, dW, sW, bKV, CU_TENSOR_MAP_SWIZZLE_128B);
  CUtensorMap mWq = make_map(enc, P.wqkv, 4, dW, sW, bQ, CU_TENSOR_MAP_SWIZZLE_128B);
  CUtensorMap mWo = make_map(enc, P.wo, 3, dO, sO, bO, CU_TENSOR_MAP_SWIZZLE_128B);
  CUtensorMap mPhi = make_map(enc, wphi, 2, dP, sP, bP, CU_TENSOR_MAP_SWIZZLE_64B);
  const cuuint64_t dWp[5] = {DM, 2, 4, 4, DM / 32}, sWp[4] = {DM * 2, 8 * DM * 2, 2 * DM * 2, 32 * DM * 2};
  const cuuint32_t bWp[5] = {64, 2, 4, 4, 2};
  CUtensorMap mWp = make_map(enc, P.wo, 5, dWp, sWp, bWp, CU_TENSOR_MAP_SWIZZLE_128B);
  CUtensorMap mOut = make_map(enc, d_out, 2, dX, sX, b64, CU_TENSOR_MAP_SWIZZLE_128B);
  const cuuint64_t dWc[2] = {3 * DM, DM}, sWc[1] = {3 * DM * 2}, dG[2] = {FF, DM}, sG[1] = {FF * 2}, dD[3] = {64, FF, 16};
  const cuuint32_t b32[2] = {32, 32}, bD[3] = {64, 32, 4};
  CUtensorMap mWc = make_map(enc, P.wqkv, 2, dWc, sWc, b32, CU_TENSOR_MAP_SWIZZLE_NONE);
  CUtensorMap mG = make_map(enc, P.w_gate, 2, dG, sG, b32, CU_TENSOR_MAP_SWIZZLE_NONE);
  CUtensorMap mU = make_map(enc, P.w_up, 2, dG, sG, b32, CU_TENSOR_MAP_SWIZZLE_NONE);
  CUtensorMap mD = make_map(enc, P.w_down, 3, dD, sO, bD, CU_TENSOR_MAP_SWIZZLE_128B);
  const cuuint64_t dXs[3] = {256, SEQ, 4}, sXs[2] = {DM * 2, 512};
  const cuuint32_t bXs[3] = {256, 16, 2};
  CUtensorMap mXs = make_map(enc, P.x, 3, dXs, sXs, bXs, CU_TENSOR_MAP_SWIZZLE_NONE);
  const cuuint64_t dG2[4] = {64, DM, FF / 64, 1}, sG2[3] = {FF * 2, 128, (cuuint64_t)FF * DM * 2};
  CUtensorMap mG2 = make_map(enc, P.w_gate, 4, dG2, sG2, bQ, CU_TENSOR_MAP_SWIZZLE_128B);
  CUtensorMap mU2 = make_map(enc, P.w_up, 4, dG2, sG2, bQ, CU_TENSOR_MAP_SWIZZLE_128B);
  fused_kernel<<<NCTA + NSPARE, 384, SM_TOTAL, cudaStreamPerThread>>>(mX, mWkv, mWq, mWo, mPhi, mWp, mOut, mWc, mG, mU, mD, mXs, mG2, mU2, P);
}
```

```cpp
#include <cuda_runtime.h>
#include <cuda_bf16.h>
#include <cuda.h>
#include <stdint.h>

namespace {

constexpr int SEQ = 2048, DM = 1024, FF = 3584;
constexpr int NCTA = 128;
constexpr int NSPARE = 4;
constexpr int NFFN = FF / 32;
#define GN 6
#define G8 2
constexpr int GROWS = (3 * GN + G8) * 32;
#define TAILN 2
#define KTAIL 1
#define XS_EARLY 1
#define PF_FIRST 2
#define PF_W 5
#define PF_PRE 1
#define PFG 0
#define PFD 80
#define BY_SM 1
#define PTAB 0x73216540u
#define ROWSPLIT 1
#define WOT 1
#define PSPLIT 1
#define KSTEPS 4
#define NOVAL 0
#define KCH 1
#define REG_C 224
#define REG_H 56
#define TW 1
#define FENCE_KIND 2
#define ORDER_ALL 1
#define AM_NS 100
constexpr bool FFN_OFF = false;

static_assert(2 * REG_C + REG_H <= 3 * 168, "the register pool of the CTA is 384 x 168");

__device__ uint32_t g_epoch[(NCTA + NSPARE) * 32];
__device__ unsigned long long g_stat[SEQ];
__device__ __align__(128) unsigned long long g_best[NCTA];
__device__ __align__(16) float g_y[2][8][DM];
__device__ __align__(128) uint32_t g_ycnt[64];
__device__ __align__(128) uint32_t g_xcnt[8 * 64];
__device__ __align__(128) uint4 g_res[2][32 * 256];
__device__ __align__(16) float g_cs[5 * DM];
__device__ __align__(128) float g_gp[2 * FF];
__device__ uint4 g_part[8 * 2 * 16 * 16 * 32];
__device__ __align__(16) float g_zpart[8 * 2 * 16 * 16 * 8];
__device__ __align__(128) float g_zres[32 * 64];
__device__ __align__(1024) uint4 g_ofr[16 * 16 * 1024];
#define PROF(i)
#define PROFT(i)
#define PROFC(i)
#define PROF_DUMP
#define PW0(J)
#define PW1(J)

constexpr uint32_t KV_STAGE = 49152, Q_STAGE = 32768;
constexpr uint32_t SM_V = 147456;
constexpr uint32_t SM_PHI = 163840;
constexpr uint32_t SM_XST = 147456;
constexpr uint32_t SM_FST = 172032;
constexpr uint32_t SM_PST0 = 196608, SM_PST1 = SM_PHI + 8192;
constexpr uint32_t SM_X0 = 131072, SM_X1 = SM_PHI + 16384;
constexpr uint32_t SM_WPHI = 204800;
constexpr uint32_t SM_ZT = 212992;
constexpr uint32_t SM_SDT = 217088;
constexpr uint32_t SM_CST = 219136;
constexpr uint32_t SM_HT = 222720;
constexpr uint32_t SM_STAT = 223232;
constexpr uint32_t SM_XSEL = 224256;
constexpr uint32_t SM_RED = 228352;
constexpr uint32_t SM_ROWS = SM_RED + 832;
constexpr uint32_t SM_GRED = SM_XSEL + 3072;
static_assert(GROWS <= 768, "xsel area");
constexpr uint32_t SM_UPD = 229632;
constexpr uint32_t SM_BAR = 230016;
constexpr uint32_t SM_PROF = 230464;
constexpr uint32_t SM_SINK = 231104;
constexpr uint32_t SM_TOTAL = 231616;
constexpr uint32_t SB = 1024;
constexpr uint32_t B_FULLKV = 0  , B_FST = 24  , B_XFULL = 88  , B_XST = 104  , B_WPHI = 120, B_CS = 128, B_CSQ = 136, B_UPD = 144,
                   B_H = 152, B_DN = 160, B_XS = 168, B_TILE = 176  , B_RES = 192  , B_PART = 208  ,
B_AIN = 224  ,
                   B_FULLQ = 288  ,
                   B_FFN = 320,
                   B_EMPTYKV = 328  , B_EMPTYQ = 352  , B_KVST = 384  , B_YD = 400, B_PHI = 408  , B_DND = 424, B_END = 432;

__device__ __forceinline__ uint32_t smem_u32(const void* p) { return (uint32_t)__cvta_generic_to_shared(p); }
__device__ __forceinline__ void mbar_init(uint32_t bar, uint32_t cnt) { asm volatile("mbarrier.init.shared::cta.b64 [%0], %1;" ::"r"(bar), "r"(cnt) : "memory"); }
__device__ __forceinline__ void mbar_expect_tx(uint32_t bar, uint32_t bytes) { asm volatile("mbarrier.arrive.expect_tx.shared::cta.b64 _, [%0], %1;" ::"r"(bar), "r"(bytes) : "memory"); }
__device__ __forceinline__ void mbar_arrive2(uint32_t bar) { asm volatile("mbarrier.arrive.shared::cta.b64 _, [%0], 2;" ::"r"(bar) : "memory"); }
__device__ __forceinline__ void mbar_arrive(uint32_t bar) { asm volatile("mbarrier.arrive.shared::cta.b64 _, [%0];" ::"r"(bar) : "memory"); }
__device__ __forceinline__ void mbar_wait(uint32_t bar, uint32_t parity) {
  asm volatile("{\n.reg .pred p;\nLW:\nmbarrier.try_wait.parity.shared::cta.b64 p, [%0], %1;\n@!p bra LW;\n}" ::"r"(bar), "r"(parity) : "memory");
}
__device__ __forceinline__ bool mbar_test(uint32_t bar, uint32_t parity) {
  uint32_t ok;
  asm volatile("{\n.reg .pred p;\nmbarrier.test_wait.parity.shared::cta.b64 p, [%1], %2;\nselp.u32 %0, 1, 0, p;\n}" : "=r"(ok) : "r"(bar), "r"(parity) : "memory");
  return ok;
}
__device__ __forceinline__ int lane_id() { int l; asm volatile("mov.u32 %0, %%laneid;" : "=r"(l)); return l; }
template <int C> __device__ __forceinline__ void sched_fence_(int zero) {
  asm volatile("{\n.reg .pred p;\nsetp.eq.s32 p, %0, %1;\n@p trap;\n}" ::"r"(zero), "n"(C) : "memory");
}
#define SCHED_FENCE() sched_fence_<1000 + __COUNTER__>(zero)
#define SCHED_PIN(V) sched_fence_<1000 + __COUNTER__>(zero & __float_as_int(V))
__device__ __forceinline__ bool elect_one() {
  uint32_t p; asm volatile("{ .reg .pred P; elect.sync _|P, 0xffffffff; selp.u32 %0, 1, 0, P; }" : "=r"(p)); return p;
}
__device__ __forceinline__ void tma2d(uint32_t dst, const CUtensorMap* m, int x, int y, uint32_t bar) {
  asm volatile("cp.async.bulk.tensor.2d.shared::cluster.global.mbarrier::complete_tx::bytes [%0], [%1, {%3, %4}], [%2];" ::"r"(dst), "l"(m), "r"(bar), "r"(x), "r"(y) : "memory");
}
__device__ __forceinline__ void tma3d(uint32_t dst, const CUtensorMap* m, int x, int y, int z, uint32_t bar) {
  asm volatile("cp.async.bulk.tensor.3d.shared::cluster.global.mbarrier::complete_tx::bytes [%0], [%1, {%3, %4, %5}], [%2];" ::"r"(dst), "l"(m), "r"(bar), "r"(x), "r"(y), "r"(z) : "memory");
}
__device__ __forceinline__ void tma4d(uint32_t dst, const CUtensorMap* m, int x, int y, int z, int w, uint32_t bar) {
  asm volatile("cp.async.bulk.tensor.4d.shared::cluster.global.mbarrier::complete_tx::bytes [%0], [%1, {%3, %4, %5, %6}], [%2];" ::"r"(dst), "l"(m), "r"(bar), "r"(x), "r"(y), "r"(z), "r"(w) : "memory");
}
__device__ __forceinline__ void tma5d(uint32_t dst, const CUtensorMap* m, int x, int v, uint32_t bar) {
  asm volatile("cp.async.bulk.tensor.5d.shared::cluster.global.mbarrier::complete_tx::bytes [%0], [%1, {%3, %5, %5, %5, %4}], [%2];" ::"r"(dst), "l"(m), "r"(bar), "r"(x), "r"(v), "r"(0) : "memory");
}
__device__ __forceinline__ void tma_store2d(const CUtensorMap* m, uint32_t src, int x, int y) {
  asm volatile("cp.async.bulk.tensor.2d.global.shared::cta.bulk_group [%0, {%2, %3}], [%1];" ::"l"(m), "r"(src), "r"(x), "r"(y) : "memory");
}
__device__ __forceinline__ void bulk_load(uint32_t dst, const void* src, uint32_t bytes, uint32_t bar) {
  asm volatile("cp.async.bulk.shared::cluster.global.mbarrier::complete_tx::bytes [%0], [%1], %2, [%3];" ::"r"(dst), "l"(src), "r"(bytes), "r"(bar) : "memory");
}
__device__ __forceinline__ void bulk_commit() { asm volatile("cp.async.bulk.commit_group;" ::: "memory"); }
__device__ __forceinline__ void bulk_wait0() { asm volatile("cp.async.bulk.wait_group 0;" ::: "memory"); }
__device__ __forceinline__ void bulk_wait_read0() { asm volatile("cp.async.bulk.wait_group.read 0;" ::: "memory"); }
__device__ __forceinline__ void prefetch_l2(const void* p) { asm volatile("prefetch.global.L2 [%0];" ::"l"(p) : "memory"); }
__device__ __forceinline__ void touch_l2(const void* p, int lane) { asm volatile("cp.async.cg.shared.global.L2::128B [%0], [%1], 16;" ::"r"(SB + SM_SINK + lane * 16), "l"(p) : "memory"); }
__device__ __forceinline__ void prefetch_map(const CUtensorMap* m) { asm volatile("prefetch.tensormap [%0];" ::"l"(m) : "memory"); }
__device__ __forceinline__ void fence_async_smem() { asm volatile("fence.proxy.async.shared::cta;" ::: "memory"); }
__device__ __forceinline__ void fence_async_global() { asm volatile("fence.proxy.async.global;" ::: "memory"); }
__device__ __forceinline__ void bar_sync(int id, int n) { asm volatile("bar.sync %0, %1;" ::"r"(id), "r"(n) : "memory"); }
__device__ __forceinline__ void wg_fence() { asm volatile("wgmma.fence.sync.aligned;" ::: "memory"); }
__device__ __forceinline__ void wg_commit() { asm volatile("wgmma.commit_group.sync.aligned;" ::: "memory"); }
template <int N> __device__ __forceinline__ void wg_wait() { asm volatile("wgmma.wait_group.sync.aligned %0;" ::"n"(N) : "memory"); }
template <int N> __device__ __forceinline__ void reg_fence(uint32_t* r) {
#pragma unroll
  for (int i = 0; i < N; i++) asm volatile("" : "+r"(r[i])::"memory");
}
template <int N> __device__ __forceinline__ void reg_fence(float* r) {
#pragma unroll
  for (int i = 0; i < N; i++) asm volatile("" : "+f"(r[i])::"memory");
}
__device__ __forceinline__ uint64_t mkdesc(uint32_t addr, uint32_t lbo, uint32_t sbo, uint32_t swz, uint32_t dyn = 0) {
  const uint32_t lo = ((addr >> 4) | ((lbo >> 4) << 16)) + dyn;
  const uint32_t hi = (sbo >> 4) | (swz << 30);
  uint64_t d;
  asm("mov.b64 %0, {%1, %2};" : "=l"(d) : "r"(lo), "r"(hi));
  return d;
}
__device__ __forceinline__ void stsm4(uint32_t addr, uint32_t a, uint32_t b, uint32_t c, uint32_t d) {
  asm volatile("stmatrix.sync.aligned.m8n8.x4.shared.b16 [%0], {%1, %2, %3, %4};" ::"r"(addr), "r"(a), "r"(b), "r"(c), "r"(d) : "memory");
}
__device__ __forceinline__ void ldsm4(uint32_t addr, uint32_t& a, uint32_t& b, uint32_t& c, uint32_t& d) {
  asm volatile("ldmatrix.sync.aligned.m8n8.x4.shared.b16 {%0, %1, %2, %3}, [%4];" : "=r"(a), "=r"(b), "=r"(c), "=r"(d) : "r"(addr) : "memory");
}
__device__ __forceinline__ uint32_t pack2(float lo, float hi) { uint32_t r; asm("cvt.rn.bf16x2.f32 %0, %1, %2;" : "=r"(r) : "f"(hi), "f"(lo)); return r; }
__device__ __forceinline__ uint32_t bsub2(uint32_t a, uint32_t b) { uint32_t r; asm("sub.rn.bf16x2 %0, %1, %2;" : "=r"(r) : "r"(a), "r"(b)); return r; }
__device__ __forceinline__ uint32_t badd2(uint32_t a, uint32_t b) { uint32_t r; asm("add.rn.bf16x2 %0, %1, %2;" : "=r"(r) : "r"(a), "r"(b)); return r; }
__device__ __forceinline__ uint32_t bmul2(uint32_t a, uint32_t b) { uint32_t r; asm("mul.rn.bf16x2 %0, %1, %2;" : "=r"(r) : "r"(a), "r"(b)); return r; }
__device__ __forceinline__ float bf_lo(uint32_t v) { return __uint_as_float(v << 16); }
__device__ __forceinline__ float bf_hi(uint32_t v) { return __uint_as_float(v & 0xffff0000u); }
__device__ __forceinline__ float bf_round(float v) { return bf_lo(pack2(v, 0.f)); }
__device__ __forceinline__ float ex2(float v) { float r; asm("ex2.approx.ftz.f32 %0, %1;" : "=f"(r) : "f"(v)); return r; }
__device__ __forceinline__ float rcp(float v) { float r; asm("rcp.approx.ftz.f32 %0, %1;" : "=f"(r) : "f"(v)); return r; }
__device__ __forceinline__ float sqrt_approx(float v) { float r; asm("sqrt.approx.f32 %0, %1;" : "=f"(r) : "f"(v)); return r; }
__device__ __forceinline__ float4 lds128(uint32_t a) { float4 v; asm volatile("ld.shared.v4.f32 {%0, %1, %2, %3}, [%4];" : "=f"(v.x), "=f"(v.y), "=f"(v.z), "=f"(v.w) : "r"(a) : "memory"); return v; }
__device__ __forceinline__ uint4 lds128u(uint32_t a) { uint4 v; asm volatile("ld.shared.v4.u32 {%0, %1, %2, %3}, [%4];" : "=r"(v.x), "=r"(v.y), "=r"(v.z), "=r"(v.w) : "r"(a) : "memory"); return v; }
__device__ __forceinline__ float2 lds64(uint32_t a) { float2 v; asm volatile("ld.shared.v2.f32 {%0, %1}, [%2];" : "=f"(v.x), "=f"(v.y) : "r"(a) : "memory"); return v; }
__device__ __forceinline__ float lds32(uint32_t a) { float v; asm volatile("ld.shared.f32 %0, [%1];" : "=f"(v) : "r"(a) : "memory"); return v; }
__device__ __forceinline__ void sts32(uint32_t a, float v) { asm volatile("st.shared.f32 [%0], %1;" ::"r"(a), "f"(v) : "memory"); }
__device__ __forceinline__ void sts64(uint32_t a, float x, float y) { asm volatile("st.shared.v2.f32 [%0], {%1, %2};" ::"r"(a), "f"(x), "f"(y) : "memory"); }
__device__ __forceinline__ void sts128(uint32_t a, float x, float y, float z, float w) { asm volatile("st.shared.v4.f32 [%0], {%1, %2, %3, %4};" ::"r"(a), "f"(x), "f"(y), "f"(z), "f"(w) : "memory"); }
__device__ __forceinline__ void sts64u(uint32_t a, uint32_t x, uint32_t y) { asm volatile("st.shared.v2.u32 [%0], {%1, %2};" ::"r"(a), "r"(x), "r"(y) : "memory"); }
__device__ __forceinline__ void sts128u(uint32_t a, uint32_t x, uint32_t y, uint32_t z, uint32_t w) { asm volatile("st.shared.v4.u32 [%0], {%1, %2, %3, %4};" ::"r"(a), "r"(x), "r"(y), "r"(z), "r"(w) : "memory"); }
__device__ __forceinline__ uint4 ldg_nc(const void* p) { uint4 v; asm volatile("ld.global.nc.L1::no_allocate.v4.u32 {%0, %1, %2, %3}, [%4];" : "=r"(v.x), "=r"(v.y), "=r"(v.z), "=r"(v.w) : "l"(p)); return v; }
__device__ __forceinline__ float4 ldg_cg4(const float* p) { float4 v; asm volatile("ld.global.cg.v4.f32 {%0, %1, %2, %3}, [%4];" : "=f"(v.x), "=f"(v.y), "=f"(v.z), "=f"(v.w) : "l"(p) : "memory"); return v; }
__device__ __forceinline__ uint32_t ld_acq(const uint32_t* p) { uint32_t v; asm volatile("ld.acquire.gpu.global.u32 %0, [%1];" : "=r"(v) : "l"(p) : "memory"); return v; }
__device__ __forceinline__ uint32_t ld_acq_cta(uint32_t a) { uint32_t v; asm volatile("ld.acquire.cta.shared.u32 %0, [%1];" : "=r"(v) : "r"(a) : "memory"); return v; }
__device__ __forceinline__ void st_rel_cta(uint32_t a, uint32_t v) { asm volatile("st.release.cta.shared.u32 [%0], %1;" ::"r"(a), "r"(v) : "memory"); }
__device__ __forceinline__ unsigned long long ld_rlx64(const unsigned long long* p) { unsigned long long v; asm volatile("ld.relaxed.gpu.global.u64 %0, [%1];" : "=l"(v) : "l"(p) : "memory"); return v; }
__device__ __forceinline__ void st_rlx64(unsigned long long* p, unsigned long long v) { asm volatile("st.relaxed.gpu.global.u64 [%0], %1;" ::"l"(p), "l"(v) : "memory"); }
__device__ __forceinline__ uint4 ld_rlx128(const void* p) {
  uint4 v;
  asm volatile("{ .reg .b128 t; .reg .b64 a, b; ld.relaxed.gpu.global.b128 t, [%4]; mov.b128 {a, b}, t; mov.b64 {%0, %1}, a; mov.b64 {%2, %3}, b; }"
               : "=r"(v.x), "=r"(v.y), "=r"(v.z), "=r"(v.w) : "l"(p) : "memory");
  return v;
}
__device__ __forceinline__ void st_rlx128(void* p, uint32_t x, uint32_t y, uint32_t z, uint32_t w) {
  asm volatile("{ .reg .b128 t; .reg .b64 a, b; mov.b64 a, {%1, %2}; mov.b64 b, {%3, %4}; mov.b128 t, {a, b}; st.relaxed.gpu.global.b128 [%0], t; }"
               ::"l"(p), "r"(x), "r"(y), "r"(z), "r"(w) : "memory");
}
__device__ __forceinline__ void stg128(void* p, uint32_t x, uint32_t y, uint32_t z, uint32_t w) { asm volatile("st.global.v4.u32 [%0], {%1, %2, %3, %4};" ::"l"(p), "r"(x), "r"(y), "r"(z), "r"(w) : "memory"); }
__device__ __forceinline__ void st_rlx(void* p, uint32_t v) { asm volatile("st.relaxed.gpu.global.u32 [%0], %1;" ::"l"(p), "r"(v) : "memory"); }
__device__ __forceinline__ uint32_t lop_select(uint32_t a, uint32_t b, uint32_t m) { uint32_t r; asm("lop3.b32 %0, %1, %2, %3, 0xd8;" : "=r"(r) : "r"(a), "r"(b), "r"(m)); return r; }
__device__ __forceinline__ float unmark(uint32_t v) { return __uint_as_float(v & ~1u); }
__device__ __forceinline__ uint32_t mark(uint32_t v, uint32_t par) { return (v & ~1u) | par; }
__device__ __forceinline__ float tanh_approx(float v) { float r; asm("tanh.approx.f32 %0, %1;" : "=f"(r) : "f"(v)); return r; }
__device__ __forceinline__ void flag_rel(uint32_t* p, uint32_t v) { asm volatile("red.release.gpu.global.max.u32 [%0], %1;" ::"l"(p), "r"(v) : "memory"); }
__device__ __forceinline__ void red1(float* p, float a) { asm volatile("red.global.add.f32 [%0], %1;" ::"l"(p), "f"(a) : "memory"); }
__device__ __forceinline__ void red_inc(uint32_t* p) { asm volatile("red.relaxed.gpu.global.add.u32 [%0], 1;" ::"l"(p) : "memory"); }
__device__ __forceinline__ void red_rel(uint32_t* p) { asm volatile("red.release.gpu.global.add.u32 [%0], 1;" ::"l"(p) : "memory"); }
__device__ __forceinline__ void red4(float* p, float a, float b, float c, float d) { asm volatile("red.global.add.v4.f32 [%0], {%1, %2, %3, %4};" ::"l"(p), "f"(a), "f"(b), "f"(c), "f"(d) : "memory"); }
constexpr int SPIN_MAX = 100000;
__device__ __forceinline__ uint32_t ld_rlx(const uint32_t* p) { uint32_t v; asm volatile("ld.relaxed.gpu.global.u32 %0, [%1];" : "=r"(v) : "l"(p) : "memory"); return v; }
template <int NS = 0> __device__ __forceinline__ void wait_hint(const uint32_t* p, uint32_t target) {
#pragma unroll 1
  for (int i = 0; i < SPIN_MAX; i++) { if ((int)(ld_rlx(p) - target) >= 0) break; if (NS) __nanosleep(NS); }
}
template <int NS> __device__ __forceinline__ void wait_cnt(const uint32_t* p, uint32_t target) {
#pragma unroll 1
  for (int i = 0; i < SPIN_MAX; i++) { if ((int)(ld_rlx(p) - target) >= 0) break; if (NS) __nanosleep(NS); }
  (void)ld_acq(p);
}
template <int NS> __device__ __forceinline__ unsigned long long wait_tag(const unsigned long long* p, uint32_t tag) {
  unsigned long long v = 0;
#pragma unroll 1
  for (int i = 0; i < SPIN_MAX; i++) { v = ld_rlx64(p); if ((uint32_t)(v >> 32) == tag) break; if (NS) __nanosleep(NS); }
  return v;
}
__device__ __forceinline__ float silu_f(float v) { return v * rcp(1.f + ex2(-1.4426950408889634f * v)); }

__device__ __forceinline__ void wgmma_n8_ss_ta1_tb0(float* d, uint64_t da, uint64_t db, bool accumulate) {
  if (accumulate) {
    asm volatile("{\n.reg .pred p;\nsetp.ne.b32 p, 1, 0;\n"
      "wgmma.mma_async.sync.aligned.m64n8k16.f32.bf16.bf16 "
      "{%0, %1, %2, %3}, "
      "%4, %5, p, 1, 1, 1, 0;\n}\n"
      : "+f"(d[0]), "+f"(d[1]), "+f"(d[2]), "+f"(d[3])
      : "l"(da), "l"(db));
  } else {
    asm volatile("{\n.reg .pred p;\nsetp.ne.b32 p, 0, 0;\n"
      "wgmma.mma_async.sync.aligned.m64n8k16.f32.bf16.bf16 "
      "{%0, %1, %2, %3}, "
      "%4, %5, p, 1, 1, 1, 0;\n}\n"
      : "=f"(d[0]), "=f"(d[1]), "=f"(d[2]), "=f"(d[3])
      : "l"(da), "l"(db));
  }
}
__device__ __forceinline__ void wgmma_n8_ss_ta1_tb1(float* d, uint64_t da, uint64_t db, bool accumulate) {
  if (accumulate) {
    asm volatile("{\n.reg .pred p;\nsetp.ne.b32 p, 1, 0;\n"
      "wgmma.mma_async.sync.aligned.m64n8k16.f32.bf16.bf16 "
      "{%0, %1, %2, %3}, "
      "%4, %5, p, 1, 1, 1, 1;\n}\n"
      : "+f"(d[0]), "+f"(d[1]), "+f"(d[2]), "+f"(d[3])
      : "l"(da), "l"(db));
  } else {
    asm volatile("{\n.reg .pred p;\nsetp.ne.b32 p, 0, 0;\n"
      "wgmma.mma_async.sync.aligned.m64n8k16.f32.bf16.bf16 "
      "{%0, %1, %2, %3}, "
      "%4, %5, p, 1, 1, 1, 1;\n}\n"
      : "=f"(d[0]), "=f"(d[1]), "=f"(d[2]), "=f"(d[3])
      : "l"(da), "l"(db));
  }
}
__device__ __forceinline__ void wgmma_n32_rs_ta0_tb1(float* d, uint32_t a0, uint32_t a1, uint32_t a2, uint32_t a3, uint64_t db, bool accumulate) {
  if (accumulate) {
    asm volatile("{\n.reg .pred p;\nsetp.ne.b32 p, 1, 0;\n"
      "wgmma.mma_async.sync.aligned.m64n32k16.f32.bf16.bf16 "
      "{%0, %1, %2, %3, %4, %5, %6, %7, %8, %9, %10, %11, %12, %13, %14, %15}, "
      "{%16, %17, %18, %19}, %20, p, 1, 1, 1;\n}\n"
      : "+f"(d[0]), "+f"(d[1]), "+f"(d[2]), "+f"(d[3]), "+f"(d[4]), "+f"(d[5]), "+f"(d[6]), "+f"(d[7]), "+f"(d[8]), "+f"(d[9]), "+f"(d[10]), "+f"(d[11]), "+f"(d[12]), "+f"(d[13]), "+f"(d[14]), "+f"(d[15])
      : "r"(a0), "r"(a1), "r"(a2), "r"(a3), "l"(db));
  } else {
    asm volatile("{\n.reg .pred p;\nsetp.ne.b32 p, 0, 0;\n"
      "wgmma.mma_async.sync.aligned.m64n32k16.f32.bf16.bf16 "
      "{%0, %1, %2, %3, %4, %5, %6, %7, %8, %9, %10, %11, %12, %13, %14, %15}, "
      "{%16, %17, %18, %19}, %20, p, 1, 1, 1;\n}\n"
      : "=f"(d[0]), "=f"(d[1]), "=f"(d[2]), "=f"(d[3]), "=f"(d[4]), "=f"(d[5]), "=f"(d[6]), "=f"(d[7]), "=f"(d[8]), "=f"(d[9]), "=f"(d[10]), "=f"(d[11]), "=f"(d[12]), "=f"(d[13]), "=f"(d[14]), "=f"(d[15])
      : "r"(a0), "r"(a1), "r"(a2), "r"(a3), "l"(db));
  }
}
__device__ __forceinline__ void wgmma_n40_rs_ta0_tb1(float* d, uint32_t a0, uint32_t a1, uint32_t a2, uint32_t a3, uint64_t db, bool accumulate) {
  if (accumulate) {
    asm volatile("{\n.reg .pred p;\nsetp.ne.b32 p, 1, 0;\n"
      "wgmma.mma_async.sync.aligned.m64n40k16.f32.bf16.bf16 "
      "{%0, %1, %2, %3, %4, %5, %6, %7, %8, %9, %10, %11, %12, %13, %14, %15, %16, %17, %18, %19}, "
      "{%20, %21, %22, %23}, %24, p, 1, 1, 1;\n}\n"
      : "+f"(d[0]), "+f"(d[1]), "+f"(d[2]), "+f"(d[3]), "+f"(d[4]), "+f"(d[5]), "+f"(d[6]), "+f"(d[7]), "+f"(d[8]), "+f"(d[9]), "+f"(d[10]), "+f"(d[11]), "+f"(d[12]), "+f"(d[13]), "+f"(d[14]), "+f"(d[15]), "+f"(d[16]), "+f"(d[17]), "+f"(d[18]), "+f"(d[19])
      : "r"(a0), "r"(a1), "r"(a2), "r"(a3), "l"(db));
  } else {
    asm volatile("{\n.reg .pred p;\nsetp.ne.b32 p, 0, 0;\n"
      "wgmma.mma_async.sync.aligned.m64n40k16.f32.bf16.bf16 "
      "{%0, %1, %2, %3, %4, %5, %6, %7, %8, %9, %10, %11, %12, %13, %14, %15, %16, %17, %18, %19}, "
      "{%20, %21, %22, %23}, %24, p, 1, 1, 1;\n}\n"
      : "=f"(d[0]), "=f"(d[1]), "=f"(d[2]), "=f"(d[3]), "=f"(d[4]), "=f"(d[5]), "=f"(d[6]), "=f"(d[7]), "=f"(d[8]), "=f"(d[9]), "=f"(d[10]), "=f"(d[11]), "=f"(d[12]), "=f"(d[13]), "=f"(d[14]), "=f"(d[15]), "=f"(d[16]), "=f"(d[17]), "=f"(d[18]), "=f"(d[19])
      : "r"(a0), "r"(a1), "r"(a2), "r"(a3), "l"(db));
  }
}
__device__ __forceinline__ void wgmma_n40_ss_ta1_tb1(float* d, uint64_t da, uint64_t db, bool accumulate) {
  if (accumulate) {
    asm volatile("{\n.reg .pred p;\nsetp.ne.b32 p, 1, 0;\n"
      "wgmma.mma_async.sync.aligned.m64n40k16.f32.bf16.bf16 "
      "{%0, %1, %2, %3, %4, %5, %6, %7, %8, %9, %10, %11, %12, %13, %14, %15, %16, %17, %18, %19}, "
      "%20, %21, p, 1, 1, 1, 1;\n}\n"
      : "+f"(d[0]), "+f"(d[1]), "+f"(d[2]), "+f"(d[3]), "+f"(d[4]), "+f"(d[5]), "+f"(d[6]), "+f"(d[7]), "+f"(d[8]), "+f"(d[9]), "+f"(d[10]), "+f"(d[11]), "+f"(d[12]), "+f"(d[13]), "+f"(d[14]), "+f"(d[15]), "+f"(d[16]), "+f"(d[17]), "+f"(d[18]), "+f"(d[19])
      : "l"(da), "l"(db));
  } else {
    asm volatile("{\n.reg .pred p;\nsetp.ne.b32 p, 0, 0;\n"
      "wgmma.mma_async.sync.aligned.m64n40k16.f32.bf16.bf16 "
      "{%0, %1, %2, %3, %4, %5, %6, %7, %8, %9, %10, %11, %12, %13, %14, %15, %16, %17, %18, %19}, "
      "%20, %21, p, 1, 1, 1, 1;\n}\n"
      : "=f"(d[0]), "=f"(d[1]), "=f"(d[2]), "=f"(d[3]), "=f"(d[4]), "=f"(d[5]), "=f"(d[6]), "=f"(d[7]), "=f"(d[8]), "=f"(d[9]), "=f"(d[10]), "=f"(d[11]), "=f"(d[12]), "=f"(d[13]), "=f"(d[14]), "=f"(d[15]), "=f"(d[16]), "=f"(d[17]), "=f"(d[18]), "=f"(d[19])
      : "l"(da), "l"(db));
  }
}
__device__ __forceinline__ void wgmma_n128_rs_ta0_tb1(float* d, uint32_t a0, uint32_t a1, uint32_t a2, uint32_t a3, uint64_t db, bool accumulate) {
  if (accumulate) {
    asm volatile("{\n.reg .pred p;\nsetp.ne.b32 p, 1, 0;\n"
      "wgmma.mma_async.sync.aligned.m64n128k16.f32.bf16.bf16 "
      "{%0, %1, %2, %3, %4, %5, %6, %7, %8, %9, %10, %11, %12, %13, %14, %15, %16, %17, %18, %19, %20, %21, %22, %23, %24, %25, %26, %27, %28, %29, %30, %31, %32, %33, %34, %35, %36, %37, %38, %39, %40, %41, %42, %43, %44, %45, %46, %47, %48, %49, %50, %51, %52, %53, %54, %55, %56, %57, %58, %59, %60, %61, %62, %63}, "
      "{%64, %65, %66, %67}, %68, p, 1, 1, 1;\n}\n"
      : "+f"(d[0]), "+f"(d[1]), "+f"(d[2]), "+f"(d[3]), "+f"(d[4]), "+f"(d[5]), "+f"(d[6]), "+f"(d[7]), "+f"(d[8]), "+f"(d[9]), "+f"(d[10]), "+f"(d[11]), "+f"(d[12]), "+f"(d[13]), "+f"(d[14]), "+f"(d[15]), "+f"(d[16]), "+f"(d[17]), "+f"(d[18]), "+f"(d[19]), "+f"(d[20]), "+f"(d[21]), "+f"(d[22]), "+f"(d[23]), "+f"(d[24]), "+f"(d[25]), "+f"(d[26]), "+f"(d[27]), "+f"(d[28]), "+f"(d[29]), "+f"(d[30]), "+f"(d[31]), "+f"(d[32]), "+f"(d[33]), "+f"(d[34]), "+f"(d[35]), "+f"(d[36]), "+f"(d[37]), "+f"(d[38]), "+f"(d[39]), "+f"(d[40]), "+f"(d[41]), "+f"(d[42]), "+f"(d[43]), "+f"(d[44]), "+f"(d[45]), "+f"(d[46]), "+f"(d[47]), "+f"(d[48]), "+f"(d[49]), "+f"(d[50]), "+f"(d[51]), "+f"(d[52]), "+f"(d[53]), "+f"(d[54]), "+f"(d[55]), "+f"(d[56]), "+f"(d[57]), "+f"(d[58]), "+f"(d[59]), "+f"(d[60]), "+f"(d[61]), "+f"(d[62]), "+f"(d[63])
      : "r"(a0), "r"(a1), "r"(a2), "r"(a3), "l"(db));
  } else {
    asm volatile("{\n.reg .pred p;\nsetp.ne.b32 p, 0, 0;\n"
      "wgmma.mma_async.sync.aligned.m64n128k16.f32.bf16.bf16 "
      "{%0, %1, %2, %3, %4, %5, %6, %7, %8, %9, %10, %11, %12, %13, %14, %15, %16, %17, %18, %19, %20, %21, %22, %23, %24, %25, %26, %27, %28, %29, %30, %31, %32, %33, %34, %35, %36, %37, %38, %39, %40, %41, %42, %43, %44, %45, %46, %47, %48, %49, %50, %51, %52, %53, %54, %55, %56, %57, %58, %59, %60, %61, %62, %63}, "
      "{%64, %65, %66, %67}, %68, p, 1, 1, 1;\n}\n"
      : "=f"(d[0]), "=f"(d[1]), "=f"(d[2]), "=f"(d[3]), "=f"(d[4]), "=f"(d[5]), "=f"(d[6]), "=f"(d[7]), "=f"(d[8]), "=f"(d[9]), "=f"(d[10]), "=f"(d[11]), "=f"(d[12]), "=f"(d[13]), "=f"(d[14]), "=f"(d[15]), "=f"(d[16]), "=f"(d[17]), "=f"(d[18]), "=f"(d[19]), "=f"(d[20]), "=f"(d[21]), "=f"(d[22]), "=f"(d[23]), "=f"(d[24]), "=f"(d[25]), "=f"(d[26]), "=f"(d[27]), "=f"(d[28]), "=f"(d[29]), "=f"(d[30]), "=f"(d[31]), "=f"(d[32]), "=f"(d[33]), "=f"(d[34]), "=f"(d[35]), "=f"(d[36]), "=f"(d[37]), "=f"(d[38]), "=f"(d[39]), "=f"(d[40]), "=f"(d[41]), "=f"(d[42]), "=f"(d[43]), "=f"(d[44]), "=f"(d[45]), "=f"(d[46]), "=f"(d[47]), "=f"(d[48]), "=f"(d[49]), "=f"(d[50]), "=f"(d[51]), "=f"(d[52]), "=f"(d[53]), "=f"(d[54]), "=f"(d[55]), "=f"(d[56]), "=f"(d[57]), "=f"(d[58]), "=f"(d[59]), "=f"(d[60]), "=f"(d[61]), "=f"(d[62]), "=f"(d[63])
      : "r"(a0), "r"(a1), "r"(a2), "r"(a3), "l"(db));
  }
}
__device__ __forceinline__ void wgmma_n128_ss_ta0_tb1(float* d, uint64_t da, uint64_t db, bool accumulate) {
  if (accumulate) {
    asm volatile("{\n.reg .pred p;\nsetp.ne.b32 p, 1, 0;\n"
      "wgmma.mma_async.sync.aligned.m64n128k16.f32.bf16.bf16 "
      "{%0, %1, %2, %3, %4, %5, %6, %7, %8, %9, %10, %11, %12, %13, %14, %15, %16, %17, %18, %19, %20, %21, %22, %23, %24, %25, %26, %27, %28, %29, %30, %31, %32, %33, %34, %35, %36, %37, %38, %39, %40, %41, %42, %43, %44, %45, %46, %47, %48, %49, %50, %51, %52, %53, %54, %55, %56, %57, %58, %59, %60, %61, %62, %63}, "
      "%64, %65, p, 1, 1, 0, 1;\n}\n"
      : "+f"(d[0]), "+f"(d[1]), "+f"(d[2]), "+f"(d[3]), "+f"(d[4]), "+f"(d[5]), "+f"(d[6]), "+f"(d[7]), "+f"(d[8]), "+f"(d[9]), "+f"(d[10]), "+f"(d[11]), "+f"(d[12]), "+f"(d[13]), "+f"(d[14]), "+f"(d[15]), "+f"(d[16]), "+f"(d[17]), "+f"(d[18]), "+f"(d[19]), "+f"(d[20]), "+f"(d[21]), "+f"(d[22]), "+f"(d[23]), "+f"(d[24]), "+f"(d[25]), "+f"(d[26]), "+f"(d[27]), "+f"(d[28]), "+f"(d[29]), "+f"(d[30]), "+f"(d[31]), "+f"(d[32]), "+f"(d[33]), "+f"(d[34]), "+f"(d[35]), "+f"(d[36]), "+f"(d[37]), "+f"(d[38]), "+f"(d[39]), "+f"(d[40]), "+f"(d[41]), "+f"(d[42]), "+f"(d[43]), "+f"(d[44]), "+f"(d[45]), "+f"(d[46]), "+f"(d[47]), "+f"(d[48]), "+f"(d[49]), "+f"(d[50]), "+f"(d[51]), "+f"(d[52]), "+f"(d[53]), "+f"(d[54]), "+f"(d[55]), "+f"(d[56]), "+f"(d[57]), "+f"(d[58]), "+f"(d[59]), "+f"(d[60]), "+f"(d[61]), "+f"(d[62]), "+f"(d[63])
      : "l"(da), "l"(db));
  } else {
    asm volatile("{\n.reg .pred p;\nsetp.ne.b32 p, 0, 0;\n"
      "wgmma.mma_async.sync.aligned.m64n128k16.f32.bf16.bf16 "
      "{%0, %1, %2, %3, %4, %5, %6, %7, %8, %9, %10, %11, %12, %13, %14, %15, %16, %17, %18, %19, %20, %21, %22, %23, %24, %25, %26, %27, %28, %29, %30, %31, %32, %33, %34, %35, %36, %37, %38, %39, %40, %41, %42, %43, %44, %45, %46, %47, %48, %49, %50, %51, %52, %53, %54, %55, %56, %57, %58, %59, %60, %61, %62, %63}, "
      "%64, %65, p, 1, 1, 0, 1;\n}\n"
      : "=f"(d[0]), "=f"(d[1]), "=f"(d[2]), "=f"(d[3]), "=f"(d[4]), "=f"(d[5]), "=f"(d[6]), "=f"(d[7]), "=f"(d[8]), "=f"(d[9]), "=f"(d[10]), "=f"(d[11]), "=f"(d[12]), "=f"(d[13]), "=f"(d[14]), "=f"(d[15]), "=f"(d[16]), "=f"(d[17]), "=f"(d[18]), "=f"(d[19]), "=f"(d[20]), "=f"(d[21]), "=f"(d[22]), "=f"(d[23]), "=f"(d[24]), "=f"(d[25]), "=f"(d[26]), "=f"(d[27]), "=f"(d[28]), "=f"(d[29]), "=f"(d[30]), "=f"(d[31]), "=f"(d[32]), "=f"(d[33]), "=f"(d[34]), "=f"(d[35]), "=f"(d[36]), "=f"(d[37]), "=f"(d[38]), "=f"(d[39]), "=f"(d[40]), "=f"(d[41]), "=f"(d[42]), "=f"(d[43]), "=f"(d[44]), "=f"(d[45]), "=f"(d[46]), "=f"(d[47]), "=f"(d[48]), "=f"(d[49]), "=f"(d[50]), "=f"(d[51]), "=f"(d[52]), "=f"(d[53]), "=f"(d[54]), "=f"(d[55]), "=f"(d[56]), "=f"(d[57]), "=f"(d[58]), "=f"(d[59]), "=f"(d[60]), "=f"(d[61]), "=f"(d[62]), "=f"(d[63])
      : "l"(da), "l"(db));
  }
}
__device__ __forceinline__ void wgmma_n256_rs_ta0_tb1(float* d, uint32_t a0, uint32_t a1, uint32_t a2, uint32_t a3, uint64_t db, bool accumulate) {
  if (accumulate) {
    asm volatile("{\n.reg .pred p;\nsetp.ne.b32 p, 1, 0;\n"
      "wgmma.mma_async.sync.aligned.m64n256k16.f32.bf16.bf16 "
      "{%0, %1, %2, %3, %4, %5, %6, %7, %8, %9, %10, %11, %12, %13, %14, %15, %16, %17, %18, %19, %20, %21, %22, %23, %24, %25, %26, %27, %28, %29, %30, %31, %32, %33, %34, %35, %36, %37, %38, %39, %40, %41, %42, %43, %44, %45, %46, %47, %48, %49, %50, %51, %52, %53, %54, %55, %56, %57, %58, %59, %60, %61, %62, %63, %64, %65, %66, %67, %68, %69, %70, %71, %72, %73, %74, %75, %76, %77, %78, %79, %80, %81, %82, %83, %84, %85, %86, %87, %88, %89, %90, %91, %92, %93, %94, %95, %96, %97, %98, %99, %100, %101, %102, %103, %104, %105, %106, %107, %108, %109, %110, %111, %112, %113, %114, %115, %116, %117, %118, %119, %120, %121, %122, %123, %124, %125, %126, %127}, "
      "{%128, %129, %130, %131}, %132, p, 1, 1, 1;\n}\n"
      : "+f"(d[0]), "+f"(d[1]), "+f"(d[2]), "+f"(d[3]), "+f"(d[4]), "+f"(d[5]), "+f"(d[6]), "+f"(d[7]), "+f"(d[8]), "+f"(d[9]), "+f"(d[10]), "+f"(d[11]), "+f"(d[12]), "+f"(d[13]), "+f"(d[14]), "+f"(d[15]), "+f"(d[16]), "+f"(d[17]), "+f"(d[18]), "+f"(d[19]), "+f"(d[20]), "+f"(d[21]), "+f"(d[22]), "+f"(d[23]), "+f"(d[24]), "+f"(d[25]), "+f"(d[26]), "+f"(d[27]), "+f"(d[28]), "+f"(d[29]), "+f"(d[30]), "+f"(d[31]), "+f"(d[32]), "+f"(d[33]), "+f"(d[34]), "+f"(d[35]), "+f"(d[36]), "+f"(d[37]), "+f"(d[38]), "+f"(d[39]), "+f"(d[40]), "+f"(d[41]), "+f"(d[42]), "+f"(d[43]), "+f"(d[44]), "+f"(d[45]), "+f"(d[46]), "+f"(d[47]), "+f"(d[48]), "+f"(d[49]), "+f"(d[50]), "+f"(d[51]), "+f"(d[52]), "+f"(d[53]), "+f"(d[54]), "+f"(d[55]), "+f"(d[56]), "+f"(d[57]), "+f"(d[58]), "+f"(d[59]), "+f"(d[60]), "+f"(d[61]), "+f"(d[62]), "+f"(d[63]), "+f"(d[64]), "+f"(d[65]), "+f"(d[66]), "+f"(d[67]), "+f"(d[68]), "+f"(d[69]), "+f"(d[70]), "+f"(d[71]), "+f"(d[72]), "+f"(d[73]), "+f"(d[74]), "+f"(d[75]), "+f"(d[76]), "+f"(d[77]), "+f"(d[78]), "+f"(d[79]), "+f"(d[80]), "+f"(d[81]), "+f"(d[82]), "+f"(d[83]), "+f"(d[84]), "+f"(d[85]), "+f"(d[86]), "+f"(d[87]), "+f"(d[88]), "+f"(d[89]), "+f"(d[90]), "+f"(d[91]), "+f"(d[92]), "+f"(d[93]), "+f"(d[94]), "+f"(d[95]), "+f"(d[96]), "+f"(d[97]), "+f"(d[98]), "+f"(d[99]), "+f"(d[100]), "+f"(d[101]), "+f"(d[102]), "+f"(d[103]), "+f"(d[104]), "+f"(d[105]), "+f"(d[106]), "+f"(d[107]), "+f"(d[108]), "+f"(d[109]), "+f"(d[110]), "+f"(d[111]), "+f"(d[112]), "+f"(d[113]), "+f"(d[114]), "+f"(d[115]), "+f"(d[116]), "+f"(d[117]), "+f"(d[118]), "+f"(d[119]), "+f"(d[120]), "+f"(d[121]), "+f"(d[122]), "+f"(d[123]), "+f"(d[124]), "+f"(d[125]), "+f"(d[126]), "+f"(d[127])
      : "r"(a0), "r"(a1), "r"(a2), "r"(a3), "l"(db));
  } else {
    asm volatile("{\n.reg .pred p;\nsetp.ne.b32 p, 0, 0;\n"
      "wgmma.mma_async.sync.aligned.m64n256k16.f32.bf16.bf16 "
      "{%0, %1, %2, %3, %4, %5, %6, %7, %8, %9, %10, %11, %12, %13, %14, %15, %16, %17, %18, %19, %20, %21, %22, %23, %24, %25, %26, %27, %28, %29, %30, %31, %32, %33, %34, %35, %36, %37, %38, %39, %40, %41, %42, %43, %44, %45, %46, %47, %48, %49, %50, %51, %52, %53, %54, %55, %56, %57, %58, %59, %60, %61, %62, %63, %64, %65, %66, %67, %68, %69, %70, %71, %72, %73, %74, %75, %76, %77, %78, %79, %80, %81, %82, %83, %84, %85, %86, %87, %88, %89, %90, %91, %92, %93, %94, %95, %96, %97, %98, %99, %100, %101, %102, %103, %104, %105, %106, %107, %108, %109, %110, %111, %112, %113, %114, %115, %116, %117, %118, %119, %120, %121, %122, %123, %124, %125, %126, %127}, "
      "{%128, %129, %130, %131}, %132, p, 1, 1, 1;\n}\n"
      : "=f"(d[0]), "=f"(d[1]), "=f"(d[2]), "=f"(d[3]), "=f"(d[4]), "=f"(d[5]), "=f"(d[6]), "=f"(d[7]), "=f"(d[8]), "=f"(d[9]), "=f"(d[10]), "=f"(d[11]), "=f"(d[12]), "=f"(d[13]), "=f"(d[14]), "=f"(d[15]), "=f"(d[16]), "=f"(d[17]), "=f"(d[18]), "=f"(d[19]), "=f"(d[20]), "=f"(d[21]), "=f"(d[22]), "=f"(d[23]), "=f"(d[24]), "=f"(d[25]), "=f"(d[26]), "=f"(d[27]), "=f"(d[28]), "=f"(d[29]), "=f"(d[30]), "=f"(d[31]), "=f"(d[32]), "=f"(d[33]), "=f"(d[34]), "=f"(d[35]), "=f"(d[36]), "=f"(d[37]), "=f"(d[38]), "=f"(d[39]), "=f"(d[40]), "=f"(d[41]), "=f"(d[42]), "=f"(d[43]), "=f"(d[44]), "=f"(d[45]), "=f"(d[46]), "=f"(d[47]), "=f"(d[48]), "=f"(d[49]), "=f"(d[50]), "=f"(d[51]), "=f"(d[52]), "=f"(d[53]), "=f"(d[54]), "=f"(d[55]), "=f"(d[56]), "=f"(d[57]), "=f"(d[58]), "=f"(d[59]), "=f"(d[60]), "=f"(d[61]), "=f"(d[62]), "=f"(d[63]), "=f"(d[64]), "=f"(d[65]), "=f"(d[66]), "=f"(d[67]), "=f"(d[68]), "=f"(d[69]), "=f"(d[70]), "=f"(d[71]), "=f"(d[72]), "=f"(d[73]), "=f"(d[74]), "=f"(d[75]), "=f"(d[76]), "=f"(d[77]), "=f"(d[78]), "=f"(d[79]), "=f"(d[80]), "=f"(d[81]), "=f"(d[82]), "=f"(d[83]), "=f"(d[84]), "=f"(d[85]), "=f"(d[86]), "=f"(d[87]), "=f"(d[88]), "=f"(d[89]), "=f"(d[90]), "=f"(d[91]), "=f"(d[92]), "=f"(d[93]), "=f"(d[94]), "=f"(d[95]), "=f"(d[96]), "=f"(d[97]), "=f"(d[98]), "=f"(d[99]), "=f"(d[100]), "=f"(d[101]), "=f"(d[102]), "=f"(d[103]), "=f"(d[104]), "=f"(d[105]), "=f"(d[106]), "=f"(d[107]), "=f"(d[108]), "=f"(d[109]), "=f"(d[110]), "=f"(d[111]), "=f"(d[112]), "=f"(d[113]), "=f"(d[114]), "=f"(d[115]), "=f"(d[116]), "=f"(d[117]), "=f"(d[118]), "=f"(d[119]), "=f"(d[120]), "=f"(d[121]), "=f"(d[122]), "=f"(d[123]), "=f"(d[124]), "=f"(d[125]), "=f"(d[126]), "=f"(d[127])
      : "r"(a0), "r"(a1), "r"(a2), "r"(a3), "l"(db));
  }
}
__device__ __forceinline__ void wgmma_n256_ss_ta0_tb1(float* d, uint64_t da, uint64_t db, bool accumulate) {
  if (accumulate) {
    asm volatile("{\n.reg .pred p;\nsetp.ne.b32 p, 1, 0;\n"
      "wgmma.mma_async.sync.aligned.m64n256k16.f32.bf16.bf16 "
      "{%0, %1, %2, %3, %4, %5, %6, %7, %8, %9, %10, %11, %12, %13, %14, %15, %16, %17, %18, %19, %20, %21, %22, %23, %24, %25, %26, %27, %28, %29, %30, %31, %32, %33, %34, %35, %36, %37, %38, %39, %40, %41, %42, %43, %44, %45, %46, %47, %48, %49, %50, %51, %52, %53, %54, %55, %56, %57, %58, %59, %60, %61, %62, %63, %64, %65, %66, %67, %68, %69, %70, %71, %72, %73, %74, %75, %76, %77, %78, %79, %80, %81, %82, %83, %84, %85, %86, %87, %88, %89, %90, %91, %92, %93, %94, %95, %96, %97, %98, %99, %100, %101, %102, %103, %104, %105, %106, %107, %108, %109, %110, %111, %112, %113, %114, %115, %116, %117, %118, %119, %120, %121, %122, %123, %124, %125, %126, %127}, "
      "%128, %129, p, 1, 1, 0, 1;\n}\n"
      : "+f"(d[0]), "+f"(d[1]), "+f"(d[2]), "+f"(d[3]), "+f"(d[4]), "+f"(d[5]), "+f"(d[6]), "+f"(d[7]), "+f"(d[8]), "+f"(d[9]), "+f"(d[10]), "+f"(d[11]), "+f"(d[12]), "+f"(d[13]), "+f"(d[14]), "+f"(d[15]), "+f"(d[16]), "+f"(d[17]), "+f"(d[18]), "+f"(d[19]), "+f"(d[20]), "+f"(d[21]), "+f"(d[22]), "+f"(d[23]), "+f"(d[24]), "+f"(d[25]), "+f"(d[26]), "+f"(d[27]), "+f"(d[28]), "+f"(d[29]), "+f"(d[30]), "+f"(d[31]), "+f"(d[32]), "+f"(d[33]), "+f"(d[34]), "+f"(d[35]), "+f"(d[36]), "+f"(d[37]), "+f"(d[38]), "+f"(d[39]), "+f"(d[40]), "+f"(d[41]), "+f"(d[42]), "+f"(d[43]), "+f"(d[44]), "+f"(d[45]), "+f"(d[46]), "+f"(d[47]), "+f"(d[48]), "+f"(d[49]), "+f"(d[50]), "+f"(d[51]), "+f"(d[52]), "+f"(d[53]), "+f"(d[54]), "+f"(d[55]), "+f"(d[56]), "+f"(d[57]), "+f"(d[58]), "+f"(d[59]), "+f"(d[60]), "+f"(d[61]), "+f"(d[62]), "+f"(d[63]), "+f"(d[64]), "+f"(d[65]), "+f"(d[66]), "+f"(d[67]), "+f"(d[68]), "+f"(d[69]), "+f"(d[70]), "+f"(d[71]), "+f"(d[72]), "+f"(d[73]), "+f"(d[74]), "+f"(d[75]), "+f"(d[76]), "+f"(d[77]), "+f"(d[78]), "+f"(d[79]), "+f"(d[80]), "+f"(d[81]), "+f"(d[82]), "+f"(d[83]), "+f"(d[84]), "+f"(d[85]), "+f"(d[86]), "+f"(d[87]), "+f"(d[88]), "+f"(d[89]), "+f"(d[90]), "+f"(d[91]), "+f"(d[92]), "+f"(d[93]), "+f"(d[94]), "+f"(d[95]), "+f"(d[96]), "+f"(d[97]), "+f"(d[98]), "+f"(d[99]), "+f"(d[100]), "+f"(d[101]), "+f"(d[102]), "+f"(d[103]), "+f"(d[104]), "+f"(d[105]), "+f"(d[106]), "+f"(d[107]), "+f"(d[108]), "+f"(d[109]), "+f"(d[110]), "+f"(d[111]), "+f"(d[112]), "+f"(d[113]), "+f"(d[114]), "+f"(d[115]), "+f"(d[116]), "+f"(d[117]), "+f"(d[118]), "+f"(d[119]), "+f"(d[120]), "+f"(d[121]), "+f"(d[122]), "+f"(d[123]), "+f"(d[124]), "+f"(d[125]), "+f"(d[126]), "+f"(d[127])
      : "l"(da), "l"(db));
  } else {
    asm volatile("{\n.reg .pred p;\nsetp.ne.b32 p, 0, 0;\n"
      "wgmma.mma_async.sync.aligned.m64n256k16.f32.bf16.bf16 "
      "{%0, %1, %2, %3, %4, %5, %6, %7, %8, %9, %10, %11, %12, %13, %14, %15, %16, %17, %18, %19, %20, %21, %22, %23, %24, %25, %26, %27, %28, %29, %30, %31, %32, %33, %34, %35, %36, %37, %38, %39, %40, %41, %42, %43, %44, %45, %46, %47, %48, %49, %50, %51, %52, %53, %54, %55, %56, %57, %58, %59, %60, %61, %62, %63, %64, %65, %66, %67, %68, %69, %70, %71, %72, %73, %74, %75, %76, %77, %78, %79, %80, %81, %82, %83, %84, %85, %86, %87, %88, %89, %90, %91, %92, %93, %94, %95, %96, %97, %98, %99, %100, %101, %102, %103, %104, %105, %106, %107, %108, %109, %110, %111, %112, %113, %114, %115, %116, %117, %118, %119, %120, %121, %122, %123, %124, %125, %126, %127}, "
      "%128, %129, p, 1, 1, 0, 1;\n}\n"
      : "=f"(d[0]), "=f"(d[1]), "=f"(d[2]), "=f"(d[3]), "=f"(d[4]), "=f"(d[5]), "=f"(d[6]), "=f"(d[7]), "=f"(d[8]), "=f"(d[9]), "=f"(d[10]), "=f"(d[11]), "=f"(d[12]), "=f"(d[13]), "=f"(d[14]), "=f"(d[15]), "=f"(d[16]), "=f"(d[17]), "=f"(d[18]), "=f"(d[19]), "=f"(d[20]), "=f"(d[21]), "=f"(d[22]), "=f"(d[23]), "=f"(d[24]), "=f"(d[25]), "=f"(d[26]), "=f"(d[27]), "=f"(d[28]), "=f"(d[29]), "=f"(d[30]), "=f"(d[31]), "=f"(d[32]), "=f"(d[33]), "=f"(d[34]), "=f"(d[35]), "=f"(d[36]), "=f"(d[37]), "=f"(d[38]), "=f"(d[39]), "=f"(d[40]), "=f"(d[41]), "=f"(d[42]), "=f"(d[43]), "=f"(d[44]), "=f"(d[45]), "=f"(d[46]), "=f"(d[47]), "=f"(d[48]), "=f"(d[49]), "=f"(d[50]), "=f"(d[51]), "=f"(d[52]), "=f"(d[53]), "=f"(d[54]), "=f"(d[55]), "=f"(d[56]), "=f"(d[57]), "=f"(d[58]), "=f"(d[59]), "=f"(d[60]), "=f"(d[61]), "=f"(d[62]), "=f"(d[63]), "=f"(d[64]), "=f"(d[65]), "=f"(d[66]), "=f"(d[67]), "=f"(d[68]), "=f"(d[69]), "=f"(d[70]), "=f"(d[71]), "=f"(d[72]), "=f"(d[73]), "=f"(d[74]), "=f"(d[75]), "=f"(d[76]), "=f"(d[77]), "=f"(d[78]), "=f"(d[79]), "=f"(d[80]), "=f"(d[81]), "=f"(d[82]), "=f"(d[83]), "=f"(d[84]), "=f"(d[85]), "=f"(d[86]), "=f"(d[87]), "=f"(d[88]), "=f"(d[89]), "=f"(d[90]), "=f"(d[91]), "=f"(d[92]), "=f"(d[93]), "=f"(d[94]), "=f"(d[95]), "=f"(d[96]), "=f"(d[97]), "=f"(d[98]), "=f"(d[99]), "=f"(d[100]), "=f"(d[101]), "=f"(d[102]), "=f"(d[103]), "=f"(d[104]), "=f"(d[105]), "=f"(d[106]), "=f"(d[107]), "=f"(d[108]), "=f"(d[109]), "=f"(d[110]), "=f"(d[111]), "=f"(d[112]), "=f"(d[113]), "=f"(d[114]), "=f"(d[115]), "=f"(d[116]), "=f"(d[117]), "=f"(d[118]), "=f"(d[119]), "=f"(d[120]), "=f"(d[121]), "=f"(d[122]), "=f"(d[123]), "=f"(d[124]), "=f"(d[125]), "=f"(d[126]), "=f"(d[127])
      : "l"(da), "l"(db));
  }
}
__device__ __forceinline__ void wgmma_n256_ssp_ta0_tb1(float* d, uint64_t da, uint64_t db, int accumulate) {
    asm volatile("{\n.reg .pred p;\nsetp.ne.b32 p, %130, 0;\n"
      "wgmma.mma_async.sync.aligned.m64n256k16.f32.bf16.bf16 "
      "{%0, %1, %2, %3, %4, %5, %6, %7, %8, %9, %10, %11, %12, %13, %14, %15, %16, %17, %18, %19, %20, %21, %22, %23, %24, %25, %26, %27, %28, %29, %30, %31, %32, %33, %34, %35, %36, %37, %38, %39, %40, %41, %42, %43, %44, %45, %46, %47, %48, %49, %50, %51, %52, %53, %54, %55, %56, %57, %58, %59, %60, %61, %62, %63, %64, %65, %66, %67, %68, %69, %70, %71, %72, %73, %74, %75, %76, %77, %78, %79, %80, %81, %82, %83, %84, %85, %86, %87, %88, %89, %90, %91, %92, %93, %94, %95, %96, %97, %98, %99, %100, %101, %102, %103, %104, %105, %106, %107, %108, %109, %110, %111, %112, %113, %114, %115, %116, %117, %118, %119, %120, %121, %122, %123, %124, %125, %126, %127}, "
      "%128, %129, p, 1, 1, 0, 1;\n}\n"
      : "+f"(d[0]), "+f"(d[1]), "+f"(d[2]), "+f"(d[3]), "+f"(d[4]), "+f"(d[5]), "+f"(d[6]), "+f"(d[7]), "+f"(d[8]), "+f"(d[9]), "+f"(d[10]), "+f"(d[11]), "+f"(d[12]), "+f"(d[13]), "+f"(d[14]), "+f"(d[15]), "+f"(d[16]), "+f"(d[17]), "+f"(d[18]), "+f"(d[19]), "+f"(d[20]), "+f"(d[21]), "+f"(d[22]), "+f"(d[23]), "+f"(d[24]), "+f"(d[25]), "+f"(d[26]), "+f"(d[27]), "+f"(d[28]), "+f"(d[29]), "+f"(d[30]), "+f"(d[31]), "+f"(d[32]), "+f"(d[33]), "+f"(d[34]), "+f"(d[35]), "+f"(d[36]), "+f"(d[37]), "+f"(d[38]), "+f"(d[39]), "+f"(d[40]), "+f"(d[41]), "+f"(d[42]), "+f"(d[43]), "+f"(d[44]), "+f"(d[45]), "+f"(d[46]), "+f"(d[47]), "+f"(d[48]), "+f"(d[49]), "+f"(d[50]), "+f"(d[51]), "+f"(d[52]), "+f"(d[53]), "+f"(d[54]), "+f"(d[55]), "+f"(d[56]), "+f"(d[57]), "+f"(d[58]), "+f"(d[59]), "+f"(d[60]), "+f"(d[61]), "+f"(d[62]), "+f"(d[63]), "+f"(d[64]), "+f"(d[65]), "+f"(d[66]), "+f"(d[67]), "+f"(d[68]), "+f"(d[69]), "+f"(d[70]), "+f"(d[71]), "+f"(d[72]), "+f"(d[73]), "+f"(d[74]), "+f"(d[75]), "+f"(d[76]), "+f"(d[77]), "+f"(d[78]), "+f"(d[79]), "+f"(d[80]), "+f"(d[81]), "+f"(d[82]), "+f"(d[83]), "+f"(d[84]), "+f"(d[85]), "+f"(d[86]), "+f"(d[87]), "+f"(d[88]), "+f"(d[89]), "+f"(d[90]), "+f"(d[91]), "+f"(d[92]), "+f"(d[93]), "+f"(d[94]), "+f"(d[95]), "+f"(d[96]), "+f"(d[97]), "+f"(d[98]), "+f"(d[99]), "+f"(d[100]), "+f"(d[101]), "+f"(d[102]), "+f"(d[103]), "+f"(d[104]), "+f"(d[105]), "+f"(d[106]), "+f"(d[107]), "+f"(d[108]), "+f"(d[109]), "+f"(d[110]), "+f"(d[111]), "+f"(d[112]), "+f"(d[113]), "+f"(d[114]), "+f"(d[115]), "+f"(d[116]), "+f"(d[117]), "+f"(d[118]), "+f"(d[119]), "+f"(d[120]), "+f"(d[121]), "+f"(d[122]), "+f"(d[123]), "+f"(d[124]), "+f"(d[125]), "+f"(d[126]), "+f"(d[127])
      : "l"(da), "l"(db), "r"(accumulate));
}

template <int N> __device__ __forceinline__ void quad_sum(float* m) {
#pragma unroll
  for (int o = 1; o <= 2; o <<= 1) {
    float t[N];
#pragma unroll
    for (int i = 0; i < N; i++) t[i] = __shfl_xor_sync(~0u, m[i], o);
#pragma unroll
    for (int i = 0; i < N; i++) m[i] += t[i];
  }
}
__device__ __forceinline__ bool softmax_unsafe(const uint32_t* t, float l0, float l1) {
  const float m0 = fmaxf(bf_lo(t[0]) + bf_hi(t[0]), bf_lo(t[2]) + bf_hi(t[2])), m1 = fmaxf(bf_lo(t[1]) + bf_hi(t[1]), bf_lo(t[3]) + bf_hi(t[3]));
  return __any_sync(~0u, !(m0 * l0 < 2500.f) | !(m1 * l1 < 2500.f));
}
__device__ __forceinline__ void softmax_shift(float* p, float c0, float c1) {
#pragma unroll 1
  for (int it = 0; it < 8; it++) {
    float mx = p[0], mn = p[0];
#pragma unroll
    for (int j = 1; j < 8; j++) { mx = fmaxf(mx, p[(j >> 1) * 4 + (j & 1)]); mn = fminf(mn, p[(j >> 1) * 4 + (j & 1)]); }
#pragma unroll
    for (int o = 1; o <= 2; o <<= 1) { mx = fmaxf(mx, __shfl_xor_sync(~0u, mx, o)); mn = fminf(mn, __shfl_xor_sync(~0u, mn, o)); }
    const float half = fminf(0.5f * (mx - mn), 50.f * rcp(it & 1 ? c1 : c0));
    float r[8];
#pragma unroll
    for (int j = 0; j < 8; j++) {
      const float v = p[(j >> 1) * 4 + (j & 1)];
      r[j] = fmaxf(v - mx + half, 0.f) + fminf(v - mn - half, 0.f) + (v - v);
    }
#pragma unroll
    for (int k = 0; k < 7; k++)
#pragma unroll
      for (int j = 0; j < 8; j++) p[(k >> 1) * 16 + (k & 1) * 2 + (j >> 1) * 4 + (j & 1)] = p[((k + 1) >> 1) * 16 + ((k + 1) & 1) * 2 + (j >> 1) * 4 + (j & 1)];
#pragma unroll
    for (int j = 0; j < 8; j++) p[50 + (j >> 1) * 4 + (j & 1)] = r[j];
  }
}
template <int J0 = 0, int J1 = 8> __device__ __forceinline__ void k_exp(const float* p, float c0, float c1, float* e, float* s) {
#pragma unroll
  for (int j = J0; j < J1; j++) {
    e[2 * j] = ex2(p[2 * j] * (j & 1 ? c1 : c0));
    e[2 * j + 1] = ex2(p[2 * j + 1] * (j & 1 ? c1 : c0));
    e[16 + j] = rcp(e[2 * j] * e[2 * j + 1]);
    const float t = e[2 * j] + e[2 * j + 1];
    s[j & 1] = j < 2 ? t : s[j & 1] + t;
    s[2 + (j & 1)] = j < 2 ? e[16 + j] * t : fmaf(e[16 + j], t, s[2 + (j & 1)]);
  }
}
template <int J0 = 0, int J1 = 8> __device__ __forceinline__ void q_exp(const float* p, float c0, float c1, uint32_t* f) {
#pragma unroll
  for (int j = J0; j < J1; j++) {
    const float e0 = ex2(p[2 * j] * (j & 1 ? c1 : c0)), e1 = ex2(p[2 * j + 1] * (j & 1 ? c1 : c0)), r = rcp(e0 * e1);
    f[j] = pack2(e0, e1);
    f[8 + j] = bmul2(f[j], pack2(r, r));
  }
}

#define FMA8(A, U, X)                                                                                        \
  A[0] = fmaf(bf_lo(U.x), X, A[0]); A[1] = fmaf(bf_hi(U.x), X, A[1]); A[2] = fmaf(bf_lo(U.y), X, A[2]); A[3] = fmaf(bf_hi(U.y), X, A[3]); \
  A[4] = fmaf(bf_lo(U.z), X, A[4]); A[5] = fmaf(bf_hi(U.z), X, A[5]); A[6] = fmaf(bf_lo(U.w), X, A[6]); A[7] = fmaf(bf_hi(U.w), X, A[7])

__device__ __forceinline__ uint32_t routed_row(const __nv_bfloat16* x, uint32_t tag, int lane, uint4* xr) {
  uint32_t best = 0, sv = 0;
#pragma unroll 1
  for (int it = 0; it < SPIN_MAX; it++) {
    const uint4 h = ld_rlx128(g_ycnt + 32);
    best = h.x;
    if (__all_sync(~0u, (int)(h.z - tag * NCTA) >= 0)) break;
    __nanosleep(AM_NS);
  }
#pragma unroll 1
  for (int it = 0; it < SPIN_MAX; it++) {
    const int sel = 2047 - (best & 0x7ff);
#pragma unroll
    for (int i = 0; i < 4; i++) xr[i] = ldg_nc(x + (size_t)sel * DM + i * 256 + lane * 8);
    const unsigned long long st = ld_rlx64(g_stat + sel);
    const uint4 b0 = ld_rlx128(g_best + lane * 2), b1 = ld_rlx128(g_best + 64 + lane * 2);
    const uint32_t m = __reduce_max_sync(~0u, max(max(b0.x, b0.z), max(b1.x, b1.z)));
    sv = (uint32_t)st;
    if (__all_sync(~0u, b0.y == tag && b0.w == tag && b1.y == tag && b1.w == tag && m == best && (uint32_t)(st >> 32) == tag)) break;
    best = m;
  }
  const uint32_t m2 = (sv & 0xffff0000u) | (sv >> 16);
  const float rs = rcp(bf_lo(sv));
#pragma unroll
  for (int i = 0; i < 4; i++) {
    const uint32_t d0 = bsub2(xr[i].x, m2), d1 = bsub2(xr[i].y, m2), d2 = bsub2(xr[i].z, m2), d3 = bsub2(xr[i].w, m2);
    xr[i] = make_uint4(pack2(bf_lo(d0) * rs, bf_hi(d0) * rs), pack2(bf_lo(d1) * rs, bf_hi(d1) * rs), pack2(bf_lo(d2) * rs, bf_hi(d2) * rs),
                       pack2(bf_lo(d3) * rs, bf_hi(d3) * rs));
  }
  return best;
}

struct Params {
  const __nv_bfloat16 *x, *wqkv, *wo, *w_r, *w_gate, *w_up, *w_down;
  int by_sm;
};

__global__ void __launch_bounds__(384, 1)
fused_kernel(const __grid_constant__ CUtensorMap mX, const __grid_constant__ CUtensorMap mWkv, const __grid_constant__ CUtensorMap mWq,
             const __grid_constant__ CUtensorMap mWo, const __grid_constant__ CUtensorMap mPhi, const __grid_constant__ CUtensorMap mWp,
             const __grid_constant__ CUtensorMap mOut, const __grid_constant__ CUtensorMap mWc,
             const __grid_constant__ CUtensorMap mG, const __grid_constant__ CUtensorMap mU, const __grid_constant__ CUtensorMap mD,
             const __grid_constant__ CUtensorMap mXs, const __grid_constant__ CUtensorMap mG2, const __grid_constant__ CUtensorMap mU2, const Params P) {
  extern __shared__ __align__(1024) uint8_t smem[];
  if (smem_u32(smem) != SB) return;
  constexpr uint32_t sb = SB, bar = SB + SM_BAR;
  int bid = blockIdx.x;
  if (P.by_sm) {
    uint32_t sm;
    asm volatile("mov.u32 %0, %%smid;" : "=r"(sm));
    const uint32_t tq = (sm - 64) >> 1, q7 = (tq * 37) >> 8;
    const uint32_t gpc = sm < 64 ? (sm >> 1) & 7 : 1 + tq - 7 * q7, idx = (sm < 64 ? sm >> 4 : 4 + q7) * 2 + (sm & 1);
    bid = sm < 120 ? ((PTAB >> (4 * gpc)) & 7) * 16 + idx : sm < 124 ? sm + 8 : sm - 116;
  }
  const int hg = ((bid >> 2) & 3) + 4 * ((bid >> 4) & 1), mb = (bid & 3) + 4 * ((bid >> 5) & 3);
  const int warp = __shfl_sync(~0u, threadIdx.x >> 5, 0);

  if (bid >= NCTA) {
    constexpr uint32_t XV = SM_WPHI, ONES = SM_ZT, BF = bar, BE = bar + 48, BX = bar + 96;
    constexpr int NJ = (DM - GROWS) / 64;
    const int lane = lane_id(), sp = bid - NCTA;
    const uint32_t tag = ld_rlx(g_epoch + bid * 32 + lane) + 1;
    if (warp == 8 && elect_one()) {
#pragma unroll 1
      for (int i = 0; i < 13; i++) mbar_init(bar + 8 * i, i >= 6 && i < 12 ? 8 : 1);
    }
    if (warp == 9) { sts64u(sb + ONES + lane * 8, 0x3f803f80u, 0x3f803f80u); fence_async_smem(); }
    __syncthreads();
    if (warp == 8) {
      if (elect_one()) {
        uint32_t s = 0, ph = 1;
#pragma unroll 1
        for (int job = 0; job < 8; job++) {
          const CUtensorMap* m = job == 0 ? &mWq : sp & 2 ? &mU2 : &mG2;
          const int g0 = job ? (sp & 1) * 28 + job * 4 - 4 : sp * 4;
#pragma unroll 1
          for (int row = job ? GROWS : 0; row < DM; row += 64) {
            mbar_wait(BE + 8 * s, ph);
            mbar_expect_tx(BF + 8 * s, Q_STAGE);
            tma4d(sb + s * Q_STAGE, m, 0, row, g0, 0, BF + 8 * s);
            tma4d(sb + s * Q_STAGE + 16384, m, 0, row, g0 + 2, 0, BF + 8 * s);
            if (++s == 6) { s = 0; ph ^= 1; }
          }
        }
      }
    } else if (warp == 9) {
      uint4 xr[4];
      routed_row(P.x, tag, lane, xr);
#pragma unroll
      for (int i = 0; i < 4; i++) sts128u(sb + XV + i * 512 + lane * 16, xr[i].x, xr[i].y, xr[i].z, xr[i].w);
      fence_async_smem();
      __syncwarp();
      if (lane == 0) mbar_arrive(BX);
    } else if (warp < 8) {
      uint32_t s = 0, ph = 0;
#pragma unroll 1
      for (int job = 0; job < 8; job++) {
        float d[8] = {0.f, 0.f, 0.f, 0.f, 0.f, 0.f, 0.f, 0.f};
        if (job == 1) mbar_wait(BX, 0);
#pragma unroll 1
        for (int i = 0; i < (job ? NJ : 16); i++) {
          mbar_wait(BF + 8 * s, ph);
          wg_fence();
#pragma unroll
          for (int k = 0; k < 8; k++)
            wgmma_n8_ss_ta1_tb0(d + 4 * (k >> 2), mkdesc(sb + k * 2048, 16, 1024, 1, s * (Q_STAGE / 16) + (warp >> 2) * 1024),
                                mkdesc(sb, 16, 128, 0, job ? (XV + GROWS * 2) / 16 + i * 8 + (k & 3) * 2 : ONES / 16), 1);
          wg_commit();
          wg_wait<0>();
          if (lane == 0) mbar_arrive(BE + 8 * s);
          if (++s == 6) { s = 0; ph ^= 1; }
        }
        reg_fence<8>(d);
        float* dst = (job ? g_gp + sp * 1792 + job * 256 - 256 : g_cs + sp * 256) + (warp >> 2) * 128 + (warp & 3) * 16 + (lane >> 2);
        if ((lane & 3) == 0) {
#pragma unroll
          for (int i = 0; i < 4; i++) st_rlx(dst + (i >> 1) * 64 + (i & 1) * 8, mark(__float_as_uint(d[2 * i]), tag & 1));
        }
        __syncwarp();
      }
      if (warp == 0) g_epoch[bid * 32 + lane] = tag;
    }
    return;
  }
#define Q_SLAB(J) ((J) < 8 ? ((J) + 8 - 2 * (hg & 4)) & 15 : 2 * (hg & 4) + 2 * ((J) & 3) + ((J) >> 2 & 1))
#define Q_AOFF(J) ((J) == 8 + (hg & 3) ? SM_X0 : (J) == 12 + (hg & 3) ? SM_X1 : ((J) & 3) * Q_STAGE)
#define Q_LOAD(J)                                                                                            \
  do {                                                                                                       \
    const uint32_t fb_ = bar + B_FULLQ + 8 * ((J) & 3);                                                      \
    const int k_ = Q_SLAB(J) * 64;                                                                           \
    mbar_expect_tx(fb_, Q_STAGE);                                                                            \
    mbar_arrive2(fb_);                                                                                       \
    tma2d(sb + Q_AOFF(J), &mX, k_, mb * 128, fb_);                                                           \
    tma4d(sb + ((J) & 3) * Q_STAGE + 16384, &mWq, 0, k_, hg * 2, 0, fb_);                                    \
  } while (0)
  if (warp >= 8) {
    asm volatile("setmaxnreg.dec.sync.aligned.u32 %0;" ::"n"(REG_H));
    const int lane = lane_id();
    const int f = (warp - 9) & 3;
    const uint32_t ep = ld_rlx(g_epoch + bid * 32 + lane);
    if (f == 3) {
      if (elect_one()) {
        PROF(0); PROFT(32);
#pragma unroll
        for (int j = 0; j < 3; j++) {
          const int s = (j + 2) % 3;
          mbar_init(bar + B_FULLKV + 8 * s, 1);
          mbar_expect_tx(bar + B_FULLKV + 8 * s, KV_STAGE);
          tma2d(sb + s * KV_STAGE, &mX, j * 64, mb * 128, bar + B_FULLKV + 8 * s);
          tma4d(sb + s * KV_STAGE + 16384, &mWkv, 0, j * 64, hg * 2, 1, bar + B_FULLKV + 8 * s);
        }
      }
    } else if (f < 2) {
#pragma unroll
      for (int i = 0; i < 2; i++) {
        const uint4 u = __ldg((const uint4*)P.w_r + (f * 2 + i) * 32 + lane);
        sts128u(sb + SM_XSEL + (f * 2 + i) * 512 + lane * 16, u.x, u.y, u.z, u.w);
      }
    }
    __syncwarp();
    bar_sync(0, 384);
    const uint32_t tag = ep + 1, par = tag & 1;
    const bool ffn = bid < NFFN;
    const int fb = bid, cu = bid >> 1, ch = bid & 1;
#define CS_STORE(SEC, C)                                                                                     \
  _Pragma("unroll") for (int r = 0; r < 3; r++) {                                                            \
    const uint32_t h0 = pack2(C.x, C.y), h1 = pack2(C.z, C.w);                                               \
    sts64u(sb + SM_CST + (SEC) * 1024 + (lane >> 4) * 512 + (lane & 1) * 8 + r * 128 + ((((lane & 15) >> 1) ^ (r + (lane >> 4) * 4)) << 4), h0, h1); \
    C.x -= bf_lo(h0); C.y -= bf_hi(h0); C.z -= bf_lo(h1); C.w -= bf_hi(h1);                                  \
  }
#define BAD4(U) ((U.x ^ par) | (U.y ^ par) | (U.z ^ par) | (U.w ^ par))
    const int n0 = f < 2 ? 0 : 2 * f - 3, ne = FFN_OFF || !ffn ? 3 : f == 3 ? 3 + G8 : 3 + GN;
    const uint32_t fsb = sb + SM_FST + ((f + 1) & 3) * 8192, fbar = bar + B_FST + f * 16, fst = fsb + (lane >> 4) * 2048 + (lane & 15) * 16;
    const CUtensorMap *ma = &mWc, *mc = &mWc;
    int sx = 1024 + cu * 32, sy = ch * 512 + f * 192, sdy = 32;
#define STAGEG(N)                                                                                            \
  do {                                                                                                       \
    if ((N) == 3) { ma = &mG; mc = &mU; sx = fb * 32; sy = f * (GN * 32);  sdy = 0; }                        \
    if ((N) < ne && elect_one()) {                                                                           \
      const uint32_t dst_ = fsb + ((N) & 1) * 4096, b_ = fbar + ((N) & 1) * 8;                               \
      mbar_expect_tx(b_, 4096);                                                                              \
      tma2d(dst_, ma, sx, sy, b_);                                                                           \
      tma2d(dst_ + 2048, mc, sx, sy + sdy, b_);                                                              \
    }                                                                                                        \
    sy += 32 + sdy;                                                                                          \
  } while (0)
    float a[8], gsum = 0.f, usum = 0.f;
    {
      if (f == 3) {
        if (elect_one()) {
          if (XS_EARLY) { mbar_expect_tx(bar + B_XST, 16384); tma3d(sb + SM_XST, &mXs, 0, bid * 16, 0, bar + B_XST); }
          mbar_expect_tx(bar + B_WPHI, 8192);
          tma2d(sb + SM_WPHI, &mPhi, 0, hg * 128, bar + B_WPHI);
          prefetch_map(&mWq); prefetch_map(&mWo); prefetch_map(&mWp); prefetch_map(&mD);
          PROF(31);
        }
        __syncwarp();
      } else {
        if (lane == 0) prefetch_map(f == 0 ? &mWc : f == 1 ? &mG : &mU);
        if (f == 2) ((float2*)g_y[par])[bid * 32 + lane] = make_float2(0.f, 0.f);
      }
      float st[13];
#pragma unroll
      for (int i = 0; i < 13; i++) st[i] = 0.f;
#pragma unroll 1
      for (int i = 0; i < 4; i++) {
        mbar_wait(bar + B_XST + 8 * (i >> 1), 0);
        if (f == 0 && lane == 0 && i == 0) PROF(1);
        const uint4 wu = lds128u(sb + SM_XSEL + i * 512 + lane * 16);
        const float wf[8] = {bf_lo(wu.x), bf_hi(wu.x), bf_lo(wu.y), bf_hi(wu.y), bf_lo(wu.z), bf_hi(wu.z), bf_lo(wu.w), bf_hi(wu.w)};
        st[12] += ((wf[0] + wf[1]) + (wf[2] + wf[3])) + ((wf[4] + wf[5]) + (wf[6] + wf[7]));
#pragma unroll
        for (int r = 0; r < 4; r++) {
          const uint4 u = lds128u(sb + SM_XST + i * 8192 + (4 * f + r) * 512 + lane * 16);
          const float xf[8] = {bf_lo(u.x), bf_hi(u.x), bf_lo(u.y), bf_hi(u.y), bf_lo(u.z), bf_hi(u.z), bf_lo(u.w), bf_hi(u.w)};
#pragma unroll
          for (int k = 0; k < 8; k++) { st[r] += xf[k]; st[4 + r] = fmaf(xf[k], xf[k], st[4 + r]); st[8 + r] = fmaf(xf[k], wf[k], st[8 + r]); }
        }
        if (i >= 2 && f < 3) STAGEG(n0 + i - 2);
      }
      const bool up = lane & 16, up2 = lane & 8;
#pragma unroll
      for (int q = 0; q < 3; q++) {
        const float k0 = up ? st[4 * q + 2] : st[4 * q], k1 = up ? st[4 * q + 3] : st[4 * q + 1];
        const float o0 = up ? st[4 * q] : st[4 * q + 2], o1 = up ? st[4 * q + 1] : st[4 * q + 3];
        const float m0 = k0 + __shfl_xor_sync(~0u, o0, 16), m1 = k1 + __shfl_xor_sync(~0u, o1, 16);
        a[q] = (up2 ? m1 : m0) + __shfl_xor_sync(~0u, up2 ? m0 : m1, 8);
      }
      a[3] = st[12] + __shfl_xor_sync(~0u, st[12], 16);
      a[3] += __shfl_xor_sync(~0u, a[3], 8);
#pragma unroll
      for (int o = 4; o; o >>= 1)
#pragma unroll
        for (int q = 0; q < 4; q++) a[q] += __shfl_xor_sync(~0u, a[q], o);
      if ((lane & 7) == 0) sts128(sb + SM_ROWS + (4 * f + (lane >> 3)) * 16, a[0], a[1], a[2], a[3]);
      if (f < 3) asm volatile("bar.arrive 7, 128;" ::: "memory");
    }
    if (f == 3) {
      bar_sync(7, 128);
      const int row = bid * 16 + (lane & 15);
      const float4 v = lds128(sb + SM_ROWS + (lane & 15) * 16);
      const float mf = v.x * (1.f / DM), mean = bf_round(mf), var = fmaxf(fmaf(-mf, mf, v.y * (1.f / DM)), 0.f);
      const float sd = bf_round(sqrt_approx(bf_round(bf_round(var) + 1e-5f)));
      const uint32_t rb = pack2(fmaf(-mean, v.w, v.z) * rcp(sd), 0.f) & 0xffffu, ord = (rb & 0x8000u) ? (~rb & 0xffffu) : (rb | 0x8000u);
      uint32_t best = __reduce_max_sync(~0u, (ord << 16) | (uint32_t)(2047 - row));
      if (lane < 16) st_rlx64(g_stat + row, ((unsigned long long)tag << 32) | __float_as_uint(mean) | (__float_as_uint(sd) >> 16));
      if (lane < 2) asm volatile("red.relaxed.gpu.global.max.u64 [%0], %1;" ::"l"(lane ? (void*)(g_ycnt + 32) : (void*)(g_best + bid)), "l"(((unsigned long long)tag << 32) | best) : "memory");
      if (lane == 1) { red_inc(g_ycnt + 34); PROF(17); }
#pragma unroll 1
      for (int n = 3; n < 5; n++) STAGEG(n);
      {
        uint4 xr[4];
        best = routed_row(P.x, tag, lane, xr);
#pragma unroll
        for (int i = 0; i < (GROWS + 255) / 256; i++) {
          const uint32_t dst = sb + SM_XSEL + i * 1024 + (lane >> 2) * 128 + (lane & 3) * 8;
          sts64(dst, bf_lo(xr[i].x), bf_lo(xr[i].z)); sts64(dst + 32, bf_hi(xr[i].x), bf_hi(xr[i].z));
          sts64(dst + 64, bf_lo(xr[i].y), bf_lo(xr[i].w)); sts64(dst + 96, bf_hi(xr[i].y), bf_hi(xr[i].w));
        }
        sts64u(sb + SM_RED + 16, tag, best);
        __syncwarp();
        if (lane == 0) { mbar_arrive(bar + B_XS); PROF(19); }
      }
      unsigned long long sv4[4];
      uint4 u[4];
#pragma unroll 1
      for (int it = 0; it < SPIN_MAX; it++) {
#pragma unroll
        for (int i = 0; i < 4; i++) { u[i] = ld_rlx128(g_cs + (1 + i) * 1024 + hg * 128 + lane * 4); sv4[i] = ld_rlx64(g_stat + mb * 128 + i * 32 + lane); }
        bool ok = ((BAD4(u[0]) | BAD4(u[1]) | BAD4(u[2]) | BAD4(u[3])) & 1) == 0;
#pragma unroll
        for (int i = 0; i < 4; i++) ok = ok && (uint32_t)(sv4[i] >> 32) == tag;
        if (__all_sync(~0u, ok)) break;
        __nanosleep(200);
      }
#pragma unroll
      for (int i = 0; i < 4; i++) {
        const uint32_t sv = (uint32_t)sv4[i], sd2 = (sv << 16) | (sv & 0xffffu);
        sts64(sb + SM_STAT + (i * 32 + lane) * 8, -bf_hi(sv), rcp(bf_lo(sv)));
        sts128u(sb + SM_SDT + lane * 64 + ((i ^ ((lane >> 1) & 3)) << 4), sd2, sd2, sd2, sd2);
      }
#pragma unroll
      for (int i = 0; i < 2; i++) {
        float4 c = make_float4(unmark(u[i].x) + unmark(u[i + 2].x), unmark(u[i].y) + unmark(u[i + 2].y), unmark(u[i].z) + unmark(u[i + 2].z),
                               unmark(u[i].w) + unmark(u[i + 2].w));
        CS_STORE(i, c);
      }
      fence_async_smem();
      bar_sync(8, 64);
      if (lane == 0) { mbar_arrive(bar + B_CS); PROF(10); }
    }
    {
      uint32_t xa = sb + SM_RED + 32, xstep = 0;
      const uint32_t zero = __float_as_uint(lds32(sb + SM_RED + 12));
#pragma unroll 1
      for (int ph = f == 3; ph < 2; ph++) {
#pragma unroll
        for (int j = 0; j < 8; j++) a[j] = 0.f;
        if (ph && f == 0) {
        {
          mbar_wait(bar + B_WPHI, 0);
          float nq[8] = {0.f, 0.f, 0.f, 0.f, 0.f, 0.f, 0.f, 0.f};
  #pragma unroll 2
          for (int r = 0; r < 16; r++) {
            const uint4 u = lds128u(sb + SM_WPHI + ((lane >> 2) * 16 + r) * 64 + (((lane ^ (r >> 1)) & 3) << 4));
            nq[0] = fmaf(bf_lo(u.x), bf_lo(u.x), nq[0]); nq[1] = fmaf(bf_hi(u.x), bf_hi(u.x), nq[1]); nq[2] = fmaf(bf_lo(u.y), bf_lo(u.y), nq[2]);
            nq[3] = fmaf(bf_hi(u.y), bf_hi(u.y), nq[3]); nq[4] = fmaf(bf_lo(u.z), bf_lo(u.z), nq[4]); nq[5] = fmaf(bf_hi(u.z), bf_hi(u.z), nq[5]);
            nq[6] = fmaf(bf_lo(u.w), bf_lo(u.w), nq[6]); nq[7] = fmaf(bf_hi(u.w), bf_hi(u.w), nq[7]);
          }
          uint32_t m = 0;
  #pragma unroll
          for (int i = 0; i < 8; i++) m = max(m, __float_as_uint(nq[i] + __shfl_xor_sync(~0u, nq[i], 4)) & 0x7fffffffu);
          sts32(sb + SM_RED + 24, 4.2f * __uint_as_float(__reduce_max_sync(~0u, m)));
        }
          asm volatile("bar.arrive 8, 64;" ::: "memory");
        }
        if (ph) { mbar_wait(bar + B_XS, 0); xa = sb + SM_XSEL + f * (GN * 128) + ((lane >> 2) & 3) * 32; xstep = 128; }
#pragma unroll 1
        for (int n = ph ? 3 : n0; n < (ph ? ne : 3); n++) {
          const float4 x0 = lds128(xa), x1 = lds128(xa + 16);
          xa += xstep;
          mbar_wait(fbar + (n & 1) * 8, ((n - n0) >> 1) & 1);
          uint4 u[8];
#pragma unroll
          for (int j = 0; j < 8; j++) u[j] = lds128u(fst + (n & 1) * 4096 + j * 256);
          FMA8(a, u[0], x0.x); FMA8(a, u[1], x0.y); FMA8(a, u[2], x0.z); FMA8(a, u[3], x0.w);
          if (__any_sync(~0u, ((u[4].x | u[5].x | u[6].x | u[7].x | __float_as_uint(a[0]) | __float_as_uint(a[7])) & zero) == 0)) STAGEG(n + 2);
          FMA8(a, u[4], x1.x); FMA8(a, u[5], x1.y); FMA8(a, u[6], x1.z); FMA8(a, u[7], x1.w);
        }
#pragma unroll
        for (int o = 4; o <= 8; o <<= 1)
#pragma unroll
          for (int j = 0; j < 8; j++) a[j] += __shfl_xor_sync(~0u, a[j], o);
        if (ph && lane == 0) mbar_arrive(bar + B_FFN);
        const uint32_t red = ph ? sb + SM_GRED : sb + SM_RED + 64;
        if ((lane & 12) == 0) {
          const uint32_t d = red + f * 256 + (lane >> 4) * 128 + (lane & 3) * 32;
          sts128(d, a[0], a[1], a[2], a[3]); sts128(d + 16, a[4], a[5], a[6], a[7]);
        }
        if (f != 2) {
          asm volatile("bar.arrive %0, %1;" ::"r"(4 + ph), "r"(96 + 32 * ph) : "memory");
        } else {
          bar_sync(4 + ph, 96 + 32 * ph);
          const uint32_t ra = red + lane * 4;
          gsum = lds32(ra) + lds32(ra + 256) + lds32(ra + 512);
          usum = lds32(ra + 128) + lds32(ra + 384) + lds32(ra + 640);
          if (!ph) st_rlx(g_cs + 1024 + ch * 2048 + cu * 32 + lane, mark(__float_as_uint(gsum + usum), par));
          else { gsum += lds32(ra + 768); usum += lds32(ra + 896); }
          if (lane == 0) PROF(ph ? 34 : 18);
        }
      }
    }
    if (f == 3) {
      if (elect_one()) {
        PROF(7);
        mbar_wait(bar + B_FULLQ, 0);
#pragma unroll 1
        for (int j = 3; j < 16; j++) {
          mbar_wait(bar + (j < 4 ? B_EMPTYKV + 16 : B_EMPTYQ + 8 * (j & 3)), ((j >> 2) & 1) ^ 1);
          if (j == 12 + (hg & 3)) mbar_wait(bar + B_KVST + 8, 0);
          Q_LOAD(j);
        }
        PROF(47);
        mbar_expect_tx(bar + B_DN, 65536);
#pragma unroll 1
        for (int i = 0; i < 4; i++) {
          mbar_wait(bar + B_EMPTYQ + 8 * i, 1);
          tma3d(sb + i * Q_STAGE, &mD, 0, fb * 32, i * 4, bar + B_DN);
        }
        PROF(48);
#pragma unroll 1
        for (int i = 0; i < 16; i++) {
          const int s = i & 3, n = i < 9 ? i - 2 : i - 9, kb = i < 2 ? 2 * hg + i : 2 * (n + (n >= hg)) + (i >= 9);
          if (i >= 4) mbar_wait(bar + B_EMPTYQ + 8 * s, ((i >> 2) & 1) ^ 1);
          mbar_expect_tx(bar + B_FULLQ + 8 * s, 16384);
          if (i < 2) {
            mbar_arrive2(bar + B_FULLQ + 8 * s);
            tma3d(sb + s * Q_STAGE + 16384, &mWo, 0, kb * 64, hg * 2, bar + B_FULLQ + 8 * s);
          } else {
            tma5d(sb + s * Q_STAGE + 16384, &mWp, hg * 128, kb * 2, bar + B_FULLQ + 8 * s);
            tma5d(sb + s * Q_STAGE + 24576, &mWp, hg * 128 + 64, kb * 2, bar + B_FULLQ + 8 * s);
            if (i >= 3) {
              if (i == 3) { mbar_wait(bar + B_DND, 0); PROF(14); }
#pragma unroll 1
              for (int a = i == 3 ? 2 : i; a <= i; a++) {
                const uint4* src = g_ofr + (mb * 16 + (a == 2 ? (hg == 0 ? 2 : 0) : kb)) * 1024;
#pragma unroll
                for (int h = 0; h < 2; h++) {
                  mbar_expect_tx(bar + B_AIN + (a & 3) * 16 + h * 8, 8192);
                  bulk_load(sb + (a & 3) * Q_STAGE + h * 8192, src + h * 512, 8192, bar + B_AIN + (a & 3) * 16 + h * 8);
                }
              }
            }
          }
        }
      }
    } else {
      if (f == 2) {
        if (PFD && ffn) {
#pragma unroll 1
          for (int i = 0; i < 16; i++) { touch_l2((const char*)P.w_down + fb * 65536 + i * 4096 + lane * 128, lane); __nanosleep(PFD); }
        }
        if (WOT) {
#pragma unroll 1
          for (int i = 0; i < 8; i++) { touch_l2((const char*)P.wo + ((mb & 7) * 128 + i * 16 + (lane >> 1)) * 2048 + hg * 256 + (lane & 1) * 128, lane); __nanosleep(PFD); }
        }
        asm volatile("cp.async.wait_all;" ::: "memory");
        uint4 u;
#pragma unroll 1
        for (int it = 0; it < SPIN_MAX; it++) {
          u = ld_rlx128(g_cs + hg * 128 + lane * 4);
          if (__all_sync(~0u, !(BAD4(u) & 1))) break;
          __nanosleep(200);
        }
        mbar_wait(bar + B_PHI, 0);
        float4 c = make_float4(unmark(u.x), unmark(u.y), unmark(u.z), unmark(u.w));
        CS_STORE(2, c);
        fence_async_smem();
        __syncwarp();
        if (lane == 0) mbar_arrive(bar + B_CSQ);
        if (ffn && !FFN_OFF) {
#pragma unroll 1
          for (int it = 0; it < SPIN_MAX; it++) {
            const uint32_t pg = ld_rlx((const uint32_t*)g_gp + fb * 32 + lane), pu = ld_rlx((const uint32_t*)g_gp + FF + fb * 32 + lane);
            if (__all_sync(~0u, !(((pg ^ par) | (pu ^ par)) & 1))) { gsum += unmark(pg); usum += unmark(pu); break; }
            __nanosleep(200);
          }
        }
        const float h = bf_round(silu_f(bf_round(gsum))) * bf_round(usum);
        const uint32_t h2 = pack2(h, h);
        sts128u(sb + SM_HT + lane * 16, h2, h2, h2, h2);
        fence_async_smem();
        __syncwarp();
        if (lane == 0) { mbar_arrive(bar + B_H); PROF(20); }
      }
      if (f < 2) {
        const uint32_t own = (hg * 2 + f) * 16 + mb, target = __shfl_sync(~0u, tag, 0) * 16;
        mbar_wait(bar + B_KVST + 8 * f, 0);
        if (f == 1 && lane == 0) PROF(11);
        wait_hint(g_xcnt + hg * 64 + f * 16 + mb, target);
        if (elect_one()) {
          PROF(35 + f);
          fence_async_global();
          mbar_expect_tx(bar + B_PART + 8 * f, 8192);
          bulk_load(sb + (f ? SM_PST1 : SM_PST0), g_part + own * 512, 8192, bar + B_PART + 8 * f);
        }
        __syncwarp();
        {
          uint4 uz;
#pragma unroll 1
          for (int it = 0; it < SPIN_MAX; it++) {
            uz = ld_rlx128(g_zpart + own * 128 + lane * 4);
            if (__all_sync(~0u, !(BAD4(uz) & 1))) break;
          }
          const bool b1 = lane & 2, b2 = lane & 4;
          const float z0 = unmark(b1 ? uz.z : uz.x) + __shfl_xor_sync(~0u, unmark(b1 ? uz.x : uz.z), 2);
          const float z1 = unmark(b1 ? uz.w : uz.y) + __shfl_xor_sync(~0u, unmark(b1 ? uz.y : uz.w), 2);
          float z = (b2 ? z1 : z0) + __shfl_xor_sync(~0u, b2 ? z0 : z1, 4);
          z += __shfl_xor_sync(~0u, z, 8);
          z += __shfl_xor_sync(~0u, z, 16);
          if (lane < 8) st_rlx(g_zres + own * 8 + (lane & 1) * 4 + (lane & 2) + (lane >> 2), mark(__float_as_uint(z), par));
          if (lane == 0) red_inc(g_xcnt + hg * 64 + 32 + f * 16);
          __syncwarp();
        }
        wait_hint(g_xcnt + hg * 64 + 32 + f * 16, 5 * target);
        mbar_wait(bar + B_KVST + 8, 0);
        if (lane == 0) PROF(40 + f);
#pragma unroll 1
        for (int it = 0; it < SPIN_MAX; it++) {
          if (elect_one()) {
            fence_async_global();
            mbar_expect_tx(bar + B_RES + 8 * f, 8192);
            bulk_load(sb + SM_V + f * 8192, g_res[par] + (hg * 4 + f * 2) * 256, 8192, bar + B_RES + 8 * f);
          }
          __syncwarp();
          const uint4 uz = ld_rlx128(g_zres + (hg * 4 + f * 2) * 64 + lane * 4);
          const uint32_t zw[4] = {uz.x, uz.y, uz.z, uz.w};
#pragma unroll
          for (int j = 0; j < 4; j++) {
            const uint32_t zz = pack2(unmark(zw[j]), 1.f), row = (lane & 3) * 4 + j;
            sts128u(sb + SM_ZT + (2 * f + (lane >> 4)) * 1024 + row * 64 + ((((lane >> 2) ^ (row >> 1)) & 3) << 4), zz, zz, zz, zz);
          }
          uint32_t bad = BAD4(uz);
          mbar_wait(bar + B_RES + 8 * f, it & 1);
#pragma unroll
          for (int i = 0; i < 16; i++) bad |= ~__float_as_uint(lds32(sb + SM_V + f * 8192 + i * 512 + lane * 16));
          if (__all_sync(~0u, !(bad & 1))) break;
        }
        fence_async_smem();
        __syncwarp();
        if (lane == 0) { mbar_arrive(bar + B_TILE + 8 * f); PROF(f ? 13 : 27); }
      }
      if (f < 2) {
        uint32_t phases = 0;
#pragma unroll 1
        for (int i = 2; i < 16; i++) {
          const int s = i & 3;
          const uint32_t ab = bar + B_AIN + s * 16 + f * 8, slot = sb + s * Q_STAGE + f * 8192;
#pragma unroll 1
          for (int it = 0; it < SPIN_MAX; it++) {
            mbar_wait(ab, (phases >> s) & 1);
            phases ^= 1u << s;
            uint32_t bad = 0;
#pragma unroll
            for (int n = 0; n < (NOVAL ? 0 : 8); n++) bad |= __float_as_uint(lds32(slot + n * 1024 + lane * 32 + (lane >> 2) * 4)) ^ par;
            if (__all_sync(~0u, !(bad & 1))) break;
            if (elect_one()) {
              const int n = i < 9 ? i - 2 : i - 9, kb = 2 * (n + (n >= hg)) + (i >= 9);
              PROF(49);
              mbar_expect_tx(ab, 8192);
              bulk_load(slot, g_ofr + (mb * 16 + kb) * 1024 + f * 512, 8192, ab);
            }
            __syncwarp();
          }
          if (lane == 0) { mbar_arrive(bar + B_FULLQ + 8 * s); if (i == 2 && f == 0) PROF(15); }
        }
        if (f == 0) g_epoch[bid * 32 + lane] = tag;
      } else {
        if (elect_one()) {
          prefetch_map(&mOut);
          if (ffn) { mbar_wait(bar + B_YD, 0); red_rel(g_ycnt); PROF(21); }
        }
        __syncwarp();
        if (f == 2) {
          const uint32_t best = __float_as_uint(lds32(sb + SM_RED + 20));
          const int sel = 2047 - (best & 0x7ff) - mb * 128;
          if (sel >= 0 && sel < 128) {
            const uint2 xr = __ldg((const uint2*)(P.x + (size_t)(mb * 128 + sel) * DM + hg * 128 + lane * 4));
            const float2 st = lds64(sb + SM_STAT + sel * 8);
            const uint32_t ord = best >> 16, rb = (ord & 0x8000u) ? (ord & 0x7fffu) : (~ord & 0xffffu);
            const float sg = rcp(1.f + ex2(-1.4426950408889634f * bf_lo(rb)));
            const uint32_t sg2 = pack2(sg, sg), nm2 = pack2(st.x, st.x);
            wait_cnt<0>(g_ycnt, tag * NFFN);
            float4 y = make_float4(0.f, 0.f, 0.f, 0.f);
#pragma unroll
            for (int i = 0; i < 8; i++) {
              const float4 c = ldg_cg4(g_y[par ^ 1][i] + hg * 128 + lane * 4);
              y.x += c.x; y.y += c.y; y.z += c.z; y.w += c.w;
            }
            uint32_t o[2];
#pragma unroll
            for (int i = 0; i < 2; i++) {
              const uint32_t d = badd2(i ? xr.y : xr.x, nm2);
              const uint32_t tt = badd2(pack2(bf_lo(d) * st.y, bf_hi(d) * st.y), bmul2(i ? pack2(y.z, y.w) : pack2(y.x, y.y), sg2));
              o[i] = pack2(silu_f(bf_lo(tt)), silu_f(bf_hi(tt)));
            }
            sts64u(sb + SM_UPD + lane * 8, o[0], o[1]);
          }
          if (lane == 0) sts32(sb + SM_UPD + 256, __int_as_float(sel));
          __syncwarp();
          if (lane == 0) { mbar_arrive(bar + B_UPD); PROF(22); }
        }
      }
    }
  } else {
    const int t7 = threadIdx.x & 127;
    const char* pfa = warp < 4 ? (const char*)P.x + bid * 32768 + (t7 & 15) * 2048 + (t7 >> 4) * 128
                               : (const char*)P.wqkv + (size_t)((t7 >> 4) * 64 + (bid >> 1)) * 6144 + 2048 + (bid & 1) * 2048 + (t7 & 15) * 128;
    if (t7 < 16 * PF_FIRST) prefetch_l2(pfa);
    if (warp < 7) sts128(sb + SM_CST + threadIdx.x * 16, 0.f, 0.f, 0.f, 0.f);
    else sts32(sb + SM_RED + (threadIdx.x & 15) * 4, threadIdx.x & 8 ? 1.f : 0.f);
    fence_async_smem();
    if (elect_one()) {
#pragma unroll 1
      for (uint32_t b = B_FST + warp * 8; b < B_END; b += 64)
        mbar_init(bar + b, b < B_FULLQ ? 1 : b < B_FFN ? 3 : b < B_EMPTYKV ? 4 : 8);
    }
    __syncwarp();
    asm volatile("setmaxnreg.inc.sync.aligned.u32 %0;" ::"n"(REG_C));
    if (PF_PRE && t7 >= 16 * PF_FIRST && threadIdx.x < 128 + 16 * PF_W) prefetch_l2(pfa);
    bar_sync(0, 384);
    if (!PF_PRE && t7 >= 16 * PF_FIRST && threadIdx.x < 128 + 16 * PF_W) prefetch_l2(pfa);
    const int lane = lane_id();
    const int wg = warp >> 2, w = warp & 3, g = lane >> 2, t = lane & 3;
    float kv[128];
    {
      uint32_t s = 2, ph = 0, sp = 0, php = 0;
#pragma unroll 1
      for (int j = 0; j < 15; j++) {
        PW0(32 + j); mbar_wait(bar + B_FULLKV + 8 * s, ph); PW1(32 + j);
        if (wg == 1 && (ORDER_ALL || j == 0)) bar_sync(10 + s, 256);
        wg_fence();
        wgmma_n256_ssp_ta0_tb1(kv, mkdesc(sb, 16, 1024, 1, wg * 512 + s * (KV_STAGE / 16)), mkdesc(sb + 16384, 8192, 1024, 1, s * (KV_STAGE / 16)), j);
#pragma unroll
        for (int k = 1; k < 4; k++)
          wgmma_n256_ss_ta0_tb1(kv, mkdesc(sb + k * 32, 16, 1024, 1, wg * 512 + s * (KV_STAGE / 16)),
                                mkdesc(sb + 16384 + k * 2048, 8192, 1024, 1, s * (KV_STAGE / 16)), 1);
        wg_commit();
        if (wg == 0 && (ORDER_ALL || j == 0)) asm volatile("bar.arrive %0, 256;" ::"r"(10 + s) : "memory");
        if (warp == 0 && j) {
          mbar_wait(bar + B_EMPTYKV + 8 * sp, php);
          if (elect_one()) {
            if (j < 14) {
              mbar_expect_tx(bar + B_FULLKV + 8 * sp, KV_STAGE);
              tma2d(sb + sp * KV_STAGE, &mX, (j + 2) * 64, mb * 128, bar + B_FULLKV + 8 * sp);
              tma4d(sb + sp * KV_STAGE + 16384, &mWkv, 0, (j + 2) * 64, hg * 2, 1, bar + B_FULLKV + 8 * sp);
            } else {
              Q_LOAD(0);
            }
            if (j < 3 - XS_EARLY) {
              const int xh = j - 1 + XS_EARLY;
              mbar_expect_tx(bar + B_XST + 8 * xh, 16384);
              tma3d(sb + SM_XST + xh * 16384, &mXs, 0, bid * 16, 2 * xh, bar + B_XST + 8 * xh);
            }
          }
          __syncwarp();
        }
        if (j == 0) {
          if (wg == 0) prefetch_l2(pfa + 1024);
        } else if (wg == 1) {
          if (j < 3) {
            if (j == 2 || t7 >= 16 * PF_W) prefetch_l2(pfa + (j - 1) * (8 * 393216));
          } else if (j == 13) {
            prefetch_l2((const char*)P.wo + bid * 16384 + t7 * 128);
          }
          if (PFG && !FFN_OFF && bid < NFFN && j >= 2 && j < 2 + GROWS / 64 && w < 2)
            touch_l2((const char*)((bid & 1) ? P.w_up : P.w_gate) + (size_t)((0x852a7419630ull >> (4 * j - 8) & 15) * 64 + t7) * 7168 + (bid >> 1) * 128, lane);
        }
        wg_wait<0>();
        if (lane == 0) mbar_arrive(bar + B_EMPTYKV + 8 * s);
        sp = s; php = ph;
        ph ^= s == 1;
        s = s == 2 ? 0 : s + 1;
      }
    }
    const int lrow = wg * 64 + w * 16 + (lane & 15);
    const uint32_t sw128 = lrow * 128, x128 = (lrow & 7), hi16 = lane >> 4;
    mbar_wait(bar + B_CS, 0);
    const uint32_t tag = __float_as_uint(lds32(sb + SM_RED + 16));
    const int zero = __float_as_int(lds32(sb + SM_RED + 12));
    const float wn = lds32(sb + SM_RED + 24);
    const float2 st0 = lds64(sb + SM_STAT + (wg * 64 + w * 16 + g) * 8), st1 = lds64(sb + SM_STAT + (wg * 64 + w * 16 + g + 8) * 8);
    const float c0 = st0.y * 1.4426950408889634f, c1 = st1.y * 1.4426950408889634f;
    const uint32_t nm20 = pack2(st0.x, st0.x), nm21 = pack2(st1.x, st1.x), fmask = t == 0 ? ~0u : t == 1 ? 0xffffu : 0u;
    const uint32_t fa0 = nm20 & fmask, fa1 = nm21 & fmask;
    asm volatile("cp.async.wait_all;" ::: "memory");
    PW0(47); mbar_wait(bar + B_FULLKV + 16, 1); PW1(47);
    wg_fence();
    wgmma_n256_rs_ta0_tb1(kv, fa0, fa1, 0u, 0u, mkdesc(sb + SM_CST, 512, 0, 1), 1);
#pragma unroll
    for (int k = 0; k < 4; k++)
      wgmma_n256_ss_ta0_tb1(kv, mkdesc(sb + 2 * KV_STAGE + k * 32, 16, 1024, 1, wg * 512), mkdesc(sb + 2 * KV_STAGE + 16384 + k * 2048, 8192, 1024, 1), 1);
    wg_commit();
    if (warp == 0) {
      mbar_wait(bar + B_EMPTYKV + 8, 0);
      if (elect_one()) {
#pragma unroll 1
        for (int j = 1; j < 3; j++) Q_LOAD(j);
      }
      __syncwarp();
    }
    wg_wait<0>();
    reg_fence<128>(kv);
    if (lane == 0) mbar_arrive(bar + B_EMPTYKV + 16);
    PROFC(2);
    float q[64];
#define QMMA(J, AOFF16, ACCUM)                                                                                     \
  _Pragma("unroll") for (int k = 0; k < 4; k++)                                                                    \
      wgmma_n128_ss_ta0_tb1(q, mkdesc(sb + k * 32, 16, 1024, 1, wg * 512 + (AOFF16)),                              \
                            mkdesc(sb + 16384 + k * 2048, 8192, 1024, 1, ((J) & 3) * (Q_STAGE / 16)), k ? 1 : (ACCUM))
#define QWAIT(J) do { PW0(J); mbar_wait(bar + B_FULLQ + 8 * ((J) & 3), ((J) >> 2) & 1); PW1(J); } while (0)
#define QSTEP_A(J, AOFF16, ACCUM) do { QWAIT(J); wg_fence(); QMMA(J, AOFF16, ACCUM); wg_commit(); } while (0)
#define QREL(J) do { if (lane == 0) mbar_arrive(bar + B_EMPTYQ + 8 * ((J) & 3)); } while (0)
#define Q_OFF16(J) ((J) >= 8 && (J) < 16 ? Q_AOFF(J) / 16 : ((J) & 3) * (Q_STAGE / 16))
#define QPLAIN(J) do { QSTEP_A(J, Q_OFF16(J), 1); wg_wait<1>(); QREL((J) - 1); } while (0)
#define QNEXT(J) do { QPLAIN(J); SCHED_FENCE(); } while (0)
#define PHI_PROJ(DST, SRC, H0, H1)                                                                                 \
  do {                                                                                                             \
    uint32_t a_[32];                                                                                               \
    _Pragma("unroll") for (int j = 8 * (H0); j < 8 * (H1); j++) {                                                  \
      a_[j] = pack2(SRC[2 * j], SRC[2 * j + 1]);                                                                   \
      asm volatile("fma.rn.bf16x2 %0, %1, %1, %0;" : "+r"(nq[(j >> 4) * 2 + (j & 1)]) : "r"(a_[j]));               \
    }                                                                                                              \
    wg_fence();                                                                                                    \
    _Pragma("unroll") for (int hk = 2 * (H0); hk < 2 * (H1); hk++)                                                 \
        wgmma_n32_rs_ta0_tb1(DST + 16 * (hk >> 1), a_[4 * hk], a_[4 * hk + 1], a_[4 * hk + 2], a_[4 * hk + 3],     \
                             mkdesc(sb + SM_WPHI + hk * 1024, 16, 512, 2), hk & 1);                                \
    wg_commit();                                                                                                   \
  } while (0)
    {
      float p[64], ea[24], eb[24], sa[4], sc[4], kz[20];
      uint32_t vp[32];
#pragma unroll
      for (int j = 0; j < 32; j++) vp[j] = pack2(kv[64 + 2 * j], kv[65 + 2 * j]);
      const uint32_t vr = w * 16 + (lane & 15), vb = sb + SM_V + wg * 4096 + vr * 64, x64 = (vr >> 1) & 3;
#define V_STORE(R)                                                                                           \
  _Pragma("unroll") for (int j = 0; j < 4; j++)                                                              \
      stsm4(vb + (j >> 1) * 8192 + ((((j & 1) * 2 + hi16) ^ x64) << 4), vp[16 * (R) + 4 * j], vp[16 * (R) + 4 * j + 1], vp[16 * (R) + 4 * j + 2], vp[16 * (R) + 4 * j + 3])
      V_STORE(0);
      mbar_wait(bar + B_WPHI, 0);
      {
        uint32_t nq[4] = {0u, 0u, 0u, 0u};
        PHI_PROJ(p, kv, 0, 4);
        QSTEP_A(0, 0, 0);
        const bool unsafe = softmax_unsafe(nq, c0 * c0 * wn, c1 * c1 * wn);
        wg_wait<1>();
        reg_fence<64>(p);
        if (__builtin_expect(unsafe, 0)) softmax_shift(p, c0, c1);
      }
#define K_NORM(S) do { quad_sum<4>(S); _Pragma("unroll") for (int i = 0; i < 4; i++) S[i] = rcp(S[i]) * ((i & 1) ? st1.y : st0.y); } while (0)
#define K_STORE(SLOT, E, S) K_STORE_(SLOT, E, S, 0, 2)
#define K_STORE_(SLOT, E, S, J0, J1)                                                                         \
  _Pragma("unroll") for (int j = (J0); j < (J1); j++) {                                                      \
    uint32_t fp[4], fm[4];                                                                                   \
    _Pragma("unroll") for (int i = 0; i < 4; i++) {                                                          \
      const float e0 = E[8 * j + 2 * i], e1 = E[8 * j + 2 * i + 1], r = E[16 + 4 * j + i] * S[2 + (i & 1)];  \
      const uint32_t e2 = pack2(e0, e1);                                                                     \
      fp[i] = bmul2(e2, pack2(S[i & 1], S[i & 1]));                                                          \
      fm[i] = bmul2(e2, pack2(r, r));                                                                        \
    }                                                                                                        \
    stsm4(sb + SM_PHI + (SLOT) * 16384 + sw128 + (((2 * j + hi16) ^ x128) << 4), fp[0], fp[1], fp[2], fp[3]); \
    stsm4(sb + SM_PHI + (SLOT) * 16384 + sw128 + (((4 + 2 * j + hi16) ^ x128) << 4), fm[0], fm[1], fm[2], fm[3]); \
  }
#define KV_MMA(R)                                                                                            \
  do {                                                                                                       \
    mbar_wait(bar + B_PHI + 8 * (R), 0);                                                                     \
    wg_fence();                                                                                              \
    _Pragma("unroll") for (int k = 0; k < 8; k++) {                                                          \
      const uint32_t vs = SM_V + (k >> 2) * 4096 + (k & 3) * 1024;                                           \
      wgmma_n40_ss_ta1_tb1(kz, mkdesc(sb + SM_PHI + k * 2048, 16, 1024, 1, wg * 1024),                       \
                           mkdesc(sb + vs, SM_SDT + (k & 1) * 1024 + (k >> 1) * 16 - vs, 512, 2, wg * (512u - (512u << 16))), k); \
    }                                                                                                        \
    wg_commit();                                                                                             \
  } while (0)
#define QKV(J, R) do { KV_MMA(R); QSTEP_A(J, Q_OFF16(J), 1); wg_wait<2>(); QREL((J) - 1); SCHED_FENCE(); } while (0)
#define KV_SEND(R)                                                                                           \
  do {                                                                                                       \
    reg_fence<20>(kz);                                                                                       \
    if (lane == 0) mbar_arrive(bar + B_KVST + 8 * (R));                                                      \
    const uint32_t slot = ((hg * 2 + (R)) * 16 + warp * 2) * 16 + mb;                                        \
    _Pragma("unroll") for (int u = 0; u < 2; u++)                                                            \
      st_rlx128(g_part + (slot + u * 16) * 32 + lane, mark(pack2(kz[2 * u], kz[2 * u + 1]), tag & 1), pack2(kz[2 * u + 4], kz[2 * u + 5]), \
                pack2(kz[2 * u + 8], kz[2 * u + 9]), pack2(kz[2 * u + 12], kz[2 * u + 13]));                 \
    if (t < 2) st_rlx(g_zpart + (slot + t * 16) * 8 + g, mark(__float_as_uint(t ? kz[18] : kz[16]), tag & 1)); \
    if (lane < 2) red_inc(g_xcnt + hg * 64 + (R) * 16 + warp * 2 + lane);                                    \
  } while (0)
#define K_PUB(R) do { fence_async_smem(); __syncwarp(); if (lane == 0) mbar_arrive(bar + B_PHI + 8 * (R)); } while (0)
#define S_PIN(S) SCHED_PIN(S[0] + S[1] + S[2] + S[3])
      k_exp(p, c0, c1, ea, sa);
      S_PIN(sa);
      QNEXT(1);
      K_NORM(sa);
      k_exp<0, 4>(p + 16, c0, c1, eb, sc);
      mbar_wait(bar + B_FFN, 0);
      K_STORE_(0, ea, sa, 0, 1);
      S_PIN(sc);
      QNEXT(2);
      K_STORE_(0, ea, sa, 1, 2);
      k_exp<4, 8>(p + 16, c0, c1, eb, sc);
      K_NORM(sc);
      S_PIN(sc);
      QNEXT(3);
      K_STORE(1, eb, sc);
      K_PUB(0);
      k_exp<0, 4>(p + 32, c0, c1, ea, sa);
      S_PIN(sa);
      QKV(4, 0);
      k_exp<4, 8>(p + 32, c0, c1, ea, sa);
      K_NORM(sa);
      k_exp<0, 4>(p + 48, c0, c1, eb, sc);
      SCHED_PIN(sa[0] + sa[1] + sa[2] + sa[3] + sc[2] + sc[3]);
      QNEXT(5);
      KV_SEND(0);
      k_exp<4, 8>(p + 48, c0, c1, eb, sc);
      S_PIN(sc);
      QNEXT(6);
      K_NORM(sc);
      mbar_wait(bar + B_KVST, 0);
      V_STORE(1);
      K_STORE(0, ea, sa);
      QNEXT(7);
      K_STORE(1, eb, sc);
      K_PUB(1);
      QKV(8, 1);
      QNEXT(9);
      KV_SEND(1);
    }
#define JQ0 10
    PROFC(3);
    {
      bool todo = true;
#pragma unroll 1
      for (int j = JQ0; j < 15 || todo; j++) {
        if (j < 15) { QSTEP_A(j, Q_AOFF(j) / 16, 1); wg_wait<1>(); QREL(j - 1); }
        if (todo && __any_sync(~0u, mbar_test(bar + B_PART + 8 * wg, 0))) {
          todo = false;
          const uint32_t own = (hg * 2 + wg) * 16 + mb, word = w * 32 + lane;
          uint32_t u[16], bad = 0;
#pragma unroll
          for (int i = 0; i < 16; i++) { u[i] = __float_as_uint(lds32(sb + (wg ? SM_PST1 : SM_PST0) + i * 512 + word * 4)); bad |= u[i] ^ tag; }
#pragma unroll 1
          for (int it = 0; it < SPIN_MAX && __any_sync(~0u, t == 0 && (bad & 1)); it++) {
            bad = 0;
#pragma unroll
            for (int i = 0; i < 16; i++) { u[i] = ld_rlx((const uint32_t*)g_part + own * 2048 + i * 128 + word); bad |= u[i] ^ tag; }
          }
          float s0 = 0.f, s1 = 0.f, s2 = 0.f, s3 = 0.f;
#pragma unroll
          for (int i = 0; i < 16; i += 2) { s0 += bf_lo(u[i] | !t); s1 += bf_hi(u[i]); s2 += bf_lo(u[i + 1] & (t ? ~0u : ~1u)); s3 += bf_hi(u[i + 1]); }
          const uint32_t r = pack2(s0 + s2, s1 + s3);
          st_rlx((uint32_t*)g_res[tag & 1] + own * 128 + w * 32 + (lane & 16) + ((t ^ w) << 2) + ((lane >> 2) & 3), lane & 12 ? r : r | 1);
          ((uint32_t*)g_res[~tag & 1])[own * 128 + word] = 0;
          __syncwarp();
          if (lane == 0) { red_inc(g_xcnt + hg * 64 + 32 + wg * 16); if (w == 0) PROF(wg ? 12 : 30); }
          __syncwarp();
        }
      }
    }
    mbar_wait(bar + B_CSQ, 0);
    QWAIT(15);
    if (wg == 1) bar_sync(6, 256);
    wg_fence();
    wgmma_n128_rs_ta0_tb1(q, fa0, fa1, 0u, 0u, mkdesc(sb + SM_CST + 2048, 512, 0, 1), 1);
    QMMA(15, Q_AOFF(15) / 16, 1);
    wg_commit();
    if (wg == 0) asm volatile("bar.arrive 6, 256;" ::: "memory");
    wg_wait<1>();
    QREL(14);
    wg_wait<0>();
    QREL(15);
    reg_fence<64>(q);
    PROFC(5);
    float yp[4];
    const uint32_t par = tag & 1;
    uint4* ofr = g_ofr + (mb * 16 + hg * 2) * 1024 + (warp * 16 + g) * 8;
#define O_MMA(H, F, N)                                                                                       \
  do {                                                                                                       \
    wg_fence();                                                                                              \
    _Pragma("unroll") for (int k = 0; k < 4; k++) {                                                          \
      const uint32_t ks = SM_V + (H) * 4096 + k * 1024;                                                      \
      wgmma_n40_rs_ta0_tb1(N + 20 * (k >> 1), F[4 * k], F[4 * k + 1], F[4 * k + 2], F[4 * k + 3],            \
                           mkdesc(sb + ks, SM_ZT + (H) * 1024 + k * 16 - ks, 512, 2), k & 1);                \
    }                                                                                                        \
    wg_commit();                                                                                             \
  } while (0)
#define O_FIN(H, N, o)                                                                                        \
  do {                                                                                                       \
    reg_fence<40>(N);                                                                                        \
    const float *np = N, *nm = N + 20;                                                                       \
    const float d0 = rcp(fmaf(np[16], nm[17], fmaf(nm[16], np[17], 1e-6f * np[17] * nm[17])));               \
    const float d1 = rcp(fmaf(np[18], nm[19], fmaf(nm[18], np[19], 1e-6f * np[19] * nm[19])));               \
    const float bp0 = nm[17] * d0, bm0 = np[17] * d0, bp1 = nm[19] * d1, bm1 = np[19] * d1;                  \
    _Pragma("unroll") for (int j = 0; j < 4; j++) {                                                          \
      o[2 * j] = pack2(fmaf(np[4 * j], bp0, nm[4 * j] * bm0), fmaf(np[4 * j + 1], bp0, nm[4 * j + 1] * bm0)); \
      o[2 * j + 1] = pack2(fmaf(np[4 * j + 2], bp1, nm[4 * j + 2] * bm1), fmaf(np[4 * j + 3], bp1, nm[4 * j + 3] * bm1)); \
    }                                                                                                        \
  } while (0)
#define O_STG(H, o)                                                                                          \
  _Pragma("unroll") for (int u = 0; u < 2; u++) {                                                            \
    uint32_t v_[4];                                                                                          \
    _Pragma("unroll") for (int j = 0; j < 4; j++) v_[j] = lop_select(o[2 * j + u], parm, vword == j);        \
    st_rlx128(ofr + ((H) >> 1) * 1024 + u * 64 + ((((H) & 1) * 4 + t) ^ g), v_[0], v_[1], v_[2], v_[3]);     \
  }
    uint32_t gf[32], ao[16];
    const uint32_t parm = 0u - par, vword = ((t ^ g) & 1) == (g >> 2) ? g & 3 : 4;
    const float rh0 = 0.5f * st0.y, rh1 = 0.5f * st1.y, mh0 = st0.x * rh0, mh1 = st1.x * rh1;
#define GATE_LD(J) ldsm4(sb + ((J) >> 2 ? SM_X1 : SM_X0) + sw128 + (((((J) & 3) * 2 + hi16) ^ x128) << 4), gf[4 * (J)], gf[4 * (J) + 1], gf[4 * (J) + 2], gf[4 * (J) + 3])
#define GATE(I0, I1)                                                                                         \
  _Pragma("unroll") for (int i = (I0); i < (I1); i++) {                                                      \
    const float rs = (i & 1) ? rh1 : rh0, mh = (i & 1) ? mh1 : mh0;                                          \
    const float h0 = fmaf(bf_lo(gf[i]), rs, mh), h1 = fmaf(bf_hi(gf[i]), rs, mh);                            \
    gf[i] = pack2(fmaf(h0, tanh_approx(h0), h0), fmaf(h1, tanh_approx(h1), h1));                             \
  }
#define GATE_PIN(I0, I1) do { uint32_t o_ = 0; _Pragma("unroll") for (int i = (I0); i < (I1); i++) o_ |= gf[i]; SCHED_PIN(__uint_as_float(o_)); } while (0)
    {
      float p[64], na[40], nb[40];
      uint32_t fa[16], fb[16];
      {
        uint32_t nq[4] = {0u, 0u, 0u, 0u};
        PHI_PROJ(p, q, 0, 2);
        SCHED_FENCE();
        PHI_PROJ(p, q, 2, 4);
        const bool unsafe = softmax_unsafe(nq, c0 * c0 * wn, c1 * c1 * wn);
        if (TW == 0) mbar_wait(bar + B_TILE, 0);
        wg_wait<0>();
        reg_fence<64>(p);
        PROFC(24);
        if (__builtin_expect(unsafe, 0)) softmax_shift(p, c0, c1);
      }
      float dn[32];
#define DN_PART(A, B)                                                                                        \
  do {                                                                                                       \
    wg_fence();                                                                                              \
    _Pragma("unroll") for (int i = (A); i < (B); i++)                                                        \
      wgmma_n8_ss_ta1_tb1(dn + 4 * (i >> 1), mkdesc(sb + (i >> 3) * Q_STAGE + (i & 7) * 2048, 16, 1024, 1, wg * (2 * Q_STAGE / 16)), \
                          mkdesc(sb + SM_HT + (i & 1) * 256, 128, 128, 0), i & 1);                           \
  } while (0)
#define F_PIN(F, A, B) do { uint32_t o_ = 0; _Pragma("unroll") for (int i = (A); i < (B); i++) o_ |= F[8 + i]; SCHED_PIN(__uint_as_float(o_)); } while (0)
#define RMMA(J, A, ACCUM)                                                                                    \
  do {                                                                                                       \
    wg_fence();                                                                                              \
    _Pragma("unroll") for (int k = 0; k < 4; k++)                                                            \
      wgmma_n128_rs_ta0_tb1(q, (A)[4 * k], (A)[4 * k + 1], (A)[4 * k + 2], (A)[4 * k + 3],                   \
                            mkdesc(sb + 16384 + k * 2048, 8192, 1024, 1, ((J) & 3) * (Q_STAGE / 16)), k ? 1 : (ACCUM)); \
    wg_commit();                                                                                             \
  } while (0)
#define RSTEP(J, A, ACCUM) do { QWAIT(J); RMMA(J, A, ACCUM); } while (0)
      PROFC(4);
      q_exp(p, c0, c1, fa);
      if (TW == 1) { F_PIN(fa, 0, 8); mbar_wait(bar + B_TILE, 0); }
      if (TW == 2) { q_exp(p + 16, c0, c1, fb); F_PIN(fb, 0, 8); mbar_wait(bar + B_TILE, 0); }
      O_MMA(0, fa, na);
      if (TW != 2) q_exp(p + 16, c0, c1, fb);
      O_MMA(1, fb, nb);
      PROFC(25);
      wg_wait<1>();
      O_FIN(0, na, ao);
      O_STG(0, ao);
      wg_wait<0>();
      O_FIN(1, nb, (ao + 8));
      O_STG(1, (ao + 8));
      PROFC(28);
      RSTEP(16, ao, 0);
      SCHED_FENCE();
      q_exp(p + 32, c0, c1, fa);
      F_PIN(fa, 0, 8);
      mbar_wait(bar + B_H, 0);
      mbar_wait(bar + B_DN, 0);
      PROFC(45);
      DN_PART(0, 4);
      SCHED_FENCE();
      q_exp<0, 2>(p + 48, c0, c1, fb);
      F_PIN(fb, 0, 2);
      DN_PART(4, 8);
      SCHED_FENCE();
      q_exp<2, 4>(p + 48, c0, c1, fb);
      F_PIN(fb, 2, 4);
      DN_PART(8, 12);
      SCHED_FENCE();
      q_exp<4, 6>(p + 48, c0, c1, fb);
      F_PIN(fb, 4, 6);
      DN_PART(12, 16);
      wg_commit();
      SCHED_FENCE();
      q_exp<6, 8>(p + 48, c0, c1, fb);
      F_PIN(fb, 6, 8);
      wg_wait<0>();
      reg_fence<32>(dn);
      if (lane == 0) mbar_arrive(bar + B_DND);
      QREL(16);
#pragma unroll
      for (int i = 0; i < 4; i++) yp[i] = t & 2 ? (t & 1 ? dn[24 + 2 * i] : dn[16 + 2 * i]) : (t & 1 ? dn[8 + 2 * i] : dn[2 * i]);
      PROFC(29);
      mbar_wait(bar + B_TILE + 8, 0);
      PROFC(23);
      if (bid < NFFN) {
        float* y = g_y[par ^ 1][bid & 7] + wg * 512 + t * 128 + w * 16 + g;
#pragma unroll
        for (int i = 0; i < 4; i++) red1(y + (i >> 1) * 64 + (i & 1) * 8, yp[i]);
      }
      SCHED_FENCE();
      O_MMA(2, fa, na);
      O_MMA(3, fb, nb);
      __syncwarp();
      if (lane == 0) mbar_arrive(bar + B_YD);
      wg_wait<1>();
      O_FIN(2, na, ao);
      O_STG(2, ao);
      wg_wait<0>();
      O_FIN(3, nb, (ao + 8));
      O_STG(3, (ao + 8));
      PROFC(6);
    }
    RSTEP(17, ao, 1);
    SCHED_FENCE();
    GATE_LD(0); GATE_LD(1);
    GATE(0, 4);
    GATE_PIN(0, 4);
#define GSTEP(J, I) do { QNEXT(J); if ((I) < 7) GATE_LD(((I) + 1) & 7); GATE(4 * (I), 4 * (I) + 4); GATE_PIN(4 * (I), 4 * (I) + 4); } while (0)
    GSTEP(18, 1); GSTEP(19, 2); GSTEP(20, 3); GSTEP(21, 4); GSTEP(22, 5); GSTEP(23, 6); GSTEP(24, 7);
#pragma unroll 1
    for (int j = 25; j < 32 - TAILN; j++) QPLAIN(j);
    if (wg == 1) bar_sync(6, 256);
#pragma unroll 1
    for (int j = 32 - TAILN; j < 32; j++) QSTEP_A(j, (j & 3) * (Q_STAGE / 16), 1);
    if (wg == 0) asm volatile("bar.arrive 6, 256;" ::: "memory");
    mbar_wait(bar + B_UPD, 0);
    {
      const int sel = __float_as_int(lds32(sb + SM_UPD + 256)) - (wg * 64 + w * 16 + g);
      if (sel == 0 || sel == 8) {
#pragma unroll
        for (int j = 0; j < 16; j++) {
          const uint32_t u = __float_as_uint(lds32(sb + SM_UPD + j * 16 + t * 4));
          if (sel) gf[2 * j + 1] = u; else gf[2 * j] = u;
        }
      }
      __syncwarp();
      uint32_t xf[32];
#pragma unroll
      for (int j = 0; j < 8; j++)
        ldsm4(sb + (j >> 2 ? SM_X1 : SM_X0) + sw128 + ((((j & 3) * 2 + hi16) ^ x128) << 4), xf[4 * j], xf[4 * j + 1], xf[4 * j + 2], xf[4 * j + 3]);
      wg_wait<0>();
      reg_fence<64>(q);
      PROFC(8);
#pragma unroll
      for (int j = 0; j < 8; j++) {
        uint32_t o[4];
#pragma unroll
        for (int i = 0; i < 4; i++) o[i] = badd2(xf[4 * j + i], bmul2(pack2(q[8 * j + 2 * i], q[8 * j + 2 * i + 1]), gf[4 * j + i]));
        stsm4(sb + (j >> 2 ? SM_X1 : SM_X0) + sw128 + ((((j & 3) * 2 + hi16) ^ x128) << 4), o[0], o[1], o[2], o[3]);
      }
    }
    fence_async_smem();
    bar_sync(2 + wg, 128);
    if (w == 0 && elect_one()) {
      tma_store2d(&mOut, sb + SM_X0 + wg * 8192, hg * 128, mb * 128 + wg * 64);
      tma_store2d(&mOut, sb + SM_X1 + wg * 8192, hg * 128 + 64, mb * 128 + wg * 64);
      bulk_commit();
      bulk_wait_read0();
      if (wg == 1) { PROF(9); PROFT(33); PROF_DUMP; }
    }
  }
}

typedef CUresult (*EncodeFn)(CUtensorMap*, CUtensorMapDataType, cuuint32_t, void*, const cuuint64_t*, const cuuint64_t*, const cuuint32_t*,
                             const cuuint32_t*, CUtensorMapInterleave, CUtensorMapSwizzle, CUtensorMapL2promotion, CUtensorMapFloatOOBfill);

CUtensorMap make_map(EncodeFn enc, const void* ptr, int rank, const cuuint64_t* dims, const cuuint64_t* strides, const cuuint32_t* box, CUtensorMapSwizzle sw) {
  CUtensorMap m;
  const cuuint32_t es[5] = {1, 1, 1, 1, 1};
  enc(&m, CU_TENSOR_MAP_DATA_TYPE_BFLOAT16, rank, (void*)ptr, dims, strides, box, es, CU_TENSOR_MAP_INTERLEAVE_NONE, sw,
      CU_TENSOR_MAP_L2_PROMOTION_L2_128B, CU_TENSOR_MAP_FLOAT_OOB_FILL_NONE);
  return m;
}

}

extern "C" void kernel_launch(void* const* d_in, const int* in_sizes, int n_in, void* d_out, int out_size) {
  static EncodeFn enc = nullptr;
  static int by_sm = 0;
  if (!enc) {
    void* fn = nullptr;
    cudaDriverEntryPointQueryResult qr;
    cudaGetDriverEntryPoint("cuTensorMapEncodeTiled", &fn, cudaEnableDefault, &qr);
    enc = (EncodeFn)fn;
    cudaFuncSetAttribute(fused_kernel, cudaFuncAttributeMaxDynamicSharedMemorySize, SM_TOTAL);
    int dev = 0, sms = 0;
    cudaGetDevice(&dev);
    cudaDeviceGetAttribute(&sms, cudaDevAttrMultiProcessorCount, dev);
    by_sm = BY_SM && sms == NCTA + NSPARE;
  }
  Params P;
  P.by_sm = by_sm;
  P.x = (const __nv_bfloat16*)d_in[0];
  P.wqkv = (const __nv_bfloat16*)d_in[1];
  const void* wphi = d_in[2];
  P.wo = (const __nv_bfloat16*)d_in[3];
  P.w_r = (const __nv_bfloat16*)d_in[5];
  P.w_gate = (const __nv_bfloat16*)d_in[6];
  P.w_up = (const __nv_bfloat16*)d_in[7];
  P.w_down = (const __nv_bfloat16*)d_in[8];

  const cuuint64_t dX[2] = {DM, SEQ}, sX[1] = {DM * 2};
  const cuuint32_t b128[2] = {64, 128}, b64[2] = {64, 64};
  const cuuint64_t dW[4] = {64, DM, 16, 3}, sW[3] = {3 * DM * 2, 128, DM * 2};
  const cuuint32_t bKV[4] = {64, 64, 2, 2}, bQ[4] = {64, 64, 2, 1};
  const cuuint64_t dO[3] = {64, DM, 16}, sO[2] = {DM * 2, 128};
  const cuuint32_t bO[3] = {64, 64, 2};
  const cuuint64_t dP[2] = {32, 1024}, sP[1] = {64};
  const cuuint32_t bP[2] = {32, 128};
  CUtensorMap mX = make_map(enc, P.x, 2, dX, sX, b128, CU_TENSOR_MAP_SWIZZLE_128B);
  CUtensorMap mWkv = make_map(enc, P.wqkv, 4, dW, sW, bKV, CU_TENSOR_MAP_SWIZZLE_128B);
  CUtensorMap mWq = make_map(enc, P.wqkv, 4, dW, sW, bQ, CU_TENSOR_MAP_SWIZZLE_128B);
  CUtensorMap mWo = make_map(enc, P.wo, 3, dO, sO, bO, CU_TENSOR_MAP_SWIZZLE_128B);
  CUtensorMap mPhi = make_map(enc, wphi, 2, dP, sP, bP, CU_TENSOR_MAP_SWIZZLE_64B);
  const cuuint64_t dWp[5] = {DM, 2, 4, 4, DM / 32}, sWp[4] = {DM * 2, 8 * DM * 2, 2 * DM * 2, 32 * DM * 2};
  const cuuint32_t bWp[5] = {64, 2, 4, 4, 2};
  CUtensorMap mWp = make_map(enc, P.wo, 5, dWp, sWp, bWp, CU_TENSOR_MAP_SWIZZLE_128B);
  CUtensorMap mOut = make_map(enc, d_out, 2, dX, sX, b64, CU_TENSOR_MAP_SWIZZLE_128B);
  const cuuint64_t dWc[2] = {3 * DM, DM}, sWc[1] = {3 * DM * 2}, dG[2] = {FF, DM}, sG[1] = {FF * 2}, dD[3] = {64, FF, 16};
  const cuuint32_t b32[2] = {32, 32}, bD[3] = {64, 32, 4};
  CUtensorMap mWc = make_map(enc, P.wqkv, 2, dWc, sWc, b32, CU_TENSOR_MAP_SWIZZLE_NONE);
  CUtensorMap mG = make_map(enc, P.w_gate, 2, dG, sG, b32, CU_TENSOR_MAP_SWIZZLE_NONE);
  CUtensorMap mU = make_map(enc, P.w_up, 2, dG, sG, b32, CU_TENSOR_MAP_SWIZZLE_NONE);
  CUtensorMap mD = make_map(enc, P.w_down, 3, dD, sO, bD, CU_TENSOR_MAP_SWIZZLE_128B);
  const cuuint64_t dXs[3] = {256, SEQ, 4}, sXs[2] = {DM * 2, 512};
  const cuuint32_t bXs[3] = {256, 16, 2};
  CUtensorMap mXs = make_map(enc, P.x, 3, dXs, sXs, bXs, CU_TENSOR_MAP_SWIZZLE_NONE);
  const cuuint64_t dG2[4] = {64, DM, FF / 64, 1}, sG2[3] = {FF * 2, 128, (cuuint64_t)FF * DM * 2};
  CUtensorMap mG2 = make_map(enc, P.w_gate, 4, dG2, sG2, bQ, CU_TENSOR_MAP_SWIZZLE_128B);
  CUtensorMap mU2 = make_map(enc, P.w_up, 4, dG2, sG2, bQ, CU_TENSOR_MAP_SWIZZLE_128B);
  fused_kernel<<<NCTA + NSPARE, 384, SM_TOTAL, cudaStreamPerThread>>>(mX, mWkv, mWq, mWo, mPhi, mWp, mOut, mWc, mG, mU, mD, mXs, mG2, mU2, P);
}
```

```cpp
#include <cuda_runtime.h>
#include <cuda_bf16.h>
#include <cuda.h>
#include <stdint.h>

namespace {

constexpr int SEQ = 2048, DM = 1024, FF = 3584;
constexpr int NCTA = 128;
constexpr int NSPARE = 4;
constexpr int NFFN = FF / 32;
#define GN 6
#define G8 2
constexpr int GROWS = (3 * GN + G8) * 32;
#define TAILN 2
#define KTAIL 1
#define XS_EARLY 1
#define PF_FIRST 2
#define PF_W 5
#define PF_PRE 1
#define PFG 0
#define PFD 80
#define BY_SM 1
#define PTAB 0x73216540u
#define ROWSPLIT 1
#define WOT 1
#define PSPLIT 1
#define KSTEPS 4
#define NOVAL 0
#define KCH 1
#define REG_C 224
#define REG_H 56
#define TW 1
#define FENCE_KIND 2
#define ORDER_ALL 1
#define AM_NS 100
constexpr bool FFN_OFF = false;

static_assert(2 * REG_C + REG_H <= 3 * 168, "the register pool of the CTA is 384 x 168");

__device__ uint32_t g_epoch[(NCTA + NSPARE) * 32];
__device__ unsigned long long g_stat[SEQ];
__device__ __align__(128) unsigned long long g_best[NCTA];
__device__ __align__(16) float g_y[2][8][DM];
__device__ __align__(128) uint32_t g_ycnt[64];
__device__ __align__(128) uint32_t g_xcnt[8 * 64];
__device__ __align__(128) uint4 g_res[2][32 * 256];
__device__ __align__(16) float g_cs[5 * DM];
__device__ __align__(128) float g_gp[2 * FF];
__device__ uint4 g_part[8 * 2 * 16 * 16 * 32];
__device__ __align__(16) float g_zpart[8 * 2 * 16 * 16 * 8];
__device__ __align__(128) float g_zres[32 * 64];
__device__ __align__(1024) uint4 g_ofr[16 * 16 * 1024];
#define PROF(i)
#define PROFT(i)
#define PROFC(i)
#define PROF_DUMP
#define PW0(J)
#define PW1(J)

constexpr uint32_t KV_STAGE = 49152, Q_STAGE = 32768;
constexpr uint32_t SM_V = 147456;
constexpr uint32_t SM_PHI = 163840;
constexpr uint32_t SM_XST = 147456;
constexpr uint32_t SM_FST = 172032;
constexpr uint32_t SM_PST0 = 196608, SM_PST1 = SM_PHI + 8192;
constexpr uint32_t SM_X0 = 131072, SM_X1 = SM_PHI + 16384;
constexpr uint32_t SM_WPHI = 204800;
constexpr uint32_t SM_ZT = 212992;
constexpr uint32_t SM_SDT = 217088;
constexpr uint32_t SM_CST = 219136;
constexpr uint32_t SM_HT = 222720;
constexpr uint32_t SM_STAT = 223232;
constexpr uint32_t SM_XSEL = 224256;
constexpr uint32_t SM_RED = 228352;
constexpr uint32_t SM_ROWS = SM_RED + 832;
constexpr uint32_t SM_GRED = SM_XSEL + 3072;
static_assert(GROWS <= 768, "xsel area");
constexpr uint32_t SM_UPD = 229632;
constexpr uint32_t SM_BAR = 230016;
constexpr uint32_t SM_PROF = 230464;
constexpr uint32_t SM_SINK = 231104;
constexpr uint32_t SM_TOTAL = 231616;
constexpr uint32_t SB = 1024;
constexpr uint32_t B_FULLKV = 0  , B_FST = 24  , B_XFULL = 88  , B_XST = 104  , B_WPHI = 120, B_CS = 128, B_CSQ = 136, B_UPD = 144,
                   B_H = 152, B_DN = 160, B_XS = 168, B_TILE = 176  , B_RES = 192  , B_PART = 208  ,
B_AIN = 224  ,
                   B_FULLQ = 288  ,
                   B_FFN = 320,
                   B_EMPTYKV = 328  , B_EMPTYQ = 352  , B_KVST = 384  , B_YD = 400, B_PHI = 408  , B_DND = 424, B_END = 432;

__device__ __forceinline__ uint32_t smem_u32(const void* p) { return (uint32_t)__cvta_generic_to_shared(p); }
__device__ __forceinline__ void mbar_init(uint32_t bar, uint32_t cnt) { asm volatile("mbarrier.init.shared::cta.b64 [%0], %1;" ::"r"(bar), "r"(cnt) : "memory"); }
__device__ __forceinline__ void mbar_expect_tx(uint32_t bar, uint32_t bytes) { asm volatile("mbarrier.arrive.expect_tx.shared::cta.b64 _, [%0], %1;" ::"r"(bar), "r"(bytes) : "memory"); }
__device__ __forceinline__ void mbar_arrive2(uint32_t bar) { asm volatile("mbarrier.arrive.shared::cta.b64 _, [%0], 2;" ::"r"(bar) : "memory"); }
__device__ __forceinline__ void mbar_arrive(uint32_t bar) { asm volatile("mbarrier.arrive.shared::cta.b64 _, [%0];" ::"r"(bar) : "memory"); }
__device__ __forceinline__ void mbar_wait(uint32_t bar, uint32_t parity) {
  asm volatile("{\n.reg .pred p;\nLW:\nmbarrier.try_wait.parity.shared::cta.b64 p, [%0], %1;\n@!p bra LW;\n}" ::"r"(bar), "r"(parity) : "memory");
}
__device__ __forceinline__ bool mbar_test(uint32_t bar, uint32_t parity) {
  uint32_t ok;
  asm volatile("{\n.reg .pred p;\nmbarrier.test_wait.parity.shared::cta.b64 p, [%1], %2;\nselp.u32 %0, 1, 0, p;\n}" : "=r"(ok) : "r"(bar), "r"(parity) : "memory");
  return ok;
}
__device__ __forceinline__ int lane_id() { int l; asm volatile("mov.u32 %0, %%laneid;" : "=r"(l)); return l; }
template <int C> __device__ __forceinline__ void sched_fence_(int zero) {
  asm volatile("{\n.reg .pred p;\nsetp.eq.s32 p, %0, %1;\n@p trap;\n}" ::"r"(zero), "n"(C) : "memory");
}
#define SCHED_FENCE() sched_fence_<1000 + __COUNTER__>(zero)
#define SCHED_PIN(V) sched_fence_<1000 + __COUNTER__>(zero & __float_as_int(V))
__device__ __forceinline__ bool elect_one() {
  uint32_t p; asm volatile("{ .reg .pred P; elect.sync _|P, 0xffffffff; selp.u32 %0, 1, 0, P; }" : "=r"(p)); return p;
}
__device__ __forceinline__ void tma2d(uint32_t dst, const CUtensorMap* m, int x, int y, uint32_t bar) {
  asm volatile("cp.async.bulk.tensor.2d.shared::cluster.global.mbarrier::complete_tx::bytes [%0], [%1, {%3, %4}], [%2];" ::"r"(dst), "l"(m), "r"(bar), "r"(x), "r"(y) : "memory");
}
__device__ __forceinline__ void tma3d(uint32_t dst, const CUtensorMap* m, int x, int y, int z, uint32_t bar) {
  asm volatile("cp.async.bulk.tensor.3d.shared::cluster.global.mbarrier::complete_tx::bytes [%0], [%1, {%3, %4, %5}], [%2];" ::"r"(dst), "l"(m), "r"(bar), "r"(x), "r"(y), "r"(z) : "memory");
}
__device__ __forceinline__ void tma4d(uint32_t dst, const CUtensorMap* m, int x, int y, int z, int w, uint32_t bar) {
  asm volatile("cp.async.bulk.tensor.4d.shared::cluster.global.mbarrier::complete_tx::bytes [%0], [%1, {%3, %4, %5, %6}], [%2];" ::"r"(dst), "l"(m), "r"(bar), "r"(x), "r"(y), "r"(z), "r"(w) : "memory");
}
__device__ __forceinline__ void tma5d(uint32_t dst, const CUtensorMap* m, int x, int v, uint32_t bar) {
  asm volatile("cp.async.bulk.tensor.5d.shared::cluster.global.mbarrier::complete_tx::bytes [%0], [%1, {%3, %5, %5, %5, %4}], [%2];" ::"r"(dst), "l"(m), "r"(bar), "r"(x), "r"(v), "r"(0) : "memory");
}
__device__ __forceinline__ void tma_store2d(const CUtensorMap* m, uint32_t src, int x, int y) {
  asm volatile("cp.async.bulk.tensor.2d.global.shared::cta.bulk_group [%0, {%2, %3}], [%1];" ::"l"(m), "r"(src), "r"(x), "r"(y) : "memory");
}
__device__ __forceinline__ void bulk_load(uint32_t dst, const void* src, uint32_t bytes, uint32_t bar) {
  asm volatile("cp.async.bulk.shared::cluster.global.mbarrier::complete_tx::bytes [%0], [%1], %2, [%3];" ::"r"(dst), "l"(src), "r"(bytes), "r"(bar) : "memory");
}
__device__ __forceinline__ void bulk_commit() { asm volatile("cp.async.bulk.commit_group;" ::: "memory"); }
__device__ __forceinline__ void bulk_wait0() { asm volatile("cp.async.bulk.wait_group 0;" ::: "memory"); }
__device__ __forceinline__ void bulk_wait_read0() { asm volatile("cp.async.bulk.wait_group.read 0;" ::: "memory"); }
__device__ __forceinline__ void prefetch_l2(const void* p) { asm volatile("prefetch.global.L2 [%0];" ::"l"(p) : "memory"); }
__device__ __forceinline__ void touch_l2(const void* p, int lane) { asm volatile("cp.async.cg.shared.global.L2::128B [%0], [%1], 16;" ::"r"(SB + SM_SINK + lane * 16), "l"(p) : "memory"); }
__device__ __forceinline__ void prefetch_map(const CUtensorMap* m) { asm volatile("prefetch.tensormap [%0];" ::"l"(m) : "memory"); }
__device__ __forceinline__ void fence_async_smem() { asm volatile("fence.proxy.async.shared::cta;" ::: "memory"); }
__device__ __forceinline__ void fence_async_global() { asm volatile("fence.proxy.async.global;" ::: "memory"); }
__device__ __forceinline__ void bar_sync(int id, int n) { asm volatile("bar.sync %0, %1;" ::"r"(id), "r"(n) : "memory"); }
__device__ __forceinline__ void wg_fence() { asm volatile("wgmma.fence.sync.aligned;" ::: "memory"); }
__device__ __forceinline__ void wg_commit() { asm volatile("wgmma.commit_group.sync.aligned;" ::: "memory"); }
template <int N> __device__ __forceinline__ void wg_wait() { asm volatile("wgmma.wait_group.sync.aligned %0;" ::"n"(N) : "memory"); }
template <int N> __device__ __forceinline__ void reg_fence(uint32_t* r) {
#pragma unroll
  for (int i = 0; i < N; i++) asm volatile("" : "+r"(r[i])::"memory");
}
template <int N> __device__ __forceinline__ void reg_fence(float* r) {
#pragma unroll
  for (int i = 0; i < N; i++) asm volatile("" : "+f"(r[i])::"memory");
}
__device__ __forceinline__ uint64_t mkdesc(uint32_t addr, uint32_t lbo, uint32_t sbo, uint32_t swz, uint32_t dyn = 0) {
  const uint32_t lo = ((addr >> 4) | ((lbo >> 4) << 16)) + dyn;
  const uint32_t hi = (sbo >> 4) | (swz << 30);
  uint64_t d;
  asm("mov.b64 %0, {%1, %2};" : "=l"(d) : "r"(lo), "r"(hi));
  return d;
}
__device__ __forceinline__ void stsm4(uint32_t addr, uint32_t a, uint32_t b, uint32_t c, uint32_t d) {
  asm volatile("stmatrix.sync.aligned.m8n8.x4.shared.b16 [%0], {%1, %2, %3, %4};" ::"r"(addr), "r"(a), "r"(b), "r"(c), "r"(d) : "memory");
}
__device__ __forceinline__ void ldsm4(uint32_t addr, uint32_t& a, uint32_t& b, uint32_t& c, uint32_t& d) {
  asm volatile("ldmatrix.sync.aligned.m8n8.x4.shared.b16 {%0, %1, %2, %3}, [%4];" : "=r"(a), "=r"(b), "=r"(c), "=r"(d) : "r"(addr) : "memory");
}
__device__ __forceinline__ uint32_t pack2(float lo, float hi) { uint32_t r; asm("cvt.rn.bf16x2.f32 %0, %1, %2;" : "=r"(r) : "f"(hi), "f"(lo)); return r; }
__device__ __forceinline__ uint32_t bsub2(uint32_t a, uint32_t b) { uint32_t r; asm("sub.rn.bf16x2 %0, %1, %2;" : "=r"(r) : "r"(a), "r"(b)); return r; }
__device__ __forceinline__ uint32_t badd2(uint32_t a, uint32_t b) { uint32_t r; asm("add.rn.bf16x2 %0, %1, %2;" : "=r"(r) : "r"(a), "r"(b)); return r; }
__device__ __forceinline__ uint32_t bmul2(uint32_t a, uint32_t b) { uint32_t r; asm("mul.rn.bf16x2 %0, %1, %2;" : "=r"(r) : "r"(a), "r"(b)); return r; }
__device__ __forceinline__ float bf_lo(uint32_t v) { return __uint_as_float(v << 16); }
__device__ __forceinline__ float bf_hi(uint32_t v) { return __uint_as_float(v & 0xffff0000u); }
__device__ __forceinline__ float bf_round(float v) { return bf_lo(pack2(v, 0.f)); }
__device__ __forceinline__ float ex2(float v) { float r; asm("ex2.approx.ftz.f32 %0, %1;" : "=f"(r) : "f"(v)); return r; }
__device__ __forceinline__ float rcp(float v) { float r; asm("rcp.approx.ftz.f32 %0, %1;" : "=f"(r) : "f"(v)); return r; }
__device__ __forceinline__ float sqrt_approx(float v) { float r; asm("sqrt.approx.f32 %0, %1;" : "=f"(r) : "f"(v)); return r; }
__device__ __forceinline__ float4 lds128(uint32_t a) { float4 v; asm volatile("ld.shared.v4.f32 {%0, %1, %2, %3}, [%4];" : "=f"(v.x), "=f"(v.y), "=f"(v.z), "=f"(v.w) : "r"(a) : "memory"); return v; }
__device__ __forceinline__ uint4 lds128u(uint32_t a) { uint4 v; asm volatile("ld.shared.v4.u32 {%0, %1, %2, %3}, [%4];" : "=r"(v.x), "=r"(v.y), "=r"(v.z), "=r"(v.w) : "r"(a) : "memory"); return v; }
__device__ __forceinline__ float2 lds64(uint32_t a) { float2 v; asm volatile("ld.shared.v2.f32 {%0, %1}, [%2];" : "=f"(v.x), "=f"(v.y) : "r"(a) : "memory"); return v; }
__device__ __forceinline__ float lds32(uint32_t a) { float v; asm volatile("ld.shared.f32 %0, [%1];" : "=f"(v) : "r"(a) : "memory"); return v; }
__device__ __forceinline__ void sts32(uint32_t a, float v) { asm volatile("st.shared.f32 [%0], %1;" ::"r"(a), "f"(v) : "memory"); }
__device__ __forceinline__ void sts64(uint32_t a, float x, float y) { asm volatile("st.shared.v2.f32 [%0], {%1, %2};" ::"r"(a), "f"(x), "f"(y) : "memory"); }
__device__ __forceinline__ void sts128(uint32_t a, float x, float y, float z, float w) { asm volatile("st.shared.v4.f32 [%0], {%1, %2, %3, %4};" ::"r"(a), "f"(x), "f"(y), "f"(z), "f"(w) : "memory"); }
__device__ __forceinline__ void sts64u(uint32_t a, uint32_t x, uint32_t y) { asm volatile("st.shared.v2.u32 [%0], {%1, %2};" ::"r"(a), "r"(x), "r"(y) : "memory"); }
__device__ __forceinline__ void sts128u(uint32_t a, uint32_t x, uint32_t y, uint32_t z, uint32_t w) { asm volatile("st.shared.v4.u32 [%0], {%1, %2, %3, %4};" ::"r"(a), "r"(x), "r"(y), "r"(z), "r"(w) : "memory"); }
__device__ __forceinline__ uint4 ldg_nc(const void* p) { uint4 v; asm volatile("ld.global.nc.L1::no_allocate.v4.u32 {%0, %1, %2, %3}, [%4];" : "=r"(v.x), "=r"(v.y), "=r"(v.z), "=r"(v.w) : "l"(p)); return v; }
__device__ __forceinline__ float4 ldg_cg4(const float* p) { float4 v; asm volatile("ld.global.cg.v4.f32 {%0, %1, %2, %3}, [%4];" : "=f"(v.x), "=f"(v.y), "=f"(v.z), "=f"(v.w) : "l"(p) : "memory"); return v; }
__device__ __forceinline__ uint32_t ld_acq(const uint32_t* p) { uint32_t v; asm volatile("ld.acquire.gpu.global.u32 %0, [%1];" : "=r"(v) : "l"(p) : "memory"); return v; }
__device__ __forceinline__ uint32_t ld_acq_cta(uint32_t a) { uint32_t v; asm volatile("ld.acquire.cta.shared.u32 %0, [%1];" : "=r"(v) : "r"(a) : "memory"); return v; }
__device__ __forceinline__ void st_rel_cta(uint32_t a, uint32_t v) { asm volatile("st.release.cta.shared.u32 [%0], %1;" ::"r"(a), "r"(v) : "memory"); }
__device__ __forceinline__ unsigned long long ld_rlx64(const unsigned long long* p) { unsigned long long v; asm volatile("ld.relaxed.gpu.global.u64 %0, [%1];" : "=l"(v) : "l"(p) : "memory"); return v; }
__device__ __forceinline__ void st_rlx64(unsigned long long* p, unsigned long long v) { asm volatile("st.relaxed.gpu.global.u64 [%0], %1;" ::"l"(p), "l"(v) : "memory"); }
__device__ __forceinline__ uint4 ld_rlx128(const void* p) {
  uint4 v;
  asm volatile("{ .reg .b128 t; .reg .b64 a, b; ld.relaxed.gpu.global.b128 t, [%4]; mov.b128 {a, b}, t; mov.b64 {%0, %1}, a; mov.b64 {%2, %3}, b; }"
               : "=r"(v.x), "=r"(v.y), "=r"(v.z), "=r"(v.w) : "l"(p) : "memory");
  return v;
}
__device__ __forceinline__ void st_rlx128(void* p, uint32_t x, uint32_t y, uint32_t z, uint32_t w) {
  asm volatile("{ .reg .b128 t; .reg .b64 a, b; mov.b64 a, {%1, %2}; mov.b64 b, {%3, %4}; mov.b128 t, {a, b}; st.relaxed.gpu.global.b128 [%0], t; }"
               ::"l"(p), "r"(x), "r"(y), "r"(z), "r"(w) : "memory");
}
__device__ __forceinline__ void stg128(void* p, uint32_t x, uint32_t y, uint32_t z, uint32_t w) { asm volatile("st.global.v4.u32 [%0], {%1, %2, %3, %4};" ::"l"(p), "r"(x), "r"(y), "r"(z), "r"(w) : "memory"); }
__device__ __forceinline__ void st_rlx(void* p, uint32_t v) { asm volatile("st.relaxed.gpu.global.u32 [%0], %1;" ::"l"(p), "r"(v) : "memory"); }
__device__ __forceinline__ uint32_t lop_select(uint32_t a, uint32_t b, uint32_t m) { uint32_t r; asm("lop3.b32 %0, %1, %2, %3, 0xd8;" : "=r"(r) : "r"(a), "r"(b), "r"(m)); return r; }
__device__ __forceinline__ float unmark(uint32_t v) { return __uint_as_float(v & ~1u); }
__device__ __forceinline__ uint32_t mark(uint32_t v, uint32_t par) { return (v & ~1u) | par; }
__device__ __forceinline__ float tanh_approx(float v) { float r; asm("tanh.approx.f32 %0, %1;" : "=f"(r) : "f"(v)); return r; }
__device__ __forceinline__ void flag_rel(uint32_t* p, uint32_t v) { asm volatile("red.release.gpu.global.max.u32 [%0], %1;" ::"l"(p), "r"(v) : "memory"); }
__device__ __forceinline__ void red1(float* p, float a) { asm volatile("red.global.add.f32 [%0], %1;" ::"l"(p), "f"(a) : "memory"); }
__device__ __forceinline__ void red_inc(uint32_t* p) { asm volatile("red.relaxed.gpu.global.add.u32 [%0], 1;" ::"l"(p) : "memory"); }
__device__ __forceinline__ void red_rel(uint32_t* p) { asm volatile("red.release.gpu.global.add.u32 [%0], 1;" ::"l"(p) : "memory"); }
__device__ __forceinline__ void red4(float* p, float a, float b, float c, float d) { asm volatile("red.global.add.v4.f32 [%0], {%1, %2, %3, %4};" ::"l"(p), "f"(a), "f"(b), "f"(c), "f"(d) : "memory"); }
constexpr int SPIN_MAX = 100000;
__device__ __forceinline__ uint32_t ld_rlx(const uint32_t* p) { uint32_t v; asm volatile("ld.relaxed.gpu.global.u32 %0, [%1];" : "=r"(v) : "l"(p) : "memory"); return v; }
template <int NS = 0> __device__ __forceinline__ void wait_hint(const uint32_t* p, uint32_t target) {
#pragma unroll 1
  for (int i = 0; i < SPIN_MAX; i++) { if ((int)(ld_rlx(p) - target) >= 0) break; if (NS) __nanosleep(NS); }
}
template <int NS> __device__ __forceinline__ void wait_cnt(const uint32_t* p, uint32_t target) {
#pragma unroll 1
  for (int i = 0; i < SPIN_MAX; i++) { if ((int)(ld_rlx(p) - target) >= 0) break; if (NS) __nanosleep(NS); }
  (void)ld_acq(p);
}
template <int NS> __device__ __forceinline__ unsigned long long wait_tag(const unsigned long long* p, uint32_t tag) {
  unsigned long long v = 0;
#pragma unroll 1
  for (int i = 0; i < SPIN_MAX; i++) { v = ld_rlx64(p); if ((uint32_t)(v >> 32) == tag) break; if (NS) __nanosleep(NS); }
  return v;
}
__device__ __forceinline__ float silu_f(float v) { return v * rcp(1.f + ex2(-1.4426950408889634f * v)); }

__device__ __forceinline__ void wgmma_n8_ss_ta1_tb0(float* d, uint64_t da, uint64_t db, bool accumulate) {
  if (accumulate) {
    asm volatile("{\n.reg .pred p;\nsetp.ne.b32 p, 1, 0;\n"
      "wgmma.mma_async.sync.aligned.m64n8k16.f32.bf16.bf16 "
      "{%0, %1, %2, %3}, "
      "%4, %5, p, 1, 1, 1, 0;\n}\n"
      : "+f"(d[0]), "+f"(d[1]), "+f"(d[2]), "+f"(d[3])
      : "l"(da), "l"(db));
  } else {
    asm volatile("{\n.reg .pred p;\nsetp.ne.b32 p, 0, 0;\n"
      "wgmma.mma_async.sync.aligned.m64n8k16.f32.bf16.bf16 "
      "{%0, %1, %2, %3}, "
      "%4, %5, p, 1, 1, 1, 0;\n}\n"
      : "=f"(d[0]), "=f"(d[1]), "=f"(d[2]), "=f"(d[3])
      : "l"(da), "l"(db));
  }
}
__device__ __forceinline__ void wgmma_n8_ss_ta1_tb1(float* d, uint64_t da, uint64_t db, bool accumulate) {
  if (accumulate) {
    asm volatile("{\n.reg .pred p;\nsetp.ne.b32 p, 1, 0;\n"
      "wgmma.mma_async.sync.aligned.m64n8k16.f32.bf16.bf16 "
      "{%0, %1, %2, %3}, "
      "%4, %5, p, 1, 1, 1, 1;\n}\n"
      : "+f"(d[0]), "+f"(d[1]), "+f"(d[2]), "+f"(d[3])
      : "l"(da), "l"(db));
  } else {
    asm volatile("{\n.reg .pred p;\nsetp.ne.b32 p, 0, 0;\n"
      "wgmma.mma_async.sync.aligned.m64n8k16.f32.bf16.bf16 "
      "{%0, %1, %2, %3}, "
      "%4, %5, p, 1, 1, 1, 1;\n}\n"
      : "=f"(d[0]), "=f"(d[1]), "=f"(d[2]), "=f"(d[3])
      : "l"(da), "l"(db));
  }
}
__device__ __forceinline__ void wgmma_n32_rs_ta0_tb1(float* d, uint32_t a0, uint32_t a1, uint32_t a2, uint32_t a3, uint64_t db, bool accumulate) {
  if (accumulate) {
    asm volatile("{\n.reg .pred p;\nsetp.ne.b32 p, 1, 0;\n"
      "wgmma.mma_async.sync.aligned.m64n32k16.f32.bf16.bf16 "
      "{%0, %1, %2, %3, %4, %5, %6, %7, %8, %9, %10, %11, %12, %13, %14, %15}, "
      "{%16, %17, %18, %19}, %20, p, 1, 1, 1;\n}\n"
      : "+f"(d[0]), "+f"(d[1]), "+f"(d[2]), "+f"(d[3]), "+f"(d[4]), "+f"(d[5]), "+f"(d[6]), "+f"(d[7]), "+f"(d[8]), "+f"(d[9]), "+f"(d[10]), "+f"(d[11]), "+f"(d[12]), "+f"(d[13]), "+f"(d[14]), "+f"(d[15])
      : "r"(a0), "r"(a1), "r"(a2), "r"(a3), "l"(db));
  } else {
    asm volatile("{\n.reg .pred p;\nsetp.ne.b32 p, 0, 0;\n"
      "wgmma.mma_async.sync.aligned.m64n32k16.f32.bf16.bf16 "
      "{%0, %1, %2, %3, %4, %5, %6, %7, %8, %9, %10, %11, %12, %13, %14, %15}, "
      "{%16, %17, %18, %19}, %20, p, 1, 1, 1;\n}\n"
      : "=f"(d[0]), "=f"(d[1]), "=f"(d[2]), "=f"(d[3]), "=f"(d[4]), "=f"(d[5]), "=f"(d[6]), "=f"(d[7]), "=f"(d[8]), "=f"(d[9]), "=f"(d[10]), "=f"(d[11]), "=f"(d[12]), "=f"(d[13]), "=f"(d[14]), "=f"(d[15])
      : "r"(a0), "r"(a1), "r"(a2), "r"(a3), "l"(db));
  }
}
__device__ __forceinline__ void wgmma_n40_rs_ta0_tb1(float* d, uint32_t a0, uint32_t a1, uint32_t a2, uint32_t a3, uint64_t db, bool accumulate) {
  if (accumulate) {
    asm volatile("{\n.reg .pred p;\nsetp.ne.b32 p, 1, 0;\n"
      "wgmma.mma_async.sync.aligned.m64n40k16.f32.bf16.bf16 "
      "{%0, %1, %2, %3, %4, %5, %6, %7, %8, %9, %10, %11, %12, %13, %14, %15, %16, %17, %18, %19}, "
      "{%20, %21, %22, %23}, %24, p, 1, 1, 1;\n}\n"
      : "+f"(d[0]), "+f"(d[1]), "+f"(d[2]), "+f"(d[3]), "+f"(d[4]), "+f"(d[5]), "+f"(d[6]), "+f"(d[7]), "+f"(d[8]), "+f"(d[9]), "+f"(d[10]), "+f"(d[11]), "+f"(d[12]), "+f"(d[13]), "+f"(d[14]), "+f"(d[15]), "+f"(d[16]), "+f"(d[17]), "+f"(d[18]), "+f"(d[19])
      : "r"(a0), "r"(a1), "r"(a2), "r"(a3), "l"(db));
  } else {
    asm volatile("{\n.reg .pred p;\nsetp.ne.b32 p, 0, 0;\n"
      "wgmma.mma_async.sync.aligned.m64n40k16.f32.bf16.bf16 "
      "{%0, %1, %2, %3, %4, %5, %6, %7, %8, %9, %10, %11, %12, %13, %14, %15, %16, %17, %18, %19}, "
      "{%20, %21, %22, %23}, %24, p, 1, 1, 1;\n}\n"
      : "=f"(d[0]), "=f"(d[1]), "=f"(d[2]), "=f"(d[3]), "=f"(d[4]), "=f"(d[5]), "=f"(d[6]), "=f"(d[7]), "=f"(d[8]), "=f"(d[9]), "=f"(d[10]), "=f"(d[11]), "=f"(d[12]), "=f"(d[13]), "=f"(d[14]), "=f"(d[15]), "=f"(d[16]), "=f"(d[17]), "=f"(d[18]), "=f"(d[19])
      : "r"(a0), "r"(a1), "r"(a2), "r"(a3), "l"(db));
  }
}
__device__ __forceinline__ void wgmma_n40_ss_ta1_tb1(float* d, uint64_t da, uint64_t db, bool accumulate) {
  if (accumulate) {
    asm volatile("{\n.reg .pred p;\nsetp.ne.b32 p, 1, 0;\n"
      "wgmma.mma_async.sync.aligned.m64n40k16.f32.bf16.bf16 "
      "{%0, %1, %2, %3, %4, %5, %6, %7, %8, %9, %10, %11, %12, %13, %14, %15, %16, %17, %18, %19}, "
      "%20, %21, p, 1, 1, 1, 1;\n}\n"
      : "+f"(d[0]), "+f"(d[1]), "+f"(d[2]), "+f"(d[3]), "+f"(d[4]), "+f"(d[5]), "+f"(d[6]), "+f"(d[7]), "+f"(d[8]), "+f"(d[9]), "+f"(d[10]), "+f"(d[11]), "+f"(d[12]), "+f"(d[13]), "+f"(d[14]), "+f"(d[15]), "+f"(d[16]), "+f"(d[17]), "+f"(d[18]), "+f"(d[19])
      : "l"(da), "l"(db));
  } else {
    asm volatile("{\n.reg .pred p;\nsetp.ne.b32 p, 0, 0;\n"
      "wgmma.mma_async.sync.aligned.m64n40k16.f32.bf16.bf16 "
      "{%0, %1, %2, %3, %4, %5, %6, %7, %8, %9, %10, %11, %12, %13, %14, %15, %16, %17, %18, %19}, "
      "%20, %21, p, 1, 1, 1, 1;\n}\n"
      : "=f"(d[0]), "=f"(d[1]), "=f"(d[2]), "=f"(d[3]), "=f"(d[4]), "=f"(d[5]), "=f"(d[6]), "=f"(d[7]), "=f"(d[8]), "=f"(d[9]), "=f"(d[10]), "=f"(d[11]), "=f"(d[12]), "=f"(d[13]), "=f"(d[14]), "=f"(d[15]), "=f"(d[16]), "=f"(d[17]), "=f"(d[18]), "=f"(d[19])
      : "l"(da), "l"(db));
  }
}
__device__ __forceinline__ void wgmma_n128_rs_ta0_tb1(float* d, uint32_t a0, uint32_t a1, uint32_t a2, uint32_t a3, uint64_t db, bool accumulate) {
  if (accumulate) {
    asm volatile("{\n.reg .pred p;\nsetp.ne.b32 p, 1, 0;\n"
      "wgmma.mma_async.sync.aligned.m64n128k16.f32.bf16.bf16 "
      "{%0, %1, %2, %3, %4, %5, %6, %7, %8, %9, %10, %11, %12, %13, %14, %15, %16, %17, %18, %19, %20, %21, %22, %23, %24, %25, %26, %27, %28, %29, %30, %31, %32, %33, %34, %35, %36, %37, %38, %39, %40, %41, %42, %43, %44, %45, %46, %47, %48, %49, %50, %51, %52, %53, %54, %55, %56, %57, %58, %59, %60, %61, %62, %63}, "
      "{%64, %65, %66, %67}, %68, p, 1, 1, 1;\n}\n"
      : "+f"(d[0]), "+f"(d[1]), "+f"(d[2]), "+f"(d[3]), "+f"(d[4]), "+f"(d[5]), "+f"(d[6]), "+f"(d[7]), "+f"(d[8]), "+f"(d[9]), "+f"(d[10]), "+f"(d[11]), "+f"(d[12]), "+f"(d[13]), "+f"(d[14]), "+f"(d[15]), "+f"(d[16]), "+f"(d[17]), "+f"(d[18]), "+f"(d[19]), "+f"(d[20]), "+f"(d[21]), "+f"(d[22]), "+f"(d[23]), "+f"(d[24]), "+f"(d[25]), "+f"(d[26]), "+f"(d[27]), "+f"(d[28]), "+f"(d[29]), "+f"(d[30]), "+f"(d[31]), "+f"(d[32]), "+f"(d[33]), "+f"(d[34]), "+f"(d[35]), "+f"(d[36]), "+f"(d[37]), "+f"(d[38]), "+f"(d[39]), "+f"(d[40]), "+f"(d[41]), "+f"(d[42]), "+f"(d[43]), "+f"(d[44]), "+f"(d[45]), "+f"(d[46]), "+f"(d[47]), "+f"(d[48]), "+f"(d[49]), "+f"(d[50]), "+f"(d[51]), "+f"(d[52]), "+f"(d[53]), "+f"(d[54]), "+f"(d[55]), "+f"(d[56]), "+f"(d[57]), "+f"(d[58]), "+f"(d[59]), "+f"(d[60]), "+f"(d[61]), "+f"(d[62]), "+f"(d[63])
      : "r"(a0), "r"(a1), "r"(a2), "r"(a3), "l"(db));
  } else {
    asm volatile("{\n.reg .pred p;\nsetp.ne.b32 p, 0, 0;\n"
      "wgmma.mma_async.sync.aligned.m64n128k16.f32.bf16.bf16 "
      "{%0, %1, %2, %3, %4, %5, %6, %7, %8, %9, %10, %11, %12, %13, %14, %15, %16, %17, %18, %19, %20, %21, %22, %23, %24, %25, %26, %27, %28, %29, %30, %31, %32, %33, %34, %35, %36, %37, %38, %39, %40, %41, %42, %43, %44, %45, %46, %47, %48, %49, %50, %51, %52, %53, %54, %55, %56, %57, %58, %59, %60, %61, %62, %63}, "
      "{%64, %65, %66, %67}, %68, p, 1, 1, 1;\n}\n"
      : "=f"(d[0]), "=f"(d[1]), "=f"(d[2]), "=f"(d[3]), "=f"(d[4]), "=f"(d[5]), "=f"(d[6]), "=f"(d[7]), "=f"(d[8]), "=f"(d[9]), "=f"(d[10]), "=f"(d[11]), "=f"(d[12]), "=f"(d[13]), "=f"(d[14]), "=f"(d[15]), "=f"(d[16]), "=f"(d[17]), "=f"(d[18]), "=f"(d[19]), "=f"(d[20]), "=f"(d[21]), "=f"(d[22]), "=f"(d[23]), "=f"(d[24]), "=f"(d[25]), "=f"(d[26]), "=f"(d[27]), "=f"(d[28]), "=f"(d[29]), "=f"(d[30]), "=f"(d[31]), "=f"(d[32]), "=f"(d[33]), "=f"(d[34]), "=f"(d[35]), "=f"(d[36]), "=f"(d[37]), "=f"(d[38]), "=f"(d[39]), "=f"(d[40]), "=f"(d[41]), "=f"(d[42]), "=f"(d[43]), "=f"(d[44]), "=f"(d[45]), "=f"(d[46]), "=f"(d[47]), "=f"(d[48]), "=f"(d[49]), "=f"(d[50]), "=f"(d[51]), "=f"(d[52]), "=f"(d[53]), "=f"(d[54]), "=f"(d[55]), "=f"(d[56]), "=f"(d[57]), "=f"(d[58]), "=f"(d[59]), "=f"(d[60]), "=f"(d[61]), "=f"(d[62]), "=f"(d[63])
      : "r"(a0), "r"(a1), "r"(a2), "r"(a3), "l"(db));
  }
}
__device__ __forceinline__ void wgmma_n128_ss_ta0_tb1(float* d, uint64_t da, uint64_t db, bool accumulate) {
  if (accumulate) {
    asm volatile("{\n.reg .pred p;\nsetp.ne.b32 p, 1, 0;\n"
      "wgmma.mma_async.sync.aligned.m64n128k16.f32.bf16.bf16 "
      "{%0, %1, %2, %3, %4, %5, %6, %7, %8, %9, %10, %11, %12, %13, %14, %15, %16, %17, %18, %19, %20, %21, %22, %23, %24, %25, %26, %27, %28, %29, %30, %31, %32, %33, %34, %35, %36, %37, %38, %39, %40, %41, %42, %43, %44, %45, %46, %47, %48, %49, %50, %51, %52, %53, %54, %55, %56, %57, %58, %59, %60, %61, %62, %63}, "
      "%64, %65, p, 1, 1, 0, 1;\n}\n"
      : "+f"(d[0]), "+f"(d[1]), "+f"(d[2]), "+f"(d[3]), "+f"(d[4]), "+f"(d[5]), "+f"(d[6]), "+f"(d[7]), "+f"(d[8]), "+f"(d[9]), "+f"(d[10]), "+f"(d[11]), "+f"(d[12]), "+f"(d[13]), "+f"(d[14]), "+f"(d[15]), "+f"(d[16]), "+f"(d[17]), "+f"(d[18]), "+f"(d[19]), "+f"(d[20]), "+f"(d[21]), "+f"(d[22]), "+f"(d[23]), "+f"(d[24]), "+f"(d[25]), "+f"(d[26]), "+f"(d[27]), "+f"(d[28]), "+f"(d[29]), "+f"(d[30]), "+f"(d[31]), "+f"(d[32]), "+f"(d[33]), "+f"(d[34]), "+f"(d[35]), "+f"(d[36]), "+f"(d[37]), "+f"(d[38]), "+f"(d[39]), "+f"(d[40]), "+f"(d[41]), "+f"(d[42]), "+f"(d[43]), "+f"(d[44]), "+f"(d[45]), "+f"(d[46]), "+f"(d[47]), "+f"(d[48]), "+f"(d[49]), "+f"(d[50]), "+f"(d[51]), "+f"(d[52]), "+f"(d[53]), "+f"(d[54]), "+f"(d[55]), "+f"(d[56]), "+f"(d[57]), "+f"(d[58]), "+f"(d[59]), "+f"(d[60]), "+f"(d[61]), "+f"(d[62]), "+f"(d[63])
      : "l"(da), "l"(db));
  } else {
    asm volatile("{\n.reg .pred p;\nsetp.ne.b32 p, 0, 0;\n"
      "wgmma.mma_async.sync.aligned.m64n128k16.f32.bf16.bf16 "
      "{%0, %1, %2, %3, %4, %5, %6, %7, %8, %9, %10, %11, %12, %13, %14, %15, %16, %17, %18, %19, %20, %21, %22, %23, %24, %25, %26, %27, %28, %29, %30, %31, %32, %33, %34, %35, %36, %37, %38, %39, %40, %41, %42, %43, %44, %45, %46, %47, %48, %49, %50, %51, %52, %53, %54, %55, %56, %57, %58, %59, %60, %61, %62, %63}, "
      "%64, %65, p, 1, 1, 0, 1;\n}\n"
      : "=f"(d[0]), "=f"(d[1]), "=f"(d[2]), "=f"(d[3]), "=f"(d[4]), "=f"(d[5]), "=f"(d[6]), "=f"(d[7]), "=f"(d[8]), "=f"(d[9]), "=f"(d[10]), "=f"(d[11]), "=f"(d[12]), "=f"(d[13]), "=f"(d[14]), "=f"(d[15]), "=f"(d[16]), "=f"(d[17]), "=f"(d[18]), "=f"(d[19]), "=f"(d[20]), "=f"(d[21]), "=f"(d[22]), "=f"(d[23]), "=f"(d[24]), "=f"(d[25]), "=f"(d[26]), "=f"(d[27]), "=f"(d[28]), "=f"(d[29]), "=f"(d[30]), "=f"(d[31]), "=f"(d[32]), "=f"(d[33]), "=f"(d[34]), "=f"(d[35]), "=f"(d[36]), "=f"(d[37]), "=f"(d[38]), "=f"(d[39]), "=f"(d[40]), "=f"(d[41]), "=f"(d[42]), "=f"(d[43]), "=f"(d[44]), "=f"(d[45]), "=f"(d[46]), "=f"(d[47]), "=f"(d[48]), "=f"(d[49]), "=f"(d[50]), "=f"(d[51]), "=f"(d[52]), "=f"(d[53]), "=f"(d[54]), "=f"(d[55]), "=f"(d[56]), "=f"(d[57]), "=f"(d[58]), "=f"(d[59]), "=f"(d[60]), "=f"(d[61]), "=f"(d[62]), "=f"(d[63])
      : "l"(da), "l"(db));
  }
}
__device__ __forceinline__ void wgmma_n256_rs_ta0_tb1(float* d, uint32_t a0, uint32_t a1, uint32_t a2, uint32_t a3, uint64_t db, bool accumulate) {
  if (accumulate) {
    asm volatile("{\n.reg .pred p;\nsetp.ne.b32 p, 1, 0;\n"
      "wgmma.mma_async.sync.aligned.m64n256k16.f32.bf16.bf16 "
      "{%0, %1, %2, %3, %4, %5, %6, %7, %8, %9, %10, %11, %12, %13, %14, %15, %16, %17, %18, %19, %20, %21, %22, %23, %24, %25, %26, %27, %28, %29, %30, %31, %32, %33, %34, %35, %36, %37, %38, %39, %40, %41, %42, %43, %44, %45, %46, %47, %48, %49, %50, %51, %52, %53, %54, %55, %56, %57, %58, %59, %60, %61, %62, %63, %64, %65, %66, %67, %68, %69, %70, %71, %72, %73, %74, %75, %76, %77, %78, %79, %80, %81, %82, %83, %84, %85, %86, %87, %88, %89, %90, %91, %92, %93, %94, %95, %96, %97, %98, %99, %100, %101, %102, %103, %104, %105, %106, %107, %108, %109, %110, %111, %112, %113, %114, %115, %116, %117, %118, %119, %120, %121, %122, %123, %124, %125, %126, %127}, "
      "{%128, %129, %130, %131}, %132, p, 1, 1, 1;\n}\n"
      : "+f"(d[0]), "+f"(d[1]), "+f"(d[2]), "+f"(d[3]), "+f"(d[4]), "+f"(d[5]), "+f"(d[6]), "+f"(d[7]), "+f"(d[8]), "+f"(d[9]), "+f"(d[10]), "+f"(d[11]), "+f"(d[12]), "+f"(d[13]), "+f"(d[14]), "+f"(d[15]), "+f"(d[16]), "+f"(d[17]), "+f"(d[18]), "+f"(d[19]), "+f"(d[20]), "+f"(d[21]), "+f"(d[22]), "+f"(d[23]), "+f"(d[24]), "+f"(d[25]), "+f"(d[26]), "+f"(d[27]), "+f"(d[28]), "+f"(d[29]), "+f"(d[30]), "+f"(d[31]), "+f"(d[32]), "+f"(d[33]), "+f"(d[34]), "+f"(d[35]), "+f"(d[36]), "+f"(d[37]), "+f"(d[38]), "+f"(d[39]), "+f"(d[40]), "+f"(d[41]), "+f"(d[42]), "+f"(d[43]), "+f"(d[44]), "+f"(d[45]), "+f"(d[46]), "+f"(d[47]), "+f"(d[48]), "+f"(d[49]), "+f"(d[50]), "+f"(d[51]), "+f"(d[52]), "+f"(d[53]), "+f"(d[54]), "+f"(d[55]), "+f"(d[56]), "+f"(d[57]), "+f"(d[58]), "+f"(d[59]), "+f"(d[60]), "+f"(d[61]), "+f"(d[62]), "+f"(d[63]), "+f"(d[64]), "+f"(d[65]), "+f"(d[66]), "+f"(d[67]), "+f"(d[68]), "+f"(d[69]), "+f"(d[70]), "+f"(d[71]), "+f"(d[72]), "+f"(d[73]), "+f"(d[74]), "+f"(d[75]), "+f"(d[76]), "+f"(d[77]), "+f"(d[78]), "+f"(d[79]), "+f"(d[80]), "+f"(d[81]), "+f"(d[82]), "+f"(d[83]), "+f"(d[84]), "+f"(d[85]), "+f"(d[86]), "+f"(d[87]), "+f"(d[88]), "+f"(d[89]), "+f"(d[90]), "+f"(d[91]), "+f"(d[92]), "+f"(d[93]), "+f"(d[94]), "+f"(d[95]), "+f"(d[96]), "+f"(d[97]), "+f"(d[98]), "+f"(d[99]), "+f"(d[100]), "+f"(d[101]), "+f"(d[102]), "+f"(d[103]), "+f"(d[104]), "+f"(d[105]), "+f"(d[106]), "+f"(d[107]), "+f"(d[108]), "+f"(d[109]), "+f"(d[110]), "+f"(d[111]), "+f"(d[112]), "+f"(d[113]), "+f"(d[114]), "+f"(d[115]), "+f"(d[116]), "+f"(d[117]), "+f"(d[118]), "+f"(d[119]), "+f"(d[120]), "+f"(d[121]), "+f"(d[122]), "+f"(d[123]), "+f"(d[124]), "+f"(d[125]), "+f"(d[126]), "+f"(d[127])
      : "r"(a0), "r"(a1), "r"(a2), "r"(a3), "l"(db));
  } else {
    asm volatile("{\n.reg .pred p;\nsetp.ne.b32 p, 0, 0;\n"
      "wgmma.mma_async.sync.aligned.m64n256k16.f32.bf16.bf16 "
      "{%0, %1, %2, %3, %4, %5, %6, %7, %8, %9, %10, %11, %12, %13, %14, %15, %16, %17, %18, %19, %20, %21, %22, %23, %24, %25, %26, %27, %28, %29, %30, %31, %32, %33, %34, %35, %36, %37, %38, %39, %40, %41, %42, %43, %44, %45, %46, %47, %48, %49, %50, %51, %52, %53, %54, %55, %56, %57, %58, %59, %60, %61, %62, %63, %64, %65, %66, %67, %68, %69, %70, %71, %72, %73, %74, %75, %76, %77, %78, %79, %80, %81, %82, %83, %84, %85, %86, %87, %88, %89, %90, %91, %92, %93, %94, %95, %96, %97, %98, %99, %100, %101, %102, %103, %104, %105, %106, %107, %108, %109, %110, %111, %112, %113, %114, %115, %116, %117, %118, %119, %120, %121, %122, %123, %124, %125, %126, %127}, "
      "{%128, %129, %130, %131}, %132, p, 1, 1, 1;\n}\n"
      : "=f"(d[0]), "=f"(d[1]), "=f"(d[2]), "=f"(d[3]), "=f"(d[4]), "=f"(d[5]), "=f"(d[6]), "=f"(d[7]), "=f"(d[8]), "=f"(d[9]), "=f"(d[10]), "=f"(d[11]), "=f"(d[12]), "=f"(d[13]), "=f"(d[14]), "=f"(d[15]), "=f"(d[16]), "=f"(d[17]), "=f"(d[18]), "=f"(d[19]), "=f"(d[20]), "=f"(d[21]), "=f"(d[22]), "=f"(d[23]), "=f"(d[24]), "=f"(d[25]), "=f"(d[26]), "=f"(d[27]), "=f"(d[28]), "=f"(d[29]), "=f"(d[30]), "=f"(d[31]), "=f"(d[32]), "=f"(d[33]), "=f"(d[34]), "=f"(d[35]), "=f"(d[36]), "=f"(d[37]), "=f"(d[38]), "=f"(d[39]), "=f"(d[40]), "=f"(d[41]), "=f"(d[42]), "=f"(d[43]), "=f"(d[44]), "=f"(d[45]), "=f"(d[46]), "=f"(d[47]), "=f"(d[48]), "=f"(d[49]), "=f"(d[50]), "=f"(d[51]), "=f"(d[52]), "=f"(d[53]), "=f"(d[54]), "=f"(d[55]), "=f"(d[56]), "=f"(d[57]), "=f"(d[58]), "=f"(d[59]), "=f"(d[60]), "=f"(d[61]), "=f"(d[62]), "=f"(d[63]), "=f"(d[64]), "=f"(d[65]), "=f"(d[66]), "=f"(d[67]), "=f"(d[68]), "=f"(d[69]), "=f"(d[70]), "=f"(d[71]), "=f"(d[72]), "=f"(d[73]), "=f"(d[74]), "=f"(d[75]), "=f"(d[76]), "=f"(d[77]), "=f"(d[78]), "=f"(d[79]), "=f"(d[80]), "=f"(d[81]), "=f"(d[82]), "=f"(d[83]), "=f"(d[84]), "=f"(d[85]), "=f"(d[86]), "=f"(d[87]), "=f"(d[88]), "=f"(d[89]), "=f"(d[90]), "=f"(d[91]), "=f"(d[92]), "=f"(d[93]), "=f"(d[94]), "=f"(d[95]), "=f"(d[96]), "=f"(d[97]), "=f"(d[98]), "=f"(d[99]), "=f"(d[100]), "=f"(d[101]), "=f"(d[102]), "=f"(d[103]), "=f"(d[104]), "=f"(d[105]), "=f"(d[106]), "=f"(d[107]), "=f"(d[108]), "=f"(d[109]), "=f"(d[110]), "=f"(d[111]), "=f"(d[112]), "=f"(d[113]), "=f"(d[114]), "=f"(d[115]), "=f"(d[116]), "=f"(d[117]), "=f"(d[118]), "=f"(d[119]), "=f"(d[120]), "=f"(d[121]), "=f"(d[122]), "=f"(d[123]), "=f"(d[124]), "=f"(d[125]), "=f"(d[126]), "=f"(d[127])
      : "r"(a0), "r"(a1), "r"(a2), "r"(a3), "l"(db));
  }
}
__device__ __forceinline__ void wgmma_n256_ss_ta0_tb1(float* d, uint64_t da, uint64_t db, bool accumulate) {
  if (accumulate) {
    asm volatile("{\n.reg .pred p;\nsetp.ne.b32 p, 1, 0;\n"
      "wgmma.mma_async.sync.aligned.m64n256k16.f32.bf16.bf16 "
      "{%0, %1, %2, %3, %4, %5, %6, %7, %8, %9, %10, %11, %12, %13, %14, %15, %16, %17, %18, %19, %20, %21, %22, %23, %24, %25, %26, %27, %28, %29, %30, %31, %32, %33, %34, %35, %36, %37, %38, %39, %40, %41, %42, %43, %44, %45, %46, %47, %48, %49, %50, %51, %52, %53, %54, %55, %56, %57, %58, %59, %60, %61, %62, %63, %64, %65, %66, %67, %68, %69, %70, %71, %72, %73, %74, %75, %76, %77, %78, %79, %80, %81, %82, %83, %84, %85, %86, %87, %88, %89, %90, %91, %92, %93, %94, %95, %96, %97, %98, %99, %100, %101, %102, %103, %104, %105, %106, %107, %108, %109, %110, %111, %112, %113, %114, %115, %116, %117, %118, %119, %120, %121, %122, %123, %124, %125, %126, %127}, "
      "%128, %129, p, 1, 1, 0, 1;\n}\n"
      : "+f"(d[0]), "+f"(d[1]), "+f"(d[2]), "+f"(d[3]), "+f"(d[4]), "+f"(d[5]), "+f"(d[6]), "+f"(d[7]), "+f"(d[8]), "+f"(d[9]), "+f"(d[10]), "+f"(d[11]), "+f"(d[12]), "+f"(d[13]), "+f"(d[14]), "+f"(d[15]), "+f"(d[16]), "+f"(d[17]), "+f"(d[18]), "+f"(d[19]), "+f"(d[20]), "+f"(d[21]), "+f"(d[22]), "+f"(d[23]), "+f"(d[24]), "+f"(d[25]), "+f"(d[26]), "+f"(d[27]), "+f"(d[28]), "+f"(d[29]), "+f"(d[30]), "+f"(d[31]), "+f"(d[32]), "+f"(d[33]), "+f"(d[34]), "+f"(d[35]), "+f"(d[36]), "+f"(d[37]), "+f"(d[38]), "+f"(d[39]), "+f"(d[40]), "+f"(d[41]), "+f"(d[42]), "+f"(d[43]), "+f"(d[44]), "+f"(d[45]), "+f"(d[46]), "+f"(d[47]), "+f"(d[48]), "+f"(d[49]), "+f"(d[50]), "+f"(d[51]), "+f"(d[52]), "+f"(d[53]), "+f"(d[54]), "+f"(d[55]), "+f"(d[56]), "+f"(d[57]), "+f"(d[58]), "+f"(d[59]), "+f"(d[60]), "+f"(d[61]), "+f"(d[62]), "+f"(d[63]), "+f"(d[64]), "+f"(d[65]), "+f"(d[66]), "+f"(d[67]), "+f"(d[68]), "+f"(d[69]), "+f"(d[70]), "+f"(d[71]), "+f"(d[72]), "+f"(d[73]), "+f"(d[74]), "+f"(d[75]), "+f"(d[76]), "+f"(d[77]), "+f"(d[78]), "+f"(d[79]), "+f"(d[80]), "+f"(d[81]), "+f"(d[82]), "+f"(d[83]), "+f"(d[84]), "+f"(d[85]), "+f"(d[86]), "+f"(d[87]), "+f"(d[88]), "+f"(d[89]), "+f"(d[90]), "+f"(d[91]), "+f"(d[92]), "+f"(d[93]), "+f"(d[94]), "+f"(d[95]), "+f"(d[96]), "+f"(d[97]), "+f"(d[98]), "+f"(d[99]), "+f"(d[100]), "+f"(d[101]), "+f"(d[102]), "+f"(d[103]), "+f"(d[104]), "+f"(d[105]), "+f"(d[106]), "+f"(d[107]), "+f"(d[108]), "+f"(d[109]), "+f"(d[110]), "+f"(d[111]), "+f"(d[112]), "+f"(d[113]), "+f"(d[114]), "+f"(d[115]), "+f"(d[116]), "+f"(d[117]), "+f"(d[118]), "+f"(d[119]), "+f"(d[120]), "+f"(d[121]), "+f"(d[122]), "+f"(d[123]), "+f"(d[124]), "+f"(d[125]), "+f"(d[126]), "+f"(d[127])
      : "l"(da), "l"(db));
  } else {
    asm volatile("{\n.reg .pred p;\nsetp.ne.b32 p, 0, 0;\n"
      "wgmma.mma_async.sync.aligned.m64n256k16.f32.bf16.bf16 "
      "{%0, %1, %2, %3, %4, %5, %6, %7, %8, %9, %10, %11, %12, %13, %14, %15, %16, %17, %18, %19, %20, %21, %22, %23, %24, %25, %26, %27, %28, %29, %30, %31, %32, %33, %34, %35, %36, %37, %38, %39, %40, %41, %42, %43, %44, %45, %46, %47, %48, %49, %50, %51, %52, %53, %54, %55, %56, %57, %58, %59, %60, %61, %62, %63, %64, %65, %66, %67, %68, %69, %70, %71, %72, %73, %74, %75, %76, %77, %78, %79, %80, %81, %82, %83, %84, %85, %86, %87, %88, %89, %90, %91, %92, %93, %94, %95, %96, %97, %98, %99, %100, %101, %102, %103, %104, %105, %106, %107, %108, %109, %110, %111, %112, %113, %114, %115, %116, %117, %118, %119, %120, %121, %122, %123, %124, %125, %126, %127}, "
      "%128, %129, p, 1, 1, 0, 1;\n}\n"
      : "=f"(d[0]), "=f"(d[1]), "=f"(d[2]), "=f"(d[3]), "=f"(d[4]), "=f"(d[5]), "=f"(d[6]), "=f"(d[7]), "=f"(d[8]), "=f"(d[9]), "=f"(d[10]), "=f"(d[11]), "=f"(d[12]), "=f"(d[13]), "=f"(d[14]), "=f"(d[15]), "=f"(d[16]), "=f"(d[17]), "=f"(d[18]), "=f"(d[19]), "=f"(d[20]), "=f"(d[21]), "=f"(d[22]), "=f"(d[23]), "=f"(d[24]), "=f"(d[25]), "=f"(d[26]), "=f"(d[27]), "=f"(d[28]), "=f"(d[29]), "=f"(d[30]), "=f"(d[31]), "=f"(d[32]), "=f"(d[33]), "=f"(d[34]), "=f"(d[35]), "=f"(d[36]), "=f"(d[37]), "=f"(d[38]), "=f"(d[39]), "=f"(d[40]), "=f"(d[41]), "=f"(d[42]), "=f"(d[43]), "=f"(d[44]), "=f"(d[45]), "=f"(d[46]), "=f"(d[47]), "=f"(d[48]), "=f"(d[49]), "=f"(d[50]), "=f"(d[51]), "=f"(d[52]), "=f"(d[53]), "=f"(d[54]), "=f"(d[55]), "=f"(d[56]), "=f"(d[57]), "=f"(d[58]), "=f"(d[59]), "=f"(d[60]), "=f"(d[61]), "=f"(d[62]), "=f"(d[63]), "=f"(d[64]), "=f"(d[65]), "=f"(d[66]), "=f"(d[67]), "=f"(d[68]), "=f"(d[69]), "=f"(d[70]), "=f"(d[71]), "=f"(d[72]), "=f"(d[73]), "=f"(d[74]), "=f"(d[75]), "=f"(d[76]), "=f"(d[77]), "=f"(d[78]), "=f"(d[79]), "=f"(d[80]), "=f"(d[81]), "=f"(d[82]), "=f"(d[83]), "=f"(d[84]), "=f"(d[85]), "=f"(d[86]), "=f"(d[87]), "=f"(d[88]), "=f"(d[89]), "=f"(d[90]), "=f"(d[91]), "=f"(d[92]), "=f"(d[93]), "=f"(d[94]), "=f"(d[95]), "=f"(d[96]), "=f"(d[97]), "=f"(d[98]), "=f"(d[99]), "=f"(d[100]), "=f"(d[101]), "=f"(d[102]), "=f"(d[103]), "=f"(d[104]), "=f"(d[105]), "=f"(d[106]), "=f"(d[107]), "=f"(d[108]), "=f"(d[109]), "=f"(d[110]), "=f"(d[111]), "=f"(d[112]), "=f"(d[113]), "=f"(d[114]), "=f"(d[115]), "=f"(d[116]), "=f"(d[117]), "=f"(d[118]), "=f"(d[119]), "=f"(d[120]), "=f"(d[121]), "=f"(d[122]), "=f"(d[123]), "=f"(d[124]), "=f"(d[125]), "=f"(d[126]), "=f"(d[127])
      : "l"(da), "l"(db));
  }
}
__device__ __forceinline__ void wgmma_n256_ssp_ta0_tb1(float* d, uint64_t da, uint64_t db, int accumulate) {
    asm volatile("{\n.reg .pred p;\nsetp.ne.b32 p, %130, 0;\n"
      "wgmma.mma_async.sync.aligned.m64n256k16.f32.bf16.bf16 "
      "{%0, %1, %2, %3, %4, %5, %6, %7, %8, %9, %10, %11, %12, %13, %14, %15, %16, %17, %18, %19, %20, %21, %22, %23, %24, %25, %26, %27, %28, %29, %30, %31, %32, %33, %34, %35, %36, %37, %38, %39, %40, %41, %42, %43, %44, %45, %46, %47, %48, %49, %50, %51, %52, %53, %54, %55, %56, %57, %58, %59, %60, %61, %62, %63, %64, %65, %66, %67, %68, %69, %70, %71, %72, %73, %74, %75, %76, %77, %78, %79, %80, %81, %82, %83, %84, %85, %86, %87, %88, %89, %90, %91, %92, %93, %94, %95, %96, %97, %98, %99, %100, %101, %102, %103, %104, %105, %106, %107, %108, %109, %110, %111, %112, %113, %114, %115, %116, %117, %118, %119, %120, %121, %122, %123, %124, %125, %126, %127}, "
      "%128, %129, p, 1, 1, 0, 1;\n}\n"
      : "+f"(d[0]), "+f"(d[1]), "+f"(d[2]), "+f"(d[3]), "+f"(d[4]), "+f"(d[5]), "+f"(d[6]), "+f"(d[7]), "+f"(d[8]), "+f"(d[9]), "+f"(d[10]), "+f"(d[11]), "+f"(d[12]), "+f"(d[13]), "+f"(d[14]), "+f"(d[15]), "+f"(d[16]), "+f"(d[17]), "+f"(d[18]), "+f"(d[19]), "+f"(d[20]), "+f"(d[21]), "+f"(d[22]), "+f"(d[23]), "+f"(d[24]), "+f"(d[25]), "+f"(d[26]), "+f"(d[27]), "+f"(d[28]), "+f"(d[29]), "+f"(d[30]), "+f"(d[31]), "+f"(d[32]), "+f"(d[33]), "+f"(d[34]), "+f"(d[35]), "+f"(d[36]), "+f"(d[37]), "+f"(d[38]), "+f"(d[39]), "+f"(d[40]), "+f"(d[41]), "+f"(d[42]), "+f"(d[43]), "+f"(d[44]), "+f"(d[45]), "+f"(d[46]), "+f"(d[47]), "+f"(d[48]), "+f"(d[49]), "+f"(d[50]), "+f"(d[51]), "+f"(d[52]), "+f"(d[53]), "+f"(d[54]), "+f"(d[55]), "+f"(d[56]), "+f"(d[57]), "+f"(d[58]), "+f"(d[59]), "+f"(d[60]), "+f"(d[61]), "+f"(d[62]), "+f"(d[63]), "+f"(d[64]), "+f"(d[65]), "+f"(d[66]), "+f"(d[67]), "+f"(d[68]), "+f"(d[69]), "+f"(d[70]), "+f"(d[71]), "+f"(d[72]), "+f"(d[73]), "+f"(d[74]), "+f"(d[75]), "+f"(d[76]), "+f"(d[77]), "+f"(d[78]), "+f"(d[79]), "+f"(d[80]), "+f"(d[81]), "+f"(d[82]), "+f"(d[83]), "+f"(d[84]), "+f"(d[85]), "+f"(d[86]), "+f"(d[87]), "+f"(d[88]), "+f"(d[89]), "+f"(d[90]), "+f"(d[91]), "+f"(d[92]), "+f"(d[93]), "+f"(d[94]), "+f"(d[95]), "+f"(d[96]), "+f"(d[97]), "+f"(d[98]), "+f"(d[99]), "+f"(d[100]), "+f"(d[101]), "+f"(d[102]), "+f"(d[103]), "+f"(d[104]), "+f"(d[105]), "+f"(d[106]), "+f"(d[107]), "+f"(d[108]), "+f"(d[109]), "+f"(d[110]), "+f"(d[111]), "+f"(d[112]), "+f"(d[113]), "+f"(d[114]), "+f"(d[115]), "+f"(d[116]), "+f"(d[117]), "+f"(d[118]), "+f"(d[119]), "+f"(d[120]), "+f"(d[121]), "+f"(d[122]), "+f"(d[123]), "+f"(d[124]), "+f"(d[125]), "+f"(d[126]), "+f"(d[127])
      : "l"(da), "l"(db), "r"(accumulate));
}

template <int N> __device__ __forceinline__ void quad_sum(float* m) {
#pragma unroll
  for (int o = 1; o <= 2; o <<= 1) {
    float t[N];
#pragma unroll
    for (int i = 0; i < N; i++) t[i] = __shfl_xor_sync(~0u, m[i], o);
#pragma unroll
    for (int i = 0; i < N; i++) m[i] += t[i];
  }
}
__device__ __forceinline__ bool softmax_unsafe(const uint32_t* t, float l0, float l1) {
  const float m0 = fmaxf(bf_lo(t[0]) + bf_hi(t[0]), bf_lo(t[2]) + bf_hi(t[2])), m1 = fmaxf(bf_lo(t[1]) + bf_hi(t[1]), bf_lo(t[3]) + bf_hi(t[3]));
  return __any_sync(~0u, !(m0 * l0 < 2500.f) | !(m1 * l1 < 2500.f));
}
__device__ __forceinline__ void softmax_shift(float* p, float c0, float c1) {
#pragma unroll 1
  for (int it = 0; it < 8; it++) {
    float mx = p[0], mn = p[0];
#pragma unroll
    for (int j = 1; j < 8; j++) { mx = fmaxf(mx, p[(j >> 1) * 4 + (j & 1)]); mn = fminf(mn, p[(j >> 1) * 4 + (j & 1)]); }
#pragma unroll
    for (int o = 1; o <= 2; o <<= 1) { mx = fmaxf(mx, __shfl_xor_sync(~0u, mx, o)); mn = fminf(mn, __shfl_xor_sync(~0u, mn, o)); }
    const float half = fminf(0.5f * (mx - mn), 50.f * rcp(it & 1 ? c1 : c0));
    float r[8];
#pragma unroll
    for (int j = 0; j < 8; j++) {
      const float v = p[(j >> 1) * 4 + (j & 1)];
      r[j] = fmaxf(v - mx + half, 0.f) + fminf(v - mn - half, 0.f) + (v - v);
    }
#pragma unroll
    for (int k = 0; k < 7; k++)
#pragma unroll
      for (int j = 0; j < 8; j++) p[(k >> 1) * 16 + (k & 1) * 2 + (j >> 1) * 4 + (j & 1)] = p[((k + 1) >> 1) * 16 + ((k + 1) & 1) * 2 + (j >> 1) * 4 + (j & 1)];
#pragma unroll
    for (int j = 0; j < 8; j++) p[50 + (j >> 1) * 4 + (j & 1)] = r[j];
  }
}
template <int J0 = 0, int J1 = 8> __device__ __forceinline__ void k_exp(const float* p, float c0, float c1, float* e, float* s) {
#pragma unroll
  for (int j = J0; j < J1; j++) {
    e[2 * j] = ex2(p[2 * j] * (j & 1 ? c1 : c0));
    e[2 * j + 1] = ex2(p[2 * j + 1] * (j & 1 ? c1 : c0));
    e[16 + j] = rcp(e[2 * j] * e[2 * j + 1]);
    const float t = e[2 * j] + e[2 * j + 1];
    s[j & 1] = j < 2 ? t : s[j & 1] + t;
    s[2 + (j & 1)] = j < 2 ? e[16 + j] * t : fmaf(e[16 + j], t, s[2 + (j & 1)]);
  }
}
template <int J0 = 0, int J1 = 8> __device__ __forceinline__ void q_exp(const float* p, float c0, float c1, uint32_t* f) {
#pragma unroll
  for (int j = J0; j < J1; j++) {
    const float e0 = ex2(p[2 * j] * (j & 1 ? c1 : c0)), e1 = ex2(p[2 * j + 1] * (j & 1 ? c1 : c0)), r = rcp(e0 * e1);
    f[j] = pack2(e0, e1);
    f[8 + j] = bmul2(f[j], pack2(r, r));
  }
}

#define FMA8(A, U, X)                                                                                        \
  A[0] = fmaf(bf_lo(U.x), X, A[0]); A[1] = fmaf(bf_hi(U.x), X, A[1]); A[2] = fmaf(bf_lo(U.y), X, A[2]); A[3] = fmaf(bf_hi(U.y), X, A[3]); \
  A[4] = fmaf(bf_lo(U.z), X, A[4]); A[5] = fmaf(bf_hi(U.z), X, A[5]); A[6] = fmaf(bf_lo(U.w), X, A[6]); A[7] = fmaf(bf_hi(U.w), X, A[7])

__device__ __forceinline__ uint32_t routed_row(const __nv_bfloat16* x, uint32_t tag, int lane, uint4* xr) {
  uint32_t best = 0, sv = 0;
#pragma unroll 1
  for (int it = 0; it < SPIN_MAX; it++) {
    const uint4 h = ld_rlx128(g_ycnt + 32);
    best = h.x;
    if (__all_sync(~0u, (int)(h.z - tag * NCTA) >= 0)) break;
    __nanosleep(AM_NS);
  }
#pragma unroll 1
  for (int it = 0; it < SPIN_MAX; it++) {
    const int sel = 2047 - (best & 0x7ff);
#pragma unroll
    for (int i = 0; i < 4; i++) xr[i] = ldg_nc(x + (size_t)sel * DM + i * 256 + lane * 8);
    const unsigned long long st = ld_rlx64(g_stat + sel);
    const uint4 b0 = ld_rlx128(g_best + lane * 2), b1 = ld_rlx128(g_best + 64 + lane * 2);
    const uint32_t m = __reduce_max_sync(~0u, max(max(b0.x, b0.z), max(b1.x, b1.z)));
    sv = (uint32_t)st;
    if (__all_sync(~0u, b0.y == tag && b0.w == tag && b1.y == tag && b1.w == tag && m == best && (uint32_t)(st >> 32) == tag)) break;
    best = m;
  }
  const uint32_t m2 = (sv & 0xffff0000u) | (sv >> 16);
  const float rs = rcp(bf_lo(sv));
#pragma unroll
  for (int i = 0; i < 4; i++) {
    const uint32_t d0 = bsub2(xr[i].x, m2), d1 = bsub2(xr[i].y, m2), d2 = bsub2(xr[i].z, m2), d3 = bsub2(xr[i].w, m2);
    xr[i] = make_uint4(pack2(bf_lo(d0) * rs, bf_hi(d0) * rs), pack2(bf_lo(d1) * rs, bf_hi(d1) * rs), pack2(bf_lo(d2) * rs, bf_hi(d2) * rs),
                       pack2(bf_lo(d3) * rs, bf_hi(d3) * rs));
  }
  return best;
}

struct Params {
  const __nv_bfloat16 *x, *wqkv, *wo, *w_r, *w_gate, *w_up, *w_down;
};

template <bool BY_SMID> __global__ void __launch_bounds__(384, 1)
fused_kernel(const __grid_constant__ CUtensorMap mX, const __grid_constant__ CUtensorMap mWkv, const __grid_constant__ CUtensorMap mWq,
             const __grid_constant__ CUtensorMap mWo, const __grid_constant__ CUtensorMap mPhi, const __grid_constant__ CUtensorMap mWp,
             const __grid_constant__ CUtensorMap mOut, const __grid_constant__ CUtensorMap mWc,
             const __grid_constant__ CUtensorMap mG, const __grid_constant__ CUtensorMap mU, const __grid_constant__ CUtensorMap mD,
             const __grid_constant__ CUtensorMap mXs, const __grid_constant__ CUtensorMap mG2, const __grid_constant__ CUtensorMap mU2, const Params P) {
  constexpr uint32_t sb = SB, bar = SB + SM_BAR;
  int bid = blockIdx.x;
  if (BY_SMID) {
    uint32_t sm;
    asm volatile("mov.u32 %0, %%smid;" : "=r"(sm));
    const uint32_t tq = (sm - 64) >> 1, q7 = (tq * 37) >> 8;
    const uint32_t gpc = sm < 64 ? (sm >> 1) & 7 : 1 + tq - 7 * q7, idx = (sm < 64 ? sm >> 4 : 4 + q7) * 2 + (sm & 1);
    bid = sm < 120 ? ((PTAB >> (4 * gpc)) & 7) * 16 + idx : sm < 124 ? sm + 8 : sm - 116;
  }
  const int hg = ((bid >> 2) & 3) + 4 * ((bid >> 4) & 1), mb = (bid & 3) + 4 * ((bid >> 5) & 3);
  if (bid < NCTA && threadIdx.x >> 5 == 8 && elect_one()) {
    PROF(0); PROFT(32);
#pragma unroll
    for (int j = 0; j < 3; j++) {
      const int s = (j + 2) % 3;
      mbar_init(bar + B_FULLKV + 8 * s, 1);
      mbar_expect_tx(bar + B_FULLKV + 8 * s, KV_STAGE);
      tma2d(sb + s * KV_STAGE, &mX, j * 64, mb * 128, bar + B_FULLKV + 8 * s);
      tma4d(sb + s * KV_STAGE + 16384, &mWkv, 0, j * 64, hg * 2, 1, bar + B_FULLKV + 8 * s);
    }
  }
  __syncwarp();
  extern __shared__ __align__(1024) uint8_t smem[];
  if (smem_u32(smem) != SB) __trap();
  const int warp = __shfl_sync(~0u, threadIdx.x >> 5, 0);

  if (bid >= NCTA) {
    constexpr uint32_t XV = SM_WPHI, ONES = SM_ZT, BF = bar, BE = bar + 48, BX = bar + 96;
    constexpr int NJ = (DM - GROWS) / 64;
    const int lane = lane_id(), sp = bid - NCTA;
    const uint32_t tag = ld_rlx(g_epoch + bid * 32 + lane) + 1;
    if (warp == 8 && elect_one()) {
#pragma unroll 1
      for (int i = 0; i < 13; i++) mbar_init(bar + 8 * i, i >= 6 && i < 12 ? 8 : 1);
    }
    if (warp == 9) { sts64u(sb + ONES + lane * 8, 0x3f803f80u, 0x3f803f80u); fence_async_smem(); }
    __syncthreads();
    if (warp == 8) {
      if (elect_one()) {
        uint32_t s = 0, ph = 1;
#pragma unroll 1
        for (int job = 0; job < 8; job++) {
          const CUtensorMap* m = job == 0 ? &mWq : sp & 2 ? &mU2 : &mG2;
          const int g0 = job ? (sp & 1) * 28 + job * 4 - 4 : sp * 4;
#pragma unroll 1
          for (int row = job ? GROWS : 0; row < DM; row += 64) {
            mbar_wait(BE + 8 * s, ph);
            mbar_expect_tx(BF + 8 * s, Q_STAGE);
            tma4d(sb + s * Q_STAGE, m, 0, row, g0, 0, BF + 8 * s);
            tma4d(sb + s * Q_STAGE + 16384, m, 0, row, g0 + 2, 0, BF + 8 * s);
            if (++s == 6) { s = 0; ph ^= 1; }
          }
        }
      }
    } else if (warp == 9) {
      uint4 xr[4];
      routed_row(P.x, tag, lane, xr);
#pragma unroll
      for (int i = 0; i < 4; i++) sts128u(sb + XV + i * 512 + lane * 16, xr[i].x, xr[i].y, xr[i].z, xr[i].w);
      fence_async_smem();
      __syncwarp();
      if (lane == 0) mbar_arrive(BX);
    } else if (warp < 8) {
      uint32_t s = 0, ph = 0;
#pragma unroll 1
      for (int job = 0; job < 8; job++) {
        float d[8] = {0.f, 0.f, 0.f, 0.f, 0.f, 0.f, 0.f, 0.f};
        if (job == 1) mbar_wait(BX, 0);
#pragma unroll 1
        for (int i = 0; i < (job ? NJ : 16); i++) {
          mbar_wait(BF + 8 * s, ph);
          wg_fence();
#pragma unroll
          for (int k = 0; k < 8; k++)
            wgmma_n8_ss_ta1_tb0(d + 4 * (k >> 2), mkdesc(sb + k * 2048, 16, 1024, 1, s * (Q_STAGE / 16) + (warp >> 2) * 1024),
                                mkdesc(sb, 16, 128, 0, job ? (XV + GROWS * 2) / 16 + i * 8 + (k & 3) * 2 : ONES / 16), 1);
          wg_commit();
          wg_wait<0>();
          if (lane == 0) mbar_arrive(BE + 8 * s);
          if (++s == 6) { s = 0; ph ^= 1; }
        }
        reg_fence<8>(d);
        float* dst = (job ? g_gp + sp * 1792 + job * 256 - 256 : g_cs + sp * 256) + (warp >> 2) * 128 + (warp & 3) * 16 + (lane >> 2);
        if ((lane & 3) == 0) {
#pragma unroll
          for (int i = 0; i < 4; i++) st_rlx(dst + (i >> 1) * 64 + (i & 1) * 8, mark(__float_as_uint(d[2 * i]), tag & 1));
        }
        __syncwarp();
      }
      if (warp == 0) g_epoch[bid * 32 + lane] = tag;
    }
    return;
  }
#define Q_SLAB(J) ((J) < 8 ? ((J) + 8 - 2 * (hg & 4)) & 15 : 2 * (hg & 4) + 2 * ((J) & 3) + ((J) >> 2 & 1))
#define Q_AOFF(J) ((J) == 8 + (hg & 3) ? SM_X0 : (J) == 12 + (hg & 3) ? SM_X1 : ((J) & 3) * Q_STAGE)
#define Q_LOAD(J)                                                                                            \
  do {                                                                                                       \
    const uint32_t fb_ = bar + B_FULLQ + 8 * ((J) & 3);                                                      \
    const int k_ = Q_SLAB(J) * 64;                                                                           \
    mbar_expect_tx(fb_, Q_STAGE);                                                                            \
    mbar_arrive2(fb_);                                                                                       \
    tma2d(sb + Q_AOFF(J), &mX, k_, mb * 128, fb_);                                                           \
    tma4d(sb + ((J) & 3) * Q_STAGE + 16384, &mWq, 0, k_, hg * 2, 0, fb_);                                    \
  } while (0)
  if (warp >= 8) {
    asm volatile("setmaxnreg.dec.sync.aligned.u32 %0;" ::"n"(REG_H));
    const int lane = lane_id();
    const int f = (warp - 9) & 3;
    const uint32_t ep = ld_rlx(g_epoch + bid * 32 + lane);
    if (f < 2) {
#pragma unroll
      for (int i = 0; i < 2; i++) {
        const uint4 u = __ldg((const uint4*)P.w_r + (f * 2 + i) * 32 + lane);
        sts128u(sb + SM_XSEL + (f * 2 + i) * 512 + lane * 16, u.x, u.y, u.z, u.w);
      }
    }
    __syncwarp();
    bar_sync(0, 384);
    const uint32_t tag = ep + 1, par = tag & 1;
    const bool ffn = bid < NFFN;
    const int fb = bid, cu = bid >> 1, ch = bid & 1;
#define CS_STORE(SEC, C)                                                                                     \
  _Pragma("unroll") for (int r = 0; r < 3; r++) {                                                            \
    const uint32_t h0 = pack2(C.x, C.y), h1 = pack2(C.z, C.w);                                               \
    sts64u(sb + SM_CST + (SEC) * 1024 + (lane >> 4) * 512 + (lane & 1) * 8 + r * 128 + ((((lane & 15) >> 1) ^ (r + (lane >> 4) * 4)) << 4), h0, h1); \
    C.x -= bf_lo(h0); C.y -= bf_hi(h0); C.z -= bf_lo(h1); C.w -= bf_hi(h1);                                  \
  }
#define BAD4(U) ((U.x ^ par) | (U.y ^ par) | (U.z ^ par) | (U.w ^ par))
    const int n0 = f < 2 ? 0 : 2 * f - 3, ne = FFN_OFF || !ffn ? 3 : f == 3 ? 3 + G8 : 3 + GN;
    const uint32_t fsb = sb + SM_FST + ((f + 1) & 3) * 8192, fbar = bar + B_FST + f * 16, fst = fsb + (lane >> 4) * 2048 + (lane & 15) * 16;
    const CUtensorMap *ma = &mWc, *mc = &mWc;
    int sx = 1024 + cu * 32, sy = ch * 512 + f * 192, sdy = 32;
#define STAGEG(N)                                                                                            \
  do {                                                                                                       \
    if ((N) == 3) { ma = &mG; mc = &mU; sx = fb * 32; sy = f * (GN * 32);  sdy = 0; }                        \
    if ((N) < ne && elect_one()) {                                                                           \
      const uint32_t dst_ = fsb + ((N) & 1) * 4096, b_ = fbar + ((N) & 1) * 8;                               \
      mbar_expect_tx(b_, 4096);                                                                              \
      tma2d(dst_, ma, sx, sy, b_);                                                                           \
      tma2d(dst_ + 2048, mc, sx, sy + sdy, b_);                                                              \
    }                                                                                                        \
    sy += 32 + sdy;                                                                                          \
  } while (0)
    float a[8], gsum = 0.f, usum = 0.f;
    {
      if (f == 3) {
        if (elect_one()) {
          if (XS_EARLY) { mbar_expect_tx(bar + B_XST, 16384); tma3d(sb + SM_XST, &mXs, 0, bid * 16, 0, bar + B_XST); }
          mbar_expect_tx(bar + B_WPHI, 8192);
          tma2d(sb + SM_WPHI, &mPhi, 0, hg * 128, bar + B_WPHI);
          prefetch_map(&mWq); prefetch_map(&mWo); prefetch_map(&mWp); prefetch_map(&mD);
          PROF(31);
        }
        __syncwarp();
      } else {
        if (lane == 0) prefetch_map(f == 0 ? &mWc : f == 1 ? &mG : &mU);
        if (f == 2) ((float2*)g_y[par])[bid * 32 + lane] = make_float2(0.f, 0.f);
      }
      float st[13];
#pragma unroll
      for (int i = 0; i < 13; i++) st[i] = 0.f;
#pragma unroll 1
      for (int i = 0; i < 4; i++) {
        mbar_wait(bar + B_XST + 8 * (i >> 1), 0);
        if (f == 0 && lane == 0 && i == 0) PROF(1);
        const uint4 wu = lds128u(sb + SM_XSEL + i * 512 + lane * 16);
        const float wf[8] = {bf_lo(wu.x), bf_hi(wu.x), bf_lo(wu.y), bf_hi(wu.y), bf_lo(wu.z), bf_hi(wu.z), bf_lo(wu.w), bf_hi(wu.w)};
        st[12] += ((wf[0] + wf[1]) + (wf[2] + wf[3])) + ((wf[4] + wf[5]) + (wf[6] + wf[7]));
#pragma unroll
        for (int r = 0; r < 4; r++) {
          const uint4 u = lds128u(sb + SM_XST + i * 8192 + (4 * f + r) * 512 + lane * 16);
          const float xf[8] = {bf_lo(u.x), bf_hi(u.x), bf_lo(u.y), bf_hi(u.y), bf_lo(u.z), bf_hi(u.z), bf_lo(u.w), bf_hi(u.w)};
#pragma unroll
          for (int k = 0; k < 8; k++) { st[r] += xf[k]; st[4 + r] = fmaf(xf[k], xf[k], st[4 + r]); st[8 + r] = fmaf(xf[k], wf[k], st[8 + r]); }
        }
        if (i >= 2 && f < 3) STAGEG(n0 + i - 2);
      }
      const bool up = lane & 16, up2 = lane & 8;
#pragma unroll
      for (int q = 0; q < 3; q++) {
        const float k0 = up ? st[4 * q + 2] : st[4 * q], k1 = up ? st[4 * q + 3] : st[4 * q + 1];
        const float o0 = up ? st[4 * q] : st[4 * q + 2], o1 = up ? st[4 * q + 1] : st[4 * q + 3];
        const float m0 = k0 + __shfl_xor_sync(~0u, o0, 16), m1 = k1 + __shfl_xor_sync(~0u, o1, 16);
        a[q] = (up2 ? m1 : m0) + __shfl_xor_sync(~0u, up2 ? m0 : m1, 8);
      }
      a[3] = st[12] + __shfl_xor_sync(~0u, st[12], 16);
      a[3] += __shfl_xor_sync(~0u, a[3], 8);
#pragma unroll
      for (int o = 4; o; o >>= 1)
#pragma unroll
        for (int q = 0; q < 4; q++) a[q] += __shfl_xor_sync(~0u, a[q], o);
      if ((lane & 7) == 0) sts128(sb + SM_ROWS + (4 * f + (lane >> 3)) * 16, a[0], a[1], a[2], a[3]);
      if (f < 3) asm volatile("bar.arrive 7, 128;" ::: "memory");
    }
    if (f == 3) {
      bar_sync(7, 128);
      const int row = bid * 16 + (lane & 15);
      const float4 v = lds128(sb + SM_ROWS + (lane & 15) * 16);
      const float mf = v.x * (1.f / DM), mean = bf_round(mf), var = fmaxf(fmaf(-mf, mf, v.y * (1.f / DM)), 0.f);
      const float sd = bf_round(sqrt_approx(bf_round(bf_round(var) + 1e-5f)));
      const uint32_t rb = pack2(fmaf(-mean, v.w, v.z) * rcp(sd), 0.f) & 0xffffu, ord = (rb & 0x8000u) ? (~rb & 0xffffu) : (rb | 0x8000u);
      uint32_t best = __reduce_max_sync(~0u, (ord << 16) | (uint32_t)(2047 - row));
      if (lane < 16) st_rlx64(g_stat + row, ((unsigned long long)tag << 32) | __float_as_uint(mean) | (__float_as_uint(sd) >> 16));
      if (lane < 2) asm volatile("red.relaxed.gpu.global.max.u64 [%0], %1;" ::"l"(lane ? (void*)(g_ycnt + 32) : (void*)(g_best + bid)), "l"(((unsigned long long)tag << 32) | best) : "memory");
      if (lane == 1) { red_inc(g_ycnt + 34); PROF(17); }
#pragma unroll 1
      for (int n = 3; n < 5; n++) STAGEG(n);
      {
        uint4 xr[4];
        best = routed_row(P.x, tag, lane, xr);
#pragma unroll
        for (int i = 0; i < (GROWS + 255) / 256; i++) {
          const uint32_t dst = sb + SM_XSEL + i * 1024 + (lane >> 2) * 128 + (lane & 3) * 8;
          sts64(dst, bf_lo(xr[i].x), bf_lo(xr[i].z)); sts64(dst + 32, bf_hi(xr[i].x), bf_hi(xr[i].z));
          sts64(dst + 64, bf_lo(xr[i].y), bf_lo(xr[i].w)); sts64(dst + 96, bf_hi(xr[i].y), bf_hi(xr[i].w));
        }
        sts64u(sb + SM_RED + 16, tag, best);
        __syncwarp();
        if (lane == 0) { mbar_arrive(bar + B_XS); PROF(19); }
      }
      unsigned long long sv4[4];
      uint4 u[4];
#pragma unroll 1
      for (int it = 0; it < SPIN_MAX; it++) {
#pragma unroll
        for (int i = 0; i < 4; i++) { u[i] = ld_rlx128(g_cs + (1 + i) * 1024 + hg * 128 + lane * 4); sv4[i] = ld_rlx64(g_stat + mb * 128 + i * 32 + lane); }
        bool ok = ((BAD4(u[0]) | BAD4(u[1]) | BAD4(u[2]) | BAD4(u[3])) & 1) == 0;
#pragma unroll
        for (int i = 0; i < 4; i++) ok = ok && (uint32_t)(sv4[i] >> 32) == tag;
        if (__all_sync(~0u, ok)) break;
        __nanosleep(200);
      }
#pragma unroll
      for (int i = 0; i < 4; i++) {
        const uint32_t sv = (uint32_t)sv4[i], sd2 = (sv << 16) | (sv & 0xffffu);
        sts64(sb + SM_STAT + (i * 32 + lane) * 8, -bf_hi(sv), rcp(bf_lo(sv)));
        sts128u(sb + SM_SDT + lane * 64 + ((i ^ ((lane >> 1) & 3)) << 4), sd2, sd2, sd2, sd2);
      }
#pragma unroll
      for (int i = 0; i < 2; i++) {
        float4 c = make_float4(unmark(u[i].x) + unmark(u[i + 2].x), unmark(u[i].y) + unmark(u[i + 2].y), unmark(u[i].z) + unmark(u[i + 2].z),
                               unmark(u[i].w) + unmark(u[i + 2].w));
        CS_STORE(i, c);
      }
      fence_async_smem();
      bar_sync(8, 64);
      if (lane == 0) { mbar_arrive(bar + B_CS); PROF(10); }
    }
    {
      uint32_t xa = sb + SM_RED + 32, xstep = 0;
      const uint32_t zero = __float_as_uint(lds32(sb + SM_RED + 12));
#pragma unroll 1
      for (int ph = f == 3; ph < 2; ph++) {
#pragma unroll
        for (int j = 0; j < 8; j++) a[j] = 0.f;
        if (ph && f == 0) {
        {
          mbar_wait(bar + B_WPHI, 0);
          float nq[8] = {0.f, 0.f, 0.f, 0.f, 0.f, 0.f, 0.f, 0.f};
  #pragma unroll 2
          for (int r = 0; r < 16; r++) {
            const uint4 u = lds128u(sb + SM_WPHI + ((lane >> 2) * 16 + r) * 64 + (((lane ^ (r >> 1)) & 3) << 4));
            nq[0] = fmaf(bf_lo(u.x), bf_lo(u.x), nq[0]); nq[1] = fmaf(bf_hi(u.x), bf_hi(u.x), nq[1]); nq[2] = fmaf(bf_lo(u.y), bf_lo(u.y), nq[2]);
            nq[3] = fmaf(bf_hi(u.y), bf_hi(u.y), nq[3]); nq[4] = fmaf(bf_lo(u.z), bf_lo(u.z), nq[4]); nq[5] = fmaf(bf_hi(u.z), bf_hi(u.z), nq[5]);
            nq[6] = fmaf(bf_lo(u.w), bf_lo(u.w), nq[6]); nq[7] = fmaf(bf_hi(u.w), bf_hi(u.w), nq[7]);
          }
          uint32_t m = 0;
  #pragma unroll
          for (int i = 0; i < 8; i++) m = max(m, __float_as_uint(nq[i] + __shfl_xor_sync(~0u, nq[i], 4)) & 0x7fffffffu);
          sts32(sb + SM_RED + 24, 4.2f * __uint_as_float(__reduce_max_sync(~0u, m)));
        }
          asm volatile("bar.arrive 8, 64;" ::: "memory");
        }
        if (ph) { mbar_wait(bar + B_XS, 0); xa = sb + SM_XSEL + f * (GN * 128) + ((lane >> 2) & 3) * 32; xstep = 128; }
#pragma unroll 1
        for (int n = ph ? 3 : n0; n < (ph ? ne : 3); n++) {
          const float4 x0 = lds128(xa), x1 = lds128(xa + 16);
          xa += xstep;
          mbar_wait(fbar + (n & 1) * 8, ((n - n0) >> 1) & 1);
          uint4 u[8];
#pragma unroll
          for (int j = 0; j < 8; j++) u[j] = lds128u(fst + (n & 1) * 4096 + j * 256);
          FMA8(a, u[0], x0.x); FMA8(a, u[1], x0.y); FMA8(a, u[2], x0.z); FMA8(a, u[3], x0.w);
          if (__any_sync(~0u, ((u[4].x | u[5].x | u[6].x | u[7].x | __float_as_uint(a[0]) | __float_as_uint(a[7])) & zero) == 0)) STAGEG(n + 2);
          FMA8(a, u[4], x1.x); FMA8(a, u[5], x1.y); FMA8(a, u[6], x1.z); FMA8(a, u[7], x1.w);
        }
#pragma unroll
        for (int o = 4; o <= 8; o <<= 1)
#pragma unroll
          for (int j = 0; j < 8; j++) a[j] += __shfl_xor_sync(~0u, a[j], o);
        if (ph && lane == 0) mbar_arrive(bar + B_FFN);
        const uint32_t red = ph ? sb + SM_GRED : sb + SM_RED + 64;
        if ((lane & 12) == 0) {
          const uint32_t d = red + f * 256 + (lane >> 4) * 128 + (lane & 3) * 32;
          sts128(d, a[0], a[1], a[2], a[3]); sts128(d + 16, a[4], a[5], a[6], a[7]);
        }
        if (f != 2) {
          asm volatile("bar.arrive %0, %1;" ::"r"(4 + ph), "r"(96 + 32 * ph) : "memory");
        } else {
          bar_sync(4 + ph, 96 + 32 * ph);
          const uint32_t ra = red + lane * 4;
          gsum = lds32(ra) + lds32(ra + 256) + lds32(ra + 512);
          usum = lds32(ra + 128) + lds32(ra + 384) + lds32(ra + 640);
          if (!ph) st_rlx(g_cs + 1024 + ch * 2048 + cu * 32 + lane, mark(__float_as_uint(gsum + usum), par));
          else { gsum += lds32(ra + 768); usum += lds32(ra + 896); }
          if (lane == 0) PROF(ph ? 34 : 18);
        }
      }
    }
    if (f == 3) {
      if (elect_one()) {
        PROF(7);
        mbar_wait(bar + B_FULLQ, 0);
#pragma unroll 1
        for (int j = 3; j < 16; j++) {
          mbar_wait(bar + (j < 4 ? B_EMPTYKV + 16 : B_EMPTYQ + 8 * (j & 3)), ((j >> 2) & 1) ^ 1);
          if (j == 12 + (hg & 3)) mbar_wait(bar + B_KVST + 8, 0);
          Q_LOAD(j);
        }
        PROF(47);
        mbar_expect_tx(bar + B_DN, 65536);
#pragma unroll 1
        for (int i = 0; i < 4; i++) {
          mbar_wait(bar + B_EMPTYQ + 8 * i, 1);
          tma3d(sb + i * Q_STAGE, &mD, 0, fb * 32, i * 4, bar + B_DN);
        }
        PROF(48);
#pragma unroll 1
        for (int i = 0; i < 16; i++) {
          const int s = i & 3, n = i < 9 ? i - 2 : i - 9, kb = i < 2 ? 2 * hg + i : 2 * (n + (n >= hg)) + (i >= 9);
          if (i >= 4) mbar_wait(bar + B_EMPTYQ + 8 * s, ((i >> 2) & 1) ^ 1);
          mbar_expect_tx(bar + B_FULLQ + 8 * s, 16384);
          if (i < 2) {
            mbar_arrive2(bar + B_FULLQ + 8 * s);
            tma3d(sb + s * Q_STAGE + 16384, &mWo, 0, kb * 64, hg * 2, bar + B_FULLQ + 8 * s);
          } else {
            tma5d(sb + s * Q_STAGE + 16384, &mWp, hg * 128, kb * 2, bar + B_FULLQ + 8 * s);
            tma5d(sb + s * Q_STAGE + 24576, &mWp, hg * 128 + 64, kb * 2, bar + B_FULLQ + 8 * s);
            if (i >= 3) {
              if (i == 3) { mbar_wait(bar + B_DND, 0); PROF(14); }
#pragma unroll 1
              for (int a = i == 3 ? 2 : i; a <= i; a++) {
                const uint4* src = g_ofr + (mb * 16 + (a == 2 ? (hg == 0 ? 2 : 0) : kb)) * 1024;
#pragma unroll
                for (int h = 0; h < 2; h++) {
                  mbar_expect_tx(bar + B_AIN + (a & 3) * 16 + h * 8, 8192);
                  bulk_load(sb + (a & 3) * Q_STAGE + h * 8192, src + h * 512, 8192, bar + B_AIN + (a & 3) * 16 + h * 8);
                }
              }
            }
          }
        }
      }
    } else {
      if (f == 2) {
        if (PFD && ffn) {
#pragma unroll 1
          for (int i = 0; i < 16; i++) { touch_l2((const char*)P.w_down + fb * 65536 + i * 4096 + lane * 128, lane); __nanosleep(PFD); }
        }
        if (WOT) {
#pragma unroll 1
          for (int i = 0; i < 8; i++) { touch_l2((const char*)P.wo + ((mb & 7) * 128 + i * 16 + (lane >> 1)) * 2048 + hg * 256 + (lane & 1) * 128, lane); __nanosleep(PFD); }
        }
        asm volatile("cp.async.wait_all;" ::: "memory");
        uint4 u;
#pragma unroll 1
        for (int it = 0; it < SPIN_MAX; it++) {
          u = ld_rlx128(g_cs + hg * 128 + lane * 4);
          if (__all_sync(~0u, !(BAD4(u) & 1))) break;
          __nanosleep(200);
        }
        mbar_wait(bar + B_PHI, 0);
        float4 c = make_float4(unmark(u.x), unmark(u.y), unmark(u.z), unmark(u.w));
        CS_STORE(2, c);
        fence_async_smem();
        __syncwarp();
        if (lane == 0) mbar_arrive(bar + B_CSQ);
        if (ffn && !FFN_OFF) {
#pragma unroll 1
          for (int it = 0; it < SPIN_MAX; it++) {
            const uint32_t pg = ld_rlx((const uint32_t*)g_gp + fb * 32 + lane), pu = ld_rlx((const uint32_t*)g_gp + FF + fb * 32 + lane);
            if (__all_sync(~0u, !(((pg ^ par) | (pu ^ par)) & 1))) { gsum += unmark(pg); usum += unmark(pu); break; }
            __nanosleep(200);
          }
        }
        const float h = bf_round(silu_f(bf_round(gsum))) * bf_round(usum);
        const uint32_t h2 = pack2(h, h);
        sts128u(sb + SM_HT + lane * 16, h2, h2, h2, h2);
        fence_async_smem();
        __syncwarp();
        if (lane == 0) { mbar_arrive(bar + B_H); PROF(20); }
      }
      if (f < 2) {
        const uint32_t own = (hg * 2 + f) * 16 + mb, target = __shfl_sync(~0u, tag, 0) * 16;
        mbar_wait(bar + B_KVST + 8 * f, 0);
        if (f == 1 && lane == 0) PROF(11);
        wait_hint(g_xcnt + hg * 64 + f * 16 + mb, target);
        if (elect_one()) {
          PROF(35 + f);
          fence_async_global();
          mbar_expect_tx(bar + B_PART + 8 * f, 8192);
          bulk_load(sb + (f ? SM_PST1 : SM_PST0), g_part + own * 512, 8192, bar + B_PART + 8 * f);
        }
        __syncwarp();
        {
          uint4 uz;
#pragma unroll 1
          for (int it = 0; it < SPIN_MAX; it++) {
            uz = ld_rlx128(g_zpart + own * 128 + lane * 4);
            if (__all_sync(~0u, !(BAD4(uz) & 1))) break;
          }
          const bool b1 = lane & 2, b2 = lane & 4;
          const float z0 = unmark(b1 ? uz.z : uz.x) + __shfl_xor_sync(~0u, unmark(b1 ? uz.x : uz.z), 2);
          const float z1 = unmark(b1 ? uz.w : uz.y) + __shfl_xor_sync(~0u, unmark(b1 ? uz.y : uz.w), 2);
          float z = (b2 ? z1 : z0) + __shfl_xor_sync(~0u, b2 ? z0 : z1, 4);
          z += __shfl_xor_sync(~0u, z, 8);
          z += __shfl_xor_sync(~0u, z, 16);
          if (lane < 8) st_rlx(g_zres + own * 8 + (lane & 1) * 4 + (lane & 2) + (lane >> 2), mark(__float_as_uint(z), par));
          if (lane == 0) red_inc(g_xcnt + hg * 64 + 32 + f * 16);
          __syncwarp();
        }
        wait_hint(g_xcnt + hg * 64 + 32 + f * 16, 5 * target);
        mbar_wait(bar + B_KVST + 8, 0);
        if (lane == 0) PROF(40 + f);
#pragma unroll 1
        for (int it = 0; it < SPIN_MAX; it++) {
          if (elect_one()) {
            fence_async_global();
            mbar_expect_tx(bar + B_RES + 8 * f, 8192);
            bulk_load(sb + SM_V + f * 8192, g_res[par] + (hg * 4 + f * 2) * 256, 8192, bar + B_RES + 8 * f);
          }
          __syncwarp();
          const uint4 uz = ld_rlx128(g_zres + (hg * 4 + f * 2) * 64 + lane * 4);
          const uint32_t zw[4] = {uz.x, uz.y, uz.z, uz.w};
#pragma unroll
          for (int j = 0; j < 4; j++) {
            const uint32_t zz = pack2(unmark(zw[j]), 1.f), row = (lane & 3) * 4 + j;
            sts128u(sb + SM_ZT + (2 * f + (lane >> 4)) * 1024 + row * 64 + ((((lane >> 2) ^ (row >> 1)) & 3) << 4), zz, zz, zz, zz);
          }
          uint32_t bad = BAD4(uz);
          mbar_wait(bar + B_RES + 8 * f, it & 1);
#pragma unroll
          for (int i = 0; i < 16; i++) bad |= ~__float_as_uint(lds32(sb + SM_V + f * 8192 + i * 512 + lane * 16));
          if (__all_sync(~0u, !(bad & 1))) break;
        }
        fence_async_smem();
        __syncwarp();
        if (lane == 0) { mbar_arrive(bar + B_TILE + 8 * f); PROF(f ? 13 : 27); }
      }
      if (f < 2) {
        uint32_t phases = 0;
#pragma unroll 1
        for (int i = 2; i < 16; i++) {
          const int s = i & 3;
          const uint32_t ab = bar + B_AIN + s * 16 + f * 8, slot = sb + s * Q_STAGE + f * 8192;
#pragma unroll 1
          for (int it = 0; it < SPIN_MAX; it++) {
            mbar_wait(ab, (phases >> s) & 1);
            phases ^= 1u << s;
            uint32_t bad = 0;
#pragma unroll
            for (int n = 0; n < (NOVAL ? 0 : 8); n++) bad |= __float_as_uint(lds32(slot + n * 1024 + lane * 32 + (lane >> 2) * 4)) ^ par;
            if (__all_sync(~0u, !(bad & 1))) break;
            if (elect_one()) {
              const int n = i < 9 ? i - 2 : i - 9, kb = 2 * (n + (n >= hg)) + (i >= 9);
              PROF(49);
              mbar_expect_tx(ab, 8192);
              bulk_load(slot, g_ofr + (mb * 16 + kb) * 1024 + f * 512, 8192, ab);
            }
            __syncwarp();
          }
          if (lane == 0) { mbar_arrive(bar + B_FULLQ + 8 * s); if (i == 2 && f == 0) PROF(15); }
        }
        if (f == 0) g_epoch[bid * 32 + lane] = tag;
      } else {
        if (elect_one()) {
          prefetch_map(&mOut);
          if (ffn) { mbar_wait(bar + B_YD, 0); red_rel(g_ycnt); PROF(21); }
        }
        __syncwarp();
        if (f == 2) {
          const uint32_t best = __float_as_uint(lds32(sb + SM_RED + 20));
          const int sel = 2047 - (best & 0x7ff) - mb * 128;
          if (sel >= 0 && sel < 128) {
            const uint2 xr = __ldg((const uint2*)(P.x + (size_t)(mb * 128 + sel) * DM + hg * 128 + lane * 4));
            const float2 st = lds64(sb + SM_STAT + sel * 8);
            const uint32_t ord = best >> 16, rb = (ord & 0x8000u) ? (ord & 0x7fffu) : (~ord & 0xffffu);
            const float sg = rcp(1.f + ex2(-1.4426950408889634f * bf_lo(rb)));
            const uint32_t sg2 = pack2(sg, sg), nm2 = pack2(st.x, st.x);
            wait_cnt<0>(g_ycnt, tag * NFFN);
            float4 y = make_float4(0.f, 0.f, 0.f, 0.f);
#pragma unroll
            for (int i = 0; i < 8; i++) {
              const float4 c = ldg_cg4(g_y[par ^ 1][i] + hg * 128 + lane * 4);
              y.x += c.x; y.y += c.y; y.z += c.z; y.w += c.w;
            }
            uint32_t o[2];
#pragma unroll
            for (int i = 0; i < 2; i++) {
              const uint32_t d = badd2(i ? xr.y : xr.x, nm2);
              const uint32_t tt = badd2(pack2(bf_lo(d) * st.y, bf_hi(d) * st.y), bmul2(i ? pack2(y.z, y.w) : pack2(y.x, y.y), sg2));
              o[i] = pack2(silu_f(bf_lo(tt)), silu_f(bf_hi(tt)));
            }
            sts64u(sb + SM_UPD + lane * 8, o[0], o[1]);
          }
          if (lane == 0) sts32(sb + SM_UPD + 256, __int_as_float(sel));
          __syncwarp();
          if (lane == 0) { mbar_arrive(bar + B_UPD); PROF(22); }
        }
      }
    }
  } else {
    const int t7 = threadIdx.x & 127;
    const char* pfa = warp < 4 ? (const char*)P.x + bid * 32768 + (t7 & 15) * 2048 + (t7 >> 4) * 128
                               : (const char*)P.wqkv + (size_t)((t7 >> 4) * 64 + (bid >> 1)) * 6144 + 2048 + (bid & 1) * 2048 + (t7 & 15) * 128;
    if (t7 < 16 * PF_FIRST) prefetch_l2(pfa);
    if (warp < 7) sts128(sb + SM_CST + threadIdx.x * 16, 0.f, 0.f, 0.f, 0.f);
    else sts32(sb + SM_RED + (threadIdx.x & 15) * 4, threadIdx.x & 8 ? 1.f : 0.f);
    fence_async_smem();
    if (elect_one()) {
#pragma unroll 1
      for (uint32_t b = B_FST + warp * 8; b < B_END; b += 64)
        mbar_init(bar + b, b < B_FULLQ ? 1 : b < B_FFN ? 3 : b < B_EMPTYKV ? 4 : 8);
    }
    __syncwarp();
    asm volatile("setmaxnreg.inc.sync.aligned.u32 %0;" ::"n"(REG_C));
    if (PF_PRE && t7 >= 16 * PF_FIRST && threadIdx.x < 128 + 16 * PF_W) prefetch_l2(pfa);
    bar_sync(0, 384);
    if (!PF_PRE && t7 >= 16 * PF_FIRST && threadIdx.x < 128 + 16 * PF_W) prefetch_l2(pfa);
    const int lane = lane_id();
    const int wg = warp >> 2, w = warp & 3, g = lane >> 2, t = lane & 3;
    float kv[128];
    {
      uint32_t s = 2, ph = 0, sp = 0, php = 0;
#pragma unroll 1
      for (int j = 0; j < 15; j++) {
        PW0(32 + j); mbar_wait(bar + B_FULLKV + 8 * s, ph); PW1(32 + j);
        if (wg == 1 && (ORDER_ALL || j == 0)) bar_sync(10 + s, 256);
        wg_fence();
        wgmma_n256_ssp_ta0_tb1(kv, mkdesc(sb, 16, 1024, 1, wg * 512 + s * (KV_STAGE / 16)), mkdesc(sb + 16384, 8192, 1024, 1, s * (KV_STAGE / 16)), j);
#pragma unroll
        for (int k = 1; k < 4; k++)
          wgmma_n256_ss_ta0_tb1(kv, mkdesc(sb + k * 32, 16, 1024, 1, wg * 512 + s * (KV_STAGE / 16)),
                                mkdesc(sb + 16384 + k * 2048, 8192, 1024, 1, s * (KV_STAGE / 16)), 1);
        wg_commit();
        if (wg == 0 && (ORDER_ALL || j == 0)) asm volatile("bar.arrive %0, 256;" ::"r"(10 + s) : "memory");
        if (warp == 0 && j) {
          mbar_wait(bar + B_EMPTYKV + 8 * sp, php);
          if (elect_one()) {
            if (j < 14) {
              mbar_expect_tx(bar + B_FULLKV + 8 * sp, KV_STAGE);
              tma2d(sb + sp * KV_STAGE, &mX, (j + 2) * 64, mb * 128, bar + B_FULLKV + 8 * sp);
              tma4d(sb + sp * KV_STAGE + 16384, &mWkv, 0, (j + 2) * 64, hg * 2, 1, bar + B_FULLKV + 8 * sp);
            } else {
              Q_LOAD(0);
            }
            if (j < 3 - XS_EARLY) {
              const int xh = j - 1 + XS_EARLY;
              mbar_expect_tx(bar + B_XST + 8 * xh, 16384);
              tma3d(sb + SM_XST + xh * 16384, &mXs, 0, bid * 16, 2 * xh, bar + B_XST + 8 * xh);
            }
          }
          __syncwarp();
        }
        if (j == 0) {
          if (wg == 0) prefetch_l2(pfa + 1024);
        } else if (wg == 1) {
          if (j < 3) {
            if (j == 2 || t7 >= 16 * PF_W) prefetch_l2(pfa + (j - 1) * (8 * 393216));
          } else if (j == 13) {
            prefetch_l2((const char*)P.wo + bid * 16384 + t7 * 128);
          }
          if (PFG && !FFN_OFF && bid < NFFN && j >= 2 && j < 2 + GROWS / 64 && w < 2)
            touch_l2((const char*)((bid & 1) ? P.w_up : P.w_gate) + (size_t)((0x852a7419630ull >> (4 * j - 8) & 15) * 64 + t7) * 7168 + (bid >> 1) * 128, lane);
        }
        wg_wait<0>();
        if (lane == 0) mbar_arrive(bar + B_EMPTYKV + 8 * s);
        sp = s; php = ph;
        ph ^= s == 1;
        s = s == 2 ? 0 : s + 1;
      }
    }
    const int lrow = wg * 64 + w * 16 + (lane & 15);
    const uint32_t sw128 = lrow * 128, x128 = (lrow & 7), hi16 = lane >> 4;
    mbar_wait(bar + B_CS, 0);
    const uint32_t tag = __float_as_uint(lds32(sb + SM_RED + 16));
    const int zero = __float_as_int(lds32(sb + SM_RED + 12));
    const float wn = lds32(sb + SM_RED + 24);
    const float2 st0 = lds64(sb + SM_STAT + (wg * 64 + w * 16 + g) * 8), st1 = lds64(sb + SM_STAT + (wg * 64 + w * 16 + g + 8) * 8);
    const float c0 = st0.y * 1.4426950408889634f, c1 = st1.y * 1.4426950408889634f;
    const uint32_t nm20 = pack2(st0.x, st0.x), nm21 = pack2(st1.x, st1.x), fmask = t == 0 ? ~0u : t == 1 ? 0xffffu : 0u;
    const uint32_t fa0 = nm20 & fmask, fa1 = nm21 & fmask;
    asm volatile("cp.async.wait_all;" ::: "memory");
    PW0(47); mbar_wait(bar + B_FULLKV + 16, 1); PW1(47);
    wg_fence();
    wgmma_n256_rs_ta0_tb1(kv, fa0, fa1, 0u, 0u, mkdesc(sb + SM_CST, 512, 0, 1), 1);
#pragma unroll
    for (int k = 0; k < 4; k++)
      wgmma_n256_ss_ta0_tb1(kv, mkdesc(sb + 2 * KV_STAGE + k * 32, 16, 1024, 1, wg * 512), mkdesc(sb + 2 * KV_STAGE + 16384 + k * 2048, 8192, 1024, 1), 1);
    wg_commit();
    if (warp == 0) {
      mbar_wait(bar + B_EMPTYKV + 8, 0);
      if (elect_one()) {
#pragma unroll 1
        for (int j = 1; j < 3; j++) Q_LOAD(j);
      }
      __syncwarp();
    }
    wg_wait<0>();
    reg_fence<128>(kv);
    if (lane == 0) mbar_arrive(bar + B_EMPTYKV + 16);
    PROFC(2);
    float q[64];
#define QMMA(J, AOFF16, ACCUM)                                                                                     \
  _Pragma("unroll") for (int k = 0; k < 4; k++)                                                                    \
      wgmma_n128_ss_ta0_tb1(q, mkdesc(sb + k * 32, 16, 1024, 1, wg * 512 + (AOFF16)),                              \
                            mkdesc(sb + 16384 + k * 2048, 8192, 1024, 1, ((J) & 3) * (Q_STAGE / 16)), k ? 1 : (ACCUM))
#define QWAIT(J) do { PW0(J); mbar_wait(bar + B_FULLQ + 8 * ((J) & 3), ((J) >> 2) & 1); PW1(J); } while (0)
#define QSTEP_A(J, AOFF16, ACCUM) do { QWAIT(J); wg_fence(); QMMA(J, AOFF16, ACCUM); wg_commit(); } while (0)
#define QREL(J) do { if (lane == 0) mbar_arrive(bar + B_EMPTYQ + 8 * ((J) & 3)); } while (0)
#define Q_OFF16(J) ((J) >= 8 && (J) < 16 ? Q_AOFF(J) / 16 : ((J) & 3) * (Q_STAGE / 16))
#define QPLAIN(J) do { QSTEP_A(J, Q_OFF16(J), 1); wg_wait<1>(); QREL((J) - 1); } while (0)
#define QNEXT(J) do { QPLAIN(J); SCHED_FENCE(); } while (0)
#define PHI_PROJ(DST, SRC, H0, H1)                                                                                 \
  do {                                                                                                             \
    uint32_t a_[32];                                                                                               \
    _Pragma("unroll") for (int j = 8 * (H0); j < 8 * (H1); j++) {                                                  \
      a_[j] = pack2(SRC[2 * j], SRC[2 * j + 1]);                                                                   \
      asm volatile("fma.rn.bf16x2 %0, %1, %1, %0;" : "+r"(nq[(j >> 4) * 2 + (j & 1)]) : "r"(a_[j]));               \
    }                                                                                                              \
    wg_fence();                                                                                                    \
    _Pragma("unroll") for (int hk = 2 * (H0); hk < 2 * (H1); hk++)                                                 \
        wgmma_n32_rs_ta0_tb1(DST + 16 * (hk >> 1), a_[4 * hk], a_[4 * hk + 1], a_[4 * hk + 2], a_[4 * hk + 3],     \
                             mkdesc(sb + SM_WPHI + hk * 1024, 16, 512, 2), hk & 1);                                \
    wg_commit();                                                                                                   \
  } while (0)
    {
      float p[64], ea[24], eb[24], sa[4], sc[4], kz[20];
      uint32_t vp[32];
#pragma unroll
      for (int j = 0; j < 32; j++) vp[j] = pack2(kv[64 + 2 * j], kv[65 + 2 * j]);
      const uint32_t vr = w * 16 + (lane & 15), vb = sb + SM_V + wg * 4096 + vr * 64, x64 = (vr >> 1) & 3;
#define V_STORE(R)                                                                                           \
  _Pragma("unroll") for (int j = 0; j < 4; j++)                                                              \
      stsm4(vb + (j >> 1) * 8192 + ((((j & 1) * 2 + hi16) ^ x64) << 4), vp[16 * (R) + 4 * j], vp[16 * (R) + 4 * j + 1], vp[16 * (R) + 4 * j + 2], vp[16 * (R) + 4 * j + 3])
      V_STORE(0);
      mbar_wait(bar + B_WPHI, 0);
      {
        uint32_t nq[4] = {0u, 0u, 0u, 0u};
        PHI_PROJ(p, kv, 0, 4);
        QSTEP_A(0, 0, 0);
        const bool unsafe = softmax_unsafe(nq, c0 * c0 * wn, c1 * c1 * wn);
        wg_wait<1>();
        reg_fence<64>(p);
        if (__builtin_expect(unsafe, 0)) softmax_shift(p, c0, c1);
      }
#define K_NORM(S) do { quad_sum<4>(S); _Pragma("unroll") for (int i = 0; i < 4; i++) S[i] = rcp(S[i]) * ((i & 1) ? st1.y : st0.y); } while (0)
#define K_STORE(SLOT, E, S) K_STORE_(SLOT, E, S, 0, 2)
#define K_STORE_(SLOT, E, S, J0, J1)                                                                         \
  _Pragma("unroll") for (int j = (J0); j < (J1); j++) {                                                      \
    uint32_t fp[4], fm[4];                                                                                   \
    _Pragma("unroll") for (int i = 0; i < 4; i++) {                                                          \
      const float e0 = E[8 * j + 2 * i], e1 = E[8 * j + 2 * i + 1], r = E[16 + 4 * j + i] * S[2 + (i & 1)];  \
      const uint32_t e2 = pack2(e0, e1);                                                                     \
      fp[i] = bmul2(e2, pack2(S[i & 1], S[i & 1]));                                                          \
      fm[i] = bmul2(e2, pack2(r, r));                                                                        \
    }                                                                                                        \
    stsm4(sb + SM_PHI + (SLOT) * 16384 + sw128 + (((2 * j + hi16) ^ x128) << 4), fp[0], fp[1], fp[2], fp[3]); \
    stsm4(sb + SM_PHI + (SLOT) * 16384 + sw128 + (((4 + 2 * j + hi16) ^ x128) << 4), fm[0], fm[1], fm[2], fm[3]); \
  }
#define KV_MMA(R)                                                                                            \
  do {                                                                                                       \
    mbar_wait(bar + B_PHI + 8 * (R), 0);                                                                     \
    wg_fence();                                                                                              \
    _Pragma("unroll") for (int k = 0; k < 8; k++) {                                                          \
      const uint32_t vs = SM_V + (k >> 2) * 4096 + (k & 3) * 1024;                                           \
      wgmma_n40_ss_ta1_tb1(kz, mkdesc(sb + SM_PHI + k * 2048, 16, 1024, 1, wg * 1024),                       \
                           mkdesc(sb + vs, SM_SDT + (k & 1) * 1024 + (k >> 1) * 16 - vs, 512, 2, wg * (512u - (512u << 16))), k); \
    }                                                                                                        \
    wg_commit();                                                                                             \
  } while (0)
#define QKV(J, R) do { KV_MMA(R); QSTEP_A(J, Q_OFF16(J), 1); wg_wait<2>(); QREL((J) - 1); SCHED_FENCE(); } while (0)
#define KV_SEND(R)                                                                                           \
  do {                                                                                                       \
    reg_fence<20>(kz);                                                                                       \
    if (lane == 0) mbar_arrive(bar + B_KVST + 8 * (R));                                                      \
    const uint32_t slot = ((hg * 2 + (R)) * 16 + warp * 2) * 16 + mb;                                        \
    _Pragma("unroll") for (int u = 0; u < 2; u++)                                                            \
      st_rlx128(g_part + (slot + u * 16) * 32 + lane, mark(pack2(kz[2 * u], kz[2 * u + 1]), tag & 1), pack2(kz[2 * u + 4], kz[2 * u + 5]), \
                pack2(kz[2 * u + 8], kz[2 * u + 9]), pack2(kz[2 * u + 12], kz[2 * u + 13]));                 \
    if (t < 2) st_rlx(g_zpart + (slot + t * 16) * 8 + g, mark(__float_as_uint(t ? kz[18] : kz[16]), tag & 1)); \
    if (lane < 2) red_inc(g_xcnt + hg * 64 + (R) * 16 + warp * 2 + lane);                                    \
  } while (0)
#define K_PUB(R) do { fence_async_smem(); __syncwarp(); if (lane == 0) mbar_arrive(bar + B_PHI + 8 * (R)); } while (0)
#define S_PIN(S) SCHED_PIN(S[0] + S[1] + S[2] + S[3])
      k_exp(p, c0, c1, ea, sa);
      S_PIN(sa);
      QNEXT(1);
      K_NORM(sa);
      k_exp<0, 4>(p + 16, c0, c1, eb, sc);
      mbar_wait(bar + B_FFN, 0);
      K_STORE_(0, ea, sa, 0, 1);
      S_PIN(sc);
      QNEXT(2);
      K_STORE_(0, ea, sa, 1, 2);
      k_exp<4, 8>(p + 16, c0, c1, eb, sc);
      K_NORM(sc);
      S_PIN(sc);
      QNEXT(3);
      K_STORE(1, eb, sc);
      K_PUB(0);
      k_exp<0, 4>(p + 32, c0, c1, ea, sa);
      S_PIN(sa);
      QKV(4, 0);
      k_exp<4, 8>(p + 32, c0, c1, ea, sa);
      K_NORM(sa);
      k_exp<0, 4>(p + 48, c0, c1, eb, sc);
      SCHED_PIN(sa[0] + sa[1] + sa[2] + sa[3] + sc[2] + sc[3]);
      QNEXT(5);
      KV_SEND(0);
      k_exp<4, 8>(p + 48, c0, c1, eb, sc);
      S_PIN(sc);
      QNEXT(6);
      K_NORM(sc);
      mbar_wait(bar + B_KVST, 0);
      V_STORE(1);
      K_STORE(0, ea, sa);
      QNEXT(7);
      K_STORE(1, eb, sc);
      K_PUB(1);
      QKV(8, 1);
      QNEXT(9);
      KV_SEND(1);
    }
#define JQ0 10
    PROFC(3);
    {
      bool todo = true;
#pragma unroll 1
      for (int j = JQ0; j < 15 || todo; j++) {
        if (j < 15) { QSTEP_A(j, Q_AOFF(j) / 16, 1); wg_wait<1>(); QREL(j - 1); }
        if (todo && __any_sync(~0u, mbar_test(bar + B_PART + 8 * wg, 0))) {
          todo = false;
          const uint32_t own = (hg * 2 + wg) * 16 + mb, word = w * 32 + lane;
          uint32_t u[16], bad = 0;
#pragma unroll
          for (int i = 0; i < 16; i++) { u[i] = __float_as_uint(lds32(sb + (wg ? SM_PST1 : SM_PST0) + i * 512 + word * 4)); bad |= u[i] ^ tag; }
#pragma unroll 1
          for (int it = 0; it < SPIN_MAX && __any_sync(~0u, t == 0 && (bad & 1)); it++) {
            bad = 0;
#pragma unroll
            for (int i = 0; i < 16; i++) { u[i] = ld_rlx((const uint32_t*)g_part + own * 2048 + i * 128 + word); bad |= u[i] ^ tag; }
          }
          float s0 = 0.f, s1 = 0.f, s2 = 0.f, s3 = 0.f;
#pragma unroll
          for (int i = 0; i < 16; i += 2) { s0 += bf_lo(u[i] | !t); s1 += bf_hi(u[i]); s2 += bf_lo(u[i + 1] & (t ? ~0u : ~1u)); s3 += bf_hi(u[i + 1]); }
          const uint32_t r = pack2(s0 + s2, s1 + s3);
          st_rlx((uint32_t*)g_res[tag & 1] + own * 128 + w * 32 + (lane & 16) + ((t ^ w) << 2) + ((lane >> 2) & 3), lane & 12 ? r : r | 1);
          ((uint32_t*)g_res[~tag & 1])[own * 128 + word] = 0;
          __syncwarp();
          if (lane == 0) { red_inc(g_xcnt + hg * 64 + 32 + wg * 16); if (w == 0) PROF(wg ? 12 : 30); }
          __syncwarp();
        }
      }
    }
    mbar_wait(bar + B_CSQ, 0);
    QWAIT(15);
    if (wg == 1) bar_sync(6, 256);
    wg_fence();
    wgmma_n128_rs_ta0_tb1(q, fa0, fa1, 0u, 0u, mkdesc(sb + SM_CST + 2048, 512, 0, 1), 1);
    QMMA(15, Q_AOFF(15) / 16, 1);
    wg_commit();
    if (wg == 0) asm volatile("bar.arrive 6, 256;" ::: "memory");
    wg_wait<1>();
    QREL(14);
    wg_wait<0>();
    QREL(15);
    reg_fence<64>(q);
    PROFC(5);
    float yp[4];
    const uint32_t par = tag & 1;
    uint4* ofr = g_ofr + (mb * 16 + hg * 2) * 1024 + (warp * 16 + g) * 8;
#define O_MMA(H, F, N)                                                                                       \
  do {                                                                                                       \
    wg_fence();                                                                                              \
    _Pragma("unroll") for (int k = 0; k < 4; k++) {                                                          \
      const uint32_t ks = SM_V + (H) * 4096 + k * 1024;                                                      \
      wgmma_n40_rs_ta0_tb1(N + 20 * (k >> 1), F[4 * k], F[4 * k + 1], F[4 * k + 2], F[4 * k + 3],            \
                           mkdesc(sb + ks, SM_ZT + (H) * 1024 + k * 16 - ks, 512, 2), k & 1);                \
    }                                                                                                        \
    wg_commit();                                                                                             \
  } while (0)
#define O_FIN(H, N, o)                                                                                        \
  do {                                                                                                       \
    reg_fence<40>(N);                                                                                        \
    const float *np = N, *nm = N + 20;                                                                       \
    const float d0 = rcp(fmaf(np[16], nm[17], fmaf(nm[16], np[17], 1e-6f * np[17] * nm[17])));               \
    const float d1 = rcp(fmaf(np[18], nm[19], fmaf(nm[18], np[19], 1e-6f * np[19] * nm[19])));               \
    const float bp0 = nm[17] * d0, bm0 = np[17] * d0, bp1 = nm[19] * d1, bm1 = np[19] * d1;                  \
    _Pragma("unroll") for (int j = 0; j < 4; j++) {                                                          \
      o[2 * j] = pack2(fmaf(np[4 * j], bp0, nm[4 * j] * bm0), fmaf(np[4 * j + 1], bp0, nm[4 * j + 1] * bm0)); \
      o[2 * j + 1] = pack2(fmaf(np[4 * j + 2], bp1, nm[4 * j + 2] * bm1), fmaf(np[4 * j + 3], bp1, nm[4 * j + 3] * bm1)); \
    }                                                                                                        \
  } while (0)
#define O_STG(H, o)                                                                                          \
  _Pragma("unroll") for (int u = 0; u < 2; u++) {                                                            \
    uint32_t v_[4];                                                                                          \
    _Pragma("unroll") for (int j = 0; j < 4; j++) v_[j] = lop_select(o[2 * j + u], parm, vword == j);        \
    st_rlx128(ofr + ((H) >> 1) * 1024 + u * 64 + ((((H) & 1) * 4 + t) ^ g), v_[0], v_[1], v_[2], v_[3]);     \
  }
    uint32_t gf[32], ao[16];
    const uint32_t parm = 0u - par, vword = ((t ^ g) & 1) == (g >> 2) ? g & 3 : 4;
    const float rh0 = 0.5f * st0.y, rh1 = 0.5f * st1.y, mh0 = st0.x * rh0, mh1 = st1.x * rh1;
#define GATE_LD(J) ldsm4(sb + ((J) >> 2 ? SM_X1 : SM_X0) + sw128 + (((((J) & 3) * 2 + hi16) ^ x128) << 4), gf[4 * (J)], gf[4 * (J) + 1], gf[4 * (J) + 2], gf[4 * (J) + 3])
#define GATE(I0, I1)                                                                                         \
  _Pragma("unroll") for (int i = (I0); i < (I1); i++) {                                                      \
    const float rs = (i & 1) ? rh1 : rh0, mh = (i & 1) ? mh1 : mh0;                                          \
    const float h0 = fmaf(bf_lo(gf[i]), rs, mh), h1 = fmaf(bf_hi(gf[i]), rs, mh);                            \
    gf[i] = pack2(fmaf(h0, tanh_approx(h0), h0), fmaf(h1, tanh_approx(h1), h1));                             \
  }
#define GATE_PIN(I0, I1) do { uint32_t o_ = 0; _Pragma("unroll") for (int i = (I0); i < (I1); i++) o_ |= gf[i]; SCHED_PIN(__uint_as_float(o_)); } while (0)
    {
      float p[64], na[40], nb[40];
      uint32_t fa[16], fb[16];
      {
        uint32_t nq[4] = {0u, 0u, 0u, 0u};
        PHI_PROJ(p, q, 0, 2);
        SCHED_FENCE();
        PHI_PROJ(p, q, 2, 4);
        const bool unsafe = softmax_unsafe(nq, c0 * c0 * wn, c1 * c1 * wn);
        if (TW == 0) mbar_wait(bar + B_TILE, 0);
        wg_wait<0>();
        reg_fence<64>(p);
        PROFC(24);
        if (__builtin_expect(unsafe, 0)) softmax_shift(p, c0, c1);
      }
      float dn[32];
#define DN_PART(A, B)                                                                                        \
  do {                                                                                                       \
    wg_fence();                                                                                              \
    _Pragma("unroll") for (int i = (A); i < (B); i++)                                                        \
      wgmma_n8_ss_ta1_tb1(dn + 4 * (i >> 1), mkdesc(sb + (i >> 3) * Q_STAGE + (i & 7) * 2048, 16, 1024, 1, wg * (2 * Q_STAGE / 16)), \
                          mkdesc(sb + SM_HT + (i & 1) * 256, 128, 128, 0), i & 1);                           \
  } while (0)
#define F_PIN(F, A, B) do { uint32_t o_ = 0; _Pragma("unroll") for (int i = (A); i < (B); i++) o_ |= F[8 + i]; SCHED_PIN(__uint_as_float(o_)); } while (0)
#define RMMA(J, A, ACCUM)                                                                                    \
  do {                                                                                                       \
    wg_fence();                                                                                              \
    _Pragma("unroll") for (int k = 0; k < 4; k++)                                                            \
      wgmma_n128_rs_ta0_tb1(q, (A)[4 * k], (A)[4 * k + 1], (A)[4 * k + 2], (A)[4 * k + 3],                   \
                            mkdesc(sb + 16384 + k * 2048, 8192, 1024, 1, ((J) & 3) * (Q_STAGE / 16)), k ? 1 : (ACCUM)); \
    wg_commit();                                                                                             \
  } while (0)
#define RSTEP(J, A, ACCUM) do { QWAIT(J); RMMA(J, A, ACCUM); } while (0)
      PROFC(4);
      q_exp(p, c0, c1, fa);
      if (TW == 1) { F_PIN(fa, 0, 8); mbar_wait(bar + B_TILE, 0); }
      if (TW == 2) { q_exp(p + 16, c0, c1, fb); F_PIN(fb, 0, 8); mbar_wait(bar + B_TILE, 0); }
      O_MMA(0, fa, na);
      if (TW != 2) q_exp(p + 16, c0, c1, fb);
      O_MMA(1, fb, nb);
      PROFC(25);
      wg_wait<1>();
      O_FIN(0, na, ao);
      O_STG(0, ao);
      wg_wait<0>();
      O_FIN(1, nb, (ao + 8));
      O_STG(1, (ao + 8));
      PROFC(28);
      RSTEP(16, ao, 0);
      SCHED_FENCE();
      q_exp(p + 32, c0, c1, fa);
      F_PIN(fa, 0, 8);
      mbar_wait(bar + B_H, 0);
      mbar_wait(bar + B_DN, 0);
      PROFC(45);
      DN_PART(0, 4);
      SCHED_FENCE();
      q_exp<0, 2>(p + 48, c0, c1, fb);
      F_PIN(fb, 0, 2);
      DN_PART(4, 8);
      SCHED_FENCE();
      q_exp<2, 4>(p + 48, c0, c1, fb);
      F_PIN(fb, 2, 4);
      DN_PART(8, 12);
      SCHED_FENCE();
      q_exp<4, 6>(p + 48, c0, c1, fb);
      F_PIN(fb, 4, 6);
      DN_PART(12, 16);
      wg_commit();
      SCHED_FENCE();
      q_exp<6, 8>(p + 48, c0, c1, fb);
      F_PIN(fb, 6, 8);
      wg_wait<0>();
      reg_fence<32>(dn);
      if (lane == 0) mbar_arrive(bar + B_DND);
      QREL(16);
#pragma unroll
      for (int i = 0; i < 4; i++) yp[i] = t & 2 ? (t & 1 ? dn[24 + 2 * i] : dn[16 + 2 * i]) : (t & 1 ? dn[8 + 2 * i] : dn[2 * i]);
      PROFC(29);
      mbar_wait(bar + B_TILE + 8, 0);
      PROFC(23);
      if (bid < NFFN) {
        float* y = g_y[par ^ 1][bid & 7] + wg * 512 + t * 128 + w * 16 + g;
#pragma unroll
        for (int i = 0; i < 4; i++) red1(y + (i >> 1) * 64 + (i & 1) * 8, yp[i]);
      }
      SCHED_FENCE();
      O_MMA(2, fa, na);
      O_MMA(3, fb, nb);
      __syncwarp();
      if (lane == 0) mbar_arrive(bar + B_YD);
      wg_wait<1>();
      O_FIN(2, na, ao);
      O_STG(2, ao);
      wg_wait<0>();
      O_FIN(3, nb, (ao + 8));
      O_STG(3, (ao + 8));
      PROFC(6);
    }
    RSTEP(17, ao, 1);
    SCHED_FENCE();
    GATE_LD(0); GATE_LD(1);
    GATE(0, 4);
    GATE_PIN(0, 4);
#define GSTEP(J, I) do { QNEXT(J); if ((I) < 7) GATE_LD(((I) + 1) & 7); GATE(4 * (I), 4 * (I) + 4); GATE_PIN(4 * (I), 4 * (I) + 4); } while (0)
    GSTEP(18, 1); GSTEP(19, 2); GSTEP(20, 3); GSTEP(21, 4); GSTEP(22, 5); GSTEP(23, 6); GSTEP(24, 7);
#pragma unroll 1
    for (int j = 25; j < 32 - TAILN; j++) QPLAIN(j);
    if (wg == 1) bar_sync(6, 256);
#pragma unroll 1
    for (int j = 32 - TAILN; j < 32; j++) QSTEP_A(j, (j & 3) * (Q_STAGE / 16), 1);
    if (wg == 0) asm volatile("bar.arrive 6, 256;" ::: "memory");
    mbar_wait(bar + B_UPD, 0);
    {
      const int sel = __float_as_int(lds32(sb + SM_UPD + 256)) - (wg * 64 + w * 16 + g);
      if (sel == 0 || sel == 8) {
#pragma unroll
        for (int j = 0; j < 16; j++) {
          const uint32_t u = __float_as_uint(lds32(sb + SM_UPD + j * 16 + t * 4));
          if (sel) gf[2 * j + 1] = u; else gf[2 * j] = u;
        }
      }
      __syncwarp();
      uint32_t xf[32];
#pragma unroll
      for (int j = 0; j < 8; j++)
        ldsm4(sb + (j >> 2 ? SM_X1 : SM_X0) + sw128 + ((((j & 3) * 2 + hi16) ^ x128) << 4), xf[4 * j], xf[4 * j + 1], xf[4 * j + 2], xf[4 * j + 3]);
      wg_wait<0>();
      reg_fence<64>(q);
      PROFC(8);
#pragma unroll
      for (int j = 0; j < 8; j++) {
        uint32_t o[4];
#pragma unroll
        for (int i = 0; i < 4; i++) o[i] = badd2(xf[4 * j + i], bmul2(pack2(q[8 * j + 2 * i], q[8 * j + 2 * i + 1]), gf[4 * j + i]));
        stsm4(sb + (j >> 2 ? SM_X1 : SM_X0) + sw128 + ((((j & 3) * 2 + hi16) ^ x128) << 4), o[0], o[1], o[2], o[3]);
      }
    }
    fence_async_smem();
    bar_sync(2 + wg, 128);
    if (w == 0 && elect_one()) {
      tma_store2d(&mOut, sb + SM_X0 + wg * 8192, hg * 128, mb * 128 + wg * 64);
      tma_store2d(&mOut, sb + SM_X1 + wg * 8192, hg * 128 + 64, mb * 128 + wg * 64);
      bulk_commit();
      bulk_wait_read0();
      if (wg == 1) { PROF(9); PROFT(33); PROF_DUMP; }
    }
  }
}

typedef CUresult (*EncodeFn)(CUtensorMap*, CUtensorMapDataType, cuuint32_t, void*, const cuuint64_t*, const cuuint64_t*, const cuuint32_t*,
                             const cuuint32_t*, CUtensorMapInterleave, CUtensorMapSwizzle, CUtensorMapL2promotion, CUtensorMapFloatOOBfill);

CUtensorMap make_map(EncodeFn enc, const void* ptr, int rank, const cuuint64_t* dims, const cuuint64_t* strides, const cuuint32_t* box, CUtensorMapSwizzle sw) {
  CUtensorMap m;
  const cuuint32_t es[5] = {1, 1, 1, 1, 1};
  enc(&m, CU_TENSOR_MAP_DATA_TYPE_BFLOAT16, rank, (void*)ptr, dims, strides, box, es, CU_TENSOR_MAP_INTERLEAVE_NONE, sw,
      CU_TENSOR_MAP_L2_PROMOTION_L2_128B, CU_TENSOR_MAP_FLOAT_OOB_FILL_NONE);
  return m;
}

}

extern "C" void kernel_launch(void* const* d_in, const int* in_sizes, int n_in, void* d_out, int out_size) {
  static EncodeFn enc = nullptr;
  static int by_sm = 0;
  if (!enc) {
    void* fn = nullptr;
    cudaDriverEntryPointQueryResult qr;
    cudaGetDriverEntryPoint("cuTensorMapEncodeTiled", &fn, cudaEnableDefault, &qr);
    enc = (EncodeFn)fn;
    cudaFuncSetAttribute(fused_kernel<false>, cudaFuncAttributeMaxDynamicSharedMemorySize, SM_TOTAL);
    cudaFuncSetAttribute(fused_kernel<true>, cudaFuncAttributeMaxDynamicSharedMemorySize, SM_TOTAL);
    int dev = 0, sms = 0;
    cudaGetDevice(&dev);
    cudaDeviceGetAttribute(&sms, cudaDevAttrMultiProcessorCount, dev);
    by_sm = BY_SM && sms == NCTA + NSPARE;
  }
  Params P;
  P.x = (const __nv_bfloat16*)d_in[0];
  P.wqkv = (const __nv_bfloat16*)d_in[1];
  const void* wphi = d_in[2];
  P.wo = (const __nv_bfloat16*)d_in[3];
  P.w_r = (const __nv_bfloat16*)d_in[5];
  P.w_gate = (const __nv_bfloat16*)d_in[6];
  P.w_up = (const __nv_bfloat16*)d_in[7];
  P.w_down = (const __nv_bfloat16*)d_in[8];

  const cuuint64_t dX[2] = {DM, SEQ}, sX[1] = {DM * 2};
  const cuuint32_t b128[2] = {64, 128}, b64[2] = {64, 64};
  const cuuint64_t dW[4] = {64, DM, 16, 3}, sW[3] = {3 * DM * 2, 128, DM * 2};
  const cuuint32_t bKV[4] = {64, 64, 2, 2}, bQ[4] = {64, 64, 2, 1};
  const cuuint64_t dO[3] = {64, DM, 16}, sO[2] = {DM * 2, 128};
  const cuuint32_t bO[3] = {64, 64, 2};
  const cuuint64_t dP[2] = {32, 1024}, sP[1] = {64};
  const cuuint32_t bP[2] = {32, 128};
  CUtensorMap mX = make_map(enc, P.x, 2, dX, sX, b128, CU_TENSOR_MAP_SWIZZLE_128B);
  CUtensorMap mWkv = make_map(enc, P.wqkv, 4, dW, sW, bKV, CU_TENSOR_MAP_SWIZZLE_128B);
  CUtensorMap mWq = make_map(enc, P.wqkv, 4, dW, sW, bQ, CU_TENSOR_MAP_SWIZZLE_128B);
  CUtensorMap mWo = make_map(enc, P.wo, 3, dO, sO, bO, CU_TENSOR_MAP_SWIZZLE_128B);
  CUtensorMap mPhi = make_map(enc, wphi, 2, dP, sP, bP, CU_TENSOR_MAP_SWIZZLE_64B);
  const cuuint64_t dWp[5] = {DM, 2, 4, 4, DM / 32}, sWp[4] = {DM * 2, 8 * DM * 2, 2 * DM * 2, 32 * DM * 2};
  const cuuint32_t bWp[5] = {64, 2, 4, 4, 2};
  CUtensorMap mWp = make_map(enc, P.wo, 5, dWp, sWp, bWp, CU_TENSOR_MAP_SWIZZLE_128B);
  CUtensorMap mOut = make_map(enc, d_out, 2, dX, sX, b64, CU_TENSOR_MAP_SWIZZLE_128B);
  const cuuint64_t dWc[2] = {3 * DM, DM}, sWc[1] = {3 * DM * 2}, dG[2] = {FF, DM}, sG[1] = {FF * 2}, dD[3] = {64, FF, 16};
  const cuuint32_t b32[2] = {32, 32}, bD[3] = {64, 32, 4};
  CUtensorMap mWc = make_map(enc, P.wqkv, 2, dWc, sWc, b32, CU_TENSOR_MAP_SWIZZLE_NONE);
  CUtensorMap mG = make_map(enc, P.w_gate, 2, dG, sG, b32, CU_TENSOR_MAP_SWIZZLE_NONE);
  CUtensorMap mU = make_map(enc, P.w_up, 2, dG, sG, b32, CU_TENSOR_MAP_SWIZZLE_NONE);
  CUtensorMap mD = make_map(enc, P.w_down, 3, dD, sO, bD, CU_TENSOR_MAP_SWIZZLE_128B);
  const cuuint64_t dXs[3] = {256, SEQ, 4}, sXs[2] = {DM * 2, 512};
  const cuuint32_t bXs[3] = {256, 16, 2};
  CUtensorMap mXs = make_map(enc, P.x, 3, dXs, sXs, bXs, CU_TENSOR_MAP_SWIZZLE_NONE);
  const cuuint64_t dG2[4] = {64, DM, FF / 64, 1}, sG2[3] = {FF * 2, 128, (cuuint64_t)FF * DM * 2};
  CUtensorMap mG2 = make_map(enc, P.w_gate, 4, dG2, sG2, bQ, CU_TENSOR_MAP_SWIZZLE_128B);
  CUtensorMap mU2 = make_map(enc, P.w_up, 4, dG2, sG2, bQ, CU_TENSOR_MAP_SWIZZLE_128B);
  (by_sm ? fused_kernel<true> : fused_kernel<false>)<<<NCTA + NSPARE, 384, SM_TOTAL, cudaStreamPerThread>>>(mX, mWkv, mWq, mWo, mPhi, mWp, mOut, mWc, mG, mU, mD, mXs,
                                                                                                           mG2, mU2, P);
}
```

```cpp
#include <cuda_runtime.h>
#include <cuda_bf16.h>
#include <cuda.h>
#include <stdint.h>

namespace {

constexpr int SEQ = 2048, DM = 1024, FF = 3584;
constexpr int NCTA = 128;
constexpr int NSPARE = 4;
constexpr int NFFN = FF / 32;
#define GN 6
#define G8 2
constexpr int GROWS = (3 * GN + G8) * 32;
#define TAILN 2
#define KTAIL 1
#define XS_EARLY 1
#define PF_FIRST 2
#define PF_W 5
#define PF_PRE 1
#define PFG 0
#define PFD 80
#define BY_SM 1
#define PTAB 0x73216540u
#define ROWSPLIT 1
#define WOT 1
#define PSPLIT 1
#define KSTEPS 4
#define NOVAL 0
#define KCH 1
#define REG_C 224
#define REG_H 56
#define TW 1
#define FENCE_KIND 2
#define ORDER_ALL 1
#define AM_NS 100
constexpr bool FFN_OFF = false;

static_assert(2 * REG_C + REG_H <= 3 * 168, "the register pool of the CTA is 384 x 168");

__device__ uint32_t g_epoch[(NCTA + NSPARE) * 32];
__device__ unsigned long long g_stat[SEQ];
__device__ __align__(128) unsigned long long g_best[NCTA];
__device__ __align__(16) float g_y[2][8][DM];
__device__ __align__(128) uint32_t g_ycnt[64];
__device__ __align__(128) uint32_t g_xcnt[8 * 64];
__device__ __align__(128) uint4 g_res[2][32 * 256];
__device__ __align__(16) float g_cs[5 * DM];
__device__ __align__(128) float g_gp[2 * FF];
__device__ uint4 g_part[8 * 2 * 16 * 16 * 32];
__device__ __align__(16) float g_zpart[8 * 2 * 16 * 16 * 8];
__device__ __align__(128) float g_zres[32 * 64];
__device__ __align__(1024) uint4 g_ofr[16 * 16 * 1024];
#define PROF(i)
#define PROFT(i)
#define PROFC(i)
#define PROF_DUMP
#define PW0(J)
#define PW1(J)

constexpr uint32_t KV_STAGE = 49152, Q_STAGE = 32768;
constexpr uint32_t SM_V = 147456;
constexpr uint32_t SM_PHI = 163840;
constexpr uint32_t SM_XST = 147456;
constexpr uint32_t SM_FST = 172032;
constexpr uint32_t SM_PST0 = 196608, SM_PST1 = SM_PHI + 8192;
constexpr uint32_t SM_X0 = 131072, SM_X1 = SM_PHI + 16384;
constexpr uint32_t SM_WPHI = 204800;
constexpr uint32_t SM_ZT = 212992;
constexpr uint32_t SM_SDT = 217088;
constexpr uint32_t SM_CST = 219136;
constexpr uint32_t SM_HT = 222720;
constexpr uint32_t SM_STAT = 223232;
constexpr uint32_t SM_XSEL = 224256;
constexpr uint32_t SM_RED = 228352;
constexpr uint32_t SM_ROWS = SM_RED + 832;
constexpr uint32_t SM_GRED = SM_XSEL + 3072;
static_assert(GROWS <= 768, "xsel area");
constexpr uint32_t SM_UPD = 229632;
constexpr uint32_t SM_BAR = 230016;
constexpr uint32_t SM_PROF = 230464;
constexpr uint32_t SM_SINK = 231104;
constexpr uint32_t SM_TOTAL = 231616;
constexpr uint32_t SB = 1024;
constexpr uint32_t B_FULLKV = 0  , B_FST = 24  , B_XFULL = 88  , B_XST = 104  , B_WPHI = 120, B_CS = 128, B_CSQ = 136, B_UPD = 144,
                   B_H = 152, B_DN = 160, B_XS = 168, B_TILE = 176  , B_RES = 192  , B_PART = 208  ,
B_AIN = 224  ,
                   B_FULLQ = 288  ,
                   B_FFN = 320,
                   B_EMPTYKV = 328  , B_EMPTYQ = 352  , B_KVST = 384  , B_YD = 400, B_PHI = 408  , B_DND = 424, B_END = 432;

__device__ __forceinline__ uint32_t smem_u32(const void* p) { return (uint32_t)__cvta_generic_to_shared(p); }
__device__ __forceinline__ void mbar_init(uint32_t bar, uint32_t cnt) { asm volatile("mbarrier.init.shared::cta.b64 [%0], %1;" ::"r"(bar), "r"(cnt) : "memory"); }
__device__ __forceinline__ void mbar_expect_tx(uint32_t bar, uint32_t bytes) { asm volatile("mbarrier.arrive.expect_tx.shared::cta.b64 _, [%0], %1;" ::"r"(bar), "r"(bytes) : "memory"); }
__device__ __forceinline__ void mbar_arrive2(uint32_t bar) { asm volatile("mbarrier.arrive.shared::cta.b64 _, [%0], 2;" ::"r"(bar) : "memory"); }
__device__ __forceinline__ void mbar_arrive(uint32_t bar) { asm volatile("mbarrier.arrive.shared::cta.b64 _, [%0];" ::"r"(bar) : "memory"); }
__device__ __forceinline__ void mbar_wait(uint32_t bar, uint32_t parity) {
  asm volatile("{\n.reg .pred p;\nLW:\nmbarrier.try_wait.parity.shared::cta.b64 p, [%0], %1;\n@!p bra LW;\n}" ::"r"(bar), "r"(parity) : "memory");
}
__device__ __forceinline__ bool mbar_test(uint32_t bar, uint32_t parity) {
  uint32_t ok;
  asm volatile("{\n.reg .pred p;\nmbarrier.test_wait.parity.shared::cta.b64 p, [%1], %2;\nselp.u32 %0, 1, 0, p;\n}" : "=r"(ok) : "r"(bar), "r"(parity) : "memory");
  return ok;
}
__device__ __forceinline__ int lane_id() { int l; asm volatile("mov.u32 %0, %%laneid;" : "=r"(l)); return l; }
template <int C> __device__ __forceinline__ void sched_fence_(int zero) {
  asm volatile("{\n.reg .pred p;\nsetp.eq.s32 p, %0, %1;\n@p trap;\n}" ::"r"(zero), "n"(C) : "memory");
}
#define SCHED_FENCE() sched_fence_<1000 + __COUNTER__>(zero)
#define SCHED_PIN(V) sched_fence_<1000 + __COUNTER__>(zero & __float_as_int(V))
__device__ __forceinline__ bool elect_one() {
  uint32_t p; asm volatile("{ .reg .pred P; elect.sync _|P, 0xffffffff; selp.u32 %0, 1, 0, P; }" : "=r"(p)); return p;
}
__device__ __forceinline__ void tma2d(uint32_t dst, const CUtensorMap* m, int x, int y, uint32_t bar) {
  asm volatile("cp.async.bulk.tensor.2d.shared::cluster.global.mbarrier::complete_tx::bytes [%0], [%1, {%3, %4}], [%2];" ::"r"(dst), "l"(m), "r"(bar), "r"(x), "r"(y) : "memory");
}
__device__ __forceinline__ void tma3d(uint32_t dst, const CUtensorMap* m, int x, int y, int z, uint32_t bar) {
  asm volatile("cp.async.bulk.tensor.3d.shared::cluster.global.mbarrier::complete_tx::bytes [%0], [%1, {%3, %4, %5}], [%2];" ::"r"(dst), "l"(m), "r"(bar), "r"(x), "r"(y), "r"(z) : "memory");
}
__device__ __forceinline__ void tma4d(uint32_t dst, const CUtensorMap* m, int x, int y, int z, int w, uint32_t bar) {
  asm volatile("cp.async.bulk.tensor.4d.shared::cluster.global.mbarrier::complete_tx::bytes [%0], [%1, {%3, %4, %5, %6}], [%2];" ::"r"(dst), "l"(m), "r"(bar), "r"(x), "r"(y), "r"(z), "r"(w) : "memory");
}
__device__ __forceinline__ void tma5d(uint32_t dst, const CUtensorMap* m, int x, int v, uint32_t bar) {
  asm volatile("cp.async.bulk.tensor.5d.shared::cluster.global.mbarrier::complete_tx::bytes [%0], [%1, {%3, %5, %5, %5, %4}], [%2];" ::"r"(dst), "l"(m), "r"(bar), "r"(x), "r"(v), "r"(0) : "memory");
}
__device__ __forceinline__ void tma_store2d(const CUtensorMap* m, uint32_t src, int x, int y) {
  asm volatile("cp.async.bulk.tensor.2d.global.shared::cta.bulk_group [%0, {%2, %3}], [%1];" ::"l"(m), "r"(src), "r"(x), "r"(y) : "memory");
}
__device__ __forceinline__ void bulk_load(uint32_t dst, const void* src, uint32_t bytes, uint32_t bar) {
  asm volatile("cp.async.bulk.shared::cluster.global.mbarrier::complete_tx::bytes [%0], [%1], %2, [%3];" ::"r"(dst), "l"(src), "r"(bytes), "r"(bar) : "memory");
}
__device__ __forceinline__ void bulk_commit() { asm volatile("cp.async.bulk.commit_group;" ::: "memory"); }
__device__ __forceinline__ void bulk_wait0() { asm volatile("cp.async.bulk.wait_group 0;" ::: "memory"); }
__device__ __forceinline__ void bulk_wait_read0() { asm volatile("cp.async.bulk.wait_group.read 0;" ::: "memory"); }
__device__ __forceinline__ void prefetch_l2(const void* p) { asm volatile("prefetch.global.L2 [%0];" ::"l"(p) : "memory"); }
__device__ __forceinline__ void touch_l2(const void* p, int lane) { asm volatile("cp.async.cg.shared.global.L2::128B [%0], [%1], 16;" ::"r"(SB + SM_SINK + lane * 16), "l"(p) : "memory"); }
__device__ __forceinline__ void cp_async16(uint32_t dst, const void* src) { asm volatile("cp.async.cg.shared.global [%0], [%1], 16;" ::"r"(dst), "l"(src) : "memory"); }
__device__ __forceinline__ void prefetch_map(const CUtensorMap* m) { asm volatile("prefetch.tensormap [%0];" ::"l"(m) : "memory"); }
__device__ __forceinline__ void fence_async_smem() { asm volatile("fence.proxy.async.shared::cta;" ::: "memory"); }
__device__ __forceinline__ void fence_async_global() { asm volatile("fence.proxy.async.global;" ::: "memory"); }
__device__ __forceinline__ void bar_sync(int id, int n) { asm volatile("bar.sync %0, %1;" ::"r"(id), "r"(n) : "memory"); }
__device__ __forceinline__ void wg_fence() { asm volatile("wgmma.fence.sync.aligned;" ::: "memory"); }
__device__ __forceinline__ void wg_commit() { asm volatile("wgmma.commit_group.sync.aligned;" ::: "memory"); }
template <int N> __device__ __forceinline__ void wg_wait() { asm volatile("wgmma.wait_group.sync.aligned %0;" ::"n"(N) : "memory"); }
template <int N> __device__ __forceinline__ void reg_fence(uint32_t* r) {
#pragma unroll
  for (int i = 0; i < N; i++) asm volatile("" : "+r"(r[i])::"memory");
}
template <int N> __device__ __forceinline__ void reg_fence(float* r) {
#pragma unroll
  for (int i = 0; i < N; i++) asm volatile("" : "+f"(r[i])::"memory");
}
__device__ __forceinline__ uint64_t mkdesc(uint32_t addr, uint32_t lbo, uint32_t sbo, uint32_t swz, uint32_t dyn = 0) {
  const uint32_t lo = ((addr >> 4) | ((lbo >> 4) << 16)) + dyn;
  const uint32_t hi = (sbo >> 4) | (swz << 30);
  uint64_t d;
  asm("mov.b64 %0, {%1, %2};" : "=l"(d) : "r"(lo), "r"(hi));
  return d;
}
__device__ __forceinline__ void stsm4(uint32_t addr, uint32_t a, uint32_t b, uint32_t c, uint32_t d) {
  asm volatile("stmatrix.sync.aligned.m8n8.x4.shared.b16 [%0], {%1, %2, %3, %4};" ::"r"(addr), "r"(a), "r"(b), "r"(c), "r"(d) : "memory");
}
__device__ __forceinline__ void ldsm4(uint32_t addr, uint32_t& a, uint32_t& b, uint32_t& c, uint32_t& d) {
  asm volatile("ldmatrix.sync.aligned.m8n8.x4.shared.b16 {%0, %1, %2, %3}, [%4];" : "=r"(a), "=r"(b), "=r"(c), "=r"(d) : "r"(addr) : "memory");
}
__device__ __forceinline__ uint32_t pack2(float lo, float hi) { uint32_t r; asm("cvt.rn.bf16x2.f32 %0, %1, %2;" : "=r"(r) : "f"(hi), "f"(lo)); return r; }
__device__ __forceinline__ uint32_t bsub2(uint32_t a, uint32_t b) { uint32_t r; asm("sub.rn.bf16x2 %0, %1, %2;" : "=r"(r) : "r"(a), "r"(b)); return r; }
__device__ __forceinline__ uint32_t badd2(uint32_t a, uint32_t b) { uint32_t r; asm("add.rn.bf16x2 %0, %1, %2;" : "=r"(r) : "r"(a), "r"(b)); return r; }
__device__ __forceinline__ uint32_t bmul2(uint32_t a, uint32_t b) { uint32_t r; asm("mul.rn.bf16x2 %0, %1, %2;" : "=r"(r) : "r"(a), "r"(b)); return r; }
__device__ __forceinline__ float bf_lo(uint32_t v) { return __uint_as_float(v << 16); }
__device__ __forceinline__ float bf_hi(uint32_t v) { return __uint_as_float(v & 0xffff0000u); }
__device__ __forceinline__ float bf_round(float v) { return bf_lo(pack2(v, 0.f)); }
__device__ __forceinline__ float ex2(float v) { float r; asm("ex2.approx.ftz.f32 %0, %1;" : "=f"(r) : "f"(v)); return r; }
__device__ __forceinline__ float rcp(float v) { float r; asm("rcp.approx.ftz.f32 %0, %1;" : "=f"(r) : "f"(v)); return r; }
__device__ __forceinline__ float sqrt_approx(float v) { float r; asm("sqrt.approx.f32 %0, %1;" : "=f"(r) : "f"(v)); return r; }
__device__ __forceinline__ float4 lds128(uint32_t a) { float4 v; asm volatile("ld.shared.v4.f32 {%0, %1, %2, %3}, [%4];" : "=f"(v.x), "=f"(v.y), "=f"(v.z), "=f"(v.w) : "r"(a) : "memory"); return v; }
__device__ __forceinline__ uint4 lds128u(uint32_t a) { uint4 v; asm volatile("ld.shared.v4.u32 {%0, %1, %2, %3}, [%4];" : "=r"(v.x), "=r"(v.y), "=r"(v.z), "=r"(v.w) : "r"(a) : "memory"); return v; }
__device__ __forceinline__ float2 lds64(uint32_t a) { float2 v; asm volatile("ld.shared.v2.f32 {%0, %1}, [%2];" : "=f"(v.x), "=f"(v.y) : "r"(a) : "memory"); return v; }
__device__ __forceinline__ float lds32(uint32_t a) { float v; asm volatile("ld.shared.f32 %0, [%1];" : "=f"(v) : "r"(a) : "memory"); return v; }
__device__ __forceinline__ void sts32(uint32_t a, float v) { asm volatile("st.shared.f32 [%0], %1;" ::"r"(a), "f"(v) : "memory"); }
__device__ __forceinline__ void sts64(uint32_t a, float x, float y) { asm volatile("st.shared.v2.f32 [%0], {%1, %2};" ::"r"(a), "f"(x), "f"(y) : "memory"); }
__device__ __forceinline__ void sts128(uint32_t a, float x, float y, float z, float w) { asm volatile("st.shared.v4.f32 [%0], {%1, %2, %3, %4};" ::"r"(a), "f"(x), "f"(y), "f"(z), "f"(w) : "memory"); }
__device__ __forceinline__ void sts64u(uint32_t a, uint32_t x, uint32_t y) { asm volatile("st.shared.v2.u32 [%0], {%1, %2};" ::"r"(a), "r"(x), "r"(y) : "memory"); }
__device__ __forceinline__ void sts128u(uint32_t a, uint32_t x, uint32_t y, uint32_t z, uint32_t w) { asm volatile("st.shared.v4.u32 [%0], {%1, %2, %3, %4};" ::"r"(a), "r"(x), "r"(y), "r"(z), "r"(w) : "memory"); }
__device__ __forceinline__ uint4 ldg_nc(const void* p) { uint4 v; asm volatile("ld.global.nc.L1::no_allocate.v4.u32 {%0, %1, %2, %3}, [%4];" : "=r"(v.x), "=r"(v.y), "=r"(v.z), "=r"(v.w) : "l"(p)); return v; }
__device__ __forceinline__ float4 ldg_cg4(const float* p) { float4 v; asm volatile("ld.global.cg.v4.f32 {%0, %1, %2, %3}, [%4];" : "=f"(v.x), "=f"(v.y), "=f"(v.z), "=f"(v.w) : "l"(p) : "memory"); return v; }
__device__ __forceinline__ uint32_t ld_acq(const uint32_t* p) { uint32_t v; asm volatile("ld.acquire.gpu.global.u32 %0, [%1];" : "=r"(v) : "l"(p) : "memory"); return v; }
__device__ __forceinline__ uint32_t ld_acq_cta(uint32_t a) { uint32_t v; asm volatile("ld.acquire.cta.shared.u32 %0, [%1];" : "=r"(v) : "r"(a) : "memory"); return v; }
__device__ __forceinline__ void st_rel_cta(uint32_t a, uint32_t v) { asm volatile("st.release.cta.shared.u32 [%0], %1;" ::"r"(a), "r"(v) : "memory"); }
__device__ __forceinline__ unsigned long long ld_rlx64(const unsigned long long* p) { unsigned long long v; asm volatile("ld.relaxed.gpu.global.u64 %0, [%1];" : "=l"(v) : "l"(p) : "memory"); return v; }
__device__ __forceinline__ void st_rlx64(unsigned long long* p, unsigned long long v) { asm volatile("st.relaxed.gpu.global.u64 [%0], %1;" ::"l"(p), "l"(v) : "memory"); }
__device__ __forceinline__ uint4 ld_rlx128(const void* p) {
  uint4 v;
  asm volatile("{ .reg .b128 t; .reg .b64 a, b; ld.relaxed.gpu.global.b128 t, [%4]; mov.b128 {a, b}, t; mov.b64 {%0, %1}, a; mov.b64 {%2, %3}, b; }"
               : "=r"(v.x), "=r"(v.y), "=r"(v.z), "=r"(v.w) : "l"(p) : "memory");
  return v;
}
__device__ __forceinline__ void st_rlx128(void* p, uint32_t x, uint32_t y, uint32_t z, uint32_t w) {
  asm volatile("{ .reg .b128 t; .reg .b64 a, b; mov.b64 a, {%1, %2}; mov.b64 b, {%3, %4}; mov.b128 t, {a, b}; st.relaxed.gpu.global.b128 [%0], t; }"
               ::"l"(p), "r"(x), "r"(y), "r"(z), "r"(w) : "memory");
}
__device__ __forceinline__ void stg128(void* p, uint32_t x, uint32_t y, uint32_t z, uint32_t w) { asm volatile("st.global.v4.u32 [%0], {%1, %2, %3, %4};" ::"l"(p), "r"(x), "r"(y), "r"(z), "r"(w) : "memory"); }
__device__ __forceinline__ void st_rlx(void* p, uint32_t v) { asm volatile("st.relaxed.gpu.global.u32 [%0], %1;" ::"l"(p), "r"(v) : "memory"); }
__device__ __forceinline__ uint32_t lop_select(uint32_t a, uint32_t b, uint32_t m) { uint32_t r; asm("lop3.b32 %0, %1, %2, %3, 0xd8;" : "=r"(r) : "r"(a), "r"(b), "r"(m)); return r; }
__device__ __forceinline__ float unmark(uint32_t v) { return __uint_as_float(v & ~1u); }
__device__ __forceinline__ uint32_t mark(uint32_t v, uint32_t par) { return (v & ~1u) | par; }
__device__ __forceinline__ float tanh_approx(float v) { float r; asm("tanh.approx.f32 %0, %1;" : "=f"(r) : "f"(v)); return r; }
__device__ __forceinline__ void flag_rel(uint32_t* p, uint32_t v) { asm volatile("red.release.gpu.global.max.u32 [%0], %1;" ::"l"(p), "r"(v) : "memory"); }
__device__ __forceinline__ void red1(float* p, float a) { asm volatile("red.global.add.f32 [%0], %1;" ::"l"(p), "f"(a) : "memory"); }
__device__ __forceinline__ void red_inc(uint32_t* p) { asm volatile("red.relaxed.gpu.global.add.u32 [%0], 1;" ::"l"(p) : "memory"); }
__device__ __forceinline__ void red_rel(uint32_t* p) { asm volatile("red.release.gpu.global.add.u32 [%0], 1;" ::"l"(p) : "memory"); }
__device__ __forceinline__ void red4(float* p, float a, float b, float c, float d) { asm volatile("red.global.add.v4.f32 [%0], {%1, %2, %3, %4};" ::"l"(p), "f"(a), "f"(b), "f"(c), "f"(d) : "memory"); }
constexpr int SPIN_MAX = 100000;
__device__ __forceinline__ uint32_t ld_rlx(const uint32_t* p) { uint32_t v; asm volatile("ld.relaxed.gpu.global.u32 %0, [%1];" : "=r"(v) : "l"(p) : "memory"); return v; }
template <int NS = 0> __device__ __forceinline__ void wait_hint(const uint32_t* p, uint32_t target) {
#pragma unroll 1
  for (int i = 0; i < SPIN_MAX; i++) { if ((int)(ld_rlx(p) - target) >= 0) break; if (NS) __nanosleep(NS); }
}
template <int NS> __device__ __forceinline__ void wait_cnt(const uint32_t* p, uint32_t target) {
#pragma unroll 1
  for (int i = 0; i < SPIN_MAX; i++) { if ((int)(ld_rlx(p) - target) >= 0) break; if (NS) __nanosleep(NS); }
  (void)ld_acq(p);
}
template <int NS> __device__ __forceinline__ unsigned long long wait_tag(const unsigned long long* p, uint32_t tag) {
  unsigned long long v = 0;
#pragma unroll 1
  for (int i = 0; i < SPIN_MAX; i++) { v = ld_rlx64(p); if ((uint32_t)(v >> 32) == tag) break; if (NS) __nanosleep(NS); }
  return v;
}
__device__ __forceinline__ float silu_f(float v) { return v * rcp(1.f + ex2(-1.4426950408889634f * v)); }

__device__ __forceinline__ void wgmma_n8_ss_ta1_tb0(float* d, uint64_t da, uint64_t db, bool accumulate) {
  if (accumulate) {
    asm volatile("{\n.reg .pred p;\nsetp.ne.b32 p, 1, 0;\n"
      "wgmma.mma_async.sync.aligned.m64n8k16.f32.bf16.bf16 "
      "{%0, %1, %2, %3}, "
      "%4, %5, p, 1, 1, 1, 0;\n}\n"
      : "+f"(d[0]), "+f"(d[1]), "+f"(d[2]), "+f"(d[3])
      : "l"(da), "l"(db));
  } else {
    asm volatile("{\n.reg .pred p;\nsetp.ne.b32 p, 0, 0;\n"
      "wgmma.mma_async.sync.aligned.m64n8k16.f32.bf16.bf16 "
      "{%0, %1, %2, %3}, "
      "%4, %5, p, 1, 1, 1, 0;\n}\n"
      : "=f"(d[0]), "=f"(d[1]), "=f"(d[2]), "=f"(d[3])
      : "l"(da), "l"(db));
  }
}
__device__ __forceinline__ void wgmma_n8_ss_ta1_tb1(float* d, uint64_t da, uint64_t db, bool accumulate) {
  if (accumulate) {
    asm volatile("{\n.reg .pred p;\nsetp.ne.b32 p, 1, 0;\n"
      "wgmma.mma_async.sync.aligned.m64n8k16.f32.bf16.bf16 "
      "{%0, %1, %2, %3}, "
      "%4, %5, p, 1, 1, 1, 1;\n}\n"
      : "+f"(d[0]), "+f"(d[1]), "+f"(d[2]), "+f"(d[3])
      : "l"(da), "l"(db));
  } else {
    asm volatile("{\n.reg .pred p;\nsetp.ne.b32 p, 0, 0;\n"
      "wgmma.mma_async.sync.aligned.m64n8k16.f32.bf16.bf16 "
      "{%0, %1, %2, %3}, "
      "%4, %5, p, 1, 1, 1, 1;\n}\n"
      : "=f"(d[0]), "=f"(d[1]), "=f"(d[2]), "=f"(d[3])
      : "l"(da), "l"(db));
  }
}
__device__ __forceinline__ void wgmma_n32_rs_ta0_tb1(float* d, uint32_t a0, uint32_t a1, uint32_t a2, uint32_t a3, uint64_t db, bool accumulate) {
  if (accumulate) {
    asm volatile("{\n.reg .pred p;\nsetp.ne.b32 p, 1, 0;\n"
      "wgmma.mma_async.sync.aligned.m64n32k16.f32.bf16.bf16 "
      "{%0, %1, %2, %3, %4, %5, %6, %7, %8, %9, %10, %11, %12, %13, %14, %15}, "
      "{%16, %17, %18, %19}, %20, p, 1, 1, 1;\n}\n"
      : "+f"(d[0]), "+f"(d[1]), "+f"(d[2]), "+f"(d[3]), "+f"(d[4]), "+f"(d[5]), "+f"(d[6]), "+f"(d[7]), "+f"(d[8]), "+f"(d[9]), "+f"(d[10]), "+f"(d[11]), "+f"(d[12]), "+f"(d[13]), "+f"(d[14]), "+f"(d[15])
      : "r"(a0), "r"(a1), "r"(a2), "r"(a3), "l"(db));
  } else {
    asm volatile("{\n.reg .pred p;\nsetp.ne.b32 p, 0, 0;\n"
      "wgmma.mma_async.sync.aligned.m64n32k16.f32.bf16.bf16 "
      "{%0, %1, %2, %3, %4, %5, %6, %7, %8, %9, %10, %11, %12, %13, %14, %15}, "
      "{%16, %17, %18, %19}, %20, p, 1, 1, 1;\n}\n"
      : "=f"(d[0]), "=f"(d[1]), "=f"(d[2]), "=f"(d[3]), "=f"(d[4]), "=f"(d[5]), "=f"(d[6]), "=f"(d[7]), "=f"(d[8]), "=f"(d[9]), "=f"(d[10]), "=f"(d[11]), "=f"(d[12]), "=f"(d[13]), "=f"(d[14]), "=f"(d[15])
      : "r"(a0), "r"(a1), "r"(a2), "r"(a3), "l"(db));
  }
}
__device__ __forceinline__ void wgmma_n40_rs_ta0_tb1(float* d, uint32_t a0, uint32_t a1, uint32_t a2, uint32_t a3, uint64_t db, bool accumulate) {
  if (accumulate) {
    asm volatile("{\n.reg .pred p;\nsetp.ne.b32 p, 1, 0;\n"
      "wgmma.mma_async.sync.aligned.m64n40k16.f32.bf16.bf16 "
      "{%0, %1, %2, %3, %4, %5, %6, %7, %8, %9, %10, %11, %12, %13, %14, %15, %16, %17, %18, %19}, "
      "{%20, %21, %22, %23}, %24, p, 1, 1, 1;\n}\n"
      : "+f"(d[0]), "+f"(d[1]), "+f"(d[2]), "+f"(d[3]), "+f"(d[4]), "+f"(d[5]), "+f"(d[6]), "+f"(d[7]), "+f"(d[8]), "+f"(d[9]), "+f"(d[10]), "+f"(d[11]), "+f"(d[12]), "+f"(d[13]), "+f"(d[14]), "+f"(d[15]), "+f"(d[16]), "+f"(d[17]), "+f"(d[18]), "+f"(d[19])
      : "r"(a0), "r"(a1), "r"(a2), "r"(a3), "l"(db));
  } else {
    asm volatile("{\n.reg .pred p;\nsetp.ne.b32 p, 0, 0;\n"
      "wgmma.mma_async.sync.aligned.m64n40k16.f32.bf16.bf16 "
      "{%0, %1, %2, %3, %4, %5, %6, %7, %8, %9, %10, %11, %12, %13, %14, %15, %16, %17, %18, %19}, "
      "{%20, %21, %22, %23}, %24, p, 1, 1, 1;\n}\n"
      : "=f"(d[0]), "=f"(d[1]), "=f"(d[2]), "=f"(d[3]), "=f"(d[4]), "=f"(d[5]), "=f"(d[6]), "=f"(d[7]), "=f"(d[8]), "=f"(d[9]), "=f"(d[10]), "=f"(d[11]), "=f"(d[12]), "=f"(d[13]), "=f"(d[14]), "=f"(d[15]), "=f"(d[16]), "=f"(d[17]), "=f"(d[18]), "=f"(d[19])
      : "r"(a0), "r"(a1), "r"(a2), "r"(a3), "l"(db));
  }
}
__device__ __forceinline__ void wgmma_n40_ss_ta1_tb1(float* d, uint64_t da, uint64_t db, bool accumulate) {
  if (accumulate) {
    asm volatile("{\n.reg .pred p;\nsetp.ne.b32 p, 1, 0;\n"
      "wgmma.mma_async.sync.aligned.m64n40k16.f32.bf16.bf16 "
      "{%0, %1, %2, %3, %4, %5, %6, %7, %8, %9, %10, %11, %12, %13, %14, %15, %16, %17, %18, %19}, "
      "%20, %21, p, 1, 1, 1, 1;\n}\n"
      : "+f"(d[0]), "+f"(d[1]), "+f"(d[2]), "+f"(d[3]), "+f"(d[4]), "+f"(d[5]), "+f"(d[6]), "+f"(d[7]), "+f"(d[8]), "+f"(d[9]), "+f"(d[10]), "+f"(d[11]), "+f"(d[12]), "+f"(d[13]), "+f"(d[14]), "+f"(d[15]), "+f"(d[16]), "+f"(d[17]), "+f"(d[18]), "+f"(d[19])
      : "l"(da), "l"(db));
  } else {
    asm volatile("{\n.reg .pred p;\nsetp.ne.b32 p, 0, 0;\n"
      "wgmma.mma_async.sync.aligned.m64n40k16.f32.bf16.bf16 "
      "{%0, %1, %2, %3, %4, %5, %6, %7, %8, %9, %10, %11, %12, %13, %14, %15, %16, %17, %18, %19}, "
      "%20, %21, p, 1, 1, 1, 1;\n}\n"
      : "=f"(d[0]), "=f"(d[1]), "=f"(d[2]), "=f"(d[3]), "=f"(d[4]), "=f"(d[5]), "=f"(d[6]), "=f"(d[7]), "=f"(d[8]), "=f"(d[9]), "=f"(d[10]), "=f"(d[11]), "=f"(d[12]), "=f"(d[13]), "=f"(d[14]), "=f"(d[15]), "=f"(d[16]), "=f"(d[17]), "=f"(d[18]), "=f"(d[19])
      : "l"(da), "l"(db));
  }
}
__device__ __forceinline__ void wgmma_n128_rs_ta0_tb1(float* d, uint32_t a0, uint32_t a1, uint32_t a2, uint32_t a3, uint64_t db, bool accumulate) {
  if (accumulate) {
    asm volatile("{\n.reg .pred p;\nsetp.ne.b32 p, 1, 0;\n"
      "wgmma.mma_async.sync.aligned.m64n128k16.f32.bf16.bf16 "
      "{%0, %1, %2, %3, %4, %5, %6, %7, %8, %9, %10, %11, %12, %13, %14, %15, %16, %17, %18, %19, %20, %21, %22, %23, %24, %25, %26, %27, %28, %29, %30, %31, %32, %33, %34, %35, %36, %37, %38, %39, %40, %41, %42, %43, %44, %45, %46, %47, %48, %49, %50, %51, %52, %53, %54, %55, %56, %57, %58, %59, %60, %61, %62, %63}, "
      "{%64, %65, %66, %67}, %68, p, 1, 1, 1;\n}\n"
      : "+f"(d[0]), "+f"(d[1]), "+f"(d[2]), "+f"(d[3]), "+f"(d[4]), "+f"(d[5]), "+f"(d[6]), "+f"(d[7]), "+f"(d[8]), "+f"(d[9]), "+f"(d[10]), "+f"(d[11]), "+f"(d[12]), "+f"(d[13]), "+f"(d[14]), "+f"(d[15]), "+f"(d[16]), "+f"(d[17]), "+f"(d[18]), "+f"(d[19]), "+f"(d[20]), "+f"(d[21]), "+f"(d[22]), "+f"(d[23]), "+f"(d[24]), "+f"(d[25]), "+f"(d[26]), "+f"(d[27]), "+f"(d[28]), "+f"(d[29]), "+f"(d[30]), "+f"(d[31]), "+f"(d[32]), "+f"(d[33]), "+f"(d[34]), "+f"(d[35]), "+f"(d[36]), "+f"(d[37]), "+f"(d[38]), "+f"(d[39]), "+f"(d[40]), "+f"(d[41]), "+f"(d[42]), "+f"(d[43]), "+f"(d[44]), "+f"(d[45]), "+f"(d[46]), "+f"(d[47]), "+f"(d[48]), "+f"(d[49]), "+f"(d[50]), "+f"(d[51]), "+f"(d[52]), "+f"(d[53]), "+f"(d[54]), "+f"(d[55]), "+f"(d[56]), "+f"(d[57]), "+f"(d[58]), "+f"(d[59]), "+f"(d[60]), "+f"(d[61]), "+f"(d[62]), "+f"(d[63])
      : "r"(a0), "r"(a1), "r"(a2), "r"(a3), "l"(db));
  } else {
    asm volatile("{\n.reg .pred p;\nsetp.ne.b32 p, 0, 0;\n"
      "wgmma.mma_async.sync.aligned.m64n128k16.f32.bf16.bf16 "
      "{%0, %1, %2, %3, %4, %5, %6, %7, %8, %9, %10, %11, %12, %13, %14, %15, %16, %17, %18, %19, %20, %21, %22, %23, %24, %25, %26, %27, %28, %29, %30, %31, %32, %33, %34, %35, %36, %37, %38, %39, %40, %41, %42, %43, %44, %45, %46, %47, %48, %49, %50, %51, %52, %53, %54, %55, %56, %57, %58, %59, %60, %61, %62, %63}, "
      "{%64, %65, %66, %67}, %68, p, 1, 1, 1;\n}\n"
      : "=f"(d[0]), "=f"(d[1]), "=f"(d[2]), "=f"(d[3]), "=f"(d[4]), "=f"(d[5]), "=f"(d[6]), "=f"(d[7]), "=f"(d[8]), "=f"(d[9]), "=f"(d[10]), "=f"(d[11]), "=f"(d[12]), "=f"(d[13]), "=f"(d[14]), "=f"(d[15]), "=f"(d[16]), "=f"(d[17]), "=f"(d[18]), "=f"(d[19]), "=f"(d[20]), "=f"(d[21]), "=f"(d[22]), "=f"(d[23]), "=f"(d[24]), "=f"(d[25]), "=f"(d[26]), "=f"(d[27]), "=f"(d[28]), "=f"(d[29]), "=f"(d[30]), "=f"(d[31]), "=f"(d[32]), "=f"(d[33]), "=f"(d[34]), "=f"(d[35]), "=f"(d[36]), "=f"(d[37]), "=f"(d[38]), "=f"(d[39]), "=f"(d[40]), "=f"(d[41]), "=f"(d[42]), "=f"(d[43]), "=f"(d[44]), "=f"(d[45]), "=f"(d[46]), "=f"(d[47]), "=f"(d[48]), "=f"(d[49]), "=f"(d[50]), "=f"(d[51]), "=f"(d[52]), "=f"(d[53]), "=f"(d[54]), "=f"(d[55]), "=f"(d[56]), "=f"(d[57]), "=f"(d[58]), "=f"(d[59]), "=f"(d[60]), "=f"(d[61]), "=f"(d[62]), "=f"(d[63])
      : "r"(a0), "r"(a1), "r"(a2), "r"(a3), "l"(db));
  }
}
__device__ __forceinline__ void wgmma_n128_ss_ta0_tb1(float* d, uint64_t da, uint64_t db, bool accumulate) {
  if (accumulate) {
    asm volatile("{\n.reg .pred p;\nsetp.ne.b32 p, 1, 0;\n"
      "wgmma.mma_async.sync.aligned.m64n128k16.f32.bf16.bf16 "
      "{%0, %1, %2, %3, %4, %5, %6, %7, %8, %9, %10, %11, %12, %13, %14, %15, %16, %17, %18, %19, %20, %21, %22, %23, %24, %25, %26, %27, %28, %29, %30, %31, %32, %33, %34, %35, %36, %37, %38, %39, %40, %41, %42, %43, %44, %45, %46, %47, %48, %49, %50, %51, %52, %53, %54, %55, %56, %57, %58, %59, %60, %61, %62, %63}, "
      "%64, %65, p, 1, 1, 0, 1;\n}\n"
      : "+f"(d[0]), "+f"(d[1]), "+f"(d[2]), "+f"(d[3]), "+f"(d[4]), "+f"(d[5]), "+f"(d[6]), "+f"(d[7]), "+f"(d[8]), "+f"(d[9]), "+f"(d[10]), "+f"(d[11]), "+f"(d[12]), "+f"(d[13]), "+f"(d[14]), "+f"(d[15]), "+f"(d[16]), "+f"(d[17]), "+f"(d[18]), "+f"(d[19]), "+f"(d[20]), "+f"(d[21]), "+f"(d[22]), "+f"(d[23]), "+f"(d[24]), "+f"(d[25]), "+f"(d[26]), "+f"(d[27]), "+f"(d[28]), "+f"(d[29]), "+f"(d[30]), "+f"(d[31]), "+f"(d[32]), "+f"(d[33]), "+f"(d[34]), "+f"(d[35]), "+f"(d[36]), "+f"(d[37]), "+f"(d[38]), "+f"(d[39]), "+f"(d[40]), "+f"(d[41]), "+f"(d[42]), "+f"(d[43]), "+f"(d[44]), "+f"(d[45]), "+f"(d[46]), "+f"(d[47]), "+f"(d[48]), "+f"(d[49]), "+f"(d[50]), "+f"(d[51]), "+f"(d[52]), "+f"(d[53]), "+f"(d[54]), "+f"(d[55]), "+f"(d[56]), "+f"(d[57]), "+f"(d[58]), "+f"(d[59]), "+f"(d[60]), "+f"(d[61]), "+f"(d[62]), "+f"(d[63])
      : "l"(da), "l"(db));
  } else {
    asm volatile("{\n.reg .pred p;\nsetp.ne.b32 p, 0, 0;\n"
      "wgmma.mma_async.sync.aligned.m64n128k16.f32.bf16.bf16 "
      "{%0, %1, %2, %3, %4, %5, %6, %7, %8, %9, %10, %11, %12, %13, %14, %15, %16, %17, %18, %19, %20, %21, %22, %23, %24, %25, %26, %27, %28, %29, %30, %31, %32, %33, %34, %35, %36, %37, %38, %39, %40, %41, %42, %43, %44, %45, %46, %47, %48, %49, %50, %51, %52, %53, %54, %55, %56, %57, %58, %59, %60, %61, %62, %63}, "
      "%64, %65, p, 1, 1, 0, 1;\n}\n"
      : "=f"(d[0]), "=f"(d[1]), "=f"(d[2]), "=f"(d[3]), "=f"(d[4]), "=f"(d[5]), "=f"(d[6]), "=f"(d[7]), "=f"(d[8]), "=f"(d[9]), "=f"(d[10]), "=f"(d[11]), "=f"(d[12]), "=f"(d[13]), "=f"(d[14]), "=f"(d[15]), "=f"(d[16]), "=f"(d[17]), "=f"(d[18]), "=f"(d[19]), "=f"(d[20]), "=f"(d[21]), "=f"(d[22]), "=f"(d[23]), "=f"(d[24]), "=f"(d[25]), "=f"(d[26]), "=f"(d[27]), "=f"(d[28]), "=f"(d[29]), "=f"(d[30]), "=f"(d[31]), "=f"(d[32]), "=f"(d[33]), "=f"(d[34]), "=f"(d[35]), "=f"(d[36]), "=f"(d[37]), "=f"(d[38]), "=f"(d[39]), "=f"(d[40]), "=f"(d[41]), "=f"(d[42]), "=f"(d[43]), "=f"(d[44]), "=f"(d[45]), "=f"(d[46]), "=f"(d[47]), "=f"(d[48]), "=f"(d[49]), "=f"(d[50]), "=f"(d[51]), "=f"(d[52]), "=f"(d[53]), "=f"(d[54]), "=f"(d[55]), "=f"(d[56]), "=f"(d[57]), "=f"(d[58]), "=f"(d[59]), "=f"(d[60]), "=f"(d[61]), "=f"(d[62]), "=f"(d[63])
      : "l"(da), "l"(db));
  }
}
__device__ __forceinline__ void wgmma_n256_rs_ta0_tb1(float* d, uint32_t a0, uint32_t a1, uint32_t a2, uint32_t a3, uint64_t db, bool accumulate) {
  if (accumulate) {
    asm volatile("{\n.reg .pred p;\nsetp.ne.b32 p, 1, 0;\n"
      "wgmma.mma_async.sync.aligned.m64n256k16.f32.bf16.bf16 "
      "{%0, %1, %2, %3, %4, %5, %6, %7, %8, %9, %10, %11, %12, %13, %14, %15, %16, %17, %18, %19, %20, %21, %22, %23, %24, %25, %26, %27, %28, %29, %30, %31, %32, %33, %34, %35, %36, %37, %38, %39, %40, %41, %42, %43, %44, %45, %46, %47, %48, %49, %50, %51, %52, %53, %54, %55, %56, %57, %58, %59, %60, %61, %62, %63, %64, %65, %66, %67, %68, %69, %70, %71, %72, %73, %74, %75, %76, %77, %78, %79, %80, %81, %82, %83, %84, %85, %86, %87, %88, %89, %90, %91, %92, %93, %94, %95, %96, %97, %98, %99, %100, %101, %102, %103, %104, %105, %106, %107, %108, %109, %110, %111, %112, %113, %114, %115, %116, %117, %118, %119, %120, %121, %122, %123, %124, %125, %126, %127}, "
      "{%128, %129, %130, %131}, %132, p, 1, 1, 1;\n}\n"
      : "+f"(d[0]), "+f"(d[1]), "+f"(d[2]), "+f"(d[3]), "+f"(d[4]), "+f"(d[5]), "+f"(d[6]), "+f"(d[7]), "+f"(d[8]), "+f"(d[9]), "+f"(d[10]), "+f"(d[11]), "+f"(d[12]), "+f"(d[13]), "+f"(d[14]), "+f"(d[15]), "+f"(d[16]), "+f"(d[17]), "+f"(d[18]), "+f"(d[19]), "+f"(d[20]), "+f"(d[21]), "+f"(d[22]), "+f"(d[23]), "+f"(d[24]), "+f"(d[25]), "+f"(d[26]), "+f"(d[27]), "+f"(d[28]), "+f"(d[29]), "+f"(d[30]), "+f"(d[31]), "+f"(d[32]), "+f"(d[33]), "+f"(d[34]), "+f"(d[35]), "+f"(d[36]), "+f"(d[37]), "+f"(d[38]), "+f"(d[39]), "+f"(d[40]), "+f"(d[41]), "+f"(d[42]), "+f"(d[43]), "+f"(d[44]), "+f"(d[45]), "+f"(d[46]), "+f"(d[47]), "+f"(d[48]), "+f"(d[49]), "+f"(d[50]), "+f"(d[51]), "+f"(d[52]), "+f"(d[53]), "+f"(d[54]), "+f"(d[55]), "+f"(d[56]), "+f"(d[57]), "+f"(d[58]), "+f"(d[59]), "+f"(d[60]), "+f"(d[61]), "+f"(d[62]), "+f"(d[63]), "+f"(d[64]), "+f"(d[65]), "+f"(d[66]), "+f"(d[67]), "+f"(d[68]), "+f"(d[69]), "+f"(d[70]), "+f"(d[71]), "+f"(d[72]), "+f"(d[73]), "+f"(d[74]), "+f"(d[75]), "+f"(d[76]), "+f"(d[77]), "+f"(d[78]), "+f"(d[79]), "+f"(d[80]), "+f"(d[81]), "+f"(d[82]), "+f"(d[83]), "+f"(d[84]), "+f"(d[85]), "+f"(d[86]), "+f"(d[87]), "+f"(d[88]), "+f"(d[89]), "+f"(d[90]), "+f"(d[91]), "+f"(d[92]), "+f"(d[93]), "+f"(d[94]), "+f"(d[95]), "+f"(d[96]), "+f"(d[97]), "+f"(d[98]), "+f"(d[99]), "+f"(d[100]), "+f"(d[101]), "+f"(d[102]), "+f"(d[103]), "+f"(d[104]), "+f"(d[105]), "+f"(d[106]), "+f"(d[107]), "+f"(d[108]), "+f"(d[109]), "+f"(d[110]), "+f"(d[111]), "+f"(d[112]), "+f"(d[113]), "+f"(d[114]), "+f"(d[115]), "+f"(d[116]), "+f"(d[117]), "+f"(d[118]), "+f"(d[119]), "+f"(d[120]), "+f"(d[121]), "+f"(d[122]), "+f"(d[123]), "+f"(d[124]), "+f"(d[125]), "+f"(d[126]), "+f"(d[127])
      : "r"(a0), "r"(a1), "r"(a2), "r"(a3), "l"(db));
  } else {
    asm volatile("{\n.reg .pred p;\nsetp.ne.b32 p, 0, 0;\n"
      "wgmma.mma_async.sync.aligned.m64n256k16.f32.bf16.bf16 "
      "{%0, %1, %2, %3, %4, %5, %6, %7, %8, %9, %10, %11, %12, %13, %14, %15, %16, %17, %18, %19, %20, %21, %22, %23, %24, %25, %26, %27, %28, %29, %30, %31, %32, %33, %34, %35, %36, %37, %38, %39, %40, %41, %42, %43, %44, %45, %46, %47, %48, %49, %50, %51, %52, %53, %54, %55, %56, %57, %58, %59, %60, %61, %62, %63, %64, %65, %66, %67, %68, %69, %70, %71, %72, %73, %74, %75, %76, %77, %78, %79, %80, %81, %82, %83, %84, %85, %86, %87, %88, %89, %90, %91, %92, %93, %94, %95, %96, %97, %98, %99, %100, %101, %102, %103, %104, %105, %106, %107, %108, %109, %110, %111, %112, %113, %114, %115, %116, %117, %118, %119, %120, %121, %122, %123, %124, %125, %126, %127}, "
      "{%128, %129, %130, %131}, %132, p, 1, 1, 1;\n}\n"
      : "=f"(d[0]), "=f"(d[1]), "=f"(d[2]), "=f"(d[3]), "=f"(d[4]), "=f"(d[5]), "=f"(d[6]), "=f"(d[7]), "=f"(d[8]), "=f"(d[9]), "=f"(d[10]), "=f"(d[11]), "=f"(d[12]), "=f"(d[13]), "=f"(d[14]), "=f"(d[15]), "=f"(d[16]), "=f"(d[17]), "=f"(d[18]), "=f"(d[19]), "=f"(d[20]), "=f"(d[21]), "=f"(d[22]), "=f"(d[23]), "=f"(d[24]), "=f"(d[25]), "=f"(d[26]), "=f"(d[27]), "=f"(d[28]), "=f"(d[29]), "=f"(d[30]), "=f"(d[31]), "=f"(d[32]), "=f"(d[33]), "=f"(d[34]), "=f"(d[35]), "=f"(d[36]), "=f"(d[37]), "=f"(d[38]), "=f"(d[39]), "=f"(d[40]), "=f"(d[41]), "=f"(d[42]), "=f"(d[43]), "=f"(d[44]), "=f"(d[45]), "=f"(d[46]), "=f"(d[47]), "=f"(d[48]), "=f"(d[49]), "=f"(d[50]), "=f"(d[51]), "=f"(d[52]), "=f"(d[53]), "=f"(d[54]), "=f"(d[55]), "=f"(d[56]), "=f"(d[57]), "=f"(d[58]), "=f"(d[59]), "=f"(d[60]), "=f"(d[61]), "=f"(d[62]), "=f"(d[63]), "=f"(d[64]), "=f"(d[65]), "=f"(d[66]), "=f"(d[67]), "=f"(d[68]), "=f"(d[69]), "=f"(d[70]), "=f"(d[71]), "=f"(d[72]), "=f"(d[73]), "=f"(d[74]), "=f"(d[75]), "=f"(d[76]), "=f"(d[77]), "=f"(d[78]), "=f"(d[79]), "=f"(d[80]), "=f"(d[81]), "=f"(d[82]), "=f"(d[83]), "=f"(d[84]), "=f"(d[85]), "=f"(d[86]), "=f"(d[87]), "=f"(d[88]), "=f"(d[89]), "=f"(d[90]), "=f"(d[91]), "=f"(d[92]), "=f"(d[93]), "=f"(d[94]), "=f"(d[95]), "=f"(d[96]), "=f"(d[97]), "=f"(d[98]), "=f"(d[99]), "=f"(d[100]), "=f"(d[101]), "=f"(d[102]), "=f"(d[103]), "=f"(d[104]), "=f"(d[105]), "=f"(d[106]), "=f"(d[107]), "=f"(d[108]), "=f"(d[109]), "=f"(d[110]), "=f"(d[111]), "=f"(d[112]), "=f"(d[113]), "=f"(d[114]), "=f"(d[115]), "=f"(d[116]), "=f"(d[117]), "=f"(d[118]), "=f"(d[119]), "=f"(d[120]), "=f"(d[121]), "=f"(d[122]), "=f"(d[123]), "=f"(d[124]), "=f"(d[125]), "=f"(d[126]), "=f"(d[127])
      : "r"(a0), "r"(a1), "r"(a2), "r"(a3), "l"(db));
  }
}
__device__ __forceinline__ void wgmma_n256_ss_ta0_tb1(float* d, uint64_t da, uint64_t db, bool accumulate) {
  if (accumulate) {
    asm volatile("{\n.reg .pred p;\nsetp.ne.b32 p, 1, 0;\n"
      "wgmma.mma_async.sync.aligned.m64n256k16.f32.bf16.bf16 "
      "{%0, %1, %2, %3, %4, %5, %6, %7, %8, %9, %10, %11, %12, %13, %14, %15, %16, %17, %18, %19, %20, %21, %22, %23, %24, %25, %26, %27, %28, %29, %30, %31, %32, %33, %34, %35, %36, %37, %38, %39, %40, %41, %42, %43, %44, %45, %46, %47, %48, %49, %50, %51, %52, %53, %54, %55, %56, %57, %58, %59, %60, %61, %62, %63, %64, %65, %66, %67, %68, %69, %70, %71, %72, %73, %74, %75, %76, %77, %78, %79, %80, %81, %82, %83, %84, %85, %86, %87, %88, %89, %90, %91, %92, %93, %94, %95, %96, %97, %98, %99, %100, %101, %102, %103, %104, %105, %106, %107, %108, %109, %110, %111, %112, %113, %114, %115, %116, %117, %118, %119, %120, %121, %122, %123, %124, %125, %126, %127}, "
      "%128, %129, p, 1, 1, 0, 1;\n}\n"
      : "+f"(d[0]), "+f"(d[1]), "+f"(d[2]), "+f"(d[3]), "+f"(d[4]), "+f"(d[5]), "+f"(d[6]), "+f"(d[7]), "+f"(d[8]), "+f"(d[9]), "+f"(d[10]), "+f"(d[11]), "+f"(d[12]), "+f"(d[13]), "+f"(d[14]), "+f"(d[15]), "+f"(d[16]), "+f"(d[17]), "+f"(d[18]), "+f"(d[19]), "+f"(d[20]), "+f"(d[21]), "+f"(d[22]), "+f"(d[23]), "+f"(d[24]), "+f"(d[25]), "+f"(d[26]), "+f"(d[27]), "+f"(d[28]), "+f"(d[29]), "+f"(d[30]), "+f"(d[31]), "+f"(d[32]), "+f"(d[33]), "+f"(d[34]), "+f"(d[35]), "+f"(d[36]), "+f"(d[37]), "+f"(d[38]), "+f"(d[39]), "+f"(d[40]), "+f"(d[41]), "+f"(d[42]), "+f"(d[43]), "+f"(d[44]), "+f"(d[45]), "+f"(d[46]), "+f"(d[47]), "+f"(d[48]), "+f"(d[49]), "+f"(d[50]), "+f"(d[51]), "+f"(d[52]), "+f"(d[53]), "+f"(d[54]), "+f"(d[55]), "+f"(d[56]), "+f"(d[57]), "+f"(d[58]), "+f"(d[59]), "+f"(d[60]), "+f"(d[61]), "+f"(d[62]), "+f"(d[63]), "+f"(d[64]), "+f"(d[65]), "+f"(d[66]), "+f"(d[67]), "+f"(d[68]), "+f"(d[69]), "+f"(d[70]), "+f"(d[71]), "+f"(d[72]), "+f"(d[73]), "+f"(d[74]), "+f"(d[75]), "+f"(d[76]), "+f"(d[77]), "+f"(d[78]), "+f"(d[79]), "+f"(d[80]), "+f"(d[81]), "+f"(d[82]), "+f"(d[83]), "+f"(d[84]), "+f"(d[85]), "+f"(d[86]), "+f"(d[87]), "+f"(d[88]), "+f"(d[89]), "+f"(d[90]), "+f"(d[91]), "+f"(d[92]), "+f"(d[93]), "+f"(d[94]), "+f"(d[95]), "+f"(d[96]), "+f"(d[97]), "+f"(d[98]), "+f"(d[99]), "+f"(d[100]), "+f"(d[101]), "+f"(d[102]), "+f"(d[103]), "+f"(d[104]), "+f"(d[105]), "+f"(d[106]), "+f"(d[107]), "+f"(d[108]), "+f"(d[109]), "+f"(d[110]), "+f"(d[111]), "+f"(d[112]), "+f"(d[113]), "+f"(d[114]), "+f"(d[115]), "+f"(d[116]), "+f"(d[117]), "+f"(d[118]), "+f"(d[119]), "+f"(d[120]), "+f"(d[121]), "+f"(d[122]), "+f"(d[123]), "+f"(d[124]), "+f"(d[125]), "+f"(d[126]), "+f"(d[127])
      : "l"(da), "l"(db));
  } else {
    asm volatile("{\n.reg .pred p;\nsetp.ne.b32 p, 0, 0;\n"
      "wgmma.mma_async.sync.aligned.m64n256k16.f32.bf16.bf16 "
      "{%0, %1, %2, %3, %4, %5, %6, %7, %8, %9, %10, %11, %12, %13, %14, %15, %16, %17, %18, %19, %20, %21, %22, %23, %24, %25, %26, %27, %28, %29, %30, %31, %32, %33, %34, %35, %36, %37, %38, %39, %40, %41, %42, %43, %44, %45, %46, %47, %48, %49, %50, %51, %52, %53, %54, %55, %56, %57, %58, %59, %60, %61, %62, %63, %64, %65, %66, %67, %68, %69, %70, %71, %72, %73, %74, %75, %76, %77, %78, %79, %80, %81, %82, %83, %84, %85, %86, %87, %88, %89, %90, %91, %92, %93, %94, %95, %96, %97, %98, %99, %100, %101, %102, %103, %104, %105, %106, %107, %108, %109, %110, %111, %112, %113, %114, %115, %116, %117, %118, %119, %120, %121, %122, %123, %124, %125, %126, %127}, "
      "%128, %129, p, 1, 1, 0, 1;\n}\n"
      : "=f"(d[0]), "=f"(d[1]), "=f"(d[2]), "=f"(d[3]), "=f"(d[4]), "=f"(d[5]), "=f"(d[6]), "=f"(d[7]), "=f"(d[8]), "=f"(d[9]), "=f"(d[10]), "=f"(d[11]), "=f"(d[12]), "=f"(d[13]), "=f"(d[14]), "=f"(d[15]), "=f"(d[16]), "=f"(d[17]), "=f"(d[18]), "=f"(d[19]), "=f"(d[20]), "=f"(d[21]), "=f"(d[22]), "=f"(d[23]), "=f"(d[24]), "=f"(d[25]), "=f"(d[26]), "=f"(d[27]), "=f"(d[28]), "=f"(d[29]), "=f"(d[30]), "=f"(d[31]), "=f"(d[32]), "=f"(d[33]), "=f"(d[34]), "=f"(d[35]), "=f"(d[36]), "=f"(d[37]), "=f"(d[38]), "=f"(d[39]), "=f"(d[40]), "=f"(d[41]), "=f"(d[42]), "=f"(d[43]), "=f"(d[44]), "=f"(d[45]), "=f"(d[46]), "=f"(d[47]), "=f"(d[48]), "=f"(d[49]), "=f"(d[50]), "=f"(d[51]), "=f"(d[52]), "=f"(d[53]), "=f"(d[54]), "=f"(d[55]), "=f"(d[56]), "=f"(d[57]), "=f"(d[58]), "=f"(d[59]), "=f"(d[60]), "=f"(d[61]), "=f"(d[62]), "=f"(d[63]), "=f"(d[64]), "=f"(d[65]), "=f"(d[66]), "=f"(d[67]), "=f"(d[68]), "=f"(d[69]), "=f"(d[70]), "=f"(d[71]), "=f"(d[72]), "=f"(d[73]), "=f"(d[74]), "=f"(d[75]), "=f"(d[76]), "=f"(d[77]), "=f"(d[78]), "=f"(d[79]), "=f"(d[80]), "=f"(d[81]), "=f"(d[82]), "=f"(d[83]), "=f"(d[84]), "=f"(d[85]), "=f"(d[86]), "=f"(d[87]), "=f"(d[88]), "=f"(d[89]), "=f"(d[90]), "=f"(d[91]), "=f"(d[92]), "=f"(d[93]), "=f"(d[94]), "=f"(d[95]), "=f"(d[96]), "=f"(d[97]), "=f"(d[98]), "=f"(d[99]), "=f"(d[100]), "=f"(d[101]), "=f"(d[102]), "=f"(d[103]), "=f"(d[104]), "=f"(d[105]), "=f"(d[106]), "=f"(d[107]), "=f"(d[108]), "=f"(d[109]), "=f"(d[110]), "=f"(d[111]), "=f"(d[112]), "=f"(d[113]), "=f"(d[114]), "=f"(d[115]), "=f"(d[116]), "=f"(d[117]), "=f"(d[118]), "=f"(d[119]), "=f"(d[120]), "=f"(d[121]), "=f"(d[122]), "=f"(d[123]), "=f"(d[124]), "=f"(d[125]), "=f"(d[126]), "=f"(d[127])
      : "l"(da), "l"(db));
  }
}
__device__ __forceinline__ void wgmma_n256_ssp_ta0_tb1(float* d, uint64_t da, uint64_t db, int accumulate) {
    asm volatile("{\n.reg .pred p;\nsetp.ne.b32 p, %130, 0;\n"
      "wgmma.mma_async.sync.aligned.m64n256k16.f32.bf16.bf16 "
      "{%0, %1, %2, %3, %4, %5, %6, %7, %8, %9, %10, %11, %12, %13, %14, %15, %16, %17, %18, %19, %20, %21, %22, %23, %24, %25, %26, %27, %28, %29, %30, %31, %32, %33, %34, %35, %36, %37, %38, %39, %40, %41, %42, %43, %44, %45, %46, %47, %48, %49, %50, %51, %52, %53, %54, %55, %56, %57, %58, %59, %60, %61, %62, %63, %64, %65, %66, %67, %68, %69, %70, %71, %72, %73, %74, %75, %76, %77, %78, %79, %80, %81, %82, %83, %84, %85, %86, %87, %88, %89, %90, %91, %92, %93, %94, %95, %96, %97, %98, %99, %100, %101, %102, %103, %104, %105, %106, %107, %108, %109, %110, %111, %112, %113, %114, %115, %116, %117, %118, %119, %120, %121, %122, %123, %124, %125, %126, %127}, "
      "%128, %129, p, 1, 1, 0, 1;\n}\n"
      : "+f"(d[0]), "+f"(d[1]), "+f"(d[2]), "+f"(d[3]), "+f"(d[4]), "+f"(d[5]), "+f"(d[6]), "+f"(d[7]), "+f"(d[8]), "+f"(d[9]), "+f"(d[10]), "+f"(d[11]), "+f"(d[12]), "+f"(d[13]), "+f"(d[14]), "+f"(d[15]), "+f"(d[16]), "+f"(d[17]), "+f"(d[18]), "+f"(d[19]), "+f"(d[20]), "+f"(d[21]), "+f"(d[22]), "+f"(d[23]), "+f"(d[24]), "+f"(d[25]), "+f"(d[26]), "+f"(d[27]), "+f"(d[28]), "+f"(d[29]), "+f"(d[30]), "+f"(d[31]), "+f"(d[32]), "+f"(d[33]), "+f"(d[34]), "+f"(d[35]), "+f"(d[36]), "+f"(d[37]), "+f"(d[38]), "+f"(d[39]), "+f"(d[40]), "+f"(d[41]), "+f"(d[42]), "+f"(d[43]), "+f"(d[44]), "+f"(d[45]), "+f"(d[46]), "+f"(d[47]), "+f"(d[48]), "+f"(d[49]), "+f"(d[50]), "+f"(d[51]), "+f"(d[52]), "+f"(d[53]), "+f"(d[54]), "+f"(d[55]), "+f"(d[56]), "+f"(d[57]), "+f"(d[58]), "+f"(d[59]), "+f"(d[60]), "+f"(d[61]), "+f"(d[62]), "+f"(d[63]), "+f"(d[64]), "+f"(d[65]), "+f"(d[66]), "+f"(d[67]), "+f"(d[68]), "+f"(d[69]), "+f"(d[70]), "+f"(d[71]), "+f"(d[72]), "+f"(d[73]), "+f"(d[74]), "+f"(d[75]), "+f"(d[76]), "+f"(d[77]), "+f"(d[78]), "+f"(d[79]), "+f"(d[80]), "+f"(d[81]), "+f"(d[82]), "+f"(d[83]), "+f"(d[84]), "+f"(d[85]), "+f"(d[86]), "+f"(d[87]), "+f"(d[88]), "+f"(d[89]), "+f"(d[90]), "+f"(d[91]), "+f"(d[92]), "+f"(d[93]), "+f"(d[94]), "+f"(d[95]), "+f"(d[96]), "+f"(d[97]), "+f"(d[98]), "+f"(d[99]), "+f"(d[100]), "+f"(d[101]), "+f"(d[102]), "+f"(d[103]), "+f"(d[104]), "+f"(d[105]), "+f"(d[106]), "+f"(d[107]), "+f"(d[108]), "+f"(d[109]), "+f"(d[110]), "+f"(d[111]), "+f"(d[112]), "+f"(d[113]), "+f"(d[114]), "+f"(d[115]), "+f"(d[116]), "+f"(d[117]), "+f"(d[118]), "+f"(d[119]), "+f"(d[120]), "+f"(d[121]), "+f"(d[122]), "+f"(d[123]), "+f"(d[124]), "+f"(d[125]), "+f"(d[126]), "+f"(d[127])
      : "l"(da), "l"(db), "r"(accumulate));
}

template <int N> __device__ __forceinline__ void quad_sum(float* m) {
#pragma unroll
  for (int o = 1; o <= 2; o <<= 1) {
    float t[N];
#pragma unroll
    for (int i = 0; i < N; i++) t[i] = __shfl_xor_sync(~0u, m[i], o);
#pragma unroll
    for (int i = 0; i < N; i++) m[i] += t[i];
  }
}
__device__ __forceinline__ bool softmax_unsafe(const uint32_t* t, float l0, float l1) {
  const float m0 = fmaxf(bf_lo(t[0]) + bf_hi(t[0]), bf_lo(t[2]) + bf_hi(t[2])), m1 = fmaxf(bf_lo(t[1]) + bf_hi(t[1]), bf_lo(t[3]) + bf_hi(t[3]));
  return __any_sync(~0u, !(m0 * l0 < 2500.f) | !(m1 * l1 < 2500.f));
}
__device__ __forceinline__ void softmax_shift(float* p, float c0, float c1) {
#pragma unroll 1
  for (int it = 0; it < 8; it++) {
    float mx = p[0], mn = p[0];
#pragma unroll
    for (int j = 1; j < 8; j++) { mx = fmaxf(mx, p[(j >> 1) * 4 + (j & 1)]); mn = fminf(mn, p[(j >> 1) * 4 + (j & 1)]); }
#pragma unroll
    for (int o = 1; o <= 2; o <<= 1) { mx = fmaxf(mx, __shfl_xor_sync(~0u, mx, o)); mn = fminf(mn, __shfl_xor_sync(~0u, mn, o)); }
    const float half = fminf(0.5f * (mx - mn), 50.f * rcp(it & 1 ? c1 : c0));
    float r[8];
#pragma unroll
    for (int j = 0; j < 8; j++) {
      const float v = p[(j >> 1) * 4 + (j & 1)];
      r[j] = fmaxf(v - mx + half, 0.f) + fminf(v - mn - half, 0.f) + (v - v);
    }
#pragma unroll
    for (int k = 0; k < 7; k++)
#pragma unroll
      for (int j = 0; j < 8; j++) p[(k >> 1) * 16 + (k & 1) * 2 + (j >> 1) * 4 + (j & 1)] = p[((k + 1) >> 1) * 16 + ((k + 1) & 1) * 2 + (j >> 1) * 4 + (j & 1)];
#pragma unroll
    for (int j = 0; j < 8; j++) p[50 + (j >> 1) * 4 + (j & 1)] = r[j];
  }
}
template <int J0 = 0, int J1 = 8> __device__ __forceinline__ void k_exp(const float* p, float c0, float c1, float* e, float* s) {
#pragma unroll
  for (int j = J0; j < J1; j++) {
    e[2 * j] = ex2(p[2 * j] * (j & 1 ? c1 : c0));
    e[2 * j + 1] = ex2(p[2 * j + 1] * (j & 1 ? c1 : c0));
    e[16 + j] = rcp(e[2 * j] * e[2 * j + 1]);
    const float t = e[2 * j] + e[2 * j + 1];
    s[j & 1] = j < 2 ? t : s[j & 1] + t;
    s[2 + (j & 1)] = j < 2 ? e[16 + j] * t : fmaf(e[16 + j], t, s[2 + (j & 1)]);
  }
}
template <int J0 = 0, int J1 = 8> __device__ __forceinline__ void q_exp(const float* p, float c0, float c1, uint32_t* f) {
#pragma unroll
  for (int j = J0; j < J1; j++) {
    const float e0 = ex2(p[2 * j] * (j & 1 ? c1 : c0)), e1 = ex2(p[2 * j + 1] * (j & 1 ? c1 : c0)), r = rcp(e0 * e1);
    f[j] = pack2(e0, e1);
    f[8 + j] = bmul2(f[j], pack2(r, r));
  }
}

#define FMA8(A, U, X)                                                                                        \
  A[0] = fmaf(bf_lo(U.x), X, A[0]); A[1] = fmaf(bf_hi(U.x), X, A[1]); A[2] = fmaf(bf_lo(U.y), X, A[2]); A[3] = fmaf(bf_hi(U.y), X, A[3]); \
  A[4] = fmaf(bf_lo(U.z), X, A[4]); A[5] = fmaf(bf_hi(U.z), X, A[5]); A[6] = fmaf(bf_lo(U.w), X, A[6]); A[7] = fmaf(bf_hi(U.w), X, A[7])

__device__ __forceinline__ uint32_t routed_row(const __nv_bfloat16* x, uint32_t tag, int lane, uint4* xr) {
  uint32_t best = 0, sv = 0;
#pragma unroll 1
  for (int it = 0; it < SPIN_MAX; it++) {
    const uint4 h = ld_rlx128(g_ycnt + 32);
    best = h.x;
    if (__all_sync(~0u, (int)(h.z - tag * NCTA) >= 0)) break;
    __nanosleep(AM_NS);
  }
#pragma unroll 1
  for (int it = 0; it < SPIN_MAX; it++) {
    const int sel = 2047 - (best & 0x7ff);
#pragma unroll
    for (int i = 0; i < 4; i++) xr[i] = ldg_nc(x + (size_t)sel * DM + i * 256 + lane * 8);
    const unsigned long long st = ld_rlx64(g_stat + sel);
    const uint4 b0 = ld_rlx128(g_best + lane * 2), b1 = ld_rlx128(g_best + 64 + lane * 2);
    const uint32_t m = __reduce_max_sync(~0u, max(max(b0.x, b0.z), max(b1.x, b1.z)));
    sv = (uint32_t)st;
    if (__all_sync(~0u, b0.y == tag && b0.w == tag && b1.y == tag && b1.w == tag && m == best && (uint32_t)(st >> 32) == tag)) break;
    best = m;
  }
  const uint32_t m2 = (sv & 0xffff0000u) | (sv >> 16);
  const float rs = rcp(bf_lo(sv));
#pragma unroll
  for (int i = 0; i < 4; i++) {
    const uint32_t d0 = bsub2(xr[i].x, m2), d1 = bsub2(xr[i].y, m2), d2 = bsub2(xr[i].z, m2), d3 = bsub2(xr[i].w, m2);
    xr[i] = make_uint4(pack2(bf_lo(d0) * rs, bf_hi(d0) * rs), pack2(bf_lo(d1) * rs, bf_hi(d1) * rs), pack2(bf_lo(d2) * rs, bf_hi(d2) * rs),
                       pack2(bf_lo(d3) * rs, bf_hi(d3) * rs));
  }
  return best;
}

struct Params {
  const __nv_bfloat16 *x, *wqkv, *wo, *w_r, *w_gate, *w_up, *w_down;
};

template <bool BY_SMID> __global__ void __launch_bounds__(384, 1)
fused_kernel(const __grid_constant__ CUtensorMap mX, const __grid_constant__ CUtensorMap mWkv, const __grid_constant__ CUtensorMap mWq,
             const __grid_constant__ CUtensorMap mWo, const __grid_constant__ CUtensorMap mPhi, const __grid_constant__ CUtensorMap mWp,
             const __grid_constant__ CUtensorMap mOut, const __grid_constant__ CUtensorMap mWc,
             const __grid_constant__ CUtensorMap mG, const __grid_constant__ CUtensorMap mU, const __grid_constant__ CUtensorMap mD,
             const __grid_constant__ CUtensorMap mXs, const __grid_constant__ CUtensorMap mG2, const __grid_constant__ CUtensorMap mU2, const Params P) {
  constexpr uint32_t sb = SB, bar = SB + SM_BAR;
  int bid = blockIdx.x;
  if (BY_SMID) {
    uint32_t sm;
    asm volatile("mov.u32 %0, %%smid;" : "=r"(sm));
    const uint32_t tq = (sm - 64) >> 1, q7 = (tq * 37) >> 8;
    const uint32_t gpc = sm < 64 ? (sm >> 1) & 7 : 1 + tq - 7 * q7, idx = (sm < 64 ? sm >> 4 : 4 + q7) * 2 + (sm & 1);
    bid = sm < 120 ? ((PTAB >> (4 * gpc)) & 7) * 16 + idx : sm < 124 ? sm + 8 : sm - 116;
  }
  const int hg = ((bid >> 2) & 3) + 4 * ((bid >> 4) & 1), mb = (bid & 3) + 4 * ((bid >> 5) & 3);
  extern __shared__ __align__(1024) uint8_t smem[];
  if (smem_u32(smem) != SB) __trap();
  const int warp = __shfl_sync(~0u, threadIdx.x >> 5, 0);

  if (bid >= NCTA) {
    constexpr uint32_t XV = SM_WPHI, ONES = SM_ZT, BF = bar, BE = bar + 48, BX = bar + 96;
    constexpr int NJ = (DM - GROWS) / 64;
    const int lane = lane_id(), sp = bid - NCTA;
    const uint32_t tag = ld_rlx(g_epoch + bid * 32 + lane) + 1;
    if (warp == 8 && elect_one()) {
#pragma unroll 1
      for (int i = 0; i < 13; i++) mbar_init(bar + 8 * i, i >= 6 && i < 12 ? 8 : 1);
    }
    if (warp == 9) { sts64u(sb + ONES + lane * 8, 0x3f803f80u, 0x3f803f80u); fence_async_smem(); }
    __syncthreads();
    if (warp == 8) {
      if (elect_one()) {
        uint32_t s = 0, ph = 1;
#pragma unroll 1
        for (int job = 0; job < 8; job++) {
          const CUtensorMap* m = job == 0 ? &mWq : sp & 2 ? &mU2 : &mG2;
          const int g0 = job ? (sp & 1) * 28 + job * 4 - 4 : sp * 4;
#pragma unroll 1
          for (int row = job ? GROWS : 0; row < DM; row += 64) {
            mbar_wait(BE + 8 * s, ph);
            mbar_expect_tx(BF + 8 * s, Q_STAGE);
            tma4d(sb + s * Q_STAGE, m, 0, row, g0, 0, BF + 8 * s);
            tma4d(sb + s * Q_STAGE + 16384, m, 0, row, g0 + 2, 0, BF + 8 * s);
            if (++s == 6) { s = 0; ph ^= 1; }
          }
        }
      }
    } else if (warp == 9) {
      uint4 xr[4];
      routed_row(P.x, tag, lane, xr);
#pragma unroll
      for (int i = 0; i < 4; i++) sts128u(sb + XV + i * 512 + lane * 16, xr[i].x, xr[i].y, xr[i].z, xr[i].w);
      fence_async_smem();
      __syncwarp();
      if (lane == 0) mbar_arrive(BX);
    } else if (warp < 8) {
      uint32_t s = 0, ph = 0;
#pragma unroll 1
      for (int job = 0; job < 8; job++) {
        float d[8] = {0.f, 0.f, 0.f, 0.f, 0.f, 0.f, 0.f, 0.f};
        if (job == 1) mbar_wait(BX, 0);
#pragma unroll 1
        for (int i = 0; i < (job ? NJ : 16); i++) {
          mbar_wait(BF + 8 * s, ph);
          wg_fence();
#pragma unroll
          for (int k = 0; k < 8; k++)
            wgmma_n8_ss_ta1_tb0(d + 4 * (k >> 2), mkdesc(sb + k * 2048, 16, 1024, 1, s * (Q_STAGE / 16) + (warp >> 2) * 1024),
                                mkdesc(sb, 16, 128, 0, job ? (XV + GROWS * 2) / 16 + i * 8 + (k & 3) * 2 : ONES / 16), 1);
          wg_commit();
          wg_wait<0>();
          if (lane == 0) mbar_arrive(BE + 8 * s);
          if (++s == 6) { s = 0; ph ^= 1; }
        }
        reg_fence<8>(d);
        float* dst = (job ? g_gp + sp * 1792 + job * 256 - 256 : g_cs + sp * 256) + (warp >> 2) * 128 + (warp & 3) * 16 + (lane >> 2);
        if ((lane & 3) == 0) {
#pragma unroll
          for (int i = 0; i < 4; i++) st_rlx(dst + (i >> 1) * 64 + (i & 1) * 8, mark(__float_as_uint(d[2 * i]), tag & 1));
        }
        __syncwarp();
      }
      if (warp == 0) g_epoch[bid * 32 + lane] = tag;
    }
    return;
  }
#define Q_SLAB(J) ((J) < 8 ? ((J) + 8 - 2 * (hg & 4)) & 15 : 2 * (hg & 4) + 2 * ((J) & 3) + ((J) >> 2 & 1))
#define Q_AOFF(J) ((J) == 8 + (hg & 3) ? SM_X0 : (J) == 12 + (hg & 3) ? SM_X1 : ((J) & 3) * Q_STAGE)
#define Q_LOAD(J)                                                                                            \
  do {                                                                                                       \
    const uint32_t fb_ = bar + B_FULLQ + 8 * ((J) & 3);                                                      \
    const int k_ = Q_SLAB(J) * 64;                                                                           \
    mbar_expect_tx(fb_, Q_STAGE);                                                                            \
    mbar_arrive2(fb_);                                                                                       \
    tma2d(sb + Q_AOFF(J), &mX, k_, mb * 128, fb_);                                                           \
    tma4d(sb + ((J) & 3) * Q_STAGE + 16384, &mWq, 0, k_, hg * 2, 0, fb_);                                    \
  } while (0)
  if (warp >= 8) {
    asm volatile("setmaxnreg.dec.sync.aligned.u32 %0;" ::"n"(REG_H));
    const int lane = lane_id();
    const int f = (warp - 9) & 3;
    if (f == 3) {
      if (elect_one()) {
        PROF(0); PROFT(32);
#pragma unroll
        for (int s = 0; s < 3; s++) mbar_init(bar + B_FULLKV + 8 * s, 1);
      }
      __syncwarp();
      asm volatile("bar.arrive 14, 288;" ::: "memory");
      if (elect_one()) {
#pragma unroll
        for (int s = 0; s < 2; s++) {
          mbar_expect_tx(bar + B_FULLKV + 8 * s, KV_STAGE);
          tma2d(sb + s * KV_STAGE, &mX, (s + 1) * 64, mb * 128, bar + B_FULLKV + 8 * s);
          tma4d(sb + s * KV_STAGE + 16384, &mWkv, 0, (s + 1) * 64, hg * 2, 1, bar + B_FULLKV + 8 * s);
        }
      }
      __syncwarp();
    }
    const uint32_t ep = ld_rlx(g_epoch + bid * 32 + lane);
    if (f < 2) {
#pragma unroll
      for (int i = 0; i < 2; i++) {
        const uint4 u = __ldg((const uint4*)P.w_r + (f * 2 + i) * 32 + lane);
        sts128u(sb + SM_XSEL + (f * 2 + i) * 512 + lane * 16, u.x, u.y, u.z, u.w);
      }
    }
    bar_sync(13, 384);
    const uint32_t tag = ep + 1, par = tag & 1;
    const bool ffn = bid < NFFN;
    const int fb = bid, cu = bid >> 1, ch = bid & 1;
#define CS_STORE(SEC, C)                                                                                     \
  _Pragma("unroll") for (int r = 0; r < 3; r++) {                                                            \
    const uint32_t h0 = pack2(C.x, C.y), h1 = pack2(C.z, C.w);                                               \
    sts64u(sb + SM_CST + (SEC) * 1024 + (lane >> 4) * 512 + (lane & 1) * 8 + r * 128 + ((((lane & 15) >> 1) ^ (r + (lane >> 4) * 4)) << 4), h0, h1); \
    C.x -= bf_lo(h0); C.y -= bf_hi(h0); C.z -= bf_lo(h1); C.w -= bf_hi(h1);                                  \
  }
#define BAD4(U) ((U.x ^ par) | (U.y ^ par) | (U.z ^ par) | (U.w ^ par))
    const int n0 = f < 2 ? 0 : 2 * f - 3, ne = FFN_OFF || !ffn ? 3 : f == 3 ? 3 + G8 : 3 + GN;
    const uint32_t fsb = sb + SM_FST + ((f + 1) & 3) * 8192, fbar = bar + B_FST + f * 16, fst = fsb + (lane >> 4) * 2048 + (lane & 15) * 16;
    const CUtensorMap *ma = &mWc, *mc = &mWc;
    int sx = 1024 + cu * 32, sy = ch * 512 + f * 192, sdy = 32;
#define STAGEG(N)                                                                                            \
  do {                                                                                                       \
    if ((N) == 3) { ma = &mG; mc = &mU; sx = fb * 32; sy = f * (GN * 32);  sdy = 0; }                        \
    if ((N) < ne && elect_one()) {                                                                           \
      const uint32_t dst_ = fsb + ((N) & 1) * 4096, b_ = fbar + ((N) & 1) * 8;                               \
      mbar_expect_tx(b_, 4096);                                                                              \
      tma2d(dst_, ma, sx, sy, b_);                                                                           \
      tma2d(dst_ + 2048, mc, sx, sy + sdy, b_);                                                              \
    }                                                                                                        \
    sy += 32 + sdy;                                                                                          \
  } while (0)
    float a[8], gsum = 0.f, usum = 0.f;
    {
      if (f == 3) {
        if (elect_one()) {
          if (XS_EARLY) { mbar_expect_tx(bar + B_XST, 16384); tma3d(sb + SM_XST, &mXs, 0, bid * 16, 0, bar + B_XST); }
          mbar_expect_tx(bar + B_WPHI, 8192);
          tma2d(sb + SM_WPHI, &mPhi, 0, hg * 128, bar + B_WPHI);
          prefetch_map(&mWq); prefetch_map(&mWo); prefetch_map(&mWp); prefetch_map(&mD);
          PROF(31);
        }
        __syncwarp();
      } else {
        if (lane == 0) prefetch_map(f == 0 ? &mWc : f == 1 ? &mG : &mU);
        if (f == 2) ((float2*)g_y[par])[bid * 32 + lane] = make_float2(0.f, 0.f);
      }
      float st[13];
#pragma unroll
      for (int i = 0; i < 13; i++) st[i] = 0.f;
#pragma unroll 1
      for (int i = 0; i < 4; i++) {
        mbar_wait(bar + B_XST + 8 * (i >> 1), 0);
        if (f == 0 && lane == 0 && i == 0) PROF(1);
        const uint4 wu = lds128u(sb + SM_XSEL + i * 512 + lane * 16);
        const float wf[8] = {bf_lo(wu.x), bf_hi(wu.x), bf_lo(wu.y), bf_hi(wu.y), bf_lo(wu.z), bf_hi(wu.z), bf_lo(wu.w), bf_hi(wu.w)};
        st[12] += ((wf[0] + wf[1]) + (wf[2] + wf[3])) + ((wf[4] + wf[5]) + (wf[6] + wf[7]));
#pragma unroll
        for (int r = 0; r < 4; r++) {
          const uint4 u = lds128u(sb + SM_XST + i * 8192 + (4 * f + r) * 512 + lane * 16);
          const float xf[8] = {bf_lo(u.x), bf_hi(u.x), bf_lo(u.y), bf_hi(u.y), bf_lo(u.z), bf_hi(u.z), bf_lo(u.w), bf_hi(u.w)};
#pragma unroll
          for (int k = 0; k < 8; k++) { st[r] += xf[k]; st[4 + r] = fmaf(xf[k], xf[k], st[4 + r]); st[8 + r] = fmaf(xf[k], wf[k], st[8 + r]); }
        }
        if (i >= 2 && f < 3) STAGEG(n0 + i - 2);
      }
      const bool up = lane & 16, up2 = lane & 8;
#pragma unroll
      for (int q = 0; q < 3; q++) {
        const float k0 = up ? st[4 * q + 2] : st[4 * q], k1 = up ? st[4 * q + 3] : st[4 * q + 1];
        const float o0 = up ? st[4 * q] : st[4 * q + 2], o1 = up ? st[4 * q + 1] : st[4 * q + 3];
        const float m0 = k0 + __shfl_xor_sync(~0u, o0, 16), m1 = k1 + __shfl_xor_sync(~0u, o1, 16);
        a[q] = (up2 ? m1 : m0) + __shfl_xor_sync(~0u, up2 ? m0 : m1, 8);
      }
      a[3] = st[12] + __shfl_xor_sync(~0u, st[12], 16);
      a[3] += __shfl_xor_sync(~0u, a[3], 8);
#pragma unroll
      for (int o = 4; o; o >>= 1)
#pragma unroll
        for (int q = 0; q < 4; q++) a[q] += __shfl_xor_sync(~0u, a[q], o);
      if ((lane & 7) == 0) sts128(sb + SM_ROWS + (4 * f + (lane >> 3)) * 16, a[0], a[1], a[2], a[3]);
      if (f < 3) asm volatile("bar.arrive 7, 128;" ::: "memory");
    }
    if (f == 3) {
      bar_sync(7, 128);
      const int row = bid * 16 + (lane & 15);
      const float4 v = lds128(sb + SM_ROWS + (lane & 15) * 16);
      const float mf = v.x * (1.f / DM), mean = bf_round(mf), var = fmaxf(fmaf(-mf, mf, v.y * (1.f / DM)), 0.f);
      const float sd = bf_round(sqrt_approx(bf_round(bf_round(var) + 1e-5f)));
      const uint32_t rb = pack2(fmaf(-mean, v.w, v.z) * rcp(sd), 0.f) & 0xffffu, ord = (rb & 0x8000u) ? (~rb & 0xffffu) : (rb | 0x8000u);
      uint32_t best = __reduce_max_sync(~0u, (ord << 16) | (uint32_t)(2047 - row));
      if (lane < 16) st_rlx64(g_stat + row, ((unsigned long long)tag << 32) | __float_as_uint(mean) | (__float_as_uint(sd) >> 16));
      if (lane < 2) asm volatile("red.relaxed.gpu.global.max.u64 [%0], %1;" ::"l"(lane ? (void*)(g_ycnt + 32) : (void*)(g_best + bid)), "l"(((unsigned long long)tag << 32) | best) : "memory");
      if (lane == 1) { red_inc(g_ycnt + 34); PROF(17); }
#pragma unroll 1
      for (int n = 3; n < 5; n++) STAGEG(n);
      {
        uint4 xr[4];
        best = routed_row(P.x, tag, lane, xr);
#pragma unroll
        for (int i = 0; i < (GROWS + 255) / 256; i++) {
          const uint32_t dst = sb + SM_XSEL + i * 1024 + (lane >> 2) * 128 + (lane & 3) * 8;
          sts64(dst, bf_lo(xr[i].x), bf_lo(xr[i].z)); sts64(dst + 32, bf_hi(xr[i].x), bf_hi(xr[i].z));
          sts64(dst + 64, bf_lo(xr[i].y), bf_lo(xr[i].w)); sts64(dst + 96, bf_hi(xr[i].y), bf_hi(xr[i].w));
        }
        sts64u(sb + SM_RED + 16, tag, best);
        __syncwarp();
        if (lane == 0) { mbar_arrive(bar + B_XS); PROF(19); }
      }
      unsigned long long sv4[4];
      uint4 u[4];
#pragma unroll 1
      for (int it = 0; it < SPIN_MAX; it++) {
#pragma unroll
        for (int i = 0; i < 4; i++) { u[i] = ld_rlx128(g_cs + (1 + i) * 1024 + hg * 128 + lane * 4); sv4[i] = ld_rlx64(g_stat + mb * 128 + i * 32 + lane); }
        bool ok = ((BAD4(u[0]) | BAD4(u[1]) | BAD4(u[2]) | BAD4(u[3])) & 1) == 0;
#pragma unroll
        for (int i = 0; i < 4; i++) ok = ok && (uint32_t)(sv4[i] >> 32) == tag;
        if (__all_sync(~0u, ok)) break;
        __nanosleep(200);
      }
#pragma unroll
      for (int i = 0; i < 4; i++) {
        const uint32_t sv = (uint32_t)sv4[i], sd2 = (sv << 16) | (sv & 0xffffu);
        sts64(sb + SM_STAT + (i * 32 + lane) * 8, -bf_hi(sv), rcp(bf_lo(sv)));
        sts128u(sb + SM_SDT + lane * 64 + ((i ^ ((lane >> 1) & 3)) << 4), sd2, sd2, sd2, sd2);
      }
#pragma unroll
      for (int i = 0; i < 2; i++) {
        float4 c = make_float4(unmark(u[i].x) + unmark(u[i + 2].x), unmark(u[i].y) + unmark(u[i + 2].y), unmark(u[i].z) + unmark(u[i + 2].z),
                               unmark(u[i].w) + unmark(u[i + 2].w));
        CS_STORE(i, c);
      }
      fence_async_smem();
      bar_sync(8, 64);
      if (lane == 0) { mbar_arrive(bar + B_CS); PROF(10); }
    }
    {
      uint32_t xa = sb + SM_RED + 32, xstep = 0;
      const uint32_t zero = __float_as_uint(lds32(sb + SM_RED + 12));
#pragma unroll 1
      for (int ph = f == 3; ph < 2; ph++) {
#pragma unroll
        for (int j = 0; j < 8; j++) a[j] = 0.f;
        if (ph && f == 0) {
        {
          mbar_wait(bar + B_WPHI, 0);
          float nq[8] = {0.f, 0.f, 0.f, 0.f, 0.f, 0.f, 0.f, 0.f};
  #pragma unroll 2
          for (int r = 0; r < 16; r++) {
            const uint4 u = lds128u(sb + SM_WPHI + ((lane >> 2) * 16 + r) * 64 + (((lane ^ (r >> 1)) & 3) << 4));
            nq[0] = fmaf(bf_lo(u.x), bf_lo(u.x), nq[0]); nq[1] = fmaf(bf_hi(u.x), bf_hi(u.x), nq[1]); nq[2] = fmaf(bf_lo(u.y), bf_lo(u.y), nq[2]);
            nq[3] = fmaf(bf_hi(u.y), bf_hi(u.y), nq[3]); nq[4] = fmaf(bf_lo(u.z), bf_lo(u.z), nq[4]); nq[5] = fmaf(bf_hi(u.z), bf_hi(u.z), nq[5]);
            nq[6] = fmaf(bf_lo(u.w), bf_lo(u.w), nq[6]); nq[7] = fmaf(bf_hi(u.w), bf_hi(u.w), nq[7]);
          }
          uint32_t m = 0;
  #pragma unroll
          for (int i = 0; i < 8; i++) m = max(m, __float_as_uint(nq[i] + __shfl_xor_sync(~0u, nq[i], 4)) & 0x7fffffffu);
          sts32(sb + SM_RED + 24, 4.2f * __uint_as_float(__reduce_max_sync(~0u, m)));
        }
          asm volatile("bar.arrive 8, 64;" ::: "memory");
        }
        if (ph) { mbar_wait(bar + B_XS, 0); xa = sb + SM_XSEL + f * (GN * 128) + ((lane >> 2) & 3) * 32; xstep = 128; }
#pragma unroll 1
        for (int n = ph ? 3 : n0; n < (ph ? ne : 3); n++) {
          const float4 x0 = lds128(xa), x1 = lds128(xa + 16);
          xa += xstep;
          mbar_wait(fbar + (n & 1) * 8, ((n - n0) >> 1) & 1);
          uint4 u[8];
#pragma unroll
          for (int j = 0; j < 8; j++) u[j] = lds128u(fst + (n & 1) * 4096 + j * 256);
          FMA8(a, u[0], x0.x); FMA8(a, u[1], x0.y); FMA8(a, u[2], x0.z); FMA8(a, u[3], x0.w);
          if (__any_sync(~0u, ((u[4].x | u[5].x | u[6].x | u[7].x | __float_as_uint(a[0]) | __float_as_uint(a[7])) & zero) == 0)) STAGEG(n + 2);
          FMA8(a, u[4], x1.x); FMA8(a, u[5], x1.y); FMA8(a, u[6], x1.z); FMA8(a, u[7], x1.w);
        }
#pragma unroll
        for (int o = 4; o <= 8; o <<= 1)
#pragma unroll
          for (int j = 0; j < 8; j++) a[j] += __shfl_xor_sync(~0u, a[j], o);
        if (ph && lane == 0) mbar_arrive(bar + B_FFN);
        const uint32_t red = ph ? sb + SM_GRED : sb + SM_RED + 64;
        if ((lane & 12) == 0) {
          const uint32_t d = red + f * 256 + (lane >> 4) * 128 + (lane & 3) * 32;
          sts128(d, a[0], a[1], a[2], a[3]); sts128(d + 16, a[4], a[5], a[6], a[7]);
        }
        if (f != 2) {
          asm volatile("bar.arrive %0, %1;" ::"r"(4 + ph), "r"(96 + 32 * ph) : "memory");
        } else {
          bar_sync(4 + ph, 96 + 32 * ph);
          const uint32_t ra = red + lane * 4;
          gsum = lds32(ra) + lds32(ra + 256) + lds32(ra + 512);
          usum = lds32(ra + 128) + lds32(ra + 384) + lds32(ra + 640);
          if (!ph) st_rlx(g_cs + 1024 + ch * 2048 + cu * 32 + lane, mark(__float_as_uint(gsum + usum), par));
          else { gsum += lds32(ra + 768); usum += lds32(ra + 896); }
          if (lane == 0) PROF(ph ? 34 : 18);
        }
      }
    }
    if (f == 3) {
      if (elect_one()) {
        PROF(7);
        mbar_wait(bar + B_FULLQ, 0);
#pragma unroll 1
        for (int j = 3; j < 16; j++) {
          mbar_wait(bar + (j < 4 ? B_EMPTYKV + 16 : B_EMPTYQ + 8 * (j & 3)), ((j >> 2) & 1) ^ 1);
          if (j == 12 + (hg & 3)) mbar_wait(bar + B_KVST + 8, 0);
          Q_LOAD(j);
        }
        PROF(47);
        mbar_expect_tx(bar + B_DN, 65536);
#pragma unroll 1
        for (int i = 0; i < 4; i++) {
          mbar_wait(bar + B_EMPTYQ + 8 * i, 1);
          tma3d(sb + i * Q_STAGE, &mD, 0, fb * 32, i * 4, bar + B_DN);
        }
        PROF(48);
#pragma unroll 1
        for (int i = 0; i < 16; i++) {
          const int s = i & 3, n = i < 9 ? i - 2 : i - 9, kb = i < 2 ? 2 * hg + i : 2 * (n + (n >= hg)) + (i >= 9);
          if (i >= 4) mbar_wait(bar + B_EMPTYQ + 8 * s, ((i >> 2) & 1) ^ 1);
          mbar_expect_tx(bar + B_FULLQ + 8 * s, 16384);
          if (i < 2) {
            mbar_arrive2(bar + B_FULLQ + 8 * s);
            tma3d(sb + s * Q_STAGE + 16384, &mWo, 0, kb * 64, hg * 2, bar + B_FULLQ + 8 * s);
          } else {
            tma5d(sb + s * Q_STAGE + 16384, &mWp, hg * 128, kb * 2, bar + B_FULLQ + 8 * s);
            tma5d(sb + s * Q_STAGE + 24576, &mWp, hg * 128 + 64, kb * 2, bar + B_FULLQ + 8 * s);
            if (i >= 3) {
              if (i == 3) { mbar_wait(bar + B_DND, 0); PROF(14); }
#pragma unroll 1
              for (int a = i == 3 ? 2 : i; a <= i; a++) {
                const uint4* src = g_ofr + (mb * 16 + (a == 2 ? (hg == 0 ? 2 : 0) : kb)) * 1024;
#pragma unroll
                for (int h = 0; h < 2; h++) {
                  mbar_expect_tx(bar + B_AIN + (a & 3) * 16 + h * 8, 8192);
                  bulk_load(sb + (a & 3) * Q_STAGE + h * 8192, src + h * 512, 8192, bar + B_AIN + (a & 3) * 16 + h * 8);
                }
              }
            }
          }
        }
      }
    } else {
      if (f == 2) {
        if (PFD && ffn) {
#pragma unroll 1
          for (int i = 0; i < 16; i++) { touch_l2((const char*)P.w_down + fb * 65536 + i * 4096 + lane * 128, lane); __nanosleep(PFD); }
        }
        if (WOT) {
#pragma unroll 1
          for (int i = 0; i < 8; i++) { touch_l2((const char*)P.wo + ((mb & 7) * 128 + i * 16 + (lane >> 1)) * 2048 + hg * 256 + (lane & 1) * 128, lane); __nanosleep(PFD); }
        }
        asm volatile("cp.async.wait_all;" ::: "memory");
        uint4 u;
#pragma unroll 1
        for (int it = 0; it < SPIN_MAX; it++) {
          u = ld_rlx128(g_cs + hg * 128 + lane * 4);
          if (__all_sync(~0u, !(BAD4(u) & 1))) break;
          __nanosleep(200);
        }
        mbar_wait(bar + B_PHI, 0);
        float4 c = make_float4(unmark(u.x), unmark(u.y), unmark(u.z), unmark(u.w));
        CS_STORE(2, c);
        fence_async_smem();
        __syncwarp();
        if (lane == 0) mbar_arrive(bar + B_CSQ);
        if (ffn && !FFN_OFF) {
#pragma unroll 1
          for (int it = 0; it < SPIN_MAX; it++) {
            const uint32_t pg = ld_rlx((const uint32_t*)g_gp + fb * 32 + lane), pu = ld_rlx((const uint32_t*)g_gp + FF + fb * 32 + lane);
            if (__all_sync(~0u, !(((pg ^ par) | (pu ^ par)) & 1))) { gsum += unmark(pg); usum += unmark(pu); break; }
            __nanosleep(200);
          }
        }
        const float h = bf_round(silu_f(bf_round(gsum))) * bf_round(usum);
        const uint32_t h2 = pack2(h, h);
        sts128u(sb + SM_HT + lane * 16, h2, h2, h2, h2);
        fence_async_smem();
        __syncwarp();
        if (lane == 0) { mbar_arrive(bar + B_H); PROF(20); }
      }
      if (f < 2) {
        const uint32_t own = (hg * 2 + f) * 16 + mb, target = __shfl_sync(~0u, tag, 0) * 16;
        mbar_wait(bar + B_KVST + 8 * f, 0);
        if (f == 1 && lane == 0) PROF(11);
        wait_hint(g_xcnt + hg * 64 + f * 16 + mb, target);
        if (elect_one()) {
          PROF(35 + f);
          fence_async_global();
          mbar_expect_tx(bar + B_PART + 8 * f, 8192);
          bulk_load(sb + (f ? SM_PST1 : SM_PST0), g_part + own * 512, 8192, bar + B_PART + 8 * f);
        }
        __syncwarp();
        {
          uint4 uz;
#pragma unroll 1
          for (int it = 0; it < SPIN_MAX; it++) {
            uz = ld_rlx128(g_zpart + own * 128 + lane * 4);
            if (__all_sync(~0u, !(BAD4(uz) & 1))) break;
          }
          const bool b1 = lane & 2, b2 = lane & 4;
          const float z0 = unmark(b1 ? uz.z : uz.x) + __shfl_xor_sync(~0u, unmark(b1 ? uz.x : uz.z), 2);
          const float z1 = unmark(b1 ? uz.w : uz.y) + __shfl_xor_sync(~0u, unmark(b1 ? uz.y : uz.w), 2);
          float z = (b2 ? z1 : z0) + __shfl_xor_sync(~0u, b2 ? z0 : z1, 4);
          z += __shfl_xor_sync(~0u, z, 8);
          z += __shfl_xor_sync(~0u, z, 16);
          if (lane < 8) st_rlx(g_zres + own * 8 + (lane & 1) * 4 + (lane & 2) + (lane >> 2), mark(__float_as_uint(z), par));
          if (lane == 0) red_inc(g_xcnt + hg * 64 + 32 + f * 16);
          __syncwarp();
        }
        wait_hint(g_xcnt + hg * 64 + 32 + f * 16, 5 * target);
        mbar_wait(bar + B_KVST + 8, 0);
        if (lane == 0) PROF(40 + f);
#pragma unroll 1
        for (int it = 0; it < SPIN_MAX; it++) {
          if (elect_one()) {
            fence_async_global();
            mbar_expect_tx(bar + B_RES + 8 * f, 8192);
            bulk_load(sb + SM_V + f * 8192, g_res[par] + (hg * 4 + f * 2) * 256, 8192, bar + B_RES + 8 * f);
          }
          __syncwarp();
          const uint4 uz = ld_rlx128(g_zres + (hg * 4 + f * 2) * 64 + lane * 4);
          const uint32_t zw[4] = {uz.x, uz.y, uz.z, uz.w};
#pragma unroll
          for (int j = 0; j < 4; j++) {
            const uint32_t zz = pack2(unmark(zw[j]), 1.f), row = (lane & 3) * 4 + j;
            sts128u(sb + SM_ZT + (2 * f + (lane >> 4)) * 1024 + row * 64 + ((((lane >> 2) ^ (row >> 1)) & 3) << 4), zz, zz, zz, zz);
          }
          uint32_t bad = BAD4(uz);
          mbar_wait(bar + B_RES + 8 * f, it & 1);
#pragma unroll
          for (int i = 0; i < 16; i++) bad |= ~__float_as_uint(lds32(sb + SM_V + f * 8192 + i * 512 + lane * 16));
          if (__all_sync(~0u, !(bad & 1))) break;
        }
        fence_async_smem();
        __syncwarp();
        if (lane == 0) { mbar_arrive(bar + B_TILE + 8 * f); PROF(f ? 13 : 27); }
      }
      if (f < 2) {
        uint32_t phases = 0;
#pragma unroll 1
        for (int i = 2; i < 16; i++) {
          const int s = i & 3;
          const uint32_t ab = bar + B_AIN + s * 16 + f * 8, slot = sb + s * Q_STAGE + f * 8192;
#pragma unroll 1
          for (int it = 0; it < SPIN_MAX; it++) {
            mbar_wait(ab, (phases >> s) & 1);
            phases ^= 1u << s;
            uint32_t bad = 0;
#pragma unroll
            for (int n = 0; n < (NOVAL ? 0 : 8); n++) bad |= __float_as_uint(lds32(slot + n * 1024 + lane * 32 + (lane >> 2) * 4)) ^ par;
            if (__all_sync(~0u, !(bad & 1))) break;
            if (elect_one()) {
              const int n = i < 9 ? i - 2 : i - 9, kb = 2 * (n + (n >= hg)) + (i >= 9);
              PROF(49);
              mbar_expect_tx(ab, 8192);
              bulk_load(slot, g_ofr + (mb * 16 + kb) * 1024 + f * 512, 8192, ab);
            }
            __syncwarp();
          }
          if (lane == 0) { mbar_arrive(bar + B_FULLQ + 8 * s); if (i == 2 && f == 0) PROF(15); }
        }
        if (f == 0) g_epoch[bid * 32 + lane] = tag;
      } else {
        if (elect_one()) {
          prefetch_map(&mOut);
          if (ffn) { mbar_wait(bar + B_YD, 0); red_rel(g_ycnt); PROF(21); }
        }
        __syncwarp();
        if (f == 2) {
          const uint32_t best = __float_as_uint(lds32(sb + SM_RED + 20));
          const int sel = 2047 - (best & 0x7ff) - mb * 128;
          if (sel >= 0 && sel < 128) {
            const uint2 xr = __ldg((const uint2*)(P.x + (size_t)(mb * 128 + sel) * DM + hg * 128 + lane * 4));
            const float2 st = lds64(sb + SM_STAT + sel * 8);
            const uint32_t ord = best >> 16, rb = (ord & 0x8000u) ? (ord & 0x7fffu) : (~ord & 0xffffu);
            const float sg = rcp(1.f + ex2(-1.4426950408889634f * bf_lo(rb)));
            const uint32_t sg2 = pack2(sg, sg), nm2 = pack2(st.x, st.x);
            wait_cnt<0>(g_ycnt, tag * NFFN);
            float4 y = make_float4(0.f, 0.f, 0.f, 0.f);
#pragma unroll
            for (int i = 0; i < 8; i++) {
              const float4 c = ldg_cg4(g_y[par ^ 1][i] + hg * 128 + lane * 4);
              y.x += c.x; y.y += c.y; y.z += c.z; y.w += c.w;
            }
            uint32_t o[2];
#pragma unroll
            for (int i = 0; i < 2; i++) {
              const uint32_t d = badd2(i ? xr.y : xr.x, nm2);
              const uint32_t tt = badd2(pack2(bf_lo(d) * st.y, bf_hi(d) * st.y), bmul2(i ? pack2(y.z, y.w) : pack2(y.x, y.y), sg2));
              o[i] = pack2(silu_f(bf_lo(tt)), silu_f(bf_hi(tt)));
            }
            sts64u(sb + SM_UPD + lane * 8, o[0], o[1]);
          }
          if (lane == 0) sts32(sb + SM_UPD + 256, __int_as_float(sel));
          __syncwarp();
          if (lane == 0) { mbar_arrive(bar + B_UPD); PROF(22); }
        }
      }
    }
  } else {
    const int t7 = threadIdx.x & 127;
    const char* pfa = warp < 4 ? (const char*)P.x + bid * 32768 + (t7 & 15) * 2048 + (t7 >> 4) * 128
                               : (const char*)P.wqkv + (size_t)((t7 >> 4) * 64 + (bid >> 1)) * 6144 + 2048 + (bid & 1) * 2048 + (t7 & 15) * 128;
    {
      const uint32_t r0 = threadIdx.x >> 3, c = threadIdx.x & 7, dst = sb + 2 * KV_STAGE + r0 * 128 + ((c ^ (r0 & 7)) << 4);
      const char* xs = (const char*)P.x + (size_t)(mb * 128 + r0) * 2048 + c * 16;
      const char* ws = (const char*)P.wqkv + (size_t)r0 * 6144 + 2048 + hg * 256 + c * 16;
#pragma unroll
      for (int i = 0; i < 4; i++) cp_async16(dst + i * 4096, xs + i * 65536);
#pragma unroll
      for (int i = 0; i < 8; i++) cp_async16(dst + 16384 + i * 4096, ws + (i & 1) * 196608 + (i >> 2) * 2048 + ((i >> 1) & 1) * 128);
    }
    if (t7 >= 16 && t7 < 16 * PF_FIRST) prefetch_l2(pfa);
    if (warp < 7) sts128(sb + SM_CST + threadIdx.x * 16, 0.f, 0.f, 0.f, 0.f);
    else sts32(sb + SM_RED + (threadIdx.x & 15) * 4, threadIdx.x & 8 ? 1.f : 0.f);
    if (elect_one()) {
#pragma unroll 1
      for (uint32_t b = B_FST + warp * 8; b < B_END; b += 64)
        mbar_init(bar + b, b < B_FULLQ ? 1 : b < B_FFN ? 3 : b < B_EMPTYKV ? 4 : 8);
    }
    __syncwarp();
    asm volatile("bar.arrive 13, 384;" ::: "memory");
    asm volatile("setmaxnreg.inc.sync.aligned.u32 %0;" ::"n"(REG_C));
    if (t7 >= 16 * PF_FIRST && threadIdx.x < 128 + 16 * PF_W) prefetch_l2(pfa);
    asm volatile("cp.async.wait_all;" ::: "memory");
    fence_async_smem();
    bar_sync(14, 288);
    if (threadIdx.x == 0) mbar_arrive(bar + B_FULLKV + 16);
    const int lane = lane_id();
    const int wg = warp >> 2, w = warp & 3, g = lane >> 2, t = lane & 3;
    float kv[128];
    {
      uint32_t s = 2, ph = 0, sp = 0, php = 0;
#pragma unroll 1
      for (int j = 0; j < 15; j++) {
        PW0(32 + j); mbar_wait(bar + B_FULLKV + 8 * s, ph); PW1(32 + j);
        if (wg == 1 && (ORDER_ALL || j == 0)) bar_sync(10 + s, 256);
        wg_fence();
        wgmma_n256_ssp_ta0_tb1(kv, mkdesc(sb, 16, 1024, 1, wg * 512 + s * (KV_STAGE / 16)), mkdesc(sb + 16384, 8192, 1024, 1, s * (KV_STAGE / 16)), j);
#pragma unroll
        for (int k = 1; k < 4; k++)
          wgmma_n256_ss_ta0_tb1(kv, mkdesc(sb + k * 32, 16, 1024, 1, wg * 512 + s * (KV_STAGE / 16)),
                                mkdesc(sb + 16384 + k * 2048, 8192, 1024, 1, s * (KV_STAGE / 16)), 1);
        wg_commit();
        if (wg == 0 && (ORDER_ALL || j == 0)) asm volatile("bar.arrive %0, 256;" ::"r"(10 + s) : "memory");
        if (warp == 0 && j) {
          mbar_wait(bar + B_EMPTYKV + 8 * sp, php);
          if (elect_one()) {
            if (j < 14) {
              mbar_expect_tx(bar + B_FULLKV + 8 * sp, KV_STAGE);
              tma2d(sb + sp * KV_STAGE, &mX, (j + 2) * 64, mb * 128, bar + B_FULLKV + 8 * sp);
              tma4d(sb + sp * KV_STAGE + 16384, &mWkv, 0, (j + 2) * 64, hg * 2, 1, bar + B_FULLKV + 8 * sp);
            } else {
              Q_LOAD(0);
            }
            if (j < 3 - XS_EARLY) {
              const int xh = j - 1 + XS_EARLY;
              mbar_expect_tx(bar + B_XST + 8 * xh, 16384);
              tma3d(sb + SM_XST + xh * 16384, &mXs, 0, bid * 16, 2 * xh, bar + B_XST + 8 * xh);
            }
          }
          __syncwarp();
        }
        if (j == 0) {
          if (wg == 0) prefetch_l2(pfa + 1024);
        } else if (wg == 1) {
          if (j < 3) {
            if (j == 2 || t7 >= 16 * PF_W) prefetch_l2(pfa + (j - 1) * (8 * 393216));
          } else if (j == 13) {
            prefetch_l2((const char*)P.wo + bid * 16384 + t7 * 128);
          }
          if (PFG && !FFN_OFF && bid < NFFN && j >= 2 && j < 2 + GROWS / 64 && w < 2)
            touch_l2((const char*)((bid & 1) ? P.w_up : P.w_gate) + (size_t)((0x852a7419630ull >> (4 * j - 8) & 15) * 64 + t7) * 7168 + (bid >> 1) * 128, lane);
        }
        wg_wait<0>();
        if (lane == 0) mbar_arrive(bar + B_EMPTYKV + 8 * s);
        sp = s; php = ph;
        ph ^= s == 1;
        s = s == 2 ? 0 : s + 1;
      }
    }
    const int lrow = wg * 64 + w * 16 + (lane & 15);
    const uint32_t sw128 = lrow * 128, x128 = (lrow & 7), hi16 = lane >> 4;
    mbar_wait(bar + B_CS, 0);
    const uint32_t tag = __float_as_uint(lds32(sb + SM_RED + 16));
    const int zero = __float_as_int(lds32(sb + SM_RED + 12));
    const float wn = lds32(sb + SM_RED + 24);
    const float2 st0 = lds64(sb + SM_STAT + (wg * 64 + w * 16 + g) * 8), st1 = lds64(sb + SM_STAT + (wg * 64 + w * 16 + g + 8) * 8);
    const float c0 = st0.y * 1.4426950408889634f, c1 = st1.y * 1.4426950408889634f;
    const uint32_t nm20 = pack2(st0.x, st0.x), nm21 = pack2(st1.x, st1.x), fmask = t == 0 ? ~0u : t == 1 ? 0xffffu : 0u;
    const uint32_t fa0 = nm20 & fmask, fa1 = nm21 & fmask;
    asm volatile("cp.async.wait_all;" ::: "memory");
    PW0(47); mbar_wait(bar + B_FULLKV + 16, 1); PW1(47);
    wg_fence();
    wgmma_n256_rs_ta0_tb1(kv, fa0, fa1, 0u, 0u, mkdesc(sb + SM_CST, 512, 0, 1), 1);
#pragma unroll
    for (int k = 0; k < 4; k++)
      wgmma_n256_ss_ta0_tb1(kv, mkdesc(sb + 2 * KV_STAGE + k * 32, 16, 1024, 1, wg * 512), mkdesc(sb + 2 * KV_STAGE + 16384 + k * 2048, 8192, 1024, 1), 1);
    wg_commit();
    if (warp == 0) {
      mbar_wait(bar + B_EMPTYKV + 8, 0);
      if (elect_one()) {
#pragma unroll 1
        for (int j = 1; j < 3; j++) Q_LOAD(j);
      }
      __syncwarp();
    }
    wg_wait<0>();
    reg_fence<128>(kv);
    if (lane == 0) mbar_arrive(bar + B_EMPTYKV + 16);
    PROFC(2);
    float q[64];
#define QMMA(J, AOFF16, ACCUM)                                                                                     \
  _Pragma("unroll") for (int k = 0; k < 4; k++)                                                                    \
      wgmma_n128_ss_ta0_tb1(q, mkdesc(sb + k * 32, 16, 1024, 1, wg * 512 + (AOFF16)),                              \
                            mkdesc(sb + 16384 + k * 2048, 8192, 1024, 1, ((J) & 3) * (Q_STAGE / 16)), k ? 1 : (ACCUM))
#define QWAIT(J) do { PW0(J); mbar_wait(bar + B_FULLQ + 8 * ((J) & 3), ((J) >> 2) & 1); PW1(J); } while (0)
#define QSTEP_A(J, AOFF16, ACCUM) do { QWAIT(J); wg_fence(); QMMA(J, AOFF16, ACCUM); wg_commit(); } while (0)
#define QREL(J) do { if (lane == 0) mbar_arrive(bar + B_EMPTYQ + 8 * ((J) & 3)); } while (0)
#define Q_OFF16(J) ((J) >= 8 && (J) < 16 ? Q_AOFF(J) / 16 : ((J) & 3) * (Q_STAGE / 16))
#define QPLAIN(J) do { QSTEP_A(J, Q_OFF16(J), 1); wg_wait<1>(); QREL((J) - 1); } while (0)
#define QNEXT(J) do { QPLAIN(J); SCHED_FENCE(); } while (0)
#define PHI_PROJ(DST, SRC, H0, H1)                                                                                 \
  do {                                                                                                             \
    uint32_t a_[32];                                                                                               \
    _Pragma("unroll") for (int j = 8 * (H0); j < 8 * (H1); j++) {                                                  \
      a_[j] = pack2(SRC[2 * j], SRC[2 * j + 1]);                                                                   \
      asm volatile("fma.rn.bf16x2 %0, %1, %1, %0;" : "+r"(nq[(j >> 4) * 2 + (j & 1)]) : "r"(a_[j]));               \
    }                                                                                                              \
    wg_fence();                                                                                                    \
    _Pragma("unroll") for (int hk = 2 * (H0); hk < 2 * (H1); hk++)                                                 \
        wgmma_n32_rs_ta0_tb1(DST + 16 * (hk >> 1), a_[4 * hk], a_[4 * hk + 1], a_[4 * hk + 2], a_[4 * hk + 3],     \
                             mkdesc(sb + SM_WPHI + hk * 1024, 16, 512, 2), hk & 1);                                \
    wg_commit();                                                                                                   \
  } while (0)
    {
      float p[64], ea[24], eb[24], sa[4], sc[4], kz[20];
      uint32_t vp[32];
#pragma unroll
      for (int j = 0; j < 32; j++) vp[j] = pack2(kv[64 + 2 * j], kv[65 + 2 * j]);
      const uint32_t vr = w * 16 + (lane & 15), vb = sb + SM_V + wg * 4096 + vr * 64, x64 = (vr >> 1) & 3;
#define V_STORE(R)                                                                                           \
  _Pragma("unroll") for (int j = 0; j < 4; j++)                                                              \
      stsm4(vb + (j >> 1) * 8192 + ((((j & 1) * 2 + hi16) ^ x64) << 4), vp[16 * (R) + 4 * j], vp[16 * (R) + 4 * j + 1], vp[16 * (R) + 4 * j + 2], vp[16 * (R) + 4 * j + 3])
      V_STORE(0);
      mbar_wait(bar + B_WPHI, 0);
      {
        uint32_t nq[4] = {0u, 0u, 0u, 0u};
        PHI_PROJ(p, kv, 0, 4);
        QSTEP_A(0, 0, 0);
        const bool unsafe = softmax_unsafe(nq, c0 * c0 * wn, c1 * c1 * wn);
        wg_wait<1>();
        reg_fence<64>(p);
        if (__builtin_expect(unsafe, 0)) softmax_shift(p, c0, c1);
      }
#define K_NORM(S) do { quad_sum<4>(S); _Pragma("unroll") for (int i = 0; i < 4; i++) S[i] = rcp(S[i]) * ((i & 1) ? st1.y : st0.y); } while (0)
#define K_STORE(SLOT, E, S) K_STORE_(SLOT, E, S, 0, 2)
#define K_STORE_(SLOT, E, S, J0, J1)                                                                         \
  _Pragma("unroll") for (int j = (J0); j < (J1); j++) {                                                      \
    uint32_t fp[4], fm[4];                                                                                   \
    _Pragma("unroll") for (int i = 0; i < 4; i++) {                                                          \
      const float e0 = E[8 * j + 2 * i], e1 = E[8 * j + 2 * i + 1], r = E[16 + 4 * j + i] * S[2 + (i & 1)];  \
      const uint32_t e2 = pack2(e0, e1);                                                                     \
      fp[i] = bmul2(e2, pack2(S[i & 1], S[i & 1]));                                                          \
      fm[i] = bmul2(e2, pack2(r, r));                                                                        \
    }                                                                                                        \
    stsm4(sb + SM_PHI + (SLOT) * 16384 + sw128 + (((2 * j + hi16) ^ x128) << 4), fp[0], fp[1], fp[2], fp[3]); \
    stsm4(sb + SM_PHI + (SLOT) * 16384 + sw128 + (((4 + 2 * j + hi16) ^ x128) << 4), fm[0], fm[1], fm[2], fm[3]); \
  }
#define KV_MMA(R)                                                                                            \
  do {                                                                                                       \
    mbar_wait(bar + B_PHI + 8 * (R), 0);                                                                     \
    wg_fence();                                                                                              \
    _Pragma("unroll") for (int k = 0; k < 8; k++) {                                                          \
      const uint32_t vs = SM_V + (k >> 2) * 4096 + (k & 3) * 1024;                                           \
      wgmma_n40_ss_ta1_tb1(kz, mkdesc(sb + SM_PHI + k * 2048, 16, 1024, 1, wg * 1024),                       \
                           mkdesc(sb + vs, SM_SDT + (k & 1) * 1024 + (k >> 1) * 16 - vs, 512, 2, wg * (512u - (512u << 16))), k); \
    }                                                                                                        \
    wg_commit();                                                                                             \
  } while (0)
#define QKV(J, R) do { KV_MMA(R); QSTEP_A(J, Q_OFF16(J), 1); wg_wait<2>(); QREL((J) - 1); SCHED_FENCE(); } while (0)
#define KV_SEND(R)                                                                                           \
  do {                                                                                                       \
    reg_fence<20>(kz);                                                                                       \
    if (lane == 0) mbar_arrive(bar + B_KVST + 8 * (R));                                                      \
    const uint32_t slot = ((hg * 2 + (R)) * 16 + warp * 2) * 16 + mb;                                        \
    _Pragma("unroll") for (int u = 0; u < 2; u++)                                                            \
      st_rlx128(g_part + (slot + u * 16) * 32 + lane, mark(pack2(kz[2 * u], kz[2 * u + 1]), tag & 1), pack2(kz[2 * u + 4], kz[2 * u + 5]), \
                pack2(kz[2 * u + 8], kz[2 * u + 9]), pack2(kz[2 * u + 12], kz[2 * u + 13]));                 \
    if (t < 2) st_rlx(g_zpart + (slot + t * 16) * 8 + g, mark(__float_as_uint(t ? kz[18] : kz[16]), tag & 1)); \
    if (lane < 2) red_inc(g_xcnt + hg * 64 + (R) * 16 + warp * 2 + lane);                                    \
  } while (0)
#define K_PUB(R) do { fence_async_smem(); __syncwarp(); if (lane == 0) mbar_arrive(bar + B_PHI + 8 * (R)); } while (0)
#define S_PIN(S) SCHED_PIN(S[0] + S[1] + S[2] + S[3])
      k_exp(p, c0, c1, ea, sa);
      S_PIN(sa);
      QNEXT(1);
      K_NORM(sa);
      k_exp<0, 4>(p + 16, c0, c1, eb, sc);
      mbar_wait(bar + B_FFN, 0);
      K_STORE_(0, ea, sa, 0, 1);
      S_PIN(sc);
      QNEXT(2);
      K_STORE_(0, ea, sa, 1, 2);
      k_exp<4, 8>(p + 16, c0, c1, eb, sc);
      K_NORM(sc);
      S_PIN(sc);
      QNEXT(3);
      K_STORE(1, eb, sc);
      K_PUB(0);
      k_exp<0, 4>(p + 32, c0, c1, ea, sa);
      S_PIN(sa);
      QKV(4, 0);
      k_exp<4, 8>(p + 32, c0, c1, ea, sa);
      K_NORM(sa);
      k_exp<0, 4>(p + 48, c0, c1, eb, sc);
      SCHED_PIN(sa[0] + sa[1] + sa[2] + sa[3] + sc[2] + sc[3]);
      QNEXT(5);
      KV_SEND(0);
      k_exp<4, 8>(p + 48, c0, c1, eb, sc);
      S_PIN(sc);
      QNEXT(6);
      K_NORM(sc);
      mbar_wait(bar + B_KVST, 0);
      V_STORE(1);
      K_STORE(0, ea, sa);
      QNEXT(7);
      K_STORE(1, eb, sc);
      K_PUB(1);
      QKV(8, 1);
      QNEXT(9);
      KV_SEND(1);
    }
#define JQ0 10
    PROFC(3);
    {
      bool todo = true;
#pragma unroll 1
      for (int j = JQ0; j < 15 || todo; j++) {
        if (j < 15) { QSTEP_A(j, Q_AOFF(j) / 16, 1); wg_wait<1>(); QREL(j - 1); }
        if (todo && __any_sync(~0u, mbar_test(bar + B_PART + 8 * wg, 0))) {
          todo = false;
          const uint32_t own = (hg * 2 + wg) * 16 + mb, word = w * 32 + lane;
          uint32_t u[16], bad = 0;
#pragma unroll
          for (int i = 0; i < 16; i++) { u[i] = __float_as_uint(lds32(sb + (wg ? SM_PST1 : SM_PST0) + i * 512 + word * 4)); bad |= u[i] ^ tag; }
#pragma unroll 1
          for (int it = 0; it < SPIN_MAX && __any_sync(~0u, t == 0 && (bad & 1)); it++) {
            bad = 0;
#pragma unroll
            for (int i = 0; i < 16; i++) { u[i] = ld_rlx((const uint32_t*)g_part + own * 2048 + i * 128 + word); bad |= u[i] ^ tag; }
          }
          float s0 = 0.f, s1 = 0.f, s2 = 0.f, s3 = 0.f;
#pragma unroll
          for (int i = 0; i < 16; i += 2) { s0 += bf_lo(u[i] | !t); s1 += bf_hi(u[i]); s2 += bf_lo(u[i + 1] & (t ? ~0u : ~1u)); s3 += bf_hi(u[i + 1]); }
          const uint32_t r = pack2(s0 + s2, s1 + s3);
          st_rlx((uint32_t*)g_res[tag & 1] + own * 128 + w * 32 + (lane & 16) + ((t ^ w) << 2) + ((lane >> 2) & 3), lane & 12 ? r : r | 1);
          ((uint32_t*)g_res[~tag & 1])[own * 128 + word] = 0;
          __syncwarp();
          if (lane == 0) { red_inc(g_xcnt + hg * 64 + 32 + wg * 16); if (w == 0) PROF(wg ? 12 : 30); }
          __syncwarp();
        }
      }
    }
    mbar_wait(bar + B_CSQ, 0);
    QWAIT(15);
    if (wg == 1) bar_sync(6, 256);
    wg_fence();
    wgmma_n128_rs_ta0_tb1(q, fa0, fa1, 0u, 0u, mkdesc(sb + SM_CST + 2048, 512, 0, 1), 1);
    QMMA(15, Q_AOFF(15) / 16, 1);
    wg_commit();
    if (wg == 0) asm volatile("bar.arrive 6, 256;" ::: "memory");
    wg_wait<1>();
    QREL(14);
    wg_wait<0>();
    QREL(15);
    reg_fence<64>(q);
    PROFC(5);
    float yp[4];
    const uint32_t par = tag & 1;
    uint4* ofr = g_ofr + (mb * 16 + hg * 2) * 1024 + (warp * 16 + g) * 8;
#define O_MMA(H, F, N)                                                                                       \
  do {                                                                                                       \
    wg_fence();                                                                                              \
    _Pragma("unroll") for (int k = 0; k < 4; k++) {                                                          \
      const uint32_t ks = SM_V + (H) * 4096 + k * 1024;                                                      \
      wgmma_n40_rs_ta0_tb1(N + 20 * (k >> 1), F[4 * k], F[4 * k + 1], F[4 * k + 2], F[4 * k + 3],            \
                           mkdesc(sb + ks, SM_ZT + (H) * 1024 + k * 16 - ks, 512, 2), k & 1);                \
    }                                                                                                        \
    wg_commit();                                                                                             \
  } while (0)
#define O_FIN(H, N, o)                                                                                        \
  do {                                                                                                       \
    reg_fence<40>(N);                                                                                        \
    const float *np = N, *nm = N + 20;                                                                       \
    const float d0 = rcp(fmaf(np[16], nm[17], fmaf(nm[16], np[17], 1e-6f * np[17] * nm[17])));               \
    const float d1 = rcp(fmaf(np[18], nm[19], fmaf(nm[18], np[19], 1e-6f * np[19] * nm[19])));               \
    const float bp0 = nm[17] * d0, bm0 = np[17] * d0, bp1 = nm[19] * d1, bm1 = np[19] * d1;                  \
    _Pragma("unroll") for (int j = 0; j < 4; j++) {                                                          \
      o[2 * j] = pack2(fmaf(np[4 * j], bp0, nm[4 * j] * bm0), fmaf(np[4 * j + 1], bp0, nm[4 * j + 1] * bm0)); \
      o[2 * j + 1] = pack2(fmaf(np[4 * j + 2], bp1, nm[4 * j + 2] * bm1), fmaf(np[4 * j + 3], bp1, nm[4 * j + 3] * bm1)); \
    }                                                                                                        \
  } while (0)
#define O_STG(H, o)                                                                                          \
  _Pragma("unroll") for (int u = 0; u < 2; u++) {                                                            \
    uint32_t v_[4];                                                                                          \
    _Pragma("unroll") for (int j = 0; j < 4; j++) v_[j] = lop_select(o[2 * j + u], parm, vword == j);        \
    st_rlx128(ofr + ((H) >> 1) * 1024 + u * 64 + ((((H) & 1) * 4 + t) ^ g), v_[0], v_[1], v_[2], v_[3]);     \
  }
    uint32_t gf[32], ao[16];
    const uint32_t parm = 0u - par, vword = ((t ^ g) & 1) == (g >> 2) ? g & 3 : 4;
    const float rh0 = 0.5f * st0.y, rh1 = 0.5f * st1.y, mh0 = st0.x * rh0, mh1 = st1.x * rh1;
#define GATE_LD(J) ldsm4(sb + ((J) >> 2 ? SM_X1 : SM_X0) + sw128 + (((((J) & 3) * 2 + hi16) ^ x128) << 4), gf[4 * (J)], gf[4 * (J) + 1], gf[4 * (J) + 2], gf[4 * (J) + 3])
#define GATE(I0, I1)                                                                                         \
  _Pragma("unroll") for (int i = (I0); i < (I1); i++) {                                                      \
    const float rs = (i & 1) ? rh1 : rh0, mh = (i & 1) ? mh1 : mh0;                                          \
    const float h0 = fmaf(bf_lo(gf[i]), rs, mh), h1 = fmaf(bf_hi(gf[i]), rs, mh);                            \
    gf[i] = pack2(fmaf(h0, tanh_approx(h0), h0), fmaf(h1, tanh_approx(h1), h1));                             \
  }
#define GATE_PIN(I0, I1) do { uint32_t o_ = 0; _Pragma("unroll") for (int i = (I0); i < (I1); i++) o_ |= gf[i]; SCHED_PIN(__uint_as_float(o_)); } while (0)
    {
      float p[64], na[40], nb[40];
      uint32_t fa[16], fb[16];
      {
        uint32_t nq[4] = {0u, 0u, 0u, 0u};
        PHI_PROJ(p, q, 0, 2);
        SCHED_FENCE();
        PHI_PROJ(p, q, 2, 4);
        const bool unsafe = softmax_unsafe(nq, c0 * c0 * wn, c1 * c1 * wn);
        if (TW == 0) mbar_wait(bar + B_TILE, 0);
        wg_wait<0>();
        reg_fence<64>(p);
        PROFC(24);
        if (__builtin_expect(unsafe, 0)) softmax_shift(p, c0, c1);
      }
      float dn[32];
#define DN_PART(A, B)                                                                                        \
  do {                                                                                                       \
    wg_fence();                                                                                              \
    _Pragma("unroll") for (int i = (A); i < (B); i++)                                                        \
      wgmma_n8_ss_ta1_tb1(dn + 4 * (i >> 1), mkdesc(sb + (i >> 3) * Q_STAGE + (i & 7) * 2048, 16, 1024, 1, wg * (2 * Q_STAGE / 16)), \
                          mkdesc(sb + SM_HT + (i & 1) * 256, 128, 128, 0), i & 1);                           \
  } while (0)
#define F_PIN(F, A, B) do { uint32_t o_ = 0; _Pragma("unroll") for (int i = (A); i < (B); i++) o_ |= F[8 + i]; SCHED_PIN(__uint_as_float(o_)); } while (0)
#define RMMA(J, A, ACCUM)                                                                                    \
  do {                                                                                                       \
    wg_fence();                                                                                              \
    _Pragma("unroll") for (int k = 0; k < 4; k++)                                                            \
      wgmma_n128_rs_ta0_tb1(q, (A)[4 * k], (A)[4 * k + 1], (A)[4 * k + 2], (A)[4 * k + 3],                   \
                            mkdesc(sb + 16384 + k * 2048, 8192, 1024, 1, ((J) & 3) * (Q_STAGE / 16)), k ? 1 : (ACCUM)); \
    wg_commit();                                                                                             \
  } while (0)
#define RSTEP(J, A, ACCUM) do { QWAIT(J); RMMA(J, A, ACCUM); } while (0)
      PROFC(4);
      q_exp(p, c0, c1, fa);
      if (TW == 1) { F_PIN(fa, 0, 8); mbar_wait(bar + B_TILE, 0); }
      if (TW == 2) { q_exp(p + 16, c0, c1, fb); F_PIN(fb, 0, 8); mbar_wait(bar + B_TILE, 0); }
      O_MMA(0, fa, na);
      if (TW != 2) q_exp(p + 16, c0, c1, fb);
      O_MMA(1, fb, nb);
      PROFC(25);
      wg_wait<1>();
      O_FIN(0, na, ao);
      O_STG(0, ao);
      wg_wait<0>();
      O_FIN(1, nb, (ao + 8));
      O_STG(1, (ao + 8));
      PROFC(28);
      RSTEP(16, ao, 0);
      SCHED_FENCE();
      q_exp(p + 32, c0, c1, fa);
      F_PIN(fa, 0, 8);
      mbar_wait(bar + B_H, 0);
      mbar_wait(bar + B_DN, 0);
      PROFC(45);
      DN_PART(0, 4);
      SCHED_FENCE();
      q_exp<0, 2>(p + 48, c0, c1, fb);
      F_PIN(fb, 0, 2);
      DN_PART(4, 8);
      SCHED_FENCE();
      q_exp<2, 4>(p + 48, c0, c1, fb);
      F_PIN(fb, 2, 4);
      DN_PART(8, 12);
      SCHED_FENCE();
      q_exp<4, 6>(p + 48, c0, c1, fb);
      F_PIN(fb, 4, 6);
      DN_PART(12, 16);
      wg_commit();
      SCHED_FENCE();
      q_exp<6, 8>(p + 48, c0, c1, fb);
      F_PIN(fb, 6, 8);
      wg_wait<0>();
      reg_fence<32>(dn);
      if (lane == 0) mbar_arrive(bar + B_DND);
      QREL(16);
#pragma unroll
      for (int i = 0; i < 4; i++) yp[i] = t & 2 ? (t & 1 ? dn[24 + 2 * i] : dn[16 + 2 * i]) : (t & 1 ? dn[8 + 2 * i] : dn[2 * i]);
      PROFC(29);
      mbar_wait(bar + B_TILE + 8, 0);
      PROFC(23);
      if (bid < NFFN) {
        float* y = g_y[par ^ 1][bid & 7] + wg * 512 + t * 128 + w * 16 + g;
#pragma unroll
        for (int i = 0; i < 4; i++) red1(y + (i >> 1) * 64 + (i & 1) * 8, yp[i]);
      }
      SCHED_FENCE();
      O_MMA(2, fa, na);
      O_MMA(3, fb, nb);
      __syncwarp();
      if (lane == 0) mbar_arrive(bar + B_YD);
      wg_wait<1>();
      O_FIN(2, na, ao);
      O_STG(2, ao);
      wg_wait<0>();
      O_FIN(3, nb, (ao + 8));
      O_STG(3, (ao + 8));
      PROFC(6);
    }
    RSTEP(17, ao, 1);
    SCHED_FENCE();
    GATE_LD(0); GATE_LD(1);
    GATE(0, 4);
    GATE_PIN(0, 4);
#define GSTEP(J, I) do { QNEXT(J); if ((I) < 7) GATE_LD(((I) + 1) & 7); GATE(4 * (I), 4 * (I) + 4); GATE_PIN(4 * (I), 4 * (I) + 4); } while (0)
    GSTEP(18, 1); GSTEP(19, 2); GSTEP(20, 3); GSTEP(21, 4); GSTEP(22, 5); GSTEP(23, 6); GSTEP(24, 7);
#pragma unroll 1
    for (int j = 25; j < 32 - TAILN; j++) QPLAIN(j);
    if (wg == 1) bar_sync(6, 256);
#pragma unroll 1
    for (int j = 32 - TAILN; j < 32; j++) QSTEP_A(j, (j & 3) * (Q_STAGE / 16), 1);
    if (wg == 0) asm volatile("bar.arrive 6, 256;" ::: "memory");
    mbar_wait(bar + B_UPD, 0);
    {
      const int sel = __float_as_int(lds32(sb + SM_UPD + 256)) - (wg * 64 + w * 16 + g);
      if (sel == 0 || sel == 8) {
#pragma unroll
        for (int j = 0; j < 16; j++) {
          const uint32_t u = __float_as_uint(lds32(sb + SM_UPD + j * 16 + t * 4));
          if (sel) gf[2 * j + 1] = u; else gf[2 * j] = u;
        }
      }
      __syncwarp();
      uint32_t xf[32];
#pragma unroll
      for (int j = 0; j < 8; j++)
        ldsm4(sb + (j >> 2 ? SM_X1 : SM_X0) + sw128 + ((((j & 3) * 2 + hi16) ^ x128) << 4), xf[4 * j], xf[4 * j + 1], xf[4 * j + 2], xf[4 * j + 3]);
      wg_wait<0>();
      reg_fence<64>(q);
      PROFC(8);
#pragma unroll
      for (int j = 0; j < 8; j++) {
        uint32_t o[4];
#pragma unroll
        for (int i = 0; i < 4; i++) o[i] = badd2(xf[4 * j + i], bmul2(pack2(q[8 * j + 2 * i], q[8 * j + 2 * i + 1]), gf[4 * j + i]));
        stsm4(sb + (j >> 2 ? SM_X1 : SM_X0) + sw128 + ((((j & 3) * 2 + hi16) ^ x128) << 4), o[0], o[1], o[2], o[3]);
      }
    }
    fence_async_smem();
    bar_sync(2 + wg, 128);
    if (w == 0 && elect_one()) {
      tma_store2d(&mOut, sb + SM_X0 + wg * 8192, hg * 128, mb * 128 + wg * 64);
      tma_store2d(&mOut, sb + SM_X1 + wg * 8192, hg * 128 + 64, mb * 128 + wg * 64);
      bulk_commit();
      bulk_wait_read0();
      if (wg == 1) { PROF(9); PROFT(33); PROF_DUMP; }
    }
  }
}

typedef CUresult (*EncodeFn)(CUtensorMap*, CUtensorMapDataType, cuuint32_t, void*, const cuuint64_t*, const cuuint64_t*, const cuuint32_t*,
                             const cuuint32_t*, CUtensorMapInterleave, CUtensorMapSwizzle, CUtensorMapL2promotion, CUtensorMapFloatOOBfill);

CUtensorMap make_map(EncodeFn enc, const void* ptr, int rank, const cuuint64_t* dims, const cuuint64_t* strides, const cuuint32_t* box, CUtensorMapSwizzle sw) {
  CUtensorMap m;
  const cuuint32_t es[5] = {1, 1, 1, 1, 1};
  enc(&m, CU_TENSOR_MAP_DATA_TYPE_BFLOAT16, rank, (void*)ptr, dims, strides, box, es, CU_TENSOR_MAP_INTERLEAVE_NONE, sw,
      CU_TENSOR_MAP_L2_PROMOTION_L2_128B, CU_TENSOR_MAP_FLOAT_OOB_FILL_NONE);
  return m;
}

}

extern "C" void kernel_launch(void* const* d_in, const int* in_sizes, int n_in, void* d_out, int out_size) {
  static EncodeFn enc = nullptr;
  static int by_sm = 0;
  if (!enc) {
    void* fn = nullptr;
    cudaDriverEntryPointQueryResult qr;
    cudaGetDriverEntryPoint("cuTensorMapEncodeTiled", &fn, cudaEnableDefault, &qr);
    enc = (EncodeFn)fn;
    cudaFuncSetAttribute(fused_kernel<false>, cudaFuncAttributeMaxDynamicSharedMemorySize, SM_TOTAL);
    cudaFuncSetAttribute(fused_kernel<true>, cudaFuncAttributeMaxDynamicSharedMemorySize, SM_TOTAL);
    int dev = 0, sms = 0;
    cudaGetDevice(&dev);
    cudaDeviceGetAttribute(&sms, cudaDevAttrMultiProcessorCount, dev);
    by_sm = BY_SM && sms == NCTA + NSPARE;
  }
  Params P;
  P.x = (const __nv_bfloat16*)d_in[0];
  P.wqkv = (const __nv_bfloat16*)d_in[1];
  const void* wphi = d_in[2];
  P.wo = (const __nv_bfloat16*)d_in[3];
  P.w_r = (const __nv_bfloat16*)d_in[5];
  P.w_gate = (const __nv_bfloat16*)d_in[6];
  P.w_up = (const __nv_bfloat16*)d_in[7];
  P.w_down = (const __nv_bfloat16*)d_in[8];

  const cuuint64_t dX[2] = {DM, SEQ}, sX[1] = {DM * 2};
  const cuuint32_t b128[2] = {64, 128}, b64[2] = {64, 64};
  const cuuint64_t dW[4] = {64, DM, 16, 3}, sW[3] = {3 * DM * 2, 128, DM * 2};
  const cuuint32_t bKV[4] = {64, 64, 2, 2}, bQ[4] = {64, 64, 2, 1};
  const cuuint64_t dO[3] = {64, DM, 16}, sO[2] = {DM * 2, 128};
  const cuuint32_t bO[3] = {64, 64, 2};
  const cuuint64_t dP[2] = {32, 1024}, sP[1] = {64};
  const cuuint32_t bP[2] = {32, 128};
  CUtensorMap mX = make_map(enc, P.x, 2, dX, sX, b128, CU_TENSOR_MAP_SWIZZLE_128B);
  CUtensorMap mWkv = make_map(enc, P.wqkv, 4, dW, sW, bKV, CU_TENSOR_MAP_SWIZZLE_128B);
  CUtensorMap mWq = make_map(enc, P.wqkv, 4, dW, sW, bQ, CU_TENSOR_MAP_SWIZZLE_128B);
  CUtensorMap mWo = make_map(enc, P.wo, 3, dO, sO, bO, CU_TENSOR_MAP_SWIZZLE_128B);
  CUtensorMap mPhi = make_map(enc, wphi, 2, dP, sP, bP, CU_TENSOR_MAP_SWIZZLE_64B);
  const cuuint64_t dWp[5] = {DM, 2, 4, 4, DM / 32}, sWp[4] = {DM * 2, 8 * DM * 2, 2 * DM * 2, 32 * DM * 2};
  const cuuint32_t bWp[5] = {64, 2, 4, 4, 2};
  CUtensorMap mWp = make_map(enc, P.wo, 5, dWp, sWp, bWp, CU_TENSOR_MAP_SWIZZLE_128B);
  CUtensorMap mOut = make_map(enc, d_out, 2, dX, sX, b64, CU_TENSOR_MAP_SWIZZLE_128B);
  const cuuint64_t dWc[2] = {3 * DM, DM}, sWc[1] = {3 * DM * 2}, dG[2] = {FF, DM}, sG[1] = {FF * 2}, dD[3] = {64, FF, 16};
  const cuuint32_t b32[2] = {32, 32}, bD[3] = {64, 32, 4};
  CUtensorMap mWc = make_map(enc, P.wqkv, 2, dWc, sWc, b32, CU_TENSOR_MAP_SWIZZLE_NONE);
  CUtensorMap mG = make_map(enc, P.w_gate, 2, dG, sG, b32, CU_TENSOR_MAP_SWIZZLE_NONE);
  CUtensorMap mU = make_map(enc, P.w_up, 2, dG, sG, b32, CU_TENSOR_MAP_SWIZZLE_NONE);
  CUtensorMap mD = make_map(enc, P.w_down, 3, dD, sO, bD, CU_TENSOR_MAP_SWIZZLE_128B);
  const cuuint64_t dXs[3] = {256, SEQ, 4}, sXs[2] = {DM * 2, 512};
  const cuuint32_t bXs[3] = {256, 16, 2};
  CUtensorMap mXs = make_map(enc, P.x, 3, dXs, sXs, bXs, CU_TENSOR_MAP_SWIZZLE_NONE);
  const cuuint64_t dG2[4] = {64, DM, FF / 64, 1}, sG2[3] = {FF * 2, 128, (cuuint64_t)FF * DM * 2};
  CUtensorMap mG2 = make_map(enc, P.w_gate, 4, dG2, sG2, bQ, CU_TENSOR_MAP_SWIZZLE_128B);
  CUtensorMap mU2 = make_map(enc, P.w_up, 4, dG2, sG2, bQ, CU_TENSOR_MAP_SWIZZLE_128B);
  (by_sm ? fused_kernel<true> : fused_kernel<false>)<<<NCTA + NSPARE, 384, SM_TOTAL, cudaStreamPerThread>>>(mX, mWkv, mWq, mWo, mPhi, mWp, mOut, mWc, mG, mU, mD, mXs,
                                                                                                           mG2, mU2, P);
}
```

```cpp
#include <cuda_runtime.h>
#include <cuda_bf16.h>
#include <cuda.h>
#include <stdint.h>

namespace {

constexpr int SEQ = 2048, DM = 1024, FF = 3584;
constexpr int NCTA = 128;
constexpr int NSPARE = 4;
constexpr int NFFN = FF / 32;
#define GN 6
#define G8 2
constexpr int GROWS = (3 * GN + G8) * 32;
#define TAILN 2
#define KTAIL 1
#define XS_EARLY 1
#define PF_FIRST 2
#define PF_W 5
#define PF_PRE 1
#define PFG 0
#define PFD 80
#define BY_SM 1
#define PTAB 0x73216540u
#define ROWSPLIT 1
#define WOT 1
#define PSPLIT 1
#define KSTEPS 4
#define NOVAL 0
#define KCH 1
#define REG_C 224
#define REG_H 56
#define TW 1
#define FENCE_KIND 2
#define SP_DELAY 3000
#define ORDER_ALL 1
#define AM_NS 100
constexpr bool FFN_OFF = false;

static_assert(2 * REG_C + REG_H <= 3 * 168, "the register pool of the CTA is 384 x 168");

__device__ uint32_t g_epoch[(NCTA + NSPARE) * 32];
__device__ unsigned long long g_stat[SEQ];
__device__ __align__(128) unsigned long long g_best[NCTA];
__device__ __align__(16) float g_y[2][8][DM];
__device__ __align__(128) uint32_t g_ycnt[64];
__device__ __align__(128) uint32_t g_xcnt[8 * 64];
__device__ __align__(128) uint4 g_res[2][32 * 256];
__device__ __align__(16) float g_cs[5 * DM];
__device__ __align__(128) float g_gp[2 * FF];
__device__ uint4 g_part[8 * 2 * 16 * 16 * 32];
__device__ __align__(16) float g_zpart[8 * 2 * 16 * 16 * 8];
__device__ __align__(128) float g_zres[32 * 64];
__device__ __align__(1024) uint4 g_ofr[16 * 16 * 1024];
#define PROF(i)
#define PROFT(i)
#define PROFC(i)
#define PROF_DUMP
#define PW0(J)
#define PW1(J)

constexpr uint32_t KV_STAGE = 49152, Q_STAGE = 32768;
constexpr uint32_t SM_V = 147456;
constexpr uint32_t SM_PHI = 163840;
constexpr uint32_t SM_XST = 147456;
constexpr uint32_t SM_FST = 172032;
constexpr uint32_t SM_PST0 = 196608, SM_PST1 = SM_PHI + 8192;
constexpr uint32_t SM_X0 = 131072, SM_X1 = SM_PHI + 16384;
constexpr uint32_t SM_WPHI = 204800;
constexpr uint32_t SM_ZT = 212992;
constexpr uint32_t SM_SDT = 217088;
constexpr uint32_t SM_CST = 219136;
constexpr uint32_t SM_HT = 222720;
constexpr uint32_t SM_STAT = 223232;
constexpr uint32_t SM_XSEL = 224256;
constexpr uint32_t SM_RED = 228352;
constexpr uint32_t SM_ROWS = SM_RED + 832;
constexpr uint32_t SM_GRED = SM_XSEL + 3072;
static_assert(GROWS <= 768, "xsel area");
constexpr uint32_t SM_UPD = 229632;
constexpr uint32_t SM_BAR = 230016;
constexpr uint32_t SM_PROF = 230464;
constexpr uint32_t SM_SINK = 231104;
constexpr uint32_t SM_TOTAL = 231616;
constexpr uint32_t SB = 1024;
constexpr uint32_t B_FULLKV = 0  , B_FST = 24  , B_XFULL = 88  , B_XST = 104  , B_WPHI = 120, B_CS = 128, B_CSQ = 136, B_UPD = 144,
                   B_H = 152, B_DN = 160, B_XS = 168, B_TILE = 176  , B_RES = 192  , B_PART = 208  ,
B_AIN = 224  ,
                   B_FULLQ = 288  ,
                   B_FFN = 320,
                   B_EMPTYKV = 328  , B_EMPTYQ = 352  , B_KVST = 384  , B_YD = 400, B_PHI = 408  , B_DND = 424, B_END = 432;

__device__ __forceinline__ uint32_t smem_u32(const void* p) { return (uint32_t)__cvta_generic_to_shared(p); }
__device__ __forceinline__ void mbar_init(uint32_t bar, uint32_t cnt) { asm volatile("mbarrier.init.shared::cta.b64 [%0], %1;" ::"r"(bar), "r"(cnt) : "memory"); }
__device__ __forceinline__ void mbar_expect_tx(uint32_t bar, uint32_t bytes) { asm volatile("mbarrier.arrive.expect_tx.shared::cta.b64 _, [%0], %1;" ::"r"(bar), "r"(bytes) : "memory"); }
__device__ __forceinline__ void mbar_arrive2(uint32_t bar) { asm volatile("mbarrier.arrive.shared::cta.b64 _, [%0], 2;" ::"r"(bar) : "memory"); }
__device__ __forceinline__ void mbar_arrive(uint32_t bar) { asm volatile("mbarrier.arrive.shared::cta.b64 _, [%0];" ::"r"(bar) : "memory"); }
__device__ __forceinline__ void mbar_wait(uint32_t bar, uint32_t parity) {
  asm volatile("{\n.reg .pred p;\nLW:\nmbarrier.try_wait.parity.shared::cta.b64 p, [%0], %1;\n@!p bra LW;\n}" ::"r"(bar), "r"(parity) : "memory");
}
__device__ __forceinline__ bool mbar_test(uint32_t bar, uint32_t parity) {
  uint32_t ok;
  asm volatile("{\n.reg .pred p;\nmbarrier.test_wait.parity.shared::cta.b64 p, [%1], %2;\nselp.u32 %0, 1, 0, p;\n}" : "=r"(ok) : "r"(bar), "r"(parity) : "memory");
  return ok;
}
__device__ __forceinline__ int lane_id() { int l; asm volatile("mov.u32 %0, %%laneid;" : "=r"(l)); return l; }
template <int C> __device__ __forceinline__ void sched_fence_(int zero) {
  asm volatile("{\n.reg .pred p;\nsetp.eq.s32 p, %0, %1;\n@p trap;\n}" ::"r"(zero), "n"(C) : "memory");
}
#define SCHED_FENCE() sched_fence_<1000 + __COUNTER__>(zero)
#define SCHED_PIN(V) sched_fence_<1000 + __COUNTER__>(zero & __float_as_int(V))
__device__ __forceinline__ bool elect_one() {
  uint32_t p; asm volatile("{ .reg .pred P; elect.sync _|P, 0xffffffff; selp.u32 %0, 1, 0, P; }" : "=r"(p)); return p;
}
__device__ __forceinline__ void tma2d(uint32_t dst, const CUtensorMap* m, int x, int y, uint32_t bar) {
  asm volatile("cp.async.bulk.tensor.2d.shared::cluster.global.mbarrier::complete_tx::bytes [%0], [%1, {%3, %4}], [%2];" ::"r"(dst), "l"(m), "r"(bar), "r"(x), "r"(y) : "memory");
}
__device__ __forceinline__ void tma3d(uint32_t dst, const CUtensorMap* m, int x, int y, int z, uint32_t bar) {
  asm volatile("cp.async.bulk.tensor.3d.shared::cluster.global.mbarrier::complete_tx::bytes [%0], [%1, {%3, %4, %5}], [%2];" ::"r"(dst), "l"(m), "r"(bar), "r"(x), "r"(y), "r"(z) : "memory");
}
__device__ __forceinline__ void tma4d(uint32_t dst, const CUtensorMap* m, int x, int y, int z, int w, uint32_t bar) {
  asm volatile("cp.async.bulk.tensor.4d.shared::cluster.global.mbarrier::complete_tx::bytes [%0], [%1, {%3, %4, %5, %6}], [%2];" ::"r"(dst), "l"(m), "r"(bar), "r"(x), "r"(y), "r"(z), "r"(w) : "memory");
}
__device__ __forceinline__ void tma5d(uint32_t dst, const CUtensorMap* m, int x, int v, uint32_t bar) {
  asm volatile("cp.async.bulk.tensor.5d.shared::cluster.global.mbarrier::complete_tx::bytes [%0], [%1, {%3, %5, %5, %5, %4}], [%2];" ::"r"(dst), "l"(m), "r"(bar), "r"(x), "r"(v), "r"(0) : "memory");
}
__device__ __forceinline__ void tma_store2d(const CUtensorMap* m, uint32_t src, int x, int y) {
  asm volatile("cp.async.bulk.tensor.2d.global.shared::cta.bulk_group [%0, {%2, %3}], [%1];" ::"l"(m), "r"(src), "r"(x), "r"(y) : "memory");
}
__device__ __forceinline__ void bulk_load(uint32_t dst, const void* src, uint32_t bytes, uint32_t bar) {
  asm volatile("cp.async.bulk.shared::cluster.global.mbarrier::complete_tx::bytes [%0], [%1], %2, [%3];" ::"r"(dst), "l"(src), "r"(bytes), "r"(bar) : "memory");
}
__device__ __forceinline__ void bulk_commit() { asm volatile("cp.async.bulk.commit_group;" ::: "memory"); }
__device__ __forceinline__ void bulk_wait0() { asm volatile("cp.async.bulk.wait_group 0;" ::: "memory"); }
__device__ __forceinline__ void bulk_wait_read0() { asm volatile("cp.async.bulk.wait_group.read 0;" ::: "memory"); }
__device__ __forceinline__ void prefetch_l2(const void* p) { asm volatile("prefetch.global.L2 [%0];" ::"l"(p) : "memory"); }
__device__ __forceinline__ void touch_l2(const void* p, int lane) { asm volatile("cp.async.cg.shared.global.L2::128B [%0], [%1], 16;" ::"r"(SB + SM_SINK + lane * 16), "l"(p) : "memory"); }
__device__ __forceinline__ void cp_async16(uint32_t dst, const void* src) { asm volatile("cp.async.cg.shared.global [%0], [%1], 16;" ::"r"(dst), "l"(src) : "memory"); }
__device__ __forceinline__ void prefetch_map(const CUtensorMap* m) { asm volatile("prefetch.tensormap [%0];" ::"l"(m) : "memory"); }
__device__ __forceinline__ void fence_async_smem() { asm volatile("fence.proxy.async.shared::cta;" ::: "memory"); }
__device__ __forceinline__ void fence_async_global() { asm volatile("fence.proxy.async.global;" ::: "memory"); }
__device__ __forceinline__ void bar_sync(int id, int n) { asm volatile("bar.sync %0, %1;" ::"r"(id), "r"(n) : "memory"); }
__device__ __forceinline__ void wg_fence() { asm volatile("wgmma.fence.sync.aligned;" ::: "memory"); }
__device__ __forceinline__ void wg_commit() { asm volatile("wgmma.commit_group.sync.aligned;" ::: "memory"); }
template <int N> __device__ __forceinline__ void wg_wait() { asm volatile("wgmma.wait_group.sync.aligned %0;" ::"n"(N) : "memory"); }
template <int N> __device__ __forceinline__ void reg_fence(uint32_t* r) {
#pragma unroll
  for (int i = 0; i < N; i++) asm volatile("" : "+r"(r[i])::"memory");
}
template <int N> __device__ __forceinline__ void reg_fence(float* r) {
#pragma unroll
  for (int i = 0; i < N; i++) asm volatile("" : "+f"(r[i])::"memory");
}
__device__ __forceinline__ uint64_t mkdesc(uint32_t addr, uint32_t lbo, uint32_t sbo, uint32_t swz, uint32_t dyn = 0) {
  const uint32_t lo = ((addr >> 4) | ((lbo >> 4) << 16)) + dyn;
  const uint32_t hi = (sbo >> 4) | (swz << 30);
  uint64_t d;
  asm("mov.b64 %0, {%1, %2};" : "=l"(d) : "r"(lo), "r"(hi));
  return d;
}
__device__ __forceinline__ void stsm4(uint32_t addr, uint32_t a, uint32_t b, uint32_t c, uint32_t d) {
  asm volatile("stmatrix.sync.aligned.m8n8.x4.shared.b16 [%0], {%1, %2, %3, %4};" ::"r"(addr), "r"(a), "r"(b), "r"(c), "r"(d) : "memory");
}
__device__ __forceinline__ void ldsm4(uint32_t addr, uint32_t& a, uint32_t& b, uint32_t& c, uint32_t& d) {
  asm volatile("ldmatrix.sync.aligned.m8n8.x4.shared.b16 {%0, %1, %2, %3}, [%4];" : "=r"(a), "=r"(b), "=r"(c), "=r"(d) : "r"(addr) : "memory");
}
__device__ __forceinline__ uint32_t pack2(float lo, float hi) { uint32_t r; asm("cvt.rn.bf16x2.f32 %0, %1, %2;" : "=r"(r) : "f"(hi), "f"(lo)); return r; }
__device__ __forceinline__ uint32_t bsub2(uint32_t a, uint32_t b) { uint32_t r; asm("sub.rn.bf16x2 %0, %1, %2;" : "=r"(r) : "r"(a), "r"(b)); return r; }
__device__ __forceinline__ uint32_t badd2(uint32_t a, uint32_t b) { uint32_t r; asm("add.rn.bf16x2 %0, %1, %2;" : "=r"(r) : "r"(a), "r"(b)); return r; }
__device__ __forceinline__ uint32_t bmul2(uint32_t a, uint32_t b) { uint32_t r; asm("mul.rn.bf16x2 %0, %1, %2;" : "=r"(r) : "r"(a), "r"(b)); return r; }
__device__ __forceinline__ float bf_lo(uint32_t v) { return __uint_as_float(v << 16); }
__device__ __forceinline__ float bf_hi(uint32_t v) { return __uint_as_float(v & 0xffff0000u); }
__device__ __forceinline__ float bf_round(float v) { return bf_lo(pack2(v, 0.f)); }
__device__ __forceinline__ float ex2(float v) { float r; asm("ex2.approx.ftz.f32 %0, %1;" : "=f"(r) : "f"(v)); return r; }
__device__ __forceinline__ float rcp(float v) { float r; asm("rcp.approx.ftz.f32 %0, %1;" : "=f"(r) : "f"(v)); return r; }
__device__ __forceinline__ float sqrt_approx(float v) { float r; asm("sqrt.approx.f32 %0, %1;" : "=f"(r) : "f"(v)); return r; }
__device__ __forceinline__ float4 lds128(uint32_t a) { float4 v; asm volatile("ld.shared.v4.f32 {%0, %1, %2, %3}, [%4];" : "=f"(v.x), "=f"(v.y), "=f"(v.z), "=f"(v.w) : "r"(a) : "memory"); return v; }
__device__ __forceinline__ uint4 lds128u(uint32_t a) { uint4 v; asm volatile("ld.shared.v4.u32 {%0, %1, %2, %3}, [%4];" : "=r"(v.x), "=r"(v.y), "=r"(v.z), "=r"(v.w) : "r"(a) : "memory"); return v; }
__device__ __forceinline__ float2 lds64(uint32_t a) { float2 v; asm volatile("ld.shared.v2.f32 {%0, %1}, [%2];" : "=f"(v.x), "=f"(v.y) : "r"(a) : "memory"); return v; }
__device__ __forceinline__ float lds32(uint32_t a) { float v; asm volatile("ld.shared.f32 %0, [%1];" : "=f"(v) : "r"(a) : "memory"); return v; }
__device__ __forceinline__ void sts32(uint32_t a, float v) { asm volatile("st.shared.f32 [%0], %1;" ::"r"(a), "f"(v) : "memory"); }
__device__ __forceinline__ void sts64(uint32_t a, float x, float y) { asm volatile("st.shared.v2.f32 [%0], {%1, %2};" ::"r"(a), "f"(x), "f"(y) : "memory"); }
__device__ __forceinline__ void sts128(uint32_t a, float x, float y, float z, float w) { asm volatile("st.shared.v4.f32 [%0], {%1, %2, %3, %4};" ::"r"(a), "f"(x), "f"(y), "f"(z), "f"(w) : "memory"); }
__device__ __forceinline__ void sts64u(uint32_t a, uint32_t x, uint32_t y) { asm volatile("st.shared.v2.u32 [%0], {%1, %2};" ::"r"(a), "r"(x), "r"(y) : "memory"); }
__device__ __forceinline__ void sts128u(uint32_t a, uint32_t x, uint32_t y, uint32_t z, uint32_t w) { asm volatile("st.shared.v4.u32 [%0], {%1, %2, %3, %4};" ::"r"(a), "r"(x), "r"(y), "r"(z), "r"(w) : "memory"); }
__device__ __forceinline__ uint4 ldg_nc(const void* p) { uint4 v; asm volatile("ld.global.nc.L1::no_allocate.v4.u32 {%0, %1, %2, %3}, [%4];" : "=r"(v.x), "=r"(v.y), "=r"(v.z), "=r"(v.w) : "l"(p)); return v; }
__device__ __forceinline__ float4 ldg_cg4(const float* p) { float4 v; asm volatile("ld.global.cg.v4.f32 {%0, %1, %2, %3}, [%4];" : "=f"(v.x), "=f"(v.y), "=f"(v.z), "=f"(v.w) : "l"(p) : "memory"); return v; }
__device__ __forceinline__ uint32_t ld_acq(const uint32_t* p) { uint32_t v; asm volatile("ld.acquire.gpu.global.u32 %0, [%1];" : "=r"(v) : "l"(p) : "memory"); return v; }
__device__ __forceinline__ uint32_t ld_acq_cta(uint32_t a) { uint32_t v; asm volatile("ld.acquire.cta.shared.u32 %0, [%1];" : "=r"(v) : "r"(a) : "memory"); return v; }
__device__ __forceinline__ void st_rel_cta(uint32_t a, uint32_t v) { asm volatile("st.release.cta.shared.u32 [%0], %1;" ::"r"(a), "r"(v) : "memory"); }
__device__ __forceinline__ unsigned long long ld_rlx64(const unsigned long long* p) { unsigned long long v; asm volatile("ld.relaxed.gpu.global.u64 %0, [%1];" : "=l"(v) : "l"(p) : "memory"); return v; }
__device__ __forceinline__ void st_rlx64(unsigned long long* p, unsigned long long v) { asm volatile("st.relaxed.gpu.global.u64 [%0], %1;" ::"l"(p), "l"(v) : "memory"); }
__device__ __forceinline__ uint4 ld_rlx128(const void* p) {
  uint4 v;
  asm volatile("{ .reg .b128 t; .reg .b64 a, b; ld.relaxed.gpu.global.b128 t, [%4]; mov.b128 {a, b}, t; mov.b64 {%0, %1}, a; mov.b64 {%2, %3}, b; }"
               : "=r"(v.x), "=r"(v.y), "=r"(v.z), "=r"(v.w) : "l"(p) : "memory");
  return v;
}
__device__ __forceinline__ void st_rlx128(void* p, uint32_t x, uint32_t y, uint32_t z, uint32_t w) {
  asm volatile("{ .reg .b128 t; .reg .b64 a, b; mov.b64 a, {%1, %2}; mov.b64 b, {%3, %4}; mov.b128 t, {a, b}; st.relaxed.gpu.global.b128 [%0], t; }"
               ::"l"(p), "r"(x), "r"(y), "r"(z), "r"(w) : "memory");
}
__device__ __forceinline__ void stg128(void* p, uint32_t x, uint32_t y, uint32_t z, uint32_t w) { asm volatile("st.global.v4.u32 [%0], {%1, %2, %3, %4};" ::"l"(p), "r"(x), "r"(y), "r"(z), "r"(w) : "memory"); }
__device__ __forceinline__ void st_rlx(void* p, uint32_t v) { asm volatile("st.relaxed.gpu.global.u32 [%0], %1;" ::"l"(p), "r"(v) : "memory"); }
__device__ __forceinline__ uint32_t lop_select(uint32_t a, uint32_t b, uint32_t m) { uint32_t r; asm("lop3.b32 %0, %1, %2, %3, 0xd8;" : "=r"(r) : "r"(a), "r"(b), "r"(m)); return r; }
__device__ __forceinline__ float unmark(uint32_t v) { return __uint_as_float(v & ~1u); }
__device__ __forceinline__ uint32_t mark(uint32_t v, uint32_t par) { return (v & ~1u) | par; }
__device__ __forceinline__ float tanh_approx(float v) { float r; asm("tanh.approx.f32 %0, %1;" : "=f"(r) : "f"(v)); return r; }
__device__ __forceinline__ void flag_rel(uint32_t* p, uint32_t v) { asm volatile("red.release.gpu.global.max.u32 [%0], %1;" ::"l"(p), "r"(v) : "memory"); }
__device__ __forceinline__ void red1(float* p, float a) { asm volatile("red.global.add.f32 [%0], %1;" ::"l"(p), "f"(a) : "memory"); }
__device__ __forceinline__ void red_inc(uint32_t* p) { asm volatile("red.relaxed.gpu.global.add.u32 [%0], 1;" ::"l"(p) : "memory"); }
__device__ __forceinline__ void red_rel(uint32_t* p) { asm volatile("red.release.gpu.global.add.u32 [%0], 1;" ::"l"(p) : "memory"); }
__device__ __forceinline__ void red4(float* p, float a, float b, float c, float d) { asm volatile("red.global.add.v4.f32 [%0], {%1, %2, %3, %4};" ::"l"(p), "f"(a), "f"(b), "f"(c), "f"(d) : "memory"); }
constexpr int SPIN_MAX = 100000;
__device__ __forceinline__ uint32_t ld_rlx(const uint32_t* p) { uint32_t v; asm volatile("ld.relaxed.gpu.global.u32 %0, [%1];" : "=r"(v) : "l"(p) : "memory"); return v; }
template <int NS = 0> __device__ __forceinline__ void wait_hint(const uint32_t* p, uint32_t target) {
#pragma unroll 1
  for (int i = 0; i < SPIN_MAX; i++) { if ((int)(ld_rlx(p) - target) >= 0) break; if (NS) __nanosleep(NS); }
}
template <int NS> __device__ __forceinline__ void wait_cnt(const uint32_t* p, uint32_t target) {
#pragma unroll 1
  for (int i = 0; i < SPIN_MAX; i++) { if ((int)(ld_rlx(p) - target) >= 0) break; if (NS) __nanosleep(NS); }
  (void)ld_acq(p);
}
template <int NS> __device__ __forceinline__ unsigned long long wait_tag(const unsigned long long* p, uint32_t tag) {
  unsigned long long v = 0;
#pragma unroll 1
  for (int i = 0; i < SPIN_MAX; i++) { v = ld_rlx64(p); if ((uint32_t)(v >> 32) == tag) break; if (NS) __nanosleep(NS); }
  return v;
}
__device__ __forceinline__ float silu_f(float v) { return v * rcp(1.f + ex2(-1.4426950408889634f * v)); }

__device__ __forceinline__ void wgmma_n8_ss_ta1_tb0(float* d, uint64_t da, uint64_t db, bool accumulate) {
  if (accumulate) {
    asm volatile("{\n.reg .pred p;\nsetp.ne.b32 p, 1, 0;\n"
      "wgmma.mma_async.sync.aligned.m64n8k16.f32.bf16.bf16 "
      "{%0, %1, %2, %3}, "
      "%4, %5, p, 1, 1, 1, 0;\n}\n"
      : "+f"(d[0]), "+f"(d[1]), "+f"(d[2]), "+f"(d[3])
      : "l"(da), "l"(db));
  } else {
    asm volatile("{\n.reg .pred p;\nsetp.ne.b32 p, 0, 0;\n"
      "wgmma.mma_async.sync.aligned.m64n8k16.f32.bf16.bf16 "
      "{%0, %1, %2, %3}, "
      "%4, %5, p, 1, 1, 1, 0;\n}\n"
      : "=f"(d[0]), "=f"(d[1]), "=f"(d[2]), "=f"(d[3])
      : "l"(da), "l"(db));
  }
}
__device__ __forceinline__ void wgmma_n8_ss_ta1_tb1(float* d, uint64_t da, uint64_t db, bool accumulate) {
  if (accumulate) {
    asm volatile("{\n.reg .pred p;\nsetp.ne.b32 p, 1, 0;\n"
      "wgmma.mma_async.sync.aligned.m64n8k16.f32.bf16.bf16 "
      "{%0, %1, %2, %3}, "
      "%4, %5, p, 1, 1, 1, 1;\n}\n"
      : "+f"(d[0]), "+f"(d[1]), "+f"(d[2]), "+f"(d[3])
      : "l"(da), "l"(db));
  } else {
    asm volatile("{\n.reg .pred p;\nsetp.ne.b32 p, 0, 0;\n"
      "wgmma.mma_async.sync.aligned.m64n8k16.f32.bf16.bf16 "
      "{%0, %1, %2, %3}, "
      "%4, %5, p, 1, 1, 1, 1;\n}\n"
      : "=f"(d[0]), "=f"(d[1]), "=f"(d[2]), "=f"(d[3])
      : "l"(da), "l"(db));
  }
}
__device__ __forceinline__ void wgmma_n32_rs_ta0_tb1(float* d, uint32_t a0, uint32_t a1, uint32_t a2, uint32_t a3, uint64_t db, bool accumulate) {
  if (accumulate) {
    asm volatile("{\n.reg .pred p;\nsetp.ne.b32 p, 1, 0;\n"
      "wgmma.mma_async.sync.aligned.m64n32k16.f32.bf16.bf16 "
      "{%0, %1, %2, %3, %4, %5, %6, %7, %8, %9, %10, %11, %12, %13, %14, %15}, "
      "{%16, %17, %18, %19}, %20, p, 1, 1, 1;\n}\n"
      : "+f"(d[0]), "+f"(d[1]), "+f"(d[2]), "+f"(d[3]), "+f"(d[4]), "+f"(d[5]), "+f"(d[6]), "+f"(d[7]), "+f"(d[8]), "+f"(d[9]), "+f"(d[10]), "+f"(d[11]), "+f"(d[12]), "+f"(d[13]), "+f"(d[14]), "+f"(d[15])
      : "r"(a0), "r"(a1), "r"(a2), "r"(a3), "l"(db));
  } else {
    asm volatile("{\n.reg .pred p;\nsetp.ne.b32 p, 0, 0;\n"
      "wgmma.mma_async.sync.aligned.m64n32k16.f32.bf16.bf16 "
      "{%0, %1, %2, %3, %4, %5, %6, %7, %8, %9, %10, %11, %12, %13, %14, %15}, "
      "{%16, %17, %18, %19}, %20, p, 1, 1, 1;\n}\n"
      : "=f"(d[0]), "=f"(d[1]), "=f"(d[2]), "=f"(d[3]), "=f"(d[4]), "=f"(d[5]), "=f"(d[6]), "=f"(d[7]), "=f"(d[8]), "=f"(d[9]), "=f"(d[10]), "=f"(d[11]), "=f"(d[12]), "=f"(d[13]), "=f"(d[14]), "=f"(d[15])
      : "r"(a0), "r"(a1), "r"(a2), "r"(a3), "l"(db));
  }
}
__device__ __forceinline__ void wgmma_n40_rs_ta0_tb1(float* d, uint32_t a0, uint32_t a1, uint32_t a2, uint32_t a3, uint64_t db, bool accumulate) {
  if (accumulate) {
    asm volatile("{\n.reg .pred p;\nsetp.ne.b32 p, 1, 0;\n"
      "wgmma.mma_async.sync.aligned.m64n40k16.f32.bf16.bf16 "
      "{%0, %1, %2, %3, %4, %5, %6, %7, %8, %9, %10, %11, %12, %13, %14, %15, %16, %17, %18, %19}, "
      "{%20, %21, %22, %23}, %24, p, 1, 1, 1;\n}\n"
      : "+f"(d[0]), "+f"(d[1]), "+f"(d[2]), "+f"(d[3]), "+f"(d[4]), "+f"(d[5]), "+f"(d[6]), "+f"(d[7]), "+f"(d[8]), "+f"(d[9]), "+f"(d[10]), "+f"(d[11]), "+f"(d[12]), "+f"(d[13]), "+f"(d[14]), "+f"(d[15]), "+f"(d[16]), "+f"(d[17]), "+f"(d[18]), "+f"(d[19])
      : "r"(a0), "r"(a1), "r"(a2), "r"(a3), "l"(db));
  } else {
    asm volatile("{\n.reg .pred p;\nsetp.ne.b32 p, 0, 0;\n"
      "wgmma.mma_async.sync.aligned.m64n40k16.f32.bf16.bf16 "
      "{%0, %1, %2, %3, %4, %5, %6, %7, %8, %9, %10, %11, %12, %13, %14, %15, %16, %17, %18, %19}, "
      "{%20, %21, %22, %23}, %24, p, 1, 1, 1;\n}\n"
      : "=f"(d[0]), "=f"(d[1]), "=f"(d[2]), "=f"(d[3]), "=f"(d[4]), "=f"(d[5]), "=f"(d[6]), "=f"(d[7]), "=f"(d[8]), "=f"(d[9]), "=f"(d[10]), "=f"(d[11]), "=f"(d[12]), "=f"(d[13]), "=f"(d[14]), "=f"(d[15]), "=f"(d[16]), "=f"(d[17]), "=f"(d[18]), "=f"(d[19])
      : "r"(a0), "r"(a1), "r"(a2), "r"(a3), "l"(db));
  }
}
__device__ __forceinline__ void wgmma_n40_ss_ta1_tb1(float* d, uint64_t da, uint64_t db, bool accumulate) {
  if (accumulate) {
    asm volatile("{\n.reg .pred p;\nsetp.ne.b32 p, 1, 0;\n"
      "wgmma.mma_async.sync.aligned.m64n40k16.f32.bf16.bf16 "
      "{%0, %1, %2, %3, %4, %5, %6, %7, %8, %9, %10, %11, %12, %13, %14, %15, %16, %17, %18, %19}, "
      "%20, %21, p, 1, 1, 1, 1;\n}\n"
      : "+f"(d[0]), "+f"(d[1]), "+f"(d[2]), "+f"(d[3]), "+f"(d[4]), "+f"(d[5]), "+f"(d[6]), "+f"(d[7]), "+f"(d[8]), "+f"(d[9]), "+f"(d[10]), "+f"(d[11]), "+f"(d[12]), "+f"(d[13]), "+f"(d[14]), "+f"(d[15]), "+f"(d[16]), "+f"(d[17]), "+f"(d[18]), "+f"(d[19])
      : "l"(da), "l"(db));
  } else {
    asm volatile("{\n.reg .pred p;\nsetp.ne.b32 p, 0, 0;\n"
      "wgmma.mma_async.sync.aligned.m64n40k16.f32.bf16.bf16 "
      "{%0, %1, %2, %3, %4, %5, %6, %7, %8, %9, %10, %11, %12, %13, %14, %15, %16, %17, %18, %19}, "
      "%20, %21, p, 1, 1, 1, 1;\n}\n"
      : "=f"(d[0]), "=f"(d[1]), "=f"(d[2]), "=f"(d[3]), "=f"(d[4]), "=f"(d[5]), "=f"(d[6]), "=f"(d[7]), "=f"(d[8]), "=f"(d[9]), "=f"(d[10]), "=f"(d[11]), "=f"(d[12]), "=f"(d[13]), "=f"(d[14]), "=f"(d[15]), "=f"(d[16]), "=f"(d[17]), "=f"(d[18]), "=f"(d[19])
      : "l"(da), "l"(db));
  }
}
__device__ __forceinline__ void wgmma_n128_rs_ta0_tb1(float* d, uint32_t a0, uint32_t a1, uint32_t a2, uint32_t a3, uint64_t db, bool accumulate) {
  if (accumulate) {
    asm volatile("{\n.reg .pred p;\nsetp.ne.b32 p, 1, 0;\n"
      "wgmma.mma_async.sync.aligned.m64n128k16.f32.bf16.bf16 "
      "{%0, %1, %2, %3, %4, %5, %6, %7, %8, %9, %10, %11, %12, %13, %14, %15, %16, %17, %18, %19, %20, %21, %22, %23, %24, %25, %26, %27, %28, %29, %30, %31, %32, %33, %34, %35, %36, %37, %38, %39, %40, %41, %42, %43, %44, %45, %46, %47, %48, %49, %50, %51, %52, %53, %54, %55, %56, %57, %58, %59, %60, %61, %62, %63}, "
      "{%64, %65, %66, %67}, %68, p, 1, 1, 1;\n}\n"
      : "+f"(d[0]), "+f"(d[1]), "+f"(d[2]), "+f"(d[3]), "+f"(d[4]), "+f"(d[5]), "+f"(d[6]), "+f"(d[7]), "+f"(d[8]), "+f"(d[9]), "+f"(d[10]), "+f"(d[11]), "+f"(d[12]), "+f"(d[13]), "+f"(d[14]), "+f"(d[15]), "+f"(d[16]), "+f"(d[17]), "+f"(d[18]), "+f"(d[19]), "+f"(d[20]), "+f"(d[21]), "+f"(d[22]), "+f"(d[23]), "+f"(d[24]), "+f"(d[25]), "+f"(d[26]), "+f"(d[27]), "+f"(d[28]), "+f"(d[29]), "+f"(d[30]), "+f"(d[31]), "+f"(d[32]), "+f"(d[33]), "+f"(d[34]), "+f"(d[35]), "+f"(d[36]), "+f"(d[37]), "+f"(d[38]), "+f"(d[39]), "+f"(d[40]), "+f"(d[41]), "+f"(d[42]), "+f"(d[43]), "+f"(d[44]), "+f"(d[45]), "+f"(d[46]), "+f"(d[47]), "+f"(d[48]), "+f"(d[49]), "+f"(d[50]), "+f"(d[51]), "+f"(d[52]), "+f"(d[53]), "+f"(d[54]), "+f"(d[55]), "+f"(d[56]), "+f"(d[57]), "+f"(d[58]), "+f"(d[59]), "+f"(d[60]), "+f"(d[61]), "+f"(d[62]), "+f"(d[63])
      : "r"(a0), "r"(a1), "r"(a2), "r"(a3), "l"(db));
  } else {
    asm volatile("{\n.reg .pred p;\nsetp.ne.b32 p, 0, 0;\n"
      "wgmma.mma_async.sync.aligned.m64n128k16.f32.bf16.bf16 "
      "{%0, %1, %2, %3, %4, %5, %6, %7, %8, %9, %10, %11, %12, %13, %14, %15, %16, %17, %18, %19, %20, %21, %22, %23, %24, %25, %26, %27, %28, %29, %30, %31, %32, %33, %34, %35, %36, %37, %38, %39, %40, %41, %42, %43, %44, %45, %46, %47, %48, %49, %50, %51, %52, %53, %54, %55, %56, %57, %58, %59, %60, %61, %62, %63}, "
      "{%64, %65, %66, %67}, %68, p, 1, 1, 1;\n}\n"
      : "=f"(d[0]), "=f"(d[1]), "=f"(d[2]), "=f"(d[3]), "=f"(d[4]), "=f"(d[5]), "=f"(d[6]), "=f"(d[7]), "=f"(d[8]), "=f"(d[9]), "=f"(d[10]), "=f"(d[11]), "=f"(d[12]), "=f"(d[13]), "=f"(d[14]), "=f"(d[15]), "=f"(d[16]), "=f"(d[17]), "=f"(d[18]), "=f"(d[19]), "=f"(d[20]), "=f"(d[21]), "=f"(d[22]), "=f"(d[23]), "=f"(d[24]), "=f"(d[25]), "=f"(d[26]), "=f"(d[27]), "=f"(d[28]), "=f"(d[29]), "=f"(d[30]), "=f"(d[31]), "=f"(d[32]), "=f"(d[33]), "=f"(d[34]), "=f"(d[35]), "=f"(d[36]), "=f"(d[37]), "=f"(d[38]), "=f"(d[39]), "=f"(d[40]), "=f"(d[41]), "=f"(d[42]), "=f"(d[43]), "=f"(d[44]), "=f"(d[45]), "=f"(d[46]), "=f"(d[47]), "=f"(d[48]), "=f"(d[49]), "=f"(d[50]), "=f"(d[51]), "=f"(d[52]), "=f"(d[53]), "=f"(d[54]), "=f"(d[55]), "=f"(d[56]), "=f"(d[57]), "=f"(d[58]), "=f"(d[59]), "=f"(d[60]), "=f"(d[61]), "=f"(d[62]), "=f"(d[63])
      : "r"(a0), "r"(a1), "r"(a2), "r"(a3), "l"(db));
  }
}
__device__ __forceinline__ void wgmma_n128_ss_ta0_tb1(float* d, uint64_t da, uint64_t db, bool accumulate) {
  if (accumulate) {
    asm volatile("{\n.reg .pred p;\nsetp.ne.b32 p, 1, 0;\n"
      "wgmma.mma_async.sync.aligned.m64n128k16.f32.bf16.bf16 "
      "{%0, %1, %2, %3, %4, %5, %6, %7, %8, %9, %10, %11, %12, %13, %14, %15, %16, %17, %18, %19, %20, %21, %22, %23, %24, %25, %26, %27, %28, %29, %30, %31, %32, %33, %34, %35, %36, %37, %38, %39, %40, %41, %42, %43, %44, %45, %46, %47, %48, %49, %50, %51, %52, %53, %54, %55, %56, %57, %58, %59, %60, %61, %62, %63}, "
      "%64, %65, p, 1, 1, 0, 1;\n}\n"
      : "+f"(d[0]), "+f"(d[1]), "+f"(d[2]), "+f"(d[3]), "+f"(d[4]), "+f"(d[5]), "+f"(d[6]), "+f"(d[7]), "+f"(d[8]), "+f"(d[9]), "+f"(d[10]), "+f"(d[11]), "+f"(d[12]), "+f"(d[13]), "+f"(d[14]), "+f"(d[15]), "+f"(d[16]), "+f"(d[17]), "+f"(d[18]), "+f"(d[19]), "+f"(d[20]), "+f"(d[21]), "+f"(d[22]), "+f"(d[23]), "+f"(d[24]), "+f"(d[25]), "+f"(d[26]), "+f"(d[27]), "+f"(d[28]), "+f"(d[29]), "+f"(d[30]), "+f"(d[31]), "+f"(d[32]), "+f"(d[33]), "+f"(d[34]), "+f"(d[35]), "+f"(d[36]), "+f"(d[37]), "+f"(d[38]), "+f"(d[39]), "+f"(d[40]), "+f"(d[41]), "+f"(d[42]), "+f"(d[43]), "+f"(d[44]), "+f"(d[45]), "+f"(d[46]), "+f"(d[47]), "+f"(d[48]), "+f"(d[49]), "+f"(d[50]), "+f"(d[51]), "+f"(d[52]), "+f"(d[53]), "+f"(d[54]), "+f"(d[55]), "+f"(d[56]), "+f"(d[57]), "+f"(d[58]), "+f"(d[59]), "+f"(d[60]), "+f"(d[61]), "+f"(d[62]), "+f"(d[63])
      : "l"(da), "l"(db));
  } else {
    asm volatile("{\n.reg .pred p;\nsetp.ne.b32 p, 0, 0;\n"
      "wgmma.mma_async.sync.aligned.m64n128k16.f32.bf16.bf16 "
      "{%0, %1, %2, %3, %4, %5, %6, %7, %8, %9, %10, %11, %12, %13, %14, %15, %16, %17, %18, %19, %20, %21, %22, %23, %24, %25, %26, %27, %28, %29, %30, %31, %32, %33, %34, %35, %36, %37, %38, %39, %40, %41, %42, %43, %44, %45, %46, %47, %48, %49, %50, %51, %52, %53, %54, %55, %56, %57, %58, %59, %60, %61, %62, %63}, "
      "%64, %65, p, 1, 1, 0, 1;\n}\n"
      : "=f"(d[0]), "=f"(d[1]), "=f"(d[2]), "=f"(d[3]), "=f"(d[4]), "=f"(d[5]), "=f"(d[6]), "=f"(d[7]), "=f"(d[8]), "=f"(d[9]), "=f"(d[10]), "=f"(d[11]), "=f"(d[12]), "=f"(d[13]), "=f"(d[14]), "=f"(d[15]), "=f"(d[16]), "=f"(d[17]), "=f"(d[18]), "=f"(d[19]), "=f"(d[20]), "=f"(d[21]), "=f"(d[22]), "=f"(d[23]), "=f"(d[24]), "=f"(d[25]), "=f"(d[26]), "=f"(d[27]), "=f"(d[28]), "=f"(d[29]), "=f"(d[30]), "=f"(d[31]), "=f"(d[32]), "=f"(d[33]), "=f"(d[34]), "=f"(d[35]), "=f"(d[36]), "=f"(d[37]), "=f"(d[38]), "=f"(d[39]), "=f"(d[40]), "=f"(d[41]), "=f"(d[42]), "=f"(d[43]), "=f"(d[44]), "=f"(d[45]), "=f"(d[46]), "=f"(d[47]), "=f"(d[48]), "=f"(d[49]), "=f"(d[50]), "=f"(d[51]), "=f"(d[52]), "=f"(d[53]), "=f"(d[54]), "=f"(d[55]), "=f"(d[56]), "=f"(d[57]), "=f"(d[58]), "=f"(d[59]), "=f"(d[60]), "=f"(d[61]), "=f"(d[62]), "=f"(d[63])
      : "l"(da), "l"(db));
  }
}
__device__ __forceinline__ void wgmma_n256_rs_ta0_tb1(float* d, uint32_t a0, uint32_t a1, uint32_t a2, uint32_t a3, uint64_t db, bool accumulate) {
  if (accumulate) {
    asm volatile("{\n.reg .pred p;\nsetp.ne.b32 p, 1, 0;\n"
      "wgmma.mma_async.sync.aligned.m64n256k16.f32.bf16.bf16 "
      "{%0, %1, %2, %3, %4, %5, %6, %7, %8, %9, %10, %11, %12, %13, %14, %15, %16, %17, %18, %19, %20, %21, %22, %23, %24, %25, %26, %27, %28, %29, %30, %31, %32, %33, %34, %35, %36, %37, %38, %39, %40, %41, %42, %43, %44, %45, %46, %47, %48, %49, %50, %51, %52, %53, %54, %55, %56, %57, %58, %59, %60, %61, %62, %63, %64, %65, %66, %67, %68, %69, %70, %71, %72, %73, %74, %75, %76, %77, %78, %79, %80, %81, %82, %83, %84, %85, %86, %87, %88, %89, %90, %91, %92, %93, %94, %95, %96, %97, %98, %99, %100, %101, %102, %103, %104, %105, %106, %107, %108, %109, %110, %111, %112, %113, %114, %115, %116, %117, %118, %119, %120, %121, %122, %123, %124, %125, %126, %127}, "
      "{%128, %129, %130, %131}, %132, p, 1, 1, 1;\n}\n"
      : "+f"(d[0]), "+f"(d[1]), "+f"(d[2]), "+f"(d[3]), "+f"(d[4]), "+f"(d[5]), "+f"(d[6]), "+f"(d[7]), "+f"(d[8]), "+f"(d[9]), "+f"(d[10]), "+f"(d[11]), "+f"(d[12]), "+f"(d[13]), "+f"(d[14]), "+f"(d[15]), "+f"(d[16]), "+f"(d[17]), "+f"(d[18]), "+f"(d[19]), "+f"(d[20]), "+f"(d[21]), "+f"(d[22]), "+f"(d[23]), "+f"(d[24]), "+f"(d[25]), "+f"(d[26]), "+f"(d[27]), "+f"(d[28]), "+f"(d[29]), "+f"(d[30]), "+f"(d[31]), "+f"(d[32]), "+f"(d[33]), "+f"(d[34]), "+f"(d[35]), "+f"(d[36]), "+f"(d[37]), "+f"(d[38]), "+f"(d[39]), "+f"(d[40]), "+f"(d[41]), "+f"(d[42]), "+f"(d[43]), "+f"(d[44]), "+f"(d[45]), "+f"(d[46]), "+f"(d[47]), "+f"(d[48]), "+f"(d[49]), "+f"(d[50]), "+f"(d[51]), "+f"(d[52]), "+f"(d[53]), "+f"(d[54]), "+f"(d[55]), "+f"(d[56]), "+f"(d[57]), "+f"(d[58]), "+f"(d[59]), "+f"(d[60]), "+f"(d[61]), "+f"(d[62]), "+f"(d[63]), "+f"(d[64]), "+f"(d[65]), "+f"(d[66]), "+f"(d[67]), "+f"(d[68]), "+f"(d[69]), "+f"(d[70]), "+f"(d[71]), "+f"(d[72]), "+f"(d[73]), "+f"(d[74]), "+f"(d[75]), "+f"(d[76]), "+f"(d[77]), "+f"(d[78]), "+f"(d[79]), "+f"(d[80]), "+f"(d[81]), "+f"(d[82]), "+f"(d[83]), "+f"(d[84]), "+f"(d[85]), "+f"(d[86]), "+f"(d[87]), "+f"(d[88]), "+f"(d[89]), "+f"(d[90]), "+f"(d[91]), "+f"(d[92]), "+f"(d[93]), "+f"(d[94]), "+f"(d[95]), "+f"(d[96]), "+f"(d[97]), "+f"(d[98]), "+f"(d[99]), "+f"(d[100]), "+f"(d[101]), "+f"(d[102]), "+f"(d[103]), "+f"(d[104]), "+f"(d[105]), "+f"(d[106]), "+f"(d[107]), "+f"(d[108]), "+f"(d[109]), "+f"(d[110]), "+f"(d[111]), "+f"(d[112]), "+f"(d[113]), "+f"(d[114]), "+f"(d[115]), "+f"(d[116]), "+f"(d[117]), "+f"(d[118]), "+f"(d[119]), "+f"(d[120]), "+f"(d[121]), "+f"(d[122]), "+f"(d[123]), "+f"(d[124]), "+f"(d[125]), "+f"(d[126]), "+f"(d[127])
      : "r"(a0), "r"(a1), "r"(a2), "r"(a3), "l"(db));
  } else {
    asm volatile("{\n.reg .pred p;\nsetp.ne.b32 p, 0, 0;\n"
      "wgmma.mma_async.sync.aligned.m64n256k16.f32.bf16.bf16 "
      "{%0, %1, %2, %3, %4, %5, %6, %7, %8, %9, %10, %11, %12, %13, %14, %15, %16, %17, %18, %19, %20, %21, %22, %23, %24, %25, %26, %27, %28, %29, %30, %31, %32, %33, %34, %35, %36, %37, %38, %39, %40, %41, %42, %43, %44, %45, %46, %47, %48, %49, %50, %51, %52, %53, %54, %55, %56, %57, %58, %59, %60, %61, %62, %63, %64, %65, %66, %67, %68, %69, %70, %71, %72, %73, %74, %75, %76, %77, %78, %79, %80, %81, %82, %83, %84, %85, %86, %87, %88, %89, %90, %91, %92, %93, %94, %95, %96, %97, %98, %99, %100, %101, %102, %103, %104, %105, %106, %107, %108, %109, %110, %111, %112, %113, %114, %115, %116, %117, %118, %119, %120, %121, %122, %123, %124, %125, %126, %127}, "
      "{%128, %129, %130, %131}, %132, p, 1, 1, 1;\n}\n"
      : "=f"(d[0]), "=f"(d[1]), "=f"(d[2]), "=f"(d[3]), "=f"(d[4]), "=f"(d[5]), "=f"(d[6]), "=f"(d[7]), "=f"(d[8]), "=f"(d[9]), "=f"(d[10]), "=f"(d[11]), "=f"(d[12]), "=f"(d[13]), "=f"(d[14]), "=f"(d[15]), "=f"(d[16]), "=f"(d[17]), "=f"(d[18]), "=f"(d[19]), "=f"(d[20]), "=f"(d[21]), "=f"(d[22]), "=f"(d[23]), "=f"(d[24]), "=f"(d[25]), "=f"(d[26]), "=f"(d[27]), "=f"(d[28]), "=f"(d[29]), "=f"(d[30]), "=f"(d[31]), "=f"(d[32]), "=f"(d[33]), "=f"(d[34]), "=f"(d[35]), "=f"(d[36]), "=f"(d[37]), "=f"(d[38]), "=f"(d[39]), "=f"(d[40]), "=f"(d[41]), "=f"(d[42]), "=f"(d[43]), "=f"(d[44]), "=f"(d[45]), "=f"(d[46]), "=f"(d[47]), "=f"(d[48]), "=f"(d[49]), "=f"(d[50]), "=f"(d[51]), "=f"(d[52]), "=f"(d[53]), "=f"(d[54]), "=f"(d[55]), "=f"(d[56]), "=f"(d[57]), "=f"(d[58]), "=f"(d[59]), "=f"(d[60]), "=f"(d[61]), "=f"(d[62]), "=f"(d[63]), "=f"(d[64]), "=f"(d[65]), "=f"(d[66]), "=f"(d[67]), "=f"(d[68]), "=f"(d[69]), "=f"(d[70]), "=f"(d[71]), "=f"(d[72]), "=f"(d[73]), "=f"(d[74]), "=f"(d[75]), "=f"(d[76]), "=f"(d[77]), "=f"(d[78]), "=f"(d[79]), "=f"(d[80]), "=f"(d[81]), "=f"(d[82]), "=f"(d[83]), "=f"(d[84]), "=f"(d[85]), "=f"(d[86]), "=f"(d[87]), "=f"(d[88]), "=f"(d[89]), "=f"(d[90]), "=f"(d[91]), "=f"(d[92]), "=f"(d[93]), "=f"(d[94]), "=f"(d[95]), "=f"(d[96]), "=f"(d[97]), "=f"(d[98]), "=f"(d[99]), "=f"(d[100]), "=f"(d[101]), "=f"(d[102]), "=f"(d[103]), "=f"(d[104]), "=f"(d[105]), "=f"(d[106]), "=f"(d[107]), "=f"(d[108]), "=f"(d[109]), "=f"(d[110]), "=f"(d[111]), "=f"(d[112]), "=f"(d[113]), "=f"(d[114]), "=f"(d[115]), "=f"(d[116]), "=f"(d[117]), "=f"(d[118]), "=f"(d[119]), "=f"(d[120]), "=f"(d[121]), "=f"(d[122]), "=f"(d[123]), "=f"(d[124]), "=f"(d[125]), "=f"(d[126]), "=f"(d[127])
      : "r"(a0), "r"(a1), "r"(a2), "r"(a3), "l"(db));
  }
}
__device__ __forceinline__ void wgmma_n256_ss_ta0_tb1(float* d, uint64_t da, uint64_t db, bool accumulate) {
  if (accumulate) {
    asm volatile("{\n.reg .pred p;\nsetp.ne.b32 p, 1, 0;\n"
      "wgmma.mma_async.sync.aligned.m64n256k16.f32.bf16.bf16 "
      "{%0, %1, %2, %3, %4, %5, %6, %7, %8, %9, %10, %11, %12, %13, %14, %15, %16, %17, %18, %19, %20, %21, %22, %23, %24, %25, %26, %27, %28, %29, %30, %31, %32, %33, %34, %35, %36, %37, %38, %39, %40, %41, %42, %43, %44, %45, %46, %47, %48, %49, %50, %51, %52, %53, %54, %55, %56, %57, %58, %59, %60, %61, %62, %63, %64, %65, %66, %67, %68, %69, %70, %71, %72, %73, %74, %75, %76, %77, %78, %79, %80, %81, %82, %83, %84, %85, %86, %87, %88, %89, %90, %91, %92, %93, %94, %95, %96, %97, %98, %99, %100, %101, %102, %103, %104, %105, %106, %107, %108, %109, %110, %111, %112, %113, %114, %115, %116, %117, %118, %119, %120, %121, %122, %123, %124, %125, %126, %127}, "
      "%128, %129, p, 1, 1, 0, 1;\n}\n"
      : "+f"(d[0]), "+f"(d[1]), "+f"(d[2]), "+f"(d[3]), "+f"(d[4]), "+f"(d[5]), "+f"(d[6]), "+f"(d[7]), "+f"(d[8]), "+f"(d[9]), "+f"(d[10]), "+f"(d[11]), "+f"(d[12]), "+f"(d[13]), "+f"(d[14]), "+f"(d[15]), "+f"(d[16]), "+f"(d[17]), "+f"(d[18]), "+f"(d[19]), "+f"(d[20]), "+f"(d[21]), "+f"(d[22]), "+f"(d[23]), "+f"(d[24]), "+f"(d[25]), "+f"(d[26]), "+f"(d[27]), "+f"(d[28]), "+f"(d[29]), "+f"(d[30]), "+f"(d[31]), "+f"(d[32]), "+f"(d[33]), "+f"(d[34]), "+f"(d[35]), "+f"(d[36]), "+f"(d[37]), "+f"(d[38]), "+f"(d[39]), "+f"(d[40]), "+f"(d[41]), "+f"(d[42]), "+f"(d[43]), "+f"(d[44]), "+f"(d[45]), "+f"(d[46]), "+f"(d[47]), "+f"(d[48]), "+f"(d[49]), "+f"(d[50]), "+f"(d[51]), "+f"(d[52]), "+f"(d[53]), "+f"(d[54]), "+f"(d[55]), "+f"(d[56]), "+f"(d[57]), "+f"(d[58]), "+f"(d[59]), "+f"(d[60]), "+f"(d[61]), "+f"(d[62]), "+f"(d[63]), "+f"(d[64]), "+f"(d[65]), "+f"(d[66]), "+f"(d[67]), "+f"(d[68]), "+f"(d[69]), "+f"(d[70]), "+f"(d[71]), "+f"(d[72]), "+f"(d[73]), "+f"(d[74]), "+f"(d[75]), "+f"(d[76]), "+f"(d[77]), "+f"(d[78]), "+f"(d[79]), "+f"(d[80]), "+f"(d[81]), "+f"(d[82]), "+f"(d[83]), "+f"(d[84]), "+f"(d[85]), "+f"(d[86]), "+f"(d[87]), "+f"(d[88]), "+f"(d[89]), "+f"(d[90]), "+f"(d[91]), "+f"(d[92]), "+f"(d[93]), "+f"(d[94]), "+f"(d[95]), "+f"(d[96]), "+f"(d[97]), "+f"(d[98]), "+f"(d[99]), "+f"(d[100]), "+f"(d[101]), "+f"(d[102]), "+f"(d[103]), "+f"(d[104]), "+f"(d[105]), "+f"(d[106]), "+f"(d[107]), "+f"(d[108]), "+f"(d[109]), "+f"(d[110]), "+f"(d[111]), "+f"(d[112]), "+f"(d[113]), "+f"(d[114]), "+f"(d[115]), "+f"(d[116]), "+f"(d[117]), "+f"(d[118]), "+f"(d[119]), "+f"(d[120]), "+f"(d[121]), "+f"(d[122]), "+f"(d[123]), "+f"(d[124]), "+f"(d[125]), "+f"(d[126]), "+f"(d[127])
      : "l"(da), "l"(db));
  } else {
    asm volatile("{\n.reg .pred p;\nsetp.ne.b32 p, 0, 0;\n"
      "wgmma.mma_async.sync.aligned.m64n256k16.f32.bf16.bf16 "
      "{%0, %1, %2, %3, %4, %5, %6, %7, %8, %9, %10, %11, %12, %13, %14, %15, %16, %17, %18, %19, %20, %21, %22, %23, %24, %25, %26, %27, %28, %29, %30, %31, %32, %33, %34, %35, %36, %37, %38, %39, %40, %41, %42, %43, %44, %45, %46, %47, %48, %49, %50, %51, %52, %53, %54, %55, %56, %57, %58, %59, %60, %61, %62, %63, %64, %65, %66, %67, %68, %69, %70, %71, %72, %73, %74, %75, %76, %77, %78, %79, %80, %81, %82, %83, %84, %85, %86, %87, %88, %89, %90, %91, %92, %93, %94, %95, %96, %97, %98, %99, %100, %101, %102, %103, %104, %105, %106, %107, %108, %109, %110, %111, %112, %113, %114, %115, %116, %117, %118, %119, %120, %121, %122, %123, %124, %125, %126, %127}, "
      "%128, %129, p, 1, 1, 0, 1;\n}\n"
      : "=f"(d[0]), "=f"(d[1]), "=f"(d[2]), "=f"(d[3]), "=f"(d[4]), "=f"(d[5]), "=f"(d[6]), "=f"(d[7]), "=f"(d[8]), "=f"(d[9]), "=f"(d[10]), "=f"(d[11]), "=f"(d[12]), "=f"(d[13]), "=f"(d[14]), "=f"(d[15]), "=f"(d[16]), "=f"(d[17]), "=f"(d[18]), "=f"(d[19]), "=f"(d[20]), "=f"(d[21]), "=f"(d[22]), "=f"(d[23]), "=f"(d[24]), "=f"(d[25]), "=f"(d[26]), "=f"(d[27]), "=f"(d[28]), "=f"(d[29]), "=f"(d[30]), "=f"(d[31]), "=f"(d[32]), "=f"(d[33]), "=f"(d[34]), "=f"(d[35]), "=f"(d[36]), "=f"(d[37]), "=f"(d[38]), "=f"(d[39]), "=f"(d[40]), "=f"(d[41]), "=f"(d[42]), "=f"(d[43]), "=f"(d[44]), "=f"(d[45]), "=f"(d[46]), "=f"(d[47]), "=f"(d[48]), "=f"(d[49]), "=f"(d[50]), "=f"(d[51]), "=f"(d[52]), "=f"(d[53]), "=f"(d[54]), "=f"(d[55]), "=f"(d[56]), "=f"(d[57]), "=f"(d[58]), "=f"(d[59]), "=f"(d[60]), "=f"(d[61]), "=f"(d[62]), "=f"(d[63]), "=f"(d[64]), "=f"(d[65]), "=f"(d[66]), "=f"(d[67]), "=f"(d[68]), "=f"(d[69]), "=f"(d[70]), "=f"(d[71]), "=f"(d[72]), "=f"(d[73]), "=f"(d[74]), "=f"(d[75]), "=f"(d[76]), "=f"(d[77]), "=f"(d[78]), "=f"(d[79]), "=f"(d[80]), "=f"(d[81]), "=f"(d[82]), "=f"(d[83]), "=f"(d[84]), "=f"(d[85]), "=f"(d[86]), "=f"(d[87]), "=f"(d[88]), "=f"(d[89]), "=f"(d[90]), "=f"(d[91]), "=f"(d[92]), "=f"(d[93]), "=f"(d[94]), "=f"(d[95]), "=f"(d[96]), "=f"(d[97]), "=f"(d[98]), "=f"(d[99]), "=f"(d[100]), "=f"(d[101]), "=f"(d[102]), "=f"(d[103]), "=f"(d[104]), "=f"(d[105]), "=f"(d[106]), "=f"(d[107]), "=f"(d[108]), "=f"(d[109]), "=f"(d[110]), "=f"(d[111]), "=f"(d[112]), "=f"(d[113]), "=f"(d[114]), "=f"(d[115]), "=f"(d[116]), "=f"(d[117]), "=f"(d[118]), "=f"(d[119]), "=f"(d[120]), "=f"(d[121]), "=f"(d[122]), "=f"(d[123]), "=f"(d[124]), "=f"(d[125]), "=f"(d[126]), "=f"(d[127])
      : "l"(da), "l"(db));
  }
}
__device__ __forceinline__ void wgmma_n256_ssp_ta0_tb1(float* d, uint64_t da, uint64_t db, int accumulate) {
    asm volatile("{\n.reg .pred p;\nsetp.ne.b32 p, %130, 0;\n"
      "wgmma.mma_async.sync.aligned.m64n256k16.f32.bf16.bf16 "
      "{%0, %1, %2, %3, %4, %5, %6, %7, %8, %9, %10, %11, %12, %13, %14, %15, %16, %17, %18, %19, %20, %21, %22, %23, %24, %25, %26, %27, %28, %29, %30, %31, %32, %33, %34, %35, %36, %37, %38, %39, %40, %41, %42, %43, %44, %45, %46, %47, %48, %49, %50, %51, %52, %53, %54, %55, %56, %57, %58, %59, %60, %61, %62, %63, %64, %65, %66, %67, %68, %69, %70, %71, %72, %73, %74, %75, %76, %77, %78, %79, %80, %81, %82, %83, %84, %85, %86, %87, %88, %89, %90, %91, %92, %93, %94, %95, %96, %97, %98, %99, %100, %101, %102, %103, %104, %105, %106, %107, %108, %109, %110, %111, %112, %113, %114, %115, %116, %117, %118, %119, %120, %121, %122, %123, %124, %125, %126, %127}, "
      "%128, %129, p, 1, 1, 0, 1;\n}\n"
      : "+f"(d[0]), "+f"(d[1]), "+f"(d[2]), "+f"(d[3]), "+f"(d[4]), "+f"(d[5]), "+f"(d[6]), "+f"(d[7]), "+f"(d[8]), "+f"(d[9]), "+f"(d[10]), "+f"(d[11]), "+f"(d[12]), "+f"(d[13]), "+f"(d[14]), "+f"(d[15]), "+f"(d[16]), "+f"(d[17]), "+f"(d[18]), "+f"(d[19]), "+f"(d[20]), "+f"(d[21]), "+f"(d[22]), "+f"(d[23]), "+f"(d[24]), "+f"(d[25]), "+f"(d[26]), "+f"(d[27]), "+f"(d[28]), "+f"(d[29]), "+f"(d[30]), "+f"(d[31]), "+f"(d[32]), "+f"(d[33]), "+f"(d[34]), "+f"(d[35]), "+f"(d[36]), "+f"(d[37]), "+f"(d[38]), "+f"(d[39]), "+f"(d[40]), "+f"(d[41]), "+f"(d[42]), "+f"(d[43]), "+f"(d[44]), "+f"(d[45]), "+f"(d[46]), "+f"(d[47]), "+f"(d[48]), "+f"(d[49]), "+f"(d[50]), "+f"(d[51]), "+f"(d[52]), "+f"(d[53]), "+f"(d[54]), "+f"(d[55]), "+f"(d[56]), "+f"(d[57]), "+f"(d[58]), "+f"(d[59]), "+f"(d[60]), "+f"(d[61]), "+f"(d[62]), "+f"(d[63]), "+f"(d[64]), "+f"(d[65]), "+f"(d[66]), "+f"(d[67]), "+f"(d[68]), "+f"(d[69]), "+f"(d[70]), "+f"(d[71]), "+f"(d[72]), "+f"(d[73]), "+f"(d[74]), "+f"(d[75]), "+f"(d[76]), "+f"(d[77]), "+f"(d[78]), "+f"(d[79]), "+f"(d[80]), "+f"(d[81]), "+f"(d[82]), "+f"(d[83]), "+f"(d[84]), "+f"(d[85]), "+f"(d[86]), "+f"(d[87]), "+f"(d[88]), "+f"(d[89]), "+f"(d[90]), "+f"(d[91]), "+f"(d[92]), "+f"(d[93]), "+f"(d[94]), "+f"(d[95]), "+f"(d[96]), "+f"(d[97]), "+f"(d[98]), "+f"(d[99]), "+f"(d[100]), "+f"(d[101]), "+f"(d[102]), "+f"(d[103]), "+f"(d[104]), "+f"(d[105]), "+f"(d[106]), "+f"(d[107]), "+f"(d[108]), "+f"(d[109]), "+f"(d[110]), "+f"(d[111]), "+f"(d[112]), "+f"(d[113]), "+f"(d[114]), "+f"(d[115]), "+f"(d[116]), "+f"(d[117]), "+f"(d[118]), "+f"(d[119]), "+f"(d[120]), "+f"(d[121]), "+f"(d[122]), "+f"(d[123]), "+f"(d[124]), "+f"(d[125]), "+f"(d[126]), "+f"(d[127])
      : "l"(da), "l"(db), "r"(accumulate));
}

template <int N> __device__ __forceinline__ void quad_sum(float* m) {
#pragma unroll
  for (int o = 1; o <= 2; o <<= 1) {
    float t[N];
#pragma unroll
    for (int i = 0; i < N; i++) t[i] = __shfl_xor_sync(~0u, m[i], o);
#pragma unroll
    for (int i = 0; i < N; i++) m[i] += t[i];
  }
}
__device__ __forceinline__ bool softmax_unsafe(const uint32_t* t, float l0, float l1) {
  const float m0 = fmaxf(bf_lo(t[0]) + bf_hi(t[0]), bf_lo(t[2]) + bf_hi(t[2])), m1 = fmaxf(bf_lo(t[1]) + bf_hi(t[1]), bf_lo(t[3]) + bf_hi(t[3]));
  return __any_sync(~0u, !(m0 * l0 < 2500.f) | !(m1 * l1 < 2500.f));
}
__device__ __forceinline__ void softmax_shift(float* p, float c0, float c1) {
#pragma unroll 1
  for (int it = 0; it < 8; it++) {
    float mx = p[0], mn = p[0];
#pragma unroll
    for (int j = 1; j < 8; j++) { mx = fmaxf(mx, p[(j >> 1) * 4 + (j & 1)]); mn = fminf(mn, p[(j >> 1) * 4 + (j & 1)]); }
#pragma unroll
    for (int o = 1; o <= 2; o <<= 1) { mx = fmaxf(mx, __shfl_xor_sync(~0u, mx, o)); mn = fminf(mn, __shfl_xor_sync(~0u, mn, o)); }
    const float half = fminf(0.5f * (mx - mn), 50.f * rcp(it & 1 ? c1 : c0));
    float r[8];
#pragma unroll
    for (int j = 0; j < 8; j++) {
      const float v = p[(j >> 1) * 4 + (j & 1)];
      r[j] = fmaxf(v - mx + half, 0.f) + fminf(v - mn - half, 0.f) + (v - v);
    }
#pragma unroll
    for (int k = 0; k < 7; k++)
#pragma unroll
      for (int j = 0; j < 8; j++) p[(k >> 1) * 16 + (k & 1) * 2 + (j >> 1) * 4 + (j & 1)] = p[((k + 1) >> 1) * 16 + ((k + 1) & 1) * 2 + (j >> 1) * 4 + (j & 1)];
#pragma unroll
    for (int j = 0; j < 8; j++) p[50 + (j >> 1) * 4 + (j & 1)] = r[j];
  }
}
template <int J0 = 0, int J1 = 8> __device__ __forceinline__ void k_exp(const float* p, float c0, float c1, float* e, float* s) {
#pragma unroll
  for (int j = J0; j < J1; j++) {
    e[2 * j] = ex2(p[2 * j] * (j & 1 ? c1 : c0));
    e[2 * j + 1] = ex2(p[2 * j + 1] * (j & 1 ? c1 : c0));
    e[16 + j] = rcp(e[2 * j] * e[2 * j + 1]);
    const float t = e[2 * j] + e[2 * j + 1];
    s[j & 1] = j < 2 ? t : s[j & 1] + t;
    s[2 + (j & 1)] = j < 2 ? e[16 + j] * t : fmaf(e[16 + j], t, s[2 + (j & 1)]);
  }
}
template <int J0 = 0, int J1 = 8> __device__ __forceinline__ void q_exp(const float* p, float c0, float c1, uint32_t* f) {
#pragma unroll
  for (int j = J0; j < J1; j++) {
    const float e0 = ex2(p[2 * j] * (j & 1 ? c1 : c0)), e1 = ex2(p[2 * j + 1] * (j & 1 ? c1 : c0)), r = rcp(e0 * e1);
    f[j] = pack2(e0, e1);
    f[8 + j] = bmul2(f[j], pack2(r, r));
  }
}

#define FMA8(A, U, X)                                                                                        \
  A[0] = fmaf(bf_lo(U.x), X, A[0]); A[1] = fmaf(bf_hi(U.x), X, A[1]); A[2] = fmaf(bf_lo(U.y), X, A[2]); A[3] = fmaf(bf_hi(U.y), X, A[3]); \
  A[4] = fmaf(bf_lo(U.z), X, A[4]); A[5] = fmaf(bf_hi(U.z), X, A[5]); A[6] = fmaf(bf_lo(U.w), X, A[6]); A[7] = fmaf(bf_hi(U.w), X, A[7])

__device__ __forceinline__ uint32_t routed_row(const __nv_bfloat16* x, uint32_t tag, int lane, uint4* xr) {
  uint32_t best = 0, sv = 0;
#pragma unroll 1
  for (int it = 0; it < SPIN_MAX; it++) {
    const uint4 h = ld_rlx128(g_ycnt + 32);
    best = h.x;
    if (__all_sync(~0u, (int)(h.z - tag * NCTA) >= 0)) break;
    __nanosleep(AM_NS);
  }
#pragma unroll 1
  for (int it = 0; it < SPIN_MAX; it++) {
    const int sel = 2047 - (best & 0x7ff);
#pragma unroll
    for (int i = 0; i < 4; i++) xr[i] = ldg_nc(x + (size_t)sel * DM + i * 256 + lane * 8);
    const unsigned long long st = ld_rlx64(g_stat + sel);
    const uint4 b0 = ld_rlx128(g_best + lane * 2), b1 = ld_rlx128(g_best + 64 + lane * 2);
    const uint32_t m = __reduce_max_sync(~0u, max(max(b0.x, b0.z), max(b1.x, b1.z)));
    sv = (uint32_t)st;
    if (__all_sync(~0u, b0.y == tag && b0.w == tag && b1.y == tag && b1.w == tag && m == best && (uint32_t)(st >> 32) == tag)) break;
    best = m;
  }
  const uint32_t m2 = (sv & 0xffff0000u) | (sv >> 16);
  const float rs = rcp(bf_lo(sv));
#pragma unroll
  for (int i = 0; i < 4; i++) {
    const uint32_t d0 = bsub2(xr[i].x, m2), d1 = bsub2(xr[i].y, m2), d2 = bsub2(xr[i].z, m2), d3 = bsub2(xr[i].w, m2);
    xr[i] = make_uint4(pack2(bf_lo(d0) * rs, bf_hi(d0) * rs), pack2(bf_lo(d1) * rs, bf_hi(d1) * rs), pack2(bf_lo(d2) * rs, bf_hi(d2) * rs),
                       pack2(bf_lo(d3) * rs, bf_hi(d3) * rs));
  }
  return best;
}

struct Params {
  const __nv_bfloat16 *x, *wqkv, *wo, *w_r, *w_gate, *w_up, *w_down;
};

template <bool BY_SMID> __global__ void __launch_bounds__(384, 1)
fused_kernel(const __grid_constant__ CUtensorMap mX, const __grid_constant__ CUtensorMap mWkv, const __grid_constant__ CUtensorMap mWq,
             const __grid_constant__ CUtensorMap mWo, const __grid_constant__ CUtensorMap mPhi, const __grid_constant__ CUtensorMap mWp,
             const __grid_constant__ CUtensorMap mOut, const __grid_constant__ CUtensorMap mWc,
             const __grid_constant__ CUtensorMap mG, const __grid_constant__ CUtensorMap mU, const __grid_constant__ CUtensorMap mD,
             const __grid_constant__ CUtensorMap mXs, const __grid_constant__ CUtensorMap mG2, const __grid_constant__ CUtensorMap mU2, const Params P) {
  constexpr uint32_t sb = SB, bar = SB + SM_BAR;
  int bid = blockIdx.x;
  if (BY_SMID) {
    uint32_t sm;
    asm volatile("mov.u32 %0, %%smid;" : "=r"(sm));
    const uint32_t tq = (sm - 64) >> 1, q7 = (tq * 37) >> 8;
    const uint32_t gpc = sm < 64 ? (sm >> 1) & 7 : 1 + tq - 7 * q7, idx = (sm < 64 ? sm >> 4 : 4 + q7) * 2 + (sm & 1);
    bid = sm < 120 ? ((PTAB >> (4 * gpc)) & 7) * 16 + idx : sm < 124 ? sm + 8 : sm - 116;
  }
  const int hg = ((bid >> 2) & 3) + 4 * ((bid >> 4) & 1), mb = (bid & 3) + 4 * ((bid >> 5) & 3);
  if (bid < NCTA && threadIdx.x < 256) {
    const uint32_t r0 = threadIdx.x >> 3, c = threadIdx.x & 7, dst = sb + 2 * KV_STAGE + r0 * 128 + ((c ^ (r0 & 7)) << 4);
    const char* xs = (const char*)P.x + (size_t)(mb * 128 + r0) * 2048 + c * 16;
    const char* ws = (const char*)P.wqkv + (size_t)r0 * 6144 + 2048 + hg * 256 + c * 16;
#pragma unroll
    for (int i = 0; i < 4; i++) cp_async16(dst + i * 4096, xs + i * 65536);
#pragma unroll
    for (int i = 0; i < 8; i++) cp_async16(dst + 16384 + i * 4096, ws + (i & 1) * 196608 + (i >> 2) * 2048 + ((i >> 1) & 1) * 128);
  }
  extern __shared__ __align__(1024) uint8_t smem[];
  if (smem_u32(smem) != SB) __trap();
  const int warp = __shfl_sync(~0u, threadIdx.x >> 5, 0);

  if (bid >= NCTA) {
    constexpr uint32_t XV = SM_WPHI, ONES = SM_ZT, BF = bar, BE = bar + 48, BX = bar + 96;
    constexpr int NJ = (DM - GROWS) / 64;
    const int lane = lane_id(), sp = bid - NCTA;
    const uint32_t tag = ld_rlx(g_epoch + bid * 32 + lane) + 1;
    if (warp == 8 && elect_one()) {
#pragma unroll 1
      for (int i = 0; i < 13; i++) mbar_init(bar + 8 * i, i >= 6 && i < 12 ? 8 : 1);
    }
    if (warp == 9) { sts64u(sb + ONES + lane * 8, 0x3f803f80u, 0x3f803f80u); fence_async_smem(); }
    __syncthreads();
    if (warp == 8) {
      if (elect_one()) {
        uint32_t s = 0, ph = 1;
        for (const long long c0 = clock64(); clock64() - c0 < SP_DELAY;) {}
#pragma unroll 1
        for (int job = 0; job < 8; job++) {
          const CUtensorMap* m = job == 0 ? &mWq : sp & 2 ? &mU2 : &mG2;
          const int g0 = job ? (sp & 1) * 28 + job * 4 - 4 : sp * 4;
#pragma unroll 1
          for (int row = job ? GROWS : 0; row < DM; row += 64) {
            mbar_wait(BE + 8 * s, ph);
            mbar_expect_tx(BF + 8 * s, Q_STAGE);
            tma4d(sb + s * Q_STAGE, m, 0, row, g0, 0, BF + 8 * s);
            tma4d(sb + s * Q_STAGE + 16384, m, 0, row, g0 + 2, 0, BF + 8 * s);
            if (++s == 6) { s = 0; ph ^= 1; }
          }
        }
      }
    } else if (warp == 9) {
      uint4 xr[4];
      routed_row(P.x, tag, lane, xr);
#pragma unroll
      for (int i = 0; i < 4; i++) sts128u(sb + XV + i * 512 + lane * 16, xr[i].x, xr[i].y, xr[i].z, xr[i].w);
      fence_async_smem();
      __syncwarp();
      if (lane == 0) mbar_arrive(BX);
    } else if (warp < 8) {
      uint32_t s = 0, ph = 0;
#pragma unroll 1
      for (int job = 0; job < 8; job++) {
        float d[8] = {0.f, 0.f, 0.f, 0.f, 0.f, 0.f, 0.f, 0.f};
        if (job == 1) mbar_wait(BX, 0);
#pragma unroll 1
        for (int i = 0; i < (job ? NJ : 16); i++) {
          mbar_wait(BF + 8 * s, ph);
          wg_fence();
#pragma unroll
          for (int k = 0; k < 8; k++)
            wgmma_n8_ss_ta1_tb0(d + 4 * (k >> 2), mkdesc(sb + k * 2048, 16, 1024, 1, s * (Q_STAGE / 16) + (warp >> 2) * 1024),
                                mkdesc(sb, 16, 128, 0, job ? (XV + GROWS * 2) / 16 + i * 8 + (k & 3) * 2 : ONES / 16), 1);
          wg_commit();
          wg_wait<0>();
          if (lane == 0) mbar_arrive(BE + 8 * s);
          if (++s == 6) { s = 0; ph ^= 1; }
        }
        reg_fence<8>(d);
        float* dst = (job ? g_gp + sp * 1792 + job * 256 - 256 : g_cs + sp * 256) + (warp >> 2) * 128 + (warp & 3) * 16 + (lane >> 2);
        if ((lane & 3) == 0) {
#pragma unroll
          for (int i = 0; i < 4; i++) st_rlx(dst + (i >> 1) * 64 + (i & 1) * 8, mark(__float_as_uint(d[2 * i]), tag & 1));
        }
        __syncwarp();
      }
      if (warp == 0) g_epoch[bid * 32 + lane] = tag;
    }
    return;
  }
#define Q_SLAB(J) ((J) < 8 ? ((J) + 8 - 2 * (hg & 4)) & 15 : 2 * (hg & 4) + 2 * ((J) & 3) + ((J) >> 2 & 1))
#define Q_AOFF(J) ((J) == 8 + (hg & 3) ? SM_X0 : (J) == 12 + (hg & 3) ? SM_X1 : ((J) & 3) * Q_STAGE)
#define Q_LOAD(J)                                                                                            \
  do {                                                                                                       \
    const uint32_t fb_ = bar + B_FULLQ + 8 * ((J) & 3);                                                      \
    const int k_ = Q_SLAB(J) * 64;                                                                           \
    mbar_expect_tx(fb_, Q_STAGE);                                                                            \
    mbar_arrive2(fb_);                                                                                       \
    tma2d(sb + Q_AOFF(J), &mX, k_, mb * 128, fb_);                                                           \
    tma4d(sb + ((J) & 3) * Q_STAGE + 16384, &mWq, 0, k_, hg * 2, 0, fb_);                                    \
  } while (0)
  if (warp >= 8) {
    asm volatile("setmaxnreg.dec.sync.aligned.u32 %0;" ::"n"(REG_H));
    const int lane = lane_id();
    const int f = (warp - 9) & 3;
    if (f == 3) {
      if (elect_one()) {
        PROF(0); PROFT(32);
#pragma unroll
        for (int s = 0; s < 3; s++) mbar_init(bar + B_FULLKV + 8 * s, 1);
      }
      __syncwarp();
      asm volatile("bar.arrive 14, 288;" ::: "memory");
      if (elect_one()) {
#pragma unroll
        for (int s = 0; s < 2; s++) {
          mbar_expect_tx(bar + B_FULLKV + 8 * s, KV_STAGE);
          tma2d(sb + s * KV_STAGE, &mX, (s + 1) * 64, mb * 128, bar + B_FULLKV + 8 * s);
          tma4d(sb + s * KV_STAGE + 16384, &mWkv, 0, (s + 1) * 64, hg * 2, 1, bar + B_FULLKV + 8 * s);
        }
      }
      __syncwarp();
    }
    const uint32_t ep = ld_rlx(g_epoch + bid * 32 + lane);
    if (f < 2) {
#pragma unroll
      for (int i = 0; i < 2; i++) {
        const uint4 u = __ldg((const uint4*)P.w_r + (f * 2 + i) * 32 + lane);
        sts128u(sb + SM_XSEL + (f * 2 + i) * 512 + lane * 16, u.x, u.y, u.z, u.w);
      }
    }
    bar_sync(13, 384);
    const uint32_t tag = ep + 1, par = tag & 1;
    const bool ffn = bid < NFFN;
    const int fb = bid, cu = bid >> 1, ch = bid & 1;
#define CS_STORE(SEC, C)                                                                                     \
  _Pragma("unroll") for (int r = 0; r < 3; r++) {                                                            \
    const uint32_t h0 = pack2(C.x, C.y), h1 = pack2(C.z, C.w);                                               \
    sts64u(sb + SM_CST + (SEC) * 1024 + (lane >> 4) * 512 + (lane & 1) * 8 + r * 128 + ((((lane & 15) >> 1) ^ (r + (lane >> 4) * 4)) << 4), h0, h1); \
    C.x -= bf_lo(h0); C.y -= bf_hi(h0); C.z -= bf_lo(h1); C.w -= bf_hi(h1);                                  \
  }
#define BAD4(U) ((U.x ^ par) | (U.y ^ par) | (U.z ^ par) | (U.w ^ par))
    const int n0 = f < 2 ? 0 : 2 * f - 3, ne = FFN_OFF || !ffn ? 3 : f == 3 ? 3 + G8 : 3 + GN;
    const uint32_t fsb = sb + SM_FST + ((f + 1) & 3) * 8192, fbar = bar + B_FST + f * 16, fst = fsb + (lane >> 4) * 2048 + (lane & 15) * 16;
    const CUtensorMap *ma = &mWc, *mc = &mWc;
    int sx = 1024 + cu * 32, sy = ch * 512 + f * 192, sdy = 32;
#define STAGEG(N)                                                                                            \
  do {                                                                                                       \
    if ((N) == 3) { ma = &mG; mc = &mU; sx = fb * 32; sy = f * (GN * 32);  sdy = 0; }                        \
    if ((N) < ne && elect_one()) {                                                                           \
      const uint32_t dst_ = fsb + ((N) & 1) * 4096, b_ = fbar + ((N) & 1) * 8;                               \
      mbar_expect_tx(b_, 4096);                                                                              \
      tma2d(dst_, ma, sx, sy, b_);                                                                           \
      tma2d(dst_ + 2048, mc, sx, sy + sdy, b_);                                                              \
    }                                                                                                        \
    sy += 32 + sdy;                                                                                          \
  } while (0)
    float a[8], gsum = 0.f, usum = 0.f;
    {
      if (f == 3) {
        if (elect_one()) {
          if (XS_EARLY) { mbar_expect_tx(bar + B_XST, 16384); tma3d(sb + SM_XST, &mXs, 0, bid * 16, 0, bar + B_XST); }
          mbar_expect_tx(bar + B_WPHI, 8192);
          tma2d(sb + SM_WPHI, &mPhi, 0, hg * 128, bar + B_WPHI);
          prefetch_map(&mWq); prefetch_map(&mWo); prefetch_map(&mWp); prefetch_map(&mD);
          PROF(31);
        }
        __syncwarp();
      } else {
        if (lane == 0) prefetch_map(f == 0 ? &mWc : f == 1 ? &mG : &mU);
        if (f == 2) ((float2*)g_y[par])[bid * 32 + lane] = make_float2(0.f, 0.f);
      }
      float st[13];
#pragma unroll
      for (int i = 0; i < 13; i++) st[i] = 0.f;
#pragma unroll 1
      for (int i = 0; i < 4; i++) {
        mbar_wait(bar + B_XST + 8 * (i >> 1), 0);
        if (f == 0 && lane == 0 && i == 0) PROF(1);
        const uint4 wu = lds128u(sb + SM_XSEL + i * 512 + lane * 16);
        const float wf[8] = {bf_lo(wu.x), bf_hi(wu.x), bf_lo(wu.y), bf_hi(wu.y), bf_lo(wu.z), bf_hi(wu.z), bf_lo(wu.w), bf_hi(wu.w)};
        st[12] += ((wf[0] + wf[1]) + (wf[2] + wf[3])) + ((wf[4] + wf[5]) + (wf[6] + wf[7]));
#pragma unroll
        for (int r = 0; r < 4; r++) {
          const uint4 u = lds128u(sb + SM_XST + i * 8192 + (4 * f + r) * 512 + lane * 16);
          const float xf[8] = {bf_lo(u.x), bf_hi(u.x), bf_lo(u.y), bf_hi(u.y), bf_lo(u.z), bf_hi(u.z), bf_lo(u.w), bf_hi(u.w)};
#pragma unroll
          for (int k = 0; k < 8; k++) { st[r] += xf[k]; st[4 + r] = fmaf(xf[k], xf[k], st[4 + r]); st[8 + r] = fmaf(xf[k], wf[k], st[8 + r]); }
        }
        if (i >= 2 && f < 3) STAGEG(n0 + i - 2);
      }
      const bool up = lane & 16, up2 = lane & 8;
#pragma unroll
      for (int q = 0; q < 3; q++) {
        const float k0 = up ? st[4 * q + 2] : st[4 * q], k1 = up ? st[4 * q + 3] : st[4 * q + 1];
        const float o0 = up ? st[4 * q] : st[4 * q + 2], o1 = up ? st[4 * q + 1] : st[4 * q + 3];
        const float m0 = k0 + __shfl_xor_sync(~0u, o0, 16), m1 = k1 + __shfl_xor_sync(~0u, o1, 16);
        a[q] = (up2 ? m1 : m0) + __shfl_xor_sync(~0u, up2 ? m0 : m1, 8);
      }
      a[3] = st[12] + __shfl_xor_sync(~0u, st[12], 16);
      a[3] += __shfl_xor_sync(~0u, a[3], 8);
#pragma unroll
      for (int o = 4; o; o >>= 1)
#pragma unroll
        for (int q = 0; q < 4; q++) a[q] += __shfl_xor_sync(~0u, a[q], o);
      if ((lane & 7) == 0) sts128(sb + SM_ROWS + (4 * f + (lane >> 3)) * 16, a[0], a[1], a[2], a[3]);
      if (f < 3) asm volatile("bar.arrive 7, 128;" ::: "memory");
    }
    if (f == 3) {
      bar_sync(7, 128);
      const int row = bid * 16 + (lane & 15);
      const float4 v = lds128(sb + SM_ROWS + (lane & 15) * 16);
      const float mf = v.x * (1.f / DM), mean = bf_round(mf), var = fmaxf(fmaf(-mf, mf, v.y * (1.f / DM)), 0.f);
      const float sd = bf_round(sqrt_approx(bf_round(bf_round(var) + 1e-5f)));
      const uint32_t rb = pack2(fmaf(-mean, v.w, v.z) * rcp(sd), 0.f) & 0xffffu, ord = (rb & 0x8000u) ? (~rb & 0xffffu) : (rb | 0x8000u);
      uint32_t best = __reduce_max_sync(~0u, (ord << 16) | (uint32_t)(2047 - row));
      if (lane < 16) st_rlx64(g_stat + row, ((unsigned long long)tag << 32) | __float_as_uint(mean) | (__float_as_uint(sd) >> 16));
      if (lane < 2) asm volatile("red.relaxed.gpu.global.max.u64 [%0], %1;" ::"l"(lane ? (void*)(g_ycnt + 32) : (void*)(g_best + bid)), "l"(((unsigned long long)tag << 32) | best) : "memory");
      if (lane == 1) { red_inc(g_ycnt + 34); PROF(17); }
#pragma unroll 1
      for (int n = 3; n < 5; n++) STAGEG(n);
      {
        uint4 xr[4];
        best = routed_row(P.x, tag, lane, xr);
#pragma unroll
        for (int i = 0; i < (GROWS + 255) / 256; i++) {
          const uint32_t dst = sb + SM_XSEL + i * 1024 + (lane >> 2) * 128 + (lane & 3) * 8;
          sts64(dst, bf_lo(xr[i].x), bf_lo(xr[i].z)); sts64(dst + 32, bf_hi(xr[i].x), bf_hi(xr[i].z));
          sts64(dst + 64, bf_lo(xr[i].y), bf_lo(xr[i].w)); sts64(dst + 96, bf_hi(xr[i].y), bf_hi(xr[i].w));
        }
        sts64u(sb + SM_RED + 16, tag, best);
        __syncwarp();
        if (lane == 0) { mbar_arrive(bar + B_XS); PROF(19); }
      }
      unsigned long long sv4[4];
      uint4 u[4];
#pragma unroll 1
      for (int it = 0; it < SPIN_MAX; it++) {
#pragma unroll
        for (int i = 0; i < 4; i++) { u[i] = ld_rlx128(g_cs + (1 + i) * 1024 + hg * 128 + lane * 4); sv4[i] = ld_rlx64(g_stat + mb * 128 + i * 32 + lane); }
        bool ok = ((BAD4(u[0]) | BAD4(u[1]) | BAD4(u[2]) | BAD4(u[3])) & 1) == 0;
#pragma unroll
        for (int i = 0; i < 4; i++) ok = ok && (uint32_t)(sv4[i] >> 32) == tag;
        if (__all_sync(~0u, ok)) break;
        __nanosleep(200);
      }
#pragma unroll
      for (int i = 0; i < 4; i++) {
        const uint32_t sv = (uint32_t)sv4[i], sd2 = (sv << 16) | (sv & 0xffffu);
        sts64(sb + SM_STAT + (i * 32 + lane) * 8, -bf_hi(sv), rcp(bf_lo(sv)));
        sts128u(sb + SM_SDT + lane * 64 + ((i ^ ((lane >> 1) & 3)) << 4), sd2, sd2, sd2, sd2);
      }
#pragma unroll
      for (int i = 0; i < 2; i++) {
        float4 c = make_float4(unmark(u[i].x) + unmark(u[i + 2].x), unmark(u[i].y) + unmark(u[i + 2].y), unmark(u[i].z) + unmark(u[i + 2].z),
                               unmark(u[i].w) + unmark(u[i + 2].w));
        CS_STORE(i, c);
      }
      fence_async_smem();
      bar_sync(8, 64);
      if (lane == 0) { mbar_arrive(bar + B_CS); PROF(10); }
    }
    {
      uint32_t xa = sb + SM_RED + 32, xstep = 0;
      const uint32_t zero = __float_as_uint(lds32(sb + SM_RED + 12));
#pragma unroll 1
      for (int ph = f == 3; ph < 2; ph++) {
#pragma unroll
        for (int j = 0; j < 8; j++) a[j] = 0.f;
        if (ph && f == 0) {
        {
          mbar_wait(bar + B_WPHI, 0);
          float nq[8] = {0.f, 0.f, 0.f, 0.f, 0.f, 0.f, 0.f, 0.f};
  #pragma unroll 2
          for (int r = 0; r < 16; r++) {
            const uint4 u = lds128u(sb + SM_WPHI + ((lane >> 2) * 16 + r) * 64 + (((lane ^ (r >> 1)) & 3) << 4));
            nq[0] = fmaf(bf_lo(u.x), bf_lo(u.x), nq[0]); nq[1] = fmaf(bf_hi(u.x), bf_hi(u.x), nq[1]); nq[2] = fmaf(bf_lo(u.y), bf_lo(u.y), nq[2]);
            nq[3] = fmaf(bf_hi(u.y), bf_hi(u.y), nq[3]); nq[4] = fmaf(bf_lo(u.z), bf_lo(u.z), nq[4]); nq[5] = fmaf(bf_hi(u.z), bf_hi(u.z), nq[5]);
            nq[6] = fmaf(bf_lo(u.w), bf_lo(u.w), nq[6]); nq[7] = fmaf(bf_hi(u.w), bf_hi(u.w), nq[7]);
          }
          uint32_t m = 0;
  #pragma unroll
          for (int i = 0; i < 8; i++) m = max(m, __float_as_uint(nq[i] + __shfl_xor_sync(~0u, nq[i], 4)) & 0x7fffffffu);
          sts32(sb + SM_RED + 24, 4.2f * __uint_as_float(__reduce_max_sync(~0u, m)));
        }
          asm volatile("bar.arrive 8, 64;" ::: "memory");
        }
        if (ph) { mbar_wait(bar + B_XS, 0); xa = sb + SM_XSEL + f * (GN * 128) + ((lane >> 2) & 3) * 32; xstep = 128; }
#pragma unroll 1
        for (int n = ph ? 3 : n0; n < (ph ? ne : 3); n++) {
          const float4 x0 = lds128(xa), x1 = lds128(xa + 16);
          xa += xstep;
          mbar_wait(fbar + (n & 1) * 8, ((n - n0) >> 1) & 1);
          uint4 u[8];
#pragma unroll
          for (int j = 0; j < 8; j++) u[j] = lds128u(fst + (n & 1) * 4096 + j * 256);
          FMA8(a, u[0], x0.x); FMA8(a, u[1], x0.y); FMA8(a, u[2], x0.z); FMA8(a, u[3], x0.w);
          if (__any_sync(~0u, ((u[4].x | u[5].x | u[6].x | u[7].x | __float_as_uint(a[0]) | __float_as_uint(a[7])) & zero) == 0)) STAGEG(n + 2);
          FMA8(a, u[4], x1.x); FMA8(a, u[5], x1.y); FMA8(a, u[6], x1.z); FMA8(a, u[7], x1.w);
        }
#pragma unroll
        for (int o = 4; o <= 8; o <<= 1)
#pragma unroll
          for (int j = 0; j < 8; j++) a[j] += __shfl_xor_sync(~0u, a[j], o);
        if (ph && lane == 0) mbar_arrive(bar + B_FFN);
        const uint32_t red = ph ? sb + SM_GRED : sb + SM_RED + 64;
        if ((lane & 12) == 0) {
          const uint32_t d = red + f * 256 + (lane >> 4) * 128 + (lane & 3) * 32;
          sts128(d, a[0], a[1], a[2], a[3]); sts128(d + 16, a[4], a[5], a[6], a[7]);
        }
        if (f != 2) {
          asm volatile("bar.arrive %0, %1;" ::"r"(4 + ph), "r"(96 + 32 * ph) : "memory");
        } else {
          bar_sync(4 + ph, 96 + 32 * ph);
          const uint32_t ra = red + lane * 4;
          gsum = lds32(ra) + lds32(ra + 256) + lds32(ra + 512);
          usum = lds32(ra + 128) + lds32(ra + 384) + lds32(ra + 640);
          if (!ph) st_rlx(g_cs + 1024 + ch * 2048 + cu * 32 + lane, mark(__float_as_uint(gsum + usum), par));
          else { gsum += lds32(ra + 768); usum += lds32(ra + 896); }
          if (lane == 0) PROF(ph ? 34 : 18);
        }
      }
    }
    if (f == 3) {
      if (elect_one()) {
        PROF(7);
        mbar_wait(bar + B_FULLQ, 0);
#pragma unroll 1
        for (int j = 3; j < 16; j++) {
          mbar_wait(bar + (j < 4 ? B_EMPTYKV + 16 : B_EMPTYQ + 8 * (j & 3)), ((j >> 2) & 1) ^ 1);
          if (j == 12 + (hg & 3)) mbar_wait(bar + B_KVST + 8, 0);
          Q_LOAD(j);
        }
        PROF(47);
        mbar_expect_tx(bar + B_DN, 65536);
#pragma unroll 1
        for (int i = 0; i < 4; i++) {
          mbar_wait(bar + B_EMPTYQ + 8 * i, 1);
          tma3d(sb + i * Q_STAGE, &mD, 0, fb * 32, i * 4, bar + B_DN);
        }
        PROF(48);
#pragma unroll 1
        for (int i = 0; i < 16; i++) {
          const int s = i & 3, n = i < 9 ? i - 2 : i - 9, kb = i < 2 ? 2 * hg + i : 2 * (n + (n >= hg)) + (i >= 9);
          if (i >= 4) mbar_wait(bar + B_EMPTYQ + 8 * s, ((i >> 2) & 1) ^ 1);
          mbar_expect_tx(bar + B_FULLQ + 8 * s, 16384);
          if (i < 2) {
            mbar_arrive2(bar + B_FULLQ + 8 * s);
            tma3d(sb + s * Q_STAGE + 16384, &mWo, 0, kb * 64, hg * 2, bar + B_FULLQ + 8 * s);
          } else {
            tma5d(sb + s * Q_STAGE + 16384, &mWp, hg * 128, kb * 2, bar + B_FULLQ + 8 * s);
            tma5d(sb + s * Q_STAGE + 24576, &mWp, hg * 128 + 64, kb * 2, bar + B_FULLQ + 8 * s);
            if (i >= 3) {
              if (i == 3) { mbar_wait(bar + B_DND, 0); PROF(14); }
#pragma unroll 1
              for (int a = i == 3 ? 2 : i; a <= i; a++) {
                const uint4* src = g_ofr + (mb * 16 + (a == 2 ? (hg == 0 ? 2 : 0) : kb)) * 1024;
#pragma unroll
                for (int h = 0; h < 2; h++) {
                  mbar_expect_tx(bar + B_AIN + (a & 3) * 16 + h * 8, 8192);
                  bulk_load(sb + (a & 3) * Q_STAGE + h * 8192, src + h * 512, 8192, bar + B_AIN + (a & 3) * 16 + h * 8);
                }
              }
            }
          }
        }
      }
    } else {
      if (f == 2) {
        if (PFD && ffn) {
#pragma unroll 1
          for (int i = 0; i < 16; i++) { touch_l2((const char*)P.w_down + fb * 65536 + i * 4096 + lane * 128, lane); __nanosleep(PFD); }
        }
        if (WOT) {
#pragma unroll 1
          for (int i = 0; i < 8; i++) { touch_l2((const char*)P.wo + ((mb & 7) * 128 + i * 16 + (lane >> 1)) * 2048 + hg * 256 + (lane & 1) * 128, lane); __nanosleep(PFD); }
        }
        asm volatile("cp.async.wait_all;" ::: "memory");
        uint4 u;
#pragma unroll 1
        for (int it = 0; it < SPIN_MAX; it++) {
          u = ld_rlx128(g_cs + hg * 128 + lane * 4);
          if (__all_sync(~0u, !(BAD4(u) & 1))) break;
          __nanosleep(200);
        }
        mbar_wait(bar + B_PHI, 0);
        float4 c = make_float4(unmark(u.x), unmark(u.y), unmark(u.z), unmark(u.w));
        CS_STORE(2, c);
        fence_async_smem();
        __syncwarp();
        if (lane == 0) mbar_arrive(bar + B_CSQ);
        if (ffn && !FFN_OFF) {
#pragma unroll 1
          for (int it = 0; it < SPIN_MAX; it++) {
            const uint32_t pg = ld_rlx((const uint32_t*)g_gp + fb * 32 + lane), pu = ld_rlx((const uint32_t*)g_gp + FF + fb * 32 + lane);
            if (__all_sync(~0u, !(((pg ^ par) | (pu ^ par)) & 1))) { gsum += unmark(pg); usum += unmark(pu); break; }
            __nanosleep(200);
          }
        }
        const float h = bf_round(silu_f(bf_round(gsum))) * bf_round(usum);
        const uint32_t h2 = pack2(h, h);
        sts128u(sb + SM_HT + lane * 16, h2, h2, h2, h2);
        fence_async_smem();
        __syncwarp();
        if (lane == 0) { mbar_arrive(bar + B_H); PROF(20); }
      }
      if (f < 2) {
        const uint32_t own = (hg * 2 + f) * 16 + mb, target = __shfl_sync(~0u, tag, 0) * 16;
        mbar_wait(bar + B_KVST + 8 * f, 0);
        if (f == 1 && lane == 0) PROF(11);
        wait_hint(g_xcnt + hg * 64 + f * 16 + mb, target);
        if (elect_one()) {
          PROF(35 + f);
          fence_async_global();
          mbar_expect_tx(bar + B_PART + 8 * f, 8192);
          bulk_load(sb + (f ? SM_PST1 : SM_PST0), g_part + own * 512, 8192, bar + B_PART + 8 * f);
        }
        __syncwarp();
        {
          uint4 uz;
#pragma unroll 1
          for (int it = 0; it < SPIN_MAX; it++) {
            uz = ld_rlx128(g_zpart + own * 128 + lane * 4);
            if (__all_sync(~0u, !(BAD4(uz) & 1))) break;
          }
          const bool b1 = lane & 2, b2 = lane & 4;
          const float z0 = unmark(b1 ? uz.z : uz.x) + __shfl_xor_sync(~0u, unmark(b1 ? uz.x : uz.z), 2);
          const float z1 = unmark(b1 ? uz.w : uz.y) + __shfl_xor_sync(~0u, unmark(b1 ? uz.y : uz.w), 2);
          float z = (b2 ? z1 : z0) + __shfl_xor_sync(~0u, b2 ? z0 : z1, 4);
          z += __shfl_xor_sync(~0u, z, 8);
          z += __shfl_xor_sync(~0u, z, 16);
          if (lane < 8) st_rlx(g_zres + own * 8 + (lane & 1) * 4 + (lane & 2) + (lane >> 2), mark(__float_as_uint(z), par));
          if (lane == 0) red_inc(g_xcnt + hg * 64 + 32 + f * 16);
          __syncwarp();
        }
        wait_hint(g_xcnt + hg * 64 + 32 + f * 16, 5 * target);
        mbar_wait(bar + B_KVST + 8, 0);
        if (lane == 0) PROF(40 + f);
#pragma unroll 1
        for (int it = 0; it < SPIN_MAX; it++) {
          if (elect_one()) {
            fence_async_global();
            mbar_expect_tx(bar + B_RES + 8 * f, 8192);
            bulk_load(sb + SM_V + f * 8192, g_res[par] + (hg * 4 + f * 2) * 256, 8192, bar + B_RES + 8 * f);
          }
          __syncwarp();
          const uint4 uz = ld_rlx128(g_zres + (hg * 4 + f * 2) * 64 + lane * 4);
          const uint32_t zw[4] = {uz.x, uz.y, uz.z, uz.w};
#pragma unroll
          for (int j = 0; j < 4; j++) {
            const uint32_t zz = pack2(unmark(zw[j]), 1.f), row = (lane & 3) * 4 + j;
            sts128u(sb + SM_ZT + (2 * f + (lane >> 4)) * 1024 + row * 64 + ((((lane >> 2) ^ (row >> 1)) & 3) << 4), zz, zz, zz, zz);
          }
          uint32_t bad = BAD4(uz);
          mbar_wait(bar + B_RES + 8 * f, it & 1);
#pragma unroll
          for (int i = 0; i < 16; i++) bad |= ~__float_as_uint(lds32(sb + SM_V + f * 8192 + i * 512 + lane * 16));
          if (__all_sync(~0u, !(bad & 1))) break;
        }
        fence_async_smem();
        __syncwarp();
        if (lane == 0) { mbar_arrive(bar + B_TILE + 8 * f); PROF(f ? 13 : 27); }
      }
      if (f < 2) {
        uint32_t phases = 0;
#pragma unroll 1
        for (int i = 2; i < 16; i++) {
          const int s = i & 3;
          const uint32_t ab = bar + B_AIN + s * 16 + f * 8, slot = sb + s * Q_STAGE + f * 8192;
#pragma unroll 1
          for (int it = 0; it < SPIN_MAX; it++) {
            mbar_wait(ab, (phases >> s) & 1);
            phases ^= 1u << s;
            uint32_t bad = 0;
#pragma unroll
            for (int n = 0; n < (NOVAL ? 0 : 8); n++) bad |= __float_as_uint(lds32(slot + n * 1024 + lane * 32 + (lane >> 2) * 4)) ^ par;
            if (__all_sync(~0u, !(bad & 1))) break;
            if (elect_one()) {
              const int n = i < 9 ? i - 2 : i - 9, kb = 2 * (n + (n >= hg)) + (i >= 9);
              PROF(49);
              mbar_expect_tx(ab, 8192);
              bulk_load(slot, g_ofr + (mb * 16 + kb) * 1024 + f * 512, 8192, ab);
            }
            __syncwarp();
          }
          if (lane == 0) { mbar_arrive(bar + B_FULLQ + 8 * s); if (i == 2 && f == 0) PROF(15); }
        }
        if (f == 0) g_epoch[bid * 32 + lane] = tag;
      } else {
        if (elect_one()) {
          prefetch_map(&mOut);
          if (ffn) { mbar_wait(bar + B_YD, 0); red_rel(g_ycnt); PROF(21); }
        }
        __syncwarp();
        if (f == 2) {
          const uint32_t best = __float_as_uint(lds32(sb + SM_RED + 20));
          const int sel = 2047 - (best & 0x7ff) - mb * 128;
          if (sel >= 0 && sel < 128) {
            const uint2 xr = __ldg((const uint2*)(P.x + (size_t)(mb * 128 + sel) * DM + hg * 128 + lane * 4));
            const float2 st = lds64(sb + SM_STAT + sel * 8);
            const uint32_t ord = best >> 16, rb = (ord & 0x8000u) ? (ord & 0x7fffu) : (~ord & 0xffffu);
            const float sg = rcp(1.f + ex2(-1.4426950408889634f * bf_lo(rb)));
            const uint32_t sg2 = pack2(sg, sg), nm2 = pack2(st.x, st.x);
            wait_cnt<0>(g_ycnt, tag * NFFN);
            float4 y = make_float4(0.f, 0.f, 0.f, 0.f);
#pragma unroll
            for (int i = 0; i < 8; i++) {
              const float4 c = ldg_cg4(g_y[par ^ 1][i] + hg * 128 + lane * 4);
              y.x += c.x; y.y += c.y; y.z += c.z; y.w += c.w;
            }
            uint32_t o[2];
#pragma unroll
            for (int i = 0; i < 2; i++) {
              const uint32_t d = badd2(i ? xr.y : xr.x, nm2);
              const uint32_t tt = badd2(pack2(bf_lo(d) * st.y, bf_hi(d) * st.y), bmul2(i ? pack2(y.z, y.w) : pack2(y.x, y.y), sg2));
              o[i] = pack2(silu_f(bf_lo(tt)), silu_f(bf_hi(tt)));
            }
            sts64u(sb + SM_UPD + lane * 8, o[0], o[1]);
          }
          if (lane == 0) sts32(sb + SM_UPD + 256, __int_as_float(sel));
          __syncwarp();
          if (lane == 0) { mbar_arrive(bar + B_UPD); PROF(22); }
        }
      }
    }
  } else {
    const int t7 = threadIdx.x & 127;
    const char* pfa = warp < 4 ? (const char*)P.x + bid * 32768 + (t7 & 15) * 2048 + (t7 >> 4) * 128
                               : (const char*)P.wqkv + (size_t)((t7 >> 4) * 64 + (bid >> 1)) * 6144 + 2048 + (bid & 1) * 2048 + (t7 & 15) * 128;
    if (t7 >= 16 && t7 < 16 * PF_FIRST) prefetch_l2(pfa);
    if (warp < 7) sts128(sb + SM_CST + threadIdx.x * 16, 0.f, 0.f, 0.f, 0.f);
    else sts32(sb + SM_RED + (threadIdx.x & 15) * 4, threadIdx.x & 8 ? 1.f : 0.f);
    if (elect_one()) {
#pragma unroll 1
      for (uint32_t b = B_FST + warp * 8; b < B_END; b += 64)
        mbar_init(bar + b, b < B_FULLQ ? 1 : b < B_FFN ? 3 : b < B_EMPTYKV ? 4 : 8);
    }
    __syncwarp();
    asm volatile("bar.arrive 13, 384;" ::: "memory");
    asm volatile("setmaxnreg.inc.sync.aligned.u32 %0;" ::"n"(REG_C));
    if (t7 >= 16 * PF_FIRST && threadIdx.x < 128 + 16 * PF_W) prefetch_l2(pfa);
    asm volatile("cp.async.wait_all;" ::: "memory");
    fence_async_smem();
    bar_sync(14, 288);
    if (threadIdx.x == 0) mbar_arrive(bar + B_FULLKV + 16);
    const int lane = lane_id();
    const int wg = warp >> 2, w = warp & 3, g = lane >> 2, t = lane & 3;
    float kv[128];
    {
      uint32_t s = 2, ph = 0, sp = 0, php = 0;
#pragma unroll 1
      for (int j = 0; j < 15; j++) {
        PW0(32 + j); mbar_wait(bar + B_FULLKV + 8 * s, ph); PW1(32 + j);
        if (wg == 1 && (ORDER_ALL || j == 0)) bar_sync(10 + s, 256);
        wg_fence();
        wgmma_n256_ssp_ta0_tb1(kv, mkdesc(sb, 16, 1024, 1, wg * 512 + s * (KV_STAGE / 16)), mkdesc(sb + 16384, 8192, 1024, 1, s * (KV_STAGE / 16)), j);
#pragma unroll
        for (int k = 1; k < 4; k++)
          wgmma_n256_ss_ta0_tb1(kv, mkdesc(sb + k * 32, 16, 1024, 1, wg * 512 + s * (KV_STAGE / 16)),
                                mkdesc(sb + 16384 + k * 2048, 8192, 1024, 1, s * (KV_STAGE / 16)), 1);
        wg_commit();
        if (wg == 0 && (ORDER_ALL || j == 0)) asm volatile("bar.arrive %0, 256;" ::"r"(10 + s) : "memory");
        if (warp == 0 && j) {
          mbar_wait(bar + B_EMPTYKV + 8 * sp, php);
          if (elect_one()) {
            if (j < 14) {
              mbar_expect_tx(bar + B_FULLKV + 8 * sp, KV_STAGE);
              tma2d(sb + sp * KV_STAGE, &mX, (j + 2) * 64, mb * 128, bar + B_FULLKV + 8 * sp);
              tma4d(sb + sp * KV_STAGE + 16384, &mWkv, 0, (j + 2) * 64, hg * 2, 1, bar + B_FULLKV + 8 * sp);
            } else {
              Q_LOAD(0);
            }
            if (j < 3 - XS_EARLY) {
              const int xh = j - 1 + XS_EARLY;
              mbar_expect_tx(bar + B_XST + 8 * xh, 16384);
              tma3d(sb + SM_XST + xh * 16384, &mXs, 0, bid * 16, 2 * xh, bar + B_XST + 8 * xh);
            }
          }
          __syncwarp();
        }
        if (j == 0) {
          if (wg == 0) prefetch_l2(pfa + 1024);
        } else if (wg == 1) {
          if (j < 3) {
            if (j == 2 || t7 >= 16 * PF_W) prefetch_l2(pfa + (j - 1) * (8 * 393216));
          } else if (j == 13) {
            prefetch_l2((const char*)P.wo + bid * 16384 + t7 * 128);
          }
          if (PFG && !FFN_OFF && bid < NFFN && j >= 2 && j < 2 + GROWS / 64 && w < 2)
            touch_l2((const char*)((bid & 1) ? P.w_up : P.w_gate) + (size_t)((0x852a7419630ull >> (4 * j - 8) & 15) * 64 + t7) * 7168 + (bid >> 1) * 128, lane);
        }
        wg_wait<0>();
        if (lane == 0) mbar_arrive(bar + B_EMPTYKV + 8 * s);
        sp = s; php = ph;
        ph ^= s == 1;
        s = s == 2 ? 0 : s + 1;
      }
    }
    const int lrow = wg * 64 + w * 16 + (lane & 15);
    const uint32_t sw128 = lrow * 128, x128 = (lrow & 7), hi16 = lane >> 4;
    mbar_wait(bar + B_CS, 0);
    const uint32_t tag = __float_as_uint(lds32(sb + SM_RED + 16));
    const int zero = __float_as_int(lds32(sb + SM_RED + 12));
    const float wn = lds32(sb + SM_RED + 24);
    const float2 st0 = lds64(sb + SM_STAT + (wg * 64 + w * 16 + g) * 8), st1 = lds64(sb + SM_STAT + (wg * 64 + w * 16 + g + 8) * 8);
    const float c0 = st0.y * 1.4426950408889634f, c1 = st1.y * 1.4426950408889634f;
    const uint32_t nm20 = pack2(st0.x, st0.x), nm21 = pack2(st1.x, st1.x), fmask = t == 0 ? ~0u : t == 1 ? 0xffffu : 0u;
    const uint32_t fa0 = nm20 & fmask, fa1 = nm21 & fmask;
    asm volatile("cp.async.wait_all;" ::: "memory");
    PW0(47); mbar_wait(bar + B_FULLKV + 16, 1); PW1(47);
    wg_fence();
    wgmma_n256_rs_ta0_tb1(kv, fa0, fa1, 0u, 0u, mkdesc(sb + SM_CST, 512, 0, 1), 1);
#pragma unroll
    for (int k = 0; k < 4; k++)
      wgmma_n256_ss_ta0_tb1(kv, mkdesc(sb + 2 * KV_STAGE + k * 32, 16, 1024, 1, wg * 512), mkdesc(sb + 2 * KV_STAGE + 16384 + k * 2048, 8192, 1024, 1), 1);
    wg_commit();
    if (warp == 0) {
      mbar_wait(bar + B_EMPTYKV + 8, 0);
      if (elect_one()) {
#pragma unroll 1
        for (int j = 1; j < 3; j++) Q_LOAD(j);
      }
      __syncwarp();
    }
    wg_wait<0>();
    reg_fence<128>(kv);
    if (lane == 0) mbar_arrive(bar + B_EMPTYKV + 16);
    PROFC(2);
    float q[64];
#define QMMA(J, AOFF16, ACCUM)                                                                                     \
  _Pragma("unroll") for (int k = 0; k < 4; k++)                                                                    \
      wgmma_n128_ss_ta0_tb1(q, mkdesc(sb + k * 32, 16, 1024, 1, wg * 512 + (AOFF16)),                              \
                            mkdesc(sb + 16384 + k * 2048, 8192, 1024, 1, ((J) & 3) * (Q_STAGE / 16)), k ? 1 : (ACCUM))
#define QWAIT(J) do { PW0(J); mbar_wait(bar + B_FULLQ + 8 * ((J) & 3), ((J) >> 2) & 1); PW1(J); } while (0)
#define QSTEP_A(J, AOFF16, ACCUM) do { QWAIT(J); wg_fence(); QMMA(J, AOFF16, ACCUM); wg_commit(); } while (0)
#define QREL(J) do { if (lane == 0) mbar_arrive(bar + B_EMPTYQ + 8 * ((J) & 3)); } while (0)
#define Q_OFF16(J) ((J) >= 8 && (J) < 16 ? Q_AOFF(J) / 16 : ((J) & 3) * (Q_STAGE / 16))
#define QPLAIN(J) do { QSTEP_A(J, Q_OFF16(J), 1); wg_wait<1>(); QREL((J) - 1); } while (0)
#define QNEXT(J) do { QPLAIN(J); SCHED_FENCE(); } while (0)
#define PHI_PROJ(DST, SRC, H0, H1)                                                                                 \
  do {                                                                                                             \
    uint32_t a_[32];                                                                                               \
    _Pragma("unroll") for (int j = 8 * (H0); j < 8 * (H1); j++) {                                                  \
      a_[j] = pack2(SRC[2 * j], SRC[2 * j + 1]);                                                                   \
      asm volatile("fma.rn.bf16x2 %0, %1, %1, %0;" : "+r"(nq[(j >> 4) * 2 + (j & 1)]) : "r"(a_[j]));               \
    }                                                                                                              \
    wg_fence();                                                                                                    \
    _Pragma("unroll") for (int hk = 2 * (H0); hk < 2 * (H1); hk++)                                                 \
        wgmma_n32_rs_ta0_tb1(DST + 16 * (hk >> 1), a_[4 * hk], a_[4 * hk + 1], a_[4 * hk + 2], a_[4 * hk + 3],     \
                             mkdesc(sb + SM_WPHI + hk * 1024, 16, 512, 2), hk & 1);                                \
    wg_commit();                                                                                                   \
  } while (0)
    {
      float p[64], ea[24], eb[24], sa[4], sc[4], kz[20];
      uint32_t vp[32];
#pragma unroll
      for (int j = 0; j < 32; j++) vp[j] = pack2(kv[64 + 2 * j], kv[65 + 2 * j]);
      const uint32_t vr = w * 16 + (lane & 15), vb = sb + SM_V + wg * 4096 + vr * 64, x64 = (vr >> 1) & 3;
#define V_STORE(R)                                                                                           \
  _Pragma("unroll") for (int j = 0; j < 4; j++)                                                              \
      stsm4(vb + (j >> 1) * 8192 + ((((j & 1) * 2 + hi16) ^ x64) << 4), vp[16 * (R) + 4 * j], vp[16 * (R) + 4 * j + 1], vp[16 * (R) + 4 * j + 2], vp[16 * (R) + 4 * j + 3])
      V_STORE(0);
      mbar_wait(bar + B_WPHI, 0);
      {
        uint32_t nq[4] = {0u, 0u, 0u, 0u};
        PHI_PROJ(p, kv, 0, 4);
        QSTEP_A(0, 0, 0);
        const bool unsafe = softmax_unsafe(nq, c0 * c0 * wn, c1 * c1 * wn);
        wg_wait<1>();
        reg_fence<64>(p);
        if (__builtin_expect(unsafe, 0)) softmax_shift(p, c0, c1);
      }
#define K_NORM(S) do { quad_sum<4>(S); _Pragma("unroll") for (int i = 0; i < 4; i++) S[i] = rcp(S[i]) * ((i & 1) ? st1.y : st0.y); } while (0)
#define K_STORE(SLOT, E, S) K_STORE_(SLOT, E, S, 0, 2)
#define K_STORE_(SLOT, E, S, J0, J1)                                                                         \
  _Pragma("unroll") for (int j = (J0); j < (J1); j++) {                                                      \
    uint32_t fp[4], fm[4];                                                                                   \
    _Pragma("unroll") for (int i = 0; i < 4; i++) {                                                          \
      const float e0 = E[8 * j + 2 * i], e1 = E[8 * j + 2 * i + 1], r = E[16 + 4 * j + i] * S[2 + (i & 1)];  \
      const uint32_t e2 = pack2(e0, e1);                                                                     \
      fp[i] = bmul2(e2, pack2(S[i & 1], S[i & 1]));                                                          \
      fm[i] = bmul2(e2, pack2(r, r));                                                                        \
    }                                                                                                        \
    stsm4(sb + SM_PHI + (SLOT) * 16384 + sw128 + (((2 * j + hi16) ^ x128) << 4), fp[0], fp[1], fp[2], fp[3]); \
    stsm4(sb + SM_PHI + (SLOT) * 16384 + sw128 + (((4 + 2 * j + hi16) ^ x128) << 4), fm[0], fm[1], fm[2], fm[3]); \
  }
#define KV_MMA(R)                                                                                            \
  do {                                                                                                       \
    mbar_wait(bar + B_PHI + 8 * (R), 0);                                                                     \
    wg_fence();                                                                                              \
    _Pragma("unroll") for (int k = 0; k < 8; k++) {                                                          \
      const uint32_t vs = SM_V + (k >> 2) * 4096 + (k & 3) * 1024;                                           \
      wgmma_n40_ss_ta1_tb1(kz, mkdesc(sb + SM_PHI + k * 2048, 16, 1024, 1, wg * 1024),                       \
                           mkdesc(sb + vs, SM_SDT + (k & 1) * 1024 + (k >> 1) * 16 - vs, 512, 2, wg * (512u - (512u << 16))), k); \
    }                                                                                                        \
    wg_commit();                                                                                             \
  } while (0)
#define QKV(J, R) do { KV_MMA(R); QSTEP_A(J, Q_OFF16(J), 1); wg_wait<2>(); QREL((J) - 1); SCHED_FENCE(); } while (0)
#define KV_SEND(R)                                                                                           \
  do {                                                                                                       \
    reg_fence<20>(kz);                                                                                       \
    if (lane == 0) mbar_arrive(bar + B_KVST + 8 * (R));                                                      \
    const uint32_t slot = ((hg * 2 + (R)) * 16 + warp * 2) * 16 + mb;                                        \
    _Pragma("unroll") for (int u = 0; u < 2; u++)                                                            \
      st_rlx128(g_part + (slot + u * 16) * 32 + lane, mark(pack2(kz[2 * u], kz[2 * u + 1]), tag & 1), pack2(kz[2 * u + 4], kz[2 * u + 5]), \
                pack2(kz[2 * u + 8], kz[2 * u + 9]), pack2(kz[2 * u + 12], kz[2 * u + 13]));                 \
    if (t < 2) st_rlx(g_zpart + (slot + t * 16) * 8 + g, mark(__float_as_uint(t ? kz[18] : kz[16]), tag & 1)); \
    if (lane < 2) red_inc(g_xcnt + hg * 64 + (R) * 16 + warp * 2 + lane);                                    \
  } while (0)
#define K_PUB(R) do { fence_async_smem(); __syncwarp(); if (lane == 0) mbar_arrive(bar + B_PHI + 8 * (R)); } while (0)
#define S_PIN(S) SCHED_PIN(S[0] + S[1] + S[2] + S[3])
      k_exp(p, c0, c1, ea, sa);
      S_PIN(sa);
      QNEXT(1);
      K_NORM(sa);
      k_exp<0, 4>(p + 16, c0, c1, eb, sc);
      mbar_wait(bar + B_FFN, 0);
      K_STORE_(0, ea, sa, 0, 1);
      S_PIN(sc);
      QNEXT(2);
      K_STORE_(0, ea, sa, 1, 2);
      k_exp<4, 8>(p + 16, c0, c1, eb, sc);
      K_NORM(sc);
      S_PIN(sc);
      QNEXT(3);
      K_STORE(1, eb, sc);
      K_PUB(0);
      k_exp<0, 4>(p + 32, c0, c1, ea, sa);
      S_PIN(sa);
      QKV(4, 0);
      k_exp<4, 8>(p + 32, c0, c1, ea, sa);
      K_NORM(sa);
      k_exp<0, 4>(p + 48, c0, c1, eb, sc);
      SCHED_PIN(sa[0] + sa[1] + sa[2] + sa[3] + sc[2] + sc[3]);
      QNEXT(5);
      KV_SEND(0);
      k_exp<4, 8>(p + 48, c0, c1, eb, sc);
      S_PIN(sc);
      QNEXT(6);
      K_NORM(sc);
      mbar_wait(bar + B_KVST, 0);
      V_STORE(1);
      K_STORE(0, ea, sa);
      QNEXT(7);
      K_STORE(1, eb, sc);
      K_PUB(1);
      QKV(8, 1);
      QNEXT(9);
      KV_SEND(1);
    }
#define JQ0 10
    PROFC(3);
    {
      bool todo = true;
#pragma unroll 1
      for (int j = JQ0; j < 15 || todo; j++) {
        if (j < 15) { QSTEP_A(j, Q_AOFF(j) / 16, 1); wg_wait<1>(); QREL(j - 1); }
        if (todo && __any_sync(~0u, mbar_test(bar + B_PART + 8 * wg, 0))) {
          todo = false;
          const uint32_t own = (hg * 2 + wg) * 16 + mb, word = w * 32 + lane;
          uint32_t u[16], bad = 0;
#pragma unroll
          for (int i = 0; i < 16; i++) { u[i] = __float_as_uint(lds32(sb + (wg ? SM_PST1 : SM_PST0) + i * 512 + word * 4)); bad |= u[i] ^ tag; }
#pragma unroll 1
          for (int it = 0; it < SPIN_MAX && __any_sync(~0u, t == 0 && (bad & 1)); it++) {
            bad = 0;
#pragma unroll
            for (int i = 0; i < 16; i++) { u[i] = ld_rlx((const uint32_t*)g_part + own * 2048 + i * 128 + word); bad |= u[i] ^ tag; }
          }
          float s0 = 0.f, s1 = 0.f, s2 = 0.f, s3 = 0.f;
#pragma unroll
          for (int i = 0; i < 16; i += 2) { s0 += bf_lo(u[i] | !t); s1 += bf_hi(u[i]); s2 += bf_lo(u[i + 1] & (t ? ~0u : ~1u)); s3 += bf_hi(u[i + 1]); }
          const uint32_t r = pack2(s0 + s2, s1 + s3);
          st_rlx((uint32_t*)g_res[tag & 1] + own * 128 + w * 32 + (lane & 16) + ((t ^ w) << 2) + ((lane >> 2) & 3), lane & 12 ? r : r | 1);
          ((uint32_t*)g_res[~tag & 1])[own * 128 + word] = 0;
          __syncwarp();
          if (lane == 0) { red_inc(g_xcnt + hg * 64 + 32 + wg * 16); if (w == 0) PROF(wg ? 12 : 30); }
          __syncwarp();
        }
      }
    }
    mbar_wait(bar + B_CSQ, 0);
    QWAIT(15);
    if (wg == 1) bar_sync(6, 256);
    wg_fence();
    wgmma_n128_rs_ta0_tb1(q, fa0, fa1, 0u, 0u, mkdesc(sb + SM_CST + 2048, 512, 0, 1), 1);
    QMMA(15, Q_AOFF(15) / 16, 1);
    wg_commit();
    if (wg == 0) asm volatile("bar.arrive 6, 256;" ::: "memory");
    wg_wait<1>();
    QREL(14);
    wg_wait<0>();
    QREL(15);
    reg_fence<64>(q);
    PROFC(5);
    float yp[4];
    const uint32_t par = tag & 1;
    uint4* ofr = g_ofr + (mb * 16 + hg * 2) * 1024 + (warp * 16 + g) * 8;
#define O_MMA(H, F, N)                                                                                       \
  do {                                                                                                       \
    wg_fence();                                                                                              \
    _Pragma("unroll") for (int k = 0; k < 4; k++) {                                                          \
      const uint32_t ks = SM_V + (H) * 4096 + k * 1024;                                                      \
      wgmma_n40_rs_ta0_tb1(N + 20 * (k >> 1), F[4 * k], F[4 * k + 1], F[4 * k + 2], F[4 * k + 3],            \
                           mkdesc(sb + ks, SM_ZT + (H) * 1024 + k * 16 - ks, 512, 2), k & 1);                \
    }                                                                                                        \
    wg_commit();                                                                                             \
  } while (0)
#define O_FIN(H, N, o)                                                                                        \
  do {                                                                                                       \
    reg_fence<40>(N);                                                                                        \
    const float *np = N, *nm = N + 20;                                                                       \
    const float d0 = rcp(fmaf(np[16], nm[17], fmaf(nm[16], np[17], 1e-6f * np[17] * nm[17])));               \
    const float d1 = rcp(fmaf(np[18], nm[19], fmaf(nm[18], np[19], 1e-6f * np[19] * nm[19])));               \
    const float bp0 = nm[17] * d0, bm0 = np[17] * d0, bp1 = nm[19] * d1, bm1 = np[19] * d1;                  \
    _Pragma("unroll") for (int j = 0; j < 4; j++) {                                                          \
      o[2 * j] = pack2(fmaf(np[4 * j], bp0, nm[4 * j] * bm0), fmaf(np[4 * j + 1], bp0, nm[4 * j + 1] * bm0)); \
      o[2 * j + 1] = pack2(fmaf(np[4 * j + 2], bp1, nm[4 * j + 2] * bm1), fmaf(np[4 * j + 3], bp1, nm[4 * j + 3] * bm1)); \
    }                                                                                                        \
  } while (0)
#define O_STG(H, o)                                                                                          \
  _Pragma("unroll") for (int u = 0; u < 2; u++) {                                                            \
    uint32_t v_[4];                                                                                          \
    _Pragma("unroll") for (int j = 0; j < 4; j++) v_[j] = lop_select(o[2 * j + u], parm, vword == j);        \
    st_rlx128(ofr + ((H) >> 1) * 1024 + u * 64 + ((((H) & 1) * 4 + t) ^ g), v_[0], v_[1], v_[2], v_[3]);     \
  }
    uint32_t gf[32], ao[16];
    const uint32_t parm = 0u - par, vword = ((t ^ g) & 1) == (g >> 2) ? g & 3 : 4;
    const float rh0 = 0.5f * st0.y, rh1 = 0.5f * st1.y, mh0 = st0.x * rh0, mh1 = st1.x * rh1;
#define GATE_LD(J) ldsm4(sb + ((J) >> 2 ? SM_X1 : SM_X0) + sw128 + (((((J) & 3) * 2 + hi16) ^ x128) << 4), gf[4 * (J)], gf[4 * (J) + 1], gf[4 * (J) + 2], gf[4 * (J) + 3])
#define GATE(I0, I1)                                                                                         \
  _Pragma("unroll") for (int i = (I0); i < (I1); i++) {                                                      \
    const float rs = (i & 1) ? rh1 : rh0, mh = (i & 1) ? mh1 : mh0;                                          \
    const float h0 = fmaf(bf_lo(gf[i]), rs, mh), h1 = fmaf(bf_hi(gf[i]), rs, mh);                            \
    gf[i] = pack2(fmaf(h0, tanh_approx(h0), h0), fmaf(h1, tanh_approx(h1), h1));                             \
  }
#define GATE_PIN(I0, I1) do { uint32_t o_ = 0; _Pragma("unroll") for (int i = (I0); i < (I1); i++) o_ |= gf[i]; SCHED_PIN(__uint_as_float(o_)); } while (0)
    {
      float p[64], na[40], nb[40];
      uint32_t fa[16], fb[16];
      {
        uint32_t nq[4] = {0u, 0u, 0u, 0u};
        PHI_PROJ(p, q, 0, 2);
        SCHED_FENCE();
        PHI_PROJ(p, q, 2, 4);
        const bool unsafe = softmax_unsafe(nq, c0 * c0 * wn, c1 * c1 * wn);
        if (TW == 0) mbar_wait(bar + B_TILE, 0);
        wg_wait<0>();
        reg_fence<64>(p);
        PROFC(24);
        if (__builtin_expect(unsafe, 0)) softmax_shift(p, c0, c1);
      }
      float dn[32];
#define DN_PART(A, B)                                                                                        \
  do {                                                                                                       \
    wg_fence();                                                                                              \
    _Pragma("unroll") for (int i = (A); i < (B); i++)                                                        \
      wgmma_n8_ss_ta1_tb1(dn + 4 * (i >> 1), mkdesc(sb + (i >> 3) * Q_STAGE + (i & 7) * 2048, 16, 1024, 1, wg * (2 * Q_STAGE / 16)), \
                          mkdesc(sb + SM_HT + (i & 1) * 256, 128, 128, 0), i & 1);                           \
  } while (0)
#define F_PIN(F, A, B) do { uint32_t o_ = 0; _Pragma("unroll") for (int i = (A); i < (B); i++) o_ |= F[8 + i]; SCHED_PIN(__uint_as_float(o_)); } while (0)
#define RMMA(J, A, ACCUM)                                                                                    \
  do {                                                                                                       \
    wg_fence();                                                                                              \
    _Pragma("unroll") for (int k = 0; k < 4; k++)                                                            \
      wgmma_n128_rs_ta0_tb1(q, (A)[4 * k], (A)[4 * k + 1], (A)[4 * k + 2], (A)[4 * k + 3],                   \
                            mkdesc(sb + 16384 + k * 2048, 8192, 1024, 1, ((J) & 3) * (Q_STAGE / 16)), k ? 1 : (ACCUM)); \
    wg_commit();                                                                                             \
  } while (0)
#define RSTEP(J, A, ACCUM) do { QWAIT(J); RMMA(J, A, ACCUM); } while (0)
      PROFC(4);
      q_exp(p, c0, c1, fa);
      if (TW == 1) { F_PIN(fa, 0, 8); mbar_wait(bar + B_TILE, 0); }
      if (TW == 2) { q_exp(p + 16, c0, c1, fb); F_PIN(fb, 0, 8); mbar_wait(bar + B_TILE, 0); }
      O_MMA(0, fa, na);
      if (TW != 2) q_exp(p + 16, c0, c1, fb);
      O_MMA(1, fb, nb);
      PROFC(25);
      wg_wait<1>();
      O_FIN(0, na, ao);
      O_STG(0, ao);
      wg_wait<0>();
      O_FIN(1, nb, (ao + 8));
      O_STG(1, (ao + 8));
      PROFC(28);
      RSTEP(16, ao, 0);
      SCHED_FENCE();
      q_exp(p + 32, c0, c1, fa);
      F_PIN(fa, 0, 8);
      mbar_wait(bar + B_H, 0);
      mbar_wait(bar + B_DN, 0);
      PROFC(45);
      DN_PART(0, 4);
      SCHED_FENCE();
      q_exp<0, 2>(p + 48, c0, c1, fb);
      F_PIN(fb, 0, 2);
      DN_PART(4, 8);
      SCHED_FENCE();
      q_exp<2, 4>(p + 48, c0, c1, fb);
      F_PIN(fb, 2, 4);
      DN_PART(8, 12);
      SCHED_FENCE();
      q_exp<4, 6>(p + 48, c0, c1, fb);
      F_PIN(fb, 4, 6);
      DN_PART(12, 16);
      wg_commit();
      SCHED_FENCE();
      q_exp<6, 8>(p + 48, c0, c1, fb);
      F_PIN(fb, 6, 8);
      wg_wait<0>();
      reg_fence<32>(dn);
      if (lane == 0) mbar_arrive(bar + B_DND);
      QREL(16);
#pragma unroll
      for (int i = 0; i < 4; i++) yp[i] = t & 2 ? (t & 1 ? dn[24 + 2 * i] : dn[16 + 2 * i]) : (t & 1 ? dn[8 + 2 * i] : dn[2 * i]);
      PROFC(29);
      mbar_wait(bar + B_TILE + 8, 0);
      PROFC(23);
      if (bid < NFFN) {
        float* y = g_y[par ^ 1][bid & 7] + wg * 512 + t * 128 + w * 16 + g;
#pragma unroll
        for (int i = 0; i < 4; i++) red1(y + (i >> 1) * 64 + (i & 1) * 8, yp[i]);
      }
      SCHED_FENCE();
      O_MMA(2, fa, na);
      O_MMA(3, fb, nb);
      __syncwarp();
      if (lane == 0) mbar_arrive(bar + B_YD);
      wg_wait<1>();
      O_FIN(2, na, ao);
      O_STG(2, ao);
      wg_wait<0>();
      O_FIN(3, nb, (ao + 8));
      O_STG(3, (ao + 8));
      PROFC(6);
    }
    RSTEP(17, ao, 1);
    SCHED_FENCE();
    GATE_LD(0); GATE_LD(1);
    GATE(0, 4);
    GATE_PIN(0, 4);
#define GSTEP(J, I) do { QNEXT(J); if ((I) < 7) GATE_LD(((I) + 1) & 7); GATE(4 * (I), 4 * (I) + 4); GATE_PIN(4 * (I), 4 * (I) + 4); } while (0)
    GSTEP(18, 1); GSTEP(19, 2); GSTEP(20, 3); GSTEP(21, 4); GSTEP(22, 5); GSTEP(23, 6); GSTEP(24, 7);
#pragma unroll 1
    for (int j = 25; j < 32 - TAILN; j++) QPLAIN(j);
    if (wg == 1) bar_sync(6, 256);
#pragma unroll 1
    for (int j = 32 - TAILN; j < 32; j++) QSTEP_A(j, (j & 3) * (Q_STAGE / 16), 1);
    if (wg == 0) asm volatile("bar.arrive 6, 256;" ::: "memory");
    mbar_wait(bar + B_UPD, 0);
    {
      const int sel = __float_as_int(lds32(sb + SM_UPD + 256)) - (wg * 64 + w * 16 + g);
      if (sel == 0 || sel == 8) {
#pragma unroll
        for (int j = 0; j < 16; j++) {
          const uint32_t u = __float_as_uint(lds32(sb + SM_UPD + j * 16 + t * 4));
          if (sel) gf[2 * j + 1] = u; else gf[2 * j] = u;
        }
      }
      __syncwarp();
      uint32_t xf[32];
#pragma unroll
      for (int j = 0; j < 8; j++)
        ldsm4(sb + (j >> 2 ? SM_X1 : SM_X0) + sw128 + ((((j & 3) * 2 + hi16) ^ x128) << 4), xf[4 * j], xf[4 * j + 1], xf[4 * j + 2], xf[4 * j + 3]);
      wg_wait<0>();
      reg_fence<64>(q);
      PROFC(8);
#pragma unroll
      for (int j = 0; j < 8; j++) {
        uint32_t o[4];
#pragma unroll
        for (int i = 0; i < 4; i++) o[i] = badd2(xf[4 * j + i], bmul2(pack2(q[8 * j + 2 * i], q[8 * j + 2 * i + 1]), gf[4 * j + i]));
        stsm4(sb + (j >> 2 ? SM_X1 : SM_X0) + sw128 + ((((j & 3) * 2 + hi16) ^ x128) << 4), o[0], o[1], o[2], o[3]);
      }
    }
    fence_async_smem();
    bar_sync(2 + wg, 128);
    if (w == 0 && elect_one()) {
      tma_store2d(&mOut, sb + SM_X0 + wg * 8192, hg * 128, mb * 128 + wg * 64);
      tma_store2d(&mOut, sb + SM_X1 + wg * 8192, hg * 128 + 64, mb * 128 + wg * 64);
      bulk_commit();
      bulk_wait_read0();
      if (wg == 1) { PROF(9); PROFT(33); PROF_DUMP; }
    }
  }
}

typedef CUresult (*EncodeFn)(CUtensorMap*, CUtensorMapDataType, cuuint32_t, void*, const cuuint64_t*, const cuuint64_t*, const cuuint32_t*,
                             const cuuint32_t*, CUtensorMapInterleave, CUtensorMapSwizzle, CUtensorMapL2promotion, CUtensorMapFloatOOBfill);

CUtensorMap make_map(EncodeFn enc, const void* ptr, int rank, const cuuint64_t* dims, const cuuint64_t* strides, const cuuint32_t* box, CUtensorMapSwizzle sw) {
  CUtensorMap m;
  const cuuint32_t es[5] = {1, 1, 1, 1, 1};
  enc(&m, CU_TENSOR_MAP_DATA_TYPE_BFLOAT16, rank, (void*)ptr, dims, strides, box, es, CU_TENSOR_MAP_INTERLEAVE_NONE, sw,
      CU_TENSOR_MAP_L2_PROMOTION_L2_128B, CU_TENSOR_MAP_FLOAT_OOB_FILL_NONE);
  return m;
}

}

extern "C" void kernel_launch(void* const* d_in, const int* in_sizes, int n_in, void* d_out, int out_size) {
  static EncodeFn enc = nullptr;
  static int by_sm = 0;
  if (!enc) {
    void* fn = nullptr;
    cudaDriverEntryPointQueryResult qr;
    cudaGetDriverEntryPoint("cuTensorMapEncodeTiled", &fn, cudaEnableDefault, &qr);
    enc = (EncodeFn)fn;
    cudaFuncSetAttribute(fused_kernel<false>, cudaFuncAttributeMaxDynamicSharedMemorySize, SM_TOTAL);
    cudaFuncSetAttribute(fused_kernel<true>, cudaFuncAttributeMaxDynamicSharedMemorySize, SM_TOTAL);
    int dev = 0, sms = 0;
    cudaGetDevice(&dev);
    cudaDeviceGetAttribute(&sms, cudaDevAttrMultiProcessorCount, dev);
    by_sm = BY_SM && sms == NCTA + NSPARE;
  }
  Params P;
  P.x = (const __nv_bfloat16*)d_in[0];
  P.wqkv = (const __nv_bfloat16*)d_in[1];
  const void* wphi = d_in[2];
  P.wo = (const __nv_bfloat16*)d_in[3];
  P.w_r = (const __nv_bfloat16*)d_in[5];
  P.w_gate = (const __nv_bfloat16*)d_in[6];
  P.w_up = (const __nv_bfloat16*)d_in[7];
  P.w_down = (const __nv_bfloat16*)d_in[8];

  const cuuint64_t dX[2] = {DM, SEQ}, sX[1] = {DM * 2};
  const cuuint32_t b128[2] = {64, 128}, b64[2] = {64, 64};
  const cuuint64_t dW[4] = {64, DM, 16, 3}, sW[3] = {3 * DM * 2, 128, DM * 2};
  const cuuint32_t bKV[4] = {64, 64, 2, 2}, bQ[4] = {64, 64, 2, 1};
  const cuuint64_t dO[3] = {64, DM, 16}, sO[2] = {DM * 2, 128};
  const cuuint32_t bO[3] = {64, 64, 2};
  const cuuint64_t dP[2] = {32, 1024}, sP[1] = {64};
  const cuuint32_t bP[2] = {32, 128};
  CUtensorMap mX = make_map(enc, P.x, 2, dX, sX, b128, CU_TENSOR_MAP_SWIZZLE_128B);
  CUtensorMap mWkv = make_map(enc, P.wqkv, 4, dW, sW, bKV, CU_TENSOR_MAP_SWIZZLE_128B);
  CUtensorMap mWq = make_map(enc, P.wqkv, 4, dW, sW, bQ, CU_TENSOR_MAP_SWIZZLE_128B);
  CUtensorMap mWo = make_map(enc, P.wo, 3, dO, sO, bO, CU_TENSOR_MAP_SWIZZLE_128B);
  CUtensorMap mPhi = make_map(enc, wphi, 2, dP, sP, bP, CU_TENSOR_MAP_SWIZZLE_64B);
  const cuuint64_t dWp[5] = {DM, 2, 4, 4, DM / 32}, sWp[4] = {DM * 2, 8 * DM * 2, 2 * DM * 2, 32 * DM * 2};
  const cuuint32_t bWp[5] = {64, 2, 4, 4, 2};
  CUtensorMap mWp = make_map(enc, P.wo, 5, dWp, sWp, bWp, CU_TENSOR_MAP_SWIZZLE_128B);
  CUtensorMap mOut = make_map(enc, d_out, 2, dX, sX, b64, CU_TENSOR_MAP_SWIZZLE_128B);
  const cuuint64_t dWc[2] = {3 * DM, DM}, sWc[1] = {3 * DM * 2}, dG[2] = {FF, DM}, sG[1] = {FF * 2}, dD[3] = {64, FF, 16};
  const cuuint32_t b32[2] = {32, 32}, bD[3] = {64, 32, 4};
  CUtensorMap mWc = make_map(enc, P.wqkv, 2, dWc, sWc, b32, CU_TENSOR_MAP_SWIZZLE_NONE);
  CUtensorMap mG = make_map(enc, P.w_gate, 2, dG, sG, b32, CU_TENSOR_MAP_SWIZZLE_NONE);
  CUtensorMap mU = make_map(enc, P.w_up, 2, dG, sG, b32, CU_TENSOR_MAP_SWIZZLE_NONE);
  CUtensorMap mD = make_map(enc, P.w_down, 3, dD, sO, bD, CU_TENSOR_MAP_SWIZZLE_128B);
  const cuuint64_t dXs[3] = {256, SEQ, 4}, sXs[2] = {DM * 2, 512};
  const cuuint32_t bXs[3] = {256, 16, 2};
  CUtensorMap mXs = make_map(enc, P.x, 3, dXs, sXs, bXs, CU_TENSOR_MAP_SWIZZLE_NONE);
  const cuuint64_t dG2[4] = {64, DM, FF / 64, 1}, sG2[3] = {FF * 2, 128, (cuuint64_t)FF * DM * 2};
  CUtensorMap mG2 = make_map(enc, P.w_gate, 4, dG2, sG2, bQ, CU_TENSOR_MAP_SWIZZLE_128B);
  CUtensorMap mU2 = make_map(enc, P.w_up, 4, dG2, sG2, bQ, CU_TENSOR_MAP_SWIZZLE_128B);
  (by_sm ? fused_kernel<true> : fused_kernel<false>)<<<NCTA + NSPARE, 384, SM_TOTAL, cudaStreamPerThread>>>(mX, mWkv, mWq, mWo, mPhi, mWp, mOut, mWc, mG, mU, mD, mXs,
                                                                                                           mG2, mU2, P);
}
```

```cpp
#include <cuda_runtime.h>
#include <cuda_bf16.h>
#include <cuda.h>
#include <stdint.h>

namespace {

constexpr int SEQ = 2048, DM = 1024, FF = 3584;
constexpr int NCTA = 128;
constexpr int NSPARE = 4;
constexpr int NFFN = FF / 32;
#define GN 6
#define G8 2
constexpr int GROWS = (3 * GN + G8) * 32;
#define TAILN 2
#define KTAIL 1
#define XS_EARLY 1
#define PF_FIRST 2
#define PF_W 5
#define PF_PRE 1
#define PFG 0
#define PFD 80
#define BY_SM 1
#define PTAB 0x73216540u
#define ROWSPLIT 1
#define WOT 1
#define PSPLIT 1
#define KSTEPS 4
#define NOVAL 0
#define KCH 1
#define REG_C 224
#define REG_H 56
#define TW 1
#define FENCE_KIND 2
#define SP_DELAY 3000
#define ORDER_ALL 1
#define AM_NS 100
constexpr bool FFN_OFF = false;

static_assert(2 * REG_C + REG_H <= 3 * 168, "the register pool of the CTA is 384 x 168");

__device__ uint32_t g_epoch[(NCTA + NSPARE) * 32];
__device__ unsigned long long g_stat[SEQ];
__device__ __align__(128) unsigned long long g_best[NCTA];
__device__ __align__(16) float g_y[2][8][DM];
__device__ __align__(128) uint32_t g_ycnt[64];
__device__ __align__(128) uint32_t g_xcnt[8 * 64];
__device__ __align__(128) uint4 g_res[2][32 * 256];
__device__ __align__(16) float g_cs[5 * DM];
__device__ __align__(128) float g_gp[2 * FF];
__device__ uint4 g_part[8 * 2 * 16 * 16 * 32];
__device__ __align__(16) float g_zpart[8 * 2 * 16 * 16 * 8];
__device__ __align__(128) float g_zres[32 * 64];
__device__ __align__(1024) uint4 g_ofr[16 * 16 * 1024];
#define PROF(i)
#define PROFT(i)
#define PROFC(i)
#define PROF_DUMP
#define PW0(J)
#define PW1(J)

constexpr uint32_t KV_STAGE = 49152, Q_STAGE = 32768;
constexpr uint32_t SM_V = 147456;
constexpr uint32_t SM_PHI = 163840;
constexpr uint32_t SM_XST = 147456;
constexpr uint32_t SM_FST = 172032;
constexpr uint32_t SM_PST0 = 196608, SM_PST1 = SM_PHI + 8192;
constexpr uint32_t SM_X0 = 131072, SM_X1 = SM_PHI + 16384;
constexpr uint32_t SM_WPHI = 204800;
constexpr uint32_t SM_ZT = 212992;
constexpr uint32_t SM_SDT = 217088;
constexpr uint32_t SM_CST = 219136;
constexpr uint32_t SM_HT = 222720;
constexpr uint32_t SM_STAT = 223232;
constexpr uint32_t SM_XSEL = 224256;
constexpr uint32_t SM_RED = 228352;
constexpr uint32_t SM_ROWS = SM_RED + 832;
constexpr uint32_t SM_GRED = SM_XSEL + 3072;
static_assert(GROWS <= 768, "xsel area");
constexpr uint32_t SM_UPD = 229632;
constexpr uint32_t SM_BAR = 230016;
constexpr uint32_t SM_PROF = 230464;
constexpr uint32_t SM_SINK = 231104;
constexpr uint32_t SM_TOTAL = 231616;
constexpr uint32_t SB = 1024;
constexpr uint32_t B_FULLKV = 0  , B_FST = 24  , B_XFULL = 88  , B_XST = 104  , B_WPHI = 120, B_CS = 128, B_CSQ = 136, B_UPD = 144,
                   B_H = 152, B_DN = 160, B_XS = 168, B_TILE = 176  , B_RES = 192  , B_PART = 208  ,
B_AIN = 224  ,
                   B_FULLQ = 288  ,
                   B_FFN = 320,
                   B_EMPTYKV = 328  , B_EMPTYQ = 352  , B_KVST = 384  , B_YD = 400, B_PHI = 408  , B_DND = 424, B_END = 432;

__device__ __forceinline__ uint32_t smem_u32(const void* p) { return (uint32_t)__cvta_generic_to_shared(p); }
__device__ __forceinline__ void mbar_init(uint32_t bar, uint32_t cnt) { asm volatile("mbarrier.init.shared::cta.b64 [%0], %1;" ::"r"(bar), "r"(cnt) : "memory"); }
__device__ __forceinline__ void mbar_expect_tx(uint32_t bar, uint32_t bytes) { asm volatile("mbarrier.arrive.expect_tx.shared::cta.b64 _, [%0], %1;" ::"r"(bar), "r"(bytes) : "memory"); }
__device__ __forceinline__ void mbar_arrive2(uint32_t bar) { asm volatile("mbarrier.arrive.shared::cta.b64 _, [%0], 2;" ::"r"(bar) : "memory"); }
__device__ __forceinline__ void mbar_arrive(uint32_t bar) { asm volatile("mbarrier.arrive.shared::cta.b64 _, [%0];" ::"r"(bar) : "memory"); }
__device__ __forceinline__ void mbar_wait(uint32_t bar, uint32_t parity) {
  asm volatile("{\n.reg .pred p;\nLW:\nmbarrier.try_wait.parity.shared::cta.b64 p, [%0], %1;\n@!p bra LW;\n}" ::"r"(bar), "r"(parity) : "memory");
}
__device__ __forceinline__ bool mbar_test(uint32_t bar, uint32_t parity) {
  uint32_t ok;
  asm volatile("{\n.reg .pred p;\nmbarrier.test_wait.parity.shared::cta.b64 p, [%1], %2;\nselp.u32 %0, 1, 0, p;\n}" : "=r"(ok) : "r"(bar), "r"(parity) : "memory");
  return ok;
}
__device__ __forceinline__ int lane_id() { int l; asm volatile("mov.u32 %0, %%laneid;" : "=r"(l)); return l; }
template <int C> __device__ __forceinline__ void sched_fence_(int zero) {
  asm volatile("{\n.reg .pred p;\nsetp.eq.s32 p, %0, %1;\n@p trap;\n}" ::"r"(zero), "n"(C) : "memory");
}
#define SCHED_FENCE() sched_fence_<1000 + __COUNTER__>(zero)
#define SCHED_PIN(V) sched_fence_<1000 + __COUNTER__>(zero & __float_as_int(V))
__device__ __forceinline__ bool elect_one() {
  uint32_t p; asm volatile("{ .reg .pred P; elect.sync _|P, 0xffffffff; selp.u32 %0, 1, 0, P; }" : "=r"(p)); return p;
}
__device__ __forceinline__ void tma2d(uint32_t dst, const CUtensorMap* m, int x, int y, uint32_t bar) {
  asm volatile("cp.async.bulk.tensor.2d.shared::cluster.global.mbarrier::complete_tx::bytes [%0], [%1, {%3, %4}], [%2];" ::"r"(dst), "l"(m), "r"(bar), "r"(x), "r"(y) : "memory");
}
__device__ __forceinline__ void tma3d(uint32_t dst, const CUtensorMap* m, int x, int y, int z, uint32_t bar) {
  asm volatile("cp.async.bulk.tensor.3d.shared::cluster.global.mbarrier::complete_tx::bytes [%0], [%1, {%3, %4, %5}], [%2];" ::"r"(dst), "l"(m), "r"(bar), "r"(x), "r"(y), "r"(z) : "memory");
}
__device__ __forceinline__ void tma4d(uint32_t dst, const CUtensorMap* m, int x, int y, int z, int w, uint32_t bar) {
  asm volatile("cp.async.bulk.tensor.4d.shared::cluster.global.mbarrier::complete_tx::bytes [%0], [%1, {%3, %4, %5, %6}], [%2];" ::"r"(dst), "l"(m), "r"(bar), "r"(x), "r"(y), "r"(z), "r"(w) : "memory");
}
__device__ __forceinline__ void tma5d(uint32_t dst, const CUtensorMap* m, int x, int v, uint32_t bar) {
  asm volatile("cp.async.bulk.tensor.5d.shared::cluster.global.mbarrier::complete_tx::bytes [%0], [%1, {%3, %5, %5, %5, %4}], [%2];" ::"r"(dst), "l"(m), "r"(bar), "r"(x), "r"(v), "r"(0) : "memory");
}
__device__ __forceinline__ void tma_store2d(const CUtensorMap* m, uint32_t src, int x, int y) {
  asm volatile("cp.async.bulk.tensor.2d.global.shared::cta.bulk_group [%0, {%2, %3}], [%1];" ::"l"(m), "r"(src), "r"(x), "r"(y) : "memory");
}
__device__ __forceinline__ void bulk_load(uint32_t dst, const void* src, uint32_t bytes, uint32_t bar) {
  asm volatile("cp.async.bulk.shared::cluster.global.mbarrier::complete_tx::bytes [%0], [%1], %2, [%3];" ::"r"(dst), "l"(src), "r"(bytes), "r"(bar) : "memory");
}
__device__ __forceinline__ void bulk_commit() { asm volatile("cp.async.bulk.commit_group;" ::: "memory"); }
__device__ __forceinline__ void bulk_wait0() { asm volatile("cp.async.bulk.wait_group 0;" ::: "memory"); }
__device__ __forceinline__ void bulk_wait_read0() { asm volatile("cp.async.bulk.wait_group.read 0;" ::: "memory"); }
__device__ __forceinline__ void prefetch_l2(const void* p) { asm volatile("prefetch.global.L2 [%0];" ::"l"(p) : "memory"); }
__device__ __forceinline__ void touch_l2(const void* p, int lane) { asm volatile("cp.async.cg.shared.global.L2::128B [%0], [%1], 16;" ::"r"(SB + SM_SINK + lane * 16), "l"(p) : "memory"); }
__device__ __forceinline__ void cp_async16(uint32_t dst, const void* src) { asm volatile("cp.async.cg.shared.global [%0], [%1], 16;" ::"r"(dst), "l"(src) : "memory"); }
__device__ __forceinline__ void prefetch_map(const CUtensorMap* m) { asm volatile("prefetch.tensormap [%0];" ::"l"(m) : "memory"); }
__device__ __forceinline__ void fence_async_smem() { asm volatile("fence.proxy.async.shared::cta;" ::: "memory"); }
__device__ __forceinline__ void fence_async_global() { asm volatile("fence.proxy.async.global;" ::: "memory"); }
__device__ __forceinline__ void bar_sync(int id, int n) { asm volatile("bar.sync %0, %1;" ::"r"(id), "r"(n) : "memory"); }
__device__ __forceinline__ void wg_fence() { asm volatile("wgmma.fence.sync.aligned;" ::: "memory"); }
__device__ __forceinline__ void wg_commit() { asm volatile("wgmma.commit_group.sync.aligned;" ::: "memory"); }
template <int N> __device__ __forceinline__ void wg_wait() { asm volatile("wgmma.wait_group.sync.aligned %0;" ::"n"(N) : "memory"); }
template <int N> __device__ __forceinline__ void reg_fence(uint32_t* r) {
#pragma unroll
  for (int i = 0; i < N; i++) asm volatile("" : "+r"(r[i])::"memory");
}
template <int N> __device__ __forceinline__ void reg_fence(float* r) {
#pragma unroll
  for (int i = 0; i < N; i++) asm volatile("" : "+f"(r[i])::"memory");
}
__device__ __forceinline__ uint64_t mkdesc(uint32_t addr, uint32_t lbo, uint32_t sbo, uint32_t swz, uint32_t dyn = 0) {
  const uint32_t lo = ((addr >> 4) | ((lbo >> 4) << 16)) + dyn;
  const uint32_t hi = (sbo >> 4) | (swz << 30);
  uint64_t d;
  asm("mov.b64 %0, {%1, %2};" : "=l"(d) : "r"(lo), "r"(hi));
  return d;
}
__device__ __forceinline__ void stsm4(uint32_t addr, uint32_t a, uint32_t b, uint32_t c, uint32_t d) {
  asm volatile("stmatrix.sync.aligned.m8n8.x4.shared.b16 [%0], {%1, %2, %3, %4};" ::"r"(addr), "r"(a), "r"(b), "r"(c), "r"(d) : "memory");
}
__device__ __forceinline__ void ldsm4(uint32_t addr, uint32_t& a, uint32_t& b, uint32_t& c, uint32_t& d) {
  asm volatile("ldmatrix.sync.aligned.m8n8.x4.shared.b16 {%0, %1, %2, %3}, [%4];" : "=r"(a), "=r"(b), "=r"(c), "=r"(d) : "r"(addr) : "memory");
}
__device__ __forceinline__ uint32_t pack2(float lo, float hi) { uint32_t r; asm("cvt.rn.bf16x2.f32 %0, %1, %2;" : "=r"(r) : "f"(hi), "f"(lo)); return r; }
__device__ __forceinline__ uint32_t bsub2(uint32_t a, uint32_t b) { uint32_t r; asm("sub.rn.bf16x2 %0, %1, %2;" : "=r"(r) : "r"(a), "r"(b)); return r; }
__device__ __forceinline__ uint32_t badd2(uint32_t a, uint32_t b) { uint32_t r; asm("add.rn.bf16x2 %0, %1, %2;" : "=r"(r) : "r"(a), "r"(b)); return r; }
__device__ __forceinline__ uint32_t bmul2(uint32_t a, uint32_t b) { uint32_t r; asm("mul.rn.bf16x2 %0, %1, %2;" : "=r"(r) : "r"(a), "r"(b)); return r; }
__device__ __forceinline__ float bf_lo(uint32_t v) { return __uint_as_float(v << 16); }
__device__ __forceinline__ float bf_hi(uint32_t v) { return __uint_as_float(v & 0xffff0000u); }
__device__ __forceinline__ float bf_round(float v) { return bf_lo(pack2(v, 0.f)); }
__device__ __forceinline__ float ex2(float v) { float r; asm("ex2.approx.ftz.f32 %0, %1;" : "=f"(r) : "f"(v)); return r; }
__device__ __forceinline__ float rcp(float v) { float r; asm("rcp.approx.ftz.f32 %0, %1;" : "=f"(r) : "f"(v)); return r; }
__device__ __forceinline__ float sqrt_approx(float v) { float r; asm("sqrt.approx.f32 %0, %1;" : "=f"(r) : "f"(v)); return r; }
__device__ __forceinline__ float4 lds128(uint32_t a) { float4 v; asm volatile("ld.shared.v4.f32 {%0, %1, %2, %3}, [%4];" : "=f"(v.x), "=f"(v.y), "=f"(v.z), "=f"(v.w) : "r"(a) : "memory"); return v; }
__device__ __forceinline__ uint4 lds128u(uint32_t a) { uint4 v; asm volatile("ld.shared.v4.u32 {%0, %1, %2, %3}, [%4];" : "=r"(v.x), "=r"(v.y), "=r"(v.z), "=r"(v.w) : "r"(a) : "memory"); return v; }
__device__ __forceinline__ float2 lds64(uint32_t a) { float2 v; asm volatile("ld.shared.v2.f32 {%0, %1}, [%2];" : "=f"(v.x), "=f"(v.y) : "r"(a) : "memory"); return v; }
__device__ __forceinline__ float lds32(uint32_t a) { float v; asm volatile("ld.shared.f32 %0, [%1];" : "=f"(v) : "r"(a) : "memory"); return v; }
__device__ __forceinline__ void sts32(uint32_t a, float v) { asm volatile("st.shared.f32 [%0], %1;" ::"r"(a), "f"(v) : "memory"); }
__device__ __forceinline__ void sts64(uint32_t a, float x, float y) { asm volatile("st.shared.v2.f32 [%0], {%1, %2};" ::"r"(a), "f"(x), "f"(y) : "memory"); }
__device__ __forceinline__ void sts128(uint32_t a, float x, float y, float z, float w) { asm volatile("st.shared.v4.f32 [%0], {%1, %2, %3, %4};" ::"r"(a), "f"(x), "f"(y), "f"(z), "f"(w) : "memory"); }
__device__ __forceinline__ void sts64u(uint32_t a, uint32_t x, uint32_t y) { asm volatile("st.shared.v2.u32 [%0], {%1, %2};" ::"r"(a), "r"(x), "r"(y) : "memory"); }
__device__ __forceinline__ void sts128u(uint32_t a, uint32_t x, uint32_t y, uint32_t z, uint32_t w) { asm volatile("st.shared.v4.u32 [%0], {%1, %2, %3, %4};" ::"r"(a), "r"(x), "r"(y), "r"(z), "r"(w) : "memory"); }
__device__ __forceinline__ uint4 ldg_nc(const void* p) { uint4 v; asm volatile("ld.global.nc.L1::no_allocate.v4.u32 {%0, %1, %2, %3}, [%4];" : "=r"(v.x), "=r"(v.y), "=r"(v.z), "=r"(v.w) : "l"(p)); return v; }
__device__ __forceinline__ float4 ldg_cg4(const float* p) { float4 v; asm volatile("ld.global.cg.v4.f32 {%0, %1, %2, %3}, [%4];" : "=f"(v.x), "=f"(v.y), "=f"(v.z), "=f"(v.w) : "l"(p) : "memory"); return v; }
__device__ __forceinline__ uint32_t ld_acq(const uint32_t* p) { uint32_t v; asm volatile("ld.acquire.gpu.global.u32 %0, [%1];" : "=r"(v) : "l"(p) : "memory"); return v; }
__device__ __forceinline__ uint32_t ld_acq_cta(uint32_t a) { uint32_t v; asm volatile("ld.acquire.cta.shared.u32 %0, [%1];" : "=r"(v) : "r"(a) : "memory"); return v; }
__device__ __forceinline__ void st_rel_cta(uint32_t a, uint32_t v) { asm volatile("st.release.cta.shared.u32 [%0], %1;" ::"r"(a), "r"(v) : "memory"); }
__device__ __forceinline__ unsigned long long ld_rlx64(const unsigned long long* p) { unsigned long long v; asm volatile("ld.relaxed.gpu.global.u64 %0, [%1];" : "=l"(v) : "l"(p) : "memory"); return v; }
__device__ __forceinline__ void st_rlx64(unsigned long long* p, unsigned long long v) { asm volatile("st.relaxed.gpu.global.u64 [%0], %1;" ::"l"(p), "l"(v) : "memory"); }
__device__ __forceinline__ uint4 ld_rlx128(const void* p) {
  uint4 v;
  asm volatile("{ .reg .b128 t; .reg .b64 a, b; ld.relaxed.gpu.global.b128 t, [%4]; mov.b128 {a, b}, t; mov.b64 {%0, %1}, a; mov.b64 {%2, %3}, b; }"
               : "=r"(v.x), "=r"(v.y), "=r"(v.z), "=r"(v.w) : "l"(p) : "memory");
  return v;
}
__device__ __forceinline__ void st_rlx128(void* p, uint32_t x, uint32_t y, uint32_t z, uint32_t w) {
  asm volatile("{ .reg .b128 t; .reg .b64 a, b; mov.b64 a, {%1, %2}; mov.b64 b, {%3, %4}; mov.b128 t, {a, b}; st.relaxed.gpu.global.b128 [%0], t; }"
               ::"l"(p), "r"(x), "r"(y), "r"(z), "r"(w) : "memory");
}
__device__ __forceinline__ void stg128(void* p, uint32_t x, uint32_t y, uint32_t z, uint32_t w) { asm volatile("st.global.v4.u32 [%0], {%1, %2, %3, %4};" ::"l"(p), "r"(x), "r"(y), "r"(z), "r"(w) : "memory"); }
__device__ __forceinline__ void st_rlx(void* p, uint32_t v) { asm volatile("st.relaxed.gpu.global.u32 [%0], %1;" ::"l"(p), "r"(v) : "memory"); }
__device__ __forceinline__ uint32_t lop_select(uint32_t a, uint32_t b, uint32_t m) { uint32_t r; asm("lop3.b32 %0, %1, %2, %3, 0xd8;" : "=r"(r) : "r"(a), "r"(b), "r"(m)); return r; }
__device__ __forceinline__ float unmark(uint32_t v) { return __uint_as_float(v & ~1u); }
__device__ __forceinline__ uint32_t mark(uint32_t v, uint32_t par) { return (v & ~1u) | par; }
__device__ __forceinline__ float tanh_approx(float v) { float r; asm("tanh.approx.f32 %0, %1;" : "=f"(r) : "f"(v)); return r; }
__device__ __forceinline__ void flag_rel(uint32_t* p, uint32_t v) { asm volatile("red.release.gpu.global.max.u32 [%0], %1;" ::"l"(p), "r"(v) : "memory"); }
__device__ __forceinline__ void red1(float* p, float a) { asm volatile("red.global.add.f32 [%0], %1;" ::"l"(p), "f"(a) : "memory"); }
__device__ __forceinline__ void red_inc(uint32_t* p) { asm volatile("red.relaxed.gpu.global.add.u32 [%0], 1;" ::"l"(p) : "memory"); }
__device__ __forceinline__ void red_rel(uint32_t* p) { asm volatile("red.release.gpu.global.add.u32 [%0], 1;" ::"l"(p) : "memory"); }
__device__ __forceinline__ void red4(float* p, float a, float b, float c, float d) { asm volatile("red.global.add.v4.f32 [%0], {%1, %2, %3, %4};" ::"l"(p), "f"(a), "f"(b), "f"(c), "f"(d) : "memory"); }
constexpr int SPIN_MAX = 100000;
__device__ __forceinline__ uint32_t ld_rlx(const uint32_t* p) { uint32_t v; asm volatile("ld.relaxed.gpu.global.u32 %0, [%1];" : "=r"(v) : "l"(p) : "memory"); return v; }
template <int NS = 0> __device__ __forceinline__ void wait_hint(const uint32_t* p, uint32_t target) {
#pragma unroll 1
  for (int i = 0; i < SPIN_MAX; i++) { if ((int)(ld_rlx(p) - target) >= 0) break; if (NS) __nanosleep(NS); }
}
template <int NS> __device__ __forceinline__ void wait_cnt(const uint32_t* p, uint32_t target) {
#pragma unroll 1
  for (int i = 0; i < SPIN_MAX; i++) { if ((int)(ld_rlx(p) - target) >= 0) break; if (NS) __nanosleep(NS); }
  (void)ld_acq(p);
}
template <int NS> __device__ __forceinline__ unsigned long long wait_tag(const unsigned long long* p, uint32_t tag) {
  unsigned long long v = 0;
#pragma unroll 1
  for (int i = 0; i < SPIN_MAX; i++) { v = ld_rlx64(p); if ((uint32_t)(v >> 32) == tag) break; if (NS) __nanosleep(NS); }
  return v;
}
__device__ __forceinline__ float silu_f(float v) { return v * rcp(1.f + ex2(-1.4426950408889634f * v)); }

__device__ __forceinline__ void wgmma_n8_ss_ta1_tb0(float* d, uint64_t da, uint64_t db, bool accumulate) {
  if (accumulate) {
    asm volatile("{\n.reg .pred p;\nsetp.ne.b32 p, 1, 0;\n"
      "wgmma.mma_async.sync.aligned.m64n8k16.f32.bf16.bf16 "
      "{%0, %1, %2, %3}, "
      "%4, %5, p, 1, 1, 1, 0;\n}\n"
      : "+f"(d[0]), "+f"(d[1]), "+f"(d[2]), "+f"(d[3])
      : "l"(da), "l"(db));
  } else {
    asm volatile("{\n.reg .pred p;\nsetp.ne.b32 p, 0, 0;\n"
      "wgmma.mma_async.sync.aligned.m64n8k16.f32.bf16.bf16 "
      "{%0, %1, %2, %3}, "
      "%4, %5, p, 1, 1, 1, 0;\n}\n"
      : "=f"(d[0]), "=f"(d[1]), "=f"(d[2]), "=f"(d[3])
      : "l"(da), "l"(db));
  }
}
__device__ __forceinline__ void wgmma_n8_ss_ta1_tb1(float* d, uint64_t da, uint64_t db, bool accumulate) {
  if (accumulate) {
    asm volatile("{\n.reg .pred p;\nsetp.ne.b32 p, 1, 0;\n"
      "wgmma.mma_async.sync.aligned.m64n8k16.f32.bf16.bf16 "
      "{%0, %1, %2, %3}, "
      "%4, %5, p, 1, 1, 1, 1;\n}\n"
      : "+f"(d[0]), "+f"(d[1]), "+f"(d[2]), "+f"(d[3])
      : "l"(da), "l"(db));
  } else {
    asm volatile("{\n.reg .pred p;\nsetp.ne.b32 p, 0, 0;\n"
      "wgmma.mma_async.sync.aligned.m64n8k16.f32.bf16.bf16 "
      "{%0, %1, %2, %3}, "
      "%4, %5, p, 1, 1, 1, 1;\n}\n"
      : "=f"(d[0]), "=f"(d[1]), "=f"(d[2]), "=f"(d[3])
      : "l"(da), "l"(db));
  }
}
__device__ __forceinline__ void wgmma_n32_rs_ta0_tb1(float* d, uint32_t a0, uint32_t a1, uint32_t a2, uint32_t a3, uint64_t db, bool accumulate) {
  if (accumulate) {
    asm volatile("{\n.reg .pred p;\nsetp.ne.b32 p, 1, 0;\n"
      "wgmma.mma_async.sync.aligned.m64n32k16.f32.bf16.bf16 "
      "{%0, %1, %2, %3, %4, %5, %6, %7, %8, %9, %10, %11, %12, %13, %14, %15}, "
      "{%16, %17, %18, %19}, %20, p, 1, 1, 1;\n}\n"
      : "+f"(d[0]), "+f"(d[1]), "+f"(d[2]), "+f"(d[3]), "+f"(d[4]), "+f"(d[5]), "+f"(d[6]), "+f"(d[7]), "+f"(d[8]), "+f"(d[9]), "+f"(d[10]), "+f"(d[11]), "+f"(d[12]), "+f"(d[13]), "+f"(d[14]), "+f"(d[15])
      : "r"(a0), "r"(a1), "r"(a2), "r"(a3), "l"(db));
  } else {
    asm volatile("{\n.reg .pred p;\nsetp.ne.b32 p, 0, 0;\n"
      "wgmma.mma_async.sync.aligned.m64n32k16.f32.bf16.bf16 "
      "{%0, %1, %2, %3, %4, %5, %6, %7, %8, %9, %10, %11, %12, %13, %14, %15}, "
      "{%16, %17, %18, %19}, %20, p, 1, 1, 1;\n}\n"
      : "=f"(d[0]), "=f"(d[1]), "=f"(d[2]), "=f"(d[3]), "=f"(d[4]), "=f"(d[5]), "=f"(d[6]), "=f"(d[7]), "=f"(d[8]), "=f"(d[9]), "=f"(d[10]), "=f"(d[11]), "=f"(d[12]), "=f"(d[13]), "=f"(d[14]), "=f"(d[15])
      : "r"(a0), "r"(a1), "r"(a2), "r"(a3), "l"(db));
  }
}
__device__ __forceinline__ void wgmma_n40_rs_ta0_tb1(float* d, uint32_t a0, uint32_t a1, uint32_t a2, uint32_t a3, uint64_t db, bool accumulate) {
  if (accumulate) {
    asm volatile("{\n.reg .pred p;\nsetp.ne.b32 p, 1, 0;\n"
      "wgmma.mma_async.sync.aligned.m64n40k16.f32.bf16.bf16 "
      "{%0, %1, %2, %3, %4, %5, %6, %7, %8, %9, %10, %11, %12, %13, %14, %15, %16, %17, %18, %19}, "
      "{%20, %21, %22, %23}, %24, p, 1, 1, 1;\n}\n"
      : "+f"(d[0]), "+f"(d[1]), "+f"(d[2]), "+f"(d[3]), "+f"(d[4]), "+f"(d[5]), "+f"(d[6]), "+f"(d[7]), "+f"(d[8]), "+f"(d[9]), "+f"(d[10]), "+f"(d[11]), "+f"(d[12]), "+f"(d[13]), "+f"(d[14]), "+f"(d[15]), "+f"(d[16]), "+f"(d[17]), "+f"(d[18]), "+f"(d[19])
      : "r"(a0), "r"(a1), "r"(a2), "r"(a3), "l"(db));
  } else {
    asm volatile("{\n.reg .pred p;\nsetp.ne.b32 p, 0, 0;\n"
      "wgmma.mma_async.sync.aligned.m64n40k16.f32.bf16.bf16 "
      "{%0, %1, %2, %3, %4, %5, %6, %7, %8, %9, %10, %11, %12, %13, %14, %15, %16, %17, %18, %19}, "
      "{%20, %21, %22, %23}, %24, p, 1, 1, 1;\n}\n"
      : "=f"(d[0]), "=f"(d[1]), "=f"(d[2]), "=f"(d[3]), "=f"(d[4]), "=f"(d[5]), "=f"(d[6]), "=f"(d[7]), "=f"(d[8]), "=f"(d[9]), "=f"(d[10]), "=f"(d[11]), "=f"(d[12]), "=f"(d[13]), "=f"(d[14]), "=f"(d[15]), "=f"(d[16]), "=f"(d[17]), "=f"(d[18]), "=f"(d[19])
      : "r"(a0), "r"(a1), "r"(a2), "r"(a3), "l"(db));
  }
}
__device__ __forceinline__ void wgmma_n40_ss_ta1_tb1(float* d, uint64_t da, uint64_t db, bool accumulate) {
  if (accumulate) {
    asm volatile("{\n.reg .pred p;\nsetp.ne.b32 p, 1, 0;\n"
      "wgmma.mma_async.sync.aligned.m64n40k16.f32.bf16.bf16 "
      "{%0, %1, %2, %3, %4, %5, %6, %7, %8, %9, %10, %11, %12, %13, %14, %15, %16, %17, %18, %19}, "
      "%20, %21, p, 1, 1, 1, 1;\n}\n"
      : "+f"(d[0]), "+f"(d[1]), "+f"(d[2]), "+f"(d[3]), "+f"(d[4]), "+f"(d[5]), "+f"(d[6]), "+f"(d[7]), "+f"(d[8]), "+f"(d[9]), "+f"(d[10]), "+f"(d[11]), "+f"(d[12]), "+f"(d[13]), "+f"(d[14]), "+f"(d[15]), "+f"(d[16]), "+f"(d[17]), "+f"(d[18]), "+f"(d[19])
      : "l"(da), "l"(db));
  } else {
    asm volatile("{\n.reg .pred p;\nsetp.ne.b32 p, 0, 0;\n"
      "wgmma.mma_async.sync.aligned.m64n40k16.f32.bf16.bf16 "
      "{%0, %1, %2, %3, %4, %5, %6, %7, %8, %9, %10, %11, %12, %13, %14, %15, %16, %17, %18, %19}, "
      "%20, %21, p, 1, 1, 1, 1;\n}\n"
      : "=f"(d[0]), "=f"(d[1]), "=f"(d[2]), "=f"(d[3]), "=f"(d[4]), "=f"(d[5]), "=f"(d[6]), "=f"(d[7]), "=f"(d[8]), "=f"(d[9]), "=f"(d[10]), "=f"(d[11]), "=f"(d[12]), "=f"(d[13]), "=f"(d[14]), "=f"(d[15]), "=f"(d[16]), "=f"(d[17]), "=f"(d[18]), "=f"(d[19])
      : "l"(da), "l"(db));
  }
}
__device__ __forceinline__ void wgmma_n128_rs_ta0_tb1(float* d, uint32_t a0, uint32_t a1, uint32_t a2, uint32_t a3, uint64_t db, bool accumulate) {
  if (accumulate) {
    asm volatile("{\n.reg .pred p;\nsetp.ne.b32 p, 1, 0;\n"
      "wgmma.mma_async.sync.aligned.m64n128k16.f32.bf16.bf16 "
      "{%0, %1, %2, %3, %4, %5, %6, %7, %8, %9, %10, %11, %12, %13, %14, %15, %16, %17, %18, %19, %20, %21, %22, %23, %24, %25, %26, %27, %28, %29, %30, %31, %32, %33, %34, %35, %36, %37, %38, %39, %40, %41, %42, %43, %44, %45, %46, %47, %48, %49, %50, %51, %52, %53, %54, %55, %56, %57, %58, %59, %60, %61, %62, %63}, "
      "{%64, %65, %66, %67}, %68, p, 1, 1, 1;\n}\n"
      : "+f"(d[0]), "+f"(d[1]), "+f"(d[2]), "+f"(d[3]), "+f"(d[4]), "+f"(d[5]), "+f"(d[6]), "+f"(d[7]), "+f"(d[8]), "+f"(d[9]), "+f"(d[10]), "+f"(d[11]), "+f"(d[12]), "+f"(d[13]), "+f"(d[14]), "+f"(d[15]), "+f"(d[16]), "+f"(d[17]), "+f"(d[18]), "+f"(d[19]), "+f"(d[20]), "+f"(d[21]), "+f"(d[22]), "+f"(d[23]), "+f"(d[24]), "+f"(d[25]), "+f"(d[26]), "+f"(d[27]), "+f"(d[28]), "+f"(d[29]), "+f"(d[30]), "+f"(d[31]), "+f"(d[32]), "+f"(d[33]), "+f"(d[34]), "+f"(d[35]), "+f"(d[36]), "+f"(d[37]), "+f"(d[38]), "+f"(d[39]), "+f"(d[40]), "+f"(d[41]), "+f"(d[42]), "+f"(d[43]), "+f"(d[44]), "+f"(d[45]), "+f"(d[46]), "+f"(d[47]), "+f"(d[48]), "+f"(d[49]), "+f"(d[50]), "+f"(d[51]), "+f"(d[52]), "+f"(d[53]), "+f"(d[54]), "+f"(d[55]), "+f"(d[56]), "+f"(d[57]), "+f"(d[58]), "+f"(d[59]), "+f"(d[60]), "+f"(d[61]), "+f"(d[62]), "+f"(d[63])
      : "r"(a0), "r"(a1), "r"(a2), "r"(a3), "l"(db));
  } else {
    asm volatile("{\n.reg .pred p;\nsetp.ne.b32 p, 0, 0;\n"
      "wgmma.mma_async.sync.aligned.m64n128k16.f32.bf16.bf16 "
      "{%0, %1, %2, %3, %4, %5, %6, %7, %8, %9, %10, %11, %12, %13, %14, %15, %16, %17, %18, %19, %20, %21, %22, %23, %24, %25, %26, %27, %28, %29, %30, %31, %32, %33, %34, %35, %36, %37, %38, %39, %40, %41, %42, %43, %44, %45, %46, %47, %48, %49, %50, %51, %52, %53, %54, %55, %56, %57, %58, %59, %60, %61, %62, %63}, "
      "{%64, %65, %66, %67}, %68, p, 1, 1, 1;\n}\n"
      : "=f"(d[0]), "=f"(d[1]), "=f"(d[2]), "=f"(d[3]), "=f"(d[4]), "=f"(d[5]), "=f"(d[6]), "=f"(d[7]), "=f"(d[8]), "=f"(d[9]), "=f"(d[10]), "=f"(d[11]), "=f"(d[12]), "=f"(d[13]), "=f"(d[14]), "=f"(d[15]), "=f"(d[16]), "=f"(d[17]), "=f"(d[18]), "=f"(d[19]), "=f"(d[20]), "=f"(d[21]), "=f"(d[22]), "=f"(d[23]), "=f"(d[24]), "=f"(d[25]), "=f"(d[26]), "=f"(d[27]), "=f"(d[28]), "=f"(d[29]), "=f"(d[30]), "=f"(d[31]), "=f"(d[32]), "=f"(d[33]), "=f"(d[34]), "=f"(d[35]), "=f"(d[36]), "=f"(d[37]), "=f"(d[38]), "=f"(d[39]), "=f"(d[40]), "=f"(d[41]), "=f"(d[42]), "=f"(d[43]), "=f"(d[44]), "=f"(d[45]), "=f"(d[46]), "=f"(d[47]), "=f"(d[48]), "=f"(d[49]), "=f"(d[50]), "=f"(d[51]), "=f"(d[52]), "=f"(d[53]), "=f"(d[54]), "=f"(d[55]), "=f"(d[56]), "=f"(d[57]), "=f"(d[58]), "=f"(d[59]), "=f"(d[60]), "=f"(d[61]), "=f"(d[62]), "=f"(d[63])
      : "r"(a0), "r"(a1), "r"(a2), "r"(a3), "l"(db));
  }
}
__device__ __forceinline__ void wgmma_n128_ss_ta0_tb1(float* d, uint64_t da, uint64_t db, bool accumulate) {
  if (accumulate) {
    asm volatile("{\n.reg .pred p;\nsetp.ne.b32 p, 1, 0;\n"
      "wgmma.mma_async.sync.aligned.m64n128k16.f32.bf16.bf16 "
      "{%0, %1, %2, %3, %4, %5, %6, %7, %8, %9, %10, %11, %12, %13, %14, %15, %16, %17, %18, %19, %20, %21, %22, %23, %24, %25, %26, %27, %28, %29, %30, %31, %32, %33, %34, %35, %36, %37, %38, %39, %40, %41, %42, %43, %44, %45, %46, %47, %48, %49, %50, %51, %52, %53, %54, %55, %56, %57, %58, %59, %60, %61, %62, %63}, "
      "%64, %65, p, 1, 1, 0, 1;\n}\n"
      : "+f"(d[0]), "+f"(d[1]), "+f"(d[2]), "+f"(d[3]), "+f"(d[4]), "+f"(d[5]), "+f"(d[6]), "+f"(d[7]), "+f"(d[8]), "+f"(d[9]), "+f"(d[10]), "+f"(d[11]), "+f"(d[12]), "+f"(d[13]), "+f"(d[14]), "+f"(d[15]), "+f"(d[16]), "+f"(d[17]), "+f"(d[18]), "+f"(d[19]), "+f"(d[20]), "+f"(d[21]), "+f"(d[22]), "+f"(d[23]), "+f"(d[24]), "+f"(d[25]), "+f"(d[26]), "+f"(d[27]), "+f"(d[28]), "+f"(d[29]), "+f"(d[30]), "+f"(d[31]), "+f"(d[32]), "+f"(d[33]), "+f"(d[34]), "+f"(d[35]), "+f"(d[36]), "+f"(d[37]), "+f"(d[38]), "+f"(d[39]), "+f"(d[40]), "+f"(d[41]), "+f"(d[42]), "+f"(d[43]), "+f"(d[44]), "+f"(d[45]), "+f"(d[46]), "+f"(d[47]), "+f"(d[48]), "+f"(d[49]), "+f"(d[50]), "+f"(d[51]), "+f"(d[52]), "+f"(d[53]), "+f"(d[54]), "+f"(d[55]), "+f"(d[56]), "+f"(d[57]), "+f"(d[58]), "+f"(d[59]), "+f"(d[60]), "+f"(d[61]), "+f"(d[62]), "+f"(d[63])
      : "l"(da), "l"(db));
  } else {
    asm volatile("{\n.reg .pred p;\nsetp.ne.b32 p, 0, 0;\n"
      "wgmma.mma_async.sync.aligned.m64n128k16.f32.bf16.bf16 "
      "{%0, %1, %2, %3, %4, %5, %6, %7, %8, %9, %10, %11, %12, %13, %14, %15, %16, %17, %18, %19, %20, %21, %22, %23, %24, %25, %26, %27, %28, %29, %30, %31, %32, %33, %34, %35, %36, %37, %38, %39, %40, %41, %42, %43, %44, %45, %46, %47, %48, %49, %50, %51, %52, %53, %54, %55, %56, %57, %58, %59, %60, %61, %62, %63}, "
      "%64, %65, p, 1, 1, 0, 1;\n}\n"
      : "=f"(d[0]), "=f"(d[1]), "=f"(d[2]), "=f"(d[3]), "=f"(d[4]), "=f"(d[5]), "=f"(d[6]), "=f"(d[7]), "=f"(d[8]), "=f"(d[9]), "=f"(d[10]), "=f"(d[11]), "=f"(d[12]), "=f"(d[13]), "=f"(d[14]), "=f"(d[15]), "=f"(d[16]), "=f"(d[17]), "=f"(d[18]), "=f"(d[19]), "=f"(d[20]), "=f"(d[21]), "=f"(d[22]), "=f"(d[23]), "=f"(d[24]), "=f"(d[25]), "=f"(d[26]), "=f"(d[27]), "=f"(d[28]), "=f"(d[29]), "=f"(d[30]), "=f"(d[31]), "=f"(d[32]), "=f"(d[33]), "=f"(d[34]), "=f"(d[35]), "=f"(d[36]), "=f"(d[37]), "=f"(d[38]), "=f"(d[39]), "=f"(d[40]), "=f"(d[41]), "=f"(d[42]), "=f"(d[43]), "=f"(d[44]), "=f"(d[45]), "=f"(d[46]), "=f"(d[47]), "=f"(d[48]), "=f"(d[49]), "=f"(d[50]), "=f"(d[51]), "=f"(d[52]), "=f"(d[53]), "=f"(d[54]), "=f"(d[55]), "=f"(d[56]), "=f"(d[57]), "=f"(d[58]), "=f"(d[59]), "=f"(d[60]), "=f"(d[61]), "=f"(d[62]), "=f"(d[63])
      : "l"(da), "l"(db));
  }
}
__device__ __forceinline__ void wgmma_n256_rs_ta0_tb1(float* d, uint32_t a0, uint32_t a1, uint32_t a2, uint32_t a3, uint64_t db, bool accumulate) {
  if (accumulate) {
    asm volatile("{\n.reg .pred p;\nsetp.ne.b32 p, 1, 0;\n"
      "wgmma.mma_async.sync.aligned.m64n256k16.f32.bf16.bf16 "
      "{%0, %1, %2, %3, %4, %5, %6, %7, %8, %9, %10, %11, %12, %13, %14, %15, %16, %17, %18, %19, %20, %21, %22, %23, %24, %25, %26, %27, %28, %29, %30, %31, %32, %33, %34, %35, %36, %37, %38, %39, %40, %41, %42, %43, %44, %45, %46, %47, %48, %49, %50, %51, %52, %53, %54, %55, %56, %57, %58, %59, %60, %61, %62, %63, %64, %65, %66, %67, %68, %69, %70, %71, %72, %73, %74, %75, %76, %77, %78, %79, %80, %81, %82, %83, %84, %85, %86, %87, %88, %89, %90, %91, %92, %93, %94, %95, %96, %97, %98, %99, %100, %101, %102, %103, %104, %105, %106, %107, %108, %109, %110, %111, %112, %113, %114, %115, %116, %117, %118, %119, %120, %121, %122, %123, %124, %125, %126, %127}, "
      "{%128, %129, %130, %131}, %132, p, 1, 1, 1;\n}\n"
      : "+f"(d[0]), "+f"(d[1]), "+f"(d[2]), "+f"(d[3]), "+f"(d[4]), "+f"(d[5]), "+f"(d[6]), "+f"(d[7]), "+f"(d[8]), "+f"(d[9]), "+f"(d[10]), "+f"(d[11]), "+f"(d[12]), "+f"(d[13]), "+f"(d[14]), "+f"(d[15]), "+f"(d[16]), "+f"(d[17]), "+f"(d[18]), "+f"(d[19]), "+f"(d[20]), "+f"(d[21]), "+f"(d[22]), "+f"(d[23]), "+f"(d[24]), "+f"(d[25]), "+f"(d[26]), "+f"(d[27]), "+f"(d[28]), "+f"(d[29]), "+f"(d[30]), "+f"(d[31]), "+f"(d[32]), "+f"(d[33]), "+f"(d[34]), "+f"(d[35]), "+f"(d[36]), "+f"(d[37]), "+f"(d[38]), "+f"(d[39]), "+f"(d[40]), "+f"(d[41]), "+f"(d[42]), "+f"(d[43]), "+f"(d[44]), "+f"(d[45]), "+f"(d[46]), "+f"(d[47]), "+f"(d[48]), "+f"(d[49]), "+f"(d[50]), "+f"(d[51]), "+f"(d[52]), "+f"(d[53]), "+f"(d[54]), "+f"(d[55]), "+f"(d[56]), "+f"(d[57]), "+f"(d[58]), "+f"(d[59]), "+f"(d[60]), "+f"(d[61]), "+f"(d[62]), "+f"(d[63]), "+f"(d[64]), "+f"(d[65]), "+f"(d[66]), "+f"(d[67]), "+f"(d[68]), "+f"(d[69]), "+f"(d[70]), "+f"(d[71]), "+f"(d[72]), "+f"(d[73]), "+f"(d[74]), "+f"(d[75]), "+f"(d[76]), "+f"(d[77]), "+f"(d[78]), "+f"(d[79]), "+f"(d[80]), "+f"(d[81]), "+f"(d[82]), "+f"(d[83]), "+f"(d[84]), "+f"(d[85]), "+f"(d[86]), "+f"(d[87]), "+f"(d[88]), "+f"(d[89]), "+f"(d[90]), "+f"(d[91]), "+f"(d[92]), "+f"(d[93]), "+f"(d[94]), "+f"(d[95]), "+f"(d[96]), "+f"(d[97]), "+f"(d[98]), "+f"(d[99]), "+f"(d[100]), "+f"(d[101]), "+f"(d[102]), "+f"(d[103]), "+f"(d[104]), "+f"(d[105]), "+f"(d[106]), "+f"(d[107]), "+f"(d[108]), "+f"(d[109]), "+f"(d[110]), "+f"(d[111]), "+f"(d[112]), "+f"(d[113]), "+f"(d[114]), "+f"(d[115]), "+f"(d[116]), "+f"(d[117]), "+f"(d[118]), "+f"(d[119]), "+f"(d[120]), "+f"(d[121]), "+f"(d[122]), "+f"(d[123]), "+f"(d[124]), "+f"(d[125]), "+f"(d[126]), "+f"(d[127])
      : "r"(a0), "r"(a1), "r"(a2), "r"(a3), "l"(db));
  } else {
    asm volatile("{\n.reg .pred p;\nsetp.ne.b32 p, 0, 0;\n"
      "wgmma.mma_async.sync.aligned.m64n256k16.f32.bf16.bf16 "
      "{%0, %1, %2, %3, %4, %5, %6, %7, %8, %9, %10, %11, %12, %13, %14, %15, %16, %17, %18, %19, %20, %21, %22, %23, %24, %25, %26, %27, %28, %29, %30, %31, %32, %33, %34, %35, %36, %37, %38, %39, %40, %41, %42, %43, %44, %45, %46, %47, %48, %49, %50, %51, %52, %53, %54, %55, %56, %57, %58, %59, %60, %61, %62, %63, %64, %65, %66, %67, %68, %69, %70, %71, %72, %73, %74, %75, %76, %77, %78, %79, %80, %81, %82, %83, %84, %85, %86, %87, %88, %89, %90, %91, %92, %93, %94, %95, %96, %97, %98, %99, %100, %101, %102, %103, %104, %105, %106, %107, %108, %109, %110, %111, %112, %113, %114, %115, %116, %117, %118, %119, %120, %121, %122, %123, %124, %125, %126, %127}, "
      "{%128, %129, %130, %131}, %132, p, 1, 1, 1;\n}\n"
      : "=f"(d[0]), "=f"(d[1]), "=f"(d[2]), "=f"(d[3]), "=f"(d[4]), "=f"(d[5]), "=f"(d[6]), "=f"(d[7]), "=f"(d[8]), "=f"(d[9]), "=f"(d[10]), "=f"(d[11]), "=f"(d[12]), "=f"(d[13]), "=f"(d[14]), "=f"(d[15]), "=f"(d[16]), "=f"(d[17]), "=f"(d[18]), "=f"(d[19]), "=f"(d[20]), "=f"(d[21]), "=f"(d[22]), "=f"(d[23]), "=f"(d[24]), "=f"(d[25]), "=f"(d[26]), "=f"(d[27]), "=f"(d[28]), "=f"(d[29]), "=f"(d[30]), "=f"(d[31]), "=f"(d[32]), "=f"(d[33]), "=f"(d[34]), "=f"(d[35]), "=f"(d[36]), "=f"(d[37]), "=f"(d[38]), "=f"(d[39]), "=f"(d[40]), "=f"(d[41]), "=f"(d[42]), "=f"(d[43]), "=f"(d[44]), "=f"(d[45]), "=f"(d[46]), "=f"(d[47]), "=f"(d[48]), "=f"(d[49]), "=f"(d[50]), "=f"(d[51]), "=f"(d[52]), "=f"(d[53]), "=f"(d[54]), "=f"(d[55]), "=f"(d[56]), "=f"(d[57]), "=f"(d[58]), "=f"(d[59]), "=f"(d[60]), "=f"(d[61]), "=f"(d[62]), "=f"(d[63]), "=f"(d[64]), "=f"(d[65]), "=f"(d[66]), "=f"(d[67]), "=f"(d[68]), "=f"(d[69]), "=f"(d[70]), "=f"(d[71]), "=f"(d[72]), "=f"(d[73]), "=f"(d[74]), "=f"(d[75]), "=f"(d[76]), "=f"(d[77]), "=f"(d[78]), "=f"(d[79]), "=f"(d[80]), "=f"(d[81]), "=f"(d[82]), "=f"(d[83]), "=f"(d[84]), "=f"(d[85]), "=f"(d[86]), "=f"(d[87]), "=f"(d[88]), "=f"(d[89]), "=f"(d[90]), "=f"(d[91]), "=f"(d[92]), "=f"(d[93]), "=f"(d[94]), "=f"(d[95]), "=f"(d[96]), "=f"(d[97]), "=f"(d[98]), "=f"(d[99]), "=f"(d[100]), "=f"(d[101]), "=f"(d[102]), "=f"(d[103]), "=f"(d[104]), "=f"(d[105]), "=f"(d[106]), "=f"(d[107]), "=f"(d[108]), "=f"(d[109]), "=f"(d[110]), "=f"(d[111]), "=f"(d[112]), "=f"(d[113]), "=f"(d[114]), "=f"(d[115]), "=f"(d[116]), "=f"(d[117]), "=f"(d[118]), "=f"(d[119]), "=f"(d[120]), "=f"(d[121]), "=f"(d[122]), "=f"(d[123]), "=f"(d[124]), "=f"(d[125]), "=f"(d[126]), "=f"(d[127])
      : "r"(a0), "r"(a1), "r"(a2), "r"(a3), "l"(db));
  }
}
__device__ __forceinline__ void wgmma_n256_ss_ta0_tb1(float* d, uint64_t da, uint64_t db, bool accumulate) {
  if (accumulate) {
    asm volatile("{\n.reg .pred p;\nsetp.ne.b32 p, 1, 0;\n"
      "wgmma.mma_async.sync.aligned.m64n256k16.f32.bf16.bf16 "
      "{%0, %1, %2, %3, %4, %5, %6, %7, %8, %9, %10, %11, %12, %13, %14, %15, %16, %17, %18, %19, %20, %21, %22, %23, %24, %25, %26, %27, %28, %29, %30, %31, %32, %33, %34, %35, %36, %37, %38, %39, %40, %41, %42, %43, %44, %45, %46, %47, %48, %49, %50, %51, %52, %53, %54, %55, %56, %57, %58, %59, %60, %61, %62, %63, %64, %65, %66, %67, %68, %69, %70, %71, %72, %73, %74, %75, %76, %77, %78, %79, %80, %81, %82, %83, %84, %85, %86, %87, %88, %89, %90, %91, %92, %93, %94, %95, %96, %97, %98, %99, %100, %101, %102, %103, %104, %105, %106, %107, %108, %109, %110, %111, %112, %113, %114, %115, %116, %117, %118, %119, %120, %121, %122, %123, %124, %125, %126, %127}, "
      "%128, %129, p, 1, 1, 0, 1;\n}\n"
      : "+f"(d[0]), "+f"(d[1]), "+f"(d[2]), "+f"(d[3]), "+f"(d[4]), "+f"(d[5]), "+f"(d[6]), "+f"(d[7]), "+f"(d[8]), "+f"(d[9]), "+f"(d[10]), "+f"(d[11]), "+f"(d[12]), "+f"(d[13]), "+f"(d[14]), "+f"(d[15]), "+f"(d[16]), "+f"(d[17]), "+f"(d[18]), "+f"(d[19]), "+f"(d[20]), "+f"(d[21]), "+f"(d[22]), "+f"(d[23]), "+f"(d[24]), "+f"(d[25]), "+f"(d[26]), "+f"(d[27]), "+f"(d[28]), "+f"(d[29]), "+f"(d[30]), "+f"(d[31]), "+f"(d[32]), "+f"(d[33]), "+f"(d[34]), "+f"(d[35]), "+f"(d[36]), "+f"(d[37]), "+f"(d[38]), "+f"(d[39]), "+f"(d[40]), "+f"(d[41]), "+f"(d[42]), "+f"(d[43]), "+f"(d[44]), "+f"(d[45]), "+f"(d[46]), "+f"(d[47]), "+f"(d[48]), "+f"(d[49]), "+f"(d[50]), "+f"(d[51]), "+f"(d[52]), "+f"(d[53]), "+f"(d[54]), "+f"(d[55]), "+f"(d[56]), "+f"(d[57]), "+f"(d[58]), "+f"(d[59]), "+f"(d[60]), "+f"(d[61]), "+f"(d[62]), "+f"(d[63]), "+f"(d[64]), "+f"(d[65]), "+f"(d[66]), "+f"(d[67]), "+f"(d[68]), "+f"(d[69]), "+f"(d[70]), "+f"(d[71]), "+f"(d[72]), "+f"(d[73]), "+f"(d[74]), "+f"(d[75]), "+f"(d[76]), "+f"(d[77]), "+f"(d[78]), "+f"(d[79]), "+f"(d[80]), "+f"(d[81]), "+f"(d[82]), "+f"(d[83]), "+f"(d[84]), "+f"(d[85]), "+f"(d[86]), "+f"(d[87]), "+f"(d[88]), "+f"(d[89]), "+f"(d[90]), "+f"(d[91]), "+f"(d[92]), "+f"(d[93]), "+f"(d[94]), "+f"(d[95]), "+f"(d[96]), "+f"(d[97]), "+f"(d[98]), "+f"(d[99]), "+f"(d[100]), "+f"(d[101]), "+f"(d[102]), "+f"(d[103]), "+f"(d[104]), "+f"(d[105]), "+f"(d[106]), "+f"(d[107]), "+f"(d[108]), "+f"(d[109]), "+f"(d[110]), "+f"(d[111]), "+f"(d[112]), "+f"(d[113]), "+f"(d[114]), "+f"(d[115]), "+f"(d[116]), "+f"(d[117]), "+f"(d[118]), "+f"(d[119]), "+f"(d[120]), "+f"(d[121]), "+f"(d[122]), "+f"(d[123]), "+f"(d[124]), "+f"(d[125]), "+f"(d[126]), "+f"(d[127])
      : "l"(da), "l"(db));
  } else {
    asm volatile("{\n.reg .pred p;\nsetp.ne.b32 p, 0, 0;\n"
      "wgmma.mma_async.sync.aligned.m64n256k16.f32.bf16.bf16 "
      "{%0, %1, %2, %3, %4, %5, %6, %7, %8, %9, %10, %11, %12, %13, %14, %15, %16, %17, %18, %19, %20, %21, %22, %23, %24, %25, %26, %27, %28, %29, %30, %31, %32, %33, %34, %35, %36, %37, %38, %39, %40, %41, %42, %43, %44, %45, %46, %47, %48, %49, %50, %51, %52, %53, %54, %55, %56, %57, %58, %59, %60, %61, %62, %63, %64, %65, %66, %67, %68, %69, %70, %71, %72, %73, %74, %75, %76, %77, %78, %79, %80, %81, %82, %83, %84, %85, %86, %87, %88, %89, %90, %91, %92, %93, %94, %95, %96, %97, %98, %99, %100, %101, %102, %103, %104, %105, %106, %107, %108, %109, %110, %111, %112, %113, %114, %115, %116, %117, %118, %119, %120, %121, %122, %123, %124, %125, %126, %127}, "
      "%128, %129, p, 1, 1, 0, 1;\n}\n"
      : "=f"(d[0]), "=f"(d[1]), "=f"(d[2]), "=f"(d[3]), "=f"(d[4]), "=f"(d[5]), "=f"(d[6]), "=f"(d[7]), "=f"(d[8]), "=f"(d[9]), "=f"(d[10]), "=f"(d[11]), "=f"(d[12]), "=f"(d[13]), "=f"(d[14]), "=f"(d[15]), "=f"(d[16]), "=f"(d[17]), "=f"(d[18]), "=f"(d[19]), "=f"(d[20]), "=f"(d[21]), "=f"(d[22]), "=f"(d[23]), "=f"(d[24]), "=f"(d[25]), "=f"(d[26]), "=f"(d[27]), "=f"(d[28]), "=f"(d[29]), "=f"(d[30]), "=f"(d[31]), "=f"(d[32]), "=f"(d[33]), "=f"(d[34]), "=f"(d[35]), "=f"(d[36]), "=f"(d[37]), "=f"(d[38]), "=f"(d[39]), "=f"(d[40]), "=f"(d[41]), "=f"(d[42]), "=f"(d[43]), "=f"(d[44]), "=f"(d[45]), "=f"(d[46]), "=f"(d[47]), "=f"(d[48]), "=f"(d[49]), "=f"(d[50]), "=f"(d[51]), "=f"(d[52]), "=f"(d[53]), "=f"(d[54]), "=f"(d[55]), "=f"(d[56]), "=f"(d[57]), "=f"(d[58]), "=f"(d[59]), "=f"(d[60]), "=f"(d[61]), "=f"(d[62]), "=f"(d[63]), "=f"(d[64]), "=f"(d[65]), "=f"(d[66]), "=f"(d[67]), "=f"(d[68]), "=f"(d[69]), "=f"(d[70]), "=f"(d[71]), "=f"(d[72]), "=f"(d[73]), "=f"(d[74]), "=f"(d[75]), "=f"(d[76]), "=f"(d[77]), "=f"(d[78]), "=f"(d[79]), "=f"(d[80]), "=f"(d[81]), "=f"(d[82]), "=f"(d[83]), "=f"(d[84]), "=f"(d[85]), "=f"(d[86]), "=f"(d[87]), "=f"(d[88]), "=f"(d[89]), "=f"(d[90]), "=f"(d[91]), "=f"(d[92]), "=f"(d[93]), "=f"(d[94]), "=f"(d[95]), "=f"(d[96]), "=f"(d[97]), "=f"(d[98]), "=f"(d[99]), "=f"(d[100]), "=f"(d[101]), "=f"(d[102]), "=f"(d[103]), "=f"(d[104]), "=f"(d[105]), "=f"(d[106]), "=f"(d[107]), "=f"(d[108]), "=f"(d[109]), "=f"(d[110]), "=f"(d[111]), "=f"(d[112]), "=f"(d[113]), "=f"(d[114]), "=f"(d[115]), "=f"(d[116]), "=f"(d[117]), "=f"(d[118]), "=f"(d[119]), "=f"(d[120]), "=f"(d[121]), "=f"(d[122]), "=f"(d[123]), "=f"(d[124]), "=f"(d[125]), "=f"(d[126]), "=f"(d[127])
      : "l"(da), "l"(db));
  }
}
__device__ __forceinline__ void wgmma_n256_ssp_ta0_tb1(float* d, uint64_t da, uint64_t db, int accumulate) {
    asm volatile("{\n.reg .pred p;\nsetp.ne.b32 p, %130, 0;\n"
      "wgmma.mma_async.sync.aligned.m64n256k16.f32.bf16.bf16 "
      "{%0, %1, %2, %3, %4, %5, %6, %7, %8, %9, %10, %11, %12, %13, %14, %15, %16, %17, %18, %19, %20, %21, %22, %23, %24, %25, %26, %27, %28, %29, %30, %31, %32, %33, %34, %35, %36, %37, %38, %39, %40, %41, %42, %43, %44, %45, %46, %47, %48, %49, %50, %51, %52, %53, %54, %55, %56, %57, %58, %59, %60, %61, %62, %63, %64, %65, %66, %67, %68, %69, %70, %71, %72, %73, %74, %75, %76, %77, %78, %79, %80, %81, %82, %83, %84, %85, %86, %87, %88, %89, %90, %91, %92, %93, %94, %95, %96, %97, %98, %99, %100, %101, %102, %103, %104, %105, %106, %107, %108, %109, %110, %111, %112, %113, %114, %115, %116, %117, %118, %119, %120, %121, %122, %123, %124, %125, %126, %127}, "
      "%128, %129, p, 1, 1, 0, 1;\n}\n"
      : "+f"(d[0]), "+f"(d[1]), "+f"(d[2]), "+f"(d[3]), "+f"(d[4]), "+f"(d[5]), "+f"(d[6]), "+f"(d[7]), "+f"(d[8]), "+f"(d[9]), "+f"(d[10]), "+f"(d[11]), "+f"(d[12]), "+f"(d[13]), "+f"(d[14]), "+f"(d[15]), "+f"(d[16]), "+f"(d[17]), "+f"(d[18]), "+f"(d[19]), "+f"(d[20]), "+f"(d[21]), "+f"(d[22]), "+f"(d[23]), "+f"(d[24]), "+f"(d[25]), "+f"(d[26]), "+f"(d[27]), "+f"(d[28]), "+f"(d[29]), "+f"(d[30]), "+f"(d[31]), "+f"(d[32]), "+f"(d[33]), "+f"(d[34]), "+f"(d[35]), "+f"(d[36]), "+f"(d[37]), "+f"(d[38]), "+f"(d[39]), "+f"(d[40]), "+f"(d[41]), "+f"(d[42]), "+f"(d[43]), "+f"(d[44]), "+f"(d[45]), "+f"(d[46]), "+f"(d[47]), "+f"(d[48]), "+f"(d[49]), "+f"(d[50]), "+f"(d[51]), "+f"(d[52]), "+f"(d[53]), "+f"(d[54]), "+f"(d[55]), "+f"(d[56]), "+f"(d[57]), "+f"(d[58]), "+f"(d[59]), "+f"(d[60]), "+f"(d[61]), "+f"(d[62]), "+f"(d[63]), "+f"(d[64]), "+f"(d[65]), "+f"(d[66]), "+f"(d[67]), "+f"(d[68]), "+f"(d[69]), "+f"(d[70]), "+f"(d[71]), "+f"(d[72]), "+f"(d[73]), "+f"(d[74]), "+f"(d[75]), "+f"(d[76]), "+f"(d[77]), "+f"(d[78]), "+f"(d[79]), "+f"(d[80]), "+f"(d[81]), "+f"(d[82]), "+f"(d[83]), "+f"(d[84]), "+f"(d[85]), "+f"(d[86]), "+f"(d[87]), "+f"(d[88]), "+f"(d[89]), "+f"(d[90]), "+f"(d[91]), "+f"(d[92]), "+f"(d[93]), "+f"(d[94]), "+f"(d[95]), "+f"(d[96]), "+f"(d[97]), "+f"(d[98]), "+f"(d[99]), "+f"(d[100]), "+f"(d[101]), "+f"(d[102]), "+f"(d[103]), "+f"(d[104]), "+f"(d[105]), "+f"(d[106]), "+f"(d[107]), "+f"(d[108]), "+f"(d[109]), "+f"(d[110]), "+f"(d[111]), "+f"(d[112]), "+f"(d[113]), "+f"(d[114]), "+f"(d[115]), "+f"(d[116]), "+f"(d[117]), "+f"(d[118]), "+f"(d[119]), "+f"(d[120]), "+f"(d[121]), "+f"(d[122]), "+f"(d[123]), "+f"(d[124]), "+f"(d[125]), "+f"(d[126]), "+f"(d[127])
      : "l"(da), "l"(db), "r"(accumulate));
}

template <int N> __device__ __forceinline__ void quad_sum(float* m) {
#pragma unroll
  for (int o = 1; o <= 2; o <<= 1) {
    float t[N];
#pragma unroll
    for (int i = 0; i < N; i++) t[i] = __shfl_xor_sync(~0u, m[i], o);
#pragma unroll
    for (int i = 0; i < N; i++) m[i] += t[i];
  }
}
__device__ __forceinline__ bool softmax_unsafe(const uint32_t* t, float l0, float l1) {
  const float m0 = fmaxf(bf_lo(t[0]) + bf_hi(t[0]), bf_lo(t[2]) + bf_hi(t[2])), m1 = fmaxf(bf_lo(t[1]) + bf_hi(t[1]), bf_lo(t[3]) + bf_hi(t[3]));
  return __any_sync(~0u, !(m0 * l0 < 2500.f) | !(m1 * l1 < 2500.f));
}
__device__ __forceinline__ void softmax_shift(float* p, float c0, float c1) {
#pragma unroll 1
  for (int it = 0; it < 8; it++) {
    float mx = p[0], mn = p[0];
#pragma unroll
    for (int j = 1; j < 8; j++) { mx = fmaxf(mx, p[(j >> 1) * 4 + (j & 1)]); mn = fminf(mn, p[(j >> 1) * 4 + (j & 1)]); }
#pragma unroll
    for (int o = 1; o <= 2; o <<= 1) { mx = fmaxf(mx, __shfl_xor_sync(~0u, mx, o)); mn = fminf(mn, __shfl_xor_sync(~0u, mn, o)); }
    const float half = fminf(0.5f * (mx - mn), 50.f * rcp(it & 1 ? c1 : c0));
    float r[8];
#pragma unroll
    for (int j = 0; j < 8; j++) {
      const float v = p[(j >> 1) * 4 + (j & 1)];
      r[j] = fmaxf(v - mx + half, 0.f) + fminf(v - mn - half, 0.f) + (v - v);
    }
#pragma unroll
    for (int k = 0; k < 7; k++)
#pragma unroll
      for (int j = 0; j < 8; j++) p[(k >> 1) * 16 + (k & 1) * 2 + (j >> 1) * 4 + (j & 1)] = p[((k + 1) >> 1) * 16 + ((k + 1) & 1) * 2 + (j >> 1) * 4 + (j & 1)];
#pragma unroll
    for (int j = 0; j < 8; j++) p[50 + (j >> 1) * 4 + (j & 1)] = r[j];
  }
}
template <int J0 = 0, int J1 = 8> __device__ __forceinline__ void k_exp(const float* p, float c0, float c1, float* e, float* s) {
#pragma unroll
  for (int j = J0; j < J1; j++) {
    e[2 * j] = ex2(p[2 * j] * (j & 1 ? c1 : c0));
    e[2 * j + 1] = ex2(p[2 * j + 1] * (j & 1 ? c1 : c0));
    e[16 + j] = rcp(e[2 * j] * e[2 * j + 1]);
    const float t = e[2 * j] + e[2 * j + 1];
    s[j & 1] = j < 2 ? t : s[j & 1] + t;
    s[2 + (j & 1)] = j < 2 ? e[16 + j] * t : fmaf(e[16 + j], t, s[2 + (j & 1)]);
  }
}
template <int J0 = 0, int J1 = 8> __device__ __forceinline__ void q_exp(const float* p, float c0, float c1, uint32_t* f) {
#pragma unroll
  for (int j = J0; j < J1; j++) {
    const float e0 = ex2(p[2 * j] * (j & 1 ? c1 : c0)), e1 = ex2(p[2 * j + 1] * (j & 1 ? c1 : c0)), r = rcp(e0 * e1);
    f[j] = pack2(e0, e1);
    f[8 + j] = bmul2(f[j], pack2(r, r));
  }
}

#define FMA8(A, U, X)                                                                                        \
  A[0] = fmaf(bf_lo(U.x), X, A[0]); A[1] = fmaf(bf_hi(U.x), X, A[1]); A[2] = fmaf(bf_lo(U.y), X, A[2]); A[3] = fmaf(bf_hi(U.y), X, A[3]); \
  A[4] = fmaf(bf_lo(U.z), X, A[4]); A[5] = fmaf(bf_hi(U.z), X, A[5]); A[6] = fmaf(bf_lo(U.w), X, A[6]); A[7] = fmaf(bf_hi(U.w), X, A[7])

__device__ __forceinline__ uint32_t routed_row(const __nv_bfloat16* x, uint32_t tag, int lane, uint4* xr) {
  uint32_t best = 0, sv = 0;
#pragma unroll 1
  for (int it = 0; it < SPIN_MAX; it++) {
    const int sel = 2047 - (best & 0x7ff);
#pragma unroll
    for (int i = 0; i < 4; i++) xr[i] = ldg_nc(x + (size_t)sel * DM + i * 256 + lane * 8);
    const unsigned long long st = ld_rlx64(g_stat + sel);
    const uint4 b0 = ld_rlx128(g_best + lane * 2), b1 = ld_rlx128(g_best + 64 + lane * 2);
    const uint32_t m = __reduce_max_sync(~0u, max(max(b0.y == tag ? b0.x : 0u, b0.w == tag ? b0.z : 0u), max(b1.y == tag ? b1.x : 0u, b1.w == tag ? b1.z : 0u)));
    sv = (uint32_t)st;
    if (__all_sync(~0u, b0.y == tag && b0.w == tag && b1.y == tag && b1.w == tag && m == best && (uint32_t)(st >> 32) == tag)) break;
    best = m;
    if (AM_NS) __nanosleep(AM_NS);
  }
  const uint32_t m2 = (sv & 0xffff0000u) | (sv >> 16);
  const float rs = rcp(bf_lo(sv));
#pragma unroll
  for (int i = 0; i < 4; i++) {
    const uint32_t d0 = bsub2(xr[i].x, m2), d1 = bsub2(xr[i].y, m2), d2 = bsub2(xr[i].z, m2), d3 = bsub2(xr[i].w, m2);
    xr[i] = make_uint4(pack2(bf_lo(d0) * rs, bf_hi(d0) * rs), pack2(bf_lo(d1) * rs, bf_hi(d1) * rs), pack2(bf_lo(d2) * rs, bf_hi(d2) * rs),
                       pack2(bf_lo(d3) * rs, bf_hi(d3) * rs));
  }
  return best;
}

struct Params {
  const __nv_bfloat16 *x, *wqkv, *wo, *w_r, *w_gate, *w_up, *w_down;
};

template <bool BY_SMID> __global__ void __launch_bounds__(384, 1)
fused_kernel(const __grid_constant__ CUtensorMap mX, const __grid_constant__ CUtensorMap mWkv, const __grid_constant__ CUtensorMap mWq,
             const __grid_constant__ CUtensorMap mWo, const __grid_constant__ CUtensorMap mPhi, const __grid_constant__ CUtensorMap mWp,
             const __grid_constant__ CUtensorMap mOut, const __grid_constant__ CUtensorMap mWc,
             const __grid_constant__ CUtensorMap mG, const __grid_constant__ CUtensorMap mU, const __grid_constant__ CUtensorMap mD,
             const __grid_constant__ CUtensorMap mXs, const __grid_constant__ CUtensorMap mG2, const __grid_constant__ CUtensorMap mU2, const Params P) {
  constexpr uint32_t sb = SB, bar = SB + SM_BAR;
  int bid = blockIdx.x;
  if (BY_SMID) {
    uint32_t sm;
    asm volatile("mov.u32 %0, %%smid;" : "=r"(sm));
    const uint32_t tq = (sm - 64) >> 1, q7 = (tq * 37) >> 8;
    const uint32_t gpc = sm < 64 ? (sm >> 1) & 7 : 1 + tq - 7 * q7, idx = (sm < 64 ? sm >> 4 : 4 + q7) * 2 + (sm & 1);
    bid = sm < 120 ? ((PTAB >> (4 * gpc)) & 7) * 16 + idx : sm < 124 ? sm + 8 : sm - 116;
  }
  const int hg = ((bid >> 2) & 3) + 4 * ((bid >> 4) & 1), mb = (bid & 3) + 4 * ((bid >> 5) & 3);
  if (bid < NCTA && threadIdx.x < 256) {
    const uint32_t r0 = threadIdx.x >> 3, c = threadIdx.x & 7, dst = sb + 2 * KV_STAGE + r0 * 128 + ((c ^ (r0 & 7)) << 4);
    const char* xs = (const char*)P.x + (size_t)(mb * 128 + r0) * 2048 + c * 16;
    const char* ws = (const char*)P.wqkv + (size_t)r0 * 6144 + 2048 + hg * 256 + c * 16;
#pragma unroll
    for (int i = 0; i < 4; i++) cp_async16(dst + i * 4096, xs + i * 65536);
#pragma unroll
    for (int i = 0; i < 8; i++) cp_async16(dst + 16384 + i * 4096, ws + (i & 1) * 196608 + (i >> 2) * 2048 + ((i >> 1) & 1) * 128);
  }
  extern __shared__ __align__(1024) uint8_t smem[];
  if (smem_u32(smem) != SB) __trap();
  const int warp = __shfl_sync(~0u, threadIdx.x >> 5, 0);

  if (bid >= NCTA) {
    constexpr uint32_t XV = SM_WPHI, ONES = SM_ZT, BF = bar, BE = bar + 48, BX = bar + 96;
    constexpr int NJ = (DM - GROWS) / 64;
    const int lane = lane_id(), sp = bid - NCTA;
    const uint32_t tag = ld_rlx(g_epoch + bid * 32 + lane) + 1;
    if (warp == 8 && elect_one()) {
#pragma unroll 1
      for (int i = 0; i < 13; i++) mbar_init(bar + 8 * i, i >= 6 && i < 12 ? 8 : 1);
    }
    if (warp == 9) { sts64u(sb + ONES + lane * 8, 0x3f803f80u, 0x3f803f80u); fence_async_smem(); }
    __syncthreads();
    if (warp == 8) {
      if (elect_one()) {
        uint32_t s = 0, ph = 1;
        for (const long long c0 = clock64(); clock64() - c0 < SP_DELAY;) {}
#pragma unroll 1
        for (int job = 0; job < 8; job++) {
          const CUtensorMap* m = job == 0 ? &mWq : sp & 2 ? &mU2 : &mG2;
          const int g0 = job ? (sp & 1) * 28 + job * 4 - 4 : sp * 4;
#pragma unroll 1
          for (int row = job ? GROWS : 0; row < DM; row += 64) {
            mbar_wait(BE + 8 * s, ph);
            mbar_expect_tx(BF + 8 * s, Q_STAGE);
            tma4d(sb + s * Q_STAGE, m, 0, row, g0, 0, BF + 8 * s);
            tma4d(sb + s * Q_STAGE + 16384, m, 0, row, g0 + 2, 0, BF + 8 * s);
            if (++s == 6) { s = 0; ph ^= 1; }
          }
        }
      }
    } else if (warp == 9) {
      uint4 xr[4];
      routed_row(P.x, tag, lane, xr);
#pragma unroll
      for (int i = 0; i < 4; i++) sts128u(sb + XV + i * 512 + lane * 16, xr[i].x, xr[i].y, xr[i].z, xr[i].w);
      fence_async_smem();
      __syncwarp();
      if (lane == 0) mbar_arrive(BX);
    } else if (warp < 8) {
      uint32_t s = 0, ph = 0;
#pragma unroll 1
      for (int job = 0; job < 8; job++) {
        float d[8] = {0.f, 0.f, 0.f, 0.f, 0.f, 0.f, 0.f, 0.f};
        if (job == 1) mbar_wait(BX, 0);
#pragma unroll 1
        for (int i = 0; i < (job ? NJ : 16); i++) {
          mbar_wait(BF + 8 * s, ph);
          wg_fence();
#pragma unroll
          for (int k = 0; k < 8; k++)
            wgmma_n8_ss_ta1_tb0(d + 4 * (k >> 2), mkdesc(sb + k * 2048, 16, 1024, 1, s * (Q_STAGE / 16) + (warp >> 2) * 1024),
                                mkdesc(sb, 16, 128, 0, job ? (XV + GROWS * 2) / 16 + i * 8 + (k & 3) * 2 : ONES / 16), 1);
          wg_commit();
          wg_wait<0>();
          if (lane == 0) mbar_arrive(BE + 8 * s);
          if (++s == 6) { s = 0; ph ^= 1; }
        }
        reg_fence<8>(d);
        float* dst = (job ? g_gp + sp * 1792 + job * 256 - 256 : g_cs + sp * 256) + (warp >> 2) * 128 + (warp & 3) * 16 + (lane >> 2);
        if ((lane & 3) == 0) {
#pragma unroll
          for (int i = 0; i < 4; i++) st_rlx(dst + (i >> 1) * 64 + (i & 1) * 8, mark(__float_as_uint(d[2 * i]), tag & 1));
        }
        __syncwarp();
      }
      if (warp == 0) g_epoch[bid * 32 + lane] = tag;
    }
    return;
  }
#define Q_SLAB(J) ((J) < 8 ? ((J) + 8 - 2 * (hg & 4)) & 15 : 2 * (hg & 4) + 2 * ((J) & 3) + ((J) >> 2 & 1))
#define Q_AOFF(J) ((J) == 8 + (hg & 3) ? SM_X0 : (J) == 12 + (hg & 3) ? SM_X1 : ((J) & 3) * Q_STAGE)
#define Q_LOAD(J)                                                                                            \
  do {                                                                                                       \
    const uint32_t fb_ = bar + B_FULLQ + 8 * ((J) & 3);                                                      \
    const int k_ = Q_SLAB(J) * 64;                                                                           \
    mbar_expect_tx(fb_, Q_STAGE);                                                                            \
    mbar_arrive2(fb_);                                                                                       \
    tma2d(sb + Q_AOFF(J), &mX, k_, mb * 128, fb_);                                                           \
    tma4d(sb + ((J) & 3) * Q_STAGE + 16384, &mWq, 0, k_, hg * 2, 0, fb_);                                    \
  } while (0)
  if (warp >= 8) {
    asm volatile("setmaxnreg.dec.sync.aligned.u32 %0;" ::"n"(REG_H));
    const int lane = lane_id();
    const int f = (warp - 9) & 3;
    if (f == 3) {
      if (elect_one()) {
        PROF(0); PROFT(32);
#pragma unroll
        for (int s = 0; s < 3; s++) mbar_init(bar + B_FULLKV + 8 * s, 1);
      }
      __syncwarp();
      asm volatile("bar.arrive 14, 288;" ::: "memory");
      if (elect_one()) {
#pragma unroll
        for (int s = 0; s < 2; s++) {
          mbar_expect_tx(bar + B_FULLKV + 8 * s, KV_STAGE);
          tma2d(sb + s * KV_STAGE, &mX, (s + 1) * 64, mb * 128, bar + B_FULLKV + 8 * s);
          tma4d(sb + s * KV_STAGE + 16384, &mWkv, 0, (s + 1) * 64, hg * 2, 1, bar + B_FULLKV + 8 * s);
        }
      }
      __syncwarp();
    }
    const uint32_t ep = ld_rlx(g_epoch + bid * 32 + lane);
    if (f < 2) {
#pragma unroll
      for (int i = 0; i < 2; i++) {
        const uint4 u = __ldg((const uint4*)P.w_r + (f * 2 + i) * 32 + lane);
        sts128u(sb + SM_XSEL + (f * 2 + i) * 512 + lane * 16, u.x, u.y, u.z, u.w);
      }
    }
    bar_sync(13, 384);
    const uint32_t tag = ep + 1, par = tag & 1;
    const bool ffn = bid < NFFN;
    const int fb = bid, cu = bid >> 1, ch = bid & 1;
#define CS_STORE(SEC, C)                                                                                     \
  _Pragma("unroll") for (int r = 0; r < 3; r++) {                                                            \
    const uint32_t h0 = pack2(C.x, C.y), h1 = pack2(C.z, C.w);                                               \
    sts64u(sb + SM_CST + (SEC) * 1024 + (lane >> 4) * 512 + (lane & 1) * 8 + r * 128 + ((((lane & 15) >> 1) ^ (r + (lane >> 4) * 4)) << 4), h0, h1); \
    C.x -= bf_lo(h0); C.y -= bf_hi(h0); C.z -= bf_lo(h1); C.w -= bf_hi(h1);                                  \
  }
#define BAD4(U) ((U.x ^ par) | (U.y ^ par) | (U.z ^ par) | (U.w ^ par))
    const int n0 = f < 2 ? 0 : 2 * f - 3, ne = FFN_OFF || !ffn ? 3 : f == 3 ? 3 + G8 : 3 + GN;
    const uint32_t fsb = sb + SM_FST + ((f + 1) & 3) * 8192, fbar = bar + B_FST + f * 16, fst = fsb + (lane >> 4) * 2048 + (lane & 15) * 16;
    const CUtensorMap *ma = &mWc, *mc = &mWc;
    int sx = 1024 + cu * 32, sy = ch * 512 + f * 192, sdy = 32;
#define STAGEG(N)                                                                                            \
  do {                                                                                                       \
    if ((N) == 3) { ma = &mG; mc = &mU; sx = fb * 32; sy = f * (GN * 32);  sdy = 0; }                        \
    if ((N) < ne && elect_one()) {                                                                           \
      const uint32_t dst_ = fsb + ((N) & 1) * 4096, b_ = fbar + ((N) & 1) * 8;                               \
      mbar_expect_tx(b_, 4096);                                                                              \
      tma2d(dst_, ma, sx, sy, b_);                                                                           \
      tma2d(dst_ + 2048, mc, sx, sy + sdy, b_);                                                              \
    }                                                                                                        \
    sy += 32 + sdy;                                                                                          \
  } while (0)
    float a[8], gsum = 0.f, usum = 0.f;
    {
      if (f == 3) {
        if (elect_one()) {
          if (XS_EARLY) { mbar_expect_tx(bar + B_XST, 16384); tma3d(sb + SM_XST, &mXs, 0, bid * 16, 0, bar + B_XST); }
          mbar_expect_tx(bar + B_WPHI, 8192);
          tma2d(sb + SM_WPHI, &mPhi, 0, hg * 128, bar + B_WPHI);
          prefetch_map(&mWq); prefetch_map(&mWo); prefetch_map(&mWp); prefetch_map(&mD);
          PROF(31);
        }
        __syncwarp();
      } else {
        if (lane == 0) prefetch_map(f == 0 ? &mWc : f == 1 ? &mG : &mU);
        if (f == 2) ((float2*)g_y[par])[bid * 32 + lane] = make_float2(0.f, 0.f);
      }
      float st[13];
#pragma unroll
      for (int i = 0; i < 13; i++) st[i] = 0.f;
#pragma unroll 1
      for (int i = 0; i < 4; i++) {
        mbar_wait(bar + B_XST + 8 * (i >> 1), 0);
        if (f == 0 && lane == 0 && i == 0) PROF(1);
        const uint4 wu = lds128u(sb + SM_XSEL + i * 512 + lane * 16);
        const float wf[8] = {bf_lo(wu.x), bf_hi(wu.x), bf_lo(wu.y), bf_hi(wu.y), bf_lo(wu.z), bf_hi(wu.z), bf_lo(wu.w), bf_hi(wu.w)};
        st[12] += ((wf[0] + wf[1]) + (wf[2] + wf[3])) + ((wf[4] + wf[5]) + (wf[6] + wf[7]));
#pragma unroll
        for (int r = 0; r < 4; r++) {
          const uint4 u = lds128u(sb + SM_XST + i * 8192 + (4 * f + r) * 512 + lane * 16);
          const float xf[8] = {bf_lo(u.x), bf_hi(u.x), bf_lo(u.y), bf_hi(u.y), bf_lo(u.z), bf_hi(u.z), bf_lo(u.w), bf_hi(u.w)};
#pragma unroll
          for (int k = 0; k < 8; k++) { st[r] += xf[k]; st[4 + r] = fmaf(xf[k], xf[k], st[4 + r]); st[8 + r] = fmaf(xf[k], wf[k], st[8 + r]); }
        }
        if (i >= 2 && f < 3) STAGEG(n0 + i - 2);
      }
      const bool up = lane & 16, up2 = lane & 8;
#pragma unroll
      for (int q = 0; q < 3; q++) {
        const float k0 = up ? st[4 * q + 2] : st[4 * q], k1 = up ? st[4 * q + 3] : st[4 * q + 1];
        const float o0 = up ? st[4 * q] : st[4 * q + 2], o1 = up ? st[4 * q + 1] : st[4 * q + 3];
        const float m0 = k0 + __shfl_xor_sync(~0u, o0, 16), m1 = k1 + __shfl_xor_sync(~0u, o1, 16);
        a[q] = (up2 ? m1 : m0) + __shfl_xor_sync(~0u, up2 ? m0 : m1, 8);
      }
      a[3] = st[12] + __shfl_xor_sync(~0u, st[12], 16);
      a[3] += __shfl_xor_sync(~0u, a[3], 8);
#pragma unroll
      for (int o = 4; o; o >>= 1)
#pragma unroll
        for (int q = 0; q < 4; q++) a[q] += __shfl_xor_sync(~0u, a[q], o);
      if ((lane & 7) == 0) sts128(sb + SM_ROWS + (4 * f + (lane >> 3)) * 16, a[0], a[1], a[2], a[3]);
      if (f < 3) asm volatile("bar.arrive 7, 128;" ::: "memory");
    }
    if (f == 3) {
      bar_sync(7, 128);
      const int row = bid * 16 + (lane & 15);
      const float4 v = lds128(sb + SM_ROWS + (lane & 15) * 16);
      const float mf = v.x * (1.f / DM), mean = bf_round(mf), var = fmaxf(fmaf(-mf, mf, v.y * (1.f / DM)), 0.f);
      const float sd = bf_round(sqrt_approx(bf_round(bf_round(var) + 1e-5f)));
      const uint32_t rb = pack2(fmaf(-mean, v.w, v.z) * rcp(sd), 0.f) & 0xffffu, ord = (rb & 0x8000u) ? (~rb & 0xffffu) : (rb | 0x8000u);
      uint32_t best = __reduce_max_sync(~0u, (ord << 16) | (uint32_t)(2047 - row));
      if (lane < 16) st_rlx64(g_stat + row, ((unsigned long long)tag << 32) | __float_as_uint(mean) | (__float_as_uint(sd) >> 16));
      if (lane == 0) { asm volatile("red.relaxed.gpu.global.max.u64 [%0], %1;" ::"l"(g_best + bid), "l"(((unsigned long long)tag << 32) | best) : "memory"); PROF(17); }
#pragma unroll 1
      for (int n = 3; n < 5; n++) STAGEG(n);
      {
        uint4 xr[4];
        best = routed_row(P.x, tag, lane, xr);
#pragma unroll
        for (int i = 0; i < (GROWS + 255) / 256; i++) {
          const uint32_t dst = sb + SM_XSEL + i * 1024 + (lane >> 2) * 128 + (lane & 3) * 8;
          sts64(dst, bf_lo(xr[i].x), bf_lo(xr[i].z)); sts64(dst + 32, bf_hi(xr[i].x), bf_hi(xr[i].z));
          sts64(dst + 64, bf_lo(xr[i].y), bf_lo(xr[i].w)); sts64(dst + 96, bf_hi(xr[i].y), bf_hi(xr[i].w));
        }
        sts64u(sb + SM_RED + 16, tag, best);
        __syncwarp();
        if (lane == 0) { mbar_arrive(bar + B_XS); PROF(19); }
      }
      unsigned long long sv4[4];
      uint4 u[4];
#pragma unroll 1
      for (int it = 0; it < SPIN_MAX; it++) {
#pragma unroll
        for (int i = 0; i < 4; i++) { u[i] = ld_rlx128(g_cs + (1 + i) * 1024 + hg * 128 + lane * 4); sv4[i] = ld_rlx64(g_stat + mb * 128 + i * 32 + lane); }
        bool ok = ((BAD4(u[0]) | BAD4(u[1]) | BAD4(u[2]) | BAD4(u[3])) & 1) == 0;
#pragma unroll
        for (int i = 0; i < 4; i++) ok = ok && (uint32_t)(sv4[i] >> 32) == tag;
        if (__all_sync(~0u, ok)) break;
        __nanosleep(200);
      }
#pragma unroll
      for (int i = 0; i < 4; i++) {
        const uint32_t sv = (uint32_t)sv4[i], sd2 = (sv << 16) | (sv & 0xffffu);
        sts64(sb + SM_STAT + (i * 32 + lane) * 8, -bf_hi(sv), rcp(bf_lo(sv)));
        sts128u(sb + SM_SDT + lane * 64 + ((i ^ ((lane >> 1) & 3)) << 4), sd2, sd2, sd2, sd2);
      }
#pragma unroll
      for (int i = 0; i < 2; i++) {
        float4 c = make_float4(unmark(u[i].x) + unmark(u[i + 2].x), unmark(u[i].y) + unmark(u[i + 2].y), unmark(u[i].z) + unmark(u[i + 2].z),
                               unmark(u[i].w) + unmark(u[i + 2].w));
        CS_STORE(i, c);
      }
      fence_async_smem();
      bar_sync(8, 64);
      if (lane == 0) { mbar_arrive(bar + B_CS); PROF(10); }
    }
    {
      uint32_t xa = sb + SM_RED + 32, xstep = 0;
      const uint32_t zero = __float_as_uint(lds32(sb + SM_RED + 12));
#pragma unroll 1
      for (int ph = f == 3; ph < 2; ph++) {
#pragma unroll
        for (int j = 0; j < 8; j++) a[j] = 0.f;
        if (ph && f == 0) {
        {
          mbar_wait(bar + B_WPHI, 0);
          float nq[8] = {0.f, 0.f, 0.f, 0.f, 0.f, 0.f, 0.f, 0.f};
  #pragma unroll 2
          for (int r = 0; r < 16; r++) {
            const uint4 u = lds128u(sb + SM_WPHI + ((lane >> 2) * 16 + r) * 64 + (((lane ^ (r >> 1)) & 3) << 4));
            nq[0] = fmaf(bf_lo(u.x), bf_lo(u.x), nq[0]); nq[1] = fmaf(bf_hi(u.x), bf_hi(u.x), nq[1]); nq[2] = fmaf(bf_lo(u.y), bf_lo(u.y), nq[2]);
            nq[3] = fmaf(bf_hi(u.y), bf_hi(u.y), nq[3]); nq[4] = fmaf(bf_lo(u.z), bf_lo(u.z), nq[4]); nq[5] = fmaf(bf_hi(u.z), bf_hi(u.z), nq[5]);
            nq[6] = fmaf(bf_lo(u.w), bf_lo(u.w), nq[6]); nq[7] = fmaf(bf_hi(u.w), bf_hi(u.w), nq[7]);
          }
          uint32_t m = 0;
  #pragma unroll
          for (int i = 0; i < 8; i++) m = max(m, __float_as_uint(nq[i] + __shfl_xor_sync(~0u, nq[i], 4)) & 0x7fffffffu);
          sts32(sb + SM_RED + 24, 4.2f * __uint_as_float(__reduce_max_sync(~0u, m)));
        }
          asm volatile("bar.arrive 8, 64;" ::: "memory");
        }
        if (ph) { mbar_wait(bar + B_XS, 0); xa = sb + SM_XSEL + f * (GN * 128) + ((lane >> 2) & 3) * 32; xstep = 128; }
#pragma unroll 1
        for (int n = ph ? 3 : n0; n < (ph ? ne : 3); n++) {
          const float4 x0 = lds128(xa), x1 = lds128(xa + 16);
          xa += xstep;
          mbar_wait(fbar + (n & 1) * 8, ((n - n0) >> 1) & 1);
          uint4 u[8];
#pragma unroll
          for (int j = 0; j < 8; j++) u[j] = lds128u(fst + (n & 1) * 4096 + j * 256);
          FMA8(a, u[0], x0.x); FMA8(a, u[1], x0.y); FMA8(a, u[2], x0.z); FMA8(a, u[3], x0.w);
          if (__any_sync(~0u, ((u[4].x | u[5].x | u[6].x | u[7].x | __float_as_uint(a[0]) | __float_as_uint(a[7])) & zero) == 0)) STAGEG(n + 2);
          FMA8(a, u[4], x1.x); FMA8(a, u[5], x1.y); FMA8(a, u[6], x1.z); FMA8(a, u[7], x1.w);
        }
#pragma unroll
        for (int o = 4; o <= 8; o <<= 1)
#pragma unroll
          for (int j = 0; j < 8; j++) a[j] += __shfl_xor_sync(~0u, a[j], o);
        if (ph && lane == 0) mbar_arrive(bar + B_FFN);
        const uint32_t red = ph ? sb + SM_GRED : sb + SM_RED + 64;
        if ((lane & 12) == 0) {
          const uint32_t d = red + f * 256 + (lane >> 4) * 128 + (lane & 3) * 32;
          sts128(d, a[0], a[1], a[2], a[3]); sts128(d + 16, a[4], a[5], a[6], a[7]);
        }
        if (f != 2) {
          asm volatile("bar.arrive %0, %1;" ::"r"(4 + ph), "r"(96 + 32 * ph) : "memory");
        } else {
          bar_sync(4 + ph, 96 + 32 * ph);
          const uint32_t ra = red + lane * 4;
          gsum = lds32(ra) + lds32(ra + 256) + lds32(ra + 512);
          usum = lds32(ra + 128) + lds32(ra + 384) + lds32(ra + 640);
          if (!ph) st_rlx(g_cs + 1024 + ch * 2048 + cu * 32 + lane, mark(__float_as_uint(gsum + usum), par));
          else { gsum += lds32(ra + 768); usum += lds32(ra + 896); }
          if (lane == 0) PROF(ph ? 34 : 18);
        }
      }
    }
    if (f == 3) {
      if (elect_one()) {
        PROF(7);
        mbar_wait(bar + B_FULLQ, 0);
#pragma unroll 1
        for (int j = 3; j < 16; j++) {
          mbar_wait(bar + (j < 4 ? B_EMPTYKV + 16 : B_EMPTYQ + 8 * (j & 3)), ((j >> 2) & 1) ^ 1);
          if (j == 12 + (hg & 3)) mbar_wait(bar + B_KVST + 8, 0);
          Q_LOAD(j);
        }
        PROF(47);
        mbar_expect_tx(bar + B_DN, 65536);
#pragma unroll 1
        for (int i = 0; i < 4; i++) {
          mbar_wait(bar + B_EMPTYQ + 8 * i, 1);
          tma3d(sb + i * Q_STAGE, &mD, 0, fb * 32, i * 4, bar + B_DN);
        }
        PROF(48);
#pragma unroll 1
        for (int i = 0; i < 16; i++) {
          const int s = i & 3, n = i < 9 ? i - 2 : i - 9, kb = i < 2 ? 2 * hg + i : 2 * (n + (n >= hg)) + (i >= 9);
          if (i >= 4) mbar_wait(bar + B_EMPTYQ + 8 * s, ((i >> 2) & 1) ^ 1);
          mbar_expect_tx(bar + B_FULLQ + 8 * s, 16384);
          if (i < 2) {
            mbar_arrive2(bar + B_FULLQ + 8 * s);
            tma3d(sb + s * Q_STAGE + 16384, &mWo, 0, kb * 64, hg * 2, bar + B_FULLQ + 8 * s);
          } else {
            tma5d(sb + s * Q_STAGE + 16384, &mWp, hg * 128, kb * 2, bar + B_FULLQ + 8 * s);
            tma5d(sb + s * Q_STAGE + 24576, &mWp, hg * 128 + 64, kb * 2, bar + B_FULLQ + 8 * s);
            if (i >= 3) {
              if (i == 3) { mbar_wait(bar + B_DND, 0); PROF(14); }
#pragma unroll 1
              for (int a = i == 3 ? 2 : i; a <= i; a++) {
                const uint4* src = g_ofr + (mb * 16 + (a == 2 ? (hg == 0 ? 2 : 0) : kb)) * 1024;
#pragma unroll
                for (int h = 0; h < 2; h++) {
                  mbar_expect_tx(bar + B_AIN + (a & 3) * 16 + h * 8, 8192);
                  bulk_load(sb + (a & 3) * Q_STAGE + h * 8192, src + h * 512, 8192, bar + B_AIN + (a & 3) * 16 + h * 8);
                }
              }
            }
          }
        }
      }
    } else {
      if (f == 2) {
        if (PFD && ffn) {
#pragma unroll 1
          for (int i = 0; i < 16; i++) { touch_l2((const char*)P.w_down + fb * 65536 + i * 4096 + lane * 128, lane); __nanosleep(PFD); }
        }
        if (WOT) {
#pragma unroll 1
          for (int i = 0; i < 8; i++) { touch_l2((const char*)P.wo + ((mb & 7) * 128 + i * 16 + (lane >> 1)) * 2048 + hg * 256 + (lane & 1) * 128, lane); __nanosleep(PFD); }
        }
        asm volatile("cp.async.wait_all;" ::: "memory");
        uint4 u;
#pragma unroll 1
        for (int it = 0; it < SPIN_MAX; it++) {
          u = ld_rlx128(g_cs + hg * 128 + lane * 4);
          if (__all_sync(~0u, !(BAD4(u) & 1))) break;
          __nanosleep(200);
        }
        mbar_wait(bar + B_PHI, 0);
        float4 c = make_float4(unmark(u.x), unmark(u.y), unmark(u.z), unmark(u.w));
        CS_STORE(2, c);
        fence_async_smem();
        __syncwarp();
        if (lane == 0) mbar_arrive(bar + B_CSQ);
        if (ffn && !FFN_OFF) {
#pragma unroll 1
          for (int it = 0; it < SPIN_MAX; it++) {
            const uint32_t pg = ld_rlx((const uint32_t*)g_gp + fb * 32 + lane), pu = ld_rlx((const uint32_t*)g_gp + FF + fb * 32 + lane);
            if (__all_sync(~0u, !(((pg ^ par) | (pu ^ par)) & 1))) { gsum += unmark(pg); usum += unmark(pu); break; }
            __nanosleep(200);
          }
        }
        const float h = bf_round(silu_f(bf_round(gsum))) * bf_round(usum);
        const uint32_t h2 = pack2(h, h);
        sts128u(sb + SM_HT + lane * 16, h2, h2, h2, h2);
        fence_async_smem();
        __syncwarp();
        if (lane == 0) { mbar_arrive(bar + B_H); PROF(20); }
      }
      if (f < 2) {
        const uint32_t own = (hg * 2 + f) * 16 + mb, target = __shfl_sync(~0u, tag, 0) * 16;
        mbar_wait(bar + B_KVST + 8 * f, 0);
        if (f == 1 && lane == 0) PROF(11);
        wait_hint(g_xcnt + hg * 64 + f * 16 + mb, target);
        if (elect_one()) {
          PROF(35 + f);
          fence_async_global();
          mbar_expect_tx(bar + B_PART + 8 * f, 8192);
          bulk_load(sb + (f ? SM_PST1 : SM_PST0), g_part + own * 512, 8192, bar + B_PART + 8 * f);
        }
        __syncwarp();
        {
          uint4 uz;
#pragma unroll 1
          for (int it = 0; it < SPIN_MAX; it++) {
            uz = ld_rlx128(g_zpart + own * 128 + lane * 4);
            if (__all_sync(~0u, !(BAD4(uz) & 1))) break;
          }
          const bool b1 = lane & 2, b2 = lane & 4;
          const float z0 = unmark(b1 ? uz.z : uz.x) + __shfl_xor_sync(~0u, unmark(b1 ? uz.x : uz.z), 2);
          const float z1 = unmark(b1 ? uz.w : uz.y) + __shfl_xor_sync(~0u, unmark(b1 ? uz.y : uz.w), 2);
          float z = (b2 ? z1 : z0) + __shfl_xor_sync(~0u, b2 ? z0 : z1, 4);
          z += __shfl_xor_sync(~0u, z, 8);
          z += __shfl_xor_sync(~0u, z, 16);
          if (lane < 8) st_rlx(g_zres + own * 8 + (lane & 1) * 4 + (lane & 2) + (lane >> 2), mark(__float_as_uint(z), par));
          if (lane == 0) red_inc(g_xcnt + hg * 64 + 32 + f * 16);
          __syncwarp();
        }
        wait_hint(g_xcnt + hg * 64 + 32 + f * 16, 5 * target);
        mbar_wait(bar + B_KVST + 8, 0);
        if (lane == 0) PROF(40 + f);
#pragma unroll 1
        for (int it = 0; it < SPIN_MAX; it++) {
          if (elect_one()) {
            fence_async_global();
            mbar_expect_tx(bar + B_RES + 8 * f, 8192);
            bulk_load(sb + SM_V + f * 8192, g_res[par] + (hg * 4 + f * 2) * 256, 8192, bar + B_RES + 8 * f);
          }
          __syncwarp();
          const uint4 uz = ld_rlx128(g_zres + (hg * 4 + f * 2) * 64 + lane * 4);
          const uint32_t zw[4] = {uz.x, uz.y, uz.z, uz.w};
#pragma unroll
          for (int j = 0; j < 4; j++) {
            const uint32_t zz = pack2(unmark(zw[j]), 1.f), row = (lane & 3) * 4 + j;
            sts128u(sb + SM_ZT + (2 * f + (lane >> 4)) * 1024 + row * 64 + ((((lane >> 2) ^ (row >> 1)) & 3) << 4), zz, zz, zz, zz);
          }
          uint32_t bad = BAD4(uz);
          mbar_wait(bar + B_RES + 8 * f, it & 1);
#pragma unroll
          for (int i = 0; i < 16; i++) bad |= ~__float_as_uint(lds32(sb + SM_V + f * 8192 + i * 512 + lane * 16));
          if (__all_sync(~0u, !(bad & 1))) break;
        }
        fence_async_smem();
        __syncwarp();
        if (lane == 0) { mbar_arrive(bar + B_TILE + 8 * f); PROF(f ? 13 : 27); }
      }
      if (f < 2) {
        uint32_t phases = 0;
#pragma unroll 1
        for (int i = 2; i < 16; i++) {
          const int s = i & 3;
          const uint32_t ab = bar + B_AIN + s * 16 + f * 8, slot = sb + s * Q_STAGE + f * 8192;
#pragma unroll 1
          for (int it = 0; it < SPIN_MAX; it++) {
            mbar_wait(ab, (phases >> s) & 1);
            phases ^= 1u << s;
            uint32_t bad = 0;
#pragma unroll
            for (int n = 0; n < (NOVAL ? 0 : 8); n++) bad |= __float_as_uint(lds32(slot + n * 1024 + lane * 32 + (lane >> 2) * 4)) ^ par;
            if (__all_sync(~0u, !(bad & 1))) break;
            if (elect_one()) {
              const int n = i < 9 ? i - 2 : i - 9, kb = 2 * (n + (n >= hg)) + (i >= 9);
              PROF(49);
              mbar_expect_tx(ab, 8192);
              bulk_load(slot, g_ofr + (mb * 16 + kb) * 1024 + f * 512, 8192, ab);
            }
            __syncwarp();
          }
          if (lane == 0) { mbar_arrive(bar + B_FULLQ + 8 * s); if (i == 2 && f == 0) PROF(15); }
        }
        if (f == 0) g_epoch[bid * 32 + lane] = tag;
      } else {
        if (elect_one()) {
          prefetch_map(&mOut);
          if (ffn) { mbar_wait(bar + B_YD, 0); red_rel(g_ycnt); PROF(21); }
        }
        __syncwarp();
        if (f == 2) {
          const uint32_t best = __float_as_uint(lds32(sb + SM_RED + 20));
          const int sel = 2047 - (best & 0x7ff) - mb * 128;
          if (sel >= 0 && sel < 128) {
            const uint2 xr = __ldg((const uint2*)(P.x + (size_t)(mb * 128 + sel) * DM + hg * 128 + lane * 4));
            const float2 st = lds64(sb + SM_STAT + sel * 8);
            const uint32_t ord = best >> 16, rb = (ord & 0x8000u) ? (ord & 0x7fffu) : (~ord & 0xffffu);
            const float sg = rcp(1.f + ex2(-1.4426950408889634f * bf_lo(rb)));
            const uint32_t sg2 = pack2(sg, sg), nm2 = pack2(st.x, st.x);
            wait_cnt<0>(g_ycnt, tag * NFFN);
            float4 y = make_float4(0.f, 0.f, 0.f, 0.f);
#pragma unroll
            for (int i = 0; i < 8; i++) {
              const float4 c = ldg_cg4(g_y[par ^ 1][i] + hg * 128 + lane * 4);
              y.x += c.x; y.y += c.y; y.z += c.z; y.w += c.w;
            }
            uint32_t o[2];
#pragma unroll
            for (int i = 0; i < 2; i++) {
              const uint32_t d = badd2(i ? xr.y : xr.x, nm2);
              const uint32_t tt = badd2(pack2(bf_lo(d) * st.y, bf_hi(d) * st.y), bmul2(i ? pack2(y.z, y.w) : pack2(y.x, y.y), sg2));
              o[i] = pack2(silu_f(bf_lo(tt)), silu_f(bf_hi(tt)));
            }
            sts64u(sb + SM_UPD + lane * 8, o[0], o[1]);
          }
          if (lane == 0) sts32(sb + SM_UPD + 256, __int_as_float(sel));
          __syncwarp();
          if (lane == 0) { mbar_arrive(bar + B_UPD); PROF(22); }
        }
      }
    }
  } else {
    const int t7 = threadIdx.x & 127;
    const char* pfa = warp < 4 ? (const char*)P.x + bid * 32768 + (t7 & 15) * 2048 + (t7 >> 4) * 128
                               : (const char*)P.wqkv + (size_t)((t7 >> 4) * 64 + (bid >> 1)) * 6144 + 2048 + (bid & 1) * 2048 + (t7 & 15) * 128;
    if (t7 >= 16 && t7 < 16 * PF_FIRST) prefetch_l2(pfa);
    if (warp < 7) sts128(sb + SM_CST + threadIdx.x * 16, 0.f, 0.f, 0.f, 0.f);
    else sts32(sb + SM_RED + (threadIdx.x & 15) * 4, threadIdx.x & 8 ? 1.f : 0.f);
    if (elect_one()) {
#pragma unroll 1
      for (uint32_t b = B_FST + warp * 8; b < B_END; b += 64)
        mbar_init(bar + b, b < B_FULLQ ? 1 : b < B_FFN ? 3 : b < B_EMPTYKV ? 4 : 8);
    }
    __syncwarp();
    asm volatile("bar.arrive 13, 384;" ::: "memory");
    asm volatile("setmaxnreg.inc.sync.aligned.u32 %0;" ::"n"(REG_C));
    if (t7 >= 16 * PF_FIRST && threadIdx.x < 128 + 16 * PF_W) prefetch_l2(pfa);
    asm volatile("cp.async.wait_all;" ::: "memory");
    fence_async_smem();
    bar_sync(14, 288);
    if (threadIdx.x == 0) mbar_arrive(bar + B_FULLKV + 16);
    const int lane = lane_id();
    const int wg = warp >> 2, w = warp & 3, g = lane >> 2, t = lane & 3;
    float kv[128];
    {
      uint32_t s = 2, ph = 0, sp = 0, php = 0;
#pragma unroll 1
      for (int j = 0; j < 15; j++) {
        PW0(32 + j); mbar_wait(bar + B_FULLKV + 8 * s, ph); PW1(32 + j);
        if (wg == 1 && (ORDER_ALL || j == 0)) bar_sync(10 + s, 256);
        wg_fence();
        wgmma_n256_ssp_ta0_tb1(kv, mkdesc(sb, 16, 1024, 1, wg * 512 + s * (KV_STAGE / 16)), mkdesc(sb + 16384, 8192, 1024, 1, s * (KV_STAGE / 16)), j);
#pragma unroll
        for (int k = 1; k < 4; k++)
          wgmma_n256_ss_ta0_tb1(kv, mkdesc(sb + k * 32, 16, 1024, 1, wg * 512 + s * (KV_STAGE / 16)),
                                mkdesc(sb + 16384 + k * 2048, 8192, 1024, 1, s * (KV_STAGE / 16)), 1);
        wg_commit();
        if (wg == 0 && (ORDER_ALL || j == 0)) asm volatile("bar.arrive %0, 256;" ::"r"(10 + s) : "memory");
        if (warp == 0 && j) {
          mbar_wait(bar + B_EMPTYKV + 8 * sp, php);
          if (elect_one()) {
            if (j < 14) {
              mbar_expect_tx(bar + B_FULLKV + 8 * sp, KV_STAGE);
              tma2d(sb + sp * KV_STAGE, &mX, (j + 2) * 64, mb * 128, bar + B_FULLKV + 8 * sp);
              tma4d(sb + sp * KV_STAGE + 16384, &mWkv, 0, (j + 2) * 64, hg * 2, 1, bar + B_FULLKV + 8 * sp);
            } else {
              Q_LOAD(0);
            }
            if (j < 3 - XS_EARLY) {
              const int xh = j - 1 + XS_EARLY;
              mbar_expect_tx(bar + B_XST + 8 * xh, 16384);
              tma3d(sb + SM_XST + xh * 16384, &mXs, 0, bid * 16, 2 * xh, bar + B_XST + 8 * xh);
            }
          }
          __syncwarp();
        }
        if (j == 0) {
          if (wg == 0) prefetch_l2(pfa + 1024);
        } else if (wg == 1) {
          if (j < 3) {
            if (j == 2 || t7 >= 16 * PF_W) prefetch_l2(pfa + (j - 1) * (8 * 393216));
          } else if (j == 13) {
            prefetch_l2((const char*)P.wo + bid * 16384 + t7 * 128);
          }
          if (PFG && !FFN_OFF && bid < NFFN && j >= 2 && j < 2 + GROWS / 64 && w < 2)
            touch_l2((const char*)((bid & 1) ? P.w_up : P.w_gate) + (size_t)((0x852a7419630ull >> (4 * j - 8) & 15) * 64 + t7) * 7168 + (bid >> 1) * 128, lane);
        }
        wg_wait<0>();
        if (lane == 0) mbar_arrive(bar + B_EMPTYKV + 8 * s);
        sp = s; php = ph;
        ph ^= s == 1;
        s = s == 2 ? 0 : s + 1;
      }
    }
    const int lrow = wg * 64 + w * 16 + (lane & 15);
    const uint32_t sw128 = lrow * 128, x128 = (lrow & 7), hi16 = lane >> 4;
    mbar_wait(bar + B_CS, 0);
    const uint32_t tag = __float_as_uint(lds32(sb + SM_RED + 16));
    const int zero = __float_as_int(lds32(sb + SM_RED + 12));
    const float wn = lds32(sb + SM_RED + 24);
    const float2 st0 = lds64(sb + SM_STAT + (wg * 64 + w * 16 + g) * 8), st1 = lds64(sb + SM_STAT + (wg * 64 + w * 16 + g + 8) * 8);
    const float c0 = st0.y * 1.4426950408889634f, c1 = st1.y * 1.4426950408889634f;
    const uint32_t nm20 = pack2(st0.x, st0.x), nm21 = pack2(st1.x, st1.x), fmask = t == 0 ? ~0u : t == 1 ? 0xffffu : 0u;
    const uint32_t fa0 = nm20 & fmask, fa1 = nm21 & fmask;
    asm volatile("cp.async.wait_all;" ::: "memory");
    PW0(47); mbar_wait(bar + B_FULLKV + 16, 1); PW1(47);
    wg_fence();
    wgmma_n256_rs_ta0_tb1(kv, fa0, fa1, 0u, 0u, mkdesc(sb + SM_CST, 512, 0, 1), 1);
#pragma unroll
    for (int k = 0; k < 4; k++)
      wgmma_n256_ss_ta0_tb1(kv, mkdesc(sb + 2 * KV_STAGE + k * 32, 16, 1024, 1, wg * 512), mkdesc(sb + 2 * KV_STAGE + 16384 + k * 2048, 8192, 1024, 1), 1);
    wg_commit();
    if (warp == 0) {
      mbar_wait(bar + B_EMPTYKV + 8, 0);
      if (elect_one()) {
#pragma unroll 1
        for (int j = 1; j < 3; j++) Q_LOAD(j);
      }
      __syncwarp();
    }
    wg_wait<0>();
    reg_fence<128>(kv);
    if (lane == 0) mbar_arrive(bar + B_EMPTYKV + 16);
    PROFC(2);
    float q[64];
#define QMMA(J, AOFF16, ACCUM)                                                                                     \
  _Pragma("unroll") for (int k = 0; k < 4; k++)                                                                    \
      wgmma_n128_ss_ta0_tb1(q, mkdesc(sb + k * 32, 16, 1024, 1, wg * 512 + (AOFF16)),                              \
                            mkdesc(sb + 16384 + k * 2048, 8192, 1024, 1, ((J) & 3) * (Q_STAGE / 16)), k ? 1 : (ACCUM))
#define QWAIT(J) do { PW0(J); mbar_wait(bar + B_FULLQ + 8 * ((J) & 3), ((J) >> 2) & 1); PW1(J); } while (0)
#define QSTEP_A(J, AOFF16, ACCUM) do { QWAIT(J); wg_fence(); QMMA(J, AOFF16, ACCUM); wg_commit(); } while (0)
#define QREL(J) do { if (lane == 0) mbar_arrive(bar + B_EMPTYQ + 8 * ((J) & 3)); } while (0)
#define Q_OFF16(J) ((J) >= 8 && (J) < 16 ? Q_AOFF(J) / 16 : ((J) & 3) * (Q_STAGE / 16))
#define QPLAIN(J) do { QSTEP_A(J, Q_OFF16(J), 1); wg_wait<1>(); QREL((J) - 1); } while (0)
#define QNEXT(J) do { QPLAIN(J); SCHED_FENCE(); } while (0)
#define PHI_PROJ(DST, SRC, H0, H1)                                                                                 \
  do {                                                                                                             \
    uint32_t a_[32];                                                                                               \
    _Pragma("unroll") for (int j = 8 * (H0); j < 8 * (H1); j++) {                                                  \
      a_[j] = pack2(SRC[2 * j], SRC[2 * j + 1]);                                                                   \
      asm volatile("fma.rn.bf16x2 %0, %1, %1, %0;" : "+r"(nq[(j >> 4) * 2 + (j & 1)]) : "r"(a_[j]));               \
    }                                                                                                              \
    wg_fence();                                                                                                    \
    _Pragma("unroll") for (int hk = 2 * (H0); hk < 2 * (H1); hk++)                                                 \
        wgmma_n32_rs_ta0_tb1(DST + 16 * (hk >> 1), a_[4 * hk], a_[4 * hk + 1], a_[4 * hk + 2], a_[4 * hk + 3],     \
                             mkdesc(sb + SM_WPHI + hk * 1024, 16, 512, 2), hk & 1);                                \
    wg_commit();                                                                                                   \
  } while (0)
    {
      float p[64], ea[24], eb[24], sa[4], sc[4], kz[20];
      uint32_t vp[32];
#pragma unroll
      for (int j = 0; j < 32; j++) vp[j] = pack2(kv[64 + 2 * j], kv[65 + 2 * j]);
      const uint32_t vr = w * 16 + (lane & 15), vb = sb + SM_V + wg * 4096 + vr * 64, x64 = (vr >> 1) & 3;
#define V_STORE(R)                                                                                           \
  _Pragma("unroll") for (int j = 0; j < 4; j++)                                                              \
      stsm4(vb + (j >> 1) * 8192 + ((((j & 1) * 2 + hi16) ^ x64) << 4), vp[16 * (R) + 4 * j], vp[16 * (R) + 4 * j + 1], vp[16 * (R) + 4 * j + 2], vp[16 * (R) + 4 * j + 3])
      V_STORE(0);
      mbar_wait(bar + B_WPHI, 0);
      {
        uint32_t nq[4] = {0u, 0u, 0u, 0u};
        PHI_PROJ(p, kv, 0, 4);
        QSTEP_A(0, 0, 0);
        const bool unsafe = softmax_unsafe(nq, c0 * c0 * wn, c1 * c1 * wn);
        wg_wait<1>();
        reg_fence<64>(p);
        if (__builtin_expect(unsafe, 0)) softmax_shift(p, c0, c1);
      }
#define K_NORM(S) do { quad_sum<4>(S); _Pragma("unroll") for (int i = 0; i < 4; i++) S[i] = rcp(S[i]) * ((i & 1) ? st1.y : st0.y); } while (0)
#define K_STORE(SLOT, E, S) K_STORE_(SLOT, E, S, 0, 2)
#define K_STORE_(SLOT, E, S, J0, J1)                                                                         \
  _Pragma("unroll") for (int j = (J0); j < (J1); j++) {                                                      \
    uint32_t fp[4], fm[4];                                                                                   \
    _Pragma("unroll") for (int i = 0; i < 4; i++) {                                                          \
      const float e0 = E[8 * j + 2 * i], e1 = E[8 * j + 2 * i + 1], r = E[16 + 4 * j + i] * S[2 + (i & 1)];  \
      const uint32_t e2 = pack2(e0, e1);                                                                     \
      fp[i] = bmul2(e2, pack2(S[i & 1], S[i & 1]));                                                          \
      fm[i] = bmul2(e2, pack2(r, r));                                                                        \
    }                                                                                                        \
    stsm4(sb + SM_PHI + (SLOT) * 16384 + sw128 + (((2 * j + hi16) ^ x128) << 4), fp[0], fp[1], fp[2], fp[3]); \
    stsm4(sb + SM_PHI + (SLOT) * 16384 + sw128 + (((4 + 2 * j + hi16) ^ x128) << 4), fm[0], fm[1], fm[2], fm[3]); \
  }
#define KV_MMA(R)                                                                                            \
  do {                                                                                                       \
    mbar_wait(bar + B_PHI + 8 * (R), 0);                                                                     \
    wg_fence();                                                                                              \
    _Pragma("unroll") for (int k = 0; k < 8; k++) {                                                          \
      const uint32_t vs = SM_V + (k >> 2) * 4096 + (k & 3) * 1024;                                           \
      wgmma_n40_ss_ta1_tb1(kz, mkdesc(sb + SM_PHI + k * 2048, 16, 1024, 1, wg * 1024),                       \
                           mkdesc(sb + vs, SM_SDT + (k & 1) * 1024 + (k >> 1) * 16 - vs, 512, 2, wg * (512u - (512u << 16))), k); \
    }                                                                                                        \
    wg_commit();                                                                                             \
  } while (0)
#define QKV(J, R) do { KV_MMA(R); QSTEP_A(J, Q_OFF16(J), 1); wg_wait<2>(); QREL((J) - 1); SCHED_FENCE(); } while (0)
#define KV_SEND(R)                                                                                           \
  do {                                                                                                       \
    reg_fence<20>(kz);                                                                                       \
    if (lane == 0) mbar_arrive(bar + B_KVST + 8 * (R));                                                      \
    const uint32_t slot = ((hg * 2 + (R)) * 16 + warp * 2) * 16 + mb;                                        \
    _Pragma("unroll") for (int u = 0; u < 2; u++)                                                            \
      st_rlx128(g_part + (slot + u * 16) * 32 + lane, mark(pack2(kz[2 * u], kz[2 * u + 1]), tag & 1), pack2(kz[2 * u + 4], kz[2 * u + 5]), \
                pack2(kz[2 * u + 8], kz[2 * u + 9]), pack2(kz[2 * u + 12], kz[2 * u + 13]));                 \
    if (t < 2) st_rlx(g_zpart + (slot + t * 16) * 8 + g, mark(__float_as_uint(t ? kz[18] : kz[16]), tag & 1)); \
    if (lane < 2) red_inc(g_xcnt + hg * 64 + (R) * 16 + warp * 2 + lane);                                    \
  } while (0)
#define K_PUB(R) do { fence_async_smem(); __syncwarp(); if (lane == 0) mbar_arrive(bar + B_PHI + 8 * (R)); } while (0)
#define S_PIN(S) SCHED_PIN(S[0] + S[1] + S[2] + S[3])
      k_exp(p, c0, c1, ea, sa);
      S_PIN(sa);
      QNEXT(1);
      K_NORM(sa);
      k_exp<0, 4>(p + 16, c0, c1, eb, sc);
      mbar_wait(bar + B_FFN, 0);
      K_STORE_(0, ea, sa, 0, 1);
      S_PIN(sc);
      QNEXT(2);
      K_STORE_(0, ea, sa, 1, 2);
      k_exp<4, 8>(p + 16, c0, c1, eb, sc);
      K_NORM(sc);
      S_PIN(sc);
      QNEXT(3);
      K_STORE(1, eb, sc);
      K_PUB(0);
      k_exp<0, 4>(p + 32, c0, c1, ea, sa);
      S_PIN(sa);
      QKV(4, 0);
      k_exp<4, 8>(p + 32, c0, c1, ea, sa);
      K_NORM(sa);
      k_exp<0, 4>(p + 48, c0, c1, eb, sc);
      SCHED_PIN(sa[0] + sa[1] + sa[2] + sa[3] + sc[2] + sc[3]);
      QNEXT(5);
      KV_SEND(0);
      k_exp<4, 8>(p + 48, c0, c1, eb, sc);
      S_PIN(sc);
      QNEXT(6);
      K_NORM(sc);
      mbar_wait(bar + B_KVST, 0);
      V_STORE(1);
      K_STORE(0, ea, sa);
      QNEXT(7);
      K_STORE(1, eb, sc);
      K_PUB(1);
      QKV(8, 1);
      QNEXT(9);
      KV_SEND(1);
    }
#define JQ0 10
    PROFC(3);
    {
      bool todo = true;
#pragma unroll 1
      for (int j = JQ0; j < 15 || todo; j++) {
        if (j < 15) { QSTEP_A(j, Q_AOFF(j) / 16, 1); wg_wait<1>(); QREL(j - 1); }
        if (todo && __any_sync(~0u, mbar_test(bar + B_PART + 8 * wg, 0))) {
          todo = false;
          const uint32_t own = (hg * 2 + wg) * 16 + mb, word = w * 32 + lane;
          uint32_t u[16], bad = 0;
#pragma unroll
          for (int i = 0; i < 16; i++) { u[i] = __float_as_uint(lds32(sb + (wg ? SM_PST1 : SM_PST0) + i * 512 + word * 4)); bad |= u[i] ^ tag; }
#pragma unroll 1
          for (int it = 0; it < SPIN_MAX && __any_sync(~0u, t == 0 && (bad & 1)); it++) {
            bad = 0;
#pragma unroll
            for (int i = 0; i < 16; i++) { u[i] = ld_rlx((const uint32_t*)g_part + own * 2048 + i * 128 + word); bad |= u[i] ^ tag; }
          }
          float s0 = 0.f, s1 = 0.f, s2 = 0.f, s3 = 0.f;
#pragma unroll
          for (int i = 0; i < 16; i += 2) { s0 += bf_lo(u[i] | !t); s1 += bf_hi(u[i]); s2 += bf_lo(u[i + 1] & (t ? ~0u : ~1u)); s3 += bf_hi(u[i + 1]); }
          const uint32_t r = pack2(s0 + s2, s1 + s3);
          st_rlx((uint32_t*)g_res[tag & 1] + own * 128 + w * 32 + (lane & 16) + ((t ^ w) << 2) + ((lane >> 2) & 3), lane & 12 ? r : r | 1);
          ((uint32_t*)g_res[~tag & 1])[own * 128 + word] = 0;
          __syncwarp();
          if (lane == 0) { red_inc(g_xcnt + hg * 64 + 32 + wg * 16); if (w == 0) PROF(wg ? 12 : 30); }
          __syncwarp();
        }
      }
    }
    mbar_wait(bar + B_CSQ, 0);
    QWAIT(15);
    if (wg == 1) bar_sync(6, 256);
    wg_fence();
    wgmma_n128_rs_ta0_tb1(q, fa0, fa1, 0u, 0u, mkdesc(sb + SM_CST + 2048, 512, 0, 1), 1);
    QMMA(15, Q_AOFF(15) / 16, 1);
    wg_commit();
    if (wg == 0) asm volatile("bar.arrive 6, 256;" ::: "memory");
    wg_wait<1>();
    QREL(14);
    wg_wait<0>();
    QREL(15);
    reg_fence<64>(q);
    PROFC(5);
    float yp[4];
    const uint32_t par = tag & 1;
    uint4* ofr = g_ofr + (mb * 16 + hg * 2) * 1024 + (warp * 16 + g) * 8;
#define O_MMA(H, F, N)                                                                                       \
  do {                                                                                                       \
    wg_fence();                                                                                              \
    _Pragma("unroll") for (int k = 0; k < 4; k++) {                                                          \
      const uint32_t ks = SM_V + (H) * 4096 + k * 1024;                                                      \
      wgmma_n40_rs_ta0_tb1(N + 20 * (k >> 1), F[4 * k], F[4 * k + 1], F[4 * k + 2], F[4 * k + 3],            \
                           mkdesc(sb + ks, SM_ZT + (H) * 1024 + k * 16 - ks, 512, 2), k & 1);                \
    }                                                                                                        \
    wg_commit();                                                                                             \
  } while (0)
#define O_FIN(H, N, o)                                                                                        \
  do {                                                                                                       \
    reg_fence<40>(N);                                                                                        \
    const float *np = N, *nm = N + 20;                                                                       \
    const float d0 = rcp(fmaf(np[16], nm[17], fmaf(nm[16], np[17], 1e-6f * np[17] * nm[17])));               \
    const float d1 = rcp(fmaf(np[18], nm[19], fmaf(nm[18], np[19], 1e-6f * np[19] * nm[19])));               \
    const float bp0 = nm[17] * d0, bm0 = np[17] * d0, bp1 = nm[19] * d1, bm1 = np[19] * d1;                  \
    _Pragma("unroll") for (int j = 0; j < 4; j++) {                                                          \
      o[2 * j] = pack2(fmaf(np[4 * j], bp0, nm[4 * j] * bm0), fmaf(np[4 * j + 1], bp0, nm[4 * j + 1] * bm0)); \
      o[2 * j + 1] = pack2(fmaf(np[4 * j + 2], bp1, nm[4 * j + 2] * bm1), fmaf(np[4 * j + 3], bp1, nm[4 * j + 3] * bm1)); \
    }                                                                                                        \
  } while (0)
#define O_STG(H, o)                                                                                          \
  _Pragma("unroll") for (int u = 0; u < 2; u++) {                                                            \
    uint32_t v_[4];                                                                                          \
    _Pragma("unroll") for (int j = 0; j < 4; j++) v_[j] = lop_select(o[2 * j + u], parm, vword == j);        \
    st_rlx128(ofr + ((H) >> 1) * 1024 + u * 64 + ((((H) & 1) * 4 + t) ^ g), v_[0], v_[1], v_[2], v_[3]);     \
  }
    uint32_t gf[32], ao[16];
    const uint32_t parm = 0u - par, vword = ((t ^ g) & 1) == (g >> 2) ? g & 3 : 4;
    const float rh0 = 0.5f * st0.y, rh1 = 0.5f * st1.y, mh0 = st0.x * rh0, mh1 = st1.x * rh1;
#define GATE_LD(J) ldsm4(sb + ((J) >> 2 ? SM_X1 : SM_X0) + sw128 + (((((J) & 3) * 2 + hi16) ^ x128) << 4), gf[4 * (J)], gf[4 * (J) + 1], gf[4 * (J) + 2], gf[4 * (J) + 3])
#define GATE(I0, I1)                                                                                         \
  _Pragma("unroll") for (int i = (I0); i < (I1); i++) {                                                      \
    const float rs = (i & 1) ? rh1 : rh0, mh = (i & 1) ? mh1 : mh0;                                          \
    const float h0 = fmaf(bf_lo(gf[i]), rs, mh), h1 = fmaf(bf_hi(gf[i]), rs, mh);                            \
    gf[i] = pack2(fmaf(h0, tanh_approx(h0), h0), fmaf(h1, tanh_approx(h1), h1));                             \
  }
#define GATE_PIN(I0, I1) do { uint32_t o_ = 0; _Pragma("unroll") for (int i = (I0); i < (I1); i++) o_ |= gf[i]; SCHED_PIN(__uint_as_float(o_)); } while (0)
    {
      float p[64], na[40], nb[40];
      uint32_t fa[16], fb[16];
      {
        uint32_t nq[4] = {0u, 0u, 0u, 0u};
        PHI_PROJ(p, q, 0, 2);
        SCHED_FENCE();
        PHI_PROJ(p, q, 2, 4);
        const bool unsafe = softmax_unsafe(nq, c0 * c0 * wn, c1 * c1 * wn);
        if (TW == 0) mbar_wait(bar + B_TILE, 0);
        wg_wait<0>();
        reg_fence<64>(p);
        PROFC(24);
        if (__builtin_expect(unsafe, 0)) softmax_shift(p, c0, c1);
      }
      float dn[32];
#define DN_PART(A, B)                                                                                        \
  do {                                                                                                       \
    wg_fence();                                                                                              \
    _Pragma("unroll") for (int i = (A); i < (B); i++)                                                        \
      wgmma_n8_ss_ta1_tb1(dn + 4 * (i >> 1), mkdesc(sb + (i >> 3) * Q_STAGE + (i & 7) * 2048, 16, 1024, 1, wg * (2 * Q_STAGE / 16)), \
                          mkdesc(sb + SM_HT + (i & 1) * 256, 128, 128, 0), i & 1);                           \
  } while (0)
#define F_PIN(F, A, B) do { uint32_t o_ = 0; _Pragma("unroll") for (int i = (A); i < (B); i++) o_ |= F[8 + i]; SCHED_PIN(__uint_as_float(o_)); } while (0)
#define RMMA(J, A, ACCUM)                                                                                    \
  do {                                                                                                       \
    wg_fence();                                                                                              \
    _Pragma("unroll") for (int k = 0; k < 4; k++)                                                            \
      wgmma_n128_rs_ta0_tb1(q, (A)[4 * k], (A)[4 * k + 1], (A)[4 * k + 2], (A)[4 * k + 3],                   \
                            mkdesc(sb + 16384 + k * 2048, 8192, 1024, 1, ((J) & 3) * (Q_STAGE / 16)), k ? 1 : (ACCUM)); \
    wg_commit();                                                                                             \
  } while (0)
#define RSTEP(J, A, ACCUM) do { QWAIT(J); RMMA(J, A, ACCUM); } while (0)
      PROFC(4);
      q_exp(p, c0, c1, fa);
      if (TW == 1) { F_PIN(fa, 0, 8); mbar_wait(bar + B_TILE, 0); }
      if (TW == 2) { q_exp(p + 16, c0, c1, fb); F_PIN(fb, 0, 8); mbar_wait(bar + B_TILE, 0); }
      O_MMA(0, fa, na);
      if (TW != 2) q_exp(p + 16, c0, c1, fb);
      O_MMA(1, fb, nb);
      PROFC(25);
      wg_wait<1>();
      O_FIN(0, na, ao);
      O_STG(0, ao);
      wg_wait<0>();
      O_FIN(1, nb, (ao + 8));
      O_STG(1, (ao + 8));
      PROFC(28);
      RSTEP(16, ao, 0);
      SCHED_FENCE();
      q_exp(p + 32, c0, c1, fa);
      F_PIN(fa, 0, 8);
      mbar_wait(bar + B_H, 0);
      mbar_wait(bar + B_DN, 0);
      PROFC(45);
      DN_PART(0, 4);
      SCHED_FENCE();
      q_exp<0, 2>(p + 48, c0, c1, fb);
      F_PIN(fb, 0, 2);
      DN_PART(4, 8);
      SCHED_FENCE();
      q_exp<2, 4>(p + 48, c0, c1, fb);
      F_PIN(fb, 2, 4);
      DN_PART(8, 12);
      SCHED_FENCE();
      q_exp<4, 6>(p + 48, c0, c1, fb);
      F_PIN(fb, 4, 6);
      DN_PART(12, 16);
      wg_commit();
      SCHED_FENCE();
      q_exp<6, 8>(p + 48, c0, c1, fb);
      F_PIN(fb, 6, 8);
      wg_wait<0>();
      reg_fence<32>(dn);
      if (lane == 0) mbar_arrive(bar + B_DND);
      QREL(16);
#pragma unroll
      for (int i = 0; i < 4; i++) yp[i] = t & 2 ? (t & 1 ? dn[24 + 2 * i] : dn[16 + 2 * i]) : (t & 1 ? dn[8 + 2 * i] : dn[2 * i]);
      PROFC(29);
      mbar_wait(bar + B_TILE + 8, 0);
      PROFC(23);
      if (bid < NFFN) {
        float* y = g_y[par ^ 1][bid & 7] + wg * 512 + t * 128 + w * 16 + g;
#pragma unroll
        for (int i = 0; i < 4; i++) red1(y + (i >> 1) * 64 + (i & 1) * 8, yp[i]);
      }
      SCHED_FENCE();
      O_MMA(2, fa, na);
      O_MMA(3, fb, nb);
      __syncwarp();
      if (lane == 0) mbar_arrive(bar + B_YD);
      wg_wait<1>();
      O_FIN(2, na, ao);
      O_STG(2, ao);
      wg_wait<0>();
      O_FIN(3, nb, (ao + 8));
      O_STG(3, (ao + 8));
      PROFC(6);
    }
    RSTEP(17, ao, 1);
    SCHED_FENCE();
    GATE_LD(0); GATE_LD(1);
    GATE(0, 4);
    GATE_PIN(0, 4);
#define GSTEP(J, I) do { QNEXT(J); if ((I) < 7) GATE_LD(((I) + 1) & 7); GATE(4 * (I), 4 * (I) + 4); GATE_PIN(4 * (I), 4 * (I) + 4); } while (0)
    GSTEP(18, 1); GSTEP(19, 2); GSTEP(20, 3); GSTEP(21, 4); GSTEP(22, 5); GSTEP(23, 6); GSTEP(24, 7);
#pragma unroll 1
    for (int j = 25; j < 32 - TAILN; j++) QPLAIN(j);
    if (wg == 1) bar_sync(6, 256);
#pragma unroll 1
    for (int j = 32 - TAILN; j < 32; j++) QSTEP_A(j, (j & 3) * (Q_STAGE / 16), 1);
    if (wg == 0) asm volatile("bar.arrive 6, 256;" ::: "memory");
    mbar_wait(bar + B_UPD, 0);
    {
      const int sel = __float_as_int(lds32(sb + SM_UPD + 256)) - (wg * 64 + w * 16 + g);
      if (sel == 0 || sel == 8) {
#pragma unroll
        for (int j = 0; j < 16; j++) {
          const uint32_t u = __float_as_uint(lds32(sb + SM_UPD + j * 16 + t * 4));
          if (sel) gf[2 * j + 1] = u; else gf[2 * j] = u;
        }
      }
      __syncwarp();
      uint32_t xf[32];
#pragma unroll
      for (int j = 0; j < 8; j++)
        ldsm4(sb + (j >> 2 ? SM_X1 : SM_X0) + sw128 + ((((j & 3) * 2 + hi16) ^ x128) << 4), xf[4 * j], xf[4 * j + 1], xf[4 * j + 2], xf[4 * j + 3]);
      wg_wait<0>();
      reg_fence<64>(q);
      PROFC(8);
#pragma unroll
      for (int j = 0; j < 8; j++) {
        uint32_t o[4];
#pragma unroll
        for (int i = 0; i < 4; i++) o[i] = badd2(xf[4 * j + i], bmul2(pack2(q[8 * j + 2 * i], q[8 * j + 2 * i + 1]), gf[4 * j + i]));
        stsm4(sb + (j >> 2 ? SM_X1 : SM_X0) + sw128 + ((((j & 3) * 2 + hi16) ^ x128) << 4), o[0], o[1], o[2], o[3]);
      }
    }
    fence_async_smem();
    bar_sync(2 + wg, 128);
    if (w == 0 && elect_one()) {
      tma_store2d(&mOut, sb + SM_X0 + wg * 8192, hg * 128, mb * 128 + wg * 64);
      tma_store2d(&mOut, sb + SM_X1 + wg * 8192, hg * 128 + 64, mb * 128 + wg * 64);
      bulk_commit();
      bulk_wait_read0();
      if (wg == 1) { PROF(9); PROFT(33); PROF_DUMP; }
    }
  }
}

typedef CUresult (*EncodeFn)(CUtensorMap*, CUtensorMapDataType, cuuint32_t, void*, const cuuint64_t*, const cuuint64_t*, const cuuint32_t*,
                             const cuuint32_t*, CUtensorMapInterleave, CUtensorMapSwizzle, CUtensorMapL2promotion, CUtensorMapFloatOOBfill);

CUtensorMap make_map(EncodeFn enc, const void* ptr, int rank, const cuuint64_t* dims, const cuuint64_t* strides, const cuuint32_t* box, CUtensorMapSwizzle sw) {
  CUtensorMap m;
  const cuuint32_t es[5] = {1, 1, 1, 1, 1};
  enc(&m, CU_TENSOR_MAP_DATA_TYPE_BFLOAT16, rank, (void*)ptr, dims, strides, box, es, CU_TENSOR_MAP_INTERLEAVE_NONE, sw,
      CU_TENSOR_MAP_L2_PROMOTION_L2_128B, CU_TENSOR_MAP_FLOAT_OOB_FILL_NONE);
  return m;
}

}

extern "C" void kernel_launch(void* const* d_in, const int* in_sizes, int n_in, void* d_out, int out_size) {
  static EncodeFn enc = nullptr;
  static int by_sm = 0;
  if (!enc) {
    void* fn = nullptr;
    cudaDriverEntryPointQueryResult qr;
    cudaGetDriverEntryPoint("cuTensorMapEncodeTiled", &fn, cudaEnableDefault, &qr);
    enc = (EncodeFn)fn;
    cudaFuncSetAttribute(fused_kernel<false>, cudaFuncAttributeMaxDynamicSharedMemorySize, SM_TOTAL);
    cudaFuncSetAttribute(fused_kernel<true>, cudaFuncAttributeMaxDynamicSharedMemorySize, SM_TOTAL);
    int dev = 0, sms = 0;
    cudaGetDevice(&dev);
    cudaDeviceGetAttribute(&sms, cudaDevAttrMultiProcessorCount, dev);
    by_sm = BY_SM && sms == NCTA + NSPARE;
  }
  Params P;
  P.x = (const __nv_bfloat16*)d_in[0];
  P.wqkv = (const __nv_bfloat16*)d_in[1];
  const void* wphi = d_in[2];
  P.wo = (const __nv_bfloat16*)d_in[3];
  P.w_r = (const __nv_bfloat16*)d_in[5];
  P.w_gate = (const __nv_bfloat16*)d_in[6];
  P.w_up = (const __nv_bfloat16*)d_in[7];
  P.w_down = (const __nv_bfloat16*)d_in[8];

  const cuuint64_t dX[2] = {DM, SEQ}, sX[1] = {DM * 2};
  const cuuint32_t b128[2] = {64, 128}, b64[2] = {64, 64};
  const cuuint64_t dW[4] = {64, DM, 16, 3}, sW[3] = {3 * DM * 2, 128, DM * 2};
  const cuuint32_t bKV[4] = {64, 64, 2, 2}, bQ[4] = {64, 64, 2, 1};
  const cuuint64_t dO[3] = {64, DM, 16}, sO[2] = {DM * 2, 128};
  const cuuint32_t bO[3] = {64, 64, 2};
  const cuuint64_t dP[2] = {32, 1024}, sP[1] = {64};
  const cuuint32_t bP[2] = {32, 128};
  CUtensorMap mX = make_map(enc, P.x, 2, dX, sX, b128, CU_TENSOR_MAP_SWIZZLE_128B);
  CUtensorMap mWkv = make_map(enc, P.wqkv, 4, dW, sW, bKV, CU_TENSOR_MAP_SWIZZLE_128B);
  CUtensorMap mWq = make_map(enc, P.wqkv, 4, dW, sW, bQ, CU_TENSOR_MAP_SWIZZLE_128B);
  CUtensorMap mWo = make_map(enc, P.wo, 3, dO, sO, bO, CU_TENSOR_MAP_SWIZZLE_128B);
  CUtensorMap mPhi = make_map(enc, wphi, 2, dP, sP, bP, CU_TENSOR_MAP_SWIZZLE_64B);
  const cuuint64_t dWp[5] = {DM, 2, 4, 4, DM / 32}, sWp[4] = {DM * 2, 8 * DM * 2, 2 * DM * 2, 32 * DM * 2};
  const cuuint32_t bWp[5] = {64, 2, 4, 4, 2};
  CUtensorMap mWp = make_map(enc, P.wo, 5, dWp, sWp, bWp, CU_TENSOR_MAP_SWIZZLE_128B);
  CUtensorMap mOut = make_map(enc, d_out, 2, dX, sX, b64, CU_TENSOR_MAP_SWIZZLE_128B);
  const cuuint64_t dWc[2] = {3 * DM, DM}, sWc[1] = {3 * DM * 2}, dG[2] = {FF, DM}, sG[1] = {FF * 2}, dD[3] = {64, FF, 16};
  const cuuint32_t b32[2] = {32, 32}, bD[3] = {64, 32, 4};
  CUtensorMap mWc = make_map(enc, P.wqkv, 2, dWc, sWc, b32, CU_TENSOR_MAP_SWIZZLE_NONE);
  CUtensorMap mG = make_map(enc, P.w_gate, 2, dG, sG, b32, CU_TENSOR_MAP_SWIZZLE_NONE);
  CUtensorMap mU = make_map(enc, P.w_up, 2, dG, sG, b32, CU_TENSOR_MAP_SWIZZLE_NONE);
  CUtensorMap mD = make_map(enc, P.w_down, 3, dD, sO, bD, CU_TENSOR_MAP_SWIZZLE_128B);
  const cuuint64_t dXs[3] = {256, SEQ, 4}, sXs[2] = {DM * 2, 512};
  const cuuint32_t bXs[3] = {256, 16, 2};
  CUtensorMap mXs = make_map(enc, P.x, 3, dXs, sXs, bXs, CU_TENSOR_MAP_SWIZZLE_NONE);
  const cuuint64_t dG2[4] = {64, DM, FF / 64, 1}, sG2[3] = {FF * 2, 128, (cuuint64_t)FF * DM * 2};
  CUtensorMap mG2 = make_map(enc, P.w_gate, 4, dG2, sG2, bQ, CU_TENSOR_MAP_SWIZZLE_128B);
  CUtensorMap mU2 = make_map(enc, P.w_up, 4, dG2, sG2, bQ, CU_TENSOR_MAP_SWIZZLE_128B);
  (by_sm ? fused_kernel<true> : fused_kernel<false>)<<<NCTA + NSPARE, 384, SM_TOTAL, cudaStreamPerThread>>>(mX, mWkv, mWq, mWo, mPhi, mWp, mOut, mWc, mG, mU, mD, mXs,
                                                                                                           mG2, mU2, P);
}
```

```cpp
#include <cuda_runtime.h>
#include <cuda_bf16.h>
#include <cuda.h>
#include <stdint.h>

namespace {

constexpr int SEQ = 2048, DM = 1024, FF = 3584;
constexpr int NCTA = 128;
constexpr int NSPARE = 4;
constexpr int NFFN = FF / 32;
#define GN 6
#define G8 2
constexpr int GROWS = (3 * GN + G8) * 32;
#define TAILN 2
#define KTAIL 1
#define XS_EARLY 1
#define PF_FIRST 2
#define PF_W 5
#define PF_PRE 1
#define PFG 0
#define PFD 80
#define BY_SM 1
#define PTAB 0x73216540u
#define ROWSPLIT 1
#define WOT 1
#define PSPLIT 1
#define KSTEPS 4
#define NOVAL 0
#define KCH 1
#define REG_C 224
#define REG_H 56
#define TW 1
#define FENCE_KIND 2
#define SP_DELAY 3000
#define ORDER_ALL 1
#define AM_NS 100
constexpr bool FFN_OFF = false;

static_assert(2 * REG_C + REG_H <= 3 * 168, "the register pool of the CTA is 384 x 168");

__device__ uint32_t g_epoch[(NCTA + NSPARE) * 32];
__device__ unsigned long long g_stat[SEQ];
__device__ __align__(128) unsigned long long g_best[NCTA];
__device__ __align__(16) float g_y[2][8][DM];
__device__ __align__(128) uint32_t g_ycnt[64];
__device__ __align__(128) uint32_t g_xcnt[8 * 64];
__device__ __align__(128) uint4 g_res[2][32 * 256];
__device__ __align__(16) float g_cs[5 * DM];
__device__ __align__(128) float g_gp[2 * FF];
__device__ uint4 g_part[8 * 2 * 16 * 16 * 32];
__device__ __align__(16) float g_zpart[8 * 2 * 16 * 16 * 8];
__device__ __align__(128) float g_zres[32 * 64];
__device__ __align__(1024) uint4 g_ofr[16 * 16 * 1024];
#define PROF(i)
#define PROFT(i)
#define PROFC(i)
#define PROF_DUMP
#define PW0(J)
#define PW1(J)

constexpr uint32_t KV_STAGE = 49152, Q_STAGE = 32768;
constexpr uint32_t SM_V = 147456;
constexpr uint32_t SM_PHI = 163840;
constexpr uint32_t SM_XST = 147456;
constexpr uint32_t SM_FST = 172032;
constexpr uint32_t SM_PST0 = 196608, SM_PST1 = SM_PHI + 8192;
constexpr uint32_t SM_X0 = 131072, SM_X1 = SM_PHI + 16384;
constexpr uint32_t SM_WPHI = 204800;
constexpr uint32_t SM_ZT = 212992;
constexpr uint32_t SM_SDT = 217088;
constexpr uint32_t SM_CST = 219136;
constexpr uint32_t SM_HT = 222720;
constexpr uint32_t SM_STAT = 223232;
constexpr uint32_t SM_XSEL = 224256;
constexpr uint32_t SM_RED = 228352;
constexpr uint32_t SM_ROWS = SM_RED + 832;
constexpr uint32_t SM_GRED = SM_XSEL + 3072;
static_assert(GROWS <= 768, "xsel area");
constexpr uint32_t SM_UPD = 229632;
constexpr uint32_t SM_BAR = 230016;
constexpr uint32_t SM_PROF = 230464;
constexpr uint32_t SM_SINK = 231104;
constexpr uint32_t SM_TOTAL = 231616;
constexpr uint32_t SB = 1024;
constexpr uint32_t B_FULLKV = 0  , B_FST = 24  , B_XFULL = 88  , B_XST = 104  , B_WPHI = 120, B_CS = 128, B_CSQ = 136, B_UPD = 144,
                   B_H = 152, B_DN = 160, B_XS = 168, B_TILE = 176  , B_RES = 192  , B_PART = 208  ,
B_AIN = 224  ,
                   B_FULLQ = 288  ,
                   B_FFN = 320,
                   B_EMPTYKV = 328  , B_EMPTYQ = 352  , B_KVST = 384  , B_YD = 400, B_PHI = 408  , B_DND = 424, B_END = 432;

__device__ __forceinline__ uint32_t smem_u32(const void* p) { return (uint32_t)__cvta_generic_to_shared(p); }
__device__ __forceinline__ void mbar_init(uint32_t bar, uint32_t cnt) { asm volatile("mbarrier.init.shared::cta.b64 [%0], %1;" ::"r"(bar), "r"(cnt) : "memory"); }
__device__ __forceinline__ void mbar_expect_tx(uint32_t bar, uint32_t bytes) { asm volatile("mbarrier.arrive.expect_tx.shared::cta.b64 _, [%0], %1;" ::"r"(bar), "r"(bytes) : "memory"); }
__device__ __forceinline__ void mbar_arrive2(uint32_t bar) { asm volatile("mbarrier.arrive.shared::cta.b64 _, [%0], 2;" ::"r"(bar) : "memory"); }
__device__ __forceinline__ void mbar_arrive(uint32_t bar) { asm volatile("mbarrier.arrive.shared::cta.b64 _, [%0];" ::"r"(bar) : "memory"); }
__device__ __forceinline__ void mbar_wait(uint32_t bar, uint32_t parity) {
  asm volatile("{\n.reg .pred p;\nLW:\nmbarrier.try_wait.parity.shared::cta.b64 p, [%0], %1;\n@!p bra LW;\n}" ::"r"(bar), "r"(parity) : "memory");
}
__device__ __forceinline__ bool mbar_test(uint32_t bar, uint32_t parity) {
  uint32_t ok;
  asm volatile("{\n.reg .pred p;\nmbarrier.test_wait.parity.shared::cta.b64 p, [%1], %2;\nselp.u32 %0, 1, 0, p;\n}" : "=r"(ok) : "r"(bar), "r"(parity) : "memory");
  return ok;
}
__device__ __forceinline__ int lane_id() { int l; asm volatile("mov.u32 %0, %%laneid;" : "=r"(l)); return l; }
template <int C> __device__ __forceinline__ void sched_fence_(int zero) {
  asm volatile("{\n.reg .pred p;\nsetp.eq.s32 p, %0, %1;\n@p trap;\n}" ::"r"(zero), "n"(C) : "memory");
}
#define SCHED_FENCE() sched_fence_<1000 + __COUNTER__>(zero)
#define SCHED_PIN(V) sched_fence_<1000 + __COUNTER__>(zero & __float_as_int(V))
__device__ __forceinline__ bool elect_one() {
  uint32_t p; asm volatile("{ .reg .pred P; elect.sync _|P, 0xffffffff; selp.u32 %0, 1, 0, P; }" : "=r"(p)); return p;
}
__device__ __forceinline__ void tma2d(uint32_t dst, const CUtensorMap* m, int x, int y, uint32_t bar) {
  asm volatile("cp.async.bulk.tensor.2d.shared::cluster.global.mbarrier::complete_tx::bytes [%0], [%1, {%3, %4}], [%2];" ::"r"(dst), "l"(m), "r"(bar), "r"(x), "r"(y) : "memory");
}
__device__ __forceinline__ void tma3d(uint32_t dst, const CUtensorMap* m, int x, int y, int z, uint32_t bar) {
  asm volatile("cp.async.bulk.tensor.3d.shared::cluster.global.mbarrier::complete_tx::bytes [%0], [%1, {%3, %4, %5}], [%2];" ::"r"(dst), "l"(m), "r"(bar), "r"(x), "r"(y), "r"(z) : "memory");
}
__device__ __forceinline__ void tma4d(uint32_t dst, const CUtensorMap* m, int x, int y, int z, int w, uint32_t bar) {
  asm volatile("cp.async.bulk.tensor.4d.shared::cluster.global.mbarrier::complete_tx::bytes [%0], [%1, {%3, %4, %5, %6}], [%2];" ::"r"(dst), "l"(m), "r"(bar), "r"(x), "r"(y), "r"(z), "r"(w) : "memory");
}
__device__ __forceinline__ void tma5d(uint32_t dst, const CUtensorMap* m, int x, int v, uint32_t bar) {
  asm volatile("cp.async.bulk.tensor.5d.shared::cluster.global.mbarrier::complete_tx::bytes [%0], [%1, {%3, %5, %5, %5, %4}], [%2];" ::"r"(dst), "l"(m), "r"(bar), "r"(x), "r"(v), "r"(0) : "memory");
}
__device__ __forceinline__ void tma_store2d(const CUtensorMap* m, uint32_t src, int x, int y) {
  asm volatile("cp.async.bulk.tensor.2d.global.shared::cta.bulk_group [%0, {%2, %3}], [%1];" ::"l"(m), "r"(src), "r"(x), "r"(y) : "memory");
}
__device__ __forceinline__ void bulk_load(uint32_t dst, const void* src, uint32_t bytes, uint32_t bar) {
  asm volatile("cp.async.bulk.shared::cluster.global.mbarrier::complete_tx::bytes [%0], [%1], %2, [%3];" ::"r"(dst), "l"(src), "r"(bytes), "r"(bar) : "memory");
}
__device__ __forceinline__ void bulk_commit() { asm volatile("cp.async.bulk.commit_group;" ::: "memory"); }
__device__ __forceinline__ void bulk_wait0() { asm volatile("cp.async.bulk.wait_group 0;" ::: "memory"); }
__device__ __forceinline__ void bulk_wait_read0() { asm volatile("cp.async.bulk.wait_group.read 0;" ::: "memory"); }
__device__ __forceinline__ void prefetch_l2(const void* p) { asm volatile("prefetch.global.L2 [%0];" ::"l"(p) : "memory"); }
__device__ __forceinline__ void touch_l2(const void* p, int lane) { asm volatile("cp.async.cg.shared.global.L2::128B [%0], [%1], 16;" ::"r"(SB + SM_SINK + lane * 16), "l"(p) : "memory"); }
__device__ __forceinline__ void cp_async16(uint32_t dst, const void* src) { asm volatile("cp.async.cg.shared.global [%0], [%1], 16;" ::"r"(dst), "l"(src) : "memory"); }
__device__ __forceinline__ void prefetch_map(const CUtensorMap* m) { asm volatile("prefetch.tensormap [%0];" ::"l"(m) : "memory"); }
__device__ __forceinline__ void fence_async_smem() { asm volatile("fence.proxy.async.shared::cta;" ::: "memory"); }
__device__ __forceinline__ void fence_async_global() { asm volatile("fence.proxy.async.global;" ::: "memory"); }
__device__ __forceinline__ void bar_sync(int id, int n) { asm volatile("bar.sync %0, %1;" ::"r"(id), "r"(n) : "memory"); }
__device__ __forceinline__ void wg_fence() { asm volatile("wgmma.fence.sync.aligned;" ::: "memory"); }
__device__ __forceinline__ void wg_commit() { asm volatile("wgmma.commit_group.sync.aligned;" ::: "memory"); }
template <int N> __device__ __forceinline__ void wg_wait() { asm volatile("wgmma.wait_group.sync.aligned %0;" ::"n"(N) : "memory"); }
template <int N> __device__ __forceinline__ void reg_fence(uint32_t* r) {
#pragma unroll
  for (int i = 0; i < N; i++) asm volatile("" : "+r"(r[i])::"memory");
}
template <int N> __device__ __forceinline__ void reg_fence(float* r) {
#pragma unroll
  for (int i = 0; i < N; i++) asm volatile("" : "+f"(r[i])::"memory");
}
__device__ __forceinline__ uint64_t mkdesc(uint32_t addr, uint32_t lbo, uint32_t sbo, uint32_t swz, uint32_t dyn = 0) {
  const uint32_t lo = ((addr >> 4) | ((lbo >> 4) << 16)) + dyn;
  const uint32_t hi = (sbo >> 4) | (swz << 30);
  uint64_t d;
  asm("mov.b64 %0, {%1, %2};" : "=l"(d) : "r"(lo), "r"(hi));
  return d;
}
__device__ __forceinline__ void stsm4(uint32_t addr, uint32_t a, uint32_t b, uint32_t c, uint32_t d) {
  asm volatile("stmatrix.sync.aligned.m8n8.x4.shared.b16 [%0], {%1, %2, %3, %4};" ::"r"(addr), "r"(a), "r"(b), "r"(c), "r"(d) : "memory");
}
__device__ __forceinline__ void ldsm4(uint32_t addr, uint32_t& a, uint32_t& b, uint32_t& c, uint32_t& d) {
  asm volatile("ldmatrix.sync.aligned.m8n8.x4.shared.b16 {%0, %1, %2, %3}, [%4];" : "=r"(a), "=r"(b), "=r"(c), "=r"(d) : "r"(addr) : "memory");
}
__device__ __forceinline__ uint32_t pack2(float lo, float hi) { uint32_t r; asm("cvt.rn.bf16x2.f32 %0, %1, %2;" : "=r"(r) : "f"(hi), "f"(lo)); return r; }
__device__ __forceinline__ uint32_t bsub2(uint32_t a, uint32_t b) { uint32_t r; asm("sub.rn.bf16x2 %0, %1, %2;" : "=r"(r) : "r"(a), "r"(b)); return r; }
__device__ __forceinline__ uint32_t badd2(uint32_t a, uint32_t b) { uint32_t r; asm("add.rn.bf16x2 %0, %1, %2;" : "=r"(r) : "r"(a), "r"(b)); return r; }
__device__ __forceinline__ uint32_t bmul2(uint32_t a, uint32_t b) { uint32_t r; asm("mul.rn.bf16x2 %0, %1, %2;" : "=r"(r) : "r"(a), "r"(b)); return r; }
__device__ __forceinline__ float bf_lo(uint32_t v) { return __uint_as_float(v << 16); }
__device__ __forceinline__ float bf_hi(uint32_t v) { return __uint_as_float(v & 0xffff0000u); }
__device__ __forceinline__ float bf_round(float v) { return bf_lo(pack2(v, 0.f)); }
__device__ __forceinline__ float ex2(float v) { float r; asm("ex2.approx.ftz.f32 %0, %1;" : "=f"(r) : "f"(v)); return r; }
__device__ __forceinline__ float rcp(float v) { float r; asm("rcp.approx.ftz.f32 %0, %1;" : "=f"(r) : "f"(v)); return r; }
__device__ __forceinline__ float sqrt_approx(float v) { float r; asm("sqrt.approx.f32 %0, %1;" : "=f"(r) : "f"(v)); return r; }
__device__ __forceinline__ float4 lds128(uint32_t a) { float4 v; asm volatile("ld.shared.v4.f32 {%0, %1, %2, %3}, [%4];" : "=f"(v.x), "=f"(v.y), "=f"(v.z), "=f"(v.w) : "r"(a) : "memory"); return v; }
__device__ __forceinline__ uint4 lds128u(uint32_t a) { uint4 v; asm volatile("ld.shared.v4.u32 {%0, %1, %2, %3}, [%4];" : "=r"(v.x), "=r"(v.y), "=r"(v.z), "=r"(v.w) : "r"(a) : "memory"); return v; }
__device__ __forceinline__ float2 lds64(uint32_t a) { float2 v; asm volatile("ld.shared.v2.f32 {%0, %1}, [%2];" : "=f"(v.x), "=f"(v.y) : "r"(a) : "memory"); return v; }
__device__ __forceinline__ float lds32(uint32_t a) { float v; asm volatile("ld.shared.f32 %0, [%1];" : "=f"(v) : "r"(a) : "memory"); return v; }
__device__ __forceinline__ void sts32(uint32_t a, float v) { asm volatile("st.shared.f32 [%0], %1;" ::"r"(a), "f"(v) : "memory"); }
__device__ __forceinline__ void sts64(uint32_t a, float x, float y) { asm volatile("st.shared.v2.f32 [%0], {%1, %2};" ::"r"(a), "f"(x), "f"(y) : "memory"); }
__device__ __forceinline__ void sts128(uint32_t a, float x, float y, float z, float w) { asm volatile("st.shared.v4.f32 [%0], {%1, %2, %3, %4};" ::"r"(a), "f"(x), "f"(y), "f"(z), "f"(w) : "memory"); }
__device__ __forceinline__ void sts64u(uint32_t a, uint32_t x, uint32_t y) { asm volatile("st.shared.v2.u32 [%0], {%1, %2};" ::"r"(a), "r"(x), "r"(y) : "memory"); }
__device__ __forceinline__ void sts128u(uint32_t a, uint32_t x, uint32_t y, uint32_t z, uint32_t w) { asm volatile("st.shared.v4.u32 [%0], {%1, %2, %3, %4};" ::"r"(a), "r"(x), "r"(y), "r"(z), "r"(w) : "memory"); }
__device__ __forceinline__ uint4 ldg_nc(const void* p) { uint4 v; asm volatile("ld.global.nc.L1::no_allocate.v4.u32 {%0, %1, %2, %3}, [%4];" : "=r"(v.x), "=r"(v.y), "=r"(v.z), "=r"(v.w) : "l"(p)); return v; }
__device__ __forceinline__ float4 ldg_cg4(const float* p) { float4 v; asm volatile("ld.global.cg.v4.f32 {%0, %1, %2, %3}, [%4];" : "=f"(v.x), "=f"(v.y), "=f"(v.z), "=f"(v.w) : "l"(p) : "memory"); return v; }
__device__ __forceinline__ uint32_t ld_acq(const uint32_t* p) { uint32_t v; asm volatile("ld.acquire.gpu.global.u32 %0, [%1];" : "=r"(v) : "l"(p) : "memory"); return v; }
__device__ __forceinline__ uint32_t ld_acq_cta(uint32_t a) { uint32_t v; asm volatile("ld.acquire.cta.shared.u32 %0, [%1];" : "=r"(v) : "r"(a) : "memory"); return v; }
__device__ __forceinline__ void st_rel_cta(uint32_t a, uint32_t v) { asm volatile("st.release.cta.shared.u32 [%0], %1;" ::"r"(a), "r"(v) : "memory"); }
__device__ __forceinline__ unsigned long long ld_rlx64(const unsigned long long* p) { unsigned long long v; asm volatile("ld.relaxed.gpu.global.u64 %0, [%1];" : "=l"(v) : "l"(p) : "memory"); return v; }
__device__ __forceinline__ void st_rlx64(unsigned long long* p, unsigned long long v) { asm volatile("st.relaxed.gpu.global.u64 [%0], %1;" ::"l"(p), "l"(v) : "memory"); }
__device__ __forceinline__ uint4 ld_rlx128(const void* p) {
  uint4 v;
  asm volatile("{ .reg .b128 t; .reg .b64 a, b; ld.relaxed.gpu.global.b128 t, [%4]; mov.b128 {a, b}, t; mov.b64 {%0, %1}, a; mov.b64 {%2, %3}, b; }"
               : "=r"(v.x), "=r"(v.y), "=r"(v.z), "=r"(v.w) : "l"(p) : "memory");
  return v;
}
__device__ __forceinline__ void st_rlx128(void* p, uint32_t x, uint32_t y, uint32_t z, uint32_t w) {
  asm volatile("{ .reg .b128 t; .reg .b64 a, b; mov.b64 a, {%1, %2}; mov.b64 b, {%3, %4}; mov.b128 t, {a, b}; st.relaxed.gpu.global.b128 [%0], t; }"
               ::"l"(p), "r"(x), "r"(y), "r"(z), "r"(w) : "memory");
}
__device__ __forceinline__ void stg128(void* p, uint32_t x, uint32_t y, uint32_t z, uint32_t w) { asm volatile("st.global.v4.u32 [%0], {%1, %2, %3, %4};" ::"l"(p), "r"(x), "r"(y), "r"(z), "r"(w) : "memory"); }
__device__ __forceinline__ void st_rlx(void* p, uint32_t v) { asm volatile("st.relaxed.gpu.global.u32 [%0], %1;" ::"l"(p), "r"(v) : "memory"); }
__device__ __forceinline__ uint32_t lop_select(uint32_t a, uint32_t b, uint32_t m) { uint32_t r; asm("lop3.b32 %0, %1, %2, %3, 0xd8;" : "=r"(r) : "r"(a), "r"(b), "r"(m)); return r; }
__device__ __forceinline__ float unmark(uint32_t v) { return __uint_as_float(v & ~1u); }
__device__ __forceinline__ uint32_t mark(uint32_t v, uint32_t par) { return (v & ~1u) | par; }
__device__ __forceinline__ float tanh_approx(float v) { float r; asm("tanh.approx.f32 %0, %1;" : "=f"(r) : "f"(v)); return r; }
__device__ __forceinline__ void flag_rel(uint32_t* p, uint32_t v) { asm volatile("red.release.gpu.global.max.u32 [%0], %1;" ::"l"(p), "r"(v) : "memory"); }
__device__ __forceinline__ void red1(float* p, float a) { asm volatile("red.global.add.f32 [%0], %1;" ::"l"(p), "f"(a) : "memory"); }
__device__ __forceinline__ void red_inc(uint32_t* p) { asm volatile("red.relaxed.gpu.global.add.u32 [%0], 1;" ::"l"(p) : "memory"); }
__device__ __forceinline__ void red_rel(uint32_t* p) { asm volatile("red.release.gpu.global.add.u32 [%0], 1;" ::"l"(p) : "memory"); }
__device__ __forceinline__ void red4(float* p, float a, float b, float c, float d) { asm volatile("red.global.add.v4.f32 [%0], {%1, %2, %3, %4};" ::"l"(p), "f"(a), "f"(b), "f"(c), "f"(d) : "memory"); }
constexpr int SPIN_MAX = 100000;
__device__ __forceinline__ uint32_t ld_rlx(const uint32_t* p) { uint32_t v; asm volatile("ld.relaxed.gpu.global.u32 %0, [%1];" : "=r"(v) : "l"(p) : "memory"); return v; }
template <int NS = 0> __device__ __forceinline__ void wait_hint(const uint32_t* p, uint32_t target) {
#pragma unroll 1
  for (int i = 0; i < SPIN_MAX; i++) { if ((int)(ld_rlx(p) - target) >= 0) break; if (NS) __nanosleep(NS); }
}
template <int NS> __device__ __forceinline__ void wait_cnt(const uint32_t* p, uint32_t target) {
#pragma unroll 1
  for (int i = 0; i < SPIN_MAX; i++) { if ((int)(ld_rlx(p) - target) >= 0) break; if (NS) __nanosleep(NS); }
  (void)ld_acq(p);
}
template <int NS> __device__ __forceinline__ unsigned long long wait_tag(const unsigned long long* p, uint32_t tag) {
  unsigned long long v = 0;
#pragma unroll 1
  for (int i = 0; i < SPIN_MAX; i++) { v = ld_rlx64(p); if ((uint32_t)(v >> 32) == tag) break; if (NS) __nanosleep(NS); }
  return v;
}
__device__ __forceinline__ float silu_f(float v) { return v * rcp(1.f + ex2(-1.4426950408889634f * v)); }

__device__ __forceinline__ void wgmma_n8_ss_ta1_tb0(float* d, uint64_t da, uint64_t db, bool accumulate) {
  if (accumulate) {
    asm volatile("{\n.reg .pred p;\nsetp.ne.b32 p, 1, 0;\n"
      "wgmma.mma_async.sync.aligned.m64n8k16.f32.bf16.bf16 "
      "{%0, %1, %2, %3}, "
      "%4, %5, p, 1, 1, 1, 0;\n}\n"
      : "+f"(d[0]), "+f"(d[1]), "+f"(d[2]), "+f"(d[3])
      : "l"(da), "l"(db));
  } else {
    asm volatile("{\n.reg .pred p;\nsetp.ne.b32 p, 0, 0;\n"
      "wgmma.mma_async.sync.aligned.m64n8k16.f32.bf16.bf16 "
      "{%0, %1, %2, %3}, "
      "%4, %5, p, 1, 1, 1, 0;\n}\n"
      : "=f"(d[0]), "=f"(d[1]), "=f"(d[2]), "=f"(d[3])
      : "l"(da), "l"(db));
  }
}
__device__ __forceinline__ void wgmma_n8_ss_ta1_tb1(float* d, uint64_t da, uint64_t db, bool accumulate) {
  if (accumulate) {
    asm volatile("{\n.reg .pred p;\nsetp.ne.b32 p, 1, 0;\n"
      "wgmma.mma_async.sync.aligned.m64n8k16.f32.bf16.bf16 "
      "{%0, %1, %2, %3}, "
      "%4, %5, p, 1, 1, 1, 1;\n}\n"
      : "+f"(d[0]), "+f"(d[1]), "+f"(d[2]), "+f"(d[3])
      : "l"(da), "l"(db));
  } else {
    asm volatile("{\n.reg .pred p;\nsetp.ne.b32 p, 0, 0;\n"
      "wgmma.mma_async.sync.aligned.m64n8k16.f32.bf16.bf16 "
      "{%0, %1, %2, %3}, "
      "%4, %5, p, 1, 1, 1, 1;\n}\n"
      : "=f"(d[0]), "=f"(d[1]), "=f"(d[2]), "=f"(d[3])
      : "l"(da), "l"(db));
  }
}
__device__ __forceinline__ void wgmma_n32_rs_ta0_tb1(float* d, uint32_t a0, uint32_t a1, uint32_t a2, uint32_t a3, uint64_t db, bool accumulate) {
  if (accumulate) {
    asm volatile("{\n.reg .pred p;\nsetp.ne.b32 p, 1, 0;\n"
      "wgmma.mma_async.sync.aligned.m64n32k16.f32.bf16.bf16 "
      "{%0, %1, %2, %3, %4, %5, %6, %7, %8, %9, %10, %11, %12, %13, %14, %15}, "
      "{%16, %17, %18, %19}, %20, p, 1, 1, 1;\n}\n"
      : "+f"(d[0]), "+f"(d[1]), "+f"(d[2]), "+f"(d[3]), "+f"(d[4]), "+f"(d[5]), "+f"(d[6]), "+f"(d[7]), "+f"(d[8]), "+f"(d[9]), "+f"(d[10]), "+f"(d[11]), "+f"(d[12]), "+f"(d[13]), "+f"(d[14]), "+f"(d[15])
      : "r"(a0), "r"(a1), "r"(a2), "r"(a3), "l"(db));
  } else {
    asm volatile("{\n.reg .pred p;\nsetp.ne.b32 p, 0, 0;\n"
      "wgmma.mma_async.sync.aligned.m64n32k16.f32.bf16.bf16 "
      "{%0, %1, %2, %3, %4, %5, %6, %7, %8, %9, %10, %11, %12, %13, %14, %15}, "
      "{%16, %17, %18, %19}, %20, p, 1, 1, 1;\n}\n"
      : "=f"(d[0]), "=f"(d[1]), "=f"(d[2]), "=f"(d[3]), "=f"(d[4]), "=f"(d[5]), "=f"(d[6]), "=f"(d[7]), "=f"(d[8]), "=f"(d[9]), "=f"(d[10]), "=f"(d[11]), "=f"(d[12]), "=f"(d[13]), "=f"(d[14]), "=f"(d[15])
      : "r"(a0), "r"(a1), "r"(a2), "r"(a3), "l"(db));
  }
}
__device__ __forceinline__ void wgmma_n40_rs_ta0_tb1(float* d, uint32_t a0, uint32_t a1, uint32_t a2, uint32_t a3, uint64_t db, bool accumulate) {
  if (accumulate) {
    asm volatile("{\n.reg .pred p;\nsetp.ne.b32 p, 1, 0;\n"
      "wgmma.mma_async.sync.aligned.m64n40k16.f32.bf16.bf16 "
      "{%0, %1, %2, %3, %4, %5, %6, %7, %8, %9, %10, %11, %12, %13, %14, %15, %16, %17, %18, %19}, "
      "{%20, %21, %22, %23}, %24, p, 1, 1, 1;\n}\n"
      : "+f"(d[0]), "+f"(d[1]), "+f"(d[2]), "+f"(d[3]), "+f"(d[4]), "+f"(d[5]), "+f"(d[6]), "+f"(d[7]), "+f"(d[8]), "+f"(d[9]), "+f"(d[10]), "+f"(d[11]), "+f"(d[12]), "+f"(d[13]), "+f"(d[14]), "+f"(d[15]), "+f"(d[16]), "+f"(d[17]), "+f"(d[18]), "+f"(d[19])
      : "r"(a0), "r"(a1), "r"(a2), "r"(a3), "l"(db));
  } else {
    asm volatile("{\n.reg .pred p;\nsetp.ne.b32 p, 0, 0;\n"
      "wgmma.mma_async.sync.aligned.m64n40k16.f32.bf16.bf16 "
      "{%0, %1, %2, %3, %4, %5, %6, %7, %8, %9, %10, %11, %12, %13, %14, %15, %16, %17, %18, %19}, "
      "{%20, %21, %22, %23}, %24, p, 1, 1, 1;\n}\n"
      : "=f"(d[0]), "=f"(d[1]), "=f"(d[2]), "=f"(d[3]), "=f"(d[4]), "=f"(d[5]), "=f"(d[6]), "=f"(d[7]), "=f"(d[8]), "=f"(d[9]), "=f"(d[10]), "=f"(d[11]), "=f"(d[12]), "=f"(d[13]), "=f"(d[14]), "=f"(d[15]), "=f"(d[16]), "=f"(d[17]), "=f"(d[18]), "=f"(d[19])
      : "r"(a0), "r"(a1), "r"(a2), "r"(a3), "l"(db));
  }
}
__device__ __forceinline__ void wgmma_n40_ss_ta1_tb1(float* d, uint64_t da, uint64_t db, bool accumulate) {
  if (accumulate) {
    asm volatile("{\n.reg .pred p;\nsetp.ne.b32 p, 1, 0;\n"
      "wgmma.mma_async.sync.aligned.m64n40k16.f32.bf16.bf16 "
      "{%0, %1, %2, %3, %4, %5, %6, %7, %8, %9, %10, %11, %12, %13, %14, %15, %16, %17, %18, %19}, "
      "%20, %21, p, 1, 1, 1, 1;\n}\n"
      : "+f"(d[0]), "+f"(d[1]), "+f"(d[2]), "+f"(d[3]), "+f"(d[4]), "+f"(d[5]), "+f"(d[6]), "+f"(d[7]), "+f"(d[8]), "+f"(d[9]), "+f"(d[10]), "+f"(d[11]), "+f"(d[12]), "+f"(d[13]), "+f"(d[14]), "+f"(d[15]), "+f"(d[16]), "+f"(d[17]), "+f"(d[18]), "+f"(d[19])
      : "l"(da), "l"(db));
  } else {
    asm volatile("{\n.reg .pred p;\nsetp.ne.b32 p, 0, 0;\n"
      "wgmma.mma_async.sync.aligned.m64n40k16.f32.bf16.bf16 "
      "{%0, %1, %2, %3, %4, %5, %6, %7, %8, %9, %10, %11, %12, %13, %14, %15, %16, %17, %18, %19}, "
      "%20, %21, p, 1, 1, 1, 1;\n}\n"
      : "=f"(d[0]), "=f"(d[1]), "=f"(d[2]), "=f"(d[3]), "=f"(d[4]), "=f"(d[5]), "=f"(d[6]), "=f"(d[7]), "=f"(d[8]), "=f"(d[9]), "=f"(d[10]), "=f"(d[11]), "=f"(d[12]), "=f"(d[13]), "=f"(d[14]), "=f"(d[15]), "=f"(d[16]), "=f"(d[17]), "=f"(d[18]), "=f"(d[19])
      : "l"(da), "l"(db));
  }
}
__device__ __forceinline__ void wgmma_n128_rs_ta0_tb1(float* d, uint32_t a0, uint32_t a1, uint32_t a2, uint32_t a3, uint64_t db, bool accumulate) {
  if (accumulate) {
    asm volatile("{\n.reg .pred p;\nsetp.ne.b32 p, 1, 0;\n"
      "wgmma.mma_async.sync.aligned.m64n128k16.f32.bf16.bf16 "
      "{%0, %1, %2, %3, %4, %5, %6, %7, %8, %9, %10, %11, %12, %13, %14, %15, %16, %17, %18, %19, %20, %21, %22, %23, %24, %25, %26, %27, %28, %29, %30, %31, %32, %33, %34, %35, %36, %37, %38, %39, %40, %41, %42, %43, %44, %45, %46, %47, %48, %49, %50, %51, %52, %53, %54, %55, %56, %57, %58, %59, %60, %61, %62, %63}, "
      "{%64, %65, %66, %67}, %68, p, 1, 1, 1;\n}\n"
      : "+f"(d[0]), "+f"(d[1]), "+f"(d[2]), "+f"(d[3]), "+f"(d[4]), "+f"(d[5]), "+f"(d[6]), "+f"(d[7]), "+f"(d[8]), "+f"(d[9]), "+f"(d[10]), "+f"(d[11]), "+f"(d[12]), "+f"(d[13]), "+f"(d[14]), "+f"(d[15]), "+f"(d[16]), "+f"(d[17]), "+f"(d[18]), "+f"(d[19]), "+f"(d[20]), "+f"(d[21]), "+f"(d[22]), "+f"(d[23]), "+f"(d[24]), "+f"(d[25]), "+f"(d[26]), "+f"(d[27]), "+f"(d[28]), "+f"(d[29]), "+f"(d[30]), "+f"(d[31]), "+f"(d[32]), "+f"(d[33]), "+f"(d[34]), "+f"(d[35]), "+f"(d[36]), "+f"(d[37]), "+f"(d[38]), "+f"(d[39]), "+f"(d[40]), "+f"(d[41]), "+f"(d[42]), "+f"(d[43]), "+f"(d[44]), "+f"(d[45]), "+f"(d[46]), "+f"(d[47]), "+f"(d[48]), "+f"(d[49]), "+f"(d[50]), "+f"(d[51]), "+f"(d[52]), "+f"(d[53]), "+f"(d[54]), "+f"(d[55]), "+f"(d[56]), "+f"(d[57]), "+f"(d[58]), "+f"(d[59]), "+f"(d[60]), "+f"(d[61]), "+f"(d[62]), "+f"(d[63])
      : "r"(a0), "r"(a1), "r"(a2), "r"(a3), "l"(db));
  } else {
    asm volatile("{\n.reg .pred p;\nsetp.ne.b32 p, 0, 0;\n"
      "wgmma.mma_async.sync.aligned.m64n128k16.f32.bf16.bf16 "
      "{%0, %1, %2, %3, %4, %5, %6, %7, %8, %9, %10, %11, %12, %13, %14, %15, %16, %17, %18, %19, %20, %21, %22, %23, %24, %25, %26, %27, %28, %29, %30, %31, %32, %33, %34, %35, %36, %37, %38, %39, %40, %41, %42, %43, %44, %45, %46, %47, %48, %49, %50, %51, %52, %53, %54, %55, %56, %57, %58, %59, %60, %61, %62, %63}, "
      "{%64, %65, %66, %67}, %68, p, 1, 1, 1;\n}\n"
      : "=f"(d[0]), "=f"(d[1]), "=f"(d[2]), "=f"(d[3]), "=f"(d[4]), "=f"(d[5]), "=f"(d[6]), "=f"(d[7]), "=f"(d[8]), "=f"(d[9]), "=f"(d[10]), "=f"(d[11]), "=f"(d[12]), "=f"(d[13]), "=f"(d[14]), "=f"(d[15]), "=f"(d[16]), "=f"(d[17]), "=f"(d[18]), "=f"(d[19]), "=f"(d[20]), "=f"(d[21]), "=f"(d[22]), "=f"(d[23]), "=f"(d[24]), "=f"(d[25]), "=f"(d[26]), "=f"(d[27]), "=f"(d[28]), "=f"(d[29]), "=f"(d[30]), "=f"(d[31]), "=f"(d[32]), "=f"(d[33]), "=f"(d[34]), "=f"(d[35]), "=f"(d[36]), "=f"(d[37]), "=f"(d[38]), "=f"(d[39]), "=f"(d[40]), "=f"(d[41]), "=f"(d[42]), "=f"(d[43]), "=f"(d[44]), "=f"(d[45]), "=f"(d[46]), "=f"(d[47]), "=f"(d[48]), "=f"(d[49]), "=f"(d[50]), "=f"(d[51]), "=f"(d[52]), "=f"(d[53]), "=f"(d[54]), "=f"(d[55]), "=f"(d[56]), "=f"(d[57]), "=f"(d[58]), "=f"(d[59]), "=f"(d[60]), "=f"(d[61]), "=f"(d[62]), "=f"(d[63])
      : "r"(a0), "r"(a1), "r"(a2), "r"(a3), "l"(db));
  }
}
__device__ __forceinline__ void wgmma_n128_ss_ta0_tb1(float* d, uint64_t da, uint64_t db, bool accumulate) {
  if (accumulate) {
    asm volatile("{\n.reg .pred p;\nsetp.ne.b32 p, 1, 0;\n"
      "wgmma.mma_async.sync.aligned.m64n128k16.f32.bf16.bf16 "
      "{%0, %1, %2, %3, %4, %5, %6, %7, %8, %9, %10, %11, %12, %13, %14, %15, %16, %17, %18, %19, %20, %21, %22, %23, %24, %25, %26, %27, %28, %29, %30, %31, %32, %33, %34, %35, %36, %37, %38, %39, %40, %41, %42, %43, %44, %45, %46, %47, %48, %49, %50, %51, %52, %53, %54, %55, %56, %57, %58, %59, %60, %61, %62, %63}, "
      "%64, %65, p, 1, 1, 0, 1;\n}\n"
      : "+f"(d[0]), "+f"(d[1]), "+f"(d[2]), "+f"(d[3]), "+f"(d[4]), "+f"(d[5]), "+f"(d[6]), "+f"(d[7]), "+f"(d[8]), "+f"(d[9]), "+f"(d[10]), "+f"(d[11]), "+f"(d[12]), "+f"(d[13]), "+f"(d[14]), "+f"(d[15]), "+f"(d[16]), "+f"(d[17]), "+f"(d[18]), "+f"(d[19]), "+f"(d[20]), "+f"(d[21]), "+f"(d[22]), "+f"(d[23]), "+f"(d[24]), "+f"(d[25]), "+f"(d[26]), "+f"(d[27]), "+f"(d[28]), "+f"(d[29]), "+f"(d[30]), "+f"(d[31]), "+f"(d[32]), "+f"(d[33]), "+f"(d[34]), "+f"(d[35]), "+f"(d[36]), "+f"(d[37]), "+f"(d[38]), "+f"(d[39]), "+f"(d[40]), "+f"(d[41]), "+f"(d[42]), "+f"(d[43]), "+f"(d[44]), "+f"(d[45]), "+f"(d[46]), "+f"(d[47]), "+f"(d[48]), "+f"(d[49]), "+f"(d[50]), "+f"(d[51]), "+f"(d[52]), "+f"(d[53]), "+f"(d[54]), "+f"(d[55]), "+f"(d[56]), "+f"(d[57]), "+f"(d[58]), "+f"(d[59]), "+f"(d[60]), "+f"(d[61]), "+f"(d[62]), "+f"(d[63])
      : "l"(da), "l"(db));
  } else {
    asm volatile("{\n.reg .pred p;\nsetp.ne.b32 p, 0, 0;\n"
      "wgmma.mma_async.sync.aligned.m64n128k16.f32.bf16.bf16 "
      "{%0, %1, %2, %3, %4, %5, %6, %7, %8, %9, %10, %11, %12, %13, %14, %15, %16, %17, %18, %19, %20, %21, %22, %23, %24, %25, %26, %27, %28, %29, %30, %31, %32, %33, %34, %35, %36, %37, %38, %39, %40, %41, %42, %43, %44, %45, %46, %47, %48, %49, %50, %51, %52, %53, %54, %55, %56, %57, %58, %59, %60, %61, %62, %63}, "
      "%64, %65, p, 1, 1, 0, 1;\n}\n"
      : "=f"(d[0]), "=f"(d[1]), "=f"(d[2]), "=f"(d[3]), "=f"(d[4]), "=f"(d[5]), "=f"(d[6]), "=f"(d[7]), "=f"(d[8]), "=f"(d[9]), "=f"(d[10]), "=f"(d[11]), "=f"(d[12]), "=f"(d[13]), "=f"(d[14]), "=f"(d[15]), "=f"(d[16]), "=f"(d[17]), "=f"(d[18]), "=f"(d[19]), "=f"(d[20]), "=f"(d[21]), "=f"(d[22]), "=f"(d[23]), "=f"(d[24]), "=f"(d[25]), "=f"(d[26]), "=f"(d[27]), "=f"(d[28]), "=f"(d[29]), "=f"(d[30]), "=f"(d[31]), "=f"(d[32]), "=f"(d[33]), "=f"(d[34]), "=f"(d[35]), "=f"(d[36]), "=f"(d[37]), "=f"(d[38]), "=f"(d[39]), "=f"(d[40]), "=f"(d[41]), "=f"(d[42]), "=f"(d[43]), "=f"(d[44]), "=f"(d[45]), "=f"(d[46]), "=f"(d[47]), "=f"(d[48]), "=f"(d[49]), "=f"(d[50]), "=f"(d[51]), "=f"(d[52]), "=f"(d[53]), "=f"(d[54]), "=f"(d[55]), "=f"(d[56]), "=f"(d[57]), "=f"(d[58]), "=f"(d[59]), "=f"(d[60]), "=f"(d[61]), "=f"(d[62]), "=f"(d[63])
      : "l"(da), "l"(db));
  }
}
__device__ __forceinline__ void wgmma_n256_rs_ta0_tb1(float* d, uint32_t a0, uint32_t a1, uint32_t a2, uint32_t a3, uint64_t db, bool accumulate) {
  if (accumulate) {
    asm volatile("{\n.reg .pred p;\nsetp.ne.b32 p, 1, 0;\n"
      "wgmma.mma_async.sync.aligned.m64n256k16.f32.bf16.bf16 "
      "{%0, %1, %2, %3, %4, %5, %6, %7, %8, %9, %10, %11, %12, %13, %14, %15, %16, %17, %18, %19, %20, %21, %22, %23, %24, %25, %26, %27, %28, %29, %30, %31, %32, %33, %34, %35, %36, %37, %38, %39, %40, %41, %42, %43, %44, %45, %46, %47, %48, %49, %50, %51, %52, %53, %54, %55, %56, %57, %58, %59, %60, %61, %62, %63, %64, %65, %66, %67, %68, %69, %70, %71, %72, %73, %74, %75, %76, %77, %78, %79, %80, %81, %82, %83, %84, %85, %86, %87, %88, %89, %90, %91, %92, %93, %94, %95, %96, %97, %98, %99, %100, %101, %102, %103, %104, %105, %106, %107, %108, %109, %110, %111, %112, %113, %114, %115, %116, %117, %118, %119, %120, %121, %122, %123, %124, %125, %126, %127}, "
      "{%128, %129, %130, %131}, %132, p, 1, 1, 1;\n}\n"
      : "+f"(d[0]), "+f"(d[1]), "+f"(d[2]), "+f"(d[3]), "+f"(d[4]), "+f"(d[5]), "+f"(d[6]), "+f"(d[7]), "+f"(d[8]), "+f"(d[9]), "+f"(d[10]), "+f"(d[11]), "+f"(d[12]), "+f"(d[13]), "+f"(d[14]), "+f"(d[15]), "+f"(d[16]), "+f"(d[17]), "+f"(d[18]), "+f"(d[19]), "+f"(d[20]), "+f"(d[21]), "+f"(d[22]), "+f"(d[23]), "+f"(d[24]), "+f"(d[25]), "+f"(d[26]), "+f"(d[27]), "+f"(d[28]), "+f"(d[29]), "+f"(d[30]), "+f"(d[31]), "+f"(d[32]), "+f"(d[33]), "+f"(d[34]), "+f"(d[35]), "+f"(d[36]), "+f"(d[37]), "+f"(d[38]), "+f"(d[39]), "+f"(d[40]), "+f"(d[41]), "+f"(d[42]), "+f"(d[43]), "+f"(d[44]), "+f"(d[45]), "+f"(d[46]), "+f"(d[47]), "+f"(d[48]), "+f"(d[49]), "+f"(d[50]), "+f"(d[51]), "+f"(d[52]), "+f"(d[53]), "+f"(d[54]), "+f"(d[55]), "+f"(d[56]), "+f"(d[57]), "+f"(d[58]), "+f"(d[59]), "+f"(d[60]), "+f"(d[61]), "+f"(d[62]), "+f"(d[63]), "+f"(d[64]), "+f"(d[65]), "+f"(d[66]), "+f"(d[67]), "+f"(d[68]), "+f"(d[69]), "+f"(d[70]), "+f"(d[71]), "+f"(d[72]), "+f"(d[73]), "+f"(d[74]), "+f"(d[75]), "+f"(d[76]), "+f"(d[77]), "+f"(d[78]), "+f"(d[79]), "+f"(d[80]), "+f"(d[81]), "+f"(d[82]), "+f"(d[83]), "+f"(d[84]), "+f"(d[85]), "+f"(d[86]), "+f"(d[87]), "+f"(d[88]), "+f"(d[89]), "+f"(d[90]), "+f"(d[91]), "+f"(d[92]), "+f"(d[93]), "+f"(d[94]), "+f"(d[95]), "+f"(d[96]), "+f"(d[97]), "+f"(d[98]), "+f"(d[99]), "+f"(d[100]), "+f"(d[101]), "+f"(d[102]), "+f"(d[103]), "+f"(d[104]), "+f"(d[105]), "+f"(d[106]), "+f"(d[107]), "+f"(d[108]), "+f"(d[109]), "+f"(d[110]), "+f"(d[111]), "+f"(d[112]), "+f"(d[113]), "+f"(d[114]), "+f"(d[115]), "+f"(d[116]), "+f"(d[117]), "+f"(d[118]), "+f"(d[119]), "+f"(d[120]), "+f"(d[121]), "+f"(d[122]), "+f"(d[123]), "+f"(d[124]), "+f"(d[125]), "+f"(d[126]), "+f"(d[127])
      : "r"(a0), "r"(a1), "r"(a2), "r"(a3), "l"(db));
  } else {
    asm volatile("{\n.reg .pred p;\nsetp.ne.b32 p, 0, 0;\n"
      "wgmma.mma_async.sync.aligned.m64n256k16.f32.bf16.bf16 "
      "{%0, %1, %2, %3, %4, %5, %6, %7, %8, %9, %10, %11, %12, %13, %14, %15, %16, %17, %18, %19, %20, %21, %22, %23, %24, %25, %26, %27, %28, %29, %30, %31, %32, %33, %34, %35, %36, %37, %38, %39, %40, %41, %42, %43, %44, %45, %46, %47, %48, %49, %50, %51, %52, %53, %54, %55, %56, %57, %58, %59, %60, %61, %62, %63, %64, %65, %66, %67, %68, %69, %70, %71, %72, %73, %74, %75, %76, %77, %78, %79, %80, %81, %82, %83, %84, %85, %86, %87, %88, %89, %90, %91, %92, %93, %94, %95, %96, %97, %98, %99, %100, %101, %102, %103, %104, %105, %106, %107, %108, %109, %110, %111, %112, %113, %114, %115, %116, %117, %118, %119, %120, %121, %122, %123, %124, %125, %126, %127}, "
      "{%128, %129, %130, %131}, %132, p, 1, 1, 1;\n}\n"
      : "=f"(d[0]), "=f"(d[1]), "=f"(d[2]), "=f"(d[3]), "=f"(d[4]), "=f"(d[5]), "=f"(d[6]), "=f"(d[7]), "=f"(d[8]), "=f"(d[9]), "=f"(d[10]), "=f"(d[11]), "=f"(d[12]), "=f"(d[13]), "=f"(d[14]), "=f"(d[15]), "=f"(d[16]), "=f"(d[17]), "=f"(d[18]), "=f"(d[19]), "=f"(d[20]), "=f"(d[21]), "=f"(d[22]), "=f"(d[23]), "=f"(d[24]), "=f"(d[25]), "=f"(d[26]), "=f"(d[27]), "=f"(d[28]), "=f"(d[29]), "=f"(d[30]), "=f"(d[31]), "=f"(d[32]), "=f"(d[33]), "=f"(d[34]), "=f"(d[35]), "=f"(d[36]), "=f"(d[37]), "=f"(d[38]), "=f"(d[39]), "=f"(d[40]), "=f"(d[41]), "=f"(d[42]), "=f"(d[43]), "=f"(d[44]), "=f"(d[45]), "=f"(d[46]), "=f"(d[47]), "=f"(d[48]), "=f"(d[49]), "=f"(d[50]), "=f"(d[51]), "=f"(d[52]), "=f"(d[53]), "=f"(d[54]), "=f"(d[55]), "=f"(d[56]), "=f"(d[57]), "=f"(d[58]), "=f"(d[59]), "=f"(d[60]), "=f"(d[61]), "=f"(d[62]), "=f"(d[63]), "=f"(d[64]), "=f"(d[65]), "=f"(d[66]), "=f"(d[67]), "=f"(d[68]), "=f"(d[69]), "=f"(d[70]), "=f"(d[71]), "=f"(d[72]), "=f"(d[73]), "=f"(d[74]), "=f"(d[75]), "=f"(d[76]), "=f"(d[77]), "=f"(d[78]), "=f"(d[79]), "=f"(d[80]), "=f"(d[81]), "=f"(d[82]), "=f"(d[83]), "=f"(d[84]), "=f"(d[85]), "=f"(d[86]), "=f"(d[87]), "=f"(d[88]), "=f"(d[89]), "=f"(d[90]), "=f"(d[91]), "=f"(d[92]), "=f"(d[93]), "=f"(d[94]), "=f"(d[95]), "=f"(d[96]), "=f"(d[97]), "=f"(d[98]), "=f"(d[99]), "=f"(d[100]), "=f"(d[101]), "=f"(d[102]), "=f"(d[103]), "=f"(d[104]), "=f"(d[105]), "=f"(d[106]), "=f"(d[107]), "=f"(d[108]), "=f"(d[109]), "=f"(d[110]), "=f"(d[111]), "=f"(d[112]), "=f"(d[113]), "=f"(d[114]), "=f"(d[115]), "=f"(d[116]), "=f"(d[117]), "=f"(d[118]), "=f"(d[119]), "=f"(d[120]), "=f"(d[121]), "=f"(d[122]), "=f"(d[123]), "=f"(d[124]), "=f"(d[125]), "=f"(d[126]), "=f"(d[127])
      : "r"(a0), "r"(a1), "r"(a2), "r"(a3), "l"(db));
  }
}
__device__ __forceinline__ void wgmma_n256_ss_ta0_tb1(float* d, uint64_t da, uint64_t db, bool accumulate) {
  if (accumulate) {
    asm volatile("{\n.reg .pred p;\nsetp.ne.b32 p, 1, 0;\n"
      "wgmma.mma_async.sync.aligned.m64n256k16.f32.bf16.bf16 "
      "{%0, %1, %2, %3, %4, %5, %6, %7, %8, %9, %10, %11, %12, %13, %14, %15, %16, %17, %18, %19, %20, %21, %22, %23, %24, %25, %26, %27, %28, %29, %30, %31, %32, %33, %34, %35, %36, %37, %38, %39, %40, %41, %42, %43, %44, %45, %46, %47, %48, %49, %50, %51, %52, %53, %54, %55, %56, %57, %58, %59, %60, %61, %62, %63, %64, %65, %66, %67, %68, %69, %70, %71, %72, %73, %74, %75, %76, %77, %78, %79, %80, %81, %82, %83, %84, %85, %86, %87, %88, %89, %90, %91, %92, %93, %94, %95, %96, %97, %98, %99, %100, %101, %102, %103, %104, %105, %106, %107, %108, %109, %110, %111, %112, %113, %114, %115, %116, %117, %118, %119, %120, %121, %122, %123, %124, %125, %126, %127}, "
      "%128, %129, p, 1, 1, 0, 1;\n}\n"
      : "+f"(d[0]), "+f"(d[1]), "+f"(d[2]), "+f"(d[3]), "+f"(d[4]), "+f"(d[5]), "+f"(d[6]), "+f"(d[7]), "+f"(d[8]), "+f"(d[9]), "+f"(d[10]), "+f"(d[11]), "+f"(d[12]), "+f"(d[13]), "+f"(d[14]), "+f"(d[15]), "+f"(d[16]), "+f"(d[17]), "+f"(d[18]), "+f"(d[19]), "+f"(d[20]), "+f"(d[21]), "+f"(d[22]), "+f"(d[23]), "+f"(d[24]), "+f"(d[25]), "+f"(d[26]), "+f"(d[27]), "+f"(d[28]), "+f"(d[29]), "+f"(d[30]), "+f"(d[31]), "+f"(d[32]), "+f"(d[33]), "+f"(d[34]), "+f"(d[35]), "+f"(d[36]), "+f"(d[37]), "+f"(d[38]), "+f"(d[39]), "+f"(d[40]), "+f"(d[41]), "+f"(d[42]), "+f"(d[43]), "+f"(d[44]), "+f"(d[45]), "+f"(d[46]), "+f"(d[47]), "+f"(d[48]), "+f"(d[49]), "+f"(d[50]), "+f"(d[51]), "+f"(d[52]), "+f"(d[53]), "+f"(d[54]), "+f"(d[55]), "+f"(d[56]), "+f"(d[57]), "+f"(d[58]), "+f"(d[59]), "+f"(d[60]), "+f"(d[61]), "+f"(d[62]), "+f"(d[63]), "+f"(d[64]), "+f"(d[65]), "+f"(d[66]), "+f"(d[67]), "+f"(d[68]), "+f"(d[69]), "+f"(d[70]), "+f"(d[71]), "+f"(d[72]), "+f"(d[73]), "+f"(d[74]), "+f"(d[75]), "+f"(d[76]), "+f"(d[77]), "+f"(d[78]), "+f"(d[79]), "+f"(d[80]), "+f"(d[81]), "+f"(d[82]), "+f"(d[83]), "+f"(d[84]), "+f"(d[85]), "+f"(d[86]), "+f"(d[87]), "+f"(d[88]), "+f"(d[89]), "+f"(d[90]), "+f"(d[91]), "+f"(d[92]), "+f"(d[93]), "+f"(d[94]), "+f"(d[95]), "+f"(d[96]), "+f"(d[97]), "+f"(d[98]), "+f"(d[99]), "+f"(d[100]), "+f"(d[101]), "+f"(d[102]), "+f"(d[103]), "+f"(d[104]), "+f"(d[105]), "+f"(d[106]), "+f"(d[107]), "+f"(d[108]), "+f"(d[109]), "+f"(d[110]), "+f"(d[111]), "+f"(d[112]), "+f"(d[113]), "+f"(d[114]), "+f"(d[115]), "+f"(d[116]), "+f"(d[117]), "+f"(d[118]), "+f"(d[119]), "+f"(d[120]), "+f"(d[121]), "+f"(d[122]), "+f"(d[123]), "+f"(d[124]), "+f"(d[125]), "+f"(d[126]), "+f"(d[127])
      : "l"(da), "l"(db));
  } else {
    asm volatile("{\n.reg .pred p;\nsetp.ne.b32 p, 0, 0;\n"
      "wgmma.mma_async.sync.aligned.m64n256k16.f32.bf16.bf16 "
      "{%0, %1, %2, %3, %4, %5, %6, %7, %8, %9, %10, %11, %12, %13, %14, %15, %16, %17, %18, %19, %20, %21, %22, %23, %24, %25, %26, %27, %28, %29, %30, %31, %32, %33, %34, %35, %36, %37, %38, %39, %40, %41, %42, %43, %44, %45, %46, %47, %48, %49, %50, %51, %52, %53, %54, %55, %56, %57, %58, %59, %60, %61, %62, %63, %64, %65, %66, %67, %68, %69, %70, %71, %72, %73, %74, %75, %76, %77, %78, %79, %80, %81, %82, %83, %84, %85, %86, %87, %88, %89, %90, %91, %92, %93, %94, %95, %96, %97, %98, %99, %100, %101, %102, %103, %104, %105, %106, %107, %108, %109, %110, %111, %112, %113, %114, %115, %116, %117, %118, %119, %120, %121, %122, %123, %124, %125, %126, %127}, "
      "%128, %129, p, 1, 1, 0, 1;\n}\n"
      : "=f"(d[0]), "=f"(d[1]), "=f"(d[2]), "=f"(d[3]), "=f"(d[4]), "=f"(d[5]), "=f"(d[6]), "=f"(d[7]), "=f"(d[8]), "=f"(d[9]), "=f"(d[10]), "=f"(d[11]), "=f"(d[12]), "=f"(d[13]), "=f"(d[14]), "=f"(d[15]), "=f"(d[16]), "=f"(d[17]), "=f"(d[18]), "=f"(d[19]), "=f"(d[20]), "=f"(d[21]), "=f"(d[22]), "=f"(d[23]), "=f"(d[24]), "=f"(d[25]), "=f"(d[26]), "=f"(d[27]), "=f"(d[28]), "=f"(d[29]), "=f"(d[30]), "=f"(d[31]), "=f"(d[32]), "=f"(d[33]), "=f"(d[34]), "=f"(d[35]), "=f"(d[36]), "=f"(d[37]), "=f"(d[38]), "=f"(d[39]), "=f"(d[40]), "=f"(d[41]), "=f"(d[42]), "=f"(d[43]), "=f"(d[44]), "=f"(d[45]), "=f"(d[46]), "=f"(d[47]), "=f"(d[48]), "=f"(d[49]), "=f"(d[50]), "=f"(d[51]), "=f"(d[52]), "=f"(d[53]), "=f"(d[54]), "=f"(d[55]), "=f"(d[56]), "=f"(d[57]), "=f"(d[58]), "=f"(d[59]), "=f"(d[60]), "=f"(d[61]), "=f"(d[62]), "=f"(d[63]), "=f"(d[64]), "=f"(d[65]), "=f"(d[66]), "=f"(d[67]), "=f"(d[68]), "=f"(d[69]), "=f"(d[70]), "=f"(d[71]), "=f"(d[72]), "=f"(d[73]), "=f"(d[74]), "=f"(d[75]), "=f"(d[76]), "=f"(d[77]), "=f"(d[78]), "=f"(d[79]), "=f"(d[80]), "=f"(d[81]), "=f"(d[82]), "=f"(d[83]), "=f"(d[84]), "=f"(d[85]), "=f"(d[86]), "=f"(d[87]), "=f"(d[88]), "=f"(d[89]), "=f"(d[90]), "=f"(d[91]), "=f"(d[92]), "=f"(d[93]), "=f"(d[94]), "=f"(d[95]), "=f"(d[96]), "=f"(d[97]), "=f"(d[98]), "=f"(d[99]), "=f"(d[100]), "=f"(d[101]), "=f"(d[102]), "=f"(d[103]), "=f"(d[104]), "=f"(d[105]), "=f"(d[106]), "=f"(d[107]), "=f"(d[108]), "=f"(d[109]), "=f"(d[110]), "=f"(d[111]), "=f"(d[112]), "=f"(d[113]), "=f"(d[114]), "=f"(d[115]), "=f"(d[116]), "=f"(d[117]), "=f"(d[118]), "=f"(d[119]), "=f"(d[120]), "=f"(d[121]), "=f"(d[122]), "=f"(d[123]), "=f"(d[124]), "=f"(d[125]), "=f"(d[126]), "=f"(d[127])
      : "l"(da), "l"(db));
  }
}
__device__ __forceinline__ void wgmma_n256_ssp_ta0_tb1(float* d, uint64_t da, uint64_t db, int accumulate) {
    asm volatile("{\n.reg .pred p;\nsetp.ne.b32 p, %130, 0;\n"
      "wgmma.mma_async.sync.aligned.m64n256k16.f32.bf16.bf16 "
      "{%0, %1, %2, %3, %4, %5, %6, %7, %8, %9, %10, %11, %12, %13, %14, %15, %16, %17, %18, %19, %20, %21, %22, %23, %24, %25, %26, %27, %28, %29, %30, %31, %32, %33, %34, %35, %36, %37, %38, %39, %40, %41, %42, %43, %44, %45, %46, %47, %48, %49, %50, %51, %52, %53, %54, %55, %56, %57, %58, %59, %60, %61, %62, %63, %64, %65, %66, %67, %68, %69, %70, %71, %72, %73, %74, %75, %76, %77, %78, %79, %80, %81, %82, %83, %84, %85, %86, %87, %88, %89, %90, %91, %92, %93, %94, %95, %96, %97, %98, %99, %100, %101, %102, %103, %104, %105, %106, %107, %108, %109, %110, %111, %112, %113, %114, %115, %116, %117, %118, %119, %120, %121, %122, %123, %124, %125, %126, %127}, "
      "%128, %129, p, 1, 1, 0, 1;\n}\n"
      : "+f"(d[0]), "+f"(d[1]), "+f"(d[2]), "+f"(d[3]), "+f"(d[4]), "+f"(d[5]), "+f"(d[6]), "+f"(d[7]), "+f"(d[8]), "+f"(d[9]), "+f"(d[10]), "+f"(d[11]), "+f"(d[12]), "+f"(d[13]), "+f"(d[14]), "+f"(d[15]), "+f"(d[16]), "+f"(d[17]), "+f"(d[18]), "+f"(d[19]), "+f"(d[20]), "+f"(d[21]), "+f"(d[22]), "+f"(d[23]), "+f"(d[24]), "+f"(d[25]), "+f"(d[26]), "+f"(d[27]), "+f"(d[28]), "+f"(d[29]), "+f"(d[30]), "+f"(d[31]), "+f"(d[32]), "+f"(d[33]), "+f"(d[34]), "+f"(d[35]), "+f"(d[36]), "+f"(d[37]), "+f"(d[38]), "+f"(d[39]), "+f"(d[40]), "+f"(d[41]), "+f"(d[42]), "+f"(d[43]), "+f"(d[44]), "+f"(d[45]), "+f"(d[46]), "+f"(d[47]), "+f"(d[48]), "+f"(d[49]), "+f"(d[50]), "+f"(d[51]), "+f"(d[52]), "+f"(d[53]), "+f"(d[54]), "+f"(d[55]), "+f"(d[56]), "+f"(d[57]), "+f"(d[58]), "+f"(d[59]), "+f"(d[60]), "+f"(d[61]), "+f"(d[62]), "+f"(d[63]), "+f"(d[64]), "+f"(d[65]), "+f"(d[66]), "+f"(d[67]), "+f"(d[68]), "+f"(d[69]), "+f"(d[70]), "+f"(d[71]), "+f"(d[72]), "+f"(d[73]), "+f"(d[74]), "+f"(d[75]), "+f"(d[76]), "+f"(d[77]), "+f"(d[78]), "+f"(d[79]), "+f"(d[80]), "+f"(d[81]), "+f"(d[82]), "+f"(d[83]), "+f"(d[84]), "+f"(d[85]), "+f"(d[86]), "+f"(d[87]), "+f"(d[88]), "+f"(d[89]), "+f"(d[90]), "+f"(d[91]), "+f"(d[92]), "+f"(d[93]), "+f"(d[94]), "+f"(d[95]), "+f"(d[96]), "+f"(d[97]), "+f"(d[98]), "+f"(d[99]), "+f"(d[100]), "+f"(d[101]), "+f"(d[102]), "+f"(d[103]), "+f"(d[104]), "+f"(d[105]), "+f"(d[106]), "+f"(d[107]), "+f"(d[108]), "+f"(d[109]), "+f"(d[110]), "+f"(d[111]), "+f"(d[112]), "+f"(d[113]), "+f"(d[114]), "+f"(d[115]), "+f"(d[116]), "+f"(d[117]), "+f"(d[118]), "+f"(d[119]), "+f"(d[120]), "+f"(d[121]), "+f"(d[122]), "+f"(d[123]), "+f"(d[124]), "+f"(d[125]), "+f"(d[126]), "+f"(d[127])
      : "l"(da), "l"(db), "r"(accumulate));
}

template <int N> __device__ __forceinline__ void quad_sum(float* m) {
#pragma unroll
  for (int o = 1; o <= 2; o <<= 1) {
    float t[N];
#pragma unroll
    for (int i = 0; i < N; i++) t[i] = __shfl_xor_sync(~0u, m[i], o);
#pragma unroll
    for (int i = 0; i < N; i++) m[i] += t[i];
  }
}
__device__ __forceinline__ bool softmax_unsafe(const uint32_t* t, float l0, float l1) {
  const float m0 = fmaxf(bf_lo(t[0]) + bf_hi(t[0]), bf_lo(t[2]) + bf_hi(t[2])), m1 = fmaxf(bf_lo(t[1]) + bf_hi(t[1]), bf_lo(t[3]) + bf_hi(t[3]));
  return __any_sync(~0u, !(m0 * l0 < 2500.f) | !(m1 * l1 < 2500.f));
}
__device__ __forceinline__ void softmax_shift(float* p, float c0, float c1) {
#pragma unroll 1
  for (int it = 0; it < 8; it++) {
    float mx = p[0], mn = p[0];
#pragma unroll
    for (int j = 1; j < 8; j++) { mx = fmaxf(mx, p[(j >> 1) * 4 + (j & 1)]); mn = fminf(mn, p[(j >> 1) * 4 + (j & 1)]); }
#pragma unroll
    for (int o = 1; o <= 2; o <<= 1) { mx = fmaxf(mx, __shfl_xor_sync(~0u, mx, o)); mn = fminf(mn, __shfl_xor_sync(~0u, mn, o)); }
    const float half = fminf(0.5f * (mx - mn), 50.f * rcp(it & 1 ? c1 : c0));
    float r[8];
#pragma unroll
    for (int j = 0; j < 8; j++) {
      const float v = p[(j >> 1) * 4 + (j & 1)];
      r[j] = fmaxf(v - mx + half, 0.f) + fminf(v - mn - half, 0.f) + (v - v);
    }
#pragma unroll
    for (int k = 0; k < 7; k++)
#pragma unroll
      for (int j = 0; j < 8; j++) p[(k >> 1) * 16 + (k & 1) * 2 + (j >> 1) * 4 + (j & 1)] = p[((k + 1) >> 1) * 16 + ((k + 1) & 1) * 2 + (j >> 1) * 4 + (j & 1)];
#pragma unroll
    for (int j = 0; j < 8; j++) p[50 + (j >> 1) * 4 + (j & 1)] = r[j];
  }
}
template <int J0 = 0, int J1 = 8> __device__ __forceinline__ void k_exp(const float* p, float c0, float c1, float* e, float* s) {
#pragma unroll
  for (int j = J0; j < J1; j++) {
    e[2 * j] = ex2(p[2 * j] * (j & 1 ? c1 : c0));
    e[2 * j + 1] = ex2(p[2 * j + 1] * (j & 1 ? c1 : c0));
    e[16 + j] = rcp(e[2 * j] * e[2 * j + 1]);
    const float t = e[2 * j] + e[2 * j + 1];
    s[j & 1] = j < 2 ? t : s[j & 1] + t;
    s[2 + (j & 1)] = j < 2 ? e[16 + j] * t : fmaf(e[16 + j], t, s[2 + (j & 1)]);
  }
}
template <int J0 = 0, int J1 = 8> __device__ __forceinline__ void q_exp(const float* p, float c0, float c1, uint32_t* f) {
#pragma unroll
  for (int j = J0; j < J1; j++) {
    const float e0 = ex2(p[2 * j] * (j & 1 ? c1 : c0)), e1 = ex2(p[2 * j + 1] * (j & 1 ? c1 : c0)), r = rcp(e0 * e1);
    f[j] = pack2(e0, e1);
    f[8 + j] = bmul2(f[j], pack2(r, r));
  }
}

#define FMA8(A, U, X)                                                                                        \
  A[0] = fmaf(bf_lo(U.x), X, A[0]); A[1] = fmaf(bf_hi(U.x), X, A[1]); A[2] = fmaf(bf_lo(U.y), X, A[2]); A[3] = fmaf(bf_hi(U.y), X, A[3]); \
  A[4] = fmaf(bf_lo(U.z), X, A[4]); A[5] = fmaf(bf_hi(U.z), X, A[5]); A[6] = fmaf(bf_lo(U.w), X, A[6]); A[7] = fmaf(bf_hi(U.w), X, A[7])

__device__ __forceinline__ uint32_t routed_row(const __nv_bfloat16* x, uint32_t tag, int lane, uint4* xr) {
  uint32_t best = 0, sv = 0;
#pragma unroll 1
  for (int it = 0; it < SPIN_MAX; it++) {
    const int sel = 2047 - (best & 0x7ff);
#pragma unroll
    for (int i = 0; i < 4; i++) xr[i] = ldg_nc(x + (size_t)sel * DM + i * 256 + lane * 8);
    const unsigned long long st = ld_rlx64(g_stat + sel);
    const uint4 b0 = ld_rlx128(g_best + lane * 2), b1 = ld_rlx128(g_best + 64 + lane * 2);
    const uint32_t m = __reduce_max_sync(~0u, max(max(b0.y == tag ? b0.x : 0u, b0.w == tag ? b0.z : 0u), max(b1.y == tag ? b1.x : 0u, b1.w == tag ? b1.z : 0u)));
    sv = (uint32_t)st;
    if (__all_sync(~0u, b0.y == tag && b0.w == tag && b1.y == tag && b1.w == tag && m == best && (uint32_t)(st >> 32) == tag)) break;
    best = m;
    if (AM_NS) __nanosleep(AM_NS);
  }
  const uint32_t m2 = (sv & 0xffff0000u) | (sv >> 16);
  const float rs = rcp(bf_lo(sv));
#pragma unroll
  for (int i = 0; i < 4; i++) {
    const uint32_t d0 = bsub2(xr[i].x, m2), d1 = bsub2(xr[i].y, m2), d2 = bsub2(xr[i].z, m2), d3 = bsub2(xr[i].w, m2);
    xr[i] = make_uint4(pack2(bf_lo(d0) * rs, bf_hi(d0) * rs), pack2(bf_lo(d1) * rs, bf_hi(d1) * rs), pack2(bf_lo(d2) * rs, bf_hi(d2) * rs),
                       pack2(bf_lo(d3) * rs, bf_hi(d3) * rs));
  }
  return best;
}

struct Params {
  const __nv_bfloat16 *x, *wqkv, *wo, *w_r, *w_gate, *w_up, *w_down;
};

template <bool BY_SMID> __global__ void __launch_bounds__(384, 1)
fused_kernel(const __grid_constant__ CUtensorMap mX, const __grid_constant__ CUtensorMap mWkv, const __grid_constant__ CUtensorMap mWq,
             const __grid_constant__ CUtensorMap mWo, const __grid_constant__ CUtensorMap mPhi, const __grid_constant__ CUtensorMap mWp,
             const __grid_constant__ CUtensorMap mOut, const __grid_constant__ CUtensorMap mWc,
             const __grid_constant__ CUtensorMap mG, const __grid_constant__ CUtensorMap mU, const __grid_constant__ CUtensorMap mD,
             const __grid_constant__ CUtensorMap mXs, const __grid_constant__ CUtensorMap mG2, const __grid_constant__ CUtensorMap mU2, const Params P) {
  constexpr uint32_t sb = SB, bar = SB + SM_BAR;
  int bid = blockIdx.x;
  if (BY_SMID) {
    uint32_t sm;
    asm volatile("mov.u32 %0, %%smid;" : "=r"(sm));
    const uint32_t tq = (sm - 64) >> 1, q7 = (tq * 37) >> 8;
    const uint32_t gpc = sm < 64 ? (sm >> 1) & 7 : 1 + tq - 7 * q7, idx = (sm < 64 ? sm >> 4 : 4 + q7) * 2 + (sm & 1);
    bid = sm < 120 ? ((PTAB >> (4 * gpc)) & 7) * 16 + idx : sm < 124 ? sm + 8 : sm - 116;
  }
  const int hg = ((bid >> 2) & 3) + 4 * ((bid >> 4) & 1), mb = (bid & 3) + 4 * ((bid >> 5) & 3);
  if (bid < NCTA && threadIdx.x < 256) {
    const uint32_t r0 = threadIdx.x >> 3, c = threadIdx.x & 7, dst = sb + 2 * KV_STAGE + r0 * 128 + ((c ^ (r0 & 7)) << 4);
    const char* xs = (const char*)P.x + (size_t)(mb * 128 + r0) * 2048 + c * 16;
    const char* ws = (const char*)P.wqkv + (size_t)r0 * 6144 + 2048 + hg * 256 + c * 16;
#pragma unroll
    for (int i = 0; i < 4; i++) cp_async16(dst + i * 4096, xs + i * 65536);
#pragma unroll
    for (int i = 0; i < 8; i++) cp_async16(dst + 16384 + i * 4096, ws + (i & 1) * 196608 + (i >> 2) * 2048 + ((i >> 1) & 1) * 128);
  }
  extern __shared__ __align__(1024) uint8_t smem[];
  if (smem_u32(smem) != SB) __trap();
  const int warp = __shfl_sync(~0u, threadIdx.x >> 5, 0);

  if (bid >= NCTA) {
    constexpr uint32_t XV = SM_WPHI, ONES = SM_ZT, BF = bar, BE = bar + 48, BX = bar + 96;
    constexpr int NJ = (DM - GROWS) / 64;
    const int lane = lane_id(), sp = bid - NCTA;
    const uint32_t tag = ld_rlx(g_epoch + bid * 32 + lane) + 1;
    if (warp == 8 && elect_one()) {
#pragma unroll 1
      for (int i = 0; i < 13; i++) mbar_init(bar + 8 * i, i >= 6 && i < 12 ? 8 : 1);
    }
    if (warp == 9) { sts64u(sb + ONES + lane * 8, 0x3f803f80u, 0x3f803f80u); fence_async_smem(); }
    __syncthreads();
    if (warp == 8) {
      if (elect_one()) {
        uint32_t s = 0, ph = 1;
        for (const long long c0 = clock64(); clock64() - c0 < SP_DELAY;) {}
#pragma unroll 1
        for (int job = 0; job < 8; job++) {
          const CUtensorMap* m = job == 0 ? &mWq : sp & 2 ? &mU2 : &mG2;
          const int g0 = job ? (sp & 1) * 28 + job * 4 - 4 : sp * 4;
#pragma unroll 1
          for (int row = job ? GROWS : 0; row < DM; row += 64) {
            mbar_wait(BE + 8 * s, ph);
            mbar_expect_tx(BF + 8 * s, Q_STAGE);
            tma4d(sb + s * Q_STAGE, m, 0, row, g0, 0, BF + 8 * s);
            tma4d(sb + s * Q_STAGE + 16384, m, 0, row, g0 + 2, 0, BF + 8 * s);
            if (++s == 6) { s = 0; ph ^= 1; }
          }
        }
      }
    } else if (warp == 9) {
      uint4 xr[4];
      routed_row(P.x, tag, lane, xr);
#pragma unroll
      for (int i = 0; i < 4; i++) sts128u(sb + XV + i * 512 + lane * 16, xr[i].x, xr[i].y, xr[i].z, xr[i].w);
      fence_async_smem();
      __syncwarp();
      if (lane == 0) mbar_arrive(BX);
    } else if (warp < 8) {
      uint32_t s = 0, ph = 0;
#pragma unroll 1
      for (int job = 0; job < 8; job++) {
        float d[8] = {0.f, 0.f, 0.f, 0.f, 0.f, 0.f, 0.f, 0.f};
        if (job == 1) mbar_wait(BX, 0);
#pragma unroll 1
        for (int i = 0; i < (job ? NJ : 16); i++) {
          mbar_wait(BF + 8 * s, ph);
          wg_fence();
#pragma unroll
          for (int k = 0; k < 8; k++)
            wgmma_n8_ss_ta1_tb0(d + 4 * (k >> 2), mkdesc(sb + k * 2048, 16, 1024, 1, s * (Q_STAGE / 16) + (warp >> 2) * 1024),
                                mkdesc(sb, 16, 128, 0, job ? (XV + GROWS * 2) / 16 + i * 8 + (k & 3) * 2 : ONES / 16), 1);
          wg_commit();
          wg_wait<0>();
          if (lane == 0) mbar_arrive(BE + 8 * s);
          if (++s == 6) { s = 0; ph ^= 1; }
        }
        reg_fence<8>(d);
        float* dst = (job ? g_gp + sp * 1792 + job * 256 - 256 : g_cs + sp * 256) + (warp >> 2) * 128 + (warp & 3) * 16 + (lane >> 2);
        if ((lane & 3) == 0) {
#pragma unroll
          for (int i = 0; i < 4; i++) st_rlx(dst + (i >> 1) * 64 + (i & 1) * 8, mark(__float_as_uint(d[2 * i]), tag & 1));
        }
        __syncwarp();
      }
      if (warp == 0) g_epoch[bid * 32 + lane] = tag;
    }
    return;
  }
#define Q_SLAB(J) ((J) < 8 ? ((J) + 8 - 2 * (hg & 4)) & 15 : 2 * (hg & 4) + 2 * ((J) & 3) + ((J) >> 2 & 1))
#define Q_AOFF(J) ((J) == 8 + (hg & 3) ? SM_X0 : (J) == 12 + (hg & 3) ? SM_X1 : ((J) & 3) * Q_STAGE)
#define Q_LOAD(J)                                                                                            \
  do {                                                                                                       \
    const uint32_t fb_ = bar + B_FULLQ + 8 * ((J) & 3);                                                      \
    const int k_ = Q_SLAB(J) * 64;                                                                           \
    mbar_expect_tx(fb_, Q_STAGE);                                                                            \
    mbar_arrive2(fb_);                                                                                       \
    tma2d(sb + Q_AOFF(J), &mX, k_, mb * 128, fb_);                                                           \
    tma4d(sb + ((J) & 3) * Q_STAGE + 16384, &mWq, 0, k_, hg * 2, 0, fb_);                                    \
  } while (0)
  if (warp >= 8) {
    asm volatile("setmaxnreg.dec.sync.aligned.u32 %0;" ::"n"(REG_H));
    const int lane = lane_id();
    const int f = (warp - 9) & 3;
    if (f == 3) {
      if (elect_one()) {
        PROF(0); PROFT(32);
#pragma unroll
        for (int s = 0; s < 3; s++) mbar_init(bar + B_FULLKV + 8 * s, 1);
      }
      __syncwarp();
      asm volatile("bar.arrive 14, 288;" ::: "memory");
      if (elect_one()) {
#pragma unroll
        for (int s = 0; s < 2; s++) {
          mbar_expect_tx(bar + B_FULLKV + 8 * s, KV_STAGE);
          tma2d(sb + s * KV_STAGE, &mX, (s + 1) * 64, mb * 128, bar + B_FULLKV + 8 * s);
          tma4d(sb + s * KV_STAGE + 16384, &mWkv, 0, (s + 1) * 64, hg * 2, 1, bar + B_FULLKV + 8 * s);
        }
      }
      __syncwarp();
    }
    const uint32_t ep = ld_rlx(g_epoch + bid * 32 + lane);
    if (f < 2) {
#pragma unroll
      for (int i = 0; i < 2; i++) {
        const uint4 u = __ldg((const uint4*)P.w_r + (f * 2 + i) * 32 + lane);
        sts128u(sb + SM_XSEL + (f * 2 + i) * 512 + lane * 16, u.x, u.y, u.z, u.w);
      }
    }
    bar_sync(13, 384);
    const uint32_t tag = ep + 1, par = tag & 1;
    const bool ffn = bid < NFFN;
    const int fb = bid, cu = bid >> 1, ch = bid & 1;
#define CS_STORE(SEC, C)                                                                                     \
  _Pragma("unroll") for (int r = 0; r < 3; r++) {                                                            \
    const uint32_t h0 = pack2(C.x, C.y), h1 = pack2(C.z, C.w);                                               \
    sts64u(sb + SM_CST + (SEC) * 1024 + (lane >> 4) * 512 + (lane & 1) * 8 + r * 128 + ((((lane & 15) >> 1) ^ (r + (lane >> 4) * 4)) << 4), h0, h1); \
    C.x -= bf_lo(h0); C.y -= bf_hi(h0); C.z -= bf_lo(h1); C.w -= bf_hi(h1);                                  \
  }
#define BAD4(U) ((U.x ^ par) | (U.y ^ par) | (U.z ^ par) | (U.w ^ par))
    const int n0 = f < 2 ? 0 : 2 * f - 3, ne = FFN_OFF || !ffn ? 3 : f == 3 ? 3 + G8 : 3 + GN;
    const uint32_t fsb = sb + SM_FST + ((f + 1) & 3) * 8192, fbar = bar + B_FST + f * 16, fst = fsb + (lane >> 4) * 2048 + (lane & 15) * 16;
    const CUtensorMap *ma = &mWc, *mc = &mWc;
    int sx = 1024 + cu * 32, sy = ch * 512 + f * 192, sdy = 32;
#define STAGEG(N)                                                                                            \
  do {                                                                                                       \
    if ((N) == 3) { ma = &mG; mc = &mU; sx = fb * 32; sy = f * (GN * 32);  sdy = 0; }                        \
    if ((N) < ne && elect_one()) {                                                                           \
      const uint32_t dst_ = fsb + ((N) & 1) * 4096, b_ = fbar + ((N) & 1) * 8;                               \
      mbar_expect_tx(b_, 4096);                                                                              \
      tma2d(dst_, ma, sx, sy, b_);                                                                           \
      tma2d(dst_ + 2048, mc, sx, sy + sdy, b_);                                                              \
    }                                                                                                        \
    sy += 32 + sdy;                                                                                          \
  } while (0)
    float a[8], gsum = 0.f, usum = 0.f;
    {
      if (f == 3) {
        if (elect_one()) {
          if (XS_EARLY) { mbar_expect_tx(bar + B_XST, 16384); tma3d(sb + SM_XST, &mXs, 0, bid * 16, 0, bar + B_XST); }
          mbar_expect_tx(bar + B_WPHI, 8192);
          tma2d(sb + SM_WPHI, &mPhi, 0, hg * 128, bar + B_WPHI);
          prefetch_map(&mWq); prefetch_map(&mWo); prefetch_map(&mWp); prefetch_map(&mD);
          PROF(31);
        }
        __syncwarp();
      } else {
        if (lane == 0) prefetch_map(f == 0 ? &mWc : f == 1 ? &mG : &mU);
        if (f == 2) ((float2*)g_y[par])[bid * 32 + lane] = make_float2(0.f, 0.f);
      }
      float st[13];
#pragma unroll
      for (int i = 0; i < 13; i++) st[i] = 0.f;
#pragma unroll 1
      for (int i = 0; i < 4; i++) {
        mbar_wait(bar + B_XST + 8 * (i >> 1), 0);
        if (f == 0 && lane == 0 && i == 0) PROF(1);
        const uint4 wu = lds128u(sb + SM_XSEL + i * 512 + lane * 16);
        const float wf[8] = {bf_lo(wu.x), bf_hi(wu.x), bf_lo(wu.y), bf_hi(wu.y), bf_lo(wu.z), bf_hi(wu.z), bf_lo(wu.w), bf_hi(wu.w)};
        st[12] += ((wf[0] + wf[1]) + (wf[2] + wf[3])) + ((wf[4] + wf[5]) + (wf[6] + wf[7]));
#pragma unroll
        for (int r = 0; r < 4; r++) {
          const uint4 u = lds128u(sb + SM_XST + i * 8192 + (4 * f + r) * 512 + lane * 16);
          const float xf[8] = {bf_lo(u.x), bf_hi(u.x), bf_lo(u.y), bf_hi(u.y), bf_lo(u.z), bf_hi(u.z), bf_lo(u.w), bf_hi(u.w)};
#pragma unroll
          for (int k = 0; k < 8; k++) { st[r] += xf[k]; st[4 + r] = fmaf(xf[k], xf[k], st[4 + r]); st[8 + r] = fmaf(xf[k], wf[k], st[8 + r]); }
        }
        if (i >= 2 && f < 3) STAGEG(n0 + i - 2);
      }
      const bool up = lane & 16, up2 = lane & 8;
#pragma unroll
      for (int q = 0; q < 3; q++) {
        const float k0 = up ? st[4 * q + 2] : st[4 * q], k1 = up ? st[4 * q + 3] : st[4 * q + 1];
        const float o0 = up ? st[4 * q] : st[4 * q + 2], o1 = up ? st[4 * q + 1] : st[4 * q + 3];
        const float m0 = k0 + __shfl_xor_sync(~0u, o0, 16), m1 = k1 + __shfl_xor_sync(~0u, o1, 16);
        a[q] = (up2 ? m1 : m0) + __shfl_xor_sync(~0u, up2 ? m0 : m1, 8);
      }
      a[3] = st[12] + __shfl_xor_sync(~0u, st[12], 16);
      a[3] += __shfl_xor_sync(~0u, a[3], 8);
#pragma unroll
      for (int o = 4; o; o >>= 1)
#pragma unroll
        for (int q = 0; q < 4; q++) a[q] += __shfl_xor_sync(~0u, a[q], o);
      if ((lane & 7) == 0) sts128(sb + SM_ROWS + (4 * f + (lane >> 3)) * 16, a[0], a[1], a[2], a[3]);
      if (f < 3) asm volatile("bar.arrive 7, 128;" ::: "memory");
    }
    if (f == 3) {
      bar_sync(7, 128);
      const int row = bid * 16 + (lane & 15);
      const float4 v = lds128(sb + SM_ROWS + (lane & 15) * 16);
      const float mf = v.x * (1.f / DM), mean = bf_round(mf), var = fmaxf(fmaf(-mf, mf, v.y * (1.f / DM)), 0.f);
      const float sd = bf_round(sqrt_approx(bf_round(bf_round(var) + 1e-5f)));
      const uint32_t rb = pack2(fmaf(-mean, v.w, v.z) * rcp(sd), 0.f) & 0xffffu, ord = (rb & 0x8000u) ? (~rb & 0xffffu) : (rb | 0x8000u);
      uint32_t best = __reduce_max_sync(~0u, (ord << 16) | (uint32_t)(2047 - row));
      if (lane < 16) st_rlx64(g_stat + row, ((unsigned long long)tag << 32) | __float_as_uint(mean) | (__float_as_uint(sd) >> 16));
      if (lane == 0) { asm volatile("red.relaxed.gpu.global.max.u64 [%0], %1;" ::"l"(g_best + bid), "l"(((unsigned long long)tag << 32) | best) : "memory"); PROF(17); }
#pragma unroll 1
      for (int n = 3; n < 5; n++) STAGEG(n);
      {
        uint4 xr[4];
        best = routed_row(P.x, tag, lane, xr);
#pragma unroll
        for (int i = 0; i < (GROWS + 255) / 256; i++) {
          const uint32_t dst = sb + SM_XSEL + i * 1024 + (lane >> 2) * 128 + (lane & 3) * 8;
          sts64(dst, bf_lo(xr[i].x), bf_lo(xr[i].z)); sts64(dst + 32, bf_hi(xr[i].x), bf_hi(xr[i].z));
          sts64(dst + 64, bf_lo(xr[i].y), bf_lo(xr[i].w)); sts64(dst + 96, bf_hi(xr[i].y), bf_hi(xr[i].w));
        }
        sts64u(sb + SM_RED + 16, tag, best);
        __syncwarp();
        if (lane == 0) { mbar_arrive(bar + B_XS); PROF(19); }
      }
      unsigned long long sv4[4];
      uint4 u[4];
#pragma unroll 1
      for (int it = 0; it < SPIN_MAX; it++) {
#pragma unroll
        for (int i = 0; i < 4; i++) { u[i] = ld_rlx128(g_cs + (1 + i) * 1024 + hg * 128 + lane * 4); sv4[i] = ld_rlx64(g_stat + mb * 128 + i * 32 + lane); }
        bool ok = ((BAD4(u[0]) | BAD4(u[1]) | BAD4(u[2]) | BAD4(u[3])) & 1) == 0;
#pragma unroll
        for (int i = 0; i < 4; i++) ok = ok && (uint32_t)(sv4[i] >> 32) == tag;
        if (__all_sync(~0u, ok)) break;
        __nanosleep(200);
      }
#pragma unroll
      for (int i = 0; i < 4; i++) {
        const uint32_t sv = (uint32_t)sv4[i], sd2 = (sv << 16) | (sv & 0xffffu);
        sts64(sb + SM_STAT + (i * 32 + lane) * 8, -bf_hi(sv), rcp(bf_lo(sv)));
        sts128u(sb + SM_SDT + lane * 64 + ((i ^ ((lane >> 1) & 3)) << 4), sd2, sd2, sd2, sd2);
      }
#pragma unroll
      for (int i = 0; i < 2; i++) {
        float4 c = make_float4(unmark(u[i].x) + unmark(u[i + 2].x), unmark(u[i].y) + unmark(u[i + 2].y), unmark(u[i].z) + unmark(u[i + 2].z),
                               unmark(u[i].w) + unmark(u[i + 2].w));
        CS_STORE(i, c);
      }
      fence_async_smem();
      bar_sync(8, 64);
      if (lane == 0) { mbar_arrive(bar + B_CS); PROF(10); }
    }
    {
      uint32_t xa = sb + SM_RED + 32, xstep = 0;
      const uint32_t zero = __float_as_uint(lds32(sb + SM_RED + 12));
#pragma unroll 1
      for (int ph = f == 3; ph < 2; ph++) {
#pragma unroll
        for (int j = 0; j < 8; j++) a[j] = 0.f;
        if (ph && f == 0) {
        {
          mbar_wait(bar + B_WPHI, 0);
          float nq[8] = {0.f, 0.f, 0.f, 0.f, 0.f, 0.f, 0.f, 0.f};
  #pragma unroll 2
          for (int r = 0; r < 16; r++) {
            const uint4 u = lds128u(sb + SM_WPHI + ((lane >> 2) * 16 + r) * 64 + (((lane ^ (r >> 1)) & 3) << 4));
            nq[0] = fmaf(bf_lo(u.x), bf_lo(u.x), nq[0]); nq[1] = fmaf(bf_hi(u.x), bf_hi(u.x), nq[1]); nq[2] = fmaf(bf_lo(u.y), bf_lo(u.y), nq[2]);
            nq[3] = fmaf(bf_hi(u.y), bf_hi(u.y), nq[3]); nq[4] = fmaf(bf_lo(u.z), bf_lo(u.z), nq[4]); nq[5] = fmaf(bf_hi(u.z), bf_hi(u.z), nq[5]);
            nq[6] = fmaf(bf_lo(u.w), bf_lo(u.w), nq[6]); nq[7] = fmaf(bf_hi(u.w), bf_hi(u.w), nq[7]);
          }
          uint32_t m = 0;
  #pragma unroll
          for (int i = 0; i < 8; i++) m = max(m, __float_as_uint(nq[i] + __shfl_xor_sync(~0u, nq[i], 4)) & 0x7fffffffu);
          sts32(sb + SM_RED + 24, 4.2f * __uint_as_float(__reduce_max_sync(~0u, m)));
        }
          asm volatile("bar.arrive 8, 64;" ::: "memory");
        }
        if (ph) { mbar_wait(bar + B_XS, 0); xa = sb + SM_XSEL + f * (GN * 128) + ((lane >> 2) & 3) * 32; xstep = 128; }
#pragma unroll 1
        for (int n = ph ? 3 : n0; n < (ph ? ne : 3); n++) {
          const float4 x0 = lds128(xa), x1 = lds128(xa + 16);
          xa += xstep;
          mbar_wait(fbar + (n & 1) * 8, ((n - n0) >> 1) & 1);
          uint4 u[8];
#pragma unroll
          for (int j = 0; j < 8; j++) u[j] = lds128u(fst + (n & 1) * 4096 + j * 256);
          FMA8(a, u[0], x0.x); FMA8(a, u[1], x0.y); FMA8(a, u[2], x0.z); FMA8(a, u[3], x0.w);
          if (__any_sync(~0u, ((u[4].x | u[5].x | u[6].x | u[7].x | __float_as_uint(a[0]) | __float_as_uint(a[7])) & zero) == 0)) STAGEG(n + 2);
          FMA8(a, u[4], x1.x); FMA8(a, u[5], x1.y); FMA8(a, u[6], x1.z); FMA8(a, u[7], x1.w);
        }
#pragma unroll
        for (int o = 4; o <= 8; o <<= 1)
#pragma unroll
          for (int j = 0; j < 8; j++) a[j] += __shfl_xor_sync(~0u, a[j], o);
        if (ph && lane == 0) mbar_arrive(bar + B_FFN);
        const uint32_t red = ph ? sb + SM_GRED : sb + SM_RED + 64;
        if ((lane & 12) == 0) {
          const uint32_t d = red + f * 256 + (lane >> 4) * 128 + (lane & 3) * 32;
          sts128(d, a[0], a[1], a[2], a[3]); sts128(d + 16, a[4], a[5], a[6], a[7]);
        }
        if (f != 2) {
          asm volatile("bar.arrive %0, %1;" ::"r"(4 + ph), "r"(96 + 32 * ph) : "memory");
        } else {
          bar_sync(4 + ph, 96 + 32 * ph);
          const uint32_t ra = red + lane * 4;
          gsum = lds32(ra) + lds32(ra + 256) + lds32(ra + 512);
          usum = lds32(ra + 128) + lds32(ra + 384) + lds32(ra + 640);
          if (!ph) st_rlx(g_cs + 1024 + ch * 2048 + cu * 32 + lane, mark(__float_as_uint(gsum + usum), par));
          else { gsum += lds32(ra + 768); usum += lds32(ra + 896); }
          if (lane == 0) PROF(ph ? 34 : 18);
        }
      }
    }
    if (f == 3) {
      if (elect_one()) {
        PROF(7);
        mbar_wait(bar + B_FULLQ, 0);
#pragma unroll 1
        for (int j = 3; j < 16; j++) {
          mbar_wait(bar + (j < 4 ? B_EMPTYKV + 16 : B_EMPTYQ + 8 * (j & 3)), ((j >> 2) & 1) ^ 1);
          if (j == 12 + (hg & 3)) mbar_wait(bar + B_KVST + 8, 0);
          Q_LOAD(j);
        }
        PROF(47);
        mbar_expect_tx(bar + B_DN, 65536);
#pragma unroll 1
        for (int i = 0; i < 4; i++) {
          mbar_wait(bar + B_EMPTYQ + 8 * i, 1);
          tma3d(sb + i * Q_STAGE, &mD, 0, fb * 32, i * 4, bar + B_DN);
        }
        PROF(48);
#pragma unroll 1
        for (int i = 0; i < 16; i++) {
          const int s = i & 3, n = i < 9 ? i - 2 : i - 9, kb = i < 2 ? 2 * hg + i : 2 * (n + (n >= hg)) + (i >= 9);
          if (i >= 4) mbar_wait(bar + B_EMPTYQ + 8 * s, ((i >> 2) & 1) ^ 1);
          mbar_expect_tx(bar + B_FULLQ + 8 * s, 16384);
          if (i < 2) {
            mbar_arrive2(bar + B_FULLQ + 8 * s);
            tma3d(sb + s * Q_STAGE + 16384, &mWo, 0, kb * 64, hg * 2, bar + B_FULLQ + 8 * s);
          } else {
            tma5d(sb + s * Q_STAGE + 16384, &mWp, hg * 128, kb * 2, bar + B_FULLQ + 8 * s);
            tma5d(sb + s * Q_STAGE + 24576, &mWp, hg * 128 + 64, kb * 2, bar + B_FULLQ + 8 * s);
            if (i >= 3) {
              if (i == 3) { mbar_wait(bar + B_DND, 0); PROF(14); }
#pragma unroll 1
              for (int a = i == 3 ? 2 : i; a <= i; a++) {
                const uint4* src = g_ofr + (mb * 16 + (a == 2 ? (hg == 0 ? 2 : 0) : kb)) * 1024;
#pragma unroll
                for (int h = 0; h < 2; h++) {
                  mbar_expect_tx(bar + B_AIN + (a & 3) * 16 + h * 8, 8192);
                  bulk_load(sb + (a & 3) * Q_STAGE + h * 8192, src + h * 512, 8192, bar + B_AIN + (a & 3) * 16 + h * 8);
                }
              }
            }
          }
        }
      }
    } else {
      if (f == 2) {
        if (PFD && ffn) {
#pragma unroll 1
          for (int i = 0; i < 16; i++) { touch_l2((const char*)P.w_down + fb * 65536 + i * 4096 + lane * 128, lane); __nanosleep(PFD); }
        }
        if (WOT) {
#pragma unroll 1
          for (int i = 0; i < 8; i++) { touch_l2((const char*)P.wo + ((mb & 7) * 128 + i * 16 + (lane >> 1)) * 2048 + hg * 256 + (lane & 1) * 128, lane); __nanosleep(PFD); }
        }
        asm volatile("cp.async.wait_all;" ::: "memory");
        uint4 u;
#pragma unroll 1
        for (int it = 0; it < SPIN_MAX; it++) {
          u = ld_rlx128(g_cs + hg * 128 + lane * 4);
          if (__all_sync(~0u, !(BAD4(u) & 1))) break;
          __nanosleep(200);
        }
        mbar_wait(bar + B_PHI, 0);
        float4 c = make_float4(unmark(u.x), unmark(u.y), unmark(u.z), unmark(u.w));
        CS_STORE(2, c);
        fence_async_smem();
        __syncwarp();
        if (lane == 0) mbar_arrive(bar + B_CSQ);
      }
      const uint32_t target = __shfl_sync(~0u, tag, 0) * 16;
#pragma unroll 1
      for (int R = 0; R < 2; R++) {
        const uint32_t own = (hg * 2 + R) * 16 + mb, pst = sb + (R ? SM_PST1 : SM_PST0);
        if (f == R) {
          mbar_wait(bar + B_KVST + 8 * R, 0);
          if (f == 1 && lane == 0) PROF(11);
          wait_hint(g_xcnt + hg * 64 + R * 16 + mb, target);
          if (elect_one()) {
            PROF(35 + R);
            fence_async_global();
            mbar_expect_tx(bar + B_PART + 8 * R, 8192);
            bulk_load(pst, g_part + own * 512, 8192, bar + B_PART + 8 * R);
          }
          __syncwarp();
          uint4 uz;
#pragma unroll 1
          for (int it = 0; it < SPIN_MAX; it++) {
            uz = ld_rlx128(g_zpart + own * 128 + lane * 4);
            if (__all_sync(~0u, !(BAD4(uz) & 1))) break;
          }
          const bool b1 = lane & 2, b2 = lane & 4;
          const float z0 = unmark(b1 ? uz.z : uz.x) + __shfl_xor_sync(~0u, unmark(b1 ? uz.x : uz.z), 2);
          const float z1 = unmark(b1 ? uz.w : uz.y) + __shfl_xor_sync(~0u, unmark(b1 ? uz.y : uz.w), 2);
          float z = (b2 ? z1 : z0) + __shfl_xor_sync(~0u, b2 ? z0 : z1, 4);
          z += __shfl_xor_sync(~0u, z, 8);
          z += __shfl_xor_sync(~0u, z, 16);
          if (lane < 8) st_rlx(g_zres + own * 8 + (lane & 1) * 4 + (lane & 2) + (lane >> 2), mark(__float_as_uint(z), par));
          if (lane == 0) red_inc(g_xcnt + hg * 64 + 32 + R * 16);
          __syncwarp();
        }
        if (f == R || f == R + 1) {
          const uint32_t hf = f - R, m1 = ~lane & 1, gq = hf * 4 + (lane >> 3), ts = (lane >> 1) & 3;
          float a0 = 0.f, a1 = 0.f, a2 = 0.f, a3 = 0.f;
          mbar_wait(bar + B_PART + 8 * R, 0);
#pragma unroll 1
          for (int it = 0; it < SPIN_MAX; it++) {
            uint32_t bad = 0;
            a0 = a1 = a2 = a3 = 0.f;
#pragma unroll 1
            for (int b = 0; b < 16; b += 8) {
              uint2 u[8];
              if (it == 0) {
#pragma unroll
                for (int i = 0; i < 8; i++) { const float2 v = lds64(pst + (b + i) * 512 + hf * 256 + lane * 8); u[i] = make_uint2(__float_as_uint(v.x), __float_as_uint(v.y)); }
              } else {
#pragma unroll
                for (int i = 0; i < 8; i++) {
                  const unsigned long long v = ld_rlx64((const unsigned long long*)g_part + own * 1024 + (b + i) * 64 + hf * 32 + lane);
                  u[i] = make_uint2((uint32_t)v, (uint32_t)(v >> 32));
                }
              }
#pragma unroll
              for (int i = 0; i < 8; i++) {
                bad |= u[i].x ^ par;
                a0 += bf_lo(i & 1 ? u[i].x & ~m1 : u[i].x | m1); a1 += bf_hi(u[i].x); a2 += bf_lo(u[i].y); a3 += bf_hi(u[i].y);
              }
            }
            if (__all_sync(~0u, !(bad & m1))) break;
          }
          uint32_t* dst = (uint32_t*)g_res[par] + own * 128 + gq * 16 + ts;
          const uint32_t j0 = (lane & 1) * 2, vb = ts == 0;
          st_rlx(dst + ((j0 ^ (gq >> 1)) & 3) * 4, pack2(a0, a1) | vb);
          st_rlx(dst + (((j0 + 1) ^ (gq >> 1)) & 3) * 4, pack2(a2, a3) | vb);
          ((uint2*)g_res[par ^ 1])[own * 64 + hf * 32 + lane] = make_uint2(0u, 0u);
          __syncwarp();
          if (lane == 0) { red_inc(g_xcnt + hg * 64 + 32 + R * 16); if (!hf) PROF(R ? 12 : 30); }
        }
      }
      if (f == 2) {
        if (ffn && !FFN_OFF) {
#pragma unroll 1
          for (int it = 0; it < SPIN_MAX; it++) {
            const uint32_t pg = ld_rlx((const uint32_t*)g_gp + fb * 32 + lane), pu = ld_rlx((const uint32_t*)g_gp + FF + fb * 32 + lane);
            if (__all_sync(~0u, !(((pg ^ par) | (pu ^ par)) & 1))) { gsum += unmark(pg); usum += unmark(pu); break; }
            __nanosleep(200);
          }
        }
        const float h = bf_round(silu_f(bf_round(gsum))) * bf_round(usum);
        const uint32_t h2 = pack2(h, h);
        sts128u(sb + SM_HT + lane * 16, h2, h2, h2, h2);
        fence_async_smem();
        __syncwarp();
        if (lane == 0) { mbar_arrive(bar + B_H); PROF(20); }
      }
      if (f < 2) {
        wait_hint(g_xcnt + hg * 64 + 32 + f * 16, 3 * target);
        mbar_wait(bar + B_KVST + 8, 0);
        if (lane == 0) PROF(40 + f);
#pragma unroll 1
        for (int it = 0; it < SPIN_MAX; it++) {
          if (elect_one()) {
            fence_async_global();
            mbar_expect_tx(bar + B_RES + 8 * f, 8192);
            bulk_load(sb + SM_V + f * 8192, g_res[par] + (hg * 4 + f * 2) * 256, 8192, bar + B_RES + 8 * f);
          }
          __syncwarp();
          const uint4 uz = ld_rlx128(g_zres + (hg * 4 + f * 2) * 64 + lane * 4);
          const uint32_t zw[4] = {uz.x, uz.y, uz.z, uz.w};
#pragma unroll
          for (int j = 0; j < 4; j++) {
            const uint32_t zz = pack2(unmark(zw[j]), 1.f), row = (lane & 3) * 4 + j;
            sts128u(sb + SM_ZT + (2 * f + (lane >> 4)) * 1024 + row * 64 + ((((lane >> 2) ^ (row >> 1)) & 3) << 4), zz, zz, zz, zz);
          }
          uint32_t bad = BAD4(uz);
          mbar_wait(bar + B_RES + 8 * f, it & 1);
#pragma unroll
          for (int i = 0; i < 16; i++) bad |= ~__float_as_uint(lds32(sb + SM_V + f * 8192 + i * 512 + lane * 16));
          if (__all_sync(~0u, !(bad & 1))) break;
        }
        fence_async_smem();
        __syncwarp();
        if (lane == 0) { mbar_arrive(bar + B_TILE + 8 * f); PROF(f ? 13 : 27); }
      }
      if (f < 2) {
        uint32_t phases = 0;
#pragma unroll 1
        for (int i = 2; i < 16; i++) {
          const int s = i & 3;
          const uint32_t ab = bar + B_AIN + s * 16 + f * 8, slot = sb + s * Q_STAGE + f * 8192;
#pragma unroll 1
          for (int it = 0; it < SPIN_MAX; it++) {
            mbar_wait(ab, (phases >> s) & 1);
            phases ^= 1u << s;
            uint32_t bad = 0;
#pragma unroll
            for (int n = 0; n < (NOVAL ? 0 : 8); n++) bad |= __float_as_uint(lds32(slot + n * 1024 + lane * 32 + (lane >> 2) * 4)) ^ par;
            if (__all_sync(~0u, !(bad & 1))) break;
            if (elect_one()) {
              const int n = i < 9 ? i - 2 : i - 9, kb = 2 * (n + (n >= hg)) + (i >= 9);
              PROF(49);
              mbar_expect_tx(ab, 8192);
              bulk_load(slot, g_ofr + (mb * 16 + kb) * 1024 + f * 512, 8192, ab);
            }
            __syncwarp();
          }
          if (lane == 0) { mbar_arrive(bar + B_FULLQ + 8 * s); if (i == 2 && f == 0) PROF(15); }
        }
        if (f == 0) g_epoch[bid * 32 + lane] = tag;
      } else {
        if (elect_one()) {
          prefetch_map(&mOut);
          if (ffn) { mbar_wait(bar + B_YD, 0); red_rel(g_ycnt); PROF(21); }
        }
        __syncwarp();
        if (f == 2) {
          const uint32_t best = __float_as_uint(lds32(sb + SM_RED + 20));
          const int sel = 2047 - (best & 0x7ff) - mb * 128;
          if (sel >= 0 && sel < 128) {
            const uint2 xr = __ldg((const uint2*)(P.x + (size_t)(mb * 128 + sel) * DM + hg * 128 + lane * 4));
            const float2 st = lds64(sb + SM_STAT + sel * 8);
            const uint32_t ord = best >> 16, rb = (ord & 0x8000u) ? (ord & 0x7fffu) : (~ord & 0xffffu);
            const float sg = rcp(1.f + ex2(-1.4426950408889634f * bf_lo(rb)));
            const uint32_t sg2 = pack2(sg, sg), nm2 = pack2(st.x, st.x);
            wait_cnt<0>(g_ycnt, tag * NFFN);
            float4 y = make_float4(0.f, 0.f, 0.f, 0.f);
#pragma unroll
            for (int i = 0; i < 8; i++) {
              const float4 c = ldg_cg4(g_y[par ^ 1][i] + hg * 128 + lane * 4);
              y.x += c.x; y.y += c.y; y.z += c.z; y.w += c.w;
            }
            uint32_t o[2];
#pragma unroll
            for (int i = 0; i < 2; i++) {
              const uint32_t d = badd2(i ? xr.y : xr.x, nm2);
              const uint32_t tt = badd2(pack2(bf_lo(d) * st.y, bf_hi(d) * st.y), bmul2(i ? pack2(y.z, y.w) : pack2(y.x, y.y), sg2));
              o[i] = pack2(silu_f(bf_lo(tt)), silu_f(bf_hi(tt)));
            }
            sts64u(sb + SM_UPD + lane * 8, o[0], o[1]);
          }
          if (lane == 0) sts32(sb + SM_UPD + 256, __int_as_float(sel));
          __syncwarp();
          if (lane == 0) { mbar_arrive(bar + B_UPD); PROF(22); }
        }
      }
    }
  } else {
    const int t7 = threadIdx.x & 127;
    const char* pfa = warp < 4 ? (const char*)P.x + bid * 32768 + (t7 & 15) * 2048 + (t7 >> 4) * 128
                               : (const char*)P.wqkv + (size_t)((t7 >> 4) * 64 + (bid >> 1)) * 6144 + 2048 + (bid & 1) * 2048 + (t7 & 15) * 128;
    if (t7 >= 16 && t7 < 16 * PF_FIRST) prefetch_l2(pfa);
    if (warp < 7) sts128(sb + SM_CST + threadIdx.x * 16, 0.f, 0.f, 0.f, 0.f);
    else sts32(sb + SM_RED + (threadIdx.x & 15) * 4, threadIdx.x & 8 ? 1.f : 0.f);
    if (elect_one()) {
#pragma unroll 1
      for (uint32_t b = B_FST + warp * 8; b < B_END; b += 64)
        mbar_init(bar + b, b < B_FULLQ ? 1 : b < B_FFN ? 3 : b < B_EMPTYKV ? 4 : 8);
    }
    __syncwarp();
    asm volatile("bar.arrive 13, 384;" ::: "memory");
    asm volatile("setmaxnreg.inc.sync.aligned.u32 %0;" ::"n"(REG_C));
    if (t7 >= 16 * PF_FIRST && threadIdx.x < 128 + 16 * PF_W) prefetch_l2(pfa);
    asm volatile("cp.async.wait_all;" ::: "memory");
    fence_async_smem();
    bar_sync(14, 288);
    if (threadIdx.x == 0) mbar_arrive(bar + B_FULLKV + 16);
    const int lane = lane_id();
    const int wg = warp >> 2, w = warp & 3, g = lane >> 2, t = lane & 3;
    float kv[128];
    {
      uint32_t s = 2, ph = 0, sp = 0, php = 0;
#pragma unroll 1
      for (int j = 0; j < 15; j++) {
        PW0(32 + j); mbar_wait(bar + B_FULLKV + 8 * s, ph); PW1(32 + j);
        if (wg == 1 && (ORDER_ALL || j == 0)) bar_sync(10 + s, 256);
        wg_fence();
        wgmma_n256_ssp_ta0_tb1(kv, mkdesc(sb, 16, 1024, 1, wg * 512 + s * (KV_STAGE / 16)), mkdesc(sb + 16384, 8192, 1024, 1, s * (KV_STAGE / 16)), j);
#pragma unroll
        for (int k = 1; k < 4; k++)
          wgmma_n256_ss_ta0_tb1(kv, mkdesc(sb + k * 32, 16, 1024, 1, wg * 512 + s * (KV_STAGE / 16)),
                                mkdesc(sb + 16384 + k * 2048, 8192, 1024, 1, s * (KV_STAGE / 16)), 1);
        wg_commit();
        if (wg == 0 && (ORDER_ALL || j == 0)) asm volatile("bar.arrive %0, 256;" ::"r"(10 + s) : "memory");
        if (warp == 0 && j) {
          mbar_wait(bar + B_EMPTYKV + 8 * sp, php);
          if (elect_one()) {
            if (j < 14) {
              mbar_expect_tx(bar + B_FULLKV + 8 * sp, KV_STAGE);
              tma2d(sb + sp * KV_STAGE, &mX, (j + 2) * 64, mb * 128, bar + B_FULLKV + 8 * sp);
              tma4d(sb + sp * KV_STAGE + 16384, &mWkv, 0, (j + 2) * 64, hg * 2, 1, bar + B_FULLKV + 8 * sp);
            } else {
              Q_LOAD(0);
            }
            if (j < 3 - XS_EARLY) {
              const int xh = j - 1 + XS_EARLY;
              mbar_expect_tx(bar + B_XST + 8 * xh, 16384);
              tma3d(sb + SM_XST + xh * 16384, &mXs, 0, bid * 16, 2 * xh, bar + B_XST + 8 * xh);
            }
          }
          __syncwarp();
        }
        if (j == 0) {
          if (wg == 0) prefetch_l2(pfa + 1024);
        } else if (wg == 1) {
          if (j < 3) {
            if (j == 2 || t7 >= 16 * PF_W) prefetch_l2(pfa + (j - 1) * (8 * 393216));
          } else if (j == 13) {
            prefetch_l2((const char*)P.wo + bid * 16384 + t7 * 128);
          }
          if (PFG && !FFN_OFF && bid < NFFN && j >= 2 && j < 2 + GROWS / 64 && w < 2)
            touch_l2((const char*)((bid & 1) ? P.w_up : P.w_gate) + (size_t)((0x852a7419630ull >> (4 * j - 8) & 15) * 64 + t7) * 7168 + (bid >> 1) * 128, lane);
        }
        wg_wait<0>();
        if (lane == 0) mbar_arrive(bar + B_EMPTYKV + 8 * s);
        sp = s; php = ph;
        ph ^= s == 1;
        s = s == 2 ? 0 : s + 1;
      }
    }
    const int lrow = wg * 64 + w * 16 + (lane & 15);
    const uint32_t sw128 = lrow * 128, x128 = (lrow & 7), hi16 = lane >> 4;
    mbar_wait(bar + B_CS, 0);
    const uint32_t tag = __float_as_uint(lds32(sb + SM_RED + 16));
    const int zero = __float_as_int(lds32(sb + SM_RED + 12));
    const float wn = lds32(sb + SM_RED + 24);
    const float2 st0 = lds64(sb + SM_STAT + (wg * 64 + w * 16 + g) * 8), st1 = lds64(sb + SM_STAT + (wg * 64 + w * 16 + g + 8) * 8);
    const float c0 = st0.y * 1.4426950408889634f, c1 = st1.y * 1.4426950408889634f;
    const uint32_t nm20 = pack2(st0.x, st0.x), nm21 = pack2(st1.x, st1.x), fmask = t == 0 ? ~0u : t == 1 ? 0xffffu : 0u;
    const uint32_t fa0 = nm20 & fmask, fa1 = nm21 & fmask;
    asm volatile("cp.async.wait_all;" ::: "memory");
    PW0(47); mbar_wait(bar + B_FULLKV + 16, 1); PW1(47);
    wg_fence();
    wgmma_n256_rs_ta0_tb1(kv, fa0, fa1, 0u, 0u, mkdesc(sb + SM_CST, 512, 0, 1), 1);
#pragma unroll
    for (int k = 0; k < 4; k++)
      wgmma_n256_ss_ta0_tb1(kv, mkdesc(sb + 2 * KV_STAGE + k * 32, 16, 1024, 1, wg * 512), mkdesc(sb + 2 * KV_STAGE + 16384 + k * 2048, 8192, 1024, 1), 1);
    wg_commit();
    if (warp == 0) {
      mbar_wait(bar + B_EMPTYKV + 8, 0);
      if (elect_one()) {
#pragma unroll 1
        for (int j = 1; j < 3; j++) Q_LOAD(j);
      }
      __syncwarp();
    }
    wg_wait<0>();
    reg_fence<128>(kv);
    if (lane == 0) mbar_arrive(bar + B_EMPTYKV + 16);
    PROFC(2);
    float q[64];
#define QMMA(J, AOFF16, ACCUM)                                                                                     \
  _Pragma("unroll") for (int k = 0; k < 4; k++)                                                                    \
      wgmma_n128_ss_ta0_tb1(q, mkdesc(sb + k * 32, 16, 1024, 1, wg * 512 + (AOFF16)),                              \
                            mkdesc(sb + 16384 + k * 2048, 8192, 1024, 1, ((J) & 3) * (Q_STAGE / 16)), k ? 1 : (ACCUM))
#define QWAIT(J) do { PW0(J); mbar_wait(bar + B_FULLQ + 8 * ((J) & 3), ((J) >> 2) & 1); PW1(J); } while (0)
#define QSTEP_A(J, AOFF16, ACCUM) do { QWAIT(J); wg_fence(); QMMA(J, AOFF16, ACCUM); wg_commit(); } while (0)
#define QREL(J) do { if (lane == 0) mbar_arrive(bar + B_EMPTYQ + 8 * ((J) & 3)); } while (0)
#define Q_OFF16(J) ((J) >= 8 && (J) < 16 ? Q_AOFF(J) / 16 : ((J) & 3) * (Q_STAGE / 16))
#define QPLAIN(J) do { QSTEP_A(J, Q_OFF16(J), 1); wg_wait<1>(); QREL((J) - 1); } while (0)
#define QNEXT(J) do { QPLAIN(J); SCHED_FENCE(); } while (0)
#define PHI_PROJ(DST, SRC, H0, H1)                                                                                 \
  do {                                                                                                             \
    uint32_t a_[32];                                                                                               \
    _Pragma("unroll") for (int j = 8 * (H0); j < 8 * (H1); j++) {                                                  \
      a_[j] = pack2(SRC[2 * j], SRC[2 * j + 1]);                                                                   \
      asm volatile("fma.rn.bf16x2 %0, %1, %1, %0;" : "+r"(nq[(j >> 4) * 2 + (j & 1)]) : "r"(a_[j]));               \
    }                                                                                                              \
    wg_fence();                                                                                                    \
    _Pragma("unroll") for (int hk = 2 * (H0); hk < 2 * (H1); hk++)                                                 \
        wgmma_n32_rs_ta0_tb1(DST + 16 * (hk >> 1), a_[4 * hk], a_[4 * hk + 1], a_[4 * hk + 2], a_[4 * hk + 3],     \
                             mkdesc(sb + SM_WPHI + hk * 1024, 16, 512, 2), hk & 1);                                \
    wg_commit();                                                                                                   \
  } while (0)
    {
      float p[64], ea[24], eb[24], sa[4], sc[4], kz[20];
      uint32_t vp[32];
#pragma unroll
      for (int j = 0; j < 32; j++) vp[j] = pack2(kv[64 + 2 * j], kv[65 + 2 * j]);
      const uint32_t vr = w * 16 + (lane & 15), vb = sb + SM_V + wg * 4096 + vr * 64, x64 = (vr >> 1) & 3;
#define V_STORE(R)                                                                                           \
  _Pragma("unroll") for (int j = 0; j < 4; j++)                                                              \
      stsm4(vb + (j >> 1) * 8192 + ((((j & 1) * 2 + hi16) ^ x64) << 4), vp[16 * (R) + 4 * j], vp[16 * (R) + 4 * j + 1], vp[16 * (R) + 4 * j + 2], vp[16 * (R) + 4 * j + 3])
      V_STORE(0);
      mbar_wait(bar + B_WPHI, 0);
      {
        uint32_t nq[4] = {0u, 0u, 0u, 0u};
        PHI_PROJ(p, kv, 0, 4);
        QSTEP_A(0, 0, 0);
        const bool unsafe = softmax_unsafe(nq, c0 * c0 * wn, c1 * c1 * wn);
        wg_wait<1>();
        reg_fence<64>(p);
        if (__builtin_expect(unsafe, 0)) softmax_shift(p, c0, c1);
      }
#define K_NORM(S) do { quad_sum<4>(S); _Pragma("unroll") for (int i = 0; i < 4; i++) S[i] = rcp(S[i]) * ((i & 1) ? st1.y : st0.y); } while (0)
#define K_STORE(SLOT, E, S) K_STORE_(SLOT, E, S, 0, 2)
#define K_STORE_(SLOT, E, S, J0, J1)                                                                         \
  _Pragma("unroll") for (int j = (J0); j < (J1); j++) {                                                      \
    uint32_t fp[4], fm[4];                                                                                   \
    _Pragma("unroll") for (int i = 0; i < 4; i++) {                                                          \
      const float e0 = E[8 * j + 2 * i], e1 = E[8 * j + 2 * i + 1], r = E[16 + 4 * j + i] * S[2 + (i & 1)];  \
      const uint32_t e2 = pack2(e0, e1);                                                                     \
      fp[i] = bmul2(e2, pack2(S[i & 1], S[i & 1]));                                                          \
      fm[i] = bmul2(e2, pack2(r, r));                                                                        \
    }                                                                                                        \
    stsm4(sb + SM_PHI + (SLOT) * 16384 + sw128 + (((2 * j + hi16) ^ x128) << 4), fp[0], fp[1], fp[2], fp[3]); \
    stsm4(sb + SM_PHI + (SLOT) * 16384 + sw128 + (((4 + 2 * j + hi16) ^ x128) << 4), fm[0], fm[1], fm[2], fm[3]); \
  }
#define KV_MMA(R)                                                                                            \
  do {                                                                                                       \
    mbar_wait(bar + B_PHI + 8 * (R), 0);                                                                     \
    wg_fence();                                                                                              \
    _Pragma("unroll") for (int k = 0; k < 8; k++) {                                                          \
      const uint32_t vs = SM_V + (k >> 2) * 4096 + (k & 3) * 1024;                                           \
      wgmma_n40_ss_ta1_tb1(kz, mkdesc(sb + SM_PHI + k * 2048, 16, 1024, 1, wg * 1024),                       \
                           mkdesc(sb + vs, SM_SDT + (k & 1) * 1024 + (k >> 1) * 16 - vs, 512, 2, wg * (512u - (512u << 16))), k); \
    }                                                                                                        \
    wg_commit();                                                                                             \
  } while (0)
#define QKV(J, R) do { KV_MMA(R); QSTEP_A(J, Q_OFF16(J), 1); wg_wait<2>(); QREL((J) - 1); SCHED_FENCE(); } while (0)
#define KV_SEND(R)                                                                                           \
  do {                                                                                                       \
    reg_fence<20>(kz);                                                                                       \
    if (lane == 0) mbar_arrive(bar + B_KVST + 8 * (R));                                                      \
    const uint32_t slot = ((hg * 2 + (R)) * 16 + warp * 2) * 16 + mb;                                        \
    _Pragma("unroll") for (int u = 0; u < 2; u++)                                                            \
      st_rlx128(g_part + (slot + u * 16) * 32 + lane, mark(pack2(kz[2 * u], kz[2 * u + 1]), tag & 1), pack2(kz[2 * u + 4], kz[2 * u + 5]), \
                pack2(kz[2 * u + 8], kz[2 * u + 9]), pack2(kz[2 * u + 12], kz[2 * u + 13]));                 \
    if (t < 2) st_rlx(g_zpart + (slot + t * 16) * 8 + g, mark(__float_as_uint(t ? kz[18] : kz[16]), tag & 1)); \
    if (lane < 2) red_inc(g_xcnt + hg * 64 + (R) * 16 + warp * 2 + lane);                                    \
  } while (0)
#define K_PUB(R) do { fence_async_smem(); __syncwarp(); if (lane == 0) mbar_arrive(bar + B_PHI + 8 * (R)); } while (0)
#define S_PIN(S) SCHED_PIN(S[0] + S[1] + S[2] + S[3])
      k_exp(p, c0, c1, ea, sa);
      S_PIN(sa);
      QNEXT(1);
      K_NORM(sa);
      k_exp<0, 4>(p + 16, c0, c1, eb, sc);
      mbar_wait(bar + B_FFN, 0);
      K_STORE_(0, ea, sa, 0, 1);
      S_PIN(sc);
      QNEXT(2);
      K_STORE_(0, ea, sa, 1, 2);
      k_exp<4, 8>(p + 16, c0, c1, eb, sc);
      K_NORM(sc);
      S_PIN(sc);
      QNEXT(3);
      K_STORE(1, eb, sc);
      K_PUB(0);
      k_exp<0, 4>(p + 32, c0, c1, ea, sa);
      S_PIN(sa);
      QKV(4, 0);
      k_exp<4, 8>(p + 32, c0, c1, ea, sa);
      K_NORM(sa);
      k_exp<0, 4>(p + 48, c0, c1, eb, sc);
      SCHED_PIN(sa[0] + sa[1] + sa[2] + sa[3] + sc[2] + sc[3]);
      QNEXT(5);
      KV_SEND(0);
      k_exp<4, 8>(p + 48, c0, c1, eb, sc);
      S_PIN(sc);
      QNEXT(6);
      K_NORM(sc);
      mbar_wait(bar + B_KVST, 0);
      V_STORE(1);
      K_STORE(0, ea, sa);
      QNEXT(7);
      K_STORE(1, eb, sc);
      K_PUB(1);
      QKV(8, 1);
      QNEXT(9);
      KV_SEND(1);
    }
#define JQ0 10
    PROFC(3);
#pragma unroll 1
    for (int j = JQ0; j < 15; j++) QPLAIN(j);
    mbar_wait(bar + B_CSQ, 0);
    QWAIT(15);
    if (wg == 1) bar_sync(6, 256);
    wg_fence();
    wgmma_n128_rs_ta0_tb1(q, fa0, fa1, 0u, 0u, mkdesc(sb + SM_CST + 2048, 512, 0, 1), 1);
    QMMA(15, Q_AOFF(15) / 16, 1);
    wg_commit();
    if (wg == 0) asm volatile("bar.arrive 6, 256;" ::: "memory");
    wg_wait<1>();
    QREL(14);
    wg_wait<0>();
    QREL(15);
    reg_fence<64>(q);
    PROFC(5);
    float yp[4];
    const uint32_t par = tag & 1;
    uint4* ofr = g_ofr + (mb * 16 + hg * 2) * 1024 + (warp * 16 + g) * 8;
#define O_MMA(H, F, N)                                                                                       \
  do {                                                                                                       \
    wg_fence();                                                                                              \
    _Pragma("unroll") for (int k = 0; k < 4; k++) {                                                          \
      const uint32_t ks = SM_V + (H) * 4096 + k * 1024;                                                      \
      wgmma_n40_rs_ta0_tb1(N + 20 * (k >> 1), F[4 * k], F[4 * k + 1], F[4 * k + 2], F[4 * k + 3],            \
                           mkdesc(sb + ks, SM_ZT + (H) * 1024 + k * 16 - ks, 512, 2), k & 1);                \
    }                                                                                                        \
    wg_commit();                                                                                             \
  } while (0)
#define O_FIN(H, N, o)                                                                                        \
  do {                                                                                                       \
    reg_fence<40>(N);                                                                                        \
    const float *np = N, *nm = N + 20;                                                                       \
    const float d0 = rcp(fmaf(np[16], nm[17], fmaf(nm[16], np[17], 1e-6f * np[17] * nm[17])));               \
    const float d1 = rcp(fmaf(np[18], nm[19], fmaf(nm[18], np[19], 1e-6f * np[19] * nm[19])));               \
    const float bp0 = nm[17] * d0, bm0 = np[17] * d0, bp1 = nm[19] * d1, bm1 = np[19] * d1;                  \
    _Pragma("unroll") for (int j = 0; j < 4; j++) {                                                          \
      o[2 * j] = pack2(fmaf(np[4 * j], bp0, nm[4 * j] * bm0), fmaf(np[4 * j + 1], bp0, nm[4 * j + 1] * bm0)); \
      o[2 * j + 1] = pack2(fmaf(np[4 * j + 2], bp1, nm[4 * j + 2] * bm1), fmaf(np[4 * j + 3], bp1, nm[4 * j + 3] * bm1)); \
    }                                                                                                        \
  } while (0)
#define O_STG(H, o)                                                                                          \
  _Pragma("unroll") for (int u = 0; u < 2; u++) {                                                            \
    uint32_t v_[4];                                                                                          \
    _Pragma("unroll") for (int j = 0; j < 4; j++) v_[j] = lop_select(o[2 * j + u], parm, vword == j);        \
    st_rlx128(ofr + ((H) >> 1) * 1024 + u * 64 + ((((H) & 1) * 4 + t) ^ g), v_[0], v_[1], v_[2], v_[3]);     \
  }
    uint32_t gf[32], ao[16];
    const uint32_t parm = 0u - par, vword = ((t ^ g) & 1) == (g >> 2) ? g & 3 : 4;
    const float rh0 = 0.5f * st0.y, rh1 = 0.5f * st1.y, mh0 = st0.x * rh0, mh1 = st1.x * rh1;
#define GATE_LD(J) ldsm4(sb + ((J) >> 2 ? SM_X1 : SM_X0) + sw128 + (((((J) & 3) * 2 + hi16) ^ x128) << 4), gf[4 * (J)], gf[4 * (J) + 1], gf[4 * (J) + 2], gf[4 * (J) + 3])
#define GATE(I0, I1)                                                                                         \
  _Pragma("unroll") for (int i = (I0); i < (I1); i++) {                                                      \
    const float rs = (i & 1) ? rh1 : rh0, mh = (i & 1) ? mh1 : mh0;                                          \
    const float h0 = fmaf(bf_lo(gf[i]), rs, mh), h1 = fmaf(bf_hi(gf[i]), rs, mh);                            \
    gf[i] = pack2(fmaf(h0, tanh_approx(h0), h0), fmaf(h1, tanh_approx(h1), h1));                             \
  }
#define GATE_PIN(I0, I1) do { uint32_t o_ = 0; _Pragma("unroll") for (int i = (I0); i < (I1); i++) o_ |= gf[i]; SCHED_PIN(__uint_as_float(o_)); } while (0)
    {
      float p[64], na[40], nb[40];
      uint32_t fa[16], fb[16];
      {
        uint32_t nq[4] = {0u, 0u, 0u, 0u};
        PHI_PROJ(p, q, 0, 2);
        SCHED_FENCE();
        PHI_PROJ(p, q, 2, 4);
        const bool unsafe = softmax_unsafe(nq, c0 * c0 * wn, c1 * c1 * wn);
        if (TW == 0) mbar_wait(bar + B_TILE, 0);
        wg_wait<0>();
        reg_fence<64>(p);
        PROFC(24);
        if (__builtin_expect(unsafe, 0)) softmax_shift(p, c0, c1);
      }
      float dn[32];
#define DN_PART(A, B)                                                                                        \
  do {                                                                                                       \
    wg_fence();                                                                                              \
    _Pragma("unroll") for (int i = (A); i < (B); i++)                                                        \
      wgmma_n8_ss_ta1_tb1(dn + 4 * (i >> 1), mkdesc(sb + (i >> 3) * Q_STAGE + (i & 7) * 2048, 16, 1024, 1, wg * (2 * Q_STAGE / 16)), \
                          mkdesc(sb + SM_HT + (i & 1) * 256, 128, 128, 0), i & 1);                           \
  } while (0)
#define F_PIN(F, A, B) do { uint32_t o_ = 0; _Pragma("unroll") for (int i = (A); i < (B); i++) o_ |= F[8 + i]; SCHED_PIN(__uint_as_float(o_)); } while (0)
#define RMMA(J, A, ACCUM)                                                                                    \
  do {                                                                                                       \
    wg_fence();                                                                                              \
    _Pragma("unroll") for (int k = 0; k < 4; k++)                                                            \
      wgmma_n128_rs_ta0_tb1(q, (A)[4 * k], (A)[4 * k + 1], (A)[4 * k + 2], (A)[4 * k + 3],                   \
                            mkdesc(sb + 16384 + k * 2048, 8192, 1024, 1, ((J) & 3) * (Q_STAGE / 16)), k ? 1 : (ACCUM)); \
    wg_commit();                                                                                             \
  } while (0)
#define RSTEP(J, A, ACCUM) do { QWAIT(J); RMMA(J, A, ACCUM); } while (0)
      PROFC(4);
      q_exp(p, c0, c1, fa);
      if (TW == 1) { F_PIN(fa, 0, 8); mbar_wait(bar + B_TILE, 0); }
      if (TW == 2) { q_exp(p + 16, c0, c1, fb); F_PIN(fb, 0, 8); mbar_wait(bar + B_TILE, 0); }
      O_MMA(0, fa, na);
      if (TW != 2) q_exp(p + 16, c0, c1, fb);
      O_MMA(1, fb, nb);
      PROFC(25);
      wg_wait<1>();
      O_FIN(0, na, ao);
      O_STG(0, ao);
      wg_wait<0>();
      O_FIN(1, nb, (ao + 8));
      O_STG(1, (ao + 8));
      PROFC(28);
      RSTEP(16, ao, 0);
      SCHED_FENCE();
      q_exp(p + 32, c0, c1, fa);
      F_PIN(fa, 0, 8);
      mbar_wait(bar + B_H, 0);
      mbar_wait(bar + B_DN, 0);
      PROFC(45);
      DN_PART(0, 4);
      SCHED_FENCE();
      q_exp<0, 2>(p + 48, c0, c1, fb);
      F_PIN(fb, 0, 2);
      DN_PART(4, 8);
      SCHED_FENCE();
      q_exp<2, 4>(p + 48, c0, c1, fb);
      F_PIN(fb, 2, 4);
      DN_PART(8, 12);
      SCHED_FENCE();
      q_exp<4, 6>(p + 48, c0, c1, fb);
      F_PIN(fb, 4, 6);
      DN_PART(12, 16);
      wg_commit();
      SCHED_FENCE();
      q_exp<6, 8>(p + 48, c0, c1, fb);
      F_PIN(fb, 6, 8);
      wg_wait<0>();
      reg_fence<32>(dn);
      if (lane == 0) mbar_arrive(bar + B_DND);
      QREL(16);
#pragma unroll
      for (int i = 0; i < 4; i++) yp[i] = t & 2 ? (t & 1 ? dn[24 + 2 * i] : dn[16 + 2 * i]) : (t & 1 ? dn[8 + 2 * i] : dn[2 * i]);
      PROFC(29);
      mbar_wait(bar + B_TILE + 8, 0);
      PROFC(23);
      if (bid < NFFN) {
        float* y = g_y[par ^ 1][bid & 7] + wg * 512 + t * 128 + w * 16 + g;
#pragma unroll
        for (int i = 0; i < 4; i++) red1(y + (i >> 1) * 64 + (i & 1) * 8, yp[i]);
      }
      SCHED_FENCE();
      O_MMA(2, fa, na);
      O_MMA(3, fb, nb);
      __syncwarp();
      if (lane == 0) mbar_arrive(bar + B_YD);
      wg_wait<1>();
      O_FIN(2, na, ao);
      O_STG(2, ao);
      wg_wait<0>();
      O_FIN(3, nb, (ao + 8));
      O_STG(3, (ao + 8));
      PROFC(6);
    }
    RSTEP(17, ao, 1);
    SCHED_FENCE();
    GATE_LD(0); GATE_LD(1);
    GATE(0, 4);
    GATE_PIN(0, 4);
#define GSTEP(J, I) do { QNEXT(J); if ((I) < 7) GATE_LD(((I) + 1) & 7); GATE(4 * (I), 4 * (I) + 4); GATE_PIN(4 * (I), 4 * (I) + 4); } while (0)
    GSTEP(18, 1); GSTEP(19, 2); GSTEP(20, 3); GSTEP(21, 4); GSTEP(22, 5); GSTEP(23, 6); GSTEP(24, 7);
#pragma unroll 1
    for (int j = 25; j < 32 - TAILN; j++) QPLAIN(j);
    if (wg == 1) bar_sync(6, 256);
#pragma unroll 1
    for (int j = 32 - TAILN; j < 32; j++) QSTEP_A(j, (j & 3) * (Q_STAGE / 16), 1);
    if (wg == 0) asm volatile("bar.arrive 6, 256;" ::: "memory");
    mbar_wait(bar + B_UPD, 0);
    {
      const int sel = __float_as_int(lds32(sb + SM_UPD + 256)) - (wg * 64 + w * 16 + g);
      if (sel == 0 || sel == 8) {
#pragma unroll
        for (int j = 0; j < 16; j++) {
          const uint32_t u = __float_as_uint(lds32(sb + SM_UPD + j * 16 + t * 4));
          if (sel) gf[2 * j + 1] = u; else gf[2 * j] = u;
        }
      }
      __syncwarp();
      uint32_t xf[32];
#pragma unroll
      for (int j = 0; j < 8; j++)
        ldsm4(sb + (j >> 2 ? SM_X1 : SM_X0) + sw128 + ((((j & 3) * 2 + hi16) ^ x128) << 4), xf[4 * j], xf[4 * j + 1], xf[4 * j + 2], xf[4 * j + 3]);
      wg_wait<0>();
      reg_fence<64>(q);
      PROFC(8);
#pragma unroll
      for (int j = 0; j < 8; j++) {
        uint32_t o[4];
#pragma unroll
        for (int i = 0; i < 4; i++) o[i] = badd2(xf[4 * j + i], bmul2(pack2(q[8 * j + 2 * i], q[8 * j + 2 * i + 1]), gf[4 * j + i]));
        stsm4(sb + (j >> 2 ? SM_X1 : SM_X0) + sw128 + ((((j & 3) * 2 + hi16) ^ x128) << 4), o[0], o[1], o[2], o[3]);
      }
    }
    fence_async_smem();
    bar_sync(2 + wg, 128);
    if (w == 0 && elect_one()) {
      tma_store2d(&mOut, sb + SM_X0 + wg * 8192, hg * 128, mb * 128 + wg * 64);
      tma_store2d(&mOut, sb + SM_X1 + wg * 8192, hg * 128 + 64, mb * 128 + wg * 64);
      bulk_commit();
      bulk_wait_read0();
      if (wg == 1) { PROF(9); PROFT(33); PROF_DUMP; }
    }
  }
}

typedef CUresult (*EncodeFn)(CUtensorMap*, CUtensorMapDataType, cuuint32_t, void*, const cuuint64_t*, const cuuint64_t*, const cuuint32_t*,
                             const cuuint32_t*, CUtensorMapInterleave, CUtensorMapSwizzle, CUtensorMapL2promotion, CUtensorMapFloatOOBfill);

CUtensorMap make_map(EncodeFn enc, const void* ptr, int rank, const cuuint64_t* dims, const cuuint64_t* strides, const cuuint32_t* box, CUtensorMapSwizzle sw) {
  CUtensorMap m;
  const cuuint32_t es[5] = {1, 1, 1, 1, 1};
  enc(&m, CU_TENSOR_MAP_DATA_TYPE_BFLOAT16, rank, (void*)ptr, dims, strides, box, es, CU_TENSOR_MAP_INTERLEAVE_NONE, sw,
      CU_TENSOR_MAP_L2_PROMOTION_L2_128B, CU_TENSOR_MAP_FLOAT_OOB_FILL_NONE);
  return m;
}

}

extern "C" void kernel_launch(void* const* d_in, const int* in_sizes, int n_in, void* d_out, int out_size) {
  static EncodeFn enc = nullptr;
  static int by_sm = 0;
  if (!enc) {
    void* fn = nullptr;
    cudaDriverEntryPointQueryResult qr;
    cudaGetDriverEntryPoint("cuTensorMapEncodeTiled", &fn, cudaEnableDefault, &qr);
    enc = (EncodeFn)fn;
    cudaFuncSetAttribute(fused_kernel<false>, cudaFuncAttributeMaxDynamicSharedMemorySize, SM_TOTAL);
    cudaFuncSetAttribute(fused_kernel<true>, cudaFuncAttributeMaxDynamicSharedMemorySize, SM_TOTAL);
    int dev = 0, sms = 0;
    cudaGetDevice(&dev);
    cudaDeviceGetAttribute(&sms, cudaDevAttrMultiProcessorCount, dev);
    by_sm = BY_SM && sms == NCTA + NSPARE;
  }
  Params P;
  P.x = (const __nv_bfloat16*)d_in[0];
  P.wqkv = (const __nv_bfloat16*)d_in[1];
  const void* wphi = d_in[2];
  P.wo = (const __nv_bfloat16*)d_in[3];
  P.w_r = (const __nv_bfloat16*)d_in[5];
  P.w_gate = (const __nv_bfloat16*)d_in[6];
  P.w_up = (const __nv_bfloat16*)d_in[7];
  P.w_down = (const __nv_bfloat16*)d_in[8];

  const cuuint64_t dX[2] = {DM, SEQ}, sX[1] = {DM * 2};
  const cuuint32_t b128[2] = {64, 128}, b64[2] = {64, 64};
  const cuuint64_t dW[4] = {64, DM, 16, 3}, sW[3] = {3 * DM * 2, 128, DM * 2};
  const cuuint32_t bKV[4] = {64, 64, 2, 2}, bQ[4] = {64, 64, 2, 1};
  const cuuint64_t dO[3] = {64, DM, 16}, sO[2] = {DM * 2, 128};
  const cuuint32_t bO[3] = {64, 64, 2};
  const cuuint64_t dP[2] = {32, 1024}, sP[1] = {64};
  const cuuint32_t bP[2] = {32, 128};
  CUtensorMap mX = make_map(enc, P.x, 2, dX, sX, b128, CU_TENSOR_MAP_SWIZZLE_128B);
  CUtensorMap mWkv = make_map(enc, P.wqkv, 4, dW, sW, bKV, CU_TENSOR_MAP_SWIZZLE_128B);
  CUtensorMap mWq = make_map(enc, P.wqkv, 4, dW, sW, bQ, CU_TENSOR_MAP_SWIZZLE_128B);
  CUtensorMap mWo = make_map(enc, P.wo, 3, dO, sO, bO, CU_TENSOR_MAP_SWIZZLE_128B);
  CUtensorMap mPhi = make_map(enc, wphi, 2, dP, sP, bP, CU_TENSOR_MAP_SWIZZLE_64B);
  const cuuint64_t dWp[5] = {DM, 2, 4, 4, DM / 32}, sWp[4] = {DM * 2, 8 * DM * 2, 2 * DM * 2, 32 * DM * 2};
  const cuuint32_t bWp[5] = {64, 2, 4, 4, 2};
  CUtensorMap mWp = make_map(enc, P.wo, 5, dWp, sWp, bWp, CU_TENSOR_MAP_SWIZZLE_128B);
  CUtensorMap mOut = make_map(enc, d_out, 2, dX, sX, b64, CU_TENSOR_MAP_SWIZZLE_128B);
  const cuuint64_t dWc[2] = {3 * DM, DM}, sWc[1] = {3 * DM * 2}, dG[2] = {FF, DM}, sG[1] = {FF * 2}, dD[3] = {64, FF, 16};
  const cuuint32_t b32[2] = {32, 32}, bD[3] = {64, 32, 4};
  CUtensorMap mWc = make_map(enc, P.wqkv, 2, dWc, sWc, b32, CU_TENSOR_MAP_SWIZZLE_NONE);
  CUtensorMap mG = make_map(enc, P.w_gate, 2, dG, sG, b32, CU_TENSOR_MAP_SWIZZLE_NONE);
  CUtensorMap mU = make_map(enc, P.w_up, 2, dG, sG, b32, CU_TENSOR_MAP_SWIZZLE_NONE);
  CUtensorMap mD = make_map(enc, P.w_down, 3, dD, sO, bD, CU_TENSOR_MAP_SWIZZLE_128B);
  const cuuint64_t dXs[3] = {256, SEQ, 4}, sXs[2] = {DM * 2, 512};
  const cuuint32_t bXs[3] = {256, 16, 2};
  CUtensorMap mXs = make_map(enc, P.x, 3, dXs, sXs, bXs, CU_TENSOR_MAP_SWIZZLE_NONE);
  const cuuint64_t dG2[4] = {64, DM, FF / 64, 1}, sG2[3] = {FF * 2, 128, (cuuint64_t)FF * DM * 2};
  CUtensorMap mG2 = make_map(enc, P.w_gate, 4, dG2, sG2, bQ, CU_TENSOR_MAP_SWIZZLE_128B);
  CUtensorMap mU2 = make_map(enc, P.w_up, 4, dG2, sG2, bQ, CU_TENSOR_MAP_SWIZZLE_128B);
  (by_sm ? fused_kernel<true> : fused_kernel<false>)<<<NCTA + NSPARE, 384, SM_TOTAL, cudaStreamPerThread>>>(mX, mWkv, mWq, mWo, mPhi, mWp, mOut, mWc, mG, mU, mD, mXs,
                                                                                                           mG2, mU2, P);
}
```

```cpp
#include <cuda_runtime.h>
#include <cuda_bf16.h>
#include <cuda.h>
#include <stdint.h>

namespace {

constexpr int SEQ = 2048, DM = 1024, FF = 3584;
constexpr int NCTA = 128;
constexpr int NSPARE = 4;
constexpr int NFFN = FF / 32;
#define GN 6
#define G8 2
constexpr int GROWS = (3 * GN + G8) * 32;
#define TAILN 2
#define KTAIL 1
#define XS_EARLY 1
#define PF_FIRST 2
#define PF_W 5
#define PF_PRE 1
#define PFG 0
#define PFD 80
#define BY_SM 1
#define PTAB 0x73216540u
#define ROWSPLIT 1
#define WOT 1
#define PSPLIT 1
#define KSTEPS 4
#define NOVAL 0
#define KCH 1
#define REG_C 224
#define REG_H 56
#define TW 2
#define FENCE_KIND 2
#define SP_DELAY 2000
#define HOP2_HINT 1
#define ORDER_ALL 1
#define AM_NS 100
constexpr bool FFN_OFF = false;

static_assert(2 * REG_C + REG_H <= 3 * 168, "the register pool of the CTA is 384 x 168");

__device__ uint32_t g_epoch[(NCTA + NSPARE) * 32];
__device__ unsigned long long g_stat[SEQ];
__device__ __align__(128) unsigned long long g_best[NCTA];
__device__ __align__(16) float g_y[2][8][DM];
__device__ __align__(128) uint32_t g_ycnt[64];
__device__ __align__(128) uint32_t g_xcnt[8 * 64];
__device__ __align__(128) uint4 g_res[2][32 * 256];
__device__ __align__(16) float g_cs[5 * DM];
__device__ __align__(128) float g_gp[2 * FF];
__device__ uint4 g_part[8 * 2 * 16 * 16 * 32];
__device__ __align__(16) float g_zpart[8 * 2 * 16 * 16 * 8];
__device__ __align__(128) float g_zres[32 * 64];
__device__ __align__(1024) uint4 g_ofr[16 * 16 * 1024];
#define PROF(i)
#define PROFT(i)
#define PROFC(i)
#define PROF_DUMP
#define PW0(J)
#define PW1(J)

constexpr uint32_t KV_STAGE = 49152, Q_STAGE = 32768;
constexpr uint32_t SM_V = 147456;
constexpr uint32_t SM_PHI = 163840;
constexpr uint32_t SM_XST = 147456;
constexpr uint32_t SM_FST = 172032;
constexpr uint32_t SM_PST0 = 196608, SM_PST1 = SM_PHI + 8192;
constexpr uint32_t SM_X0 = 131072, SM_X1 = SM_PHI + 16384;
constexpr uint32_t SM_WPHI = 204800;
constexpr uint32_t SM_ZT = 212992;
constexpr uint32_t SM_SDT = 217088;
constexpr uint32_t SM_CST = 219136;
constexpr uint32_t SM_HT = 222720;
constexpr uint32_t SM_STAT = 223232;
constexpr uint32_t SM_XSEL = 224256;
constexpr uint32_t SM_RED = 228352;
constexpr uint32_t SM_ROWS = SM_RED + 832;
constexpr uint32_t SM_GRED = SM_XSEL + 3072;
static_assert(GROWS <= 768, "xsel area");
constexpr uint32_t SM_UPD = 229632;
constexpr uint32_t SM_BAR = 230016;
constexpr uint32_t SM_PROF = 230464;
constexpr uint32_t SM_SINK = 231104;
constexpr uint32_t SM_TOTAL = 231616;
constexpr uint32_t SB = 1024;
constexpr uint32_t B_FULLKV = 0  , B_FST = 24  , B_XFULL = 88  , B_XST = 104  , B_WPHI = 120, B_CS = 128, B_CSQ = 136, B_UPD = 144,
                   B_H = 152, B_DN = 160, B_XS = 168, B_TILE = 176  , B_RES = 192  , B_PART = 208  ,
B_AIN = 224  ,
                   B_FULLQ = 288  ,
                   B_FFN = 320,
                   B_EMPTYKV = 328  , B_EMPTYQ = 352  , B_KVST = 384  , B_YD = 400, B_PHI = 408  , B_DND = 424, B_END = 432;

__device__ __forceinline__ uint32_t smem_u32(const void* p) { return (uint32_t)__cvta_generic_to_shared(p); }
__device__ __forceinline__ void mbar_init(uint32_t bar, uint32_t cnt) { asm volatile("mbarrier.init.shared::cta.b64 [%0], %1;" ::"r"(bar), "r"(cnt) : "memory"); }
__device__ __forceinline__ void mbar_expect_tx(uint32_t bar, uint32_t bytes) { asm volatile("mbarrier.arrive.expect_tx.shared::cta.b64 _, [%0], %1;" ::"r"(bar), "r"(bytes) : "memory"); }
__device__ __forceinline__ void mbar_arrive2(uint32_t bar) { asm volatile("mbarrier.arrive.shared::cta.b64 _, [%0], 2;" ::"r"(bar) : "memory"); }
__device__ __forceinline__ void mbar_arrive(uint32_t bar) { asm volatile("mbarrier.arrive.shared::cta.b64 _, [%0];" ::"r"(bar) : "memory"); }
__device__ __forceinline__ void mbar_wait(uint32_t bar, uint32_t parity) {
  asm volatile("{\n.reg .pred p;\nLW:\nmbarrier.try_wait.parity.shared::cta.b64 p, [%0], %1;\n@!p bra LW;\n}" ::"r"(bar), "r"(parity) : "memory");
}
__device__ __forceinline__ bool mbar_test(uint32_t bar, uint32_t parity) {
  uint32_t ok;
  asm volatile("{\n.reg .pred p;\nmbarrier.test_wait.parity.shared::cta.b64 p, [%1], %2;\nselp.u32 %0, 1, 0, p;\n}" : "=r"(ok) : "r"(bar), "r"(parity) : "memory");
  return ok;
}
__device__ __forceinline__ int lane_id() { int l; asm volatile("mov.u32 %0, %%laneid;" : "=r"(l)); return l; }
template <int C> __device__ __forceinline__ void sched_fence_(int zero) {
  asm volatile("{\n.reg .pred p;\nsetp.eq.s32 p, %0, %1;\n@p trap;\n}" ::"r"(zero), "n"(C) : "memory");
}
#define SCHED_FENCE() sched_fence_<1000 + __COUNTER__>(zero)
#define SCHED_PIN(V) sched_fence_<1000 + __COUNTER__>(zero & __float_as_int(V))
__device__ __forceinline__ bool elect_one() {
  uint32_t p; asm volatile("{ .reg .pred P; elect.sync _|P, 0xffffffff; selp.u32 %0, 1, 0, P; }" : "=r"(p)); return p;
}
__device__ __forceinline__ void tma2d(uint32_t dst, const CUtensorMap* m, int x, int y, uint32_t bar) {
  asm volatile("cp.async.bulk.tensor.2d.shared::cluster.global.mbarrier::complete_tx::bytes [%0], [%1, {%3, %4}], [%2];" ::"r"(dst), "l"(m), "r"(bar), "r"(x), "r"(y) : "memory");
}
__device__ __forceinline__ void tma3d(uint32_t dst, const CUtensorMap* m, int x, int y, int z, uint32_t bar) {
  asm volatile("cp.async.bulk.tensor.3d.shared::cluster.global.mbarrier::complete_tx::bytes [%0], [%1, {%3, %4, %5}], [%2];" ::"r"(dst), "l"(m), "r"(bar), "r"(x), "r"(y), "r"(z) : "memory");
}
__device__ __forceinline__ void tma4d(uint32_t dst, const CUtensorMap* m, int x, int y, int z, int w, uint32_t bar) {
  asm volatile("cp.async.bulk.tensor.4d.shared::cluster.global.mbarrier::complete_tx::bytes [%0], [%1, {%3, %4, %5, %6}], [%2];" ::"r"(dst), "l"(m), "r"(bar), "r"(x), "r"(y), "r"(z), "r"(w) : "memory");
}
__device__ __forceinline__ void tma5d(uint32_t dst, const CUtensorMap* m, int x, int v, uint32_t bar) {
  asm volatile("cp.async.bulk.tensor.5d.shared::cluster.global.mbarrier::complete_tx::bytes [%0], [%1, {%3, %5, %5, %5, %4}], [%2];" ::"r"(dst), "l"(m), "r"(bar), "r"(x), "r"(v), "r"(0) : "memory");
}
__device__ __forceinline__ void tma_store2d(const CUtensorMap* m, uint32_t src, int x, int y) {
  asm volatile("cp.async.bulk.tensor.2d.global.shared::cta.bulk_group [%0, {%2, %3}], [%1];" ::"l"(m), "r"(src), "r"(x), "r"(y) : "memory");
}
__device__ __forceinline__ void bulk_load(uint32_t dst, const void* src, uint32_t bytes, uint32_t bar) {
  asm volatile("cp.async.bulk.shared::cluster.global.mbarrier::complete_tx::bytes [%0], [%1], %2, [%3];" ::"r"(dst), "l"(src), "r"(bytes), "r"(bar) : "memory");
}
__device__ __forceinline__ void bulk_commit() { asm volatile("cp.async.bulk.commit_group;" ::: "memory"); }
__device__ __forceinline__ void bulk_wait0() { asm volatile("cp.async.bulk.wait_group 0;" ::: "memory"); }
__device__ __forceinline__ void bulk_wait_read0() { asm volatile("cp.async.bulk.wait_group.read 0;" ::: "memory"); }
__device__ __forceinline__ void prefetch_l2(const void* p) { asm volatile("prefetch.global.L2 [%0];" ::"l"(p) : "memory"); }
__device__ __forceinline__ void touch_l2(const void* p, int lane) { asm volatile("cp.async.cg.shared.global.L2::128B [%0], [%1], 16;" ::"r"(SB + SM_SINK + lane * 16), "l"(p) : "memory"); }
__device__ __forceinline__ void cp_async16(uint32_t dst, const void* src) { asm volatile("cp.async.cg.shared.global [%0], [%1], 16;" ::"r"(dst), "l"(src) : "memory"); }
__device__ __forceinline__ void prefetch_map(const CUtensorMap* m) { asm volatile("prefetch.tensormap [%0];" ::"l"(m) : "memory"); }
__device__ __forceinline__ void fence_async_smem() { asm volatile("fence.proxy.async.shared::cta;" ::: "memory"); }
__device__ __forceinline__ void fence_async_global() { asm volatile("fence.proxy.async.global;" ::: "memory"); }
__device__ __forceinline__ void bar_sync(int id, int n) { asm volatile("bar.sync %0, %1;" ::"r"(id), "r"(n) : "memory"); }
__device__ __forceinline__ void wg_fence() { asm volatile("wgmma.fence.sync.aligned;" ::: "memory"); }
__device__ __forceinline__ void wg_commit() { asm volatile("wgmma.commit_group.sync.aligned;" ::: "memory"); }
template <int N> __device__ __forceinline__ void wg_wait() { asm volatile("wgmma.wait_group.sync.aligned %0;" ::"n"(N) : "memory"); }
template <int N> __device__ __forceinline__ void reg_fence(uint32_t* r) {
#pragma unroll
  for (int i = 0; i < N; i++) asm volatile("" : "+r"(r[i])::"memory");
}
template <int N> __device__ __forceinline__ void reg_fence(float* r) {
#pragma unroll
  for (int i = 0; i < N; i++) asm volatile("" : "+f"(r[i])::"memory");
}
__device__ __forceinline__ uint64_t mkdesc(uint32_t addr, uint32_t lbo, uint32_t sbo, uint32_t swz, uint32_t dyn = 0) {
  const uint32_t lo = ((addr >> 4) | ((lbo >> 4) << 16)) + dyn;
  const uint32_t hi = (sbo >> 4) | (swz << 30);
  uint64_t d;
  asm("mov.b64 %0, {%1, %2};" : "=l"(d) : "r"(lo), "r"(hi));
  return d;
}
__device__ __forceinline__ void stsm4(uint32_t addr, uint32_t a, uint32_t b, uint32_t c, uint32_t d) {
  asm volatile("stmatrix.sync.aligned.m8n8.x4.shared.b16 [%0], {%1, %2, %3, %4};" ::"r"(addr), "r"(a), "r"(b), "r"(c), "r"(d) : "memory");
}
__device__ __forceinline__ void ldsm4(uint32_t addr, uint32_t& a, uint32_t& b, uint32_t& c, uint32_t& d) {
  asm volatile("ldmatrix.sync.aligned.m8n8.x4.shared.b16 {%0, %1, %2, %3}, [%4];" : "=r"(a), "=r"(b), "=r"(c), "=r"(d) : "r"(addr) : "memory");
}
__device__ __forceinline__ uint32_t pack2(float lo, float hi) { uint32_t r; asm("cvt.rn.bf16x2.f32 %0, %1, %2;" : "=r"(r) : "f"(hi), "f"(lo)); return r; }
__device__ __forceinline__ uint32_t bsub2(uint32_t a, uint32_t b) { uint32_t r; asm("sub.rn.bf16x2 %0, %1, %2;" : "=r"(r) : "r"(a), "r"(b)); return r; }
__device__ __forceinline__ uint32_t badd2(uint32_t a, uint32_t b) { uint32_t r; asm("add.rn.bf16x2 %0, %1, %2;" : "=r"(r) : "r"(a), "r"(b)); return r; }
__device__ __forceinline__ uint32_t bmul2(uint32_t a, uint32_t b) { uint32_t r; asm("mul.rn.bf16x2 %0, %1, %2;" : "=r"(r) : "r"(a), "r"(b)); return r; }
__device__ __forceinline__ float bf_lo(uint32_t v) { return __uint_as_float(v << 16); }
__device__ __forceinline__ float bf_hi(uint32_t v) { return __uint_as_float(v & 0xffff0000u); }
__device__ __forceinline__ float bf_round(float v) { return bf_lo(pack2(v, 0.f)); }
__device__ __forceinline__ float ex2(float v) { float r; asm("ex2.approx.ftz.f32 %0, %1;" : "=f"(r) : "f"(v)); return r; }
__device__ __forceinline__ float rcp(float v) { float r; asm("rcp.approx.ftz.f32 %0, %1;" : "=f"(r) : "f"(v)); return r; }
__device__ __forceinline__ float sqrt_approx(float v) { float r; asm("sqrt.approx.f32 %0, %1;" : "=f"(r) : "f"(v)); return r; }
__device__ __forceinline__ float4 lds128(uint32_t a) { float4 v; asm volatile("ld.shared.v4.f32 {%0, %1, %2, %3}, [%4];" : "=f"(v.x), "=f"(v.y), "=f"(v.z), "=f"(v.w) : "r"(a) : "memory"); return v; }
__device__ __forceinline__ uint4 lds128u(uint32_t a) { uint4 v; asm volatile("ld.shared.v4.u32 {%0, %1, %2, %3}, [%4];" : "=r"(v.x), "=r"(v.y), "=r"(v.z), "=r"(v.w) : "r"(a) : "memory"); return v; }
__device__ __forceinline__ float2 lds64(uint32_t a) { float2 v; asm volatile("ld.shared.v2.f32 {%0, %1}, [%2];" : "=f"(v.x), "=f"(v.y) : "r"(a) : "memory"); return v; }
__device__ __forceinline__ float lds32(uint32_t a) { float v; asm volatile("ld.shared.f32 %0, [%1];" : "=f"(v) : "r"(a) : "memory"); return v; }
__device__ __forceinline__ void sts32(uint32_t a, float v) { asm volatile("st.shared.f32 [%0], %1;" ::"r"(a), "f"(v) : "memory"); }
__device__ __forceinline__ void sts64(uint32_t a, float x, float y) { asm volatile("st.shared.v2.f32 [%0], {%1, %2};" ::"r"(a), "f"(x), "f"(y) : "memory"); }
__device__ __forceinline__ void sts128(uint32_t a, float x, float y, float z, float w) { asm volatile("st.shared.v4.f32 [%0], {%1, %2, %3, %4};" ::"r"(a), "f"(x), "f"(y), "f"(z), "f"(w) : "memory"); }
__device__ __forceinline__ void sts64u(uint32_t a, uint32_t x, uint32_t y) { asm volatile("st.shared.v2.u32 [%0], {%1, %2};" ::"r"(a), "r"(x), "r"(y) : "memory"); }
__device__ __forceinline__ void sts128u(uint32_t a, uint32_t x, uint32_t y, uint32_t z, uint32_t w) { asm volatile("st.shared.v4.u32 [%0], {%1, %2, %3, %4};" ::"r"(a), "r"(x), "r"(y), "r"(z), "r"(w) : "memory"); }
__device__ __forceinline__ uint4 ldg_nc(const void* p) { uint4 v; asm volatile("ld.global.nc.L1::no_allocate.v4.u32 {%0, %1, %2, %3}, [%4];" : "=r"(v.x), "=r"(v.y), "=r"(v.z), "=r"(v.w) : "l"(p)); return v; }
__device__ __forceinline__ float4 ldg_cg4(const float* p) { float4 v; asm volatile("ld.global.cg.v4.f32 {%0, %1, %2, %3}, [%4];" : "=f"(v.x), "=f"(v.y), "=f"(v.z), "=f"(v.w) : "l"(p) : "memory"); return v; }
__device__ __forceinline__ uint32_t ld_acq(const uint32_t* p) { uint32_t v; asm volatile("ld.acquire.gpu.global.u32 %0, [%1];" : "=r"(v) : "l"(p) : "memory"); return v; }
__device__ __forceinline__ uint32_t ld_acq_cta(uint32_t a) { uint32_t v; asm volatile("ld.acquire.cta.shared.u32 %0, [%1];" : "=r"(v) : "r"(a) : "memory"); return v; }
__device__ __forceinline__ void st_rel_cta(uint32_t a, uint32_t v) { asm volatile("st.release.cta.shared.u32 [%0], %1;" ::"r"(a), "r"(v) : "memory"); }
__device__ __forceinline__ unsigned long long ld_rlx64(const unsigned long long* p) { unsigned long long v; asm volatile("ld.relaxed.gpu.global.u64 %0, [%1];" : "=l"(v) : "l"(p) : "memory"); return v; }
__device__ __forceinline__ void st_rlx64(unsigned long long* p, unsigned long long v) { asm volatile("st.relaxed.gpu.global.u64 [%0], %1;" ::"l"(p), "l"(v) : "memory"); }
__device__ __forceinline__ uint4 ld_rlx128(const void* p) {
  uint4 v;
  asm volatile("{ .reg .b128 t; .reg .b64 a, b; ld.relaxed.gpu.global.b128 t, [%4]; mov.b128 {a, b}, t; mov.b64 {%0, %1}, a; mov.b64 {%2, %3}, b; }"
               : "=r"(v.x), "=r"(v.y), "=r"(v.z), "=r"(v.w) : "l"(p) : "memory");
  return v;
}
__device__ __forceinline__ void st_rlx128(void* p, uint32_t x, uint32_t y, uint32_t z, uint32_t w) {
  asm volatile("{ .reg .b128 t; .reg .b64 a, b; mov.b64 a, {%1, %2}; mov.b64 b, {%3, %4}; mov.b128 t, {a, b}; st.relaxed.gpu.global.b128 [%0], t; }"
               ::"l"(p), "r"(x), "r"(y), "r"(z), "r"(w) : "memory");
}
__device__ __forceinline__ void stg128(void* p, uint32_t x, uint32_t y, uint32_t z, uint32_t w) { asm volatile("st.global.v4.u32 [%0], {%1, %2, %3, %4};" ::"l"(p), "r"(x), "r"(y), "r"(z), "r"(w) : "memory"); }
__device__ __forceinline__ void st_rlx(void* p, uint32_t v) { asm volatile("st.relaxed.gpu.global.u32 [%0], %1;" ::"l"(p), "r"(v) : "memory"); }
__device__ __forceinline__ uint32_t lop_select(uint32_t a, uint32_t b, uint32_t m) { uint32_t r; asm("lop3.b32 %0, %1, %2, %3, 0xd8;" : "=r"(r) : "r"(a), "r"(b), "r"(m)); return r; }
__device__ __forceinline__ float unmark(uint32_t v) { return __uint_as_float(v & ~1u); }
__device__ __forceinline__ uint32_t mark(uint32_t v, uint32_t par) { return (v & ~1u) | par; }
__device__ __forceinline__ float tanh_approx(float v) { float r; asm("tanh.approx.f32 %0, %1;" : "=f"(r) : "f"(v)); return r; }
__device__ __forceinline__ void flag_rel(uint32_t* p, uint32_t v) { asm volatile("red.release.gpu.global.max.u32 [%0], %1;" ::"l"(p), "r"(v) : "memory"); }
__device__ __forceinline__ void red1(float* p, float a) { asm volatile("red.global.add.f32 [%0], %1;" ::"l"(p), "f"(a) : "memory"); }
__device__ __forceinline__ void red_inc(uint32_t* p) { asm volatile("red.relaxed.gpu.global.add.u32 [%0], 1;" ::"l"(p) : "memory"); }
__device__ __forceinline__ void red_rel(uint32_t* p) { asm volatile("red.release.gpu.global.add.u32 [%0], 1;" ::"l"(p) : "memory"); }
__device__ __forceinline__ void red4(float* p, float a, float b, float c, float d) { asm volatile("red.global.add.v4.f32 [%0], {%1, %2, %3, %4};" ::"l"(p), "f"(a), "f"(b), "f"(c), "f"(d) : "memory"); }
constexpr int SPIN_MAX = 100000;
__device__ __forceinline__ uint32_t ld_rlx(const uint32_t* p) { uint32_t v; asm volatile("ld.relaxed.gpu.global.u32 %0, [%1];" : "=r"(v) : "l"(p) : "memory"); return v; }
template <int NS = 0> __device__ __forceinline__ void wait_hint(const uint32_t* p, uint32_t target) {
#pragma unroll 1
  for (int i = 0; i < SPIN_MAX; i++) { if ((int)(ld_rlx(p) - target) >= 0) break; if (NS) __nanosleep(NS); }
}
template <int NS> __device__ __forceinline__ void wait_cnt(const uint32_t* p, uint32_t target) {
#pragma unroll 1
  for (int i = 0; i < SPIN_MAX; i++) { if ((int)(ld_rlx(p) - target) >= 0) break; if (NS) __nanosleep(NS); }
  (void)ld_acq(p);
}
template <int NS> __device__ __forceinline__ unsigned long long wait_tag(const unsigned long long* p, uint32_t tag) {
  unsigned long long v = 0;
#pragma unroll 1
  for (int i = 0; i < SPIN_MAX; i++) { v = ld_rlx64(p); if ((uint32_t)(v >> 32) == tag) break; if (NS) __nanosleep(NS); }
  return v;
}
__device__ __forceinline__ float silu_f(float v) { return v * rcp(1.f + ex2(-1.4426950408889634f * v)); }

__device__ __forceinline__ void wgmma_n8_ss_ta1_tb0(float* d, uint64_t da, uint64_t db, bool accumulate) {
  if (accumulate) {
    asm volatile("{\n.reg .pred p;\nsetp.ne.b32 p, 1, 0;\n"
      "wgmma.mma_async.sync.aligned.m64n8k16.f32.bf16.bf16 "
      "{%0, %1, %2, %3}, "
      "%4, %5, p, 1, 1, 1, 0;\n}\n"
      : "+f"(d[0]), "+f"(d[1]), "+f"(d[2]), "+f"(d[3])
      : "l"(da), "l"(db));
  } else {
    asm volatile("{\n.reg .pred p;\nsetp.ne.b32 p, 0, 0;\n"
      "wgmma.mma_async.sync.aligned.m64n8k16.f32.bf16.bf16 "
      "{%0, %1, %2, %3}, "
      "%4, %5, p, 1, 1, 1, 0;\n}\n"
      : "=f"(d[0]), "=f"(d[1]), "=f"(d[2]), "=f"(d[3])
      : "l"(da), "l"(db));
  }
}
__device__ __forceinline__ void wgmma_n8_ss_ta1_tb1(float* d, uint64_t da, uint64_t db, bool accumulate) {
  if (accumulate) {
    asm volatile("{\n.reg .pred p;\nsetp.ne.b32 p, 1, 0;\n"
      "wgmma.mma_async.sync.aligned.m64n8k16.f32.bf16.bf16 "
      "{%0, %1, %2, %3}, "
      "%4, %5, p, 1, 1, 1, 1;\n}\n"
      : "+f"(d[0]), "+f"(d[1]), "+f"(d[2]), "+f"(d[3])
      : "l"(da), "l"(db));
  } else {
    asm volatile("{\n.reg .pred p;\nsetp.ne.b32 p, 0, 0;\n"
      "wgmma.mma_async.sync.aligned.m64n8k16.f32.bf16.bf16 "
      "{%0, %1, %2, %3}, "
      "%4, %5, p, 1, 1, 1, 1;\n}\n"
      : "=f"(d[0]), "=f"(d[1]), "=f"(d[2]), "=f"(d[3])
      : "l"(da), "l"(db));
  }
}
__device__ __forceinline__ void wgmma_n32_rs_ta0_tb1(float* d, uint32_t a0, uint32_t a1, uint32_t a2, uint32_t a3, uint64_t db, bool accumulate) {
  if (accumulate) {
    asm volatile("{\n.reg .pred p;\nsetp.ne.b32 p, 1, 0;\n"
      "wgmma.mma_async.sync.aligned.m64n32k16.f32.bf16.bf16 "
      "{%0, %1, %2, %3, %4, %5, %6, %7, %8, %9, %10, %11, %12, %13, %14, %15}, "
      "{%16, %17, %18, %19}, %20, p, 1, 1, 1;\n}\n"
      : "+f"(d[0]), "+f"(d[1]), "+f"(d[2]), "+f"(d[3]), "+f"(d[4]), "+f"(d[5]), "+f"(d[6]), "+f"(d[7]), "+f"(d[8]), "+f"(d[9]), "+f"(d[10]), "+f"(d[11]), "+f"(d[12]), "+f"(d[13]), "+f"(d[14]), "+f"(d[15])
      : "r"(a0), "r"(a1), "r"(a2), "r"(a3), "l"(db));
  } else {
    asm volatile("{\n.reg .pred p;\nsetp.ne.b32 p, 0, 0;\n"
      "wgmma.mma_async.sync.aligned.m64n32k16.f32.bf16.bf16 "
      "{%0, %1, %2, %3, %4, %5, %6, %7, %8, %9, %10, %11, %12, %13, %14, %15}, "
      "{%16, %17, %18, %19}, %20, p, 1, 1, 1;\n}\n"
      : "=f"(d[0]), "=f"(d[1]), "=f"(d[2]), "=f"(d[3]), "=f"(d[4]), "=f"(d[5]), "=f"(d[6]), "=f"(d[7]), "=f"(d[8]), "=f"(d[9]), "=f"(d[10]), "=f"(d[11]), "=f"(d[12]), "=f"(d[13]), "=f"(d[14]), "=f"(d[15])
      : "r"(a0), "r"(a1), "r"(a2), "r"(a3), "l"(db));
  }
}
__device__ __forceinline__ void wgmma_n40_rs_ta0_tb1(float* d, uint32_t a0, uint32_t a1, uint32_t a2, uint32_t a3, uint64_t db, bool accumulate) {
  if (accumulate) {
    asm volatile("{\n.reg .pred p;\nsetp.ne.b32 p, 1, 0;\n"
      "wgmma.mma_async.sync.aligned.m64n40k16.f32.bf16.bf16 "
      "{%0, %1, %2, %3, %4, %5, %6, %7, %8, %9, %10, %11, %12, %13, %14, %15, %16, %17, %18, %19}, "
      "{%20, %21, %22, %23}, %24, p, 1, 1, 1;\n}\n"
      : "+f"(d[0]), "+f"(d[1]), "+f"(d[2]), "+f"(d[3]), "+f"(d[4]), "+f"(d[5]), "+f"(d[6]), "+f"(d[7]), "+f"(d[8]), "+f"(d[9]), "+f"(d[10]), "+f"(d[11]), "+f"(d[12]), "+f"(d[13]), "+f"(d[14]), "+f"(d[15]), "+f"(d[16]), "+f"(d[17]), "+f"(d[18]), "+f"(d[19])
      : "r"(a0), "r"(a1), "r"(a2), "r"(a3), "l"(db));
  } else {
    asm volatile("{\n.reg .pred p;\nsetp.ne.b32 p, 0, 0;\n"
      "wgmma.mma_async.sync.aligned.m64n40k16.f32.bf16.bf16 "
      "{%0, %1, %2, %3, %4, %5, %6, %7, %8, %9, %10, %11, %12, %13, %14, %15, %16, %17, %18, %19}, "
      "{%20, %21, %22, %23}, %24, p, 1, 1, 1;\n}\n"
      : "=f"(d[0]), "=f"(d[1]), "=f"(d[2]), "=f"(d[3]), "=f"(d[4]), "=f"(d[5]), "=f"(d[6]), "=f"(d[7]), "=f"(d[8]), "=f"(d[9]), "=f"(d[10]), "=f"(d[11]), "=f"(d[12]), "=f"(d[13]), "=f"(d[14]), "=f"(d[15]), "=f"(d[16]), "=f"(d[17]), "=f"(d[18]), "=f"(d[19])
      : "r"(a0), "r"(a1), "r"(a2), "r"(a3), "l"(db));
  }
}
__device__ __forceinline__ void wgmma_n40_ss_ta1_tb1(float* d, uint64_t da, uint64_t db, bool accumulate) {
  if (accumulate) {
    asm volatile("{\n.reg .pred p;\nsetp.ne.b32 p, 1, 0;\n"
      "wgmma.mma_async.sync.aligned.m64n40k16.f32.bf16.bf16 "
      "{%0, %1, %2, %3, %4, %5, %6, %7, %8, %9, %10, %11, %12, %13, %14, %15, %16, %17, %18, %19}, "
      "%20, %21, p, 1, 1, 1, 1;\n}\n"
      : "+f"(d[0]), "+f"(d[1]), "+f"(d[2]), "+f"(d[3]), "+f"(d[4]), "+f"(d[5]), "+f"(d[6]), "+f"(d[7]), "+f"(d[8]), "+f"(d[9]), "+f"(d[10]), "+f"(d[11]), "+f"(d[12]), "+f"(d[13]), "+f"(d[14]), "+f"(d[15]), "+f"(d[16]), "+f"(d[17]), "+f"(d[18]), "+f"(d[19])
      : "l"(da), "l"(db));
  } else {
    asm volatile("{\n.reg .pred p;\nsetp.ne.b32 p, 0, 0;\n"
      "wgmma.mma_async.sync.aligned.m64n40k16.f32.bf16.bf16 "
      "{%0, %1, %2, %3, %4, %5, %6, %7, %8, %9, %10, %11, %12, %13, %14, %15, %16, %17, %18, %19}, "
      "%20, %21, p, 1, 1, 1, 1;\n}\n"
      : "=f"(d[0]), "=f"(d[1]), "=f"(d[2]), "=f"(d[3]), "=f"(d[4]), "=f"(d[5]), "=f"(d[6]), "=f"(d[7]), "=f"(d[8]), "=f"(d[9]), "=f"(d[10]), "=f"(d[11]), "=f"(d[12]), "=f"(d[13]), "=f"(d[14]), "=f"(d[15]), "=f"(d[16]), "=f"(d[17]), "=f"(d[18]), "=f"(d[19])
      : "l"(da), "l"(db));
  }
}
__device__ __forceinline__ void wgmma_n128_rs_ta0_tb1(float* d, uint32_t a0, uint32_t a1, uint32_t a2, uint32_t a3, uint64_t db, bool accumulate) {
  if (accumulate) {
    asm volatile("{\n.reg .pred p;\nsetp.ne.b32 p, 1, 0;\n"
      "wgmma.mma_async.sync.aligned.m64n128k16.f32.bf16.bf16 "
      "{%0, %1, %2, %3, %4, %5, %6, %7, %8, %9, %10, %11, %12, %13, %14, %15, %16, %17, %18, %19, %20, %21, %22, %23, %24, %25, %26, %27, %28, %29, %30, %31, %32, %33, %34, %35, %36, %37, %38, %39, %40, %41, %42, %43, %44, %45, %46, %47, %48, %49, %50, %51, %52, %53, %54, %55, %56, %57, %58, %59, %60, %61, %62, %63}, "
      "{%64, %65, %66, %67}, %68, p, 1, 1, 1;\n}\n"
      : "+f"(d[0]), "+f"(d[1]), "+f"(d[2]), "+f"(d[3]), "+f"(d[4]), "+f"(d[5]), "+f"(d[6]), "+f"(d[7]), "+f"(d[8]), "+f"(d[9]), "+f"(d[10]), "+f"(d[11]), "+f"(d[12]), "+f"(d[13]), "+f"(d[14]), "+f"(d[15]), "+f"(d[16]), "+f"(d[17]), "+f"(d[18]), "+f"(d[19]), "+f"(d[20]), "+f"(d[21]), "+f"(d[22]), "+f"(d[23]), "+f"(d[24]), "+f"(d[25]), "+f"(d[26]), "+f"(d[27]), "+f"(d[28]), "+f"(d[29]), "+f"(d[30]), "+f"(d[31]), "+f"(d[32]), "+f"(d[33]), "+f"(d[34]), "+f"(d[35]), "+f"(d[36]), "+f"(d[37]), "+f"(d[38]), "+f"(d[39]), "+f"(d[40]), "+f"(d[41]), "+f"(d[42]), "+f"(d[43]), "+f"(d[44]), "+f"(d[45]), "+f"(d[46]), "+f"(d[47]), "+f"(d[48]), "+f"(d[49]), "+f"(d[50]), "+f"(d[51]), "+f"(d[52]), "+f"(d[53]), "+f"(d[54]), "+f"(d[55]), "+f"(d[56]), "+f"(d[57]), "+f"(d[58]), "+f"(d[59]), "+f"(d[60]), "+f"(d[61]), "+f"(d[62]), "+f"(d[63])
      : "r"(a0), "r"(a1), "r"(a2), "r"(a3), "l"(db));
  } else {
    asm volatile("{\n.reg .pred p;\nsetp.ne.b32 p, 0, 0;\n"
      "wgmma.mma_async.sync.aligned.m64n128k16.f32.bf16.bf16 "
      "{%0, %1, %2, %3, %4, %5, %6, %7, %8, %9, %10, %11, %12, %13, %14, %15, %16, %17, %18, %19, %20, %21, %22, %23, %24, %25, %26, %27, %28, %29, %30, %31, %32, %33, %34, %35, %36, %37, %38, %39, %40, %41, %42, %43, %44, %45, %46, %47, %48, %49, %50, %51, %52, %53, %54, %55, %56, %57, %58, %59, %60, %61, %62, %63}, "
      "{%64, %65, %66, %67}, %68, p, 1, 1, 1;\n}\n"
      : "=f"(d[0]), "=f"(d[1]), "=f"(d[2]), "=f"(d[3]), "=f"(d[4]), "=f"(d[5]), "=f"(d[6]), "=f"(d[7]), "=f"(d[8]), "=f"(d[9]), "=f"(d[10]), "=f"(d[11]), "=f"(d[12]), "=f"(d[13]), "=f"(d[14]), "=f"(d[15]), "=f"(d[16]), "=f"(d[17]), "=f"(d[18]), "=f"(d[19]), "=f"(d[20]), "=f"(d[21]), "=f"(d[22]), "=f"(d[23]), "=f"(d[24]), "=f"(d[25]), "=f"(d[26]), "=f"(d[27]), "=f"(d[28]), "=f"(d[29]), "=f"(d[30]), "=f"(d[31]), "=f"(d[32]), "=f"(d[33]), "=f"(d[34]), "=f"(d[35]), "=f"(d[36]), "=f"(d[37]), "=f"(d[38]), "=f"(d[39]), "=f"(d[40]), "=f"(d[41]), "=f"(d[42]), "=f"(d[43]), "=f"(d[44]), "=f"(d[45]), "=f"(d[46]), "=f"(d[47]), "=f"(d[48]), "=f"(d[49]), "=f"(d[50]), "=f"(d[51]), "=f"(d[52]), "=f"(d[53]), "=f"(d[54]), "=f"(d[55]), "=f"(d[56]), "=f"(d[57]), "=f"(d[58]), "=f"(d[59]), "=f"(d[60]), "=f"(d[61]), "=f"(d[62]), "=f"(d[63])
      : "r"(a0), "r"(a1), "r"(a2), "r"(a3), "l"(db));
  }
}
__device__ __forceinline__ void wgmma_n128_ss_ta0_tb1(float* d, uint64_t da, uint64_t db, bool accumulate) {
  if (accumulate) {
    asm volatile("{\n.reg .pred p;\nsetp.ne.b32 p, 1, 0;\n"
      "wgmma.mma_async.sync.aligned.m64n128k16.f32.bf16.bf16 "
      "{%0, %1, %2, %3, %4, %5, %6, %7, %8, %9, %10, %11, %12, %13, %14, %15, %16, %17, %18, %19, %20, %21, %22, %23, %24, %25, %26, %27, %28, %29, %30, %31, %32, %33, %34, %35, %36, %37, %38, %39, %40, %41, %42, %43, %44, %45, %46, %47, %48, %49, %50, %51, %52, %53, %54, %55, %56, %57, %58, %59, %60, %61, %62, %63}, "
      "%64, %65, p, 1, 1, 0, 1;\n}\n"
      : "+f"(d[0]), "+f"(d[1]), "+f"(d[2]), "+f"(d[3]), "+f"(d[4]), "+f"(d[5]), "+f"(d[6]), "+f"(d[7]), "+f"(d[8]), "+f"(d[9]), "+f"(d[10]), "+f"(d[11]), "+f"(d[12]), "+f"(d[13]), "+f"(d[14]), "+f"(d[15]), "+f"(d[16]), "+f"(d[17]), "+f"(d[18]), "+f"(d[19]), "+f"(d[20]), "+f"(d[21]), "+f"(d[22]), "+f"(d[23]), "+f"(d[24]), "+f"(d[25]), "+f"(d[26]), "+f"(d[27]), "+f"(d[28]), "+f"(d[29]), "+f"(d[30]), "+f"(d[31]), "+f"(d[32]), "+f"(d[33]), "+f"(d[34]), "+f"(d[35]), "+f"(d[36]), "+f"(d[37]), "+f"(d[38]), "+f"(d[39]), "+f"(d[40]), "+f"(d[41]), "+f"(d[42]), "+f"(d[43]), "+f"(d[44]), "+f"(d[45]), "+f"(d[46]), "+f"(d[47]), "+f"(d[48]), "+f"(d[49]), "+f"(d[50]), "+f"(d[51]), "+f"(d[52]), "+f"(d[53]), "+f"(d[54]), "+f"(d[55]), "+f"(d[56]), "+f"(d[57]), "+f"(d[58]), "+f"(d[59]), "+f"(d[60]), "+f"(d[61]), "+f"(d[62]), "+f"(d[63])
      : "l"(da), "l"(db));
  } else {
    asm volatile("{\n.reg .pred p;\nsetp.ne.b32 p, 0, 0;\n"
      "wgmma.mma_async.sync.aligned.m64n128k16.f32.bf16.bf16 "
      "{%0, %1, %2, %3, %4, %5, %6, %7, %8, %9, %10, %11, %12, %13, %14, %15, %16, %17, %18, %19, %20, %21, %22, %23, %24, %25, %26, %27, %28, %29, %30, %31, %32, %33, %34, %35, %36, %37, %38, %39, %40, %41, %42, %43, %44, %45, %46, %47, %48, %49, %50, %51, %52, %53, %54, %55, %56, %57, %58, %59, %60, %61, %62, %63}, "
      "%64, %65, p, 1, 1, 0, 1;\n}\n"
      : "=f"(d[0]), "=f"(d[1]), "=f"(d[2]), "=f"(d[3]), "=f"(d[4]), "=f"(d[5]), "=f"(d[6]), "=f"(d[7]), "=f"(d[8]), "=f"(d[9]), "=f"(d[10]), "=f"(d[11]), "=f"(d[12]), "=f"(d[13]), "=f"(d[14]), "=f"(d[15]), "=f"(d[16]), "=f"(d[17]), "=f"(d[18]), "=f"(d[19]), "=f"(d[20]), "=f"(d[21]), "=f"(d[22]), "=f"(d[23]), "=f"(d[24]), "=f"(d[25]), "=f"(d[26]), "=f"(d[27]), "=f"(d[28]), "=f"(d[29]), "=f"(d[30]), "=f"(d[31]), "=f"(d[32]), "=f"(d[33]), "=f"(d[34]), "=f"(d[35]), "=f"(d[36]), "=f"(d[37]), "=f"(d[38]), "=f"(d[39]), "=f"(d[40]), "=f"(d[41]), "=f"(d[42]), "=f"(d[43]), "=f"(d[44]), "=f"(d[45]), "=f"(d[46]), "=f"(d[47]), "=f"(d[48]), "=f"(d[49]), "=f"(d[50]), "=f"(d[51]), "=f"(d[52]), "=f"(d[53]), "=f"(d[54]), "=f"(d[55]), "=f"(d[56]), "=f"(d[57]), "=f"(d[58]), "=f"(d[59]), "=f"(d[60]), "=f"(d[61]), "=f"(d[62]), "=f"(d[63])
      : "l"(da), "l"(db));
  }
}
__device__ __forceinline__ void wgmma_n256_rs_ta0_tb1(float* d, uint32_t a0, uint32_t a1, uint32_t a2, uint32_t a3, uint64_t db, bool accumulate) {
  if (accumulate) {
    asm volatile("{\n.reg .pred p;\nsetp.ne.b32 p, 1, 0;\n"
      "wgmma.mma_async.sync.aligned.m64n256k16.f32.bf16.bf16 "
      "{%0, %1, %2, %3, %4, %5, %6, %7, %8, %9, %10, %11, %12, %13, %14, %15, %16, %17, %18, %19, %20, %21, %22, %23, %24, %25, %26, %27, %28, %29, %30, %31, %32, %33, %34, %35, %36, %37, %38, %39, %40, %41, %42, %43, %44, %45, %46, %47, %48, %49, %50, %51, %52, %53, %54, %55, %56, %57, %58, %59, %60, %61, %62, %63, %64, %65, %66, %67, %68, %69, %70, %71, %72, %73, %74, %75, %76, %77, %78, %79, %80, %81, %82, %83, %84, %85, %86, %87, %88, %89, %90, %91, %92, %93, %94, %95, %96, %97, %98, %99, %100, %101, %102, %103, %104, %105, %106, %107, %108, %109, %110, %111, %112, %113, %114, %115, %116, %117, %118, %119, %120, %121, %122, %123, %124, %125, %126, %127}, "
      "{%128, %129, %130, %131}, %132, p, 1, 1, 1;\n}\n"
      : "+f"(d[0]), "+f"(d[1]), "+f"(d[2]), "+f"(d[3]), "+f"(d[4]), "+f"(d[5]), "+f"(d[6]), "+f"(d[7]), "+f"(d[8]), "+f"(d[9]), "+f"(d[10]), "+f"(d[11]), "+f"(d[12]), "+f"(d[13]), "+f"(d[14]), "+f"(d[15]), "+f"(d[16]), "+f"(d[17]), "+f"(d[18]), "+f"(d[19]), "+f"(d[20]), "+f"(d[21]), "+f"(d[22]), "+f"(d[23]), "+f"(d[24]), "+f"(d[25]), "+f"(d[26]), "+f"(d[27]), "+f"(d[28]), "+f"(d[29]), "+f"(d[30]), "+f"(d[31]), "+f"(d[32]), "+f"(d[33]), "+f"(d[34]), "+f"(d[35]), "+f"(d[36]), "+f"(d[37]), "+f"(d[38]), "+f"(d[39]), "+f"(d[40]), "+f"(d[41]), "+f"(d[42]), "+f"(d[43]), "+f"(d[44]), "+f"(d[45]), "+f"(d[46]), "+f"(d[47]), "+f"(d[48]), "+f"(d[49]), "+f"(d[50]), "+f"(d[51]), "+f"(d[52]), "+f"(d[53]), "+f"(d[54]), "+f"(d[55]), "+f"(d[56]), "+f"(d[57]), "+f"(d[58]), "+f"(d[59]), "+f"(d[60]), "+f"(d[61]), "+f"(d[62]), "+f"(d[63]), "+f"(d[64]), "+f"(d[65]), "+f"(d[66]), "+f"(d[67]), "+f"(d[68]), "+f"(d[69]), "+f"(d[70]), "+f"(d[71]), "+f"(d[72]), "+f"(d[73]), "+f"(d[74]), "+f"(d[75]), "+f"(d[76]), "+f"(d[77]), "+f"(d[78]), "+f"(d[79]), "+f"(d[80]), "+f"(d[81]), "+f"(d[82]), "+f"(d[83]), "+f"(d[84]), "+f"(d[85]), "+f"(d[86]), "+f"(d[87]), "+f"(d[88]), "+f"(d[89]), "+f"(d[90]), "+f"(d[91]), "+f"(d[92]), "+f"(d[93]), "+f"(d[94]), "+f"(d[95]), "+f"(d[96]), "+f"(d[97]), "+f"(d[98]), "+f"(d[99]), "+f"(d[100]), "+f"(d[101]), "+f"(d[102]), "+f"(d[103]), "+f"(d[104]), "+f"(d[105]), "+f"(d[106]), "+f"(d[107]), "+f"(d[108]), "+f"(d[109]), "+f"(d[110]), "+f"(d[111]), "+f"(d[112]), "+f"(d[113]), "+f"(d[114]), "+f"(d[115]), "+f"(d[116]), "+f"(d[117]), "+f"(d[118]), "+f"(d[119]), "+f"(d[120]), "+f"(d[121]), "+f"(d[122]), "+f"(d[123]), "+f"(d[124]), "+f"(d[125]), "+f"(d[126]), "+f"(d[127])
      : "r"(a0), "r"(a1), "r"(a2), "r"(a3), "l"(db));
  } else {
    asm volatile("{\n.reg .pred p;\nsetp.ne.b32 p, 0, 0;\n"
      "wgmma.mma_async.sync.aligned.m64n256k16.f32.bf16.bf16 "
      "{%0, %1, %2, %3, %4, %5, %6, %7, %8, %9, %10, %11, %12, %13, %14, %15, %16, %17, %18, %19, %20, %21, %22, %23, %24, %25, %26, %27, %28, %29, %30, %31, %32, %33, %34, %35, %36, %37, %38, %39, %40, %41, %42, %43, %44, %45, %46, %47, %48, %49, %50, %51, %52, %53, %54, %55, %56, %57, %58, %59, %60, %61, %62, %63, %64, %65, %66, %67, %68, %69, %70, %71, %72, %73, %74, %75, %76, %77, %78, %79, %80, %81, %82, %83, %84, %85, %86, %87, %88, %89, %90, %91, %92, %93, %94, %95, %96, %97, %98, %99, %100, %101, %102, %103, %104, %105, %106, %107, %108, %109, %110, %111, %112, %113, %114, %115, %116, %117, %118, %119, %120, %121, %122, %123, %124, %125, %126, %127}, "
      "{%128, %129, %130, %131}, %132, p, 1, 1, 1;\n}\n"
      : "=f"(d[0]), "=f"(d[1]), "=f"(d[2]), "=f"(d[3]), "=f"(d[4]), "=f"(d[5]), "=f"(d[6]), "=f"(d[7]), "=f"(d[8]), "=f"(d[9]), "=f"(d[10]), "=f"(d[11]), "=f"(d[12]), "=f"(d[13]), "=f"(d[14]), "=f"(d[15]), "=f"(d[16]), "=f"(d[17]), "=f"(d[18]), "=f"(d[19]), "=f"(d[20]), "=f"(d[21]), "=f"(d[22]), "=f"(d[23]), "=f"(d[24]), "=f"(d[25]), "=f"(d[26]), "=f"(d[27]), "=f"(d[28]), "=f"(d[29]), "=f"(d[30]), "=f"(d[31]), "=f"(d[32]), "=f"(d[33]), "=f"(d[34]), "=f"(d[35]), "=f"(d[36]), "=f"(d[37]), "=f"(d[38]), "=f"(d[39]), "=f"(d[40]), "=f"(d[41]), "=f"(d[42]), "=f"(d[43]), "=f"(d[44]), "=f"(d[45]), "=f"(d[46]), "=f"(d[47]), "=f"(d[48]), "=f"(d[49]), "=f"(d[50]), "=f"(d[51]), "=f"(d[52]), "=f"(d[53]), "=f"(d[54]), "=f"(d[55]), "=f"(d[56]), "=f"(d[57]), "=f"(d[58]), "=f"(d[59]), "=f"(d[60]), "=f"(d[61]), "=f"(d[62]), "=f"(d[63]), "=f"(d[64]), "=f"(d[65]), "=f"(d[66]), "=f"(d[67]), "=f"(d[68]), "=f"(d[69]), "=f"(d[70]), "=f"(d[71]), "=f"(d[72]), "=f"(d[73]), "=f"(d[74]), "=f"(d[75]), "=f"(d[76]), "=f"(d[77]), "=f"(d[78]), "=f"(d[79]), "=f"(d[80]), "=f"(d[81]), "=f"(d[82]), "=f"(d[83]), "=f"(d[84]), "=f"(d[85]), "=f"(d[86]), "=f"(d[87]), "=f"(d[88]), "=f"(d[89]), "=f"(d[90]), "=f"(d[91]), "=f"(d[92]), "=f"(d[93]), "=f"(d[94]), "=f"(d[95]), "=f"(d[96]), "=f"(d[97]), "=f"(d[98]), "=f"(d[99]), "=f"(d[100]), "=f"(d[101]), "=f"(d[102]), "=f"(d[103]), "=f"(d[104]), "=f"(d[105]), "=f"(d[106]), "=f"(d[107]), "=f"(d[108]), "=f"(d[109]), "=f"(d[110]), "=f"(d[111]), "=f"(d[112]), "=f"(d[113]), "=f"(d[114]), "=f"(d[115]), "=f"(d[116]), "=f"(d[117]), "=f"(d[118]), "=f"(d[119]), "=f"(d[120]), "=f"(d[121]), "=f"(d[122]), "=f"(d[123]), "=f"(d[124]), "=f"(d[125]), "=f"(d[126]), "=f"(d[127])
      : "r"(a0), "r"(a1), "r"(a2), "r"(a3), "l"(db));
  }
}
__device__ __forceinline__ void wgmma_n256_ss_ta0_tb1(float* d, uint64_t da, uint64_t db, bool accumulate) {
  if (accumulate) {
    asm volatile("{\n.reg .pred p;\nsetp.ne.b32 p, 1, 0;\n"
      "wgmma.mma_async.sync.aligned.m64n256k16.f32.bf16.bf16 "
      "{%0, %1, %2, %3, %4, %5, %6, %7, %8, %9, %10, %11, %12, %13, %14, %15, %16, %17, %18, %19, %20, %21, %22, %23, %24, %25, %26, %27, %28, %29, %30, %31, %32, %33, %34, %35, %36, %37, %38, %39, %40, %41, %42, %43, %44, %45, %46, %47, %48, %49, %50, %51, %52, %53, %54, %55, %56, %57, %58, %59, %60, %61, %62, %63, %64, %65, %66, %67, %68, %69, %70, %71, %72, %73, %74, %75, %76, %77, %78, %79, %80, %81, %82, %83, %84, %85, %86, %87, %88, %89, %90, %91, %92, %93, %94, %95, %96, %97, %98, %99, %100, %101, %102, %103, %104, %105, %106, %107, %108, %109, %110, %111, %112, %113, %114, %115, %116, %117, %118, %119, %120, %121, %122, %123, %124, %125, %126, %127}, "
      "%128, %129, p, 1, 1, 0, 1;\n}\n"
      : "+f"(d[0]), "+f"(d[1]), "+f"(d[2]), "+f"(d[3]), "+f"(d[4]), "+f"(d[5]), "+f"(d[6]), "+f"(d[7]), "+f"(d[8]), "+f"(d[9]), "+f"(d[10]), "+f"(d[11]), "+f"(d[12]), "+f"(d[13]), "+f"(d[14]), "+f"(d[15]), "+f"(d[16]), "+f"(d[17]), "+f"(d[18]), "+f"(d[19]), "+f"(d[20]), "+f"(d[21]), "+f"(d[22]), "+f"(d[23]), "+f"(d[24]), "+f"(d[25]), "+f"(d[26]), "+f"(d[27]), "+f"(d[28]), "+f"(d[29]), "+f"(d[30]), "+f"(d[31]), "+f"(d[32]), "+f"(d[33]), "+f"(d[34]), "+f"(d[35]), "+f"(d[36]), "+f"(d[37]), "+f"(d[38]), "+f"(d[39]), "+f"(d[40]), "+f"(d[41]), "+f"(d[42]), "+f"(d[43]), "+f"(d[44]), "+f"(d[45]), "+f"(d[46]), "+f"(d[47]), "+f"(d[48]), "+f"(d[49]), "+f"(d[50]), "+f"(d[51]), "+f"(d[52]), "+f"(d[53]), "+f"(d[54]), "+f"(d[55]), "+f"(d[56]), "+f"(d[57]), "+f"(d[58]), "+f"(d[59]), "+f"(d[60]), "+f"(d[61]), "+f"(d[62]), "+f"(d[63]), "+f"(d[64]), "+f"(d[65]), "+f"(d[66]), "+f"(d[67]), "+f"(d[68]), "+f"(d[69]), "+f"(d[70]), "+f"(d[71]), "+f"(d[72]), "+f"(d[73]), "+f"(d[74]), "+f"(d[75]), "+f"(d[76]), "+f"(d[77]), "+f"(d[78]), "+f"(d[79]), "+f"(d[80]), "+f"(d[81]), "+f"(d[82]), "+f"(d[83]), "+f"(d[84]), "+f"(d[85]), "+f"(d[86]), "+f"(d[87]), "+f"(d[88]), "+f"(d[89]), "+f"(d[90]), "+f"(d[91]), "+f"(d[92]), "+f"(d[93]), "+f"(d[94]), "+f"(d[95]), "+f"(d[96]), "+f"(d[97]), "+f"(d[98]), "+f"(d[99]), "+f"(d[100]), "+f"(d[101]), "+f"(d[102]), "+f"(d[103]), "+f"(d[104]), "+f"(d[105]), "+f"(d[106]), "+f"(d[107]), "+f"(d[108]), "+f"(d[109]), "+f"(d[110]), "+f"(d[111]), "+f"(d[112]), "+f"(d[113]), "+f"(d[114]), "+f"(d[115]), "+f"(d[116]), "+f"(d[117]), "+f"(d[118]), "+f"(d[119]), "+f"(d[120]), "+f"(d[121]), "+f"(d[122]), "+f"(d[123]), "+f"(d[124]), "+f"(d[125]), "+f"(d[126]), "+f"(d[127])
      : "l"(da), "l"(db));
  } else {
    asm volatile("{\n.reg .pred p;\nsetp.ne.b32 p, 0, 0;\n"
      "wgmma.mma_async.sync.aligned.m64n256k16.f32.bf16.bf16 "
      "{%0, %1, %2, %3, %4, %5, %6, %7, %8, %9, %10, %11, %12, %13, %14, %15, %16, %17, %18, %19, %20, %21, %22, %23, %24, %25, %26, %27, %28, %29, %30, %31, %32, %33, %34, %35, %36, %37, %38, %39, %40, %41, %42, %43, %44, %45, %46, %47, %48, %49, %50, %51, %52, %53, %54, %55, %56, %57, %58, %59, %60, %61, %62, %63, %64, %65, %66, %67, %68, %69, %70, %71, %72, %73, %74, %75, %76, %77, %78, %79, %80, %81, %82, %83, %84, %85, %86, %87, %88, %89, %90, %91, %92, %93, %94, %95, %96, %97, %98, %99, %100, %101, %102, %103, %104, %105, %106, %107, %108, %109, %110, %111, %112, %113, %114, %115, %116, %117, %118, %119, %120, %121, %122, %123, %124, %125, %126, %127}, "
      "%128, %129, p, 1, 1, 0, 1;\n}\n"
      : "=f"(d[0]), "=f"(d[1]), "=f"(d[2]), "=f"(d[3]), "=f"(d[4]), "=f"(d[5]), "=f"(d[6]), "=f"(d[7]), "=f"(d[8]), "=f"(d[9]), "=f"(d[10]), "=f"(d[11]), "=f"(d[12]), "=f"(d[13]), "=f"(d[14]), "=f"(d[15]), "=f"(d[16]), "=f"(d[17]), "=f"(d[18]), "=f"(d[19]), "=f"(d[20]), "=f"(d[21]), "=f"(d[22]), "=f"(d[23]), "=f"(d[24]), "=f"(d[25]), "=f"(d[26]), "=f"(d[27]), "=f"(d[28]), "=f"(d[29]), "=f"(d[30]), "=f"(d[31]), "=f"(d[32]), "=f"(d[33]), "=f"(d[34]), "=f"(d[35]), "=f"(d[36]), "=f"(d[37]), "=f"(d[38]), "=f"(d[39]), "=f"(d[40]), "=f"(d[41]), "=f"(d[42]), "=f"(d[43]), "=f"(d[44]), "=f"(d[45]), "=f"(d[46]), "=f"(d[47]), "=f"(d[48]), "=f"(d[49]), "=f"(d[50]), "=f"(d[51]), "=f"(d[52]), "=f"(d[53]), "=f"(d[54]), "=f"(d[55]), "=f"(d[56]), "=f"(d[57]), "=f"(d[58]), "=f"(d[59]), "=f"(d[60]), "=f"(d[61]), "=f"(d[62]), "=f"(d[63]), "=f"(d[64]), "=f"(d[65]), "=f"(d[66]), "=f"(d[67]), "=f"(d[68]), "=f"(d[69]), "=f"(d[70]), "=f"(d[71]), "=f"(d[72]), "=f"(d[73]), "=f"(d[74]), "=f"(d[75]), "=f"(d[76]), "=f"(d[77]), "=f"(d[78]), "=f"(d[79]), "=f"(d[80]), "=f"(d[81]), "=f"(d[82]), "=f"(d[83]), "=f"(d[84]), "=f"(d[85]), "=f"(d[86]), "=f"(d[87]), "=f"(d[88]), "=f"(d[89]), "=f"(d[90]), "=f"(d[91]), "=f"(d[92]), "=f"(d[93]), "=f"(d[94]), "=f"(d[95]), "=f"(d[96]), "=f"(d[97]), "=f"(d[98]), "=f"(d[99]), "=f"(d[100]), "=f"(d[101]), "=f"(d[102]), "=f"(d[103]), "=f"(d[104]), "=f"(d[105]), "=f"(d[106]), "=f"(d[107]), "=f"(d[108]), "=f"(d[109]), "=f"(d[110]), "=f"(d[111]), "=f"(d[112]), "=f"(d[113]), "=f"(d[114]), "=f"(d[115]), "=f"(d[116]), "=f"(d[117]), "=f"(d[118]), "=f"(d[119]), "=f"(d[120]), "=f"(d[121]), "=f"(d[122]), "=f"(d[123]), "=f"(d[124]), "=f"(d[125]), "=f"(d[126]), "=f"(d[127])
      : "l"(da), "l"(db));
  }
}
__device__ __forceinline__ void wgmma_n256_ssp_ta0_tb1(float* d, uint64_t da, uint64_t db, int accumulate) {
    asm volatile("{\n.reg .pred p;\nsetp.ne.b32 p, %130, 0;\n"
      "wgmma.mma_async.sync.aligned.m64n256k16.f32.bf16.bf16 "
      "{%0, %1, %2, %3, %4, %5, %6, %7, %8, %9, %10, %11, %12, %13, %14, %15, %16, %17, %18, %19, %20, %21, %22, %23, %24, %25, %26, %27, %28, %29, %30, %31, %32, %33, %34, %35, %36, %37, %38, %39, %40, %41, %42, %43, %44, %45, %46, %47, %48, %49, %50, %51, %52, %53, %54, %55, %56, %57, %58, %59, %60, %61, %62, %63, %64, %65, %66, %67, %68, %69, %70, %71, %72, %73, %74, %75, %76, %77, %78, %79, %80, %81, %82, %83, %84, %85, %86, %87, %88, %89, %90, %91, %92, %93, %94, %95, %96, %97, %98, %99, %100, %101, %102, %103, %104, %105, %106, %107, %108, %109, %110, %111, %112, %113, %114, %115, %116, %117, %118, %119, %120, %121, %122, %123, %124, %125, %126, %127}, "
      "%128, %129, p, 1, 1, 0, 1;\n}\n"
      : "+f"(d[0]), "+f"(d[1]), "+f"(d[2]), "+f"(d[3]), "+f"(d[4]), "+f"(d[5]), "+f"(d[6]), "+f"(d[7]), "+f"(d[8]), "+f"(d[9]), "+f"(d[10]), "+f"(d[11]), "+f"(d[12]), "+f"(d[13]), "+f"(d[14]), "+f"(d[15]), "+f"(d[16]), "+f"(d[17]), "+f"(d[18]), "+f"(d[19]), "+f"(d[20]), "+f"(d[21]), "+f"(d[22]), "+f"(d[23]), "+f"(d[24]), "+f"(d[25]), "+f"(d[26]), "+f"(d[27]), "+f"(d[28]), "+f"(d[29]), "+f"(d[30]), "+f"(d[31]), "+f"(d[32]), "+f"(d[33]), "+f"(d[34]), "+f"(d[35]), "+f"(d[36]), "+f"(d[37]), "+f"(d[38]), "+f"(d[39]), "+f"(d[40]), "+f"(d[41]), "+f"(d[42]), "+f"(d[43]), "+f"(d[44]), "+f"(d[45]), "+f"(d[46]), "+f"(d[47]), "+f"(d[48]), "+f"(d[49]), "+f"(d[50]), "+f"(d[51]), "+f"(d[52]), "+f"(d[53]), "+f"(d[54]), "+f"(d[55]), "+f"(d[56]), "+f"(d[57]), "+f"(d[58]), "+f"(d[59]), "+f"(d[60]), "+f"(d[61]), "+f"(d[62]), "+f"(d[63]), "+f"(d[64]), "+f"(d[65]), "+f"(d[66]), "+f"(d[67]), "+f"(d[68]), "+f"(d[69]), "+f"(d[70]), "+f"(d[71]), "+f"(d[72]), "+f"(d[73]), "+f"(d[74]), "+f"(d[75]), "+f"(d[76]), "+f"(d[77]), "+f"(d[78]), "+f"(d[79]), "+f"(d[80]), "+f"(d[81]), "+f"(d[82]), "+f"(d[83]), "+f"(d[84]), "+f"(d[85]), "+f"(d[86]), "+f"(d[87]), "+f"(d[88]), "+f"(d[89]), "+f"(d[90]), "+f"(d[91]), "+f"(d[92]), "+f"(d[93]), "+f"(d[94]), "+f"(d[95]), "+f"(d[96]), "+f"(d[97]), "+f"(d[98]), "+f"(d[99]), "+f"(d[100]), "+f"(d[101]), "+f"(d[102]), "+f"(d[103]), "+f"(d[104]), "+f"(d[105]), "+f"(d[106]), "+f"(d[107]), "+f"(d[108]), "+f"(d[109]), "+f"(d[110]), "+f"(d[111]), "+f"(d[112]), "+f"(d[113]), "+f"(d[114]), "+f"(d[115]), "+f"(d[116]), "+f"(d[117]), "+f"(d[118]), "+f"(d[119]), "+f"(d[120]), "+f"(d[121]), "+f"(d[122]), "+f"(d[123]), "+f"(d[124]), "+f"(d[125]), "+f"(d[126]), "+f"(d[127])
      : "l"(da), "l"(db), "r"(accumulate));
}

template <int N> __device__ __forceinline__ void quad_sum(float* m) {
#pragma unroll
  for (int o = 1; o <= 2; o <<= 1) {
    float t[N];
#pragma unroll
    for (int i = 0; i < N; i++) t[i] = __shfl_xor_sync(~0u, m[i], o);
#pragma unroll
    for (int i = 0; i < N; i++) m[i] += t[i];
  }
}
__device__ __forceinline__ bool softmax_unsafe(const uint32_t* t, float l0, float l1) {
  const float m0 = fmaxf(bf_lo(t[0]) + bf_hi(t[0]), bf_lo(t[2]) + bf_hi(t[2])), m1 = fmaxf(bf_lo(t[1]) + bf_hi(t[1]), bf_lo(t[3]) + bf_hi(t[3]));
  return __any_sync(~0u, !(m0 * l0 < 2500.f) | !(m1 * l1 < 2500.f));
}
__device__ __forceinline__ void softmax_shift(float* p, float c0, float c1) {
#pragma unroll 1
  for (int it = 0; it < 8; it++) {
    float mx = p[0], mn = p[0];
#pragma unroll
    for (int j = 1; j < 8; j++) { mx = fmaxf(mx, p[(j >> 1) * 4 + (j & 1)]); mn = fminf(mn, p[(j >> 1) * 4 + (j & 1)]); }
#pragma unroll
    for (int o = 1; o <= 2; o <<= 1) { mx = fmaxf(mx, __shfl_xor_sync(~0u, mx, o)); mn = fminf(mn, __shfl_xor_sync(~0u, mn, o)); }
    const float half = fminf(0.5f * (mx - mn), 50.f * rcp(it & 1 ? c1 : c0));
    float r[8];
#pragma unroll
    for (int j = 0; j < 8; j++) {
      const float v = p[(j >> 1) * 4 + (j & 1)];
      r[j] = fmaxf(v - mx + half, 0.f) + fminf(v - mn - half, 0.f) + (v - v);
    }
#pragma unroll
    for (int k = 0; k < 7; k++)
#pragma unroll
      for (int j = 0; j < 8; j++) p[(k >> 1) * 16 + (k & 1) * 2 + (j >> 1) * 4 + (j & 1)] = p[((k + 1) >> 1) * 16 + ((k + 1) & 1) * 2 + (j >> 1) * 4 + (j & 1)];
#pragma unroll
    for (int j = 0; j < 8; j++) p[50 + (j >> 1) * 4 + (j & 1)] = r[j];
  }
}
template <int J0 = 0, int J1 = 8> __device__ __forceinline__ void k_exp(const float* p, float c0, float c1, float* e, float* s) {
#pragma unroll
  for (int j = J0; j < J1; j++) {
    e[2 * j] = ex2(p[2 * j] * (j & 1 ? c1 : c0));
    e[2 * j + 1] = ex2(p[2 * j + 1] * (j & 1 ? c1 : c0));
    e[16 + j] = rcp(e[2 * j] * e[2 * j + 1]);
    const float t = e[2 * j] + e[2 * j + 1];
    s[j & 1] = j < 2 ? t : s[j & 1] + t;
    s[2 + (j & 1)] = j < 2 ? e[16 + j] * t : fmaf(e[16 + j], t, s[2 + (j & 1)]);
  }
}
template <int J0 = 0, int J1 = 8> __device__ __forceinline__ void q_exp(const float* p, float c0, float c1, uint32_t* f) {
#pragma unroll
  for (int j = J0; j < J1; j++) {
    const float e0 = ex2(p[2 * j] * (j & 1 ? c1 : c0)), e1 = ex2(p[2 * j + 1] * (j & 1 ? c1 : c0)), r = rcp(e0 * e1);
    f[j] = pack2(e0, e1);
    f[8 + j] = bmul2(f[j], pack2(r, r));
  }
}

#define FMA8(A, U, X)                                                                                        \
  A[0] = fmaf(bf_lo(U.x), X, A[0]); A[1] = fmaf(bf_hi(U.x), X, A[1]); A[2] = fmaf(bf_lo(U.y), X, A[2]); A[3] = fmaf(bf_hi(U.y), X, A[3]); \
  A[4] = fmaf(bf_lo(U.z), X, A[4]); A[5] = fmaf(bf_hi(U.z), X, A[5]); A[6] = fmaf(bf_lo(U.w), X, A[6]); A[7] = fmaf(bf_hi(U.w), X, A[7])

__device__ __forceinline__ uint32_t routed_row(const __nv_bfloat16* x, uint32_t tag, int lane, uint4* xr) {
  uint32_t best = 0, sv = 0;
#pragma unroll 1
  for (int it = 0; it < SPIN_MAX; it++) {
    const int sel = 2047 - (best & 0x7ff);
#pragma unroll
    for (int i = 0; i < 4; i++) xr[i] = ldg_nc(x + (size_t)sel * DM + i * 256 + lane * 8);
    const unsigned long long st = ld_rlx64(g_stat + sel);
    const uint4 b0 = ld_rlx128(g_best + lane * 2), b1 = ld_rlx128(g_best + 64 + lane * 2);
    const uint32_t m = __reduce_max_sync(~0u, max(max(b0.y == tag ? b0.x : 0u, b0.w == tag ? b0.z : 0u), max(b1.y == tag ? b1.x : 0u, b1.w == tag ? b1.z : 0u)));
    sv = (uint32_t)st;
    if (__all_sync(~0u, b0.y == tag && b0.w == tag && b1.y == tag && b1.w == tag && m == best && (uint32_t)(st >> 32) == tag)) break;
    best = m;
    if (AM_NS) __nanosleep(AM_NS);
  }
  const uint32_t m2 = (sv & 0xffff0000u) | (sv >> 16);
  const float rs = rcp(bf_lo(sv));
#pragma unroll
  for (int i = 0; i < 4; i++) {
    const uint32_t d0 = bsub2(xr[i].x, m2), d1 = bsub2(xr[i].y, m2), d2 = bsub2(xr[i].z, m2), d3 = bsub2(xr[i].w, m2);
    xr[i] = make_uint4(pack2(bf_lo(d0) * rs, bf_hi(d0) * rs), pack2(bf_lo(d1) * rs, bf_hi(d1) * rs), pack2(bf_lo(d2) * rs, bf_hi(d2) * rs),
                       pack2(bf_lo(d3) * rs, bf_hi(d3) * rs));
  }
  return best;
}

struct Params {
  const __nv_bfloat16 *x, *wqkv, *wo, *w_r, *w_gate, *w_up, *w_down;
};

template <bool BY_SMID> __global__ void __launch_bounds__(384, 1)
fused_kernel(const __grid_constant__ CUtensorMap mX, const __grid_constant__ CUtensorMap mWkv, const __grid_constant__ CUtensorMap mWq,
             const __grid_constant__ CUtensorMap mWo, const __grid_constant__ CUtensorMap mPhi, const __grid_constant__ CUtensorMap mWp,
             const __grid_constant__ CUtensorMap mOut, const __grid_constant__ CUtensorMap mWc,
             const __grid_constant__ CUtensorMap mG, const __grid_constant__ CUtensorMap mU, const __grid_constant__ CUtensorMap mD,
             const __grid_constant__ CUtensorMap mXs, const __grid_constant__ CUtensorMap mG2, const __grid_constant__ CUtensorMap mU2, const Params P) {
  constexpr uint32_t sb = SB, bar = SB + SM_BAR;
  int bid = blockIdx.x;
  if (BY_SMID) {
    uint32_t sm;
    asm volatile("mov.u32 %0, %%smid;" : "=r"(sm));
    const uint32_t tq = (sm - 64) >> 1, q7 = (tq * 37) >> 8;
    const uint32_t gpc = sm < 64 ? (sm >> 1) & 7 : 1 + tq - 7 * q7, idx = (sm < 64 ? sm >> 4 : 4 + q7) * 2 + (sm & 1);
    bid = sm < 120 ? ((PTAB >> (4 * gpc)) & 7) * 16 + idx : sm < 124 ? sm + 8 : sm - 116;
  }
  const int hg = ((bid >> 2) & 3) + 4 * ((bid >> 4) & 1), mb = (bid & 3) + 4 * ((bid >> 5) & 3);
  if (bid < NCTA && threadIdx.x < 256) {
    const uint32_t r0 = threadIdx.x >> 3, c = threadIdx.x & 7, dst = sb + 2 * KV_STAGE + r0 * 128 + ((c ^ (r0 & 7)) << 4);
    const char* xs = (const char*)P.x + (size_t)(mb * 128 + r0) * 2048 + c * 16;
    const char* ws = (const char*)P.wqkv + (size_t)r0 * 6144 + 2048 + hg * 256 + c * 16;
#pragma unroll
    for (int i = 0; i < 4; i++) cp_async16(dst + i * 4096, xs + i * 65536);
#pragma unroll
    for (int i = 0; i < 8; i++) cp_async16(dst + 16384 + i * 4096, ws + (i & 1) * 196608 + (i >> 2) * 2048 + ((i >> 1) & 1) * 128);
  }
  extern __shared__ __align__(1024) uint8_t smem[];
  if (smem_u32(smem) != SB) __trap();
  const int warp = __shfl_sync(~0u, threadIdx.x >> 5, 0);

  if (bid >= NCTA) {
    constexpr uint32_t XV = SM_WPHI, ONES = SM_ZT, BF = bar, BE = bar + 48, BX = bar + 96;
    constexpr int NJ = (DM - GROWS) / 64;
    const int lane = lane_id(), sp = bid - NCTA;
    const uint32_t tag = ld_rlx(g_epoch + bid * 32 + lane) + 1;
    if (warp == 8 && elect_one()) {
#pragma unroll 1
      for (int i = 0; i < 13; i++) mbar_init(bar + 8 * i, i >= 6 && i < 12 ? 8 : 1);
    }
    if (warp == 9) { sts64u(sb + ONES + lane * 8, 0x3f803f80u, 0x3f803f80u); fence_async_smem(); }
    __syncthreads();
    if (warp == 8) {
      if (elect_one()) {
        uint32_t s = 0, ph = 1;
        for (const long long c0 = clock64(); clock64() - c0 < SP_DELAY;) {}
#pragma unroll 1
        for (int job = 0; job < 8; job++) {
          const CUtensorMap* m = job == 0 ? &mWq : sp & 2 ? &mU2 : &mG2;
          const int g0 = job ? (sp & 1) * 28 + job * 4 - 4 : sp * 4;
#pragma unroll 1
          for (int row = job ? GROWS : 0; row < DM; row += 64) {
            mbar_wait(BE + 8 * s, ph);
            mbar_expect_tx(BF + 8 * s, Q_STAGE);
            tma4d(sb + s * Q_STAGE, m, 0, row, g0, 0, BF + 8 * s);
            tma4d(sb + s * Q_STAGE + 16384, m, 0, row, g0 + 2, 0, BF + 8 * s);
            if (++s == 6) { s = 0; ph ^= 1; }
          }
        }
      }
    } else if (warp == 9) {
      uint4 xr[4];
      routed_row(P.x, tag, lane, xr);
#pragma unroll
      for (int i = 0; i < 4; i++) sts128u(sb + XV + i * 512 + lane * 16, xr[i].x, xr[i].y, xr[i].z, xr[i].w);
      fence_async_smem();
      __syncwarp();
      if (lane == 0) mbar_arrive(BX);
    } else if (warp < 8) {
      uint32_t s = 0, ph = 0;
#pragma unroll 1
      for (int job = 0; job < 8; job++) {
        float d[8] = {0.f, 0.f, 0.f, 0.f, 0.f, 0.f, 0.f, 0.f};
        if (job == 1) mbar_wait(BX, 0);
#pragma unroll 1
        for (int i = 0; i < (job ? NJ : 16); i++) {
          mbar_wait(BF + 8 * s, ph);
          wg_fence();
#pragma unroll
          for (int k = 0; k < 8; k++)
            wgmma_n8_ss_ta1_tb0(d + 4 * (k >> 2), mkdesc(sb + k * 2048, 16, 1024, 1, s * (Q_STAGE / 16) + (warp >> 2) * 1024),
                                mkdesc(sb, 16, 128, 0, job ? (XV + GROWS * 2) / 16 + i * 8 + (k & 3) * 2 : ONES / 16), 1);
          wg_commit();
          wg_wait<0>();
          if (lane == 0) mbar_arrive(BE + 8 * s);
          if (++s == 6) { s = 0; ph ^= 1; }
        }
        reg_fence<8>(d);
        float* dst = (job ? g_gp + sp * 1792 + job * 256 - 256 : g_cs + sp * 256) + (warp >> 2) * 128 + (warp & 3) * 16 + (lane >> 2);
        if ((lane & 3) == 0) {
#pragma unroll
          for (int i = 0; i < 4; i++) st_rlx(dst + (i >> 1) * 64 + (i & 1) * 8, mark(__float_as_uint(d[2 * i]), tag & 1));
        }
        __syncwarp();
      }
      if (warp == 0) g_epoch[bid * 32 + lane] = tag;
    }
    return;
  }
#define Q_SLAB(J) ((J) < 8 ? ((J) + 8 - 2 * (hg & 4)) & 15 : 2 * (hg & 4) + 2 * ((J) & 3) + ((J) >> 2 & 1))
#define Q_AOFF(J) ((J) == 8 + (hg & 3) ? SM_X0 : (J) == 12 + (hg & 3) ? SM_X1 : ((J) & 3) * Q_STAGE)
#define Q_LOAD(J)                                                                                            \
  do {                                                                                                       \
    const uint32_t fb_ = bar + B_FULLQ + 8 * ((J) & 3);                                                      \
    const int k_ = Q_SLAB(J) * 64;                                                                           \
    mbar_expect_tx(fb_, Q_STAGE);                                                                            \
    mbar_arrive2(fb_);                                                                                       \
    tma2d(sb + Q_AOFF(J), &mX, k_, mb * 128, fb_);                                                           \
    tma4d(sb + ((J) & 3) * Q_STAGE + 16384, &mWq, 0, k_, hg * 2, 0, fb_);                                    \
  } while (0)
  if (warp >= 8) {
    asm volatile("setmaxnreg.dec.sync.aligned.u32 %0;" ::"n"(REG_H));
    const int lane = lane_id();
    const int f = (warp - 9) & 3;
    if (f == 3) {
      if (elect_one()) {
        PROF(0); PROFT(32);
#pragma unroll
        for (int s = 0; s < 3; s++) mbar_init(bar + B_FULLKV + 8 * s, 1);
      }
      __syncwarp();
      asm volatile("bar.arrive 14, 288;" ::: "memory");
      if (elect_one()) {
#pragma unroll
        for (int s = 0; s < 2; s++) {
          mbar_expect_tx(bar + B_FULLKV + 8 * s, KV_STAGE);
          tma2d(sb + s * KV_STAGE, &mX, (s + 1) * 64, mb * 128, bar + B_FULLKV + 8 * s);
          tma4d(sb + s * KV_STAGE + 16384, &mWkv, 0, (s + 1) * 64, hg * 2, 1, bar + B_FULLKV + 8 * s);
        }
      }
      __syncwarp();
    }
    const uint32_t ep = ld_rlx(g_epoch + bid * 32 + lane);
    if (f < 2) {
#pragma unroll
      for (int i = 0; i < 2; i++) {
        const uint4 u = __ldg((const uint4*)P.w_r + (f * 2 + i) * 32 + lane);
        sts128u(sb + SM_XSEL + (f * 2 + i) * 512 + lane * 16, u.x, u.y, u.z, u.w);
      }
    }
    bar_sync(13, 384);
    const uint32_t tag = ep + 1, par = tag & 1;
    const bool ffn = bid < NFFN;
    const int fb = bid, cu = bid >> 1, ch = bid & 1;
#define CS_STORE(SEC, C)                                                                                     \
  _Pragma("unroll") for (int r = 0; r < 3; r++) {                                                            \
    const uint32_t h0 = pack2(C.x, C.y), h1 = pack2(C.z, C.w);                                               \
    sts64u(sb + SM_CST + (SEC) * 1024 + (lane >> 4) * 512 + (lane & 1) * 8 + r * 128 + ((((lane & 15) >> 1) ^ (r + (lane >> 4) * 4)) << 4), h0, h1); \
    C.x -= bf_lo(h0); C.y -= bf_hi(h0); C.z -= bf_lo(h1); C.w -= bf_hi(h1);                                  \
  }
#define BAD4(U) ((U.x ^ par) | (U.y ^ par) | (U.z ^ par) | (U.w ^ par))
    const int n0 = f < 2 ? 0 : 2 * f - 3, ne = FFN_OFF || !ffn ? 3 : f == 3 ? 3 + G8 : 3 + GN;
    const uint32_t fsb = sb + SM_FST + ((f + 1) & 3) * 8192, fbar = bar + B_FST + f * 16, fst = fsb + (lane >> 4) * 2048 + (lane & 15) * 16;
    const CUtensorMap *ma = &mWc, *mc = &mWc;
    int sx = 1024 + cu * 32, sy = ch * 512 + f * 192, sdy = 32;
#define STAGEG(N)                                                                                            \
  do {                                                                                                       \
    if ((N) == 3) { ma = &mG; mc = &mU; sx = fb * 32; sy = f * (GN * 32);  sdy = 0; }                        \
    if ((N) < ne && elect_one()) {                                                                           \
      const uint32_t dst_ = fsb + ((N) & 1) * 4096, b_ = fbar + ((N) & 1) * 8;                               \
      mbar_expect_tx(b_, 4096);                                                                              \
      tma2d(dst_, ma, sx, sy, b_);                                                                           \
      tma2d(dst_ + 2048, mc, sx, sy + sdy, b_);                                                              \
    }                                                                                                        \
    sy += 32 + sdy;                                                                                          \
  } while (0)
    float a[8], gsum = 0.f, usum = 0.f;
    {
      if (f == 3) {
        if (elect_one()) {
          if (XS_EARLY) { mbar_expect_tx(bar + B_XST, 16384); tma3d(sb + SM_XST, &mXs, 0, bid * 16, 0, bar + B_XST); }
          mbar_expect_tx(bar + B_WPHI, 8192);
          tma2d(sb + SM_WPHI, &mPhi, 0, hg * 128, bar + B_WPHI);
          prefetch_map(&mWq); prefetch_map(&mWo); prefetch_map(&mWp); prefetch_map(&mD);
          PROF(31);
        }
        __syncwarp();
      } else {
        if (lane == 0) prefetch_map(f == 0 ? &mWc : f == 1 ? &mG : &mU);
        if (f == 2) ((float2*)g_y[par])[bid * 32 + lane] = make_float2(0.f, 0.f);
      }
      float st[13];
#pragma unroll
      for (int i = 0; i < 13; i++) st[i] = 0.f;
#pragma unroll 1
      for (int i = 0; i < 4; i++) {
        mbar_wait(bar + B_XST + 8 * (i >> 1), 0);
        if (f == 0 && lane == 0 && i == 0) PROF(1);
        const uint4 wu = lds128u(sb + SM_XSEL + i * 512 + lane * 16);
        const float wf[8] = {bf_lo(wu.x), bf_hi(wu.x), bf_lo(wu.y), bf_hi(wu.y), bf_lo(wu.z), bf_hi(wu.z), bf_lo(wu.w), bf_hi(wu.w)};
        st[12] += ((wf[0] + wf[1]) + (wf[2] + wf[3])) + ((wf[4] + wf[5]) + (wf[6] + wf[7]));
#pragma unroll
        for (int r = 0; r < 4; r++) {
          const uint4 u = lds128u(sb + SM_XST + i * 8192 + (4 * f + r) * 512 + lane * 16);
          const float xf[8] = {bf_lo(u.x), bf_hi(u.x), bf_lo(u.y), bf_hi(u.y), bf_lo(u.z), bf_hi(u.z), bf_lo(u.w), bf_hi(u.w)};
#pragma unroll
          for (int k = 0; k < 8; k++) { st[r] += xf[k]; st[4 + r] = fmaf(xf[k], xf[k], st[4 + r]); st[8 + r] = fmaf(xf[k], wf[k], st[8 + r]); }
        }
        if (i >= 2 && f < 3) STAGEG(n0 + i - 2);
      }
      const bool up = lane & 16, up2 = lane & 8;
#pragma unroll
      for (int q = 0; q < 3; q++) {
        const float k0 = up ? st[4 * q + 2] : st[4 * q], k1 = up ? st[4 * q + 3] : st[4 * q + 1];
        const float o0 = up ? st[4 * q] : st[4 * q + 2], o1 = up ? st[4 * q + 1] : st[4 * q + 3];
        const float m0 = k0 + __shfl_xor_sync(~0u, o0, 16), m1 = k1 + __shfl_xor_sync(~0u, o1, 16);
        a[q] = (up2 ? m1 : m0) + __shfl_xor_sync(~0u, up2 ? m0 : m1, 8);
      }
      a[3] = st[12] + __shfl_xor_sync(~0u, st[12], 16);
      a[3] += __shfl_xor_sync(~0u, a[3], 8);
#pragma unroll
      for (int o = 4; o; o >>= 1)
#pragma unroll
        for (int q = 0; q < 4; q++) a[q] += __shfl_xor_sync(~0u, a[q], o);
      if ((lane & 7) == 0) sts128(sb + SM_ROWS + (4 * f + (lane >> 3)) * 16, a[0], a[1], a[2], a[3]);
      if (f < 3) asm volatile("bar.arrive 7, 128;" ::: "memory");
    }
    if (f == 3) {
      bar_sync(7, 128);
      const int row = bid * 16 + (lane & 15);
      const float4 v = lds128(sb + SM_ROWS + (lane & 15) * 16);
      const float mf = v.x * (1.f / DM), mean = bf_round(mf), var = fmaxf(fmaf(-mf, mf, v.y * (1.f / DM)), 0.f);
      const float sd = bf_round(sqrt_approx(bf_round(bf_round(var) + 1e-5f)));
      const uint32_t rb = pack2(fmaf(-mean, v.w, v.z) * rcp(sd), 0.f) & 0xffffu, ord = (rb & 0x8000u) ? (~rb & 0xffffu) : (rb | 0x8000u);
      uint32_t best = __reduce_max_sync(~0u, (ord << 16) | (uint32_t)(2047 - row));
      if (lane < 16) st_rlx64(g_stat + row, ((unsigned long long)tag << 32) | __float_as_uint(mean) | (__float_as_uint(sd) >> 16));
      if (lane == 0) { asm volatile("red.relaxed.gpu.global.max.u64 [%0], %1;" ::"l"(g_best + bid), "l"(((unsigned long long)tag << 32) | best) : "memory"); PROF(17); }
#pragma unroll 1
      for (int n = 3; n < 5; n++) STAGEG(n);
      {
        uint4 xr[4];
        best = routed_row(P.x, tag, lane, xr);
#pragma unroll
        for (int i = 0; i < (GROWS + 255) / 256; i++) {
          const uint32_t dst = sb + SM_XSEL + i * 1024 + (lane >> 2) * 128 + (lane & 3) * 8;
          sts64(dst, bf_lo(xr[i].x), bf_lo(xr[i].z)); sts64(dst + 32, bf_hi(xr[i].x), bf_hi(xr[i].z));
          sts64(dst + 64, bf_lo(xr[i].y), bf_lo(xr[i].w)); sts64(dst + 96, bf_hi(xr[i].y), bf_hi(xr[i].w));
        }
        sts64u(sb + SM_RED + 16, tag, best);
        __syncwarp();
        if (lane == 0) { mbar_arrive(bar + B_XS); PROF(19); }
      }
      unsigned long long sv4[4];
      uint4 u[4];
#pragma unroll 1
      for (int it = 0; it < SPIN_MAX; it++) {
#pragma unroll
        for (int i = 0; i < 4; i++) { u[i] = ld_rlx128(g_cs + (1 + i) * 1024 + hg * 128 + lane * 4); sv4[i] = ld_rlx64(g_stat + mb * 128 + i * 32 + lane); }
        bool ok = ((BAD4(u[0]) | BAD4(u[1]) | BAD4(u[2]) | BAD4(u[3])) & 1) == 0;
#pragma unroll
        for (int i = 0; i < 4; i++) ok = ok && (uint32_t)(sv4[i] >> 32) == tag;
        if (__all_sync(~0u, ok)) break;
        __nanosleep(200);
      }
#pragma unroll
      for (int i = 0; i < 4; i++) {
        const uint32_t sv = (uint32_t)sv4[i], sd2 = (sv << 16) | (sv & 0xffffu);
        sts64(sb + SM_STAT + (i * 32 + lane) * 8, -bf_hi(sv), rcp(bf_lo(sv)));
        sts128u(sb + SM_SDT + lane * 64 + ((i ^ ((lane >> 1) & 3)) << 4), sd2, sd2, sd2, sd2);
      }
#pragma unroll
      for (int i = 0; i < 2; i++) {
        float4 c = make_float4(unmark(u[i].x) + unmark(u[i + 2].x), unmark(u[i].y) + unmark(u[i + 2].y), unmark(u[i].z) + unmark(u[i + 2].z),
                               unmark(u[i].w) + unmark(u[i + 2].w));
        CS_STORE(i, c);
      }
      fence_async_smem();
      bar_sync(8, 64);
      if (lane == 0) { mbar_arrive(bar + B_CS); PROF(10); }
    }
    {
      uint32_t xa = sb + SM_RED + 32, xstep = 0;
      const uint32_t zero = __float_as_uint(lds32(sb + SM_RED + 12));
#pragma unroll 1
      for (int ph = f == 3; ph < 2; ph++) {
#pragma unroll
        for (int j = 0; j < 8; j++) a[j] = 0.f;
        if (ph && f == 0) {
        {
          mbar_wait(bar + B_WPHI, 0);
          float nq[8] = {0.f, 0.f, 0.f, 0.f, 0.f, 0.f, 0.f, 0.f};
  #pragma unroll 2
          for (int r = 0; r < 16; r++) {
            const uint4 u = lds128u(sb + SM_WPHI + ((lane >> 2) * 16 + r) * 64 + (((lane ^ (r >> 1)) & 3) << 4));
            nq[0] = fmaf(bf_lo(u.x), bf_lo(u.x), nq[0]); nq[1] = fmaf(bf_hi(u.x), bf_hi(u.x), nq[1]); nq[2] = fmaf(bf_lo(u.y), bf_lo(u.y), nq[2]);
            nq[3] = fmaf(bf_hi(u.y), bf_hi(u.y), nq[3]); nq[4] = fmaf(bf_lo(u.z), bf_lo(u.z), nq[4]); nq[5] = fmaf(bf_hi(u.z), bf_hi(u.z), nq[5]);
            nq[6] = fmaf(bf_lo(u.w), bf_lo(u.w), nq[6]); nq[7] = fmaf(bf_hi(u.w), bf_hi(u.w), nq[7]);
          }
          uint32_t m = 0;
  #pragma unroll
          for (int i = 0; i < 8; i++) m = max(m, __float_as_uint(nq[i] + __shfl_xor_sync(~0u, nq[i], 4)) & 0x7fffffffu);
          sts32(sb + SM_RED + 24, 4.2f * __uint_as_float(__reduce_max_sync(~0u, m)));
        }
          asm volatile("bar.arrive 8, 64;" ::: "memory");
        }
        if (ph) { mbar_wait(bar + B_XS, 0); xa = sb + SM_XSEL + f * (GN * 128) + ((lane >> 2) & 3) * 32; xstep = 128; }
#pragma unroll 1
        for (int n = ph ? 3 : n0; n < (ph ? ne : 3); n++) {
          const float4 x0 = lds128(xa), x1 = lds128(xa + 16);
          xa += xstep;
          mbar_wait(fbar + (n & 1) * 8, ((n - n0) >> 1) & 1);
          uint4 u[8];
#pragma unroll
          for (int j = 0; j < 8; j++) u[j] = lds128u(fst + (n & 1) * 4096 + j * 256);
          FMA8(a, u[0], x0.x); FMA8(a, u[1], x0.y); FMA8(a, u[2], x0.z); FMA8(a, u[3], x0.w);
          if (__any_sync(~0u, ((u[4].x | u[5].x | u[6].x | u[7].x | __float_as_uint(a[0]) | __float_as_uint(a[7])) & zero) == 0)) STAGEG(n + 2);
          FMA8(a, u[4], x1.x); FMA8(a, u[5], x1.y); FMA8(a, u[6], x1.z); FMA8(a, u[7], x1.w);
        }
#pragma unroll
        for (int o = 4; o <= 8; o <<= 1)
#pragma unroll
          for (int j = 0; j < 8; j++) a[j] += __shfl_xor_sync(~0u, a[j], o);
        if (ph && lane == 0) mbar_arrive(bar + B_FFN);
        const uint32_t red = ph ? sb + SM_GRED : sb + SM_RED + 64;
        if ((lane & 12) == 0) {
          const uint32_t d = red + f * 256 + (lane >> 4) * 128 + (lane & 3) * 32;
          sts128(d, a[0], a[1], a[2], a[3]); sts128(d + 16, a[4], a[5], a[6], a[7]);
        }
        if (f != 2) {
          asm volatile("bar.arrive %0, %1;" ::"r"(4 + ph), "r"(96 + 32 * ph) : "memory");
        } else {
          bar_sync(4 + ph, 96 + 32 * ph);
          const uint32_t ra = red + lane * 4;
          gsum = lds32(ra) + lds32(ra + 256) + lds32(ra + 512);
          usum = lds32(ra + 128) + lds32(ra + 384) + lds32(ra + 640);
          if (!ph) st_rlx(g_cs + 1024 + ch * 2048 + cu * 32 + lane, mark(__float_as_uint(gsum + usum), par));
          else { gsum += lds32(ra + 768); usum += lds32(ra + 896); }
          if (lane == 0) PROF(ph ? 34 : 18);
        }
      }
    }
    if (f == 3) {
      if (elect_one()) {
        PROF(7);
        mbar_wait(bar + B_FULLQ, 0);
#pragma unroll 1
        for (int j = 3; j < 16; j++) {
          mbar_wait(bar + (j < 4 ? B_EMPTYKV + 16 : B_EMPTYQ + 8 * (j & 3)), ((j >> 2) & 1) ^ 1);
          if (j == 12 + (hg & 3)) mbar_wait(bar + B_KVST + 8, 0);
          Q_LOAD(j);
        }
        PROF(47);
        mbar_expect_tx(bar + B_DN, 65536);
#pragma unroll 1
        for (int i = 0; i < 4; i++) {
          mbar_wait(bar + B_EMPTYQ + 8 * i, 1);
          tma3d(sb + i * Q_STAGE, &mD, 0, fb * 32, i * 4, bar + B_DN);
        }
        PROF(48);
#pragma unroll 1
        for (int i = 0; i < 16; i++) {
          const int s = i & 3, n = i < 9 ? i - 2 : i - 9, kb = i < 2 ? 2 * hg + i : 2 * (n + (n >= hg)) + (i >= 9);
          if (i >= 4) mbar_wait(bar + B_EMPTYQ + 8 * s, ((i >> 2) & 1) ^ 1);
          mbar_expect_tx(bar + B_FULLQ + 8 * s, 16384);
          if (i < 2) {
            mbar_arrive2(bar + B_FULLQ + 8 * s);
            tma3d(sb + s * Q_STAGE + 16384, &mWo, 0, kb * 64, hg * 2, bar + B_FULLQ + 8 * s);
          } else {
            tma5d(sb + s * Q_STAGE + 16384, &mWp, hg * 128, kb * 2, bar + B_FULLQ + 8 * s);
            tma5d(sb + s * Q_STAGE + 24576, &mWp, hg * 128 + 64, kb * 2, bar + B_FULLQ + 8 * s);
            if (i >= 3) {
              if (i == 3) { mbar_wait(bar + B_DND, 0); PROF(14); }
#pragma unroll 1
              for (int a = i == 3 ? 2 : i; a <= i; a++) {
                const uint4* src = g_ofr + (mb * 16 + (a == 2 ? (hg == 0 ? 2 : 0) : kb)) * 1024;
#pragma unroll
                for (int h = 0; h < 2; h++) {
                  mbar_expect_tx(bar + B_AIN + (a & 3) * 16 + h * 8, 8192);
                  bulk_load(sb + (a & 3) * Q_STAGE + h * 8192, src + h * 512, 8192, bar + B_AIN + (a & 3) * 16 + h * 8);
                }
              }
            }
          }
        }
      }
    } else {
      if (f == 2) {
        if (PFD && ffn) {
#pragma unroll 1
          for (int i = 0; i < 16; i++) { touch_l2((const char*)P.w_down + fb * 65536 + i * 4096 + lane * 128, lane); __nanosleep(PFD); }
        }
        if (WOT) {
#pragma unroll 1
          for (int i = 0; i < 8; i++) { touch_l2((const char*)P.wo + ((mb & 7) * 128 + i * 16 + (lane >> 1)) * 2048 + hg * 256 + (lane & 1) * 128, lane); __nanosleep(PFD); }
        }
        asm volatile("cp.async.wait_all;" ::: "memory");
        uint4 u;
#pragma unroll 1
        for (int it = 0; it < SPIN_MAX; it++) {
          u = ld_rlx128(g_cs + hg * 128 + lane * 4);
          if (__all_sync(~0u, !(BAD4(u) & 1))) break;
          __nanosleep(200);
        }
        mbar_wait(bar + B_PHI, 0);
        float4 c = make_float4(unmark(u.x), unmark(u.y), unmark(u.z), unmark(u.w));
        CS_STORE(2, c);
        fence_async_smem();
        __syncwarp();
        if (lane == 0) mbar_arrive(bar + B_CSQ);
      }
      const uint32_t target = __shfl_sync(~0u, tag, 0) * 16;
#pragma unroll 1
      for (int R = 0; R < 2; R++) {
        const uint32_t own = (hg * 2 + R) * 16 + mb, pst = sb + (R ? SM_PST1 : SM_PST0);
        if (f == R) {
          mbar_wait(bar + B_KVST + 8 * R, 0);
          if (f == 1 && lane == 0) PROF(11);
          wait_hint(g_xcnt + hg * 64 + R * 16 + mb, target);
          if (elect_one()) {
            PROF(35 + R);
            fence_async_global();
            mbar_expect_tx(bar + B_PART + 8 * R, 8192);
            bulk_load(pst, g_part + own * 512, 8192, bar + B_PART + 8 * R);
          }
          __syncwarp();
          uint4 uz;
#pragma unroll 1
          for (int it = 0; it < SPIN_MAX; it++) {
            uz = ld_rlx128(g_zpart + own * 128 + lane * 4);
            if (__all_sync(~0u, !(BAD4(uz) & 1))) break;
          }
          const bool b1 = lane & 2, b2 = lane & 4;
          const float z0 = unmark(b1 ? uz.z : uz.x) + __shfl_xor_sync(~0u, unmark(b1 ? uz.x : uz.z), 2);
          const float z1 = unmark(b1 ? uz.w : uz.y) + __shfl_xor_sync(~0u, unmark(b1 ? uz.y : uz.w), 2);
          float z = (b2 ? z1 : z0) + __shfl_xor_sync(~0u, b2 ? z0 : z1, 4);
          z += __shfl_xor_sync(~0u, z, 8);
          z += __shfl_xor_sync(~0u, z, 16);
          if (lane < 8) st_rlx(g_zres + own * 8 + (lane & 1) * 4 + (lane & 2) + (lane >> 2), mark(__float_as_uint(z), par));
          if (HOP2_HINT && lane == 0) red_inc(g_xcnt + hg * 64 + 32 + R * 16);
          __syncwarp();
        }
        if (f == R || f == R + 1) {
          const uint32_t hf = f - R, m1 = ~lane & 1, gq = hf * 4 + (lane >> 3), ts = (lane >> 1) & 3;
          float a0 = 0.f, a1 = 0.f, a2 = 0.f, a3 = 0.f;
          mbar_wait(bar + B_PART + 8 * R, 0);
#pragma unroll 1
          for (int it = 0; it < SPIN_MAX; it++) {
            uint32_t bad = 0;
            a0 = a1 = a2 = a3 = 0.f;
#pragma unroll 1
            for (int b = 0; b < 16; b += 8) {
              uint2 u[8];
              if (it == 0) {
#pragma unroll
                for (int i = 0; i < 8; i++) { const float2 v = lds64(pst + (b + i) * 512 + hf * 256 + lane * 8); u[i] = make_uint2(__float_as_uint(v.x), __float_as_uint(v.y)); }
              } else {
#pragma unroll
                for (int i = 0; i < 8; i++) {
                  const unsigned long long v = ld_rlx64((const unsigned long long*)g_part + own * 1024 + (b + i) * 64 + hf * 32 + lane);
                  u[i] = make_uint2((uint32_t)v, (uint32_t)(v >> 32));
                }
              }
#pragma unroll
              for (int i = 0; i < 8; i++) {
                bad |= u[i].x ^ par;
                a0 += bf_lo(i & 1 ? u[i].x & ~m1 : u[i].x | m1); a1 += bf_hi(u[i].x); a2 += bf_lo(u[i].y); a3 += bf_hi(u[i].y);
              }
            }
            if (__all_sync(~0u, !(bad & m1))) break;
          }
          uint32_t* dst = (uint32_t*)g_res[par] + own * 128 + gq * 16 + ts;
          const uint32_t j0 = (lane & 1) * 2, vb = ts == 0;
          st_rlx(dst + ((j0 ^ (gq >> 1)) & 3) * 4, pack2(a0, a1) | vb);
          st_rlx(dst + (((j0 + 1) ^ (gq >> 1)) & 3) * 4, pack2(a2, a3) | vb);
          ((uint2*)g_res[par ^ 1])[own * 64 + hf * 32 + lane] = make_uint2(0u, 0u);
          __syncwarp();
          if (lane == 0) { if (HOP2_HINT) red_inc(g_xcnt + hg * 64 + 32 + R * 16); if (!hf) PROF(R ? 12 : 30); }
        }
      }
      if (f == 2) {
        if (ffn && !FFN_OFF) {
#pragma unroll 1
          for (int it = 0; it < SPIN_MAX; it++) {
            const uint32_t pg = ld_rlx((const uint32_t*)g_gp + fb * 32 + lane), pu = ld_rlx((const uint32_t*)g_gp + FF + fb * 32 + lane);
            if (__all_sync(~0u, !(((pg ^ par) | (pu ^ par)) & 1))) { gsum += unmark(pg); usum += unmark(pu); break; }
            __nanosleep(200);
          }
        }
        const float h = bf_round(silu_f(bf_round(gsum))) * bf_round(usum);
        const uint32_t h2 = pack2(h, h);
        sts128u(sb + SM_HT + lane * 16, h2, h2, h2, h2);
        fence_async_smem();
        __syncwarp();
        if (lane == 0) { mbar_arrive(bar + B_H); PROF(20); }
      }
      if (f < 2) {
        if (HOP2_HINT) wait_hint(g_xcnt + hg * 64 + 32 + f * 16, 3 * target);
        mbar_wait(bar + B_KVST + 8, 0);
        if (lane == 0) PROF(40 + f);
#pragma unroll 1
        for (int it = 0; it < SPIN_MAX; it++) {
          if (elect_one()) {
            fence_async_global();
            mbar_expect_tx(bar + B_RES + 8 * f, 8192);
            bulk_load(sb + SM_V + f * 8192, g_res[par] + (hg * 4 + f * 2) * 256, 8192, bar + B_RES + 8 * f);
          }
          __syncwarp();
          const uint4 uz = ld_rlx128(g_zres + (hg * 4 + f * 2) * 64 + lane * 4);
          const uint32_t zw[4] = {uz.x, uz.y, uz.z, uz.w};
#pragma unroll
          for (int j = 0; j < 4; j++) {
            const uint32_t zz = pack2(unmark(zw[j]), 1.f), row = (lane & 3) * 4 + j;
            sts128u(sb + SM_ZT + (2 * f + (lane >> 4)) * 1024 + row * 64 + ((((lane >> 2) ^ (row >> 1)) & 3) << 4), zz, zz, zz, zz);
          }
          uint32_t bad = BAD4(uz);
          mbar_wait(bar + B_RES + 8 * f, it & 1);
#pragma unroll
          for (int i = 0; i < 16; i++) bad |= ~__float_as_uint(lds32(sb + SM_V + f * 8192 + i * 512 + lane * 16));
          if (__all_sync(~0u, !(bad & 1))) break;
        }
        fence_async_smem();
        __syncwarp();
        if (lane == 0) { mbar_arrive(bar + B_TILE + 8 * f); PROF(f ? 13 : 27); }
      }
      if (f < 2) {
        uint32_t phases = 0;
#pragma unroll 1
        for (int i = 2; i < 16; i++) {
          const int s = i & 3;
          const uint32_t ab = bar + B_AIN + s * 16 + f * 8, slot = sb + s * Q_STAGE + f * 8192;
#pragma unroll 1
          for (int it = 0; it < SPIN_MAX; it++) {
            mbar_wait(ab, (phases >> s) & 1);
            phases ^= 1u << s;
            uint32_t bad = 0;
#pragma unroll
            for (int n = 0; n < (NOVAL ? 0 : 8); n++) bad |= __float_as_uint(lds32(slot + n * 1024 + lane * 32 + (lane >> 2) * 4)) ^ par;
            if (__all_sync(~0u, !(bad & 1))) break;
            if (elect_one()) {
              const int n = i < 9 ? i - 2 : i - 9, kb = 2 * (n + (n >= hg)) + (i >= 9);
              PROF(49);
              mbar_expect_tx(ab, 8192);
              bulk_load(slot, g_ofr + (mb * 16 + kb) * 1024 + f * 512, 8192, ab);
            }
            __syncwarp();
          }
          if (lane == 0) { mbar_arrive(bar + B_FULLQ + 8 * s); if (i == 2 && f == 0) PROF(15); }
        }
        if (f == 0) g_epoch[bid * 32 + lane] = tag;
      } else {
        if (elect_one()) {
          prefetch_map(&mOut);
          if (ffn) { mbar_wait(bar + B_YD, 0); red_rel(g_ycnt); PROF(21); }
        }
        __syncwarp();
        if (f == 2) {
          const uint32_t best = __float_as_uint(lds32(sb + SM_RED + 20));
          const int sel = 2047 - (best & 0x7ff) - mb * 128;
          if (sel >= 0 && sel < 128) {
            const uint2 xr = __ldg((const uint2*)(P.x + (size_t)(mb * 128 + sel) * DM + hg * 128 + lane * 4));
            const float2 st = lds64(sb + SM_STAT + sel * 8);
            const uint32_t ord = best >> 16, rb = (ord & 0x8000u) ? (ord & 0x7fffu) : (~ord & 0xffffu);
            const float sg = rcp(1.f + ex2(-1.4426950408889634f * bf_lo(rb)));
            const uint32_t sg2 = pack2(sg, sg), nm2 = pack2(st.x, st.x);
            wait_cnt<0>(g_ycnt, tag * NFFN);
            float4 y = make_float4(0.f, 0.f, 0.f, 0.f);
#pragma unroll
            for (int i = 0; i < 8; i++) {
              const float4 c = ldg_cg4(g_y[par ^ 1][i] + hg * 128 + lane * 4);
              y.x += c.x; y.y += c.y; y.z += c.z; y.w += c.w;
            }
            uint32_t o[2];
#pragma unroll
            for (int i = 0; i < 2; i++) {
              const uint32_t d = badd2(i ? xr.y : xr.x, nm2);
              const uint32_t tt = badd2(pack2(bf_lo(d) * st.y, bf_hi(d) * st.y), bmul2(i ? pack2(y.z, y.w) : pack2(y.x, y.y), sg2));
              o[i] = pack2(silu_f(bf_lo(tt)), silu_f(bf_hi(tt)));
            }
            sts64u(sb + SM_UPD + lane * 8, o[0], o[1]);
          }
          if (lane == 0) sts32(sb + SM_UPD + 256, __int_as_float(sel));
          __syncwarp();
          if (lane == 0) { mbar_arrive(bar + B_UPD); PROF(22); }
        }
      }
    }
  } else {
    const int t7 = threadIdx.x & 127;
    const char* pfa = warp < 4 ? (const char*)P.x + bid * 32768 + (t7 & 15) * 2048 + (t7 >> 4) * 128
                               : (const char*)P.wqkv + (size_t)((t7 >> 4) * 64 + (bid >> 1)) * 6144 + 2048 + (bid & 1) * 2048 + (t7 & 15) * 128;
    if (t7 >= 16 && t7 < 16 * PF_FIRST) prefetch_l2(pfa);
    if (warp < 7) sts128(sb + SM_CST + threadIdx.x * 16, 0.f, 0.f, 0.f, 0.f);
    else sts32(sb + SM_RED + (threadIdx.x & 15) * 4, threadIdx.x & 8 ? 1.f : 0.f);
    if (elect_one()) {
#pragma unroll 1
      for (uint32_t b = B_FST + warp * 8; b < B_END; b += 64)
        mbar_init(bar + b, b < B_FULLQ ? 1 : b < B_FFN ? 3 : b < B_EMPTYKV ? 4 : 8);
    }
    __syncwarp();
    asm volatile("bar.arrive 13, 384;" ::: "memory");
    asm volatile("setmaxnreg.inc.sync.aligned.u32 %0;" ::"n"(REG_C));
    if (t7 >= 16 * PF_FIRST && threadIdx.x < 128 + 16 * PF_W) prefetch_l2(pfa);
    asm volatile("cp.async.wait_all;" ::: "memory");
    fence_async_smem();
    bar_sync(14, 288);
    if (threadIdx.x == 0) mbar_arrive(bar + B_FULLKV + 16);
    const int lane = lane_id();
    const int wg = warp >> 2, w = warp & 3, g = lane >> 2, t = lane & 3;
    float kv[128];
    {
      uint32_t s = 2, ph = 0, sp = 0, php = 0;
#pragma unroll 1
      for (int j = 0; j < 15; j++) {
        PW0(32 + j); mbar_wait(bar + B_FULLKV + 8 * s, ph); PW1(32 + j);
        if (wg == 1 && (ORDER_ALL || j == 0)) bar_sync(10 + s, 256);
        wg_fence();
        wgmma_n256_ssp_ta0_tb1(kv, mkdesc(sb, 16, 1024, 1, wg * 512 + s * (KV_STAGE / 16)), mkdesc(sb + 16384, 8192, 1024, 1, s * (KV_STAGE / 16)), j);
#pragma unroll
        for (int k = 1; k < 4; k++)
          wgmma_n256_ss_ta0_tb1(kv, mkdesc(sb + k * 32, 16, 1024, 1, wg * 512 + s * (KV_STAGE / 16)),
                                mkdesc(sb + 16384 + k * 2048, 8192, 1024, 1, s * (KV_STAGE / 16)), 1);
        wg_commit();
        if (wg == 0 && (ORDER_ALL || j == 0)) asm volatile("bar.arrive %0, 256;" ::"r"(10 + s) : "memory");
        if (warp == 0 && j) {
          mbar_wait(bar + B_EMPTYKV + 8 * sp, php);
          if (elect_one()) {
            if (j < 14) {
              mbar_expect_tx(bar + B_FULLKV + 8 * sp, KV_STAGE);
              tma2d(sb + sp * KV_STAGE, &mX, (j + 2) * 64, mb * 128, bar + B_FULLKV + 8 * sp);
              tma4d(sb + sp * KV_STAGE + 16384, &mWkv, 0, (j + 2) * 64, hg * 2, 1, bar + B_FULLKV + 8 * sp);
            } else {
              Q_LOAD(0);
            }
            if (j < 3 - XS_EARLY) {
              const int xh = j - 1 + XS_EARLY;
              mbar_expect_tx(bar + B_XST + 8 * xh, 16384);
              tma3d(sb + SM_XST + xh * 16384, &mXs, 0, bid * 16, 2 * xh, bar + B_XST + 8 * xh);
            }
          }
          __syncwarp();
        }
        if (j == 0) {
          if (wg == 0) prefetch_l2(pfa + 1024);
        } else if (wg == 1) {
          if (j < 3) {
            if (j == 2 || t7 >= 16 * PF_W) prefetch_l2(pfa + (j - 1) * (8 * 393216));
          } else if (j == 13) {
            prefetch_l2((const char*)P.wo + bid * 16384 + t7 * 128);
          }
          if (PFG && !FFN_OFF && bid < NFFN && j >= 2 && j < 2 + GROWS / 64 && w < 2)
            touch_l2((const char*)((bid & 1) ? P.w_up : P.w_gate) + (size_t)((0x852a7419630ull >> (4 * j - 8) & 15) * 64 + t7) * 7168 + (bid >> 1) * 128, lane);
        }
        wg_wait<0>();
        if (lane == 0) mbar_arrive(bar + B_EMPTYKV + 8 * s);
        sp = s; php = ph;
        ph ^= s == 1;
        s = s == 2 ? 0 : s + 1;
      }
    }
    const int lrow = wg * 64 + w * 16 + (lane & 15);
    const uint32_t sw128 = lrow * 128, x128 = (lrow & 7), hi16 = lane >> 4;
    mbar_wait(bar + B_CS, 0);
    const uint32_t tag = __float_as_uint(lds32(sb + SM_RED + 16));
    const int zero = __float_as_int(lds32(sb + SM_RED + 12));
    const float wn = lds32(sb + SM_RED + 24);
    const float2 st0 = lds64(sb + SM_STAT + (wg * 64 + w * 16 + g) * 8), st1 = lds64(sb + SM_STAT + (wg * 64 + w * 16 + g + 8) * 8);
    const float c0 = st0.y * 1.4426950408889634f, c1 = st1.y * 1.4426950408889634f;
    const uint32_t nm20 = pack2(st0.x, st0.x), nm21 = pack2(st1.x, st1.x), fmask = t == 0 ? ~0u : t == 1 ? 0xffffu : 0u;
    const uint32_t fa0 = nm20 & fmask, fa1 = nm21 & fmask;
    asm volatile("cp.async.wait_all;" ::: "memory");
    PW0(47); mbar_wait(bar + B_FULLKV + 16, 1); PW1(47);
    wg_fence();
    wgmma_n256_rs_ta0_tb1(kv, fa0, fa1, 0u, 0u, mkdesc(sb + SM_CST, 512, 0, 1), 1);
#pragma unroll
    for (int k = 0; k < 4; k++)
      wgmma_n256_ss_ta0_tb1(kv, mkdesc(sb + 2 * KV_STAGE + k * 32, 16, 1024, 1, wg * 512), mkdesc(sb + 2 * KV_STAGE + 16384 + k * 2048, 8192, 1024, 1), 1);
    wg_commit();
    if (warp == 0) {
      mbar_wait(bar + B_EMPTYKV + 8, 0);
      if (elect_one()) {
#pragma unroll 1
        for (int j = 1; j < 3; j++) Q_LOAD(j);
      }
      __syncwarp();
    }
    wg_wait<0>();
    reg_fence<128>(kv);
    if (lane == 0) mbar_arrive(bar + B_EMPTYKV + 16);
    PROFC(2);
    float q[64];
#define QMMA(J, AOFF16, ACCUM)                                                                                     \
  _Pragma("unroll") for (int k = 0; k < 4; k++)                                                                    \
      wgmma_n128_ss_ta0_tb1(q, mkdesc(sb + k * 32, 16, 1024, 1, wg * 512 + (AOFF16)),                              \
                            mkdesc(sb + 16384 + k * 2048, 8192, 1024, 1, ((J) & 3) * (Q_STAGE / 16)), k ? 1 : (ACCUM))
#define QWAIT(J) do { PW0(J); mbar_wait(bar + B_FULLQ + 8 * ((J) & 3), ((J) >> 2) & 1); PW1(J); } while (0)
#define QSTEP_A(J, AOFF16, ACCUM) do { QWAIT(J); wg_fence(); QMMA(J, AOFF16, ACCUM); wg_commit(); } while (0)
#define QREL(J) do { if (lane == 0) mbar_arrive(bar + B_EMPTYQ + 8 * ((J) & 3)); } while (0)
#define Q_OFF16(J) ((J) >= 8 && (J) < 16 ? Q_AOFF(J) / 16 : ((J) & 3) * (Q_STAGE / 16))
#define QPLAIN(J) do { QSTEP_A(J, Q_OFF16(J), 1); wg_wait<1>(); QREL((J) - 1); } while (0)
#define QNEXT(J) do { QPLAIN(J); SCHED_FENCE(); } while (0)
#define PHI_PROJ(DST, SRC, H0, H1)                                                                                 \
  do {                                                                                                             \
    uint32_t a_[32];                                                                                               \
    _Pragma("unroll") for (int j = 8 * (H0); j < 8 * (H1); j++) {                                                  \
      a_[j] = pack2(SRC[2 * j], SRC[2 * j + 1]);                                                                   \
      asm volatile("fma.rn.bf16x2 %0, %1, %1, %0;" : "+r"(nq[(j >> 4) * 2 + (j & 1)]) : "r"(a_[j]));               \
    }                                                                                                              \
    wg_fence();                                                                                                    \
    _Pragma("unroll") for (int hk = 2 * (H0); hk < 2 * (H1); hk++)                                                 \
        wgmma_n32_rs_ta0_tb1(DST + 16 * (hk >> 1), a_[4 * hk], a_[4 * hk + 1], a_[4 * hk + 2], a_[4 * hk + 3],     \
                             mkdesc(sb + SM_WPHI + hk * 1024, 16, 512, 2), hk & 1);                                \
    wg_commit();                                                                                                   \
  } while (0)
    {
      float p[64], ea[24], eb[24], sa[4], sc[4], kz[20];
      uint32_t vp[32];
#pragma unroll
      for (int j = 0; j < 32; j++) vp[j] = pack2(kv[64 + 2 * j], kv[65 + 2 * j]);
      const uint32_t vr = w * 16 + (lane & 15), vb = sb + SM_V + wg * 4096 + vr * 64, x64 = (vr >> 1) & 3;
#define V_STORE(R)                                                                                           \
  _Pragma("unroll") for (int j = 0; j < 4; j++)                                                              \
      stsm4(vb + (j >> 1) * 8192 + ((((j & 1) * 2 + hi16) ^ x64) << 4), vp[16 * (R) + 4 * j], vp[16 * (R) + 4 * j + 1], vp[16 * (R) + 4 * j + 2], vp[16 * (R) + 4 * j + 3])
      V_STORE(0);
      mbar_wait(bar + B_WPHI, 0);
      {
        uint32_t nq[4] = {0u, 0u, 0u, 0u};
        PHI_PROJ(p, kv, 0, 4);
        QSTEP_A(0, 0, 0);
        const bool unsafe = softmax_unsafe(nq, c0 * c0 * wn, c1 * c1 * wn);
        wg_wait<1>();
        reg_fence<64>(p);
        if (__builtin_expect(unsafe, 0)) softmax_shift(p, c0, c1);
      }
#define K_NORM(S) do { quad_sum<4>(S); _Pragma("unroll") for (int i = 0; i < 4; i++) S[i] = rcp(S[i]) * ((i & 1) ? st1.y : st0.y); } while (0)
#define K_STORE(SLOT, E, S) K_STORE_(SLOT, E, S, 0, 2)
#define K_STORE_(SLOT, E, S, J0, J1)                                                                         \
  _Pragma("unroll") for (int j = (J0); j < (J1); j++) {                                                      \
    uint32_t fp[4], fm[4];                                                                                   \
    _Pragma("unroll") for (int i = 0; i < 4; i++) {                                                          \
      const float e0 = E[8 * j + 2 * i], e1 = E[8 * j + 2 * i + 1], r = E[16 + 4 * j + i] * S[2 + (i & 1)];  \
      const uint32_t e2 = pack2(e0, e1);                                                                     \
      fp[i] = bmul2(e2, pack2(S[i & 1], S[i & 1]));                                                          \
      fm[i] = bmul2(e2, pack2(r, r));                                                                        \
    }                                                                                                        \
    stsm4(sb + SM_PHI + (SLOT) * 16384 + sw128 + (((2 * j + hi16) ^ x128) << 4), fp[0], fp[1], fp[2], fp[3]); \
    stsm4(sb + SM_PHI + (SLOT) * 16384 + sw128 + (((4 + 2 * j + hi16) ^ x128) << 4), fm[0], fm[1], fm[2], fm[3]); \
  }
#define KV_MMA(R)                                                                                            \
  do {                                                                                                       \
    mbar_wait(bar + B_PHI + 8 * (R), 0);                                                                     \
    wg_fence();                                                                                              \
    _Pragma("unroll") for (int k = 0; k < 8; k++) {                                                          \
      const uint32_t vs = SM_V + (k >> 2) * 4096 + (k & 3) * 1024;                                           \
      wgmma_n40_ss_ta1_tb1(kz, mkdesc(sb + SM_PHI + k * 2048, 16, 1024, 1, wg * 1024),                       \
                           mkdesc(sb + vs, SM_SDT + (k & 1) * 1024 + (k >> 1) * 16 - vs, 512, 2, wg * (512u - (512u << 16))), k); \
    }                                                                                                        \
    wg_commit();                                                                                             \
  } while (0)
#define QKV(J, R) do { KV_MMA(R); QSTEP_A(J, Q_OFF16(J), 1); wg_wait<2>(); QREL((J) - 1); SCHED_FENCE(); } while (0)
#define KV_SEND(R)                                                                                           \
  do {                                                                                                       \
    reg_fence<20>(kz);                                                                                       \
    if (lane == 0) mbar_arrive(bar + B_KVST + 8 * (R));                                                      \
    const uint32_t slot = ((hg * 2 + (R)) * 16 + warp * 2) * 16 + mb;                                        \
    _Pragma("unroll") for (int u = 0; u < 2; u++)                                                            \
      st_rlx128(g_part + (slot + u * 16) * 32 + lane, mark(pack2(kz[2 * u], kz[2 * u + 1]), tag & 1), pack2(kz[2 * u + 4], kz[2 * u + 5]), \
                pack2(kz[2 * u + 8], kz[2 * u + 9]), pack2(kz[2 * u + 12], kz[2 * u + 13]));                 \
    if (t < 2) st_rlx(g_zpart + (slot + t * 16) * 8 + g, mark(__float_as_uint(t ? kz[18] : kz[16]), tag & 1)); \
    if (lane < 2) red_inc(g_xcnt + hg * 64 + (R) * 16 + warp * 2 + lane);                                    \
  } while (0)
#define K_PUB(R) do { fence_async_smem(); __syncwarp(); if (lane == 0) mbar_arrive(bar + B_PHI + 8 * (R)); } while (0)
#define S_PIN(S) SCHED_PIN(S[0] + S[1] + S[2] + S[3])
      k_exp(p, c0, c1, ea, sa);
      S_PIN(sa);
      QNEXT(1);
      K_NORM(sa);
      k_exp<0, 4>(p + 16, c0, c1, eb, sc);
      mbar_wait(bar + B_FFN, 0);
      K_STORE_(0, ea, sa, 0, 1);
      S_PIN(sc);
      QNEXT(2);
      K_STORE_(0, ea, sa, 1, 2);
      k_exp<4, 8>(p + 16, c0, c1, eb, sc);
      K_NORM(sc);
      S_PIN(sc);
      QNEXT(3);
      K_STORE(1, eb, sc);
      K_PUB(0);
      k_exp<0, 4>(p + 32, c0, c1, ea, sa);
      S_PIN(sa);
      QKV(4, 0);
      k_exp<4, 8>(p + 32, c0, c1, ea, sa);
      K_NORM(sa);
      k_exp<0, 4>(p + 48, c0, c1, eb, sc);
      SCHED_PIN(sa[0] + sa[1] + sa[2] + sa[3] + sc[2] + sc[3]);
      QNEXT(5);
      KV_SEND(0);
      k_exp<4, 8>(p + 48, c0, c1, eb, sc);
      S_PIN(sc);
      QNEXT(6);
      K_NORM(sc);
      mbar_wait(bar + B_KVST, 0);
      V_STORE(1);
      K_STORE(0, ea, sa);
      QNEXT(7);
      K_STORE(1, eb, sc);
      K_PUB(1);
      QKV(8, 1);
      QNEXT(9);
      KV_SEND(1);
    }
#define JQ0 10
    PROFC(3);
#pragma unroll 1
    for (int j = JQ0; j < 15; j++) QPLAIN(j);
    mbar_wait(bar + B_CSQ, 0);
    QWAIT(15);
    if (wg == 1) bar_sync(6, 256);
    wg_fence();
    wgmma_n128_rs_ta0_tb1(q, fa0, fa1, 0u, 0u, mkdesc(sb + SM_CST + 2048, 512, 0, 1), 1);
    QMMA(15, Q_AOFF(15) / 16, 1);
    wg_commit();
    if (wg == 0) asm volatile("bar.arrive 6, 256;" ::: "memory");
    wg_wait<1>();
    QREL(14);
    wg_wait<0>();
    QREL(15);
    reg_fence<64>(q);
    PROFC(5);
    float yp[4];
    const uint32_t par = tag & 1;
    uint4* ofr = g_ofr + (mb * 16 + hg * 2) * 1024 + (warp * 16 + g) * 8;
#define O_MMA(H, F, N)                                                                                       \
  do {                                                                                                       \
    wg_fence();                                                                                              \
    _Pragma("unroll") for (int k = 0; k < 4; k++) {                                                          \
      const uint32_t ks = SM_V + (H) * 4096 + k * 1024;                                                      \
      wgmma_n40_rs_ta0_tb1(N + 20 * (k >> 1), F[4 * k], F[4 * k + 1], F[4 * k + 2], F[4 * k + 3],            \
                           mkdesc(sb + ks, SM_ZT + (H) * 1024 + k * 16 - ks, 512, 2), k & 1);                \
    }                                                                                                        \
    wg_commit();                                                                                             \
  } while (0)
#define O_FIN(H, N, o)                                                                                        \
  do {                                                                                                       \
    reg_fence<40>(N);                                                                                        \
    const float *np = N, *nm = N + 20;                                                                       \
    const float d0 = rcp(fmaf(np[16], nm[17], fmaf(nm[16], np[17], 1e-6f * np[17] * nm[17])));               \
    const float d1 = rcp(fmaf(np[18], nm[19], fmaf(nm[18], np[19], 1e-6f * np[19] * nm[19])));               \
    const float bp0 = nm[17] * d0, bm0 = np[17] * d0, bp1 = nm[19] * d1, bm1 = np[19] * d1;                  \
    _Pragma("unroll") for (int j = 0; j < 4; j++) {                                                          \
      o[2 * j] = pack2(fmaf(np[4 * j], bp0, nm[4 * j] * bm0), fmaf(np[4 * j + 1], bp0, nm[4 * j + 1] * bm0)); \
      o[2 * j + 1] = pack2(fmaf(np[4 * j + 2], bp1, nm[4 * j + 2] * bm1), fmaf(np[4 * j + 3], bp1, nm[4 * j + 3] * bm1)); \
    }                                                                                                        \
  } while (0)
#define O_STG(H, o)                                                                                          \
  _Pragma("unroll") for (int u = 0; u < 2; u++) {                                                            \
    uint32_t v_[4];                                                                                          \
    _Pragma("unroll") for (int j = 0; j < 4; j++) v_[j] = lop_select(o[2 * j + u], parm, vword == j);        \
    st_rlx128(ofr + ((H) >> 1) * 1024 + u * 64 + ((((H) & 1) * 4 + t) ^ g), v_[0], v_[1], v_[2], v_[3]);     \
  }
    uint32_t gf[32], ao[16];
    const uint32_t parm = 0u - par, vword = ((t ^ g) & 1) == (g >> 2) ? g & 3 : 4;
    const float rh0 = 0.5f * st0.y, rh1 = 0.5f * st1.y, mh0 = st0.x * rh0, mh1 = st1.x * rh1;
#define GATE_LD(J) ldsm4(sb + ((J) >> 2 ? SM_X1 : SM_X0) + sw128 + (((((J) & 3) * 2 + hi16) ^ x128) << 4), gf[4 * (J)], gf[4 * (J) + 1], gf[4 * (J) + 2], gf[4 * (J) + 3])
#define GATE(I0, I1)                                                                                         \
  _Pragma("unroll") for (int i = (I0); i < (I1); i++) {                                                      \
    const float rs = (i & 1) ? rh1 : rh0, mh = (i & 1) ? mh1 : mh0;                                          \
    const float h0 = fmaf(bf_lo(gf[i]), rs, mh), h1 = fmaf(bf_hi(gf[i]), rs, mh);                            \
    gf[i] = pack2(fmaf(h0, tanh_approx(h0), h0), fmaf(h1, tanh_approx(h1), h1));                             \
  }
#define GATE_PIN(I0, I1) do { uint32_t o_ = 0; _Pragma("unroll") for (int i = (I0); i < (I1); i++) o_ |= gf[i]; SCHED_PIN(__uint_as_float(o_)); } while (0)
    {
      float p[64], na[40], nb[40];
      uint32_t fa[16], fb[16];
      {
        uint32_t nq[4] = {0u, 0u, 0u, 0u};
        PHI_PROJ(p, q, 0, 2);
        SCHED_FENCE();
        PHI_PROJ(p, q, 2, 4);
        const bool unsafe = softmax_unsafe(nq, c0 * c0 * wn, c1 * c1 * wn);
        if (TW == 0) mbar_wait(bar + B_TILE, 0);
        wg_wait<0>();
        reg_fence<64>(p);
        PROFC(24);
        if (__builtin_expect(unsafe, 0)) softmax_shift(p, c0, c1);
      }
      float dn[32];
#define DN_PART(A, B)                                                                                        \
  do {                                                                                                       \
    wg_fence();                                                                                              \
    _Pragma("unroll") for (int i = (A); i < (B); i++)                                                        \
      wgmma_n8_ss_ta1_tb1(dn + 4 * (i >> 1), mkdesc(sb + (i >> 3) * Q_STAGE + (i & 7) * 2048, 16, 1024, 1, wg * (2 * Q_STAGE / 16)), \
                          mkdesc(sb + SM_HT + (i & 1) * 256, 128, 128, 0), i & 1);                           \
  } while (0)
#define F_PIN(F, A, B) do { uint32_t o_ = 0; _Pragma("unroll") for (int i = (A); i < (B); i++) o_ |= F[8 + i]; SCHED_PIN(__uint_as_float(o_)); } while (0)
#define RMMA(J, A, ACCUM)                                                                                    \
  do {                                                                                                       \
    wg_fence();                                                                                              \
    _Pragma("unroll") for (int k = 0; k < 4; k++)                                                            \
      wgmma_n128_rs_ta0_tb1(q, (A)[4 * k], (A)[4 * k + 1], (A)[4 * k + 2], (A)[4 * k + 3],                   \
                            mkdesc(sb + 16384 + k * 2048, 8192, 1024, 1, ((J) & 3) * (Q_STAGE / 16)), k ? 1 : (ACCUM)); \
    wg_commit();                                                                                             \
  } while (0)
#define RSTEP(J, A, ACCUM) do { QWAIT(J); RMMA(J, A, ACCUM); } while (0)
      PROFC(4);
      q_exp(p, c0, c1, fa);
      if (TW == 1) { F_PIN(fa, 0, 8); mbar_wait(bar + B_TILE, 0); }
      if (TW == 2) { q_exp(p + 16, c0, c1, fb); F_PIN(fb, 0, 8); mbar_wait(bar + B_TILE, 0); }
      O_MMA(0, fa, na);
      if (TW != 2) q_exp(p + 16, c0, c1, fb);
      O_MMA(1, fb, nb);
      PROFC(25);
      wg_wait<1>();
      O_FIN(0, na, ao);
      O_STG(0, ao);
      wg_wait<0>();
      O_FIN(1, nb, (ao + 8));
      O_STG(1, (ao + 8));
      PROFC(28);
      RSTEP(16, ao, 0);
      SCHED_FENCE();
      q_exp(p + 32, c0, c1, fa);
      F_PIN(fa, 0, 8);
      mbar_wait(bar + B_H, 0);
      mbar_wait(bar + B_DN, 0);
      PROFC(45);
      DN_PART(0, 4);
      SCHED_FENCE();
      q_exp<0, 2>(p + 48, c0, c1, fb);
      F_PIN(fb, 0, 2);
      DN_PART(4, 8);
      SCHED_FENCE();
      q_exp<2, 4>(p + 48, c0, c1, fb);
      F_PIN(fb, 2, 4);
      DN_PART(8, 12);
      SCHED_FENCE();
      q_exp<4, 6>(p + 48, c0, c1, fb);
      F_PIN(fb, 4, 6);
      DN_PART(12, 16);
      wg_commit();
      SCHED_FENCE();
      q_exp<6, 8>(p + 48, c0, c1, fb);
      F_PIN(fb, 6, 8);
      wg_wait<0>();
      reg_fence<32>(dn);
      if (lane == 0) mbar_arrive(bar + B_DND);
      QREL(16);
#pragma unroll
      for (int i = 0; i < 4; i++) yp[i] = t & 2 ? (t & 1 ? dn[24 + 2 * i] : dn[16 + 2 * i]) : (t & 1 ? dn[8 + 2 * i] : dn[2 * i]);
      PROFC(29);
      mbar_wait(bar + B_TILE + 8, 0);
      PROFC(23);
      if (bid < NFFN) {
        float* y = g_y[par ^ 1][bid & 7] + wg * 512 + t * 128 + w * 16 + g;
#pragma unroll
        for (int i = 0; i < 4; i++) red1(y + (i >> 1) * 64 + (i & 1) * 8, yp[i]);
      }
      SCHED_FENCE();
      O_MMA(2, fa, na);
      O_MMA(3, fb, nb);
      __syncwarp();
      if (lane == 0) mbar_arrive(bar + B_YD);
      wg_wait<1>();
      O_FIN(2, na, ao);
      O_STG(2, ao);
      wg_wait<0>();
      O_FIN(3, nb, (ao + 8));
      O_STG(3, (ao + 8));
      PROFC(6);
    }
    RSTEP(17, ao, 1);
    SCHED_FENCE();
    GATE_LD(0); GATE_LD(1);
    GATE(0, 4);
    GATE_PIN(0, 4);
#define GSTEP(J, I) do { QNEXT(J); if ((I) < 7) GATE_LD(((I) + 1) & 7); GATE(4 * (I), 4 * (I) + 4); GATE_PIN(4 * (I), 4 * (I) + 4); } while (0)
    GSTEP(18, 1); GSTEP(19, 2); GSTEP(20, 3); GSTEP(21, 4); GSTEP(22, 5); GSTEP(23, 6); GSTEP(24, 7);
#pragma unroll 1
    for (int j = 25; j < 32 - TAILN; j++) QPLAIN(j);
    if (wg == 1) bar_sync(6, 256);
#pragma unroll 1
    for (int j = 32 - TAILN; j < 32; j++) QSTEP_A(j, (j & 3) * (Q_STAGE / 16), 1);
    if (wg == 0) asm volatile("bar.arrive 6, 256;" ::: "memory");
    mbar_wait(bar + B_UPD, 0);
    {
      const int sel = __float_as_int(lds32(sb + SM_UPD + 256)) - (wg * 64 + w * 16 + g);
      if (sel == 0 || sel == 8) {
#pragma unroll
        for (int j = 0; j < 16; j++) {
          const uint32_t u = __float_as_uint(lds32(sb + SM_UPD + j * 16 + t * 4));
          if (sel) gf[2 * j + 1] = u; else gf[2 * j] = u;
        }
      }
      __syncwarp();
      uint32_t xf[32];
#pragma unroll
      for (int j = 0; j < 8; j++)
        ldsm4(sb + (j >> 2 ? SM_X1 : SM_X0) + sw128 + ((((j & 3) * 2 + hi16) ^ x128) << 4), xf[4 * j], xf[4 * j + 1], xf[4 * j + 2], xf[4 * j + 3]);
      wg_wait<0>();
      reg_fence<64>(q);
      PROFC(8);
#pragma unroll
      for (int j = 0; j < 8; j++) {
        uint32_t o[4];
#pragma unroll
        for (int i = 0; i < 4; i++) o[i] = badd2(xf[4 * j + i], bmul2(pack2(q[8 * j + 2 * i], q[8 * j + 2 * i + 1]), gf[4 * j + i]));
        stsm4(sb + (j >> 2 ? SM_X1 : SM_X0) + sw128 + ((((j & 3) * 2 + hi16) ^ x128) << 4), o[0], o[1], o[2], o[3]);
      }
    }
    fence_async_smem();
    bar_sync(2 + wg, 128);
    if (w == 0 && elect_one()) {
      tma_store2d(&mOut, sb + SM_X0 + wg * 8192, hg * 128, mb * 128 + wg * 64);
      tma_store2d(&mOut, sb + SM_X1 + wg * 8192, hg * 128 + 64, mb * 128 + wg * 64);
      bulk_commit();
      bulk_wait_read0();
      if (wg == 1) { PROF(9); PROFT(33); PROF_DUMP; }
    }
  }
}

typedef CUresult (*EncodeFn)(CUtensorMap*, CUtensorMapDataType, cuuint32_t, void*, const cuuint64_t*, const cuuint64_t*, const cuuint32_t*,
                             const cuuint32_t*, CUtensorMapInterleave, CUtensorMapSwizzle, CUtensorMapL2promotion, CUtensorMapFloatOOBfill);

CUtensorMap make_map(EncodeFn enc, const void* ptr, int rank, const cuuint64_t* dims, const cuuint64_t* strides, const cuuint32_t* box, CUtensorMapSwizzle sw) {
  CUtensorMap m;
  const cuuint32_t es[5] = {1, 1, 1, 1, 1};
  enc(&m, CU_TENSOR_MAP_DATA_TYPE_BFLOAT16, rank, (void*)ptr, dims, strides, box, es, CU_TENSOR_MAP_INTERLEAVE_NONE, sw,
      CU_TENSOR_MAP_L2_PROMOTION_L2_128B, CU_TENSOR_MAP_FLOAT_OOB_FILL_NONE);
  return m;
}

}

extern "C" void kernel_launch(void* const* d_in, const int* in_sizes, int n_in, void* d_out, int out_size) {
  static EncodeFn enc = nullptr;
  static int by_sm = 0;
  if (!enc) {
    void* fn = nullptr;
    cudaDriverEntryPointQueryResult qr;
    cudaGetDriverEntryPoint("cuTensorMapEncodeTiled", &fn, cudaEnableDefault, &qr);
    enc = (EncodeFn)fn;
    cudaFuncSetAttribute(fused_kernel<false>, cudaFuncAttributeMaxDynamicSharedMemorySize, SM_TOTAL);
    cudaFuncSetAttribute(fused_kernel<true>, cudaFuncAttributeMaxDynamicSharedMemorySize, SM_TOTAL);
    int dev = 0, sms = 0;
    cudaGetDevice(&dev);
    cudaDeviceGetAttribute(&sms, cudaDevAttrMultiProcessorCount, dev);
    by_sm = BY_SM && sms == NCTA + NSPARE;
  }
  Params P;
  P.x = (const __nv_bfloat16*)d_in[0];
  P.wqkv = (const __nv_bfloat16*)d_in[1];
  const void* wphi = d_in[2];
  P.wo = (const __nv_bfloat16*)d_in[3];
  P.w_r = (const __nv_bfloat16*)d_in[5];
  P.w_gate = (const __nv_bfloat16*)d_in[6];
  P.w_up = (const __nv_bfloat16*)d_in[7];
  P.w_down = (const __nv_bfloat16*)d_in[8];

  const cuuint64_t dX[2] = {DM, SEQ}, sX[1] = {DM * 2};
  const cuuint32_t b128[2] = {64, 128}, b64[2] = {64, 64};
  const cuuint64_t dW[4] = {64, DM, 16, 3}, sW[3] = {3 * DM * 2, 128, DM * 2};
  const cuuint32_t bKV[4] = {64, 64, 2, 2}, bQ[4] = {64, 64, 2, 1};
  const cuuint64_t dO[3] = {64, DM, 16}, sO[2] = {DM * 2, 128};
  const cuuint32_t bO[3] = {64, 64, 2};
  const cuuint64_t dP[2] = {32, 1024}, sP[1] = {64};
  const cuuint32_t bP[2] = {32, 128};
  CUtensorMap mX = make_map(enc, P.x, 2, dX, sX, b128, CU_TENSOR_MAP_SWIZZLE_128B);
  CUtensorMap mWkv = make_map(enc, P.wqkv, 4, dW, sW, bKV, CU_TENSOR_MAP_SWIZZLE_128B);
  CUtensorMap mWq = make_map(enc, P.wqkv, 4, dW, sW, bQ, CU_TENSOR_MAP_SWIZZLE_128B);
  CUtensorMap mWo = make_map(enc, P.wo, 3, dO, sO, bO, CU_TENSOR_MAP_SWIZZLE_128B);
  CUtensorMap mPhi = make_map(enc, wphi, 2, dP, sP, bP, CU_TENSOR_MAP_SWIZZLE_64B);
  const cuuint64_t dWp[5] = {DM, 2, 4, 4, DM / 32}, sWp[4] = {DM * 2, 8 * DM * 2, 2 * DM * 2, 32 * DM * 2};
  const cuuint32_t bWp[5] = {64, 2, 4, 4, 2};
  CUtensorMap mWp = make_map(enc, P.wo, 5, dWp, sWp, bWp, CU_TENSOR_MAP_SWIZZLE_128B);
  CUtensorMap mOut = make_map(enc, d_out, 2, dX, sX, b64, CU_TENSOR_MAP_SWIZZLE_128B);
  const cuuint64_t dWc[2] = {3 * DM, DM}, sWc[1] = {3 * DM * 2}, dG[2] = {FF, DM}, sG[1] = {FF * 2}, dD[3] = {64, FF, 16};
  const cuuint32_t b32[2] = {32, 32}, bD[3] = {64, 32, 4};
  CUtensorMap mWc = make_map(enc, P.wqkv, 2, dWc, sWc, b32, CU_TENSOR_MAP_SWIZZLE_NONE);
  CUtensorMap mG = make_map(enc, P.w_gate, 2, dG, sG, b32, CU_TENSOR_MAP_SWIZZLE_NONE);
  CUtensorMap mU = make_map(enc, P.w_up, 2, dG, sG, b32, CU_TENSOR_MAP_SWIZZLE_NONE);
  CUtensorMap mD = make_map(enc, P.w_down, 3, dD, sO, bD, CU_TENSOR_MAP_SWIZZLE_128B);
  const cuuint64_t dXs[3] = {256, SEQ, 4}, sXs[2] = {DM * 2, 512};
  const cuuint32_t bXs[3] = {256, 16, 2};
  CUtensorMap mXs = make_map(enc, P.x, 3, dXs, sXs, bXs, CU_TENSOR_MAP_SWIZZLE_NONE);
  const cuuint64_t dG2[4] = {64, DM, FF / 64, 1}, sG2[3] = {FF * 2, 128, (cuuint64_t)FF * DM * 2};
  CUtensorMap mG2 = make_map(enc, P.w_gate, 4, dG2, sG2, bQ, CU_TENSOR_MAP_SWIZZLE_128B);
  CUtensorMap mU2 = make_map(enc, P.w_up, 4, dG2, sG2, bQ, CU_TENSOR_MAP_SWIZZLE_128B);
  (by_sm ? fused_kernel<true> : fused_kernel<false>)<<<NCTA + NSPARE, 384, SM_TOTAL, cudaStreamPerThread>>>(mX, mWkv, mWq, mWo, mPhi, mWp, mOut, mWc, mG, mU, mD, mXs,
                                                                                                           mG2, mU2, P);
}
```

```cpp
#include <cuda_runtime.h>
#include <cuda_bf16.h>
#include <cuda.h>
#include <stdint.h>

namespace {

constexpr int SEQ = 2048, DM = 1024, FF = 3584;
constexpr int NCTA = 128;
constexpr int NSPARE = 4;
constexpr int NFFN = FF / 32;
#define GN 6
#define G8 2
constexpr int GROWS = (3 * GN + G8) * 32;
#define TAILN 2
#define KTAIL 1
#define XS_EARLY 1
#define PF_FIRST 2
#define PF_W 5
#define PF_PRE 1
#define PFG 0
#define PFD 80
#define BY_SM 1
#define PTAB 0x73216540u
#define ROWSPLIT 1
#define WOT 1
#define PSPLIT 1
#define KSTEPS 4
#define NOVAL 0
#define KCH 1
#define REG_C 224
#define REG_H 56
#define TW 2
#define FENCE_KIND 2
#define SP_DELAY 2000
#define HOP2_HINT 1
#define DNX 1
#define ORDER_ALL 1
#define AM_NS 100
constexpr bool FFN_OFF = false;

static_assert(2 * REG_C + REG_H <= 3 * 168, "the register pool of the CTA is 384 x 168");

__device__ uint32_t g_epoch[(NCTA + NSPARE) * 32];
__device__ unsigned long long g_stat[SEQ];
__device__ __align__(128) unsigned long long g_best[NCTA];
__device__ __align__(16) float g_y[2][8][DM];
__device__ __align__(128) uint32_t g_ycnt[64];
__device__ __align__(128) uint32_t g_xcnt[8 * 64];
__device__ __align__(128) uint4 g_res[2][32 * 256];
__device__ __align__(16) float g_cs[5 * DM];
__device__ __align__(128) float g_gp[2 * FF];
__device__ uint4 g_part[8 * 2 * 16 * 16 * 32];
__device__ __align__(16) float g_zpart[8 * 2 * 16 * 16 * 8];
__device__ __align__(128) float g_zres[32 * 64];
__device__ __align__(1024) uint4 g_ofr[16 * 16 * 1024];
#define PROF(i)
#define PROFT(i)
#define PROFC(i)
#define PROF_DUMP
#define PW0(J)
#define PW1(J)

constexpr uint32_t KV_STAGE = 49152, Q_STAGE = 32768;
constexpr uint32_t SM_V = 147456;
constexpr uint32_t SM_PHI = 163840;
constexpr uint32_t SM_XST = 147456;
constexpr uint32_t SM_FST = 172032;
constexpr uint32_t SM_PST0 = 196608, SM_PST1 = SM_PHI + 8192;
constexpr uint32_t SM_X0 = 131072, SM_X1 = SM_PHI + 16384;
constexpr uint32_t SM_WPHI = 204800;
constexpr uint32_t SM_ZT = 212992;
constexpr uint32_t SM_SDT = 217088;
constexpr uint32_t SM_CST = 219136;
constexpr uint32_t SM_HT = 222720;
constexpr uint32_t SM_STAT = 223232;
constexpr uint32_t SM_XSEL = 224256;
constexpr uint32_t SM_RED = 228352;
constexpr uint32_t SM_ROWS = SM_RED + 832;
constexpr uint32_t SM_GRED = SM_XSEL + 3072;
static_assert(GROWS <= 768, "xsel area");
constexpr uint32_t SM_UPD = 229632;
constexpr uint32_t SM_BAR = 230016;
constexpr uint32_t SM_PROF = 230464;
constexpr uint32_t SM_SINK = 231104;
constexpr uint32_t SM_TOTAL = 231616;
constexpr uint32_t SB = 1024;
constexpr uint32_t B_FULLKV = 0  , B_FST = 24  , B_XFULL = 88  , B_XST = 104  , B_WPHI = 120, B_CS = 128, B_CSQ = 136, B_UPD = 144,
                   B_H = 152, B_DN = 160, B_XS = 168, B_TILE = 176  , B_RES = 192  , B_PART = 208  ,
B_AIN = 224  ,
                   B_FULLQ = 288  ,
                   B_FFN = 320,
                   B_EMPTYKV = 328  , B_EMPTYQ = 352  , B_KVST = 384  , B_YD = 400, B_PHI = 408  , B_DND = 424, B_END = 432;

__device__ __forceinline__ uint32_t smem_u32(const void* p) { return (uint32_t)__cvta_generic_to_shared(p); }
__device__ __forceinline__ void mbar_init(uint32_t bar, uint32_t cnt) { asm volatile("mbarrier.init.shared::cta.b64 [%0], %1;" ::"r"(bar), "r"(cnt) : "memory"); }
__device__ __forceinline__ void mbar_expect_tx(uint32_t bar, uint32_t bytes) { asm volatile("mbarrier.arrive.expect_tx.shared::cta.b64 _, [%0], %1;" ::"r"(bar), "r"(bytes) : "memory"); }
__device__ __forceinline__ void mbar_arrive2(uint32_t bar) { asm volatile("mbarrier.arrive.shared::cta.b64 _, [%0], 2;" ::"r"(bar) : "memory"); }
__device__ __forceinline__ void mbar_arrive(uint32_t bar) { asm volatile("mbarrier.arrive.shared::cta.b64 _, [%0];" ::"r"(bar) : "memory"); }
__device__ __forceinline__ void mbar_wait(uint32_t bar, uint32_t parity) {
  asm volatile("{\n.reg .pred p;\nLW:\nmbarrier.try_wait.parity.shared::cta.b64 p, [%0], %1;\n@!p bra LW;\n}" ::"r"(bar), "r"(parity) : "memory");
}
__device__ __forceinline__ bool mbar_test(uint32_t bar, uint32_t parity) {
  uint32_t ok;
  asm volatile("{\n.reg .pred p;\nmbarrier.test_wait.parity.shared::cta.b64 p, [%1], %2;\nselp.u32 %0, 1, 0, p;\n}" : "=r"(ok) : "r"(bar), "r"(parity) : "memory");
  return ok;
}
__device__ __forceinline__ int lane_id() { int l; asm volatile("mov.u32 %0, %%laneid;" : "=r"(l)); return l; }
template <int C> __device__ __forceinline__ void sched_fence_(int zero) {
  asm volatile("{\n.reg .pred p;\nsetp.eq.s32 p, %0, %1;\n@p trap;\n}" ::"r"(zero), "n"(C) : "memory");
}
#define SCHED_FENCE() sched_fence_<1000 + __COUNTER__>(zero)
#define SCHED_PIN(V) sched_fence_<1000 + __COUNTER__>(zero & __float_as_int(V))
__device__ __forceinline__ bool elect_one() {
  uint32_t p; asm volatile("{ .reg .pred P; elect.sync _|P, 0xffffffff; selp.u32 %0, 1, 0, P; }" : "=r"(p)); return p;
}
__device__ __forceinline__ void tma2d(uint32_t dst, const CUtensorMap* m, int x, int y, uint32_t bar) {
  asm volatile("cp.async.bulk.tensor.2d.shared::cluster.global.mbarrier::complete_tx::bytes [%0], [%1, {%3, %4}], [%2];" ::"r"(dst), "l"(m), "r"(bar), "r"(x), "r"(y) : "memory");
}
__device__ __forceinline__ void tma3d(uint32_t dst, const CUtensorMap* m, int x, int y, int z, uint32_t bar) {
  asm volatile("cp.async.bulk.tensor.3d.shared::cluster.global.mbarrier::complete_tx::bytes [%0], [%1, {%3, %4, %5}], [%2];" ::"r"(dst), "l"(m), "r"(bar), "r"(x), "r"(y), "r"(z) : "memory");
}
__device__ __forceinline__ void tma4d(uint32_t dst, const CUtensorMap* m, int x, int y, int z, int w, uint32_t bar) {
  asm volatile("cp.async.bulk.tensor.4d.shared::cluster.global.mbarrier::complete_tx::bytes [%0], [%1, {%3, %4, %5, %6}], [%2];" ::"r"(dst), "l"(m), "r"(bar), "r"(x), "r"(y), "r"(z), "r"(w) : "memory");
}
__device__ __forceinline__ void tma5d(uint32_t dst, const CUtensorMap* m, int x, int v, uint32_t bar) {
  asm volatile("cp.async.bulk.tensor.5d.shared::cluster.global.mbarrier::complete_tx::bytes [%0], [%1, {%3, %5, %5, %5, %4}], [%2];" ::"r"(dst), "l"(m), "r"(bar), "r"(x), "r"(v), "r"(0) : "memory");
}
__device__ __forceinline__ void tma_store2d(const CUtensorMap* m, uint32_t src, int x, int y) {
  asm volatile("cp.async.bulk.tensor.2d.global.shared::cta.bulk_group [%0, {%2, %3}], [%1];" ::"l"(m), "r"(src), "r"(x), "r"(y) : "memory");
}
__device__ __forceinline__ void bulk_load(uint32_t dst, const void* src, uint32_t bytes, uint32_t bar) {
  asm volatile("cp.async.bulk.shared::cluster.global.mbarrier::complete_tx::bytes [%0], [%1], %2, [%3];" ::"r"(dst), "l"(src), "r"(bytes), "r"(bar) : "memory");
}
__device__ __forceinline__ void bulk_commit() { asm volatile("cp.async.bulk.commit_group;" ::: "memory"); }
__device__ __forceinline__ void bulk_wait0() { asm volatile("cp.async.bulk.wait_group 0;" ::: "memory"); }
__device__ __forceinline__ void bulk_wait_read0() { asm volatile("cp.async.bulk.wait_group.read 0;" ::: "memory"); }
__device__ __forceinline__ void prefetch_l2(const void* p) { asm volatile("prefetch.global.L2 [%0];" ::"l"(p) : "memory"); }
__device__ __forceinline__ void touch_l2(const void* p, int lane) { asm volatile("cp.async.cg.shared.global.L2::128B [%0], [%1], 16;" ::"r"(SB + SM_SINK + lane * 16), "l"(p) : "memory"); }
__device__ __forceinline__ void cp_async16(uint32_t dst, const void* src) { asm volatile("cp.async.cg.shared.global [%0], [%1], 16;" ::"r"(dst), "l"(src) : "memory"); }
__device__ __forceinline__ void prefetch_map(const CUtensorMap* m) { asm volatile("prefetch.tensormap [%0];" ::"l"(m) : "memory"); }
__device__ __forceinline__ void fence_async_smem() { asm volatile("fence.proxy.async.shared::cta;" ::: "memory"); }
__device__ __forceinline__ void fence_async_global() { asm volatile("fence.proxy.async.global;" ::: "memory"); }
__device__ __forceinline__ void bar_sync(int id, int n) { asm volatile("bar.sync %0, %1;" ::"r"(id), "r"(n) : "memory"); }
__device__ __forceinline__ void wg_fence() { asm volatile("wgmma.fence.sync.aligned;" ::: "memory"); }
__device__ __forceinline__ void wg_commit() { asm volatile("wgmma.commit_group.sync.aligned;" ::: "memory"); }
template <int N> __device__ __forceinline__ void wg_wait() { asm volatile("wgmma.wait_group.sync.aligned %0;" ::"n"(N) : "memory"); }
template <int N> __device__ __forceinline__ void reg_fence(uint32_t* r) {
#pragma unroll
  for (int i = 0; i < N; i++) asm volatile("" : "+r"(r[i])::"memory");
}
template <int N> __device__ __forceinline__ void reg_fence(float* r) {
#pragma unroll
  for (int i = 0; i < N; i++) asm volatile("" : "+f"(r[i])::"memory");
}
__device__ __forceinline__ uint64_t mkdesc(uint32_t addr, uint32_t lbo, uint32_t sbo, uint32_t swz, uint32_t dyn = 0) {
  const uint32_t lo = ((addr >> 4) | ((lbo >> 4) << 16)) + dyn;
  const uint32_t hi = (sbo >> 4) | (swz << 30);
  uint64_t d;
  asm("mov.b64 %0, {%1, %2};" : "=l"(d) : "r"(lo), "r"(hi));
  return d;
}
__device__ __forceinline__ void stsm4(uint32_t addr, uint32_t a, uint32_t b, uint32_t c, uint32_t d) {
  asm volatile("stmatrix.sync.aligned.m8n8.x4.shared.b16 [%0], {%1, %2, %3, %4};" ::"r"(addr), "r"(a), "r"(b), "r"(c), "r"(d) : "memory");
}
__device__ __forceinline__ void ldsm4(uint32_t addr, uint32_t& a, uint32_t& b, uint32_t& c, uint32_t& d) {
  asm volatile("ldmatrix.sync.aligned.m8n8.x4.shared.b16 {%0, %1, %2, %3}, [%4];" : "=r"(a), "=r"(b), "=r"(c), "=r"(d) : "r"(addr) : "memory");
}
__device__ __forceinline__ uint32_t pack2(float lo, float hi) { uint32_t r; asm("cvt.rn.bf16x2.f32 %0, %1, %2;" : "=r"(r) : "f"(hi), "f"(lo)); return r; }
__device__ __forceinline__ uint32_t bsub2(uint32_t a, uint32_t b) { uint32_t r; asm("sub.rn.bf16x2 %0, %1, %2;" : "=r"(r) : "r"(a), "r"(b)); return r; }
__device__ __forceinline__ uint32_t badd2(uint32_t a, uint32_t b) { uint32_t r; asm("add.rn.bf16x2 %0, %1, %2;" : "=r"(r) : "r"(a), "r"(b)); return r; }
__device__ __forceinline__ uint32_t bmul2(uint32_t a, uint32_t b) { uint32_t r; asm("mul.rn.bf16x2 %0, %1, %2;" : "=r"(r) : "r"(a), "r"(b)); return r; }
__device__ __forceinline__ float bf_lo(uint32_t v) { return __uint_as_float(v << 16); }
__device__ __forceinline__ float bf_hi(uint32_t v) { return __uint_as_float(v & 0xffff0000u); }
__device__ __forceinline__ float bf_round(float v) { return bf_lo(pack2(v, 0.f)); }
__device__ __forceinline__ float ex2(float v) { float r; asm("ex2.approx.ftz.f32 %0, %1;" : "=f"(r) : "f"(v)); return r; }
__device__ __forceinline__ float rcp(float v) { float r; asm("rcp.approx.ftz.f32 %0, %1;" : "=f"(r) : "f"(v)); return r; }
__device__ __forceinline__ float sqrt_approx(float v) { float r; asm("sqrt.approx.f32 %0, %1;" : "=f"(r) : "f"(v)); return r; }
__device__ __forceinline__ float4 lds128(uint32_t a) { float4 v; asm volatile("ld.shared.v4.f32 {%0, %1, %2, %3}, [%4];" : "=f"(v.x), "=f"(v.y), "=f"(v.z), "=f"(v.w) : "r"(a) : "memory"); return v; }
__device__ __forceinline__ uint4 lds128u(uint32_t a) { uint4 v; asm volatile("ld.shared.v4.u32 {%0, %1, %2, %3}, [%4];" : "=r"(v.x), "=r"(v.y), "=r"(v.z), "=r"(v.w) : "r"(a) : "memory"); return v; }
__device__ __forceinline__ float2 lds64(uint32_t a) { float2 v; asm volatile("ld.shared.v2.f32 {%0, %1}, [%2];" : "=f"(v.x), "=f"(v.y) : "r"(a) : "memory"); return v; }
__device__ __forceinline__ float lds32(uint32_t a) { float v; asm volatile("ld.shared.f32 %0, [%1];" : "=f"(v) : "r"(a) : "memory"); return v; }
__device__ __forceinline__ void sts32(uint32_t a, float v) { asm volatile("st.shared.f32 [%0], %1;" ::"r"(a), "f"(v) : "memory"); }
__device__ __forceinline__ void sts64(uint32_t a, float x, float y) { asm volatile("st.shared.v2.f32 [%0], {%1, %2};" ::"r"(a), "f"(x), "f"(y) : "memory"); }
__device__ __forceinline__ void sts128(uint32_t a, float x, float y, float z, float w) { asm volatile("st.shared.v4.f32 [%0], {%1, %2, %3, %4};" ::"r"(a), "f"(x), "f"(y), "f"(z), "f"(w) : "memory"); }
__device__ __forceinline__ void sts64u(uint32_t a, uint32_t x, uint32_t y) { asm volatile("st.shared.v2.u32 [%0], {%1, %2};" ::"r"(a), "r"(x), "r"(y) : "memory"); }
__device__ __forceinline__ void sts128u(uint32_t a, uint32_t x, uint32_t y, uint32_t z, uint32_t w) { asm volatile("st.shared.v4.u32 [%0], {%1, %2, %3, %4};" ::"r"(a), "r"(x), "r"(y), "r"(z), "r"(w) : "memory"); }
__device__ __forceinline__ uint4 ldg_nc(const void* p) { uint4 v; asm volatile("ld.global.nc.L1::no_allocate.v4.u32 {%0, %1, %2, %3}, [%4];" : "=r"(v.x), "=r"(v.y), "=r"(v.z), "=r"(v.w) : "l"(p)); return v; }
__device__ __forceinline__ float4 ldg_cg4(const float* p) { float4 v; asm volatile("ld.global.cg.v4.f32 {%0, %1, %2, %3}, [%4];" : "=f"(v.x), "=f"(v.y), "=f"(v.z), "=f"(v.w) : "l"(p) : "memory"); return v; }
__device__ __forceinline__ uint32_t ld_acq(const uint32_t* p) { uint32_t v; asm volatile("ld.acquire.gpu.global.u32 %0, [%1];" : "=r"(v) : "l"(p) : "memory"); return v; }
__device__ __forceinline__ uint32_t ld_acq_cta(uint32_t a) { uint32_t v; asm volatile("ld.acquire.cta.shared.u32 %0, [%1];" : "=r"(v) : "r"(a) : "memory"); return v; }
__device__ __forceinline__ void st_rel_cta(uint32_t a, uint32_t v) { asm volatile("st.release.cta.shared.u32 [%0], %1;" ::"r"(a), "r"(v) : "memory"); }
__device__ __forceinline__ unsigned long long ld_rlx64(const unsigned long long* p) { unsigned long long v; asm volatile("ld.relaxed.gpu.global.u64 %0, [%1];" : "=l"(v) : "l"(p) : "memory"); return v; }
__device__ __forceinline__ void st_rlx64(unsigned long long* p, unsigned long long v) { asm volatile("st.relaxed.gpu.global.u64 [%0], %1;" ::"l"(p), "l"(v) : "memory"); }
__device__ __forceinline__ uint4 ld_rlx128(const void* p) {
  uint4 v;
  asm volatile("{ .reg .b128 t; .reg .b64 a, b; ld.relaxed.gpu.global.b128 t, [%4]; mov.b128 {a, b}, t; mov.b64 {%0, %1}, a; mov.b64 {%2, %3}, b; }"
               : "=r"(v.x), "=r"(v.y), "=r"(v.z), "=r"(v.w) : "l"(p) : "memory");
  return v;
}
__device__ __forceinline__ void st_rlx128(void* p, uint32_t x, uint32_t y, uint32_t z, uint32_t w) {
  asm volatile("{ .reg .b128 t; .reg .b64 a, b; mov.b64 a, {%1, %2}; mov.b64 b, {%3, %4}; mov.b128 t, {a, b}; st.relaxed.gpu.global.b128 [%0], t; }"
               ::"l"(p), "r"(x), "r"(y), "r"(z), "r"(w) : "memory");
}
__device__ __forceinline__ void stg128(void* p, uint32_t x, uint32_t y, uint32_t z, uint32_t w) { asm volatile("st.global.v4.u32 [%0], {%1, %2, %3, %4};" ::"l"(p), "r"(x), "r"(y), "r"(z), "r"(w) : "memory"); }
__device__ __forceinline__ void st_rlx(void* p, uint32_t v) { asm volatile("st.relaxed.gpu.global.u32 [%0], %1;" ::"l"(p), "r"(v) : "memory"); }
__device__ __forceinline__ uint32_t lop_select(uint32_t a, uint32_t b, uint32_t m) { uint32_t r; asm("lop3.b32 %0, %1, %2, %3, 0xd8;" : "=r"(r) : "r"(a), "r"(b), "r"(m)); return r; }
__device__ __forceinline__ float unmark(uint32_t v) { return __uint_as_float(v & ~1u); }
__device__ __forceinline__ uint32_t mark(uint32_t v, uint32_t par) { return (v & ~1u) | par; }
__device__ __forceinline__ float tanh_approx(float v) { float r; asm("tanh.approx.f32 %0, %1;" : "=f"(r) : "f"(v)); return r; }
__device__ __forceinline__ void flag_rel(uint32_t* p, uint32_t v) { asm volatile("red.release.gpu.global.max.u32 [%0], %1;" ::"l"(p), "r"(v) : "memory"); }
__device__ __forceinline__ void red1(float* p, float a) { asm volatile("red.global.add.f32 [%0], %1;" ::"l"(p), "f"(a) : "memory"); }
__device__ __forceinline__ void red_inc(uint32_t* p) { asm volatile("red.relaxed.gpu.global.add.u32 [%0], 1;" ::"l"(p) : "memory"); }
__device__ __forceinline__ void red_rel(uint32_t* p) { asm volatile("red.release.gpu.global.add.u32 [%0], 1;" ::"l"(p) : "memory"); }
__device__ __forceinline__ void red4(float* p, float a, float b, float c, float d) { asm volatile("red.global.add.v4.f32 [%0], {%1, %2, %3, %4};" ::"l"(p), "f"(a), "f"(b), "f"(c), "f"(d) : "memory"); }
constexpr int SPIN_MAX = 100000;
__device__ __forceinline__ uint32_t ld_rlx(const uint32_t* p) { uint32_t v; asm volatile("ld.relaxed.gpu.global.u32 %0, [%1];" : "=r"(v) : "l"(p) : "memory"); return v; }
template <int NS = 0> __device__ __forceinline__ void wait_hint(const uint32_t* p, uint32_t target) {
#pragma unroll 1
  for (int i = 0; i < SPIN_MAX; i++) { if ((int)(ld_rlx(p) - target) >= 0) break; if (NS) __nanosleep(NS); }
}
template <int NS> __device__ __forceinline__ void wait_cnt(const uint32_t* p, uint32_t target) {
#pragma unroll 1
  for (int i = 0; i < SPIN_MAX; i++) { if ((int)(ld_rlx(p) - target) >= 0) break; if (NS) __nanosleep(NS); }
  (void)ld_acq(p);
}
template <int NS> __device__ __forceinline__ unsigned long long wait_tag(const unsigned long long* p, uint32_t tag) {
  unsigned long long v = 0;
#pragma unroll 1
  for (int i = 0; i < SPIN_MAX; i++) { v = ld_rlx64(p); if ((uint32_t)(v >> 32) == tag) break; if (NS) __nanosleep(NS); }
  return v;
}
__device__ __forceinline__ float silu_f(float v) { return v * rcp(1.f + ex2(-1.4426950408889634f * v)); }

__device__ __forceinline__ void wgmma_n8_ss_ta1_tb0(float* d, uint64_t da, uint64_t db, bool accumulate) {
  if (accumulate) {
    asm volatile("{\n.reg .pred p;\nsetp.ne.b32 p, 1, 0;\n"
      "wgmma.mma_async.sync.aligned.m64n8k16.f32.bf16.bf16 "
      "{%0, %1, %2, %3}, "
      "%4, %5, p, 1, 1, 1, 0;\n}\n"
      : "+f"(d[0]), "+f"(d[1]), "+f"(d[2]), "+f"(d[3])
      : "l"(da), "l"(db));
  } else {
    asm volatile("{\n.reg .pred p;\nsetp.ne.b32 p, 0, 0;\n"
      "wgmma.mma_async.sync.aligned.m64n8k16.f32.bf16.bf16 "
      "{%0, %1, %2, %3}, "
      "%4, %5, p, 1, 1, 1, 0;\n}\n"
      : "=f"(d[0]), "=f"(d[1]), "=f"(d[2]), "=f"(d[3])
      : "l"(da), "l"(db));
  }
}
__device__ __forceinline__ void wgmma_n8_ss_ta1_tb1(float* d, uint64_t da, uint64_t db, bool accumulate) {
  if (accumulate) {
    asm volatile("{\n.reg .pred p;\nsetp.ne.b32 p, 1, 0;\n"
      "wgmma.mma_async.sync.aligned.m64n8k16.f32.bf16.bf16 "
      "{%0, %1, %2, %3}, "
      "%4, %5, p, 1, 1, 1, 1;\n}\n"
      : "+f"(d[0]), "+f"(d[1]), "+f"(d[2]), "+f"(d[3])
      : "l"(da), "l"(db));
  } else {
    asm volatile("{\n.reg .pred p;\nsetp.ne.b32 p, 0, 0;\n"
      "wgmma.mma_async.sync.aligned.m64n8k16.f32.bf16.bf16 "
      "{%0, %1, %2, %3}, "
      "%4, %5, p, 1, 1, 1, 1;\n}\n"
      : "=f"(d[0]), "=f"(d[1]), "=f"(d[2]), "=f"(d[3])
      : "l"(da), "l"(db));
  }
}
__device__ __forceinline__ void wgmma_n32_rs_ta0_tb1(float* d, uint32_t a0, uint32_t a1, uint32_t a2, uint32_t a3, uint64_t db, bool accumulate) {
  if (accumulate) {
    asm volatile("{\n.reg .pred p;\nsetp.ne.b32 p, 1, 0;\n"
      "wgmma.mma_async.sync.aligned.m64n32k16.f32.bf16.bf16 "
      "{%0, %1, %2, %3, %4, %5, %6, %7, %8, %9, %10, %11, %12, %13, %14, %15}, "
      "{%16, %17, %18, %19}, %20, p, 1, 1, 1;\n}\n"
      : "+f"(d[0]), "+f"(d[1]), "+f"(d[2]), "+f"(d[3]), "+f"(d[4]), "+f"(d[5]), "+f"(d[6]), "+f"(d[7]), "+f"(d[8]), "+f"(d[9]), "+f"(d[10]), "+f"(d[11]), "+f"(d[12]), "+f"(d[13]), "+f"(d[14]), "+f"(d[15])
      : "r"(a0), "r"(a1), "r"(a2), "r"(a3), "l"(db));
  } else {
    asm volatile("{\n.reg .pred p;\nsetp.ne.b32 p, 0, 0;\n"
      "wgmma.mma_async.sync.aligned.m64n32k16.f32.bf16.bf16 "
      "{%0, %1, %2, %3, %4, %5, %6, %7, %8, %9, %10, %11, %12, %13, %14, %15}, "
      "{%16, %17, %18, %19}, %20, p, 1, 1, 1;\n}\n"
      : "=f"(d[0]), "=f"(d[1]), "=f"(d[2]), "=f"(d[3]), "=f"(d[4]), "=f"(d[5]), "=f"(d[6]), "=f"(d[7]), "=f"(d[8]), "=f"(d[9]), "=f"(d[10]), "=f"(d[11]), "=f"(d[12]), "=f"(d[13]), "=f"(d[14]), "=f"(d[15])
      : "r"(a0), "r"(a1), "r"(a2), "r"(a3), "l"(db));
  }
}
__device__ __forceinline__ void wgmma_n40_rs_ta0_tb1(float* d, uint32_t a0, uint32_t a1, uint32_t a2, uint32_t a3, uint64_t db, bool accumulate) {
  if (accumulate) {
    asm volatile("{\n.reg .pred p;\nsetp.ne.b32 p, 1, 0;\n"
      "wgmma.mma_async.sync.aligned.m64n40k16.f32.bf16.bf16 "
      "{%0, %1, %2, %3, %4, %5, %6, %7, %8, %9, %10, %11, %12, %13, %14, %15, %16, %17, %18, %19}, "
      "{%20, %21, %22, %23}, %24, p, 1, 1, 1;\n}\n"
      : "+f"(d[0]), "+f"(d[1]), "+f"(d[2]), "+f"(d[3]), "+f"(d[4]), "+f"(d[5]), "+f"(d[6]), "+f"(d[7]), "+f"(d[8]), "+f"(d[9]), "+f"(d[10]), "+f"(d[11]), "+f"(d[12]), "+f"(d[13]), "+f"(d[14]), "+f"(d[15]), "+f"(d[16]), "+f"(d[17]), "+f"(d[18]), "+f"(d[19])
      : "r"(a0), "r"(a1), "r"(a2), "r"(a3), "l"(db));
  } else {
    asm volatile("{\n.reg .pred p;\nsetp.ne.b32 p, 0, 0;\n"
      "wgmma.mma_async.sync.aligned.m64n40k16.f32.bf16.bf16 "
      "{%0, %1, %2, %3, %4, %5, %6, %7, %8, %9, %10, %11, %12, %13, %14, %15, %16, %17, %18, %19}, "
      "{%20, %21, %22, %23}, %24, p, 1, 1, 1;\n}\n"
      : "=f"(d[0]), "=f"(d[1]), "=f"(d[2]), "=f"(d[3]), "=f"(d[4]), "=f"(d[5]), "=f"(d[6]), "=f"(d[7]), "=f"(d[8]), "=f"(d[9]), "=f"(d[10]), "=f"(d[11]), "=f"(d[12]), "=f"(d[13]), "=f"(d[14]), "=f"(d[15]), "=f"(d[16]), "=f"(d[17]), "=f"(d[18]), "=f"(d[19])
      : "r"(a0), "r"(a1), "r"(a2), "r"(a3), "l"(db));
  }
}
__device__ __forceinline__ void wgmma_n40_ss_ta1_tb1(float* d, uint64_t da, uint64_t db, bool accumulate) {
  if (accumulate) {
    asm volatile("{\n.reg .pred p;\nsetp.ne.b32 p, 1, 0;\n"
      "wgmma.mma_async.sync.aligned.m64n40k16.f32.bf16.bf16 "
      "{%0, %1, %2, %3, %4, %5, %6, %7, %8, %9, %10, %11, %12, %13, %14, %15, %16, %17, %18, %19}, "
      "%20, %21, p, 1, 1, 1, 1;\n}\n"
      : "+f"(d[0]), "+f"(d[1]), "+f"(d[2]), "+f"(d[3]), "+f"(d[4]), "+f"(d[5]), "+f"(d[6]), "+f"(d[7]), "+f"(d[8]), "+f"(d[9]), "+f"(d[10]), "+f"(d[11]), "+f"(d[12]), "+f"(d[13]), "+f"(d[14]), "+f"(d[15]), "+f"(d[16]), "+f"(d[17]), "+f"(d[18]), "+f"(d[19])
      : "l"(da), "l"(db));
  } else {
    asm volatile("{\n.reg .pred p;\nsetp.ne.b32 p, 0, 0;\n"
      "wgmma.mma_async.sync.aligned.m64n40k16.f32.bf16.bf16 "
      "{%0, %1, %2, %3, %4, %5, %6, %7, %8, %9, %10, %11, %12, %13, %14, %15, %16, %17, %18, %19}, "
      "%20, %21, p, 1, 1, 1, 1;\n}\n"
      : "=f"(d[0]), "=f"(d[1]), "=f"(d[2]), "=f"(d[3]), "=f"(d[4]), "=f"(d[5]), "=f"(d[6]), "=f"(d[7]), "=f"(d[8]), "=f"(d[9]), "=f"(d[10]), "=f"(d[11]), "=f"(d[12]), "=f"(d[13]), "=f"(d[14]), "=f"(d[15]), "=f"(d[16]), "=f"(d[17]), "=f"(d[18]), "=f"(d[19])
      : "l"(da), "l"(db));
  }
}
__device__ __forceinline__ void wgmma_n128_rs_ta0_tb1(float* d, uint32_t a0, uint32_t a1, uint32_t a2, uint32_t a3, uint64_t db, bool accumulate) {
  if (accumulate) {
    asm volatile("{\n.reg .pred p;\nsetp.ne.b32 p, 1, 0;\n"
      "wgmma.mma_async.sync.aligned.m64n128k16.f32.bf16.bf16 "
      "{%0, %1, %2, %3, %4, %5, %6, %7, %8, %9, %10, %11, %12, %13, %14, %15, %16, %17, %18, %19, %20, %21, %22, %23, %24, %25, %26, %27, %28, %29, %30, %31, %32, %33, %34, %35, %36, %37, %38, %39, %40, %41, %42, %43, %44, %45, %46, %47, %48, %49, %50, %51, %52, %53, %54, %55, %56, %57, %58, %59, %60, %61, %62, %63}, "
      "{%64, %65, %66, %67}, %68, p, 1, 1, 1;\n}\n"
      : "+f"(d[0]), "+f"(d[1]), "+f"(d[2]), "+f"(d[3]), "+f"(d[4]), "+f"(d[5]), "+f"(d[6]), "+f"(d[7]), "+f"(d[8]), "+f"(d[9]), "+f"(d[10]), "+f"(d[11]), "+f"(d[12]), "+f"(d[13]), "+f"(d[14]), "+f"(d[15]), "+f"(d[16]), "+f"(d[17]), "+f"(d[18]), "+f"(d[19]), "+f"(d[20]), "+f"(d[21]), "+f"(d[22]), "+f"(d[23]), "+f"(d[24]), "+f"(d[25]), "+f"(d[26]), "+f"(d[27]), "+f"(d[28]), "+f"(d[29]), "+f"(d[30]), "+f"(d[31]), "+f"(d[32]), "+f"(d[33]), "+f"(d[34]), "+f"(d[35]), "+f"(d[36]), "+f"(d[37]), "+f"(d[38]), "+f"(d[39]), "+f"(d[40]), "+f"(d[41]), "+f"(d[42]), "+f"(d[43]), "+f"(d[44]), "+f"(d[45]), "+f"(d[46]), "+f"(d[47]), "+f"(d[48]), "+f"(d[49]), "+f"(d[50]), "+f"(d[51]), "+f"(d[52]), "+f"(d[53]), "+f"(d[54]), "+f"(d[55]), "+f"(d[56]), "+f"(d[57]), "+f"(d[58]), "+f"(d[59]), "+f"(d[60]), "+f"(d[61]), "+f"(d[62]), "+f"(d[63])
      : "r"(a0), "r"(a1), "r"(a2), "r"(a3), "l"(db));
  } else {
    asm volatile("{\n.reg .pred p;\nsetp.ne.b32 p, 0, 0;\n"
      "wgmma.mma_async.sync.aligned.m64n128k16.f32.bf16.bf16 "
      "{%0, %1, %2, %3, %4, %5, %6, %7, %8, %9, %10, %11, %12, %13, %14, %15, %16, %17, %18, %19, %20, %21, %22, %23, %24, %25, %26, %27, %28, %29, %30, %31, %32, %33, %34, %35, %36, %37, %38, %39, %40, %41, %42, %43, %44, %45, %46, %47, %48, %49, %50, %51, %52, %53, %54, %55, %56, %57, %58, %59, %60, %61, %62, %63}, "
      "{%64, %65, %66, %67}, %68, p, 1, 1, 1;\n}\n"
      : "=f"(d[0]), "=f"(d[1]), "=f"(d[2]), "=f"(d[3]), "=f"(d[4]), "=f"(d[5]), "=f"(d[6]), "=f"(d[7]), "=f"(d[8]), "=f"(d[9]), "=f"(d[10]), "=f"(d[11]), "=f"(d[12]), "=f"(d[13]), "=f"(d[14]), "=f"(d[15]), "=f"(d[16]), "=f"(d[17]), "=f"(d[18]), "=f"(d[19]), "=f"(d[20]), "=f"(d[21]), "=f"(d[22]), "=f"(d[23]), "=f"(d[24]), "=f"(d[25]), "=f"(d[26]), "=f"(d[27]), "=f"(d[28]), "=f"(d[29]), "=f"(d[30]), "=f"(d[31]), "=f"(d[32]), "=f"(d[33]), "=f"(d[34]), "=f"(d[35]), "=f"(d[36]), "=f"(d[37]), "=f"(d[38]), "=f"(d[39]), "=f"(d[40]), "=f"(d[41]), "=f"(d[42]), "=f"(d[43]), "=f"(d[44]), "=f"(d[45]), "=f"(d[46]), "=f"(d[47]), "=f"(d[48]), "=f"(d[49]), "=f"(d[50]), "=f"(d[51]), "=f"(d[52]), "=f"(d[53]), "=f"(d[54]), "=f"(d[55]), "=f"(d[56]), "=f"(d[57]), "=f"(d[58]), "=f"(d[59]), "=f"(d[60]), "=f"(d[61]), "=f"(d[62]), "=f"(d[63])
      : "r"(a0), "r"(a1), "r"(a2), "r"(a3), "l"(db));
  }
}
__device__ __forceinline__ void wgmma_n128_ss_ta0_tb1(float* d, uint64_t da, uint64_t db, bool accumulate) {
  if (accumulate) {
    asm volatile("{\n.reg .pred p;\nsetp.ne.b32 p, 1, 0;\n"
      "wgmma.mma_async.sync.aligned.m64n128k16.f32.bf16.bf16 "
      "{%0, %1, %2, %3, %4, %5, %6, %7, %8, %9, %10, %11, %12, %13, %14, %15, %16, %17, %18, %19, %20, %21, %22, %23, %24, %25, %26, %27, %28, %29, %30, %31, %32, %33, %34, %35, %36, %37, %38, %39, %40, %41, %42, %43, %44, %45, %46, %47, %48, %49, %50, %51, %52, %53, %54, %55, %56, %57, %58, %59, %60, %61, %62, %63}, "
      "%64, %65, p, 1, 1, 0, 1;\n}\n"
      : "+f"(d[0]), "+f"(d[1]), "+f"(d[2]), "+f"(d[3]), "+f"(d[4]), "+f"(d[5]), "+f"(d[6]), "+f"(d[7]), "+f"(d[8]), "+f"(d[9]), "+f"(d[10]), "+f"(d[11]), "+f"(d[12]), "+f"(d[13]), "+f"(d[14]), "+f"(d[15]), "+f"(d[16]), "+f"(d[17]), "+f"(d[18]), "+f"(d[19]), "+f"(d[20]), "+f"(d[21]), "+f"(d[22]), "+f"(d[23]), "+f"(d[24]), "+f"(d[25]), "+f"(d[26]), "+f"(d[27]), "+f"(d[28]), "+f"(d[29]), "+f"(d[30]), "+f"(d[31]), "+f"(d[32]), "+f"(d[33]), "+f"(d[34]), "+f"(d[35]), "+f"(d[36]), "+f"(d[37]), "+f"(d[38]), "+f"(d[39]), "+f"(d[40]), "+f"(d[41]), "+f"(d[42]), "+f"(d[43]), "+f"(d[44]), "+f"(d[45]), "+f"(d[46]), "+f"(d[47]), "+f"(d[48]), "+f"(d[49]), "+f"(d[50]), "+f"(d[51]), "+f"(d[52]), "+f"(d[53]), "+f"(d[54]), "+f"(d[55]), "+f"(d[56]), "+f"(d[57]), "+f"(d[58]), "+f"(d[59]), "+f"(d[60]), "+f"(d[61]), "+f"(d[62]), "+f"(d[63])
      : "l"(da), "l"(db));
  } else {
    asm volatile("{\n.reg .pred p;\nsetp.ne.b32 p, 0, 0;\n"
      "wgmma.mma_async.sync.aligned.m64n128k16.f32.bf16.bf16 "
      "{%0, %1, %2, %3, %4, %5, %6, %7, %8, %9, %10, %11, %12, %13, %14, %15, %16, %17, %18, %19, %20, %21, %22, %23, %24, %25, %26, %27, %28, %29, %30, %31, %32, %33, %34, %35, %36, %37, %38, %39, %40, %41, %42, %43, %44, %45, %46, %47, %48, %49, %50, %51, %52, %53, %54, %55, %56, %57, %58, %59, %60, %61, %62, %63}, "
      "%64, %65, p, 1, 1, 0, 1;\n}\n"
      : "=f"(d[0]), "=f"(d[1]), "=f"(d[2]), "=f"(d[3]), "=f"(d[4]), "=f"(d[5]), "=f"(d[6]), "=f"(d[7]), "=f"(d[8]), "=f"(d[9]), "=f"(d[10]), "=f"(d[11]), "=f"(d[12]), "=f"(d[13]), "=f"(d[14]), "=f"(d[15]), "=f"(d[16]), "=f"(d[17]), "=f"(d[18]), "=f"(d[19]), "=f"(d[20]), "=f"(d[21]), "=f"(d[22]), "=f"(d[23]), "=f"(d[24]), "=f"(d[25]), "=f"(d[26]), "=f"(d[27]), "=f"(d[28]), "=f"(d[29]), "=f"(d[30]), "=f"(d[31]), "=f"(d[32]), "=f"(d[33]), "=f"(d[34]), "=f"(d[35]), "=f"(d[36]), "=f"(d[37]), "=f"(d[38]), "=f"(d[39]), "=f"(d[40]), "=f"(d[41]), "=f"(d[42]), "=f"(d[43]), "=f"(d[44]), "=f"(d[45]), "=f"(d[46]), "=f"(d[47]), "=f"(d[48]), "=f"(d[49]), "=f"(d[50]), "=f"(d[51]), "=f"(d[52]), "=f"(d[53]), "=f"(d[54]), "=f"(d[55]), "=f"(d[56]), "=f"(d[57]), "=f"(d[58]), "=f"(d[59]), "=f"(d[60]), "=f"(d[61]), "=f"(d[62]), "=f"(d[63])
      : "l"(da), "l"(db));
  }
}
__device__ __forceinline__ void wgmma_n256_rs_ta0_tb1(float* d, uint32_t a0, uint32_t a1, uint32_t a2, uint32_t a3, uint64_t db, bool accumulate) {
  if (accumulate) {
    asm volatile("{\n.reg .pred p;\nsetp.ne.b32 p, 1, 0;\n"
      "wgmma.mma_async.sync.aligned.m64n256k16.f32.bf16.bf16 "
      "{%0, %1, %2, %3, %4, %5, %6, %7, %8, %9, %10, %11, %12, %13, %14, %15, %16, %17, %18, %19, %20, %21, %22, %23, %24, %25, %26, %27, %28, %29, %30, %31, %32, %33, %34, %35, %36, %37, %38, %39, %40, %41, %42, %43, %44, %45, %46, %47, %48, %49, %50, %51, %52, %53, %54, %55, %56, %57, %58, %59, %60, %61, %62, %63, %64, %65, %66, %67, %68, %69, %70, %71, %72, %73, %74, %75, %76, %77, %78, %79, %80, %81, %82, %83, %84, %85, %86, %87, %88, %89, %90, %91, %92, %93, %94, %95, %96, %97, %98, %99, %100, %101, %102, %103, %104, %105, %106, %107, %108, %109, %110, %111, %112, %113, %114, %115, %116, %117, %118, %119, %120, %121, %122, %123, %124, %125, %126, %127}, "
      "{%128, %129, %130, %131}, %132, p, 1, 1, 1;\n}\n"
      : "+f"(d[0]), "+f"(d[1]), "+f"(d[2]), "+f"(d[3]), "+f"(d[4]), "+f"(d[5]), "+f"(d[6]), "+f"(d[7]), "+f"(d[8]), "+f"(d[9]), "+f"(d[10]), "+f"(d[11]), "+f"(d[12]), "+f"(d[13]), "+f"(d[14]), "+f"(d[15]), "+f"(d[16]), "+f"(d[17]), "+f"(d[18]), "+f"(d[19]), "+f"(d[20]), "+f"(d[21]), "+f"(d[22]), "+f"(d[23]), "+f"(d[24]), "+f"(d[25]), "+f"(d[26]), "+f"(d[27]), "+f"(d[28]), "+f"(d[29]), "+f"(d[30]), "+f"(d[31]), "+f"(d[32]), "+f"(d[33]), "+f"(d[34]), "+f"(d[35]), "+f"(d[36]), "+f"(d[37]), "+f"(d[38]), "+f"(d[39]), "+f"(d[40]), "+f"(d[41]), "+f"(d[42]), "+f"(d[43]), "+f"(d[44]), "+f"(d[45]), "+f"(d[46]), "+f"(d[47]), "+f"(d[48]), "+f"(d[49]), "+f"(d[50]), "+f"(d[51]), "+f"(d[52]), "+f"(d[53]), "+f"(d[54]), "+f"(d[55]), "+f"(d[56]), "+f"(d[57]), "+f"(d[58]), "+f"(d[59]), "+f"(d[60]), "+f"(d[61]), "+f"(d[62]), "+f"(d[63]), "+f"(d[64]), "+f"(d[65]), "+f"(d[66]), "+f"(d[67]), "+f"(d[68]), "+f"(d[69]), "+f"(d[70]), "+f"(d[71]), "+f"(d[72]), "+f"(d[73]), "+f"(d[74]), "+f"(d[75]), "+f"(d[76]), "+f"(d[77]), "+f"(d[78]), "+f"(d[79]), "+f"(d[80]), "+f"(d[81]), "+f"(d[82]), "+f"(d[83]), "+f"(d[84]), "+f"(d[85]), "+f"(d[86]), "+f"(d[87]), "+f"(d[88]), "+f"(d[89]), "+f"(d[90]), "+f"(d[91]), "+f"(d[92]), "+f"(d[93]), "+f"(d[94]), "+f"(d[95]), "+f"(d[96]), "+f"(d[97]), "+f"(d[98]), "+f"(d[99]), "+f"(d[100]), "+f"(d[101]), "+f"(d[102]), "+f"(d[103]), "+f"(d[104]), "+f"(d[105]), "+f"(d[106]), "+f"(d[107]), "+f"(d[108]), "+f"(d[109]), "+f"(d[110]), "+f"(d[111]), "+f"(d[112]), "+f"(d[113]), "+f"(d[114]), "+f"(d[115]), "+f"(d[116]), "+f"(d[117]), "+f"(d[118]), "+f"(d[119]), "+f"(d[120]), "+f"(d[121]), "+f"(d[122]), "+f"(d[123]), "+f"(d[124]), "+f"(d[125]), "+f"(d[126]), "+f"(d[127])
      : "r"(a0), "r"(a1), "r"(a2), "r"(a3), "l"(db));
  } else {
    asm volatile("{\n.reg .pred p;\nsetp.ne.b32 p, 0, 0;\n"
      "wgmma.mma_async.sync.aligned.m64n256k16.f32.bf16.bf16 "
      "{%0, %1, %2, %3, %4, %5, %6, %7, %8, %9, %10, %11, %12, %13, %14, %15, %16, %17, %18, %19, %20, %21, %22, %23, %24, %25, %26, %27, %28, %29, %30, %31, %32, %33, %34, %35, %36, %37, %38, %39, %40, %41, %42, %43, %44, %45, %46, %47, %48, %49, %50, %51, %52, %53, %54, %55, %56, %57, %58, %59, %60, %61, %62, %63, %64, %65, %66, %67, %68, %69, %70, %71, %72, %73, %74, %75, %76, %77, %78, %79, %80, %81, %82, %83, %84, %85, %86, %87, %88, %89, %90, %91, %92, %93, %94, %95, %96, %97, %98, %99, %100, %101, %102, %103, %104, %105, %106, %107, %108, %109, %110, %111, %112, %113, %114, %115, %116, %117, %118, %119, %120, %121, %122, %123, %124, %125, %126, %127}, "
      "{%128, %129, %130, %131}, %132, p, 1, 1, 1;\n}\n"
      : "=f"(d[0]), "=f"(d[1]), "=f"(d[2]), "=f"(d[3]), "=f"(d[4]), "=f"(d[5]), "=f"(d[6]), "=f"(d[7]), "=f"(d[8]), "=f"(d[9]), "=f"(d[10]), "=f"(d[11]), "=f"(d[12]), "=f"(d[13]), "=f"(d[14]), "=f"(d[15]), "=f"(d[16]), "=f"(d[17]), "=f"(d[18]), "=f"(d[19]), "=f"(d[20]), "=f"(d[21]), "=f"(d[22]), "=f"(d[23]), "=f"(d[24]), "=f"(d[25]), "=f"(d[26]), "=f"(d[27]), "=f"(d[28]), "=f"(d[29]), "=f"(d[30]), "=f"(d[31]), "=f"(d[32]), "=f"(d[33]), "=f"(d[34]), "=f"(d[35]), "=f"(d[36]), "=f"(d[37]), "=f"(d[38]), "=f"(d[39]), "=f"(d[40]), "=f"(d[41]), "=f"(d[42]), "=f"(d[43]), "=f"(d[44]), "=f"(d[45]), "=f"(d[46]), "=f"(d[47]), "=f"(d[48]), "=f"(d[49]), "=f"(d[50]), "=f"(d[51]), "=f"(d[52]), "=f"(d[53]), "=f"(d[54]), "=f"(d[55]), "=f"(d[56]), "=f"(d[57]), "=f"(d[58]), "=f"(d[59]), "=f"(d[60]), "=f"(d[61]), "=f"(d[62]), "=f"(d[63]), "=f"(d[64]), "=f"(d[65]), "=f"(d[66]), "=f"(d[67]), "=f"(d[68]), "=f"(d[69]), "=f"(d[70]), "=f"(d[71]), "=f"(d[72]), "=f"(d[73]), "=f"(d[74]), "=f"(d[75]), "=f"(d[76]), "=f"(d[77]), "=f"(d[78]), "=f"(d[79]), "=f"(d[80]), "=f"(d[81]), "=f"(d[82]), "=f"(d[83]), "=f"(d[84]), "=f"(d[85]), "=f"(d[86]), "=f"(d[87]), "=f"(d[88]), "=f"(d[89]), "=f"(d[90]), "=f"(d[91]), "=f"(d[92]), "=f"(d[93]), "=f"(d[94]), "=f"(d[95]), "=f"(d[96]), "=f"(d[97]), "=f"(d[98]), "=f"(d[99]), "=f"(d[100]), "=f"(d[101]), "=f"(d[102]), "=f"(d[103]), "=f"(d[104]), "=f"(d[105]), "=f"(d[106]), "=f"(d[107]), "=f"(d[108]), "=f"(d[109]), "=f"(d[110]), "=f"(d[111]), "=f"(d[112]), "=f"(d[113]), "=f"(d[114]), "=f"(d[115]), "=f"(d[116]), "=f"(d[117]), "=f"(d[118]), "=f"(d[119]), "=f"(d[120]), "=f"(d[121]), "=f"(d[122]), "=f"(d[123]), "=f"(d[124]), "=f"(d[125]), "=f"(d[126]), "=f"(d[127])
      : "r"(a0), "r"(a1), "r"(a2), "r"(a3), "l"(db));
  }
}
__device__ __forceinline__ void wgmma_n256_ss_ta0_tb1(float* d, uint64_t da, uint64_t db, bool accumulate) {
  if (accumulate) {
    asm volatile("{\n.reg .pred p;\nsetp.ne.b32 p, 1, 0;\n"
      "wgmma.mma_async.sync.aligned.m64n256k16.f32.bf16.bf16 "
      "{%0, %1, %2, %3, %4, %5, %6, %7, %8, %9, %10, %11, %12, %13, %14, %15, %16, %17, %18, %19, %20, %21, %22, %23, %24, %25, %26, %27, %28, %29, %30, %31, %32, %33, %34, %35, %36, %37, %38, %39, %40, %41, %42, %43, %44, %45, %46, %47, %48, %49, %50, %51, %52, %53, %54, %55, %56, %57, %58, %59, %60, %61, %62, %63, %64, %65, %66, %67, %68, %69, %70, %71, %72, %73, %74, %75, %76, %77, %78, %79, %80, %81, %82, %83, %84, %85, %86, %87, %88, %89, %90, %91, %92, %93, %94, %95, %96, %97, %98, %99, %100, %101, %102, %103, %104, %105, %106, %107, %108, %109, %110, %111, %112, %113, %114, %115, %116, %117, %118, %119, %120, %121, %122, %123, %124, %125, %126, %127}, "
      "%128, %129, p, 1, 1, 0, 1;\n}\n"
      : "+f"(d[0]), "+f"(d[1]), "+f"(d[2]), "+f"(d[3]), "+f"(d[4]), "+f"(d[5]), "+f"(d[6]), "+f"(d[7]), "+f"(d[8]), "+f"(d[9]), "+f"(d[10]), "+f"(d[11]), "+f"(d[12]), "+f"(d[13]), "+f"(d[14]), "+f"(d[15]), "+f"(d[16]), "+f"(d[17]), "+f"(d[18]), "+f"(d[19]), "+f"(d[20]), "+f"(d[21]), "+f"(d[22]), "+f"(d[23]), "+f"(d[24]), "+f"(d[25]), "+f"(d[26]), "+f"(d[27]), "+f"(d[28]), "+f"(d[29]), "+f"(d[30]), "+f"(d[31]), "+f"(d[32]), "+f"(d[33]), "+f"(d[34]), "+f"(d[35]), "+f"(d[36]), "+f"(d[37]), "+f"(d[38]), "+f"(d[39]), "+f"(d[40]), "+f"(d[41]), "+f"(d[42]), "+f"(d[43]), "+f"(d[44]), "+f"(d[45]), "+f"(d[46]), "+f"(d[47]), "+f"(d[48]), "+f"(d[49]), "+f"(d[50]), "+f"(d[51]), "+f"(d[52]), "+f"(d[53]), "+f"(d[54]), "+f"(d[55]), "+f"(d[56]), "+f"(d[57]), "+f"(d[58]), "+f"(d[59]), "+f"(d[60]), "+f"(d[61]), "+f"(d[62]), "+f"(d[63]), "+f"(d[64]), "+f"(d[65]), "+f"(d[66]), "+f"(d[67]), "+f"(d[68]), "+f"(d[69]), "+f"(d[70]), "+f"(d[71]), "+f"(d[72]), "+f"(d[73]), "+f"(d[74]), "+f"(d[75]), "+f"(d[76]), "+f"(d[77]), "+f"(d[78]), "+f"(d[79]), "+f"(d[80]), "+f"(d[81]), "+f"(d[82]), "+f"(d[83]), "+f"(d[84]), "+f"(d[85]), "+f"(d[86]), "+f"(d[87]), "+f"(d[88]), "+f"(d[89]), "+f"(d[90]), "+f"(d[91]), "+f"(d[92]), "+f"(d[93]), "+f"(d[94]), "+f"(d[95]), "+f"(d[96]), "+f"(d[97]), "+f"(d[98]), "+f"(d[99]), "+f"(d[100]), "+f"(d[101]), "+f"(d[102]), "+f"(d[103]), "+f"(d[104]), "+f"(d[105]), "+f"(d[106]), "+f"(d[107]), "+f"(d[108]), "+f"(d[109]), "+f"(d[110]), "+f"(d[111]), "+f"(d[112]), "+f"(d[113]), "+f"(d[114]), "+f"(d[115]), "+f"(d[116]), "+f"(d[117]), "+f"(d[118]), "+f"(d[119]), "+f"(d[120]), "+f"(d[121]), "+f"(d[122]), "+f"(d[123]), "+f"(d[124]), "+f"(d[125]), "+f"(d[126]), "+f"(d[127])
      : "l"(da), "l"(db));
  } else {
    asm volatile("{\n.reg .pred p;\nsetp.ne.b32 p, 0, 0;\n"
      "wgmma.mma_async.sync.aligned.m64n256k16.f32.bf16.bf16 "
      "{%0, %1, %2, %3, %4, %5, %6, %7, %8, %9, %10, %11, %12, %13, %14, %15, %16, %17, %18, %19, %20, %21, %22, %23, %24, %25, %26, %27, %28, %29, %30, %31, %32, %33, %34, %35, %36, %37, %38, %39, %40, %41, %42, %43, %44, %45, %46, %47, %48, %49, %50, %51, %52, %53, %54, %55, %56, %57, %58, %59, %60, %61, %62, %63, %64, %65, %66, %67, %68, %69, %70, %71, %72, %73, %74, %75, %76, %77, %78, %79, %80, %81, %82, %83, %84, %85, %86, %87, %88, %89, %90, %91, %92, %93, %94, %95, %96, %97, %98, %99, %100, %101, %102, %103, %104, %105, %106, %107, %108, %109, %110, %111, %112, %113, %114, %115, %116, %117, %118, %119, %120, %121, %122, %123, %124, %125, %126, %127}, "
      "%128, %129, p, 1, 1, 0, 1;\n}\n"
      : "=f"(d[0]), "=f"(d[1]), "=f"(d[2]), "=f"(d[3]), "=f"(d[4]), "=f"(d[5]), "=f"(d[6]), "=f"(d[7]), "=f"(d[8]), "=f"(d[9]), "=f"(d[10]), "=f"(d[11]), "=f"(d[12]), "=f"(d[13]), "=f"(d[14]), "=f"(d[15]), "=f"(d[16]), "=f"(d[17]), "=f"(d[18]), "=f"(d[19]), "=f"(d[20]), "=f"(d[21]), "=f"(d[22]), "=f"(d[23]), "=f"(d[24]), "=f"(d[25]), "=f"(d[26]), "=f"(d[27]), "=f"(d[28]), "=f"(d[29]), "=f"(d[30]), "=f"(d[31]), "=f"(d[32]), "=f"(d[33]), "=f"(d[34]), "=f"(d[35]), "=f"(d[36]), "=f"(d[37]), "=f"(d[38]), "=f"(d[39]), "=f"(d[40]), "=f"(d[41]), "=f"(d[42]), "=f"(d[43]), "=f"(d[44]), "=f"(d[45]), "=f"(d[46]), "=f"(d[47]), "=f"(d[48]), "=f"(d[49]), "=f"(d[50]), "=f"(d[51]), "=f"(d[52]), "=f"(d[53]), "=f"(d[54]), "=f"(d[55]), "=f"(d[56]), "=f"(d[57]), "=f"(d[58]), "=f"(d[59]), "=f"(d[60]), "=f"(d[61]), "=f"(d[62]), "=f"(d[63]), "=f"(d[64]), "=f"(d[65]), "=f"(d[66]), "=f"(d[67]), "=f"(d[68]), "=f"(d[69]), "=f"(d[70]), "=f"(d[71]), "=f"(d[72]), "=f"(d[73]), "=f"(d[74]), "=f"(d[75]), "=f"(d[76]), "=f"(d[77]), "=f"(d[78]), "=f"(d[79]), "=f"(d[80]), "=f"(d[81]), "=f"(d[82]), "=f"(d[83]), "=f"(d[84]), "=f"(d[85]), "=f"(d[86]), "=f"(d[87]), "=f"(d[88]), "=f"(d[89]), "=f"(d[90]), "=f"(d[91]), "=f"(d[92]), "=f"(d[93]), "=f"(d[94]), "=f"(d[95]), "=f"(d[96]), "=f"(d[97]), "=f"(d[98]), "=f"(d[99]), "=f"(d[100]), "=f"(d[101]), "=f"(d[102]), "=f"(d[103]), "=f"(d[104]), "=f"(d[105]), "=f"(d[106]), "=f"(d[107]), "=f"(d[108]), "=f"(d[109]), "=f"(d[110]), "=f"(d[111]), "=f"(d[112]), "=f"(d[113]), "=f"(d[114]), "=f"(d[115]), "=f"(d[116]), "=f"(d[117]), "=f"(d[118]), "=f"(d[119]), "=f"(d[120]), "=f"(d[121]), "=f"(d[122]), "=f"(d[123]), "=f"(d[124]), "=f"(d[125]), "=f"(d[126]), "=f"(d[127])
      : "l"(da), "l"(db));
  }
}
__device__ __forceinline__ void wgmma_n256_ssp_ta0_tb1(float* d, uint64_t da, uint64_t db, int accumulate) {
    asm volatile("{\n.reg .pred p;\nsetp.ne.b32 p, %130, 0;\n"
      "wgmma.mma_async.sync.aligned.m64n256k16.f32.bf16.bf16 "
      "{%0, %1, %2, %3, %4, %5, %6, %7, %8, %9, %10, %11, %12, %13, %14, %15, %16, %17, %18, %19, %20, %21, %22, %23, %24, %25, %26, %27, %28, %29, %30, %31, %32, %33, %34, %35, %36, %37, %38, %39, %40, %41, %42, %43, %44, %45, %46, %47, %48, %49, %50, %51, %52, %53, %54, %55, %56, %57, %58, %59, %60, %61, %62, %63, %64, %65, %66, %67, %68, %69, %70, %71, %72, %73, %74, %75, %76, %77, %78, %79, %80, %81, %82, %83, %84, %85, %86, %87, %88, %89, %90, %91, %92, %93, %94, %95, %96, %97, %98, %99, %100, %101, %102, %103, %104, %105, %106, %107, %108, %109, %110, %111, %112, %113, %114, %115, %116, %117, %118, %119, %120, %121, %122, %123, %124, %125, %126, %127}, "
      "%128, %129, p, 1, 1, 0, 1;\n}\n"
      : "+f"(d[0]), "+f"(d[1]), "+f"(d[2]), "+f"(d[3]), "+f"(d[4]), "+f"(d[5]), "+f"(d[6]), "+f"(d[7]), "+f"(d[8]), "+f"(d[9]), "+f"(d[10]), "+f"(d[11]), "+f"(d[12]), "+f"(d[13]), "+f"(d[14]), "+f"(d[15]), "+f"(d[16]), "+f"(d[17]), "+f"(d[18]), "+f"(d[19]), "+f"(d[20]), "+f"(d[21]), "+f"(d[22]), "+f"(d[23]), "+f"(d[24]), "+f"(d[25]), "+f"(d[26]), "+f"(d[27]), "+f"(d[28]), "+f"(d[29]), "+f"(d[30]), "+f"(d[31]), "+f"(d[32]), "+f"(d[33]), "+f"(d[34]), "+f"(d[35]), "+f"(d[36]), "+f"(d[37]), "+f"(d[38]), "+f"(d[39]), "+f"(d[40]), "+f"(d[41]), "+f"(d[42]), "+f"(d[43]), "+f"(d[44]), "+f"(d[45]), "+f"(d[46]), "+f"(d[47]), "+f"(d[48]), "+f"(d[49]), "+f"(d[50]), "+f"(d[51]), "+f"(d[52]), "+f"(d[53]), "+f"(d[54]), "+f"(d[55]), "+f"(d[56]), "+f"(d[57]), "+f"(d[58]), "+f"(d[59]), "+f"(d[60]), "+f"(d[61]), "+f"(d[62]), "+f"(d[63]), "+f"(d[64]), "+f"(d[65]), "+f"(d[66]), "+f"(d[67]), "+f"(d[68]), "+f"(d[69]), "+f"(d[70]), "+f"(d[71]), "+f"(d[72]), "+f"(d[73]), "+f"(d[74]), "+f"(d[75]), "+f"(d[76]), "+f"(d[77]), "+f"(d[78]), "+f"(d[79]), "+f"(d[80]), "+f"(d[81]), "+f"(d[82]), "+f"(d[83]), "+f"(d[84]), "+f"(d[85]), "+f"(d[86]), "+f"(d[87]), "+f"(d[88]), "+f"(d[89]), "+f"(d[90]), "+f"(d[91]), "+f"(d[92]), "+f"(d[93]), "+f"(d[94]), "+f"(d[95]), "+f"(d[96]), "+f"(d[97]), "+f"(d[98]), "+f"(d[99]), "+f"(d[100]), "+f"(d[101]), "+f"(d[102]), "+f"(d[103]), "+f"(d[104]), "+f"(d[105]), "+f"(d[106]), "+f"(d[107]), "+f"(d[108]), "+f"(d[109]), "+f"(d[110]), "+f"(d[111]), "+f"(d[112]), "+f"(d[113]), "+f"(d[114]), "+f"(d[115]), "+f"(d[116]), "+f"(d[117]), "+f"(d[118]), "+f"(d[119]), "+f"(d[120]), "+f"(d[121]), "+f"(d[122]), "+f"(d[123]), "+f"(d[124]), "+f"(d[125]), "+f"(d[126]), "+f"(d[127])
      : "l"(da), "l"(db), "r"(accumulate));
}

template <int N> __device__ __forceinline__ void quad_sum(float* m) {
#pragma unroll
  for (int o = 1; o <= 2; o <<= 1) {
    float t[N];
#pragma unroll
    for (int i = 0; i < N; i++) t[i] = __shfl_xor_sync(~0u, m[i], o);
#pragma unroll
    for (int i = 0; i < N; i++) m[i] += t[i];
  }
}
__device__ __forceinline__ bool softmax_unsafe(const uint32_t* t, float l0, float l1) {
  const float m0 = fmaxf(bf_lo(t[0]) + bf_hi(t[0]), bf_lo(t[2]) + bf_hi(t[2])), m1 = fmaxf(bf_lo(t[1]) + bf_hi(t[1]), bf_lo(t[3]) + bf_hi(t[3]));
  return __any_sync(~0u, !(m0 * l0 < 2500.f) | !(m1 * l1 < 2500.f));
}
__device__ __forceinline__ void softmax_shift(float* p, float c0, float c1) {
#pragma unroll 1
  for (int it = 0; it < 8; it++) {
    float mx = p[0], mn = p[0];
#pragma unroll
    for (int j = 1; j < 8; j++) { mx = fmaxf(mx, p[(j >> 1) * 4 + (j & 1)]); mn = fminf(mn, p[(j >> 1) * 4 + (j & 1)]); }
#pragma unroll
    for (int o = 1; o <= 2; o <<= 1) { mx = fmaxf(mx, __shfl_xor_sync(~0u, mx, o)); mn = fminf(mn, __shfl_xor_sync(~0u, mn, o)); }
    const float half = fminf(0.5f * (mx - mn), 50.f * rcp(it & 1 ? c1 : c0));
    float r[8];
#pragma unroll
    for (int j = 0; j < 8; j++) {
      const float v = p[(j >> 1) * 4 + (j & 1)];
      r[j] = fmaxf(v - mx + half, 0.f) + fminf(v - mn - half, 0.f) + (v - v);
    }
#pragma unroll
    for (int k = 0; k < 7; k++)
#pragma unroll
      for (int j = 0; j < 8; j++) p[(k >> 1) * 16 + (k & 1) * 2 + (j >> 1) * 4 + (j & 1)] = p[((k + 1) >> 1) * 16 + ((k + 1) & 1) * 2 + (j >> 1) * 4 + (j & 1)];
#pragma unroll
    for (int j = 0; j < 8; j++) p[50 + (j >> 1) * 4 + (j & 1)] = r[j];
  }
}
template <int J0 = 0, int J1 = 8> __device__ __forceinline__ void k_exp(const float* p, float c0, float c1, float* e, float* s) {
#pragma unroll
  for (int j = J0; j < J1; j++) {
    e[2 * j] = ex2(p[2 * j] * (j & 1 ? c1 : c0));
    e[2 * j + 1] = ex2(p[2 * j + 1] * (j & 1 ? c1 : c0));
    e[16 + j] = rcp(e[2 * j] * e[2 * j + 1]);
    const float t = e[2 * j] + e[2 * j + 1];
    s[j & 1] = j < 2 ? t : s[j & 1] + t;
    s[2 + (j & 1)] = j < 2 ? e[16 + j] * t : fmaf(e[16 + j], t, s[2 + (j & 1)]);
  }
}
template <int J0 = 0, int J1 = 8> __device__ __forceinline__ void q_exp(const float* p, float c0, float c1, uint32_t* f) {
#pragma unroll
  for (int j = J0; j < J1; j++) {
    const float e0 = ex2(p[2 * j] * (j & 1 ? c1 : c0)), e1 = ex2(p[2 * j + 1] * (j & 1 ? c1 : c0)), r = rcp(e0 * e1);
    f[j] = pack2(e0, e1);
    f[8 + j] = bmul2(f[j], pack2(r, r));
  }
}

#define FMA8(A, U, X)                                                                                        \
  A[0] = fmaf(bf_lo(U.x), X, A[0]); A[1] = fmaf(bf_hi(U.x), X, A[1]); A[2] = fmaf(bf_lo(U.y), X, A[2]); A[3] = fmaf(bf_hi(U.y), X, A[3]); \
  A[4] = fmaf(bf_lo(U.z), X, A[4]); A[5] = fmaf(bf_hi(U.z), X, A[5]); A[6] = fmaf(bf_lo(U.w), X, A[6]); A[7] = fmaf(bf_hi(U.w), X, A[7])

__device__ __forceinline__ uint32_t routed_row(const __nv_bfloat16* x, uint32_t tag, int lane, uint4* xr) {
  uint32_t best = 0, sv = 0;
#pragma unroll 1
  for (int it = 0; it < SPIN_MAX; it++) {
    const int sel = 2047 - (best & 0x7ff);
#pragma unroll
    for (int i = 0; i < 4; i++) xr[i] = ldg_nc(x + (size_t)sel * DM + i * 256 + lane * 8);
    const unsigned long long st = ld_rlx64(g_stat + sel);
    const uint4 b0 = ld_rlx128(g_best + lane * 2), b1 = ld_rlx128(g_best + 64 + lane * 2);
    const uint32_t m = __reduce_max_sync(~0u, max(max(b0.y == tag ? b0.x : 0u, b0.w == tag ? b0.z : 0u), max(b1.y == tag ? b1.x : 0u, b1.w == tag ? b1.z : 0u)));
    sv = (uint32_t)st;
    if (__all_sync(~0u, b0.y == tag && b0.w == tag && b1.y == tag && b1.w == tag && m == best && (uint32_t)(st >> 32) == tag)) break;
    best = m;
    if (AM_NS) __nanosleep(AM_NS);
  }
  const uint32_t m2 = (sv & 0xffff0000u) | (sv >> 16);
  const float rs = rcp(bf_lo(sv));
#pragma unroll
  for (int i = 0; i < 4; i++) {
    const uint32_t d0 = bsub2(xr[i].x, m2), d1 = bsub2(xr[i].y, m2), d2 = bsub2(xr[i].z, m2), d3 = bsub2(xr[i].w, m2);
    xr[i] = make_uint4(pack2(bf_lo(d0) * rs, bf_hi(d0) * rs), pack2(bf_lo(d1) * rs, bf_hi(d1) * rs), pack2(bf_lo(d2) * rs, bf_hi(d2) * rs),
                       pack2(bf_lo(d3) * rs, bf_hi(d3) * rs));
  }
  return best;
}

struct Params {
  const __nv_bfloat16 *x, *wqkv, *wo, *w_r, *w_gate, *w_up, *w_down;
};

template <bool BY_SMID> __global__ void __launch_bounds__(384, 1)
fused_kernel(const __grid_constant__ CUtensorMap mX, const __grid_constant__ CUtensorMap mWkv, const __grid_constant__ CUtensorMap mWq,
             const __grid_constant__ CUtensorMap mWo, const __grid_constant__ CUtensorMap mPhi, const __grid_constant__ CUtensorMap mWp,
             const __grid_constant__ CUtensorMap mOut, const __grid_constant__ CUtensorMap mWc,
             const __grid_constant__ CUtensorMap mG, const __grid_constant__ CUtensorMap mU, const __grid_constant__ CUtensorMap mD,
             const __grid_constant__ CUtensorMap mXs, const __grid_constant__ CUtensorMap mG2, const __grid_constant__ CUtensorMap mU2, const Params P) {
  constexpr uint32_t sb = SB, bar = SB + SM_BAR;
  int bid = blockIdx.x;
  if (BY_SMID) {
    uint32_t sm;
    asm volatile("mov.u32 %0, %%smid;" : "=r"(sm));
    const uint32_t tq = (sm - 64) >> 1, q7 = (tq * 37) >> 8;
    const uint32_t gpc = sm < 64 ? (sm >> 1) & 7 : 1 + tq - 7 * q7, idx = (sm < 64 ? sm >> 4 : 4 + q7) * 2 + (sm & 1);
    bid = sm < 120 ? ((PTAB >> (4 * gpc)) & 7) * 16 + idx : sm < 124 ? sm + 8 : sm - 116;
  }
  const int hg = ((bid >> 2) & 3) + 4 * ((bid >> 4) & 1), mb = (bid & 3) + 4 * ((bid >> 5) & 3);
  if (bid < NCTA && threadIdx.x < 256) {
    const uint32_t r0 = threadIdx.x >> 3, c = threadIdx.x & 7, dst = sb + 2 * KV_STAGE + r0 * 128 + ((c ^ (r0 & 7)) << 4);
    const char* xs = (const char*)P.x + (size_t)(mb * 128 + r0) * 2048 + c * 16;
    const char* ws = (const char*)P.wqkv + (size_t)r0 * 6144 + 2048 + hg * 256 + c * 16;
#pragma unroll
    for (int i = 0; i < 4; i++) cp_async16(dst + i * 4096, xs + i * 65536);
#pragma unroll
    for (int i = 0; i < 8; i++) cp_async16(dst + 16384 + i * 4096, ws + (i & 1) * 196608 + (i >> 2) * 2048 + ((i >> 1) & 1) * 128);
  }
  extern __shared__ __align__(1024) uint8_t smem[];
  if (smem_u32(smem) != SB) __trap();
  const int warp = __shfl_sync(~0u, threadIdx.x >> 5, 0);

  if (bid >= NCTA) {
    constexpr uint32_t XV = SM_WPHI, ONES = SM_ZT, BF = bar, BE = bar + 48, BX = bar + 96;
    constexpr int NJ = (DM - GROWS) / 64;
    const int lane = lane_id(), sp = bid - NCTA;
    const uint32_t tag = ld_rlx(g_epoch + bid * 32 + lane) + 1;
    if (warp == 8 && elect_one()) {
#pragma unroll 1
      for (int i = 0; i < 13; i++) mbar_init(bar + 8 * i, i >= 6 && i < 12 ? 8 : 1);
    }
    if (warp == 9) { sts64u(sb + ONES + lane * 8, 0x3f803f80u, 0x3f803f80u); fence_async_smem(); }
    __syncthreads();
    if (warp == 8) {
      if (elect_one()) {
        uint32_t s = 0, ph = 1;
        for (const long long c0 = clock64(); clock64() - c0 < SP_DELAY;) {}
#pragma unroll 1
        for (int job = 0; job < 8; job++) {
          const CUtensorMap* m = job == 0 ? &mWq : sp & 2 ? &mU2 : &mG2;
          const int g0 = job ? (sp & 1) * 28 + job * 4 - 4 : sp * 4;
#pragma unroll 1
          for (int row = job ? GROWS : 0; row < DM; row += 64) {
            mbar_wait(BE + 8 * s, ph);
            mbar_expect_tx(BF + 8 * s, Q_STAGE);
            tma4d(sb + s * Q_STAGE, m, 0, row, g0, 0, BF + 8 * s);
            tma4d(sb + s * Q_STAGE + 16384, m, 0, row, g0 + 2, 0, BF + 8 * s);
            if (++s == 6) { s = 0; ph ^= 1; }
          }
        }
      }
    } else if (warp == 9) {
      uint4 xr[4];
      routed_row(P.x, tag, lane, xr);
#pragma unroll
      for (int i = 0; i < 4; i++) sts128u(sb + XV + i * 512 + lane * 16, xr[i].x, xr[i].y, xr[i].z, xr[i].w);
      fence_async_smem();
      __syncwarp();
      if (lane == 0) mbar_arrive(BX);
    } else if (warp < 8) {
      uint32_t s = 0, ph = 0;
#pragma unroll 1
      for (int job = 0; job < 8; job++) {
        float d[8] = {0.f, 0.f, 0.f, 0.f, 0.f, 0.f, 0.f, 0.f};
        if (job == 1) mbar_wait(BX, 0);
#pragma unroll 1
        for (int i = 0; i < (job ? NJ : 16); i++) {
          mbar_wait(BF + 8 * s, ph);
          wg_fence();
#pragma unroll
          for (int k = 0; k < 8; k++)
            wgmma_n8_ss_ta1_tb0(d + 4 * (k >> 2), mkdesc(sb + k * 2048, 16, 1024, 1, s * (Q_STAGE / 16) + (warp >> 2) * 1024),
                                mkdesc(sb, 16, 128, 0, job ? (XV + GROWS * 2) / 16 + i * 8 + (k & 3) * 2 : ONES / 16), 1);
          wg_commit();
          wg_wait<0>();
          if (lane == 0) mbar_arrive(BE + 8 * s);
          if (++s == 6) { s = 0; ph ^= 1; }
        }
        reg_fence<8>(d);
        float* dst = (job ? g_gp + sp * 1792 + job * 256 - 256 : g_cs + sp * 256) + (warp >> 2) * 128 + (warp & 3) * 16 + (lane >> 2);
        if ((lane & 3) == 0) {
#pragma unroll
          for (int i = 0; i < 4; i++) st_rlx(dst + (i >> 1) * 64 + (i & 1) * 8, mark(__float_as_uint(d[2 * i]), tag & 1));
        }
        __syncwarp();
      }
      if (warp == 0) g_epoch[bid * 32 + lane] = tag;
    }
    return;
  }
#define Q_SLAB(J) ((J) < 8 ? ((J) + 8 - 2 * (hg & 4)) & 15 : 2 * (hg & 4) + 2 * ((J) & 3) + ((J) >> 2 & 1))
#define Q_AOFF(J) ((J) == 8 + (hg & 3) ? SM_X0 : (J) == 12 + (hg & 3) ? SM_X1 : ((J) & 3) * Q_STAGE)
#define Q_LOAD(J)                                                                                            \
  do {                                                                                                       \
    const uint32_t fb_ = bar + B_FULLQ + 8 * ((J) & 3);                                                      \
    const int k_ = Q_SLAB(J) * 64;                                                                           \
    mbar_expect_tx(fb_, Q_STAGE);                                                                            \
    mbar_arrive2(fb_);                                                                                       \
    tma2d(sb + Q_AOFF(J), &mX, k_, mb * 128, fb_);                                                           \
    tma4d(sb + ((J) & 3) * Q_STAGE + 16384, &mWq, 0, k_, hg * 2, 0, fb_);                                    \
  } while (0)
  if (warp >= 8) {
    asm volatile("setmaxnreg.dec.sync.aligned.u32 %0;" ::"n"(REG_H));
    const int lane = lane_id();
    const int f = (warp - 9) & 3;
    if (f == 3) {
      if (elect_one()) {
        PROF(0); PROFT(32);
#pragma unroll
        for (int s = 0; s < 3; s++) mbar_init(bar + B_FULLKV + 8 * s, 1);
      }
      __syncwarp();
      asm volatile("bar.arrive 14, 288;" ::: "memory");
      if (elect_one()) {
#pragma unroll
        for (int s = 0; s < 2; s++) {
          mbar_expect_tx(bar + B_FULLKV + 8 * s, KV_STAGE);
          tma2d(sb + s * KV_STAGE, &mX, (s + 1) * 64, mb * 128, bar + B_FULLKV + 8 * s);
          tma4d(sb + s * KV_STAGE + 16384, &mWkv, 0, (s + 1) * 64, hg * 2, 1, bar + B_FULLKV + 8 * s);
        }
      }
      __syncwarp();
    }
    const uint32_t ep = ld_rlx(g_epoch + bid * 32 + lane);
    if (f < 2) {
#pragma unroll
      for (int i = 0; i < 2; i++) {
        const uint4 u = __ldg((const uint4*)P.w_r + (f * 2 + i) * 32 + lane);
        sts128u(sb + SM_XSEL + (f * 2 + i) * 512 + lane * 16, u.x, u.y, u.z, u.w);
      }
    }
    bar_sync(13, 384);
    const uint32_t tag = ep + 1, par = tag & 1;
    const bool ffn = bid < NFFN;
    const int fb = bid, cu = bid >> 1, ch = bid & 1;
#define CS_STORE(SEC, C)                                                                                     \
  _Pragma("unroll") for (int r = 0; r < 3; r++) {                                                            \
    const uint32_t h0 = pack2(C.x, C.y), h1 = pack2(C.z, C.w);                                               \
    sts64u(sb + SM_CST + (SEC) * 1024 + (lane >> 4) * 512 + (lane & 1) * 8 + r * 128 + ((((lane & 15) >> 1) ^ (r + (lane >> 4) * 4)) << 4), h0, h1); \
    C.x -= bf_lo(h0); C.y -= bf_hi(h0); C.z -= bf_lo(h1); C.w -= bf_hi(h1);                                  \
  }
#define BAD4(U) ((U.x ^ par) | (U.y ^ par) | (U.z ^ par) | (U.w ^ par))
    const int n0 = f < 2 ? 0 : 2 * f - 3, ne = FFN_OFF || !ffn ? 3 : f == 3 ? 3 + G8 : 3 + GN;
    const uint32_t fsb = sb + SM_FST + ((f + 1) & 3) * 8192, fbar = bar + B_FST + f * 16, fst = fsb + (lane >> 4) * 2048 + (lane & 15) * 16;
    const CUtensorMap *ma = &mWc, *mc = &mWc;
    int sx = 1024 + cu * 32, sy = ch * 512 + f * 192, sdy = 32;
#define STAGEG(N)                                                                                            \
  do {                                                                                                       \
    if ((N) == 3) { ma = &mG; mc = &mU; sx = fb * 32; sy = f * (GN * 32);  sdy = 0; }                        \
    if ((N) < ne && elect_one()) {                                                                           \
      const uint32_t dst_ = fsb + ((N) & 1) * 4096, b_ = fbar + ((N) & 1) * 8;                               \
      mbar_expect_tx(b_, 4096);                                                                              \
      tma2d(dst_, ma, sx, sy, b_);                                                                           \
      tma2d(dst_ + 2048, mc, sx, sy + sdy, b_);                                                              \
    }                                                                                                        \
    sy += 32 + sdy;                                                                                          \
  } while (0)
    float a[8], gsum = 0.f, usum = 0.f;
    {
      if (f == 3) {
        if (elect_one()) {
          if (XS_EARLY) { mbar_expect_tx(bar + B_XST, 16384); tma3d(sb + SM_XST, &mXs, 0, bid * 16, 0, bar + B_XST); }
          mbar_expect_tx(bar + B_WPHI, 8192);
          tma2d(sb + SM_WPHI, &mPhi, 0, hg * 128, bar + B_WPHI);
          prefetch_map(&mWq); prefetch_map(&mWo); prefetch_map(&mWp); prefetch_map(&mD);
          PROF(31);
        }
        __syncwarp();
      } else {
        if (lane == 0) prefetch_map(f == 0 ? &mWc : f == 1 ? &mG : &mU);
        if (f == 2) ((float2*)g_y[par])[bid * 32 + lane] = make_float2(0.f, 0.f);
      }
      float st[13];
#pragma unroll
      for (int i = 0; i < 13; i++) st[i] = 0.f;
#pragma unroll 1
      for (int i = 0; i < 4; i++) {
        mbar_wait(bar + B_XST + 8 * (i >> 1), 0);
        if (f == 0 && lane == 0 && i == 0) PROF(1);
        const uint4 wu = lds128u(sb + SM_XSEL + i * 512 + lane * 16);
        const float wf[8] = {bf_lo(wu.x), bf_hi(wu.x), bf_lo(wu.y), bf_hi(wu.y), bf_lo(wu.z), bf_hi(wu.z), bf_lo(wu.w), bf_hi(wu.w)};
        st[12] += ((wf[0] + wf[1]) + (wf[2] + wf[3])) + ((wf[4] + wf[5]) + (wf[6] + wf[7]));
#pragma unroll
        for (int r = 0; r < 4; r++) {
          const uint4 u = lds128u(sb + SM_XST + i * 8192 + (4 * f + r) * 512 + lane * 16);
          const float xf[8] = {bf_lo(u.x), bf_hi(u.x), bf_lo(u.y), bf_hi(u.y), bf_lo(u.z), bf_hi(u.z), bf_lo(u.w), bf_hi(u.w)};
#pragma unroll
          for (int k = 0; k < 8; k++) { st[r] += xf[k]; st[4 + r] = fmaf(xf[k], xf[k], st[4 + r]); st[8 + r] = fmaf(xf[k], wf[k], st[8 + r]); }
        }
        if (i >= 2 && f < 3) STAGEG(n0 + i - 2);
      }
      const bool up = lane & 16, up2 = lane & 8;
#pragma unroll
      for (int q = 0; q < 3; q++) {
        const float k0 = up ? st[4 * q + 2] : st[4 * q], k1 = up ? st[4 * q + 3] : st[4 * q + 1];
        const float o0 = up ? st[4 * q] : st[4 * q + 2], o1 = up ? st[4 * q + 1] : st[4 * q + 3];
        const float m0 = k0 + __shfl_xor_sync(~0u, o0, 16), m1 = k1 + __shfl_xor_sync(~0u, o1, 16);
        a[q] = (up2 ? m1 : m0) + __shfl_xor_sync(~0u, up2 ? m0 : m1, 8);
      }
      a[3] = st[12] + __shfl_xor_sync(~0u, st[12], 16);
      a[3] += __shfl_xor_sync(~0u, a[3], 8);
#pragma unroll
      for (int o = 4; o; o >>= 1)
#pragma unroll
        for (int q = 0; q < 4; q++) a[q] += __shfl_xor_sync(~0u, a[q], o);
      if ((lane & 7) == 0) sts128(sb + SM_ROWS + (4 * f + (lane >> 3)) * 16, a[0], a[1], a[2], a[3]);
      if (f < 3) asm volatile("bar.arrive 7, 128;" ::: "memory");
    }
    if (f == 3) {
      bar_sync(7, 128);
      const int row = bid * 16 + (lane & 15);
      const float4 v = lds128(sb + SM_ROWS + (lane & 15) * 16);
      const float mf = v.x * (1.f / DM), mean = bf_round(mf), var = fmaxf(fmaf(-mf, mf, v.y * (1.f / DM)), 0.f);
      const float sd = bf_round(sqrt_approx(bf_round(bf_round(var) + 1e-5f)));
      const uint32_t rb = pack2(fmaf(-mean, v.w, v.z) * rcp(sd), 0.f) & 0xffffu, ord = (rb & 0x8000u) ? (~rb & 0xffffu) : (rb | 0x8000u);
      uint32_t best = __reduce_max_sync(~0u, (ord << 16) | (uint32_t)(2047 - row));
      if (lane < 16) st_rlx64(g_stat + row, ((unsigned long long)tag << 32) | __float_as_uint(mean) | (__float_as_uint(sd) >> 16));
      if (lane == 0) { asm volatile("red.relaxed.gpu.global.max.u64 [%0], %1;" ::"l"(g_best + bid), "l"(((unsigned long long)tag << 32) | best) : "memory"); PROF(17); }
#pragma unroll 1
      for (int n = 3; n < 5; n++) STAGEG(n);
      {
        uint4 xr[4];
        best = routed_row(P.x, tag, lane, xr);
#pragma unroll
        for (int i = 0; i < (GROWS + 255) / 256; i++) {
          const uint32_t dst = sb + SM_XSEL + i * 1024 + (lane >> 2) * 128 + (lane & 3) * 8;
          sts64(dst, bf_lo(xr[i].x), bf_lo(xr[i].z)); sts64(dst + 32, bf_hi(xr[i].x), bf_hi(xr[i].z));
          sts64(dst + 64, bf_lo(xr[i].y), bf_lo(xr[i].w)); sts64(dst + 96, bf_hi(xr[i].y), bf_hi(xr[i].w));
        }
        sts64u(sb + SM_RED + 16, tag, best);
        __syncwarp();
        if (lane == 0) { mbar_arrive(bar + B_XS); PROF(19); }
      }
      unsigned long long sv4[4];
      uint4 u[4];
#pragma unroll 1
      for (int it = 0; it < SPIN_MAX; it++) {
#pragma unroll
        for (int i = 0; i < 4; i++) { u[i] = ld_rlx128(g_cs + (1 + i) * 1024 + hg * 128 + lane * 4); sv4[i] = ld_rlx64(g_stat + mb * 128 + i * 32 + lane); }
        bool ok = ((BAD4(u[0]) | BAD4(u[1]) | BAD4(u[2]) | BAD4(u[3])) & 1) == 0;
#pragma unroll
        for (int i = 0; i < 4; i++) ok = ok && (uint32_t)(sv4[i] >> 32) == tag;
        if (__all_sync(~0u, ok)) break;
        __nanosleep(200);
      }
#pragma unroll
      for (int i = 0; i < 4; i++) {
        const uint32_t sv = (uint32_t)sv4[i], sd2 = (sv << 16) | (sv & 0xffffu);
        sts64(sb + SM_STAT + (i * 32 + lane) * 8, -bf_hi(sv), rcp(bf_lo(sv)));
        sts128u(sb + SM_SDT + lane * 64 + ((i ^ ((lane >> 1) & 3)) << 4), sd2, sd2, sd2, sd2);
      }
#pragma unroll
      for (int i = 0; i < 2; i++) {
        float4 c = make_float4(unmark(u[i].x) + unmark(u[i + 2].x), unmark(u[i].y) + unmark(u[i + 2].y), unmark(u[i].z) + unmark(u[i + 2].z),
                               unmark(u[i].w) + unmark(u[i + 2].w));
        CS_STORE(i, c);
      }
      fence_async_smem();
      bar_sync(8, 64);
      if (lane == 0) { mbar_arrive(bar + B_CS); PROF(10); }
    }
    {
      uint32_t xa = sb + SM_RED + 32, xstep = 0;
      const uint32_t zero = __float_as_uint(lds32(sb + SM_RED + 12));
#pragma unroll 1
      for (int ph = f == 3; ph < 2; ph++) {
#pragma unroll
        for (int j = 0; j < 8; j++) a[j] = 0.f;
        if (ph && f == 0) {
        {
          mbar_wait(bar + B_WPHI, 0);
          float nq[8] = {0.f, 0.f, 0.f, 0.f, 0.f, 0.f, 0.f, 0.f};
  #pragma unroll 2
          for (int r = 0; r < 16; r++) {
            const uint4 u = lds128u(sb + SM_WPHI + ((lane >> 2) * 16 + r) * 64 + (((lane ^ (r >> 1)) & 3) << 4));
            nq[0] = fmaf(bf_lo(u.x), bf_lo(u.x), nq[0]); nq[1] = fmaf(bf_hi(u.x), bf_hi(u.x), nq[1]); nq[2] = fmaf(bf_lo(u.y), bf_lo(u.y), nq[2]);
            nq[3] = fmaf(bf_hi(u.y), bf_hi(u.y), nq[3]); nq[4] = fmaf(bf_lo(u.z), bf_lo(u.z), nq[4]); nq[5] = fmaf(bf_hi(u.z), bf_hi(u.z), nq[5]);
            nq[6] = fmaf(bf_lo(u.w), bf_lo(u.w), nq[6]); nq[7] = fmaf(bf_hi(u.w), bf_hi(u.w), nq[7]);
          }
          uint32_t m = 0;
  #pragma unroll
          for (int i = 0; i < 8; i++) m = max(m, __float_as_uint(nq[i] + __shfl_xor_sync(~0u, nq[i], 4)) & 0x7fffffffu);
          sts32(sb + SM_RED + 24, 4.2f * __uint_as_float(__reduce_max_sync(~0u, m)));
        }
          asm volatile("bar.arrive 8, 64;" ::: "memory");
        }
        if (ph) { mbar_wait(bar + B_XS, 0); xa = sb + SM_XSEL + f * (GN * 128) + ((lane >> 2) & 3) * 32; xstep = 128; }
#pragma unroll 1
        for (int n = ph ? 3 : n0; n < (ph ? ne : 3); n++) {
          const float4 x0 = lds128(xa), x1 = lds128(xa + 16);
          xa += xstep;
          mbar_wait(fbar + (n & 1) * 8, ((n - n0) >> 1) & 1);
          uint4 u[8];
#pragma unroll
          for (int j = 0; j < 8; j++) u[j] = lds128u(fst + (n & 1) * 4096 + j * 256);
          FMA8(a, u[0], x0.x); FMA8(a, u[1], x0.y); FMA8(a, u[2], x0.z); FMA8(a, u[3], x0.w);
          if (__any_sync(~0u, ((u[4].x | u[5].x | u[6].x | u[7].x | __float_as_uint(a[0]) | __float_as_uint(a[7])) & zero) == 0)) STAGEG(n + 2);
          FMA8(a, u[4], x1.x); FMA8(a, u[5], x1.y); FMA8(a, u[6], x1.z); FMA8(a, u[7], x1.w);
        }
#pragma unroll
        for (int o = 4; o <= 8; o <<= 1)
#pragma unroll
          for (int j = 0; j < 8; j++) a[j] += __shfl_xor_sync(~0u, a[j], o);
        if (ph && lane == 0) mbar_arrive(bar + B_FFN);
        const uint32_t red = ph ? sb + SM_GRED : sb + SM_RED + 64;
        if ((lane & 12) == 0) {
          const uint32_t d = red + f * 256 + (lane >> 4) * 128 + (lane & 3) * 32;
          sts128(d, a[0], a[1], a[2], a[3]); sts128(d + 16, a[4], a[5], a[6], a[7]);
        }
        if (f != 2) {
          asm volatile("bar.arrive %0, %1;" ::"r"(4 + ph), "r"(96 + 32 * ph) : "memory");
        } else {
          bar_sync(4 + ph, 96 + 32 * ph);
          const uint32_t ra = red + lane * 4;
          gsum = lds32(ra) + lds32(ra + 256) + lds32(ra + 512);
          usum = lds32(ra + 128) + lds32(ra + 384) + lds32(ra + 640);
          if (!ph) st_rlx(g_cs + 1024 + ch * 2048 + cu * 32 + lane, mark(__float_as_uint(gsum + usum), par));
          else { gsum += lds32(ra + 768); usum += lds32(ra + 896); }
          if (lane == 0) PROF(ph ? 34 : 18);
        }
      }
    }
    if (f == 3) {
      if (elect_one()) {
        PROF(7);
        mbar_wait(bar + B_FULLQ, 0);
#pragma unroll 1
        for (int j = 3; j < 16; j++) {
          mbar_wait(bar + (j < 4 ? B_EMPTYKV + 16 : B_EMPTYQ + 8 * (j & 3)), ((j >> 2) & 1) ^ 1);
          if (j == 12 + (hg & 3)) mbar_wait(bar + B_KVST + 8, 0);
          Q_LOAD(j);
        }
        PROF(47);
        mbar_expect_tx(bar + B_DN, 65536);
#pragma unroll 1
        for (int i = 0; i < 4; i++) {
          mbar_wait(bar + B_EMPTYQ + 8 * i, 1);
          tma3d(sb + i * Q_STAGE, &mD, 0, fb * 32, i * 4, bar + B_DN);
        }
        PROF(48);
#pragma unroll 1
        for (int i = 0; i < 16; i++) {
          const int s = i & 3, n = i < 9 ? i - 2 : i - 9, kb = i < 2 ? 2 * hg + i : 2 * (n + (n >= hg)) + (i >= 9);
          if (i >= 4) mbar_wait(bar + B_EMPTYQ + 8 * s, ((i >> 2) & 1) ^ 1);
          mbar_expect_tx(bar + B_FULLQ + 8 * s, 16384);
          if (i < 2) {
            mbar_arrive2(bar + B_FULLQ + 8 * s);
            tma3d(sb + s * Q_STAGE + 16384, &mWo, 0, kb * 64, hg * 2, bar + B_FULLQ + 8 * s);
          } else {
            tma5d(sb + s * Q_STAGE + 16384, &mWp, hg * 128, kb * 2, bar + B_FULLQ + 8 * s);
            tma5d(sb + s * Q_STAGE + 24576, &mWp, hg * 128 + 64, kb * 2, bar + B_FULLQ + 8 * s);
            if (i >= 3) {
              if (i == 3) { mbar_wait(bar + B_DND, 0); PROF(14); }
#pragma unroll 1
              for (int a = i == 3 ? 2 : i; a <= i; a++) {
                const uint4* src = g_ofr + (mb * 16 + (a == 2 ? (hg == 0 ? 2 : 0) : kb)) * 1024;
#pragma unroll
                for (int h = 0; h < 2; h++) {
                  mbar_expect_tx(bar + B_AIN + (a & 3) * 16 + h * 8, 8192);
                  bulk_load(sb + (a & 3) * Q_STAGE + h * 8192, src + h * 512, 8192, bar + B_AIN + (a & 3) * 16 + h * 8);
                }
              }
            }
          }
        }
      }
    } else {
      if (f == 2) {
        if (PFD && ffn) {
#pragma unroll 1
          for (int i = 0; i < 16; i++) { touch_l2((const char*)P.w_down + fb * 65536 + i * 4096 + lane * 128, lane); __nanosleep(PFD); }
        }
        if (WOT) {
#pragma unroll 1
          for (int i = 0; i < 8; i++) { touch_l2((const char*)P.wo + ((mb & 7) * 128 + i * 16 + (lane >> 1)) * 2048 + hg * 256 + (lane & 1) * 128, lane); __nanosleep(PFD); }
        }
        asm volatile("cp.async.wait_all;" ::: "memory");
        uint4 u;
#pragma unroll 1
        for (int it = 0; it < SPIN_MAX; it++) {
          u = ld_rlx128(g_cs + hg * 128 + lane * 4);
          if (__all_sync(~0u, !(BAD4(u) & 1))) break;
          __nanosleep(200);
        }
        mbar_wait(bar + B_PHI, 0);
        float4 c = make_float4(unmark(u.x), unmark(u.y), unmark(u.z), unmark(u.w));
        CS_STORE(2, c);
        fence_async_smem();
        __syncwarp();
        if (lane == 0) mbar_arrive(bar + B_CSQ);
      }
      const uint32_t target = __shfl_sync(~0u, tag, 0) * 16;
#pragma unroll 1
      for (int R = 0; R < 2; R++) {
        const uint32_t own = (hg * 2 + R) * 16 + mb, pst = sb + (R ? SM_PST1 : SM_PST0);
        if (f == R) {
          mbar_wait(bar + B_KVST + 8 * R, 0);
          if (f == 1 && lane == 0) PROF(11);
          wait_hint(g_xcnt + hg * 64 + R * 16 + mb, target);
          if (elect_one()) {
            PROF(35 + R);
            fence_async_global();
            mbar_expect_tx(bar + B_PART + 8 * R, 8192);
            bulk_load(pst, g_part + own * 512, 8192, bar + B_PART + 8 * R);
          }
          __syncwarp();
          uint4 uz;
#pragma unroll 1
          for (int it = 0; it < SPIN_MAX; it++) {
            uz = ld_rlx128(g_zpart + own * 128 + lane * 4);
            if (__all_sync(~0u, !(BAD4(uz) & 1))) break;
          }
          const bool b1 = lane & 2, b2 = lane & 4;
          const float z0 = unmark(b1 ? uz.z : uz.x) + __shfl_xor_sync(~0u, unmark(b1 ? uz.x : uz.z), 2);
          const float z1 = unmark(b1 ? uz.w : uz.y) + __shfl_xor_sync(~0u, unmark(b1 ? uz.y : uz.w), 2);
          float z = (b2 ? z1 : z0) + __shfl_xor_sync(~0u, b2 ? z0 : z1, 4);
          z += __shfl_xor_sync(~0u, z, 8);
          z += __shfl_xor_sync(~0u, z, 16);
          if (lane < 8) st_rlx(g_zres + own * 8 + (lane & 1) * 4 + (lane & 2) + (lane >> 2), mark(__float_as_uint(z), par));
          if (HOP2_HINT && lane == 0) red_inc(g_xcnt + hg * 64 + 32 + R * 16);
          __syncwarp();
        }
        if (f == R || f == R + 1) {
          const uint32_t hf = f - R, m1 = ~lane & 1, gq = hf * 4 + (lane >> 3), ts = (lane >> 1) & 3;
          float a0 = 0.f, a1 = 0.f, a2 = 0.f, a3 = 0.f;
          mbar_wait(bar + B_PART + 8 * R, 0);
#pragma unroll 1
          for (int it = 0; it < SPIN_MAX; it++) {
            uint32_t bad = 0;
            a0 = a1 = a2 = a3 = 0.f;
#pragma unroll 1
            for (int b = 0; b < 16; b += 8) {
              uint2 u[8];
              if (it == 0) {
#pragma unroll
                for (int i = 0; i < 8; i++) { const float2 v = lds64(pst + (b + i) * 512 + hf * 256 + lane * 8); u[i] = make_uint2(__float_as_uint(v.x), __float_as_uint(v.y)); }
              } else {
#pragma unroll
                for (int i = 0; i < 8; i++) {
                  const unsigned long long v = ld_rlx64((const unsigned long long*)g_part + own * 1024 + (b + i) * 64 + hf * 32 + lane);
                  u[i] = make_uint2((uint32_t)v, (uint32_t)(v >> 32));
                }
              }
#pragma unroll
              for (int i = 0; i < 8; i++) {
                bad |= u[i].x ^ par;
                a0 += bf_lo(i & 1 ? u[i].x & ~m1 : u[i].x | m1); a1 += bf_hi(u[i].x); a2 += bf_lo(u[i].y); a3 += bf_hi(u[i].y);
              }
            }
            if (__all_sync(~0u, !(bad & m1))) break;
          }
          uint32_t* dst = (uint32_t*)g_res[par] + own * 128 + gq * 16 + ts;
          const uint32_t j0 = (lane & 1) * 2, vb = ts == (gq >> 1);
          st_rlx(dst + ((j0 ^ (gq >> 1)) & 3) * 4, pack2(a0, a1) | vb);
          st_rlx(dst + (((j0 + 1) ^ (gq >> 1)) & 3) * 4, pack2(a2, a3) | vb);
          ((uint2*)g_res[par ^ 1])[own * 64 + hf * 32 + lane] = make_uint2(0u, 0u);
          __syncwarp();
          if (lane == 0) { if (HOP2_HINT) red_inc(g_xcnt + hg * 64 + 32 + R * 16); if (!hf) PROF(R ? 12 : 30); }
        }
      }
      if (f == 2) {
        if (ffn && !FFN_OFF) {
#pragma unroll 1
          for (int it = 0; it < SPIN_MAX; it++) {
            const uint32_t pg = ld_rlx((const uint32_t*)g_gp + fb * 32 + lane), pu = ld_rlx((const uint32_t*)g_gp + FF + fb * 32 + lane);
            if (__all_sync(~0u, !(((pg ^ par) | (pu ^ par)) & 1))) { gsum += unmark(pg); usum += unmark(pu); break; }
            __nanosleep(200);
          }
        }
        const float h = bf_round(silu_f(bf_round(gsum))) * bf_round(usum);
        const uint32_t h2 = pack2(h, h);
        sts128u(sb + SM_HT + lane * 16, h2, h2, h2, h2);
        fence_async_smem();
        __syncwarp();
        if (lane == 0) { mbar_arrive(bar + B_H); PROF(20); }
      }
      if (f < 2) {
        if (HOP2_HINT) wait_hint(g_xcnt + hg * 64 + 32 + f * 16, 3 * target);
        mbar_wait(bar + B_KVST + 8, 0);
        if (lane == 0) PROF(40 + f);
#pragma unroll 1
        for (int it = 0; it < SPIN_MAX; it++) {
          if (elect_one()) {
            fence_async_global();
            mbar_expect_tx(bar + B_RES + 8 * f, 8192);
            bulk_load(sb + SM_V + f * 8192, g_res[par] + (hg * 4 + f * 2) * 256, 8192, bar + B_RES + 8 * f);
          }
          __syncwarp();
          const uint4 uz = ld_rlx128(g_zres + (hg * 4 + f * 2) * 64 + lane * 4);
          const uint32_t zw[4] = {uz.x, uz.y, uz.z, uz.w};
#pragma unroll
          for (int j = 0; j < 4; j++) {
            const uint32_t zz = pack2(unmark(zw[j]), 1.f), row = (lane & 3) * 4 + j;
            sts128u(sb + SM_ZT + (2 * f + (lane >> 4)) * 1024 + row * 64 + ((((lane >> 2) ^ (row >> 1)) & 3) << 4), zz, zz, zz, zz);
          }
          uint32_t bad = BAD4(uz);
          mbar_wait(bar + B_RES + 8 * f, it & 1);
#pragma unroll
          for (int i = 0; i < 16; i++) bad |= ~__float_as_uint(lds32(sb + SM_V + f * 8192 + i * 512 + lane * 16 + (lane >> 3) * 4));
          if (__all_sync(~0u, !(bad & 1))) break;
        }
        fence_async_smem();
        __syncwarp();
        if (lane == 0) { mbar_arrive(bar + B_TILE + 8 * f); PROF(f ? 13 : 27); }
      }
      if (f < 2) {
        uint32_t phases = 0;
#pragma unroll 1
        for (int i = 2; i < 16; i++) {
          const int s = i & 3;
          const uint32_t ab = bar + B_AIN + s * 16 + f * 8, slot = sb + s * Q_STAGE + f * 8192;
#pragma unroll 1
          for (int it = 0; it < SPIN_MAX; it++) {
            mbar_wait(ab, (phases >> s) & 1);
            phases ^= 1u << s;
            uint32_t bad = 0;
#pragma unroll
            for (int n = 0; n < (NOVAL ? 0 : 8); n++) bad |= __float_as_uint(lds32(slot + n * 1024 + lane * 32 + (lane >> 2) * 4)) ^ par;
            if (__all_sync(~0u, !(bad & 1))) break;
            if (elect_one()) {
              const int n = i < 9 ? i - 2 : i - 9, kb = 2 * (n + (n >= hg)) + (i >= 9);
              PROF(49);
              mbar_expect_tx(ab, 8192);
              bulk_load(slot, g_ofr + (mb * 16 + kb) * 1024 + f * 512, 8192, ab);
            }
            __syncwarp();
          }
          if (lane == 0) { mbar_arrive(bar + B_FULLQ + 8 * s); if (i == 2 && f == 0) PROF(15); }
        }
        if (f == 0) g_epoch[bid * 32 + lane] = tag;
      } else {
        if (elect_one()) {
          prefetch_map(&mOut);
          if (ffn) { mbar_wait(bar + B_YD, 0); red_rel(g_ycnt); PROF(21); }
        }
        __syncwarp();
        if (f == 2) {
          const uint32_t best = __float_as_uint(lds32(sb + SM_RED + 20));
          const int sel = 2047 - (best & 0x7ff) - mb * 128;
          if (sel >= 0 && sel < 128) {
            const uint2 xr = __ldg((const uint2*)(P.x + (size_t)(mb * 128 + sel) * DM + hg * 128 + lane * 4));
            const float2 st = lds64(sb + SM_STAT + sel * 8);
            const uint32_t ord = best >> 16, rb = (ord & 0x8000u) ? (ord & 0x7fffu) : (~ord & 0xffffu);
            const float sg = rcp(1.f + ex2(-1.4426950408889634f * bf_lo(rb)));
            const uint32_t sg2 = pack2(sg, sg), nm2 = pack2(st.x, st.x);
            wait_cnt<0>(g_ycnt, tag * NFFN);
            float4 y = make_float4(0.f, 0.f, 0.f, 0.f);
#pragma unroll
            for (int i = 0; i < 8; i++) {
              const float4 c = ldg_cg4(g_y[par ^ 1][i] + hg * 128 + lane * 4);
              y.x += c.x; y.y += c.y; y.z += c.z; y.w += c.w;
            }
            uint32_t o[2];
#pragma unroll
            for (int i = 0; i < 2; i++) {
              const uint32_t d = badd2(i ? xr.y : xr.x, nm2);
              const uint32_t tt = badd2(pack2(bf_lo(d) * st.y, bf_hi(d) * st.y), bmul2(i ? pack2(y.z, y.w) : pack2(y.x, y.y), sg2));
              o[i] = pack2(silu_f(bf_lo(tt)), silu_f(bf_hi(tt)));
            }
            sts64u(sb + SM_UPD + lane * 8, o[0], o[1]);
          }
          if (lane == 0) sts32(sb + SM_UPD + 256, __int_as_float(sel));
          __syncwarp();
          if (lane == 0) { mbar_arrive(bar + B_UPD); PROF(22); }
        }
      }
    }
  } else {
    const int t7 = threadIdx.x & 127;
    const char* pfa = warp < 4 ? (const char*)P.x + bid * 32768 + (t7 & 15) * 2048 + (t7 >> 4) * 128
                               : (const char*)P.wqkv + (size_t)((t7 >> 4) * 64 + (bid >> 1)) * 6144 + 2048 + (bid & 1) * 2048 + (t7 & 15) * 128;
    if (t7 >= 16 && t7 < 16 * PF_FIRST) prefetch_l2(pfa);
    if (warp < 7) sts128(sb + SM_CST + threadIdx.x * 16, 0.f, 0.f, 0.f, 0.f);
    else sts32(sb + SM_RED + (threadIdx.x & 15) * 4, threadIdx.x & 8 ? 1.f : 0.f);
    if (elect_one()) {
#pragma unroll 1
      for (uint32_t b = B_FST + warp * 8; b < B_END; b += 64)
        mbar_init(bar + b, b < B_FULLQ ? 1 : b < B_FFN ? 3 : b < B_EMPTYKV ? 4 : 8);
    }
    __syncwarp();
    asm volatile("bar.arrive 13, 384;" ::: "memory");
    asm volatile("setmaxnreg.inc.sync.aligned.u32 %0;" ::"n"(REG_C));
    if (t7 >= 16 * PF_FIRST && threadIdx.x < 128 + 16 * PF_W) prefetch_l2(pfa);
    asm volatile("cp.async.wait_all;" ::: "memory");
    fence_async_smem();
    bar_sync(14, 288);
    if (threadIdx.x == 0) mbar_arrive(bar + B_FULLKV + 16);
    const int lane = lane_id();
    const int wg = warp >> 2, w = warp & 3, g = lane >> 2, t = lane & 3;
    float kv[128];
    {
      uint32_t s = 2, ph = 0, sp = 0, php = 0;
#pragma unroll 1
      for (int j = 0; j < 15; j++) {
        PW0(32 + j); mbar_wait(bar + B_FULLKV + 8 * s, ph); PW1(32 + j);
        if (wg == 1 && (ORDER_ALL || j == 0)) bar_sync(10 + s, 256);
        wg_fence();
        wgmma_n256_ssp_ta0_tb1(kv, mkdesc(sb, 16, 1024, 1, wg * 512 + s * (KV_STAGE / 16)), mkdesc(sb + 16384, 8192, 1024, 1, s * (KV_STAGE / 16)), j);
#pragma unroll
        for (int k = 1; k < 4; k++)
          wgmma_n256_ss_ta0_tb1(kv, mkdesc(sb + k * 32, 16, 1024, 1, wg * 512 + s * (KV_STAGE / 16)),
                                mkdesc(sb + 16384 + k * 2048, 8192, 1024, 1, s * (KV_STAGE / 16)), 1);
        wg_commit();
        if (wg == 0 && (ORDER_ALL || j == 0)) asm volatile("bar.arrive %0, 256;" ::"r"(10 + s) : "memory");
        if (warp == 0 && j) {
          mbar_wait(bar + B_EMPTYKV + 8 * sp, php);
          if (elect_one()) {
            if (j < 14) {
              mbar_expect_tx(bar + B_FULLKV + 8 * sp, KV_STAGE);
              tma2d(sb + sp * KV_STAGE, &mX, (j + 2) * 64, mb * 128, bar + B_FULLKV + 8 * sp);
              tma4d(sb + sp * KV_STAGE + 16384, &mWkv, 0, (j + 2) * 64, hg * 2, 1, bar + B_FULLKV + 8 * sp);
            } else {
              Q_LOAD(0);
            }
            if (j < 3 - XS_EARLY) {
              const int xh = j - 1 + XS_EARLY;
              mbar_expect_tx(bar + B_XST + 8 * xh, 16384);
              tma3d(sb + SM_XST + xh * 16384, &mXs, 0, bid * 16, 2 * xh, bar + B_XST + 8 * xh);
            }
          }
          __syncwarp();
        }
        if (j == 0) {
          if (wg == 0) prefetch_l2(pfa + 1024);
        } else if (wg == 1) {
          if (j < 3) {
            if (j == 2 || t7 >= 16 * PF_W) prefetch_l2(pfa + (j - 1) * (8 * 393216));
          } else if (j == 13) {
            prefetch_l2((const char*)P.wo + bid * 16384 + t7 * 128);
          }
          if (PFG && !FFN_OFF && bid < NFFN && j >= 2 && j < 2 + GROWS / 64 && w < 2)
            touch_l2((const char*)((bid & 1) ? P.w_up : P.w_gate) + (size_t)((0x852a7419630ull >> (4 * j - 8) & 15) * 64 + t7) * 7168 + (bid >> 1) * 128, lane);
        }
        wg_wait<0>();
        if (lane == 0) mbar_arrive(bar + B_EMPTYKV + 8 * s);
        sp = s; php = ph;
        ph ^= s == 1;
        s = s == 2 ? 0 : s + 1;
      }
    }
    const int lrow = wg * 64 + w * 16 + (lane & 15);
    const uint32_t sw128 = lrow * 128, x128 = (lrow & 7), hi16 = lane >> 4;
    mbar_wait(bar + B_CS, 0);
    const uint32_t tag = __float_as_uint(lds32(sb + SM_RED + 16));
    const int zero = __float_as_int(lds32(sb + SM_RED + 12));
    const float wn = lds32(sb + SM_RED + 24);
    const float2 st0 = lds64(sb + SM_STAT + (wg * 64 + w * 16 + g) * 8), st1 = lds64(sb + SM_STAT + (wg * 64 + w * 16 + g + 8) * 8);
    const float c0 = st0.y * 1.4426950408889634f, c1 = st1.y * 1.4426950408889634f;
    const uint32_t nm20 = pack2(st0.x, st0.x), nm21 = pack2(st1.x, st1.x), fmask = t == 0 ? ~0u : t == 1 ? 0xffffu : 0u;
    const uint32_t fa0 = nm20 & fmask, fa1 = nm21 & fmask;
    asm volatile("cp.async.wait_all;" ::: "memory");
    PW0(47); mbar_wait(bar + B_FULLKV + 16, 1); PW1(47);
    wg_fence();
    wgmma_n256_rs_ta0_tb1(kv, fa0, fa1, 0u, 0u, mkdesc(sb + SM_CST, 512, 0, 1), 1);
#pragma unroll
    for (int k = 0; k < 4; k++)
      wgmma_n256_ss_ta0_tb1(kv, mkdesc(sb + 2 * KV_STAGE + k * 32, 16, 1024, 1, wg * 512), mkdesc(sb + 2 * KV_STAGE + 16384 + k * 2048, 8192, 1024, 1), 1);
    wg_commit();
    if (warp == 0) {
      mbar_wait(bar + B_EMPTYKV + 8, 0);
      if (elect_one()) {
#pragma unroll 1
        for (int j = 1; j < 3; j++) Q_LOAD(j);
      }
      __syncwarp();
    }
    wg_wait<0>();
    reg_fence<128>(kv);
    if (lane == 0) mbar_arrive(bar + B_EMPTYKV + 16);
    PROFC(2);
    float q[64];
#define QMMA(J, AOFF16, ACCUM)                                                                                     \
  _Pragma("unroll") for (int k = 0; k < 4; k++)                                                                    \
      wgmma_n128_ss_ta0_tb1(q, mkdesc(sb + k * 32, 16, 1024, 1, wg * 512 + (AOFF16)),                              \
                            mkdesc(sb + 16384 + k * 2048, 8192, 1024, 1, ((J) & 3) * (Q_STAGE / 16)), k ? 1 : (ACCUM))
#define QWAIT(J) do { PW0(J); mbar_wait(bar + B_FULLQ + 8 * ((J) & 3), ((J) >> 2) & 1); PW1(J); } while (0)
#define QSTEP_A(J, AOFF16, ACCUM) do { QWAIT(J); wg_fence(); QMMA(J, AOFF16, ACCUM); wg_commit(); } while (0)
#define QREL(J) do { if (lane == 0) mbar_arrive(bar + B_EMPTYQ + 8 * ((J) & 3)); } while (0)
#define Q_OFF16(J) ((J) >= 8 && (J) < 16 ? Q_AOFF(J) / 16 : ((J) & 3) * (Q_STAGE / 16))
#define QPLAIN(J) do { QSTEP_A(J, Q_OFF16(J), 1); wg_wait<1>(); QREL((J) - 1); } while (0)
#define QNEXT(J) do { QPLAIN(J); SCHED_FENCE(); } while (0)
#define PHI_PROJ(DST, SRC, H0, H1)                                                                                 \
  do {                                                                                                             \
    uint32_t a_[32];                                                                                               \
    _Pragma("unroll") for (int j = 8 * (H0); j < 8 * (H1); j++) {                                                  \
      a_[j] = pack2(SRC[2 * j], SRC[2 * j + 1]);                                                                   \
      asm volatile("fma.rn.bf16x2 %0, %1, %1, %0;" : "+r"(nq[(j >> 4) * 2 + (j & 1)]) : "r"(a_[j]));               \
    }                                                                                                              \
    wg_fence();                                                                                                    \
    _Pragma("unroll") for (int hk = 2 * (H0); hk < 2 * (H1); hk++)                                                 \
        wgmma_n32_rs_ta0_tb1(DST + 16 * (hk >> 1), a_[4 * hk], a_[4 * hk + 1], a_[4 * hk + 2], a_[4 * hk + 3],     \
                             mkdesc(sb + SM_WPHI + hk * 1024, 16, 512, 2), hk & 1);                                \
    wg_commit();                                                                                                   \
  } while (0)
    {
      float p[64], ea[24], eb[24], sa[4], sc[4], kz[20];
      uint32_t vp[32];
#pragma unroll
      for (int j = 0; j < 32; j++) vp[j] = pack2(kv[64 + 2 * j], kv[65 + 2 * j]);
      const uint32_t vr = w * 16 + (lane & 15), vb = sb + SM_V + wg * 4096 + vr * 64, x64 = (vr >> 1) & 3;
#define V_STORE(R)                                                                                           \
  _Pragma("unroll") for (int j = 0; j < 4; j++)                                                              \
      stsm4(vb + (j >> 1) * 8192 + ((((j & 1) * 2 + hi16) ^ x64) << 4), vp[16 * (R) + 4 * j], vp[16 * (R) + 4 * j + 1], vp[16 * (R) + 4 * j + 2], vp[16 * (R) + 4 * j + 3])
      V_STORE(0);
      mbar_wait(bar + B_WPHI, 0);
      {
        uint32_t nq[4] = {0u, 0u, 0u, 0u};
        PHI_PROJ(p, kv, 0, 4);
        QSTEP_A(0, 0, 0);
        const bool unsafe = softmax_unsafe(nq, c0 * c0 * wn, c1 * c1 * wn);
        wg_wait<1>();
        reg_fence<64>(p);
        if (__builtin_expect(unsafe, 0)) softmax_shift(p, c0, c1);
      }
#define K_NORM(S) do { quad_sum<4>(S); _Pragma("unroll") for (int i = 0; i < 4; i++) S[i] = rcp(S[i]) * ((i & 1) ? st1.y : st0.y); } while (0)
#define K_STORE(SLOT, E, S) K_STORE_(SLOT, E, S, 0, 2)
#define K_STORE_(SLOT, E, S, J0, J1)                                                                         \
  _Pragma("unroll") for (int j = (J0); j < (J1); j++) {                                                      \
    uint32_t fp[4], fm[4];                                                                                   \
    _Pragma("unroll") for (int i = 0; i < 4; i++) {                                                          \
      const float e0 = E[8 * j + 2 * i], e1 = E[8 * j + 2 * i + 1], r = E[16 + 4 * j + i] * S[2 + (i & 1)];  \
      const uint32_t e2 = pack2(e0, e1);                                                                     \
      fp[i] = bmul2(e2, pack2(S[i & 1], S[i & 1]));                                                          \
      fm[i] = bmul2(e2, pack2(r, r));                                                                        \
    }                                                                                                        \
    stsm4(sb + SM_PHI + (SLOT) * 16384 + sw128 + (((2 * j + hi16) ^ x128) << 4), fp[0], fp[1], fp[2], fp[3]); \
    stsm4(sb + SM_PHI + (SLOT) * 16384 + sw128 + (((4 + 2 * j + hi16) ^ x128) << 4), fm[0], fm[1], fm[2], fm[3]); \
  }
#define KV_MMA(R)                                                                                            \
  do {                                                                                                       \
    mbar_wait(bar + B_PHI + 8 * (R), 0);                                                                     \
    wg_fence();                                                                                              \
    _Pragma("unroll") for (int k = 0; k < 8; k++) {                                                          \
      const uint32_t vs = SM_V + (k >> 2) * 4096 + (k & 3) * 1024;                                           \
      wgmma_n40_ss_ta1_tb1(kz, mkdesc(sb + SM_PHI + k * 2048, 16, 1024, 1, wg * 1024),                       \
                           mkdesc(sb + vs, SM_SDT + (k & 1) * 1024 + (k >> 1) * 16 - vs, 512, 2, wg * (512u - (512u << 16))), k); \
    }                                                                                                        \
    wg_commit();                                                                                             \
  } while (0)
#define QKV(J, R) do { KV_MMA(R); QSTEP_A(J, Q_OFF16(J), 1); wg_wait<2>(); QREL((J) - 1); SCHED_FENCE(); } while (0)
#define KV_SEND(R)                                                                                           \
  do {                                                                                                       \
    reg_fence<20>(kz);                                                                                       \
    if (lane == 0) mbar_arrive(bar + B_KVST + 8 * (R));                                                      \
    const uint32_t slot = ((hg * 2 + (R)) * 16 + warp * 2) * 16 + mb;                                        \
    _Pragma("unroll") for (int u = 0; u < 2; u++)                                                            \
      st_rlx128(g_part + (slot + u * 16) * 32 + lane, mark(pack2(kz[2 * u], kz[2 * u + 1]), tag & 1), pack2(kz[2 * u + 4], kz[2 * u + 5]), \
                pack2(kz[2 * u + 8], kz[2 * u + 9]), pack2(kz[2 * u + 12], kz[2 * u + 13]));                 \
    if (t < 2) st_rlx(g_zpart + (slot + t * 16) * 8 + g, mark(__float_as_uint(t ? kz[18] : kz[16]), tag & 1)); \
    if (lane < 2) red_inc(g_xcnt + hg * 64 + (R) * 16 + warp * 2 + lane);                                    \
  } while (0)
#define K_PUB(R) do { fence_async_smem(); __syncwarp(); if (lane == 0) mbar_arrive(bar + B_PHI + 8 * (R)); } while (0)
#define S_PIN(S) SCHED_PIN(S[0] + S[1] + S[2] + S[3])
      k_exp(p, c0, c1, ea, sa);
      S_PIN(sa);
      QNEXT(1);
      K_NORM(sa);
      k_exp<0, 4>(p + 16, c0, c1, eb, sc);
      mbar_wait(bar + B_FFN, 0);
      K_STORE_(0, ea, sa, 0, 1);
      S_PIN(sc);
      QNEXT(2);
      K_STORE_(0, ea, sa, 1, 2);
      k_exp<4, 8>(p + 16, c0, c1, eb, sc);
      K_NORM(sc);
      S_PIN(sc);
      QNEXT(3);
      K_STORE(1, eb, sc);
      K_PUB(0);
      k_exp<0, 4>(p + 32, c0, c1, ea, sa);
      S_PIN(sa);
      QKV(4, 0);
      k_exp<4, 8>(p + 32, c0, c1, ea, sa);
      K_NORM(sa);
      k_exp<0, 4>(p + 48, c0, c1, eb, sc);
      SCHED_PIN(sa[0] + sa[1] + sa[2] + sa[3] + sc[2] + sc[3]);
      QNEXT(5);
      KV_SEND(0);
      k_exp<4, 8>(p + 48, c0, c1, eb, sc);
      S_PIN(sc);
      QNEXT(6);
      K_NORM(sc);
      mbar_wait(bar + B_KVST, 0);
      V_STORE(1);
      K_STORE(0, ea, sa);
      QNEXT(7);
      K_STORE(1, eb, sc);
      K_PUB(1);
      QKV(8, 1);
      QNEXT(9);
      KV_SEND(1);
    }
#define JQ0 10
    PROFC(3);
#pragma unroll 1
    for (int j = JQ0; j < 15; j++) QPLAIN(j);
    mbar_wait(bar + B_CSQ, 0);
    QWAIT(15);
    if (wg == 1) bar_sync(6, 256);
    wg_fence();
    wgmma_n128_rs_ta0_tb1(q, fa0, fa1, 0u, 0u, mkdesc(sb + SM_CST + 2048, 512, 0, 1), 1);
    QMMA(15, Q_AOFF(15) / 16, 1);
    wg_commit();
    if (wg == 0) asm volatile("bar.arrive 6, 256;" ::: "memory");
    wg_wait<1>();
    QREL(14);
    wg_wait<0>();
    QREL(15);
    reg_fence<64>(q);
    PROFC(5);
    float yp[4];
    const uint32_t par = tag & 1;
    uint4* ofr = g_ofr + (mb * 16 + hg * 2) * 1024 + (warp * 16 + g) * 8;
#define O_MMA(H, F, N)                                                                                       \
  do {                                                                                                       \
    wg_fence();                                                                                              \
    _Pragma("unroll") for (int k = 0; k < 4; k++) {                                                          \
      const uint32_t ks = SM_V + (H) * 4096 + k * 1024;                                                      \
      wgmma_n40_rs_ta0_tb1(N + 20 * (k >> 1), F[4 * k], F[4 * k + 1], F[4 * k + 2], F[4 * k + 3],            \
                           mkdesc(sb + ks, SM_ZT + (H) * 1024 + k * 16 - ks, 512, 2), k & 1);                \
    }                                                                                                        \
    wg_commit();                                                                                             \
  } while (0)
#define O_FIN(H, N, o)                                                                                        \
  do {                                                                                                       \
    reg_fence<40>(N);                                                                                        \
    const float *np = N, *nm = N + 20;                                                                       \
    const float d0 = rcp(fmaf(np[16], nm[17], fmaf(nm[16], np[17], 1e-6f * np[17] * nm[17])));               \
    const float d1 = rcp(fmaf(np[18], nm[19], fmaf(nm[18], np[19], 1e-6f * np[19] * nm[19])));               \
    const float bp0 = nm[17] * d0, bm0 = np[17] * d0, bp1 = nm[19] * d1, bm1 = np[19] * d1;                  \
    _Pragma("unroll") for (int j = 0; j < 4; j++) {                                                          \
      o[2 * j] = pack2(fmaf(np[4 * j], bp0, nm[4 * j] * bm0), fmaf(np[4 * j + 1], bp0, nm[4 * j + 1] * bm0)); \
      o[2 * j + 1] = pack2(fmaf(np[4 * j + 2], bp1, nm[4 * j + 2] * bm1), fmaf(np[4 * j + 3], bp1, nm[4 * j + 3] * bm1)); \
    }                                                                                                        \
  } while (0)
#define O_STG(H, o)                                                                                          \
  _Pragma("unroll") for (int u = 0; u < 2; u++) {                                                            \
    uint32_t v_[4];                                                                                          \
    _Pragma("unroll") for (int j = 0; j < 4; j++) v_[j] = lop_select(o[2 * j + u], parm, vword == j);        \
    st_rlx128(ofr + ((H) >> 1) * 1024 + u * 64 + ((((H) & 1) * 4 + t) ^ g), v_[0], v_[1], v_[2], v_[3]);     \
  }
    uint32_t gf[32], ao[16];
    const uint32_t parm = 0u - par, vword = ((t ^ g) & 1) == (g >> 2) ? g & 3 : 4;
    const float rh0 = 0.5f * st0.y, rh1 = 0.5f * st1.y, mh0 = st0.x * rh0, mh1 = st1.x * rh1;
#define GATE_LD(J) ldsm4(sb + ((J) >> 2 ? SM_X1 : SM_X0) + sw128 + (((((J) & 3) * 2 + hi16) ^ x128) << 4), gf[4 * (J)], gf[4 * (J) + 1], gf[4 * (J) + 2], gf[4 * (J) + 3])
#define GATE(I0, I1)                                                                                         \
  _Pragma("unroll") for (int i = (I0); i < (I1); i++) {                                                      \
    const float rs = (i & 1) ? rh1 : rh0, mh = (i & 1) ? mh1 : mh0;                                          \
    const float h0 = fmaf(bf_lo(gf[i]), rs, mh), h1 = fmaf(bf_hi(gf[i]), rs, mh);                            \
    gf[i] = pack2(fmaf(h0, tanh_approx(h0), h0), fmaf(h1, tanh_approx(h1), h1));                             \
  }
#define GATE_PIN(I0, I1) do { uint32_t o_ = 0; _Pragma("unroll") for (int i = (I0); i < (I1); i++) o_ |= gf[i]; SCHED_PIN(__uint_as_float(o_)); } while (0)
    {
      float p[64], na[40], nb[40];
      uint32_t fa[16], fb[16];
      {
        uint32_t nq[4] = {0u, 0u, 0u, 0u};
        PHI_PROJ(p, q, 0, 2);
        SCHED_FENCE();
        PHI_PROJ(p, q, 2, 4);
        const bool unsafe = softmax_unsafe(nq, c0 * c0 * wn, c1 * c1 * wn);
        if (TW == 0) mbar_wait(bar + B_TILE, 0);
        wg_wait<0>();
        reg_fence<64>(p);
        PROFC(24);
        if (__builtin_expect(unsafe, 0)) softmax_shift(p, c0, c1);
      }
      float dn[32];
#define DN_PART(A, B)                                                                                        \
  do {                                                                                                       \
    wg_fence();                                                                                              \
    _Pragma("unroll") for (int i = (A); i < (B); i++)                                                        \
      wgmma_n8_ss_ta1_tb1(dn + 4 * (i >> 1), mkdesc(sb + (i >> 3) * Q_STAGE + (i & 7) * 2048, 16, 1024, 1, wg * (2 * Q_STAGE / 16)), \
                          mkdesc(sb + SM_HT + (i & 1) * 256, 128, 128, 0), i & 1);                           \
  } while (0)
#define F_PIN(F, A, B) do { uint32_t o_ = 0; _Pragma("unroll") for (int i = (A); i < (B); i++) o_ |= F[8 + i]; SCHED_PIN(__uint_as_float(o_)); } while (0)
#define RMMA(J, A, ACCUM)                                                                                    \
  do {                                                                                                       \
    wg_fence();                                                                                              \
    _Pragma("unroll") for (int k = 0; k < 4; k++)                                                            \
      wgmma_n128_rs_ta0_tb1(q, (A)[4 * k], (A)[4 * k + 1], (A)[4 * k + 2], (A)[4 * k + 3],                   \
                            mkdesc(sb + 16384 + k * 2048, 8192, 1024, 1, ((J) & 3) * (Q_STAGE / 16)), k ? 1 : (ACCUM)); \
    wg_commit();                                                                                             \
  } while (0)
#define RSTEP(J, A, ACCUM) do { QWAIT(J); RMMA(J, A, ACCUM); } while (0)
      PROFC(4);
      q_exp(p, c0, c1, fa);
      if (TW == 1) { F_PIN(fa, 0, 8); mbar_wait(bar + B_TILE, 0); }
      if (TW == 2) { q_exp(p + 16, c0, c1, fb); F_PIN(fb, 0, 8); mbar_wait(bar + B_TILE, 0); }
      O_MMA(0, fa, na);
      if (TW != 2) q_exp(p + 16, c0, c1, fb);
      O_MMA(1, fb, nb);
      PROFC(25);
      wg_wait<1>();
      O_FIN(0, na, ao);
      O_STG(0, ao);
      wg_wait<0>();
      O_FIN(1, nb, (ao + 8));
      O_STG(1, (ao + 8));
      PROFC(28);
      mbar_wait(bar + B_H, 0);
      mbar_wait(bar + B_DN, 0);
      PROFC(45);
      DN_PART(0, 16);
      wg_commit();
      wg_wait<0>();
      reg_fence<32>(dn);
#pragma unroll
      for (int i = 0; i < 4; i++) yp[i] = t & 2 ? (t & 1 ? dn[24 + 2 * i] : dn[16 + 2 * i]) : (t & 1 ? dn[8 + 2 * i] : dn[2 * i]);
      RSTEP(16, ao, 0);
      SCHED_FENCE();
      q_exp(p + 32, c0, c1, fa);
      if (DNX == 1) { F_PIN(fa, 0, 8); if (lane == 0) mbar_arrive(bar + B_DND); }
      q_exp(p + 48, c0, c1, fb);
      F_PIN(fb, 0, 8);
      if (DNX == 2 && lane == 0) mbar_arrive(bar + B_DND);
      wg_wait<0>();
      QREL(16);
      PROFC(29);
      mbar_wait(bar + B_TILE + 8, 0);
      PROFC(23);
      if (bid < NFFN) {
        float* y = g_y[par ^ 1][bid & 7] + wg * 512 + t * 128 + w * 16 + g;
#pragma unroll
        for (int i = 0; i < 4; i++) red1(y + (i >> 1) * 64 + (i & 1) * 8, yp[i]);
      }
      SCHED_FENCE();
      O_MMA(2, fa, na);
      O_MMA(3, fb, nb);
      __syncwarp();
      if (lane == 0) mbar_arrive(bar + B_YD);
      wg_wait<1>();
      O_FIN(2, na, ao);
      O_STG(2, ao);
      wg_wait<0>();
      O_FIN(3, nb, (ao + 8));
      O_STG(3, (ao + 8));
      PROFC(6);
    }
    RSTEP(17, ao, 1);
    SCHED_FENCE();
    GATE_LD(0); GATE_LD(1);
    GATE(0, 4);
    GATE_PIN(0, 4);
#define GSTEP(J, I) do { QNEXT(J); if ((I) < 7) GATE_LD(((I) + 1) & 7); GATE(4 * (I), 4 * (I) + 4); GATE_PIN(4 * (I), 4 * (I) + 4); } while (0)
    GSTEP(18, 1); GSTEP(19, 2); GSTEP(20, 3); GSTEP(21, 4); GSTEP(22, 5); GSTEP(23, 6); GSTEP(24, 7);
#pragma unroll 1
    for (int j = 25; j < 32 - TAILN; j++) QPLAIN(j);
    if (wg == 1) bar_sync(6, 256);
#pragma unroll 1
    for (int j = 32 - TAILN; j < 32; j++) QSTEP_A(j, (j & 3) * (Q_STAGE / 16), 1);
    if (wg == 0) asm volatile("bar.arrive 6, 256;" ::: "memory");
    mbar_wait(bar + B_UPD, 0);
    {
      const int sel = __float_as_int(lds32(sb + SM_UPD + 256)) - (wg * 64 + w * 16 + g);
      if (sel == 0 || sel == 8) {
#pragma unroll
        for (int j = 0; j < 16; j++) {
          const uint32_t u = __float_as_uint(lds32(sb + SM_UPD + j * 16 + t * 4));
          if (sel) gf[2 * j + 1] = u; else gf[2 * j] = u;
        }
      }
      __syncwarp();
      uint32_t xf[32];
#pragma unroll
      for (int j = 0; j < 8; j++)
        ldsm4(sb + (j >> 2 ? SM_X1 : SM_X0) + sw128 + ((((j & 3) * 2 + hi16) ^ x128) << 4), xf[4 * j], xf[4 * j + 1], xf[4 * j + 2], xf[4 * j + 3]);
      wg_wait<0>();
      reg_fence<64>(q);
      PROFC(8);
#pragma unroll
      for (int j = 0; j < 8; j++) {
        uint32_t o[4];
#pragma unroll
        for (int i = 0; i < 4; i++) o[i] = badd2(xf[4 * j + i], bmul2(pack2(q[8 * j + 2 * i], q[8 * j + 2 * i + 1]), gf[4 * j + i]));
        stsm4(sb + (j >> 2 ? SM_X1 : SM_X0) + sw128 + ((((j & 3) * 2 + hi16) ^ x128) << 4), o[0], o[1], o[2], o[3]);
      }
    }
    fence_async_smem();
    bar_sync(2 + wg, 128);
    if (w == 0 && elect_one()) {
      tma_store2d(&mOut, sb + SM_X0 + wg * 8192, hg * 128, mb * 128 + wg * 64);
      tma_store2d(&mOut, sb + SM_X1 + wg * 8192, hg * 128 + 64, mb * 128 + wg * 64);
      bulk_commit();
      bulk_wait_read0();
      if (wg == 1) { PROF(9); PROFT(33); PROF_DUMP; }
    }
  }
}

typedef CUresult (*EncodeFn)(CUtensorMap*, CUtensorMapDataType, cuuint32_t, void*, const cuuint64_t*, const cuuint64_t*, const cuuint32_t*,
                             const cuuint32_t*, CUtensorMapInterleave, CUtensorMapSwizzle, CUtensorMapL2promotion, CUtensorMapFloatOOBfill);

CUtensorMap make_map(EncodeFn enc, const void* ptr, int rank, const cuuint64_t* dims, const cuuint64_t* strides, const cuuint32_t* box, CUtensorMapSwizzle sw) {
  CUtensorMap m;
  const cuuint32_t es[5] = {1, 1, 1, 1, 1};
  enc(&m, CU_TENSOR_MAP_DATA_TYPE_BFLOAT16, rank, (void*)ptr, dims, strides, box, es, CU_TENSOR_MAP_INTERLEAVE_NONE, sw,
      CU_TENSOR_MAP_L2_PROMOTION_L2_128B, CU_TENSOR_MAP_FLOAT_OOB_FILL_NONE);
  return m;
}

}

extern "C" void kernel_launch(void* const* d_in, const int* in_sizes, int n_in, void* d_out, int out_size) {
  static EncodeFn enc = nullptr;
  static int by_sm = 0;
  if (!enc) {
    void* fn = nullptr;
    cudaDriverEntryPointQueryResult qr;
    cudaGetDriverEntryPoint("cuTensorMapEncodeTiled", &fn, cudaEnableDefault, &qr);
    enc = (EncodeFn)fn;
    cudaFuncSetAttribute(fused_kernel<false>, cudaFuncAttributeMaxDynamicSharedMemorySize, SM_TOTAL);
    cudaFuncSetAttribute(fused_kernel<true>, cudaFuncAttributeMaxDynamicSharedMemorySize, SM_TOTAL);
    int dev = 0, sms = 0;
    cudaGetDevice(&dev);
    cudaDeviceGetAttribute(&sms, cudaDevAttrMultiProcessorCount, dev);
    by_sm = BY_SM && sms == NCTA + NSPARE;
  }
  Params P;
  P.x = (const __nv_bfloat16*)d_in[0];
  P.wqkv = (const __nv_bfloat16*)d_in[1];
  const void* wphi = d_in[2];
  P.wo = (const __nv_bfloat16*)d_in[3];
  P.w_r = (const __nv_bfloat16*)d_in[5];
  P.w_gate = (const __nv_bfloat16*)d_in[6];
  P.w_up = (const __nv_bfloat16*)d_in[7];
  P.w_down = (const __nv_bfloat16*)d_in[8];

  const cuuint64_t dX[2] = {DM, SEQ}, sX[1] = {DM * 2};
  const cuuint32_t b128[2] = {64, 128}, b64[2] = {64, 64};
  const cuuint64_t dW[4] = {64, DM, 16, 3}, sW[3] = {3 * DM * 2, 128, DM * 2};
  const cuuint32_t bKV[4] = {64, 64, 2, 2}, bQ[4] = {64, 64, 2, 1};
  const cuuint64_t dO[3] = {64, DM, 16}, sO[2] = {DM * 2, 128};
  const cuuint32_t bO[3] = {64, 64, 2};
  const cuuint64_t dP[2] = {32, 1024}, sP[1] = {64};
  const cuuint32_t bP[2] = {32, 128};
  CUtensorMap mX = make_map(enc, P.x, 2, dX, sX, b128, CU_TENSOR_MAP_SWIZZLE_128B);
  CUtensorMap mWkv = make_map(enc, P.wqkv, 4, dW, sW, bKV, CU_TENSOR_MAP_SWIZZLE_128B);
  CUtensorMap mWq = make_map(enc, P.wqkv, 4, dW, sW, bQ, CU_TENSOR_MAP_SWIZZLE_128B);
  CUtensorMap mWo = make_map(enc, P.wo, 3, dO, sO, bO, CU_TENSOR_MAP_SWIZZLE_128B);
  CUtensorMap mPhi = make_map(enc, wphi, 2, dP, sP, bP, CU_TENSOR_MAP_SWIZZLE_64B);
  const cuuint64_t dWp[5] = {DM, 2, 4, 4, DM / 32}, sWp[4] = {DM * 2, 8 * DM * 2, 2 * DM * 2, 32 * DM * 2};
  const cuuint32_t bWp[5] = {64, 2, 4, 4, 2};
  CUtensorMap mWp = make_map(enc, P.wo, 5, dWp, sWp, bWp, CU_TENSOR_MAP_SWIZZLE_128B);
  CUtensorMap mOut = make_map(enc, d_out, 2, dX, sX, b64, CU_TENSOR_MAP_SWIZZLE_128B);
  const cuuint64_t dWc[2] = {3 * DM, DM}, sWc[1] = {3 * DM * 2}, dG[2] = {FF, DM}, sG[1] = {FF * 2}, dD[3] = {64, FF, 16};
  const cuuint32_t b32[2] = {32, 32}, bD[3] = {64, 32, 4};
  CUtensorMap mWc = make_map(enc, P.wqkv, 2, dWc, sWc, b32, CU_TENSOR_MAP_SWIZZLE_NONE);
  CUtensorMap mG = make_map(enc, P.w_gate, 2, dG, sG, b32, CU_TENSOR_MAP_SWIZZLE_NONE);
  CUtensorMap mU = make_map(enc, P.w_up, 2, dG, sG, b32, CU_TENSOR_MAP_SWIZZLE_NONE);
  CUtensorMap mD = make_map(enc, P.w_down, 3, dD, sO, bD, CU_TENSOR_MAP_SWIZZLE_128B);
  const cuuint64_t dXs[3] = {256, SEQ, 4}, sXs[2] = {DM * 2, 512};
  const cuuint32_t bXs[3] = {256, 16, 2};
  CUtensorMap mXs = make_map(enc, P.x, 3, dXs, sXs, bXs, CU_TENSOR_MAP_SWIZZLE_NONE);
  const cuuint64_t dG2[4] = {64, DM, FF / 64, 1}, sG2[3] = {FF * 2, 128, (cuuint64_t)FF * DM * 2};
  CUtensorMap mG2 = make_map(enc, P.w_gate, 4, dG2, sG2, bQ, CU_TENSOR_MAP_SWIZZLE_128B);
  CUtensorMap mU2 = make_map(enc, P.w_up, 4, dG2, sG2, bQ, CU_TENSOR_MAP_SWIZZLE_128B);
  (by_sm ? fused_kernel<true> : fused_kernel<false>)<<<NCTA + NSPARE, 384, SM_TOTAL, cudaStreamPerThread>>>(mX, mWkv, mWq, mWo, mPhi, mWp, mOut, mWc, mG, mU, mD, mXs,
                                                                                                           mG2, mU2, P);
}
```

```cpp
#include <cuda_runtime.h>
#include <cuda_bf16.h>
#include <cuda.h>
#include <stdint.h>

namespace {

constexpr int SEQ = 2048, DM = 1024, FF = 3584;
constexpr int NCTA = 128;
constexpr int NSPARE = 4;
constexpr int NFFN = FF / 32;
#define GN 6
#define G8 2
constexpr int GROWS = (3 * GN + G8) * 32;
#define TAILN 2
#define KTAIL 1
#define XS_EARLY 1
#define PF_FIRST 2
#define PF_W 5
#define PF_PRE 1
#define PFG 0
#define PFD 80
#define BY_SM 1
#define PTAB 0x73216540u
#define ROWSPLIT 1
#define WOT 1
#define PSPLIT 1
#define KSTEPS 4
#define NOVAL 0
#define KCH 1
#define REG_C 224
#define REG_H 56
#define TW 2
#define FENCE_KIND 2
#define SP_DELAY 2000
#define HOP2_HINT 1
#define DNX 1
#define XSTR 288
#define ORDER_ALL 1
#define AM_NS 100
constexpr bool FFN_OFF = false;

static_assert(2 * REG_C + REG_H <= 3 * 168, "the register pool of the CTA is 384 x 168");

__device__ uint32_t g_epoch[(NCTA + NSPARE) * 32];
__device__ unsigned long long g_stat[SEQ];
__device__ __align__(128) unsigned long long g_best[NCTA];
__device__ __align__(16) float g_y[2][8][DM];
__device__ __align__(128) uint32_t g_ycnt[64];
__device__ __align__(1024) uint32_t g_xcnt[32 * XSTR];
#define XC1(HG, R) (g_xcnt + ((HG) * 2 + (R)) * XSTR)
#define XC2(HG, R) (g_xcnt + (16 + (HG) * 2 + (R)) * XSTR)
__device__ __align__(128) uint4 g_res[2][32 * 256];
__device__ __align__(16) float g_cs[5 * DM];
__device__ __align__(128) float g_gp[2 * FF];
__device__ uint4 g_part[8 * 2 * 16 * 16 * 32];
__device__ __align__(16) float g_zpart[8 * 2 * 16 * 16 * 8];
__device__ __align__(128) float g_zres[32 * 64];
__device__ __align__(1024) uint4 g_ofr[16 * 16 * 1024];
#define PROF(i)
#define PROFT(i)
#define PROFC(i)
#define PROF_DUMP
#define PW0(J)
#define PW1(J)

constexpr uint32_t KV_STAGE = 49152, Q_STAGE = 32768;
constexpr uint32_t SM_V = 147456;
constexpr uint32_t SM_PHI = 163840;
constexpr uint32_t SM_XST = 147456;
constexpr uint32_t SM_FST = 172032;
constexpr uint32_t SM_PST0 = 196608, SM_PST1 = SM_PHI + 8192;
constexpr uint32_t SM_X0 = 131072, SM_X1 = SM_PHI + 16384;
constexpr uint32_t SM_WPHI = 204800;
constexpr uint32_t SM_ZT = 212992;
constexpr uint32_t SM_SDT = 217088;
constexpr uint32_t SM_CST = 219136;
constexpr uint32_t SM_HT = 222720;
constexpr uint32_t SM_STAT = 223232;
constexpr uint32_t SM_XSEL = 224256;
constexpr uint32_t SM_RED = 228352;
constexpr uint32_t SM_ROWS = SM_RED + 832;
constexpr uint32_t SM_GRED = SM_XSEL + 3072;
static_assert(GROWS <= 768, "xsel area");
constexpr uint32_t SM_UPD = 229632;
constexpr uint32_t SM_BAR = 230016;
constexpr uint32_t SM_PROF = 230464;
constexpr uint32_t SM_SINK = 231104;
constexpr uint32_t SM_TOTAL = 231616;
constexpr uint32_t SB = 1024;
constexpr uint32_t B_FULLKV = 0  , B_FST = 24  , B_XFULL = 88  , B_XST = 104  , B_WPHI = 120, B_CS = 128, B_CSQ = 136, B_UPD = 144,
                   B_H = 152, B_DN = 160, B_XS = 168, B_TILE = 176  , B_RES = 192  , B_PART = 208  ,
B_AIN = 224  ,
                   B_FULLQ = 288  ,
                   B_FFN = 320,
                   B_EMPTYKV = 328  , B_EMPTYQ = 352  , B_KVST = 384  , B_YD = 400, B_PHI = 408  , B_DND = 424, B_END = 432;

__device__ __forceinline__ uint32_t smem_u32(const void* p) { return (uint32_t)__cvta_generic_to_shared(p); }
__device__ __forceinline__ void mbar_init(uint32_t bar, uint32_t cnt) { asm volatile("mbarrier.init.shared::cta.b64 [%0], %1;" ::"r"(bar), "r"(cnt) : "memory"); }
__device__ __forceinline__ void mbar_expect_tx(uint32_t bar, uint32_t bytes) { asm volatile("mbarrier.arrive.expect_tx.shared::cta.b64 _, [%0], %1;" ::"r"(bar), "r"(bytes) : "memory"); }
__device__ __forceinline__ void mbar_arrive2(uint32_t bar) { asm volatile("mbarrier.arrive.shared::cta.b64 _, [%0], 2;" ::"r"(bar) : "memory"); }
__device__ __forceinline__ void mbar_arrive(uint32_t bar) { asm volatile("mbarrier.arrive.shared::cta.b64 _, [%0];" ::"r"(bar) : "memory"); }
__device__ __forceinline__ void mbar_wait(uint32_t bar, uint32_t parity) {
  asm volatile("{\n.reg .pred p;\nLW:\nmbarrier.try_wait.parity.shared::cta.b64 p, [%0], %1;\n@!p bra LW;\n}" ::"r"(bar), "r"(parity) : "memory");
}
__device__ __forceinline__ bool mbar_test(uint32_t bar, uint32_t parity) {
  uint32_t ok;
  asm volatile("{\n.reg .pred p;\nmbarrier.test_wait.parity.shared::cta.b64 p, [%1], %2;\nselp.u32 %0, 1, 0, p;\n}" : "=r"(ok) : "r"(bar), "r"(parity) : "memory");
  return ok;
}
__device__ __forceinline__ int lane_id() { int l; asm volatile("mov.u32 %0, %%laneid;" : "=r"(l)); return l; }
template <int C> __device__ __forceinline__ void sched_fence_(int zero) {
  asm volatile("{\n.reg .pred p;\nsetp.eq.s32 p, %0, %1;\n@p trap;\n}" ::"r"(zero), "n"(C) : "memory");
}
#define SCHED_FENCE() sched_fence_<1000 + __COUNTER__>(zero)
#define SCHED_PIN(V) sched_fence_<1000 + __COUNTER__>(zero & __float_as_int(V))
__device__ __forceinline__ bool elect_one() {
  uint32_t p; asm volatile("{ .reg .pred P; elect.sync _|P, 0xffffffff; selp.u32 %0, 1, 0, P; }" : "=r"(p)); return p;
}
__device__ __forceinline__ void tma2d(uint32_t dst, const CUtensorMap* m, int x, int y, uint32_t bar) {
  asm volatile("cp.async.bulk.tensor.2d.shared::cluster.global.mbarrier::complete_tx::bytes [%0], [%1, {%3, %4}], [%2];" ::"r"(dst), "l"(m), "r"(bar), "r"(x), "r"(y) : "memory");
}
__device__ __forceinline__ void tma3d(uint32_t dst, const CUtensorMap* m, int x, int y, int z, uint32_t bar) {
  asm volatile("cp.async.bulk.tensor.3d.shared::cluster.global.mbarrier::complete_tx::bytes [%0], [%1, {%3, %4, %5}], [%2];" ::"r"(dst), "l"(m), "r"(bar), "r"(x), "r"(y), "r"(z) : "memory");
}
__device__ __forceinline__ void tma4d(uint32_t dst, const CUtensorMap* m, int x, int y, int z, int w, uint32_t bar) {
  asm volatile("cp.async.bulk.tensor.4d.shared::cluster.global.mbarrier::complete_tx::bytes [%0], [%1, {%3, %4, %5, %6}], [%2];" ::"r"(dst), "l"(m), "r"(bar), "r"(x), "r"(y), "r"(z), "r"(w) : "memory");
}
__device__ __forceinline__ void tma5d(uint32_t dst, const CUtensorMap* m, int x, int v, uint32_t bar) {
  asm volatile("cp.async.bulk.tensor.5d.shared::cluster.global.mbarrier::complete_tx::bytes [%0], [%1, {%3, %5, %5, %5, %4}], [%2];" ::"r"(dst), "l"(m), "r"(bar), "r"(x), "r"(v), "r"(0) : "memory");
}
__device__ __forceinline__ void tma_store2d(const CUtensorMap* m, uint32_t src, int x, int y) {
  asm volatile("cp.async.bulk.tensor.2d.global.shared::cta.bulk_group [%0, {%2, %3}], [%1];" ::"l"(m), "r"(src), "r"(x), "r"(y) : "memory");
}
__device__ __forceinline__ void bulk_load(uint32_t dst, const void* src, uint32_t bytes, uint32_t bar) {
  asm volatile("cp.async.bulk.shared::cluster.global.mbarrier::complete_tx::bytes [%0], [%1], %2, [%3];" ::"r"(dst), "l"(src), "r"(bytes), "r"(bar) : "memory");
}
__device__ __forceinline__ void bulk_commit() { asm volatile("cp.async.bulk.commit_group;" ::: "memory"); }
__device__ __forceinline__ void bulk_wait0() { asm volatile("cp.async.bulk.wait_group 0;" ::: "memory"); }
__device__ __forceinline__ void bulk_wait_read0() { asm volatile("cp.async.bulk.wait_group.read 0;" ::: "memory"); }
__device__ __forceinline__ void prefetch_l2(const void* p) { asm volatile("prefetch.global.L2 [%0];" ::"l"(p) : "memory"); }
__device__ __forceinline__ void touch_l2(const void* p, int lane) { asm volatile("cp.async.cg.shared.global.L2::128B [%0], [%1], 16;" ::"r"(SB + SM_SINK + lane * 16), "l"(p) : "memory"); }
__device__ __forceinline__ void cp_async16(uint32_t dst, const void* src) { asm volatile("cp.async.cg.shared.global [%0], [%1], 16;" ::"r"(dst), "l"(src) : "memory"); }
__device__ __forceinline__ void prefetch_map(const CUtensorMap* m) { asm volatile("prefetch.tensormap [%0];" ::"l"(m) : "memory"); }
__device__ __forceinline__ void fence_async_smem() { asm volatile("fence.proxy.async.shared::cta;" ::: "memory"); }
__device__ __forceinline__ void fence_async_global() { asm volatile("fence.proxy.async.global;" ::: "memory"); }
__device__ __forceinline__ void bar_sync(int id, int n) { asm volatile("bar.sync %0, %1;" ::"r"(id), "r"(n) : "memory"); }
__device__ __forceinline__ void wg_fence() { asm volatile("wgmma.fence.sync.aligned;" ::: "memory"); }
__device__ __forceinline__ void wg_commit() { asm volatile("wgmma.commit_group.sync.aligned;" ::: "memory"); }
template <int N> __device__ __forceinline__ void wg_wait() { asm volatile("wgmma.wait_group.sync.aligned %0;" ::"n"(N) : "memory"); }
template <int N> __device__ __forceinline__ void reg_fence(uint32_t* r) {
#pragma unroll
  for (int i = 0; i < N; i++) asm volatile("" : "+r"(r[i])::"memory");
}
template <int N> __device__ __forceinline__ void reg_fence(float* r) {
#pragma unroll
  for (int i = 0; i < N; i++) asm volatile("" : "+f"(r[i])::"memory");
}
__device__ __forceinline__ uint64_t mkdesc(uint32_t addr, uint32_t lbo, uint32_t sbo, uint32_t swz, uint32_t dyn = 0) {
  const uint32_t lo = ((addr >> 4) | ((lbo >> 4) << 16)) + dyn;
  const uint32_t hi = (sbo >> 4) | (swz << 30);
  uint64_t d;
  asm("mov.b64 %0, {%1, %2};" : "=l"(d) : "r"(lo), "r"(hi));
  return d;
}
__device__ __forceinline__ void stsm4(uint32_t addr, uint32_t a, uint32_t b, uint32_t c, uint32_t d) {
  asm volatile("stmatrix.sync.aligned.m8n8.x4.shared.b16 [%0], {%1, %2, %3, %4};" ::"r"(addr), "r"(a), "r"(b), "r"(c), "r"(d) : "memory");
}
__device__ __forceinline__ void ldsm4(uint32_t addr, uint32_t& a, uint32_t& b, uint32_t& c, uint32_t& d) {
  asm volatile("ldmatrix.sync.aligned.m8n8.x4.shared.b16 {%0, %1, %2, %3}, [%4];" : "=r"(a), "=r"(b), "=r"(c), "=r"(d) : "r"(addr) : "memory");
}
__device__ __forceinline__ uint32_t pack2(float lo, float hi) { uint32_t r; asm("cvt.rn.bf16x2.f32 %0, %1, %2;" : "=r"(r) : "f"(hi), "f"(lo)); return r; }
__device__ __forceinline__ uint32_t bsub2(uint32_t a, uint32_t b) { uint32_t r; asm("sub.rn.bf16x2 %0, %1, %2;" : "=r"(r) : "r"(a), "r"(b)); return r; }
__device__ __forceinline__ uint32_t badd2(uint32_t a, uint32_t b) { uint32_t r; asm("add.rn.bf16x2 %0, %1, %2;" : "=r"(r) : "r"(a), "r"(b)); return r; }
__device__ __forceinline__ uint32_t bmul2(uint32_t a, uint32_t b) { uint32_t r; asm("mul.rn.bf16x2 %0, %1, %2;" : "=r"(r) : "r"(a), "r"(b)); return r; }
__device__ __forceinline__ float bf_lo(uint32_t v) { return __uint_as_float(v << 16); }
__device__ __forceinline__ float bf_hi(uint32_t v) { return __uint_as_float(v & 0xffff0000u); }
__device__ __forceinline__ float bf_round(float v) { return bf_lo(pack2(v, 0.f)); }
__device__ __forceinline__ float ex2(float v) { float r; asm("ex2.approx.ftz.f32 %0, %1;" : "=f"(r) : "f"(v)); return r; }
__device__ __forceinline__ float rcp(float v) { float r; asm("rcp.approx.ftz.f32 %0, %1;" : "=f"(r) : "f"(v)); return r; }
__device__ __forceinline__ float sqrt_approx(float v) { float r; asm("sqrt.approx.f32 %0, %1;" : "=f"(r) : "f"(v)); return r; }
__device__ __forceinline__ float4 lds128(uint32_t a) { float4 v; asm volatile("ld.shared.v4.f32 {%0, %1, %2, %3}, [%4];" : "=f"(v.x), "=f"(v.y), "=f"(v.z), "=f"(v.w) : "r"(a) : "memory"); return v; }
__device__ __forceinline__ uint4 lds128u(uint32_t a) { uint4 v; asm volatile("ld.shared.v4.u32 {%0, %1, %2, %3}, [%4];" : "=r"(v.x), "=r"(v.y), "=r"(v.z), "=r"(v.w) : "r"(a) : "memory"); return v; }
__device__ __forceinline__ float2 lds64(uint32_t a) { float2 v; asm volatile("ld.shared.v2.f32 {%0, %1}, [%2];" : "=f"(v.x), "=f"(v.y) : "r"(a) : "memory"); return v; }
__device__ __forceinline__ float lds32(uint32_t a) { float v; asm volatile("ld.shared.f32 %0, [%1];" : "=f"(v) : "r"(a) : "memory"); return v; }
__device__ __forceinline__ void sts32(uint32_t a, float v) { asm volatile("st.shared.f32 [%0], %1;" ::"r"(a), "f"(v) : "memory"); }
__device__ __forceinline__ void sts64(uint32_t a, float x, float y) { asm volatile("st.shared.v2.f32 [%0], {%1, %2};" ::"r"(a), "f"(x), "f"(y) : "memory"); }
__device__ __forceinline__ void sts128(uint32_t a, float x, float y, float z, float w) { asm volatile("st.shared.v4.f32 [%0], {%1, %2, %3, %4};" ::"r"(a), "f"(x), "f"(y), "f"(z), "f"(w) : "memory"); }
__device__ __forceinline__ void sts64u(uint32_t a, uint32_t x, uint32_t y) { asm volatile("st.shared.v2.u32 [%0], {%1, %2};" ::"r"(a), "r"(x), "r"(y) : "memory"); }
__device__ __forceinline__ void sts128u(uint32_t a, uint32_t x, uint32_t y, uint32_t z, uint32_t w) { asm volatile("st.shared.v4.u32 [%0], {%1, %2, %3, %4};" ::"r"(a), "r"(x), "r"(y), "r"(z), "r"(w) : "memory"); }
__device__ __forceinline__ uint4 ldg_nc(const void* p) { uint4 v; asm volatile("ld.global.nc.L1::no_allocate.v4.u32 {%0, %1, %2, %3}, [%4];" : "=r"(v.x), "=r"(v.y), "=r"(v.z), "=r"(v.w) : "l"(p)); return v; }
__device__ __forceinline__ float4 ldg_cg4(const float* p) { float4 v; asm volatile("ld.global.cg.v4.f32 {%0, %1, %2, %3}, [%4];" : "=f"(v.x), "=f"(v.y), "=f"(v.z), "=f"(v.w) : "l"(p) : "memory"); return v; }
__device__ __forceinline__ uint32_t ld_acq(const uint32_t* p) { uint32_t v; asm volatile("ld.acquire.gpu.global.u32 %0, [%1];" : "=r"(v) : "l"(p) : "memory"); return v; }
__device__ __forceinline__ uint32_t ld_acq_cta(uint32_t a) { uint32_t v; asm volatile("ld.acquire.cta.shared.u32 %0, [%1];" : "=r"(v) : "r"(a) : "memory"); return v; }
__device__ __forceinline__ void st_rel_cta(uint32_t a, uint32_t v) { asm volatile("st.release.cta.shared.u32 [%0], %1;" ::"r"(a), "r"(v) : "memory"); }
__device__ __forceinline__ unsigned long long ld_rlx64(const unsigned long long* p) { unsigned long long v; asm volatile("ld.relaxed.gpu.global.u64 %0, [%1];" : "=l"(v) : "l"(p) : "memory"); return v; }
__device__ __forceinline__ void st_rlx64(unsigned long long* p, unsigned long long v) { asm volatile("st.relaxed.gpu.global.u64 [%0], %1;" ::"l"(p), "l"(v) : "memory"); }
__device__ __forceinline__ uint4 ld_rlx128(const void* p) {
  uint4 v;
  asm volatile("{ .reg .b128 t; .reg .b64 a, b; ld.relaxed.gpu.global.b128 t, [%4]; mov.b128 {a, b}, t; mov.b64 {%0, %1}, a; mov.b64 {%2, %3}, b; }"
               : "=r"(v.x), "=r"(v.y), "=r"(v.z), "=r"(v.w) : "l"(p) : "memory");
  return v;
}
__device__ __forceinline__ void st_rlx128(void* p, uint32_t x, uint32_t y, uint32_t z, uint32_t w) {
  asm volatile("{ .reg .b128 t; .reg .b64 a, b; mov.b64 a, {%1, %2}; mov.b64 b, {%3, %4}; mov.b128 t, {a, b}; st.relaxed.gpu.global.b128 [%0], t; }"
               ::"l"(p), "r"(x), "r"(y), "r"(z), "r"(w) : "memory");
}
__device__ __forceinline__ void stg128(void* p, uint32_t x, uint32_t y, uint32_t z, uint32_t w) { asm volatile("st.global.v4.u32 [%0], {%1, %2, %3, %4};" ::"l"(p), "r"(x), "r"(y), "r"(z), "r"(w) : "memory"); }
__device__ __forceinline__ void st_rlx(void* p, uint32_t v) { asm volatile("st.relaxed.gpu.global.u32 [%0], %1;" ::"l"(p), "r"(v) : "memory"); }
__device__ __forceinline__ uint32_t lop_select(uint32_t a, uint32_t b, uint32_t m) { uint32_t r; asm("lop3.b32 %0, %1, %2, %3, 0xd8;" : "=r"(r) : "r"(a), "r"(b), "r"(m)); return r; }
__device__ __forceinline__ float unmark(uint32_t v) { return __uint_as_float(v & ~1u); }
__device__ __forceinline__ uint32_t mark(uint32_t v, uint32_t par) { return (v & ~1u) | par; }
__device__ __forceinline__ float tanh_approx(float v) { float r; asm("tanh.approx.f32 %0, %1;" : "=f"(r) : "f"(v)); return r; }
__device__ __forceinline__ void flag_rel(uint32_t* p, uint32_t v) { asm volatile("red.release.gpu.global.max.u32 [%0], %1;" ::"l"(p), "r"(v) : "memory"); }
__device__ __forceinline__ void red1(float* p, float a) { asm volatile("red.global.add.f32 [%0], %1;" ::"l"(p), "f"(a) : "memory"); }
__device__ __forceinline__ void red_inc(uint32_t* p) { asm volatile("red.relaxed.gpu.global.add.u32 [%0], 1;" ::"l"(p) : "memory"); }
__device__ __forceinline__ void red_rel(uint32_t* p) { asm volatile("red.release.gpu.global.add.u32 [%0], 1;" ::"l"(p) : "memory"); }
__device__ __forceinline__ void red4(float* p, float a, float b, float c, float d) { asm volatile("red.global.add.v4.f32 [%0], {%1, %2, %3, %4};" ::"l"(p), "f"(a), "f"(b), "f"(c), "f"(d) : "memory"); }
constexpr int SPIN_MAX = 100000;
__device__ __forceinline__ uint32_t ld_rlx(const uint32_t* p) { uint32_t v; asm volatile("ld.relaxed.gpu.global.u32 %0, [%1];" : "=r"(v) : "l"(p) : "memory"); return v; }
template <int NS = 0> __device__ __forceinline__ void wait_hint(const uint32_t* p, uint32_t target) {
#pragma unroll 1
  for (int i = 0; i < SPIN_MAX; i++) { if ((int)(ld_rlx(p) - target) >= 0) break; if (NS) __nanosleep(NS); }
}
template <int NS> __device__ __forceinline__ void wait_cnt(const uint32_t* p, uint32_t target) {
#pragma unroll 1
  for (int i = 0; i < SPIN_MAX; i++) { if ((int)(ld_rlx(p) - target) >= 0) break; if (NS) __nanosleep(NS); }
  (void)ld_acq(p);
}
template <int NS> __device__ __forceinline__ unsigned long long wait_tag(const unsigned long long* p, uint32_t tag) {
  unsigned long long v = 0;
#pragma unroll 1
  for (int i = 0; i < SPIN_MAX; i++) { v = ld_rlx64(p); if ((uint32_t)(v >> 32) == tag) break; if (NS) __nanosleep(NS); }
  return v;
}
__device__ __forceinline__ float silu_f(float v) { return v * rcp(1.f + ex2(-1.4426950408889634f * v)); }

__device__ __forceinline__ void wgmma_n8_ss_ta1_tb0(float* d, uint64_t da, uint64_t db, bool accumulate) {
  if (accumulate) {
    asm volatile("{\n.reg .pred p;\nsetp.ne.b32 p, 1, 0;\n"
      "wgmma.mma_async.sync.aligned.m64n8k16.f32.bf16.bf16 "
      "{%0, %1, %2, %3}, "
      "%4, %5, p, 1, 1, 1, 0;\n}\n"
      : "+f"(d[0]), "+f"(d[1]), "+f"(d[2]), "+f"(d[3])
      : "l"(da), "l"(db));
  } else {
    asm volatile("{\n.reg .pred p;\nsetp.ne.b32 p, 0, 0;\n"
      "wgmma.mma_async.sync.aligned.m64n8k16.f32.bf16.bf16 "
      "{%0, %1, %2, %3}, "
      "%4, %5, p, 1, 1, 1, 0;\n}\n"
      : "=f"(d[0]), "=f"(d[1]), "=f"(d[2]), "=f"(d[3])
      : "l"(da), "l"(db));
  }
}
__device__ __forceinline__ void wgmma_n8_ss_ta1_tb1(float* d, uint64_t da, uint64_t db, bool accumulate) {
  if (accumulate) {
    asm volatile("{\n.reg .pred p;\nsetp.ne.b32 p, 1, 0;\n"
      "wgmma.mma_async.sync.aligned.m64n8k16.f32.bf16.bf16 "
      "{%0, %1, %2, %3}, "
      "%4, %5, p, 1, 1, 1, 1;\n}\n"
      : "+f"(d[0]), "+f"(d[1]), "+f"(d[2]), "+f"(d[3])
      : "l"(da), "l"(db));
  } else {
    asm volatile("{\n.reg .pred p;\nsetp.ne.b32 p, 0, 0;\n"
      "wgmma.mma_async.sync.aligned.m64n8k16.f32.bf16.bf16 "
      "{%0, %1, %2, %3}, "
      "%4, %5, p, 1, 1, 1, 1;\n}\n"
      : "=f"(d[0]), "=f"(d[1]), "=f"(d[2]), "=f"(d[3])
      : "l"(da), "l"(db));
  }
}
__device__ __forceinline__ void wgmma_n32_rs_ta0_tb1(float* d, uint32_t a0, uint32_t a1, uint32_t a2, uint32_t a3, uint64_t db, bool accumulate) {
  if (accumulate) {
    asm volatile("{\n.reg .pred p;\nsetp.ne.b32 p, 1, 0;\n"
      "wgmma.mma_async.sync.aligned.m64n32k16.f32.bf16.bf16 "
      "{%0, %1, %2, %3, %4, %5, %6, %7, %8, %9, %10, %11, %12, %13, %14, %15}, "
      "{%16, %17, %18, %19}, %20, p, 1, 1, 1;\n}\n"
      : "+f"(d[0]), "+f"(d[1]), "+f"(d[2]), "+f"(d[3]), "+f"(d[4]), "+f"(d[5]), "+f"(d[6]), "+f"(d[7]), "+f"(d[8]), "+f"(d[9]), "+f"(d[10]), "+f"(d[11]), "+f"(d[12]), "+f"(d[13]), "+f"(d[14]), "+f"(d[15])
      : "r"(a0), "r"(a1), "r"(a2), "r"(a3), "l"(db));
  } else {
    asm volatile("{\n.reg .pred p;\nsetp.ne.b32 p, 0, 0;\n"
      "wgmma.mma_async.sync.aligned.m64n32k16.f32.bf16.bf16 "
      "{%0, %1, %2, %3, %4, %5, %6, %7, %8, %9, %10, %11, %12, %13, %14, %15}, "
      "{%16, %17, %18, %19}, %20, p, 1, 1, 1;\n}\n"
      : "=f"(d[0]), "=f"(d[1]), "=f"(d[2]), "=f"(d[3]), "=f"(d[4]), "=f"(d[5]), "=f"(d[6]), "=f"(d[7]), "=f"(d[8]), "=f"(d[9]), "=f"(d[10]), "=f"(d[11]), "=f"(d[12]), "=f"(d[13]), "=f"(d[14]), "=f"(d[15])
      : "r"(a0), "r"(a1), "r"(a2), "r"(a3), "l"(db));
  }
}
__device__ __forceinline__ void wgmma_n40_rs_ta0_tb1(float* d, uint32_t a0, uint32_t a1, uint32_t a2, uint32_t a3, uint64_t db, bool accumulate) {
  if (accumulate) {
    asm volatile("{\n.reg .pred p;\nsetp.ne.b32 p, 1, 0;\n"
      "wgmma.mma_async.sync.aligned.m64n40k16.f32.bf16.bf16 "
      "{%0, %1, %2, %3, %4, %5, %6, %7, %8, %9, %10, %11, %12, %13, %14, %15, %16, %17, %18, %19}, "
      "{%20, %21, %22, %23}, %24, p, 1, 1, 1;\n}\n"
      : "+f"(d[0]), "+f"(d[1]), "+f"(d[2]), "+f"(d[3]), "+f"(d[4]), "+f"(d[5]), "+f"(d[6]), "+f"(d[7]), "+f"(d[8]), "+f"(d[9]), "+f"(d[10]), "+f"(d[11]), "+f"(d[12]), "+f"(d[13]), "+f"(d[14]), "+f"(d[15]), "+f"(d[16]), "+f"(d[17]), "+f"(d[18]), "+f"(d[19])
      : "r"(a0), "r"(a1), "r"(a2), "r"(a3), "l"(db));
  } else {
    asm volatile("{\n.reg .pred p;\nsetp.ne.b32 p, 0, 0;\n"
      "wgmma.mma_async.sync.aligned.m64n40k16.f32.bf16.bf16 "
      "{%0, %1, %2, %3, %4, %5, %6, %7, %8, %9, %10, %11, %12, %13, %14, %15, %16, %17, %18, %19}, "
      "{%20, %21, %22, %23}, %24, p, 1, 1, 1;\n}\n"
      : "=f"(d[0]), "=f"(d[1]), "=f"(d[2]), "=f"(d[3]), "=f"(d[4]), "=f"(d[5]), "=f"(d[6]), "=f"(d[7]), "=f"(d[8]), "=f"(d[9]), "=f"(d[10]), "=f"(d[11]), "=f"(d[12]), "=f"(d[13]), "=f"(d[14]), "=f"(d[15]), "=f"(d[16]), "=f"(d[17]), "=f"(d[18]), "=f"(d[19])
      : "r"(a0), "r"(a1), "r"(a2), "r"(a3), "l"(db));
  }
}
__device__ __forceinline__ void wgmma_n40_ss_ta1_tb1(float* d, uint64_t da, uint64_t db, bool accumulate) {
  if (accumulate) {
    asm volatile("{\n.reg .pred p;\nsetp.ne.b32 p, 1, 0;\n"
      "wgmma.mma_async.sync.aligned.m64n40k16.f32.bf16.bf16 "
      "{%0, %1, %2, %3, %4, %5, %6, %7, %8, %9, %10, %11, %12, %13, %14, %15, %16, %17, %18, %19}, "
      "%20, %21, p, 1, 1, 1, 1;\n}\n"
      : "+f"(d[0]), "+f"(d[1]), "+f"(d[2]), "+f"(d[3]), "+f"(d[4]), "+f"(d[5]), "+f"(d[6]), "+f"(d[7]), "+f"(d[8]), "+f"(d[9]), "+f"(d[10]), "+f"(d[11]), "+f"(d[12]), "+f"(d[13]), "+f"(d[14]), "+f"(d[15]), "+f"(d[16]), "+f"(d[17]), "+f"(d[18]), "+f"(d[19])
      : "l"(da), "l"(db));
  } else {
    asm volatile("{\n.reg .pred p;\nsetp.ne.b32 p, 0, 0;\n"
      "wgmma.mma_async.sync.aligned.m64n40k16.f32.bf16.bf16 "
      "{%0, %1, %2, %3, %4, %5, %6, %7, %8, %9, %10, %11, %12, %13, %14, %15, %16, %17, %18, %19}, "
      "%20, %21, p, 1, 1, 1, 1;\n}\n"
      : "=f"(d[0]), "=f"(d[1]), "=f"(d[2]), "=f"(d[3]), "=f"(d[4]), "=f"(d[5]), "=f"(d[6]), "=f"(d[7]), "=f"(d[8]), "=f"(d[9]), "=f"(d[10]), "=f"(d[11]), "=f"(d[12]), "=f"(d[13]), "=f"(d[14]), "=f"(d[15]), "=f"(d[16]), "=f"(d[17]), "=f"(d[18]), "=f"(d[19])
      : "l"(da), "l"(db));
  }
}
__device__ __forceinline__ void wgmma_n128_rs_ta0_tb1(float* d, uint32_t a0, uint32_t a1, uint32_t a2, uint32_t a3, uint64_t db, bool accumulate) {
  if (accumulate) {
    asm volatile("{\n.reg .pred p;\nsetp.ne.b32 p, 1, 0;\n"
      "wgmma.mma_async.sync.aligned.m64n128k16.f32.bf16.bf16 "
      "{%0, %1, %2, %3, %4, %5, %6, %7, %8, %9, %10, %11, %12, %13, %14, %15, %16, %17, %18, %19, %20, %21, %22, %23, %24, %25, %26, %27, %28, %29, %30, %31, %32, %33, %34, %35, %36, %37, %38, %39, %40, %41, %42, %43, %44, %45, %46, %47, %48, %49, %50, %51, %52, %53, %54, %55, %56, %57, %58, %59, %60, %61, %62, %63}, "
      "{%64, %65, %66, %67}, %68, p, 1, 1, 1;\n}\n"
      : "+f"(d[0]), "+f"(d[1]), "+f"(d[2]), "+f"(d[3]), "+f"(d[4]), "+f"(d[5]), "+f"(d[6]), "+f"(d[7]), "+f"(d[8]), "+f"(d[9]), "+f"(d[10]), "+f"(d[11]), "+f"(d[12]), "+f"(d[13]), "+f"(d[14]), "+f"(d[15]), "+f"(d[16]), "+f"(d[17]), "+f"(d[18]), "+f"(d[19]), "+f"(d[20]), "+f"(d[21]), "+f"(d[22]), "+f"(d[23]), "+f"(d[24]), "+f"(d[25]), "+f"(d[26]), "+f"(d[27]), "+f"(d[28]), "+f"(d[29]), "+f"(d[30]), "+f"(d[31]), "+f"(d[32]), "+f"(d[33]), "+f"(d[34]), "+f"(d[35]), "+f"(d[36]), "+f"(d[37]), "+f"(d[38]), "+f"(d[39]), "+f"(d[40]), "+f"(d[41]), "+f"(d[42]), "+f"(d[43]), "+f"(d[44]), "+f"(d[45]), "+f"(d[46]), "+f"(d[47]), "+f"(d[48]), "+f"(d[49]), "+f"(d[50]), "+f"(d[51]), "+f"(d[52]), "+f"(d[53]), "+f"(d[54]), "+f"(d[55]), "+f"(d[56]), "+f"(d[57]), "+f"(d[58]), "+f"(d[59]), "+f"(d[60]), "+f"(d[61]), "+f"(d[62]), "+f"(d[63])
      : "r"(a0), "r"(a1), "r"(a2), "r"(a3), "l"(db));
  } else {
    asm volatile("{\n.reg .pred p;\nsetp.ne.b32 p, 0, 0;\n"
      "wgmma.mma_async.sync.aligned.m64n128k16.f32.bf16.bf16 "
      "{%0, %1, %2, %3, %4, %5, %6, %7, %8, %9, %10, %11, %12, %13, %14, %15, %16, %17, %18, %19, %20, %21, %22, %23, %24, %25, %26, %27, %28, %29, %30, %31, %32, %33, %34, %35, %36, %37, %38, %39, %40, %41, %42, %43, %44, %45, %46, %47, %48, %49, %50, %51, %52, %53, %54, %55, %56, %57, %58, %59, %60, %61, %62, %63}, "
      "{%64, %65, %66, %67}, %68, p, 1, 1, 1;\n}\n"
      : "=f"(d[0]), "=f"(d[1]), "=f"(d[2]), "=f"(d[3]), "=f"(d[4]), "=f"(d[5]), "=f"(d[6]), "=f"(d[7]), "=f"(d[8]), "=f"(d[9]), "=f"(d[10]), "=f"(d[11]), "=f"(d[12]), "=f"(d[13]), "=f"(d[14]), "=f"(d[15]), "=f"(d[16]), "=f"(d[17]), "=f"(d[18]), "=f"(d[19]), "=f"(d[20]), "=f"(d[21]), "=f"(d[22]), "=f"(d[23]), "=f"(d[24]), "=f"(d[25]), "=f"(d[26]), "=f"(d[27]), "=f"(d[28]), "=f"(d[29]), "=f"(d[30]), "=f"(d[31]), "=f"(d[32]), "=f"(d[33]), "=f"(d[34]), "=f"(d[35]), "=f"(d[36]), "=f"(d[37]), "=f"(d[38]), "=f"(d[39]), "=f"(d[40]), "=f"(d[41]), "=f"(d[42]), "=f"(d[43]), "=f"(d[44]), "=f"(d[45]), "=f"(d[46]), "=f"(d[47]), "=f"(d[48]), "=f"(d[49]), "=f"(d[50]), "=f"(d[51]), "=f"(d[52]), "=f"(d[53]), "=f"(d[54]), "=f"(d[55]), "=f"(d[56]), "=f"(d[57]), "=f"(d[58]), "=f"(d[59]), "=f"(d[60]), "=f"(d[61]), "=f"(d[62]), "=f"(d[63])
      : "r"(a0), "r"(a1), "r"(a2), "r"(a3), "l"(db));
  }
}
__device__ __forceinline__ void wgmma_n128_ss_ta0_tb1(float* d, uint64_t da, uint64_t db, bool accumulate) {
  if (accumulate) {
    asm volatile("{\n.reg .pred p;\nsetp.ne.b32 p, 1, 0;\n"
      "wgmma.mma_async.sync.aligned.m64n128k16.f32.bf16.bf16 "
      "{%0, %1, %2, %3, %4, %5, %6, %7, %8, %9, %10, %11, %12, %13, %14, %15, %16, %17, %18, %19, %20, %21, %22, %23, %24, %25, %26, %27, %28, %29, %30, %31, %32, %33, %34, %35, %36, %37, %38, %39, %40, %41, %42, %43, %44, %45, %46, %47, %48, %49, %50, %51, %52, %53, %54, %55, %56, %57, %58, %59, %60, %61, %62, %63}, "
      "%64, %65, p, 1, 1, 0, 1;\n}\n"
      : "+f"(d[0]), "+f"(d[1]), "+f"(d[2]), "+f"(d[3]), "+f"(d[4]), "+f"(d[5]), "+f"(d[6]), "+f"(d[7]), "+f"(d[8]), "+f"(d[9]), "+f"(d[10]), "+f"(d[11]), "+f"(d[12]), "+f"(d[13]), "+f"(d[14]), "+f"(d[15]), "+f"(d[16]), "+f"(d[17]), "+f"(d[18]), "+f"(d[19]), "+f"(d[20]), "+f"(d[21]), "+f"(d[22]), "+f"(d[23]), "+f"(d[24]), "+f"(d[25]), "+f"(d[26]), "+f"(d[27]), "+f"(d[28]), "+f"(d[29]), "+f"(d[30]), "+f"(d[31]), "+f"(d[32]), "+f"(d[33]), "+f"(d[34]), "+f"(d[35]), "+f"(d[36]), "+f"(d[37]), "+f"(d[38]), "+f"(d[39]), "+f"(d[40]), "+f"(d[41]), "+f"(d[42]), "+f"(d[43]), "+f"(d[44]), "+f"(d[45]), "+f"(d[46]), "+f"(d[47]), "+f"(d[48]), "+f"(d[49]), "+f"(d[50]), "+f"(d[51]), "+f"(d[52]), "+f"(d[53]), "+f"(d[54]), "+f"(d[55]), "+f"(d[56]), "+f"(d[57]), "+f"(d[58]), "+f"(d[59]), "+f"(d[60]), "+f"(d[61]), "+f"(d[62]), "+f"(d[63])
      : "l"(da), "l"(db));
  } else {
    asm volatile("{\n.reg .pred p;\nsetp.ne.b32 p, 0, 0;\n"
      "wgmma.mma_async.sync.aligned.m64n128k16.f32.bf16.bf16 "
      "{%0, %1, %2, %3, %4, %5, %6, %7, %8, %9, %10, %11, %12, %13, %14, %15, %16, %17, %18, %19, %20, %21, %22, %23, %24, %25, %26, %27, %28, %29, %30, %31, %32, %33, %34, %35, %36, %37, %38, %39, %40, %41, %42, %43, %44, %45, %46, %47, %48, %49, %50, %51, %52, %53, %54, %55, %56, %57, %58, %59, %60, %61, %62, %63}, "
      "%64, %65, p, 1, 1, 0, 1;\n}\n"
      : "=f"(d[0]), "=f"(d[1]), "=f"(d[2]), "=f"(d[3]), "=f"(d[4]), "=f"(d[5]), "=f"(d[6]), "=f"(d[7]), "=f"(d[8]), "=f"(d[9]), "=f"(d[10]), "=f"(d[11]), "=f"(d[12]), "=f"(d[13]), "=f"(d[14]), "=f"(d[15]), "=f"(d[16]), "=f"(d[17]), "=f"(d[18]), "=f"(d[19]), "=f"(d[20]), "=f"(d[21]), "=f"(d[22]), "=f"(d[23]), "=f"(d[24]), "=f"(d[25]), "=f"(d[26]), "=f"(d[27]), "=f"(d[28]), "=f"(d[29]), "=f"(d[30]), "=f"(d[31]), "=f"(d[32]), "=f"(d[33]), "=f"(d[34]), "=f"(d[35]), "=f"(d[36]), "=f"(d[37]), "=f"(d[38]), "=f"(d[39]), "=f"(d[40]), "=f"(d[41]), "=f"(d[42]), "=f"(d[43]), "=f"(d[44]), "=f"(d[45]), "=f"(d[46]), "=f"(d[47]), "=f"(d[48]), "=f"(d[49]), "=f"(d[50]), "=f"(d[51]), "=f"(d[52]), "=f"(d[53]), "=f"(d[54]), "=f"(d[55]), "=f"(d[56]), "=f"(d[57]), "=f"(d[58]), "=f"(d[59]), "=f"(d[60]), "=f"(d[61]), "=f"(d[62]), "=f"(d[63])
      : "l"(da), "l"(db));
  }
}
__device__ __forceinline__ void wgmma_n256_rs_ta0_tb1(float* d, uint32_t a0, uint32_t a1, uint32_t a2, uint32_t a3, uint64_t db, bool accumulate) {
  if (accumulate) {
    asm volatile("{\n.reg .pred p;\nsetp.ne.b32 p, 1, 0;\n"
      "wgmma.mma_async.sync.aligned.m64n256k16.f32.bf16.bf16 "
      "{%0, %1, %2, %3, %4, %5, %6, %7, %8, %9, %10, %11, %12, %13, %14, %15, %16, %17, %18, %19, %20, %21, %22, %23, %24, %25, %26, %27, %28, %29, %30, %31, %32, %33, %34, %35, %36, %37, %38, %39, %40, %41, %42, %43, %44, %45, %46, %47, %48, %49, %50, %51, %52, %53, %54, %55, %56, %57, %58, %59, %60, %61, %62, %63, %64, %65, %66, %67, %68, %69, %70, %71, %72, %73, %74, %75, %76, %77, %78, %79, %80, %81, %82, %83, %84, %85, %86, %87, %88, %89, %90, %91, %92, %93, %94, %95, %96, %97, %98, %99, %100, %101, %102, %103, %104, %105, %106, %107, %108, %109, %110, %111, %112, %113, %114, %115, %116, %117, %118, %119, %120, %121, %122, %123, %124, %125, %126, %127}, "
      "{%128, %129, %130, %131}, %132, p, 1, 1, 1;\n}\n"
      : "+f"(d[0]), "+f"(d[1]), "+f"(d[2]), "+f"(d[3]), "+f"(d[4]), "+f"(d[5]), "+f"(d[6]), "+f"(d[7]), "+f"(d[8]), "+f"(d[9]), "+f"(d[10]), "+f"(d[11]), "+f"(d[12]), "+f"(d[13]), "+f"(d[14]), "+f"(d[15]), "+f"(d[16]), "+f"(d[17]), "+f"(d[18]), "+f"(d[19]), "+f"(d[20]), "+f"(d[21]), "+f"(d[22]), "+f"(d[23]), "+f"(d[24]), "+f"(d[25]), "+f"(d[26]), "+f"(d[27]), "+f"(d[28]), "+f"(d[29]), "+f"(d[30]), "+f"(d[31]), "+f"(d[32]), "+f"(d[33]), "+f"(d[34]), "+f"(d[35]), "+f"(d[36]), "+f"(d[37]), "+f"(d[38]), "+f"(d[39]), "+f"(d[40]), "+f"(d[41]), "+f"(d[42]), "+f"(d[43]), "+f"(d[44]), "+f"(d[45]), "+f"(d[46]), "+f"(d[47]), "+f"(d[48]), "+f"(d[49]), "+f"(d[50]), "+f"(d[51]), "+f"(d[52]), "+f"(d[53]), "+f"(d[54]), "+f"(d[55]), "+f"(d[56]), "+f"(d[57]), "+f"(d[58]), "+f"(d[59]), "+f"(d[60]), "+f"(d[61]), "+f"(d[62]), "+f"(d[63]), "+f"(d[64]), "+f"(d[65]), "+f"(d[66]), "+f"(d[67]), "+f"(d[68]), "+f"(d[69]), "+f"(d[70]), "+f"(d[71]), "+f"(d[72]), "+f"(d[73]), "+f"(d[74]), "+f"(d[75]), "+f"(d[76]), "+f"(d[77]), "+f"(d[78]), "+f"(d[79]), "+f"(d[80]), "+f"(d[81]), "+f"(d[82]), "+f"(d[83]), "+f"(d[84]), "+f"(d[85]), "+f"(d[86]), "+f"(d[87]), "+f"(d[88]), "+f"(d[89]), "+f"(d[90]), "+f"(d[91]), "+f"(d[92]), "+f"(d[93]), "+f"(d[94]), "+f"(d[95]), "+f"(d[96]), "+f"(d[97]), "+f"(d[98]), "+f"(d[99]), "+f"(d[100]), "+f"(d[101]), "+f"(d[102]), "+f"(d[103]), "+f"(d[104]), "+f"(d[105]), "+f"(d[106]), "+f"(d[107]), "+f"(d[108]), "+f"(d[109]), "+f"(d[110]), "+f"(d[111]), "+f"(d[112]), "+f"(d[113]), "+f"(d[114]), "+f"(d[115]), "+f"(d[116]), "+f"(d[117]), "+f"(d[118]), "+f"(d[119]), "+f"(d[120]), "+f"(d[121]), "+f"(d[122]), "+f"(d[123]), "+f"(d[124]), "+f"(d[125]), "+f"(d[126]), "+f"(d[127])
      : "r"(a0), "r"(a1), "r"(a2), "r"(a3), "l"(db));
  } else {
    asm volatile("{\n.reg .pred p;\nsetp.ne.b32 p, 0, 0;\n"
      "wgmma.mma_async.sync.aligned.m64n256k16.f32.bf16.bf16 "
      "{%0, %1, %2, %3, %4, %5, %6, %7, %8, %9, %10, %11, %12, %13, %14, %15, %16, %17, %18, %19, %20, %21, %22, %23, %24, %25, %26, %27, %28, %29, %30, %31, %32, %33, %34, %35, %36, %37, %38, %39, %40, %41, %42, %43, %44, %45, %46, %47, %48, %49, %50, %51, %52, %53, %54, %55, %56, %57, %58, %59, %60, %61, %62, %63, %64, %65, %66, %67, %68, %69, %70, %71, %72, %73, %74, %75, %76, %77, %78, %79, %80, %81, %82, %83, %84, %85, %86, %87, %88, %89, %90, %91, %92, %93, %94, %95, %96, %97, %98, %99, %100, %101, %102, %103, %104, %105, %106, %107, %108, %109, %110, %111, %112, %113, %114, %115, %116, %117, %118, %119, %120, %121, %122, %123, %124, %125, %126, %127}, "
      "{%128, %129, %130, %131}, %132, p, 1, 1, 1;\n}\n"
      : "=f"(d[0]), "=f"(d[1]), "=f"(d[2]), "=f"(d[3]), "=f"(d[4]), "=f"(d[5]), "=f"(d[6]), "=f"(d[7]), "=f"(d[8]), "=f"(d[9]), "=f"(d[10]), "=f"(d[11]), "=f"(d[12]), "=f"(d[13]), "=f"(d[14]), "=f"(d[15]), "=f"(d[16]), "=f"(d[17]), "=f"(d[18]), "=f"(d[19]), "=f"(d[20]), "=f"(d[21]), "=f"(d[22]), "=f"(d[23]), "=f"(d[24]), "=f"(d[25]), "=f"(d[26]), "=f"(d[27]), "=f"(d[28]), "=f"(d[29]), "=f"(d[30]), "=f"(d[31]), "=f"(d[32]), "=f"(d[33]), "=f"(d[34]), "=f"(d[35]), "=f"(d[36]), "=f"(d[37]), "=f"(d[38]), "=f"(d[39]), "=f"(d[40]), "=f"(d[41]), "=f"(d[42]), "=f"(d[43]), "=f"(d[44]), "=f"(d[45]), "=f"(d[46]), "=f"(d[47]), "=f"(d[48]), "=f"(d[49]), "=f"(d[50]), "=f"(d[51]), "=f"(d[52]), "=f"(d[53]), "=f"(d[54]), "=f"(d[55]), "=f"(d[56]), "=f"(d[57]), "=f"(d[58]), "=f"(d[59]), "=f"(d[60]), "=f"(d[61]), "=f"(d[62]), "=f"(d[63]), "=f"(d[64]), "=f"(d[65]), "=f"(d[66]), "=f"(d[67]), "=f"(d[68]), "=f"(d[69]), "=f"(d[70]), "=f"(d[71]), "=f"(d[72]), "=f"(d[73]), "=f"(d[74]), "=f"(d[75]), "=f"(d[76]), "=f"(d[77]), "=f"(d[78]), "=f"(d[79]), "=f"(d[80]), "=f"(d[81]), "=f"(d[82]), "=f"(d[83]), "=f"(d[84]), "=f"(d[85]), "=f"(d[86]), "=f"(d[87]), "=f"(d[88]), "=f"(d[89]), "=f"(d[90]), "=f"(d[91]), "=f"(d[92]), "=f"(d[93]), "=f"(d[94]), "=f"(d[95]), "=f"(d[96]), "=f"(d[97]), "=f"(d[98]), "=f"(d[99]), "=f"(d[100]), "=f"(d[101]), "=f"(d[102]), "=f"(d[103]), "=f"(d[104]), "=f"(d[105]), "=f"(d[106]), "=f"(d[107]), "=f"(d[108]), "=f"(d[109]), "=f"(d[110]), "=f"(d[111]), "=f"(d[112]), "=f"(d[113]), "=f"(d[114]), "=f"(d[115]), "=f"(d[116]), "=f"(d[117]), "=f"(d[118]), "=f"(d[119]), "=f"(d[120]), "=f"(d[121]), "=f"(d[122]), "=f"(d[123]), "=f"(d[124]), "=f"(d[125]), "=f"(d[126]), "=f"(d[127])
      : "r"(a0), "r"(a1), "r"(a2), "r"(a3), "l"(db));
  }
}
__device__ __forceinline__ void wgmma_n256_ss_ta0_tb1(float* d, uint64_t da, uint64_t db, bool accumulate) {
  if (accumulate) {
    asm volatile("{\n.reg .pred p;\nsetp.ne.b32 p, 1, 0;\n"
      "wgmma.mma_async.sync.aligned.m64n256k16.f32.bf16.bf16 "
      "{%0, %1, %2, %3, %4, %5, %6, %7, %8, %9, %10, %11, %12, %13, %14, %15, %16, %17, %18, %19, %20, %21, %22, %23, %24, %25, %26, %27, %28, %29, %30, %31, %32, %33, %34, %35, %36, %37, %38, %39, %40, %41, %42, %43, %44, %45, %46, %47, %48, %49, %50, %51, %52, %53, %54, %55, %56, %57, %58, %59, %60, %61, %62, %63, %64, %65, %66, %67, %68, %69, %70, %71, %72, %73, %74, %75, %76, %77, %78, %79, %80, %81, %82, %83, %84, %85, %86, %87, %88, %89, %90, %91, %92, %93, %94, %95, %96, %97, %98, %99, %100, %101, %102, %103, %104, %105, %106, %107, %108, %109, %110, %111, %112, %113, %114, %115, %116, %117, %118, %119, %120, %121, %122, %123, %124, %125, %126, %127}, "
      "%128, %129, p, 1, 1, 0, 1;\n}\n"
      : "+f"(d[0]), "+f"(d[1]), "+f"(d[2]), "+f"(d[3]), "+f"(d[4]), "+f"(d[5]), "+f"(d[6]), "+f"(d[7]), "+f"(d[8]), "+f"(d[9]), "+f"(d[10]), "+f"(d[11]), "+f"(d[12]), "+f"(d[13]), "+f"(d[14]), "+f"(d[15]), "+f"(d[16]), "+f"(d[17]), "+f"(d[18]), "+f"(d[19]), "+f"(d[20]), "+f"(d[21]), "+f"(d[22]), "+f"(d[23]), "+f"(d[24]), "+f"(d[25]), "+f"(d[26]), "+f"(d[27]), "+f"(d[28]), "+f"(d[29]), "+f"(d[30]), "+f"(d[31]), "+f"(d[32]), "+f"(d[33]), "+f"(d[34]), "+f"(d[35]), "+f"(d[36]), "+f"(d[37]), "+f"(d[38]), "+f"(d[39]), "+f"(d[40]), "+f"(d[41]), "+f"(d[42]), "+f"(d[43]), "+f"(d[44]), "+f"(d[45]), "+f"(d[46]), "+f"(d[47]), "+f"(d[48]), "+f"(d[49]), "+f"(d[50]), "+f"(d[51]), "+f"(d[52]), "+f"(d[53]), "+f"(d[54]), "+f"(d[55]), "+f"(d[56]), "+f"(d[57]), "+f"(d[58]), "+f"(d[59]), "+f"(d[60]), "+f"(d[61]), "+f"(d[62]), "+f"(d[63]), "+f"(d[64]), "+f"(d[65]), "+f"(d[66]), "+f"(d[67]), "+f"(d[68]), "+f"(d[69]), "+f"(d[70]), "+f"(d[71]), "+f"(d[72]), "+f"(d[73]), "+f"(d[74]), "+f"(d[75]), "+f"(d[76]), "+f"(d[77]), "+f"(d[78]), "+f"(d[79]), "+f"(d[80]), "+f"(d[81]), "+f"(d[82]), "+f"(d[83]), "+f"(d[84]), "+f"(d[85]), "+f"(d[86]), "+f"(d[87]), "+f"(d[88]), "+f"(d[89]), "+f"(d[90]), "+f"(d[91]), "+f"(d[92]), "+f"(d[93]), "+f"(d[94]), "+f"(d[95]), "+f"(d[96]), "+f"(d[97]), "+f"(d[98]), "+f"(d[99]), "+f"(d[100]), "+f"(d[101]), "+f"(d[102]), "+f"(d[103]), "+f"(d[104]), "+f"(d[105]), "+f"(d[106]), "+f"(d[107]), "+f"(d[108]), "+f"(d[109]), "+f"(d[110]), "+f"(d[111]), "+f"(d[112]), "+f"(d[113]), "+f"(d[114]), "+f"(d[115]), "+f"(d[116]), "+f"(d[117]), "+f"(d[118]), "+f"(d[119]), "+f"(d[120]), "+f"(d[121]), "+f"(d[122]), "+f"(d[123]), "+f"(d[124]), "+f"(d[125]), "+f"(d[126]), "+f"(d[127])
      : "l"(da), "l"(db));
  } else {
    asm volatile("{\n.reg .pred p;\nsetp.ne.b32 p, 0, 0;\n"
      "wgmma.mma_async.sync.aligned.m64n256k16.f32.bf16.bf16 "
      "{%0, %1, %2, %3, %4, %5, %6, %7, %8, %9, %10, %11, %12, %13, %14, %15, %16, %17, %18, %19, %20, %21, %22, %23, %24, %25, %26, %27, %28, %29, %30, %31, %32, %33, %34, %35, %36, %37, %38, %39, %40, %41, %42, %43, %44, %45, %46, %47, %48, %49, %50, %51, %52, %53, %54, %55, %56, %57, %58, %59, %60, %61, %62, %63, %64, %65, %66, %67, %68, %69, %70, %71, %72, %73, %74, %75, %76, %77, %78, %79, %80, %81, %82, %83, %84, %85, %86, %87, %88, %89, %90, %91, %92, %93, %94, %95, %96, %97, %98, %99, %100, %101, %102, %103, %104, %105, %106, %107, %108, %109, %110, %111, %112, %113, %114, %115, %116, %117, %118, %119, %120, %121, %122, %123, %124, %125, %126, %127}, "
      "%128, %129, p, 1, 1, 0, 1;\n}\n"
      : "=f"(d[0]), "=f"(d[1]), "=f"(d[2]), "=f"(d[3]), "=f"(d[4]), "=f"(d[5]), "=f"(d[6]), "=f"(d[7]), "=f"(d[8]), "=f"(d[9]), "=f"(d[10]), "=f"(d[11]), "=f"(d[12]), "=f"(d[13]), "=f"(d[14]), "=f"(d[15]), "=f"(d[16]), "=f"(d[17]), "=f"(d[18]), "=f"(d[19]), "=f"(d[20]), "=f"(d[21]), "=f"(d[22]), "=f"(d[23]), "=f"(d[24]), "=f"(d[25]), "=f"(d[26]), "=f"(d[27]), "=f"(d[28]), "=f"(d[29]), "=f"(d[30]), "=f"(d[31]), "=f"(d[32]), "=f"(d[33]), "=f"(d[34]), "=f"(d[35]), "=f"(d[36]), "=f"(d[37]), "=f"(d[38]), "=f"(d[39]), "=f"(d[40]), "=f"(d[41]), "=f"(d[42]), "=f"(d[43]), "=f"(d[44]), "=f"(d[45]), "=f"(d[46]), "=f"(d[47]), "=f"(d[48]), "=f"(d[49]), "=f"(d[50]), "=f"(d[51]), "=f"(d[52]), "=f"(d[53]), "=f"(d[54]), "=f"(d[55]), "=f"(d[56]), "=f"(d[57]), "=f"(d[58]), "=f"(d[59]), "=f"(d[60]), "=f"(d[61]), "=f"(d[62]), "=f"(d[63]), "=f"(d[64]), "=f"(d[65]), "=f"(d[66]), "=f"(d[67]), "=f"(d[68]), "=f"(d[69]), "=f"(d[70]), "=f"(d[71]), "=f"(d[72]), "=f"(d[73]), "=f"(d[74]), "=f"(d[75]), "=f"(d[76]), "=f"(d[77]), "=f"(d[78]), "=f"(d[79]), "=f"(d[80]), "=f"(d[81]), "=f"(d[82]), "=f"(d[83]), "=f"(d[84]), "=f"(d[85]), "=f"(d[86]), "=f"(d[87]), "=f"(d[88]), "=f"(d[89]), "=f"(d[90]), "=f"(d[91]), "=f"(d[92]), "=f"(d[93]), "=f"(d[94]), "=f"(d[95]), "=f"(d[96]), "=f"(d[97]), "=f"(d[98]), "=f"(d[99]), "=f"(d[100]), "=f"(d[101]), "=f"(d[102]), "=f"(d[103]), "=f"(d[104]), "=f"(d[105]), "=f"(d[106]), "=f"(d[107]), "=f"(d[108]), "=f"(d[109]), "=f"(d[110]), "=f"(d[111]), "=f"(d[112]), "=f"(d[113]), "=f"(d[114]), "=f"(d[115]), "=f"(d[116]), "=f"(d[117]), "=f"(d[118]), "=f"(d[119]), "=f"(d[120]), "=f"(d[121]), "=f"(d[122]), "=f"(d[123]), "=f"(d[124]), "=f"(d[125]), "=f"(d[126]), "=f"(d[127])
      : "l"(da), "l"(db));
  }
}
__device__ __forceinline__ void wgmma_n256_ssp_ta0_tb1(float* d, uint64_t da, uint64_t db, int accumulate) {
    asm volatile("{\n.reg .pred p;\nsetp.ne.b32 p, %130, 0;\n"
      "wgmma.mma_async.sync.aligned.m64n256k16.f32.bf16.bf16 "
      "{%0, %1, %2, %3, %4, %5, %6, %7, %8, %9, %10, %11, %12, %13, %14, %15, %16, %17, %18, %19, %20, %21, %22, %23, %24, %25, %26, %27, %28, %29, %30, %31, %32, %33, %34, %35, %36, %37, %38, %39, %40, %41, %42, %43, %44, %45, %46, %47, %48, %49, %50, %51, %52, %53, %54, %55, %56, %57, %58, %59, %60, %61, %62, %63, %64, %65, %66, %67, %68, %69, %70, %71, %72, %73, %74, %75, %76, %77, %78, %79, %80, %81, %82, %83, %84, %85, %86, %87, %88, %89, %90, %91, %92, %93, %94, %95, %96, %97, %98, %99, %100, %101, %102, %103, %104, %105, %106, %107, %108, %109, %110, %111, %112, %113, %114, %115, %116, %117, %118, %119, %120, %121, %122, %123, %124, %125, %126, %127}, "
      "%128, %129, p, 1, 1, 0, 1;\n}\n"
      : "+f"(d[0]), "+f"(d[1]), "+f"(d[2]), "+f"(d[3]), "+f"(d[4]), "+f"(d[5]), "+f"(d[6]), "+f"(d[7]), "+f"(d[8]), "+f"(d[9]), "+f"(d[10]), "+f"(d[11]), "+f"(d[12]), "+f"(d[13]), "+f"(d[14]), "+f"(d[15]), "+f"(d[16]), "+f"(d[17]), "+f"(d[18]), "+f"(d[19]), "+f"(d[20]), "+f"(d[21]), "+f"(d[22]), "+f"(d[23]), "+f"(d[24]), "+f"(d[25]), "+f"(d[26]), "+f"(d[27]), "+f"(d[28]), "+f"(d[29]), "+f"(d[30]), "+f"(d[31]), "+f"(d[32]), "+f"(d[33]), "+f"(d[34]), "+f"(d[35]), "+f"(d[36]), "+f"(d[37]), "+f"(d[38]), "+f"(d[39]), "+f"(d[40]), "+f"(d[41]), "+f"(d[42]), "+f"(d[43]), "+f"(d[44]), "+f"(d[45]), "+f"(d[46]), "+f"(d[47]), "+f"(d[48]), "+f"(d[49]), "+f"(d[50]), "+f"(d[51]), "+f"(d[52]), "+f"(d[53]), "+f"(d[54]), "+f"(d[55]), "+f"(d[56]), "+f"(d[57]), "+f"(d[58]), "+f"(d[59]), "+f"(d[60]), "+f"(d[61]), "+f"(d[62]), "+f"(d[63]), "+f"(d[64]), "+f"(d[65]), "+f"(d[66]), "+f"(d[67]), "+f"(d[68]), "+f"(d[69]), "+f"(d[70]), "+f"(d[71]), "+f"(d[72]), "+f"(d[73]), "+f"(d[74]), "+f"(d[75]), "+f"(d[76]), "+f"(d[77]), "+f"(d[78]), "+f"(d[79]), "+f"(d[80]), "+f"(d[81]), "+f"(d[82]), "+f"(d[83]), "+f"(d[84]), "+f"(d[85]), "+f"(d[86]), "+f"(d[87]), "+f"(d[88]), "+f"(d[89]), "+f"(d[90]), "+f"(d[91]), "+f"(d[92]), "+f"(d[93]), "+f"(d[94]), "+f"(d[95]), "+f"(d[96]), "+f"(d[97]), "+f"(d[98]), "+f"(d[99]), "+f"(d[100]), "+f"(d[101]), "+f"(d[102]), "+f"(d[103]), "+f"(d[104]), "+f"(d[105]), "+f"(d[106]), "+f"(d[107]), "+f"(d[108]), "+f"(d[109]), "+f"(d[110]), "+f"(d[111]), "+f"(d[112]), "+f"(d[113]), "+f"(d[114]), "+f"(d[115]), "+f"(d[116]), "+f"(d[117]), "+f"(d[118]), "+f"(d[119]), "+f"(d[120]), "+f"(d[121]), "+f"(d[122]), "+f"(d[123]), "+f"(d[124]), "+f"(d[125]), "+f"(d[126]), "+f"(d[127])
      : "l"(da), "l"(db), "r"(accumulate));
}

template <int N> __device__ __forceinline__ void quad_sum(float* m) {
#pragma unroll
  for (int o = 1; o <= 2; o <<= 1) {
    float t[N];
#pragma unroll
    for (int i = 0; i < N; i++) t[i] = __shfl_xor_sync(~0u, m[i], o);
#pragma unroll
    for (int i = 0; i < N; i++) m[i] += t[i];
  }
}
__device__ __forceinline__ bool softmax_unsafe(const uint32_t* t, float l0, float l1) {
  const float m0 = fmaxf(bf_lo(t[0]) + bf_hi(t[0]), bf_lo(t[2]) + bf_hi(t[2])), m1 = fmaxf(bf_lo(t[1]) + bf_hi(t[1]), bf_lo(t[3]) + bf_hi(t[3]));
  return __any_sync(~0u, !(m0 * l0 < 2500.f) | !(m1 * l1 < 2500.f));
}
__device__ __forceinline__ void softmax_shift(float* p, float c0, float c1) {
#pragma unroll 1
  for (int it = 0; it < 8; it++) {
    float mx = p[0], mn = p[0];
#pragma unroll
    for (int j = 1; j < 8; j++) { mx = fmaxf(mx, p[(j >> 1) * 4 + (j & 1)]); mn = fminf(mn, p[(j >> 1) * 4 + (j & 1)]); }
#pragma unroll
    for (int o = 1; o <= 2; o <<= 1) { mx = fmaxf(mx, __shfl_xor_sync(~0u, mx, o)); mn = fminf(mn, __shfl_xor_sync(~0u, mn, o)); }
    const float half = fminf(0.5f * (mx - mn), 50.f * rcp(it & 1 ? c1 : c0));
    float r[8];
#pragma unroll
    for (int j = 0; j < 8; j++) {
      const float v = p[(j >> 1) * 4 + (j & 1)];
      r[j] = fmaxf(v - mx + half, 0.f) + fminf(v - mn - half, 0.f) + (v - v);
    }
#pragma unroll
    for (int k = 0; k < 7; k++)
#pragma unroll
      for (int j = 0; j < 8; j++) p[(k >> 1) * 16 + (k & 1) * 2 + (j >> 1) * 4 + (j & 1)] = p[((k + 1) >> 1) * 16 + ((k + 1) & 1) * 2 + (j >> 1) * 4 + (j & 1)];
#pragma unroll
    for (int j = 0; j < 8; j++) p[50 + (j >> 1) * 4 + (j & 1)] = r[j];
  }
}
template <int J0 = 0, int J1 = 8> __device__ __forceinline__ void k_exp(const float* p, float c0, float c1, float* e, float* s) {
#pragma unroll
  for (int j = J0; j < J1; j++) {
    e[2 * j] = ex2(p[2 * j] * (j & 1 ? c1 : c0));
    e[2 * j + 1] = ex2(p[2 * j + 1] * (j & 1 ? c1 : c0));
    e[16 + j] = rcp(e[2 * j] * e[2 * j + 1]);
    const float t = e[2 * j] + e[2 * j + 1];
    s[j & 1] = j < 2 ? t : s[j & 1] + t;
    s[2 + (j & 1)] = j < 2 ? e[16 + j] * t : fmaf(e[16 + j], t, s[2 + (j & 1)]);
  }
}
template <int J0 = 0, int J1 = 8> __device__ __forceinline__ void q_exp(const float* p, float c0, float c1, uint32_t* f) {
#pragma unroll
  for (int j = J0; j < J1; j++) {
    const float e0 = ex2(p[2 * j] * (j & 1 ? c1 : c0)), e1 = ex2(p[2 * j + 1] * (j & 1 ? c1 : c0)), r = rcp(e0 * e1);
    f[j] = pack2(e0, e1);
    f[8 + j] = bmul2(f[j], pack2(r, r));
  }
}

#define FMA8(A, U, X)                                                                                        \
  A[0] = fmaf(bf_lo(U.x), X, A[0]); A[1] = fmaf(bf_hi(U.x), X, A[1]); A[2] = fmaf(bf_lo(U.y), X, A[2]); A[3] = fmaf(bf_hi(U.y), X, A[3]); \
  A[4] = fmaf(bf_lo(U.z), X, A[4]); A[5] = fmaf(bf_hi(U.z), X, A[5]); A[6] = fmaf(bf_lo(U.w), X, A[6]); A[7] = fmaf(bf_hi(U.w), X, A[7])

__device__ __forceinline__ uint32_t routed_row(const __nv_bfloat16* x, uint32_t tag, int lane, uint4* xr) {
  uint32_t best = 0, sv = 0;
#pragma unroll 1
  for (int it = 0; it < SPIN_MAX; it++) {
    const int sel = 2047 - (best & 0x7ff);
#pragma unroll
    for (int i = 0; i < 4; i++) xr[i] = ldg_nc(x + (size_t)sel * DM + i * 256 + lane * 8);
    const unsigned long long st = ld_rlx64(g_stat + sel);
    const uint4 b0 = ld_rlx128(g_best + lane * 2), b1 = ld_rlx128(g_best + 64 + lane * 2);
    const uint32_t m = __reduce_max_sync(~0u, max(max(b0.y == tag ? b0.x : 0u, b0.w == tag ? b0.z : 0u), max(b1.y == tag ? b1.x : 0u, b1.w == tag ? b1.z : 0u)));
    sv = (uint32_t)st;
    if (__all_sync(~0u, b0.y == tag && b0.w == tag && b1.y == tag && b1.w == tag && m == best && (uint32_t)(st >> 32) == tag)) break;
    best = m;
    if (AM_NS) __nanosleep(AM_NS);
  }
  const uint32_t m2 = (sv & 0xffff0000u) | (sv >> 16);
  const float rs = rcp(bf_lo(sv));
#pragma unroll
  for (int i = 0; i < 4; i++) {
    const uint32_t d0 = bsub2(xr[i].x, m2), d1 = bsub2(xr[i].y, m2), d2 = bsub2(xr[i].z, m2), d3 = bsub2(xr[i].w, m2);
    xr[i] = make_uint4(pack2(bf_lo(d0) * rs, bf_hi(d0) * rs), pack2(bf_lo(d1) * rs, bf_hi(d1) * rs), pack2(bf_lo(d2) * rs, bf_hi(d2) * rs),
                       pack2(bf_lo(d3) * rs, bf_hi(d3) * rs));
  }
  return best;
}

struct Params {
  const __nv_bfloat16 *x, *wqkv, *wo, *w_r, *w_gate, *w_up, *w_down;
};

template <bool BY_SMID> __global__ void __launch_bounds__(384, 1)
fused_kernel(const __grid_constant__ CUtensorMap mX, const __grid_constant__ CUtensorMap mWkv, const __grid_constant__ CUtensorMap mWq,
             const __grid_constant__ CUtensorMap mWo, const __grid_constant__ CUtensorMap mPhi, const __grid_constant__ CUtensorMap mWp,
             const __grid_constant__ CUtensorMap mOut, const __grid_constant__ CUtensorMap mWc,
             const __grid_constant__ CUtensorMap mG, const __grid_constant__ CUtensorMap mU, const __grid_constant__ CUtensorMap mD,
             const __grid_constant__ CUtensorMap mXs, const __grid_constant__ CUtensorMap mG2, const __grid_constant__ CUtensorMap mU2, const Params P) {
  constexpr uint32_t sb = SB, bar = SB + SM_BAR;
  int bid = blockIdx.x;
  if (BY_SMID) {
    uint32_t sm;
    asm volatile("mov.u32 %0, %%smid;" : "=r"(sm));
    const uint32_t tq = (sm - 64) >> 1, q7 = (tq * 37) >> 8;
    const uint32_t gpc = sm < 64 ? (sm >> 1) & 7 : 1 + tq - 7 * q7, idx = (sm < 64 ? sm >> 4 : 4 + q7) * 2 + (sm & 1);
    bid = sm < 120 ? ((PTAB >> (4 * gpc)) & 7) * 16 + idx : sm < 124 ? sm + 8 : sm - 116;
  }
  const int hg = ((bid >> 2) & 3) + 4 * ((bid >> 4) & 1), mb = (bid & 3) + 4 * ((bid >> 5) & 3);
  if (bid < NCTA && threadIdx.x < 256) {
    const uint32_t r0 = threadIdx.x >> 3, c = threadIdx.x & 7, dst = sb + 2 * KV_STAGE + r0 * 128 + ((c ^ (r0 & 7)) << 4);
    const char* xs = (const char*)P.x + (size_t)(mb * 128 + r0) * 2048 + c * 16;
    const char* ws = (const char*)P.wqkv + (size_t)r0 * 6144 + 2048 + hg * 256 + c * 16;
#pragma unroll
    for (int i = 0; i < 4; i++) cp_async16(dst + i * 4096, xs + i * 65536);
#pragma unroll
    for (int i = 0; i < 8; i++) cp_async16(dst + 16384 + i * 4096, ws + (i & 1) * 196608 + (i >> 2) * 2048 + ((i >> 1) & 1) * 128);
  }
  extern __shared__ __align__(1024) uint8_t smem[];
  if (smem_u32(smem) != SB) __trap();
  const int warp = __shfl_sync(~0u, threadIdx.x >> 5, 0);

  if (bid >= NCTA) {
    constexpr uint32_t XV = SM_WPHI, ONES = SM_ZT, BF = bar, BE = bar + 48, BX = bar + 96;
    constexpr int NJ = (DM - GROWS) / 64;
    const int lane = lane_id(), sp = bid - NCTA;
    const uint32_t tag = ld_rlx(g_epoch + bid * 32 + lane) + 1;
    if (warp == 8 && elect_one()) {
#pragma unroll 1
      for (int i = 0; i < 13; i++) mbar_init(bar + 8 * i, i >= 6 && i < 12 ? 8 : 1);
    }
    if (warp == 9) { sts64u(sb + ONES + lane * 8, 0x3f803f80u, 0x3f803f80u); fence_async_smem(); }
    __syncthreads();
    if (warp == 8) {
      if (elect_one()) {
        uint32_t s = 0, ph = 1;
        for (const long long c0 = clock64(); clock64() - c0 < SP_DELAY;) {}
#pragma unroll 1
        for (int job = 0; job < 8; job++) {
          const CUtensorMap* m = job == 0 ? &mWq : sp & 2 ? &mU2 : &mG2;
          const int g0 = job ? (sp & 1) * 28 + job * 4 - 4 : sp * 4;
#pragma unroll 1
          for (int row = job ? GROWS : 0; row < DM; row += 64) {
            mbar_wait(BE + 8 * s, ph);
            mbar_expect_tx(BF + 8 * s, Q_STAGE);
            tma4d(sb + s * Q_STAGE, m, 0, row, g0, 0, BF + 8 * s);
            tma4d(sb + s * Q_STAGE + 16384, m, 0, row, g0 + 2, 0, BF + 8 * s);
            if (++s == 6) { s = 0; ph ^= 1; }
          }
        }
      }
    } else if (warp == 9) {
      uint4 xr[4];
      routed_row(P.x, tag, lane, xr);
#pragma unroll
      for (int i = 0; i < 4; i++) sts128u(sb + XV + i * 512 + lane * 16, xr[i].x, xr[i].y, xr[i].z, xr[i].w);
      fence_async_smem();
      __syncwarp();
      if (lane == 0) mbar_arrive(BX);
    } else if (warp < 8) {
      uint32_t s = 0, ph = 0;
#pragma unroll 1
      for (int job = 0; job < 8; job++) {
        float d[8] = {0.f, 0.f, 0.f, 0.f, 0.f, 0.f, 0.f, 0.f};
        if (job == 1) mbar_wait(BX, 0);
#pragma unroll 1
        for (int i = 0; i < (job ? NJ : 16); i++) {
          mbar_wait(BF + 8 * s, ph);
          wg_fence();
#pragma unroll
          for (int k = 0; k < 8; k++)
            wgmma_n8_ss_ta1_tb0(d + 4 * (k >> 2), mkdesc(sb + k * 2048, 16, 1024, 1, s * (Q_STAGE / 16) + (warp >> 2) * 1024),
                                mkdesc(sb, 16, 128, 0, job ? (XV + GROWS * 2) / 16 + i * 8 + (k & 3) * 2 : ONES / 16), 1);
          wg_commit();
          wg_wait<0>();
          if (lane == 0) mbar_arrive(BE + 8 * s);
          if (++s == 6) { s = 0; ph ^= 1; }
        }
        reg_fence<8>(d);
        float* dst = (job ? g_gp + sp * 1792 + job * 256 - 256 : g_cs + sp * 256) + (warp >> 2) * 128 + (warp & 3) * 16 + (lane >> 2);
        if ((lane & 3) == 0) {
#pragma unroll
          for (int i = 0; i < 4; i++) st_rlx(dst + (i >> 1) * 64 + (i & 1) * 8, mark(__float_as_uint(d[2 * i]), tag & 1));
        }
        __syncwarp();
      }
      if (warp == 0) g_epoch[bid * 32 + lane] = tag;
    }
    return;
  }
#define Q_SLAB(J) ((J) < 8 ? ((J) + 8 - 2 * (hg & 4)) & 15 : 2 * (hg & 4) + 2 * ((J) & 3) + ((J) >> 2 & 1))
#define Q_AOFF(J) ((J) == 8 + (hg & 3) ? SM_X0 : (J) == 12 + (hg & 3) ? SM_X1 : ((J) & 3) * Q_STAGE)
#define Q_LOAD(J)                                                                                            \
  do {                                                                                                       \
    const uint32_t fb_ = bar + B_FULLQ + 8 * ((J) & 3);                                                      \
    const int k_ = Q_SLAB(J) * 64;                                                                           \
    mbar_expect_tx(fb_, Q_STAGE);                                                                            \
    mbar_arrive2(fb_);                                                                                       \
    tma2d(sb + Q_AOFF(J), &mX, k_, mb * 128, fb_);                                                           \
    tma4d(sb + ((J) & 3) * Q_STAGE + 16384, &mWq, 0, k_, hg * 2, 0, fb_);                                    \
  } while (0)
  if (warp >= 8) {
    asm volatile("setmaxnreg.dec.sync.aligned.u32 %0;" ::"n"(REG_H));
    const int lane = lane_id();
    const int f = (warp - 9) & 3;
    if (f == 3) {
      if (elect_one()) {
        PROF(0); PROFT(32);
#pragma unroll
        for (int s = 0; s < 3; s++) mbar_init(bar + B_FULLKV + 8 * s, 1);
      }
      __syncwarp();
      asm volatile("bar.arrive 14, 288;" ::: "memory");
      if (elect_one()) {
#pragma unroll
        for (int s = 0; s < 2; s++) {
          mbar_expect_tx(bar + B_FULLKV + 8 * s, KV_STAGE);
          tma2d(sb + s * KV_STAGE, &mX, (s + 1) * 64, mb * 128, bar + B_FULLKV + 8 * s);
          tma4d(sb + s * KV_STAGE + 16384, &mWkv, 0, (s + 1) * 64, hg * 2, 1, bar + B_FULLKV + 8 * s);
        }
      }
      __syncwarp();
    }
    const uint32_t ep = ld_rlx(g_epoch + bid * 32 + lane);
    if (f < 2) {
#pragma unroll
      for (int i = 0; i < 2; i++) {
        const uint4 u = __ldg((const uint4*)P.w_r + (f * 2 + i) * 32 + lane);
        sts128u(sb + SM_XSEL + (f * 2 + i) * 512 + lane * 16, u.x, u.y, u.z, u.w);
      }
    }
    bar_sync(13, 384);
    const uint32_t tag = ep + 1, par = tag & 1;
    const bool ffn = bid < NFFN;
    const int fb = bid, cu = bid >> 1, ch = bid & 1;
#define CS_STORE(SEC, C)                                                                                     \
  _Pragma("unroll") for (int r = 0; r < 3; r++) {                                                            \
    const uint32_t h0 = pack2(C.x, C.y), h1 = pack2(C.z, C.w);                                               \
    sts64u(sb + SM_CST + (SEC) * 1024 + (lane >> 4) * 512 + (lane & 1) * 8 + r * 128 + ((((lane & 15) >> 1) ^ (r + (lane >> 4) * 4)) << 4), h0, h1); \
    C.x -= bf_lo(h0); C.y -= bf_hi(h0); C.z -= bf_lo(h1); C.w -= bf_hi(h1);                                  \
  }
#define BAD4(U) ((U.x ^ par) | (U.y ^ par) | (U.z ^ par) | (U.w ^ par))
    const int n0 = f < 2 ? 0 : 2 * f - 3, ne = FFN_OFF || !ffn ? 3 : f == 3 ? 3 + G8 : 3 + GN;
    const uint32_t fsb = sb + SM_FST + ((f + 1) & 3) * 8192, fbar = bar + B_FST + f * 16, fst = fsb + (lane >> 4) * 2048 + (lane & 15) * 16;
    const CUtensorMap *ma = &mWc, *mc = &mWc;
    int sx = 1024 + cu * 32, sy = ch * 512 + f * 192, sdy = 32;
#define STAGEG(N)                                                                                            \
  do {                                                                                                       \
    if ((N) == 3) { ma = &mG; mc = &mU; sx = fb * 32; sy = f * (GN * 32);  sdy = 0; }                        \
    if ((N) < ne && elect_one()) {                                                                           \
      const uint32_t dst_ = fsb + ((N) & 1) * 4096, b_ = fbar + ((N) & 1) * 8;                               \
      mbar_expect_tx(b_, 4096);                                                                              \
      tma2d(dst_, ma, sx, sy, b_);                                                                           \
      tma2d(dst_ + 2048, mc, sx, sy + sdy, b_);                                                              \
    }                                                                                                        \
    sy += 32 + sdy;                                                                                          \
  } while (0)
    float a[8], gsum = 0.f, usum = 0.f;
    {
      if (f == 3) {
        if (elect_one()) {
          if (XS_EARLY) { mbar_expect_tx(bar + B_XST, 16384); tma3d(sb + SM_XST, &mXs, 0, bid * 16, 0, bar + B_XST); }
          mbar_expect_tx(bar + B_WPHI, 8192);
          tma2d(sb + SM_WPHI, &mPhi, 0, hg * 128, bar + B_WPHI);
          prefetch_map(&mWq); prefetch_map(&mWo); prefetch_map(&mWp); prefetch_map(&mD);
          PROF(31);
        }
        __syncwarp();
      } else {
        if (lane == 0) prefetch_map(f == 0 ? &mWc : f == 1 ? &mG : &mU);
        if (f == 2) ((float2*)g_y[par])[bid * 32 + lane] = make_float2(0.f, 0.f);
      }
      float st[13];
#pragma unroll
      for (int i = 0; i < 13; i++) st[i] = 0.f;
#pragma unroll 1
      for (int i = 0; i < 4; i++) {
        mbar_wait(bar + B_XST + 8 * (i >> 1), 0);
        if (f == 0 && lane == 0 && i == 0) PROF(1);
        const uint4 wu = lds128u(sb + SM_XSEL + i * 512 + lane * 16);
        const float wf[8] = {bf_lo(wu.x), bf_hi(wu.x), bf_lo(wu.y), bf_hi(wu.y), bf_lo(wu.z), bf_hi(wu.z), bf_lo(wu.w), bf_hi(wu.w)};
        st[12] += ((wf[0] + wf[1]) + (wf[2] + wf[3])) + ((wf[4] + wf[5]) + (wf[6] + wf[7]));
#pragma unroll
        for (int r = 0; r < 4; r++) {
          const uint4 u = lds128u(sb + SM_XST + i * 8192 + (4 * f + r) * 512 + lane * 16);
          const float xf[8] = {bf_lo(u.x), bf_hi(u.x), bf_lo(u.y), bf_hi(u.y), bf_lo(u.z), bf_hi(u.z), bf_lo(u.w), bf_hi(u.w)};
#pragma unroll
          for (int k = 0; k < 8; k++) { st[r] += xf[k]; st[4 + r] = fmaf(xf[k], xf[k], st[4 + r]); st[8 + r] = fmaf(xf[k], wf[k], st[8 + r]); }
        }
        if (i >= 2 && f < 3) STAGEG(n0 + i - 2);
      }
      const bool up = lane & 16, up2 = lane & 8;
#pragma unroll
      for (int q = 0; q < 3; q++) {
        const float k0 = up ? st[4 * q + 2] : st[4 * q], k1 = up ? st[4 * q + 3] : st[4 * q + 1];
        const float o0 = up ? st[4 * q] : st[4 * q + 2], o1 = up ? st[4 * q + 1] : st[4 * q + 3];
        const float m0 = k0 + __shfl_xor_sync(~0u, o0, 16), m1 = k1 + __shfl_xor_sync(~0u, o1, 16);
        a[q] = (up2 ? m1 : m0) + __shfl_xor_sync(~0u, up2 ? m0 : m1, 8);
      }
      a[3] = st[12] + __shfl_xor_sync(~0u, st[12], 16);
      a[3] += __shfl_xor_sync(~0u, a[3], 8);
#pragma unroll
      for (int o = 4; o; o >>= 1)
#pragma unroll
        for (int q = 0; q < 4; q++) a[q] += __shfl_xor_sync(~0u, a[q], o);
      if ((lane & 7) == 0) sts128(sb + SM_ROWS + (4 * f + (lane >> 3)) * 16, a[0], a[1], a[2], a[3]);
      if (f < 3) asm volatile("bar.arrive 7, 128;" ::: "memory");
    }
    if (f == 3) {
      bar_sync(7, 128);
      const int row = bid * 16 + (lane & 15);
      const float4 v = lds128(sb + SM_ROWS + (lane & 15) * 16);
      const float mf = v.x * (1.f / DM), mean = bf_round(mf), var = fmaxf(fmaf(-mf, mf, v.y * (1.f / DM)), 0.f);
      const float sd = bf_round(sqrt_approx(bf_round(bf_round(var) + 1e-5f)));
      const uint32_t rb = pack2(fmaf(-mean, v.w, v.z) * rcp(sd), 0.f) & 0xffffu, ord = (rb & 0x8000u) ? (~rb & 0xffffu) : (rb | 0x8000u);
      uint32_t best = __reduce_max_sync(~0u, (ord << 16) | (uint32_t)(2047 - row));
      if (lane < 16) st_rlx64(g_stat + row, ((unsigned long long)tag << 32) | __float_as_uint(mean) | (__float_as_uint(sd) >> 16));
      if (lane == 0) { asm volatile("red.relaxed.gpu.global.max.u64 [%0], %1;" ::"l"(g_best + bid), "l"(((unsigned long long)tag << 32) | best) : "memory"); PROF(17); }
#pragma unroll 1
      for (int n = 3; n < 5; n++) STAGEG(n);
      {
        uint4 xr[4];
        best = routed_row(P.x, tag, lane, xr);
#pragma unroll
        for (int i = 0; i < (GROWS + 255) / 256; i++) {
          const uint32_t dst = sb + SM_XSEL + i * 1024 + (lane >> 2) * 128 + (lane & 3) * 8;
          sts64(dst, bf_lo(xr[i].x), bf_lo(xr[i].z)); sts64(dst + 32, bf_hi(xr[i].x), bf_hi(xr[i].z));
          sts64(dst + 64, bf_lo(xr[i].y), bf_lo(xr[i].w)); sts64(dst + 96, bf_hi(xr[i].y), bf_hi(xr[i].w));
        }
        sts64u(sb + SM_RED + 16, tag, best);
        __syncwarp();
        if (lane == 0) { mbar_arrive(bar + B_XS); PROF(19); }
      }
      unsigned long long sv4[4];
      uint4 u[4];
#pragma unroll 1
      for (int it = 0; it < SPIN_MAX; it++) {
#pragma unroll
        for (int i = 0; i < 4; i++) { u[i] = ld_rlx128(g_cs + (1 + i) * 1024 + hg * 128 + lane * 4); sv4[i] = ld_rlx64(g_stat + mb * 128 + i * 32 + lane); }
        bool ok = ((BAD4(u[0]) | BAD4(u[1]) | BAD4(u[2]) | BAD4(u[3])) & 1) == 0;
#pragma unroll
        for (int i = 0; i < 4; i++) ok = ok && (uint32_t)(sv4[i] >> 32) == tag;
        if (__all_sync(~0u, ok)) break;
        __nanosleep(200);
      }
#pragma unroll
      for (int i = 0; i < 4; i++) {
        const uint32_t sv = (uint32_t)sv4[i], sd2 = (sv << 16) | (sv & 0xffffu);
        sts64(sb + SM_STAT + (i * 32 + lane) * 8, -bf_hi(sv), rcp(bf_lo(sv)));
        sts128u(sb + SM_SDT + lane * 64 + ((i ^ ((lane >> 1) & 3)) << 4), sd2, sd2, sd2, sd2);
      }
#pragma unroll
      for (int i = 0; i < 2; i++) {
        float4 c = make_float4(unmark(u[i].x) + unmark(u[i + 2].x), unmark(u[i].y) + unmark(u[i + 2].y), unmark(u[i].z) + unmark(u[i + 2].z),
                               unmark(u[i].w) + unmark(u[i + 2].w));
        CS_STORE(i, c);
      }
      fence_async_smem();
      bar_sync(8, 64);
      if (lane == 0) { mbar_arrive(bar + B_CS); PROF(10); }
    }
    {
      uint32_t xa = sb + SM_RED + 32, xstep = 0;
      const uint32_t zero = __float_as_uint(lds32(sb + SM_RED + 12));
#pragma unroll 1
      for (int ph = f == 3; ph < 2; ph++) {
#pragma unroll
        for (int j = 0; j < 8; j++) a[j] = 0.f;
        if (ph && f == 0) {
        {
          mbar_wait(bar + B_WPHI, 0);
          float nq[8] = {0.f, 0.f, 0.f, 0.f, 0.f, 0.f, 0.f, 0.f};
  #pragma unroll 2
          for (int r = 0; r < 16; r++) {
            const uint4 u = lds128u(sb + SM_WPHI + ((lane >> 2) * 16 + r) * 64 + (((lane ^ (r >> 1)) & 3) << 4));
            nq[0] = fmaf(bf_lo(u.x), bf_lo(u.x), nq[0]); nq[1] = fmaf(bf_hi(u.x), bf_hi(u.x), nq[1]); nq[2] = fmaf(bf_lo(u.y), bf_lo(u.y), nq[2]);
            nq[3] = fmaf(bf_hi(u.y), bf_hi(u.y), nq[3]); nq[4] = fmaf(bf_lo(u.z), bf_lo(u.z), nq[4]); nq[5] = fmaf(bf_hi(u.z), bf_hi(u.z), nq[5]);
            nq[6] = fmaf(bf_lo(u.w), bf_lo(u.w), nq[6]); nq[7] = fmaf(bf_hi(u.w), bf_hi(u.w), nq[7]);
          }
          uint32_t m = 0;
  #pragma unroll
          for (int i = 0; i < 8; i++) m = max(m, __float_as_uint(nq[i] + __shfl_xor_sync(~0u, nq[i], 4)) & 0x7fffffffu);
          sts32(sb + SM_RED + 24, 4.2f * __uint_as_float(__reduce_max_sync(~0u, m)));
        }
          asm volatile("bar.arrive 8, 64;" ::: "memory");
        }
        if (ph) { mbar_wait(bar + B_XS, 0); xa = sb + SM_XSEL + f * (GN * 128) + ((lane >> 2) & 3) * 32; xstep = 128; }
#pragma unroll 1
        for (int n = ph ? 3 : n0; n < (ph ? ne : 3); n++) {
          const float4 x0 = lds128(xa), x1 = lds128(xa + 16);
          xa += xstep;
          mbar_wait(fbar + (n & 1) * 8, ((n - n0) >> 1) & 1);
          uint4 u[8];
#pragma unroll
          for (int j = 0; j < 8; j++) u[j] = lds128u(fst + (n & 1) * 4096 + j * 256);
          FMA8(a, u[0], x0.x); FMA8(a, u[1], x0.y); FMA8(a, u[2], x0.z); FMA8(a, u[3], x0.w);
          if (__any_sync(~0u, ((u[4].x | u[5].x | u[6].x | u[7].x | __float_as_uint(a[0]) | __float_as_uint(a[7])) & zero) == 0)) STAGEG(n + 2);
          FMA8(a, u[4], x1.x); FMA8(a, u[5], x1.y); FMA8(a, u[6], x1.z); FMA8(a, u[7], x1.w);
        }
#pragma unroll
        for (int o = 4; o <= 8; o <<= 1)
#pragma unroll
          for (int j = 0; j < 8; j++) a[j] += __shfl_xor_sync(~0u, a[j], o);
        if (ph && lane == 0) mbar_arrive(bar + B_FFN);
        const uint32_t red = ph ? sb + SM_GRED : sb + SM_RED + 64;
        if ((lane & 12) == 0) {
          const uint32_t d = red + f * 256 + (lane >> 4) * 128 + (lane & 3) * 32;
          sts128(d, a[0], a[1], a[2], a[3]); sts128(d + 16, a[4], a[5], a[6], a[7]);
        }
        if (f != 2) {
          asm volatile("bar.arrive %0, %1;" ::"r"(4 + ph), "r"(96 + 32 * ph) : "memory");
        } else {
          bar_sync(4 + ph, 96 + 32 * ph);
          const uint32_t ra = red + lane * 4;
          gsum = lds32(ra) + lds32(ra + 256) + lds32(ra + 512);
          usum = lds32(ra + 128) + lds32(ra + 384) + lds32(ra + 640);
          if (!ph) st_rlx(g_cs + 1024 + ch * 2048 + cu * 32 + lane, mark(__float_as_uint(gsum + usum), par));
          else { gsum += lds32(ra + 768); usum += lds32(ra + 896); }
          if (lane == 0) PROF(ph ? 34 : 18);
        }
      }
    }
    if (f == 3) {
      if (elect_one()) {
        PROF(7);
        mbar_wait(bar + B_FULLQ, 0);
#pragma unroll 1
        for (int j = 3; j < 16; j++) {
          mbar_wait(bar + (j < 4 ? B_EMPTYKV + 16 : B_EMPTYQ + 8 * (j & 3)), ((j >> 2) & 1) ^ 1);
          if (j == 12 + (hg & 3)) mbar_wait(bar + B_KVST + 8, 0);
          Q_LOAD(j);
        }
        PROF(47);
        mbar_expect_tx(bar + B_DN, 65536);
#pragma unroll 1
        for (int i = 0; i < 4; i++) {
          mbar_wait(bar + B_EMPTYQ + 8 * i, 1);
          tma3d(sb + i * Q_STAGE, &mD, 0, fb * 32, i * 4, bar + B_DN);
        }
        PROF(48);
#pragma unroll 1
        for (int i = 0; i < 16; i++) {
          const int s = i & 3, n = i < 9 ? i - 2 : i - 9, kb = i < 2 ? 2 * hg + i : 2 * (n + (n >= hg)) + (i >= 9);
          if (i >= 4) mbar_wait(bar + B_EMPTYQ + 8 * s, ((i >> 2) & 1) ^ 1);
          mbar_expect_tx(bar + B_FULLQ + 8 * s, 16384);
          if (i < 2) {
            mbar_arrive2(bar + B_FULLQ + 8 * s);
            tma3d(sb + s * Q_STAGE + 16384, &mWo, 0, kb * 64, hg * 2, bar + B_FULLQ + 8 * s);
          } else {
            tma5d(sb + s * Q_STAGE + 16384, &mWp, hg * 128, kb * 2, bar + B_FULLQ + 8 * s);
            tma5d(sb + s * Q_STAGE + 24576, &mWp, hg * 128 + 64, kb * 2, bar + B_FULLQ + 8 * s);
            if (i >= 3) {
              if (i == 3) { mbar_wait(bar + B_DND, 0); PROF(14); }
#pragma unroll 1
              for (int a = i == 3 ? 2 : i; a <= i; a++) {
                const uint4* src = g_ofr + (mb * 16 + (a == 2 ? (hg == 0 ? 2 : 0) : kb)) * 1024;
#pragma unroll
                for (int h = 0; h < 2; h++) {
                  mbar_expect_tx(bar + B_AIN + (a & 3) * 16 + h * 8, 8192);
                  bulk_load(sb + (a & 3) * Q_STAGE + h * 8192, src + h * 512, 8192, bar + B_AIN + (a & 3) * 16 + h * 8);
                }
              }
            }
          }
        }
      }
    } else {
      if (f == 2) {
        if (PFD && ffn) {
#pragma unroll 1
          for (int i = 0; i < 16; i++) { touch_l2((const char*)P.w_down + fb * 65536 + i * 4096 + lane * 128, lane); __nanosleep(PFD); }
        }
        if (WOT) {
#pragma unroll 1
          for (int i = 0; i < 8; i++) { touch_l2((const char*)P.wo + ((mb & 7) * 128 + i * 16 + (lane >> 1)) * 2048 + hg * 256 + (lane & 1) * 128, lane); __nanosleep(PFD); }
        }
        asm volatile("cp.async.wait_all;" ::: "memory");
        uint4 u;
#pragma unroll 1
        for (int it = 0; it < SPIN_MAX; it++) {
          u = ld_rlx128(g_cs + hg * 128 + lane * 4);
          if (__all_sync(~0u, !(BAD4(u) & 1))) break;
          __nanosleep(200);
        }
        mbar_wait(bar + B_PHI, 0);
        float4 c = make_float4(unmark(u.x), unmark(u.y), unmark(u.z), unmark(u.w));
        CS_STORE(2, c);
        fence_async_smem();
        __syncwarp();
        if (lane == 0) mbar_arrive(bar + B_CSQ);
      }
      const uint32_t target = __shfl_sync(~0u, tag, 0) * 16;
#pragma unroll 1
      for (int R = 0; R < 2; R++) {
        const uint32_t own = (hg * 2 + R) * 16 + mb, pst = sb + (R ? SM_PST1 : SM_PST0);
        if (f == R) {
          mbar_wait(bar + B_KVST + 8 * R, 0);
          if (f == 1 && lane == 0) PROF(11);
          wait_hint(XC1(hg, R) + mb, target);
          if (elect_one()) {
            PROF(35 + R);
            fence_async_global();
            mbar_expect_tx(bar + B_PART + 8 * R, 8192);
            bulk_load(pst, g_part + own * 512, 8192, bar + B_PART + 8 * R);
          }
          __syncwarp();
          uint4 uz;
#pragma unroll 1
          for (int it = 0; it < SPIN_MAX; it++) {
            uz = ld_rlx128(g_zpart + own * 128 + lane * 4);
            if (__all_sync(~0u, !(BAD4(uz) & 1))) break;
          }
          const bool b1 = lane & 2, b2 = lane & 4;
          const float z0 = unmark(b1 ? uz.z : uz.x) + __shfl_xor_sync(~0u, unmark(b1 ? uz.x : uz.z), 2);
          const float z1 = unmark(b1 ? uz.w : uz.y) + __shfl_xor_sync(~0u, unmark(b1 ? uz.y : uz.w), 2);
          float z = (b2 ? z1 : z0) + __shfl_xor_sync(~0u, b2 ? z0 : z1, 4);
          z += __shfl_xor_sync(~0u, z, 8);
          z += __shfl_xor_sync(~0u, z, 16);
          if (lane < 8) st_rlx(g_zres + own * 8 + (lane & 1) * 4 + (lane & 2) + (lane >> 2), mark(__float_as_uint(z), par));
          if (HOP2_HINT && lane == 0) red_inc(XC2(hg, R));
          __syncwarp();
        }
        if (f == R || f == R + 1) {
          const uint32_t hf = f - R, m1 = ~lane & 1, gq = hf * 4 + (lane >> 3), ts = (lane >> 1) & 3;
          float a0 = 0.f, a1 = 0.f, a2 = 0.f, a3 = 0.f;
          mbar_wait(bar + B_PART + 8 * R, 0);
#pragma unroll 1
          for (int it = 0; it < SPIN_MAX; it++) {
            uint32_t bad = 0;
            a0 = a1 = a2 = a3 = 0.f;
#pragma unroll 1
            for (int b = 0; b < 16; b += 8) {
              uint2 u[8];
              if (it == 0) {
#pragma unroll
                for (int i = 0; i < 8; i++) { const float2 v = lds64(pst + (b + i) * 512 + hf * 256 + lane * 8); u[i] = make_uint2(__float_as_uint(v.x), __float_as_uint(v.y)); }
              } else {
#pragma unroll
                for (int i = 0; i < 8; i++) {
                  const unsigned long long v = ld_rlx64((const unsigned long long*)g_part + own * 1024 + (b + i) * 64 + hf * 32 + lane);
                  u[i] = make_uint2((uint32_t)v, (uint32_t)(v >> 32));
                }
              }
#pragma unroll
              for (int i = 0; i < 8; i++) {
                bad |= u[i].x ^ par;
                a0 += bf_lo(i & 1 ? u[i].x & ~m1 : u[i].x | m1); a1 += bf_hi(u[i].x); a2 += bf_lo(u[i].y); a3 += bf_hi(u[i].y);
              }
            }
            if (__all_sync(~0u, !(bad & m1))) break;
          }
          uint32_t* dst = (uint32_t*)g_res[par] + own * 128 + gq * 16 + ts;
          const uint32_t j0 = (lane & 1) * 2, vb = ts == (gq >> 1);
          st_rlx(dst + ((j0 ^ (gq >> 1)) & 3) * 4, pack2(a0, a1) | vb);
          st_rlx(dst + (((j0 + 1) ^ (gq >> 1)) & 3) * 4, pack2(a2, a3) | vb);
          ((uint2*)g_res[par ^ 1])[own * 64 + hf * 32 + lane] = make_uint2(0u, 0u);
          __syncwarp();
          if (lane == 0) { if (HOP2_HINT) red_inc(XC2(hg, R)); if (!hf) PROF(R ? 12 : 30); }
        }
      }
      if (f == 2) {
        if (ffn && !FFN_OFF) {
#pragma unroll 1
          for (int it = 0; it < SPIN_MAX; it++) {
            const uint32_t pg = ld_rlx((const uint32_t*)g_gp + fb * 32 + lane), pu = ld_rlx((const uint32_t*)g_gp + FF + fb * 32 + lane);
            if (__all_sync(~0u, !(((pg ^ par) | (pu ^ par)) & 1))) { gsum += unmark(pg); usum += unmark(pu); break; }
            __nanosleep(200);
          }
        }
        const float h = bf_round(silu_f(bf_round(gsum))) * bf_round(usum);
        const uint32_t h2 = pack2(h, h);
        sts128u(sb + SM_HT + lane * 16, h2, h2, h2, h2);
        fence_async_smem();
        __syncwarp();
        if (lane == 0) { mbar_arrive(bar + B_H); PROF(20); }
      }
      if (f < 2) {
        if (HOP2_HINT) wait_hint(XC2(hg, f), 3 * target);
        mbar_wait(bar + B_KVST + 8, 0);
        if (lane == 0) PROF(40 + f);
#pragma unroll 1
        for (int it = 0; it < SPIN_MAX; it++) {
          if (elect_one()) {
            fence_async_global();
            mbar_expect_tx(bar + B_RES + 8 * f, 8192);
            bulk_load(sb + SM_V + f * 8192, g_res[par] + (hg * 4 + f * 2) * 256, 8192, bar + B_RES + 8 * f);
          }
          __syncwarp();
          const uint4 uz = ld_rlx128(g_zres + (hg * 4 + f * 2) * 64 + lane * 4);
          const uint32_t zw[4] = {uz.x, uz.y, uz.z, uz.w};
#pragma unroll
          for (int j = 0; j < 4; j++) {
            const uint32_t zz = pack2(unmark(zw[j]), 1.f), row = (lane & 3) * 4 + j;
            sts128u(sb + SM_ZT + (2 * f + (lane >> 4)) * 1024 + row * 64 + ((((lane >> 2) ^ (row >> 1)) & 3) << 4), zz, zz, zz, zz);
          }
          uint32_t bad = BAD4(uz);
          mbar_wait(bar + B_RES + 8 * f, it & 1);
#pragma unroll
          for (int i = 0; i < 16; i++) bad |= ~__float_as_uint(lds32(sb + SM_V + f * 8192 + i * 512 + lane * 16 + (lane >> 3) * 4));
          if (__all_sync(~0u, !(bad & 1))) break;
        }
        fence_async_smem();
        __syncwarp();
        if (lane == 0) { mbar_arrive(bar + B_TILE + 8 * f); PROF(f ? 13 : 27); }
      }
      if (f < 2) {
        uint32_t phases = 0;
#pragma unroll 1
        for (int i = 2; i < 16; i++) {
          const int s = i & 3;
          const uint32_t ab = bar + B_AIN + s * 16 + f * 8, slot = sb + s * Q_STAGE + f * 8192;
#pragma unroll 1
          for (int it = 0; it < SPIN_MAX; it++) {
            mbar_wait(ab, (phases >> s) & 1);
            phases ^= 1u << s;
            uint32_t bad = 0;
#pragma unroll
            for (int n = 0; n < (NOVAL ? 0 : 8); n++) bad |= __float_as_uint(lds32(slot + n * 1024 + lane * 32 + (lane >> 2) * 4)) ^ par;
            if (__all_sync(~0u, !(bad & 1))) break;
            if (elect_one()) {
              const int n = i < 9 ? i - 2 : i - 9, kb = 2 * (n + (n >= hg)) + (i >= 9);
              PROF(49);
              mbar_expect_tx(ab, 8192);
              bulk_load(slot, g_ofr + (mb * 16 + kb) * 1024 + f * 512, 8192, ab);
            }
            __syncwarp();
          }
          if (lane == 0) { mbar_arrive(bar + B_FULLQ + 8 * s); if (i == 2 && f == 0) PROF(15); }
        }
        if (f == 0) g_epoch[bid * 32 + lane] = tag;
      } else {
        if (elect_one()) {
          prefetch_map(&mOut);
          if (ffn) { mbar_wait(bar + B_YD, 0); red_rel(g_ycnt); PROF(21); }
        }
        __syncwarp();
        if (f == 2) {
          const uint32_t best = __float_as_uint(lds32(sb + SM_RED + 20));
          const int sel = 2047 - (best & 0x7ff) - mb * 128;
          if (sel >= 0 && sel < 128) {
            const uint2 xr = __ldg((const uint2*)(P.x + (size_t)(mb * 128 + sel) * DM + hg * 128 + lane * 4));
            const float2 st = lds64(sb + SM_STAT + sel * 8);
            const uint32_t ord = best >> 16, rb = (ord & 0x8000u) ? (ord & 0x7fffu) : (~ord & 0xffffu);
            const float sg = rcp(1.f + ex2(-1.4426950408889634f * bf_lo(rb)));
            const uint32_t sg2 = pack2(sg, sg), nm2 = pack2(st.x, st.x);
            wait_cnt<0>(g_ycnt, tag * NFFN);
            float4 y = make_float4(0.f, 0.f, 0.f, 0.f);
#pragma unroll
            for (int i = 0; i < 8; i++) {
              const float4 c = ldg_cg4(g_y[par ^ 1][i] + hg * 128 + lane * 4);
              y.x += c.x; y.y += c.y; y.z += c.z; y.w += c.w;
            }
            uint32_t o[2];
#pragma unroll
            for (int i = 0; i < 2; i++) {
              const uint32_t d = badd2(i ? xr.y : xr.x, nm2);
              const uint32_t tt = badd2(pack2(bf_lo(d) * st.y, bf_hi(d) * st.y), bmul2(i ? pack2(y.z, y.w) : pack2(y.x, y.y), sg2));
              o[i] = pack2(silu_f(bf_lo(tt)), silu_f(bf_hi(tt)));
            }
            sts64u(sb + SM_UPD + lane * 8, o[0], o[1]);
          }
          if (lane == 0) sts32(sb + SM_UPD + 256, __int_as_float(sel));
          __syncwarp();
          if (lane == 0) { mbar_arrive(bar + B_UPD); PROF(22); }
        }
      }
    }
  } else {
    const int t7 = threadIdx.x & 127;
    const char* pfa = warp < 4 ? (const char*)P.x + bid * 32768 + (t7 & 15) * 2048 + (t7 >> 4) * 128
                               : (const char*)P.wqkv + (size_t)((t7 >> 4) * 64 + (bid >> 1)) * 6144 + 2048 + (bid & 1) * 2048 + (t7 & 15) * 128;
    if (t7 >= 16 && t7 < 16 * PF_FIRST) prefetch_l2(pfa);
    if (warp < 7) sts128(sb + SM_CST + threadIdx.x * 16, 0.f, 0.f, 0.f, 0.f);
    else sts32(sb + SM_RED + (threadIdx.x & 15) * 4, threadIdx.x & 8 ? 1.f : 0.f);
    if (elect_one()) {
#pragma unroll 1
      for (uint32_t b = B_FST + warp * 8; b < B_END; b += 64)
        mbar_init(bar + b, b < B_FULLQ ? 1 : b < B_FFN ? 3 : b < B_EMPTYKV ? 4 : 8);
    }
    __syncwarp();
    asm volatile("bar.arrive 13, 384;" ::: "memory");
    asm volatile("setmaxnreg.inc.sync.aligned.u32 %0;" ::"n"(REG_C));
    if (t7 >= 16 * PF_FIRST && threadIdx.x < 128 + 16 * PF_W) prefetch_l2(pfa);
    asm volatile("cp.async.wait_all;" ::: "memory");
    fence_async_smem();
    bar_sync(14, 288);
    if (threadIdx.x == 0) mbar_arrive(bar + B_FULLKV + 16);
    const int lane = lane_id();
    const int wg = warp >> 2, w = warp & 3, g = lane >> 2, t = lane & 3;
    float kv[128];
    {
      uint32_t s = 2, ph = 0, sp = 0, php = 0;
#pragma unroll 1
      for (int j = 0; j < 15; j++) {
        PW0(32 + j); mbar_wait(bar + B_FULLKV + 8 * s, ph); PW1(32 + j);
        if (wg == 1 && (ORDER_ALL || j == 0)) bar_sync(10 + s, 256);
        wg_fence();
        wgmma_n256_ssp_ta0_tb1(kv, mkdesc(sb, 16, 1024, 1, wg * 512 + s * (KV_STAGE / 16)), mkdesc(sb + 16384, 8192, 1024, 1, s * (KV_STAGE / 16)), j);
#pragma unroll
        for (int k = 1; k < 4; k++)
          wgmma_n256_ss_ta0_tb1(kv, mkdesc(sb + k * 32, 16, 1024, 1, wg * 512 + s * (KV_STAGE / 16)),
                                mkdesc(sb + 16384 + k * 2048, 8192, 1024, 1, s * (KV_STAGE / 16)), 1);
        wg_commit();
        if (wg == 0 && (ORDER_ALL || j == 0)) asm volatile("bar.arrive %0, 256;" ::"r"(10 + s) : "memory");
        if (warp == 0 && j) {
          mbar_wait(bar + B_EMPTYKV + 8 * sp, php);
          if (elect_one()) {
            if (j < 14) {
              mbar_expect_tx(bar + B_FULLKV + 8 * sp, KV_STAGE);
              tma2d(sb + sp * KV_STAGE, &mX, (j + 2) * 64, mb * 128, bar + B_FULLKV + 8 * sp);
              tma4d(sb + sp * KV_STAGE + 16384, &mWkv, 0, (j + 2) * 64, hg * 2, 1, bar + B_FULLKV + 8 * sp);
            } else {
              Q_LOAD(0);
            }
            if (j < 3 - XS_EARLY) {
              const int xh = j - 1 + XS_EARLY;
              mbar_expect_tx(bar + B_XST + 8 * xh, 16384);
              tma3d(sb + SM_XST + xh * 16384, &mXs, 0, bid * 16, 2 * xh, bar + B_XST + 8 * xh);
            }
          }
          __syncwarp();
        }
        if (j == 0) {
          if (wg == 0) prefetch_l2(pfa + 1024);
        } else if (wg == 1) {
          if (j < 3) {
            if (j == 2 || t7 >= 16 * PF_W) prefetch_l2(pfa + (j - 1) * (8 * 393216));
          } else if (j == 13) {
            prefetch_l2((const char*)P.wo + bid * 16384 + t7 * 128);
          }
          if (PFG && !FFN_OFF && bid < NFFN && j >= 2 && j < 2 + GROWS / 64 && w < 2)
            touch_l2((const char*)((bid & 1) ? P.w_up : P.w_gate) + (size_t)((0x852a7419630ull >> (4 * j - 8) & 15) * 64 + t7) * 7168 + (bid >> 1) * 128, lane);
        }
        wg_wait<0>();
        if (lane == 0) mbar_arrive(bar + B_EMPTYKV + 8 * s);
        sp = s; php = ph;
        ph ^= s == 1;
        s = s == 2 ? 0 : s + 1;
      }
    }
    const int lrow = wg * 64 + w * 16 + (lane & 15);
    const uint32_t sw128 = lrow * 128, x128 = (lrow & 7), hi16 = lane >> 4;
    mbar_wait(bar + B_CS, 0);
    const uint32_t tag = __float_as_uint(lds32(sb + SM_RED + 16));
    const int zero = __float_as_int(lds32(sb + SM_RED + 12));
    const float wn = lds32(sb + SM_RED + 24);
    const float2 st0 = lds64(sb + SM_STAT + (wg * 64 + w * 16 + g) * 8), st1 = lds64(sb + SM_STAT + (wg * 64 + w * 16 + g + 8) * 8);
    const float c0 = st0.y * 1.4426950408889634f, c1 = st1.y * 1.4426950408889634f;
    const uint32_t nm20 = pack2(st0.x, st0.x), nm21 = pack2(st1.x, st1.x), fmask = t == 0 ? ~0u : t == 1 ? 0xffffu : 0u;
    const uint32_t fa0 = nm20 & fmask, fa1 = nm21 & fmask;
    asm volatile("cp.async.wait_all;" ::: "memory");
    PW0(47); mbar_wait(bar + B_FULLKV + 16, 1); PW1(47);
    wg_fence();
    wgmma_n256_rs_ta0_tb1(kv, fa0, fa1, 0u, 0u, mkdesc(sb + SM_CST, 512, 0, 1), 1);
#pragma unroll
    for (int k = 0; k < 4; k++)
      wgmma_n256_ss_ta0_tb1(kv, mkdesc(sb + 2 * KV_STAGE + k * 32, 16, 1024, 1, wg * 512), mkdesc(sb + 2 * KV_STAGE + 16384 + k * 2048, 8192, 1024, 1), 1);
    wg_commit();
    if (warp == 0) {
      mbar_wait(bar + B_EMPTYKV + 8, 0);
      if (elect_one()) {
#pragma unroll 1
        for (int j = 1; j < 3; j++) Q_LOAD(j);
      }
      __syncwarp();
    }
    wg_wait<0>();
    reg_fence<128>(kv);
    if (lane == 0) mbar_arrive(bar + B_EMPTYKV + 16);
    PROFC(2);
    float q[64];
#define QMMA(J, AOFF16, ACCUM)                                                                                     \
  _Pragma("unroll") for (int k = 0; k < 4; k++)                                                                    \
      wgmma_n128_ss_ta0_tb1(q, mkdesc(sb + k * 32, 16, 1024, 1, wg * 512 + (AOFF16)),                              \
                            mkdesc(sb + 16384 + k * 2048, 8192, 1024, 1, ((J) & 3) * (Q_STAGE / 16)), k ? 1 : (ACCUM))
#define QWAIT(J) do { PW0(J); mbar_wait(bar + B_FULLQ + 8 * ((J) & 3), ((J) >> 2) & 1); PW1(J); } while (0)
#define QSTEP_A(J, AOFF16, ACCUM) do { QWAIT(J); wg_fence(); QMMA(J, AOFF16, ACCUM); wg_commit(); } while (0)
#define QREL(J) do { if (lane == 0) mbar_arrive(bar + B_EMPTYQ + 8 * ((J) & 3)); } while (0)
#define Q_OFF16(J) ((J) >= 8 && (J) < 16 ? Q_AOFF(J) / 16 : ((J) & 3) * (Q_STAGE / 16))
#define QPLAIN(J) do { QSTEP_A(J, Q_OFF16(J), 1); wg_wait<1>(); QREL((J) - 1); } while (0)
#define QNEXT(J) do { QPLAIN(J); SCHED_FENCE(); } while (0)
#define PHI_PROJ(DST, SRC, H0, H1)                                                                                 \
  do {                                                                                                             \
    uint32_t a_[32];                                                                                               \
    _Pragma("unroll") for (int j = 8 * (H0); j < 8 * (H1); j++) {                                                  \
      a_[j] = pack2(SRC[2 * j], SRC[2 * j + 1]);                                                                   \
      asm volatile("fma.rn.bf16x2 %0, %1, %1, %0;" : "+r"(nq[(j >> 4) * 2 + (j & 1)]) : "r"(a_[j]));               \
    }                                                                                                              \
    wg_fence();                                                                                                    \
    _Pragma("unroll") for (int hk = 2 * (H0); hk < 2 * (H1); hk++)                                                 \
        wgmma_n32_rs_ta0_tb1(DST + 16 * (hk >> 1), a_[4 * hk], a_[4 * hk + 1], a_[4 * hk + 2], a_[4 * hk + 3],     \
                             mkdesc(sb + SM_WPHI + hk * 1024, 16, 512, 2), hk & 1);                                \
    wg_commit();                                                                                                   \
  } while (0)
    {
      float p[64], ea[24], eb[24], sa[4], sc[4], kz[20];
      uint32_t vp[32];
#pragma unroll
      for (int j = 0; j < 32; j++) vp[j] = pack2(kv[64 + 2 * j], kv[65 + 2 * j]);
      const uint32_t vr = w * 16 + (lane & 15), vb = sb + SM_V + wg * 4096 + vr * 64, x64 = (vr >> 1) & 3;
#define V_STORE(R)                                                                                           \
  _Pragma("unroll") for (int j = 0; j < 4; j++)                                                              \
      stsm4(vb + (j >> 1) * 8192 + ((((j & 1) * 2 + hi16) ^ x64) << 4), vp[16 * (R) + 4 * j], vp[16 * (R) + 4 * j + 1], vp[16 * (R) + 4 * j + 2], vp[16 * (R) + 4 * j + 3])
      V_STORE(0);
      mbar_wait(bar + B_WPHI, 0);
      {
        uint32_t nq[4] = {0u, 0u, 0u, 0u};
        PHI_PROJ(p, kv, 0, 4);
        QSTEP_A(0, 0, 0);
        const bool unsafe = softmax_unsafe(nq, c0 * c0 * wn, c1 * c1 * wn);
        wg_wait<1>();
        reg_fence<64>(p);
        if (__builtin_expect(unsafe, 0)) softmax_shift(p, c0, c1);
      }
#define K_NORM(S) do { quad_sum<4>(S); _Pragma("unroll") for (int i = 0; i < 4; i++) S[i] = rcp(S[i]) * ((i & 1) ? st1.y : st0.y); } while (0)
#define K_STORE(SLOT, E, S) K_STORE_(SLOT, E, S, 0, 2)
#define K_STORE_(SLOT, E, S, J0, J1)                                                                         \
  _Pragma("unroll") for (int j = (J0); j < (J1); j++) {                                                      \
    uint32_t fp[4], fm[4];                                                                                   \
    _Pragma("unroll") for (int i = 0; i < 4; i++) {                                                          \
      const float e0 = E[8 * j + 2 * i], e1 = E[8 * j + 2 * i + 1], r = E[16 + 4 * j + i] * S[2 + (i & 1)];  \
      const uint32_t e2 = pack2(e0, e1);                                                                     \
      fp[i] = bmul2(e2, pack2(S[i & 1], S[i & 1]));                                                          \
      fm[i] = bmul2(e2, pack2(r, r));                                                                        \
    }                                                                                                        \
    stsm4(sb + SM_PHI + (SLOT) * 16384 + sw128 + (((2 * j + hi16) ^ x128) << 4), fp[0], fp[1], fp[2], fp[3]); \
    stsm4(sb + SM_PHI + (SLOT) * 16384 + sw128 + (((4 + 2 * j + hi16) ^ x128) << 4), fm[0], fm[1], fm[2], fm[3]); \
  }
#define KV_MMA(R)                                                                                            \
  do {                                                                                                       \
    mbar_wait(bar + B_PHI + 8 * (R), 0);                                                                     \
    wg_fence();                                                                                              \
    _Pragma("unroll") for (int k = 0; k < 8; k++) {                                                          \
      const uint32_t vs = SM_V + (k >> 2) * 4096 + (k & 3) * 1024;                                           \
      wgmma_n40_ss_ta1_tb1(kz, mkdesc(sb + SM_PHI + k * 2048, 16, 1024, 1, wg * 1024),                       \
                           mkdesc(sb + vs, SM_SDT + (k & 1) * 1024 + (k >> 1) * 16 - vs, 512, 2, wg * (512u - (512u << 16))), k); \
    }                                                                                                        \
    wg_commit();                                                                                             \
  } while (0)
#define QKV(J, R) do { KV_MMA(R); QSTEP_A(J, Q_OFF16(J), 1); wg_wait<2>(); QREL((J) - 1); SCHED_FENCE(); } while (0)
#define KV_SEND(R)                                                                                           \
  do {                                                                                                       \
    reg_fence<20>(kz);                                                                                       \
    if (lane == 0) mbar_arrive(bar + B_KVST + 8 * (R));                                                      \
    const uint32_t slot = ((hg * 2 + (R)) * 16 + warp * 2) * 16 + mb;                                        \
    _Pragma("unroll") for (int u = 0; u < 2; u++)                                                            \
      st_rlx128(g_part + (slot + u * 16) * 32 + lane, mark(pack2(kz[2 * u], kz[2 * u + 1]), tag & 1), pack2(kz[2 * u + 4], kz[2 * u + 5]), \
                pack2(kz[2 * u + 8], kz[2 * u + 9]), pack2(kz[2 * u + 12], kz[2 * u + 13]));                 \
    if (t < 2) st_rlx(g_zpart + (slot + t * 16) * 8 + g, mark(__float_as_uint(t ? kz[18] : kz[16]), tag & 1)); \
    if (lane < 2) red_inc(XC1(hg, R) + warp * 2 + lane);                                                          \
  } while (0)
#define K_PUB(R) do { fence_async_smem(); __syncwarp(); if (lane == 0) mbar_arrive(bar + B_PHI + 8 * (R)); } while (0)
#define S_PIN(S) SCHED_PIN(S[0] + S[1] + S[2] + S[3])
      k_exp(p, c0, c1, ea, sa);
      S_PIN(sa);
      QNEXT(1);
      K_NORM(sa);
      k_exp<0, 4>(p + 16, c0, c1, eb, sc);
      mbar_wait(bar + B_FFN, 0);
      K_STORE_(0, ea, sa, 0, 1);
      S_PIN(sc);
      QNEXT(2);
      K_STORE_(0, ea, sa, 1, 2);
      k_exp<4, 8>(p + 16, c0, c1, eb, sc);
      K_NORM(sc);
      S_PIN(sc);
      QNEXT(3);
      K_STORE(1, eb, sc);
      K_PUB(0);
      k_exp<0, 4>(p + 32, c0, c1, ea, sa);
      S_PIN(sa);
      QKV(4, 0);
      k_exp<4, 8>(p + 32, c0, c1, ea, sa);
      K_NORM(sa);
      k_exp<0, 4>(p + 48, c0, c1, eb, sc);
      SCHED_PIN(sa[0] + sa[1] + sa[2] + sa[3] + sc[2] + sc[3]);
      QNEXT(5);
      KV_SEND(0);
      k_exp<4, 8>(p + 48, c0, c1, eb, sc);
      S_PIN(sc);
      QNEXT(6);
      K_NORM(sc);
      mbar_wait(bar + B_KVST, 0);
      V_STORE(1);
      K_STORE(0, ea, sa);
      QNEXT(7);
      K_STORE(1, eb, sc);
      K_PUB(1);
      QKV(8, 1);
      QNEXT(9);
      KV_SEND(1);
    }
#define JQ0 10
    PROFC(3);
#pragma unroll 1
    for (int j = JQ0; j < 15; j++) QPLAIN(j);
    mbar_wait(bar + B_CSQ, 0);
    QWAIT(15);
    if (wg == 1) bar_sync(6, 256);
    wg_fence();
    wgmma_n128_rs_ta0_tb1(q, fa0, fa1, 0u, 0u, mkdesc(sb + SM_CST + 2048, 512, 0, 1), 1);
    QMMA(15, Q_AOFF(15) / 16, 1);
    wg_commit();
    if (wg == 0) asm volatile("bar.arrive 6, 256;" ::: "memory");
    wg_wait<1>();
    QREL(14);
    wg_wait<0>();
    QREL(15);
    reg_fence<64>(q);
    PROFC(5);
    float yp[4];
    const uint32_t par = tag & 1;
    uint4* ofr = g_ofr + (mb * 16 + hg * 2) * 1024 + (warp * 16 + g) * 8;
#define O_MMA(H, F, N)                                                                                       \
  do {                                                                                                       \
    wg_fence();                                                                                              \
    _Pragma("unroll") for (int k = 0; k < 4; k++) {                                                          \
      const uint32_t ks = SM_V + (H) * 4096 + k * 1024;                                                      \
      wgmma_n40_rs_ta0_tb1(N + 20 * (k >> 1), F[4 * k], F[4 * k + 1], F[4 * k + 2], F[4 * k + 3],            \
                           mkdesc(sb + ks, SM_ZT + (H) * 1024 + k * 16 - ks, 512, 2), k & 1);                \
    }                                                                                                        \
    wg_commit();                                                                                             \
  } while (0)
#define O_FIN(H, N, o)                                                                                        \
  do {                                                                                                       \
    reg_fence<40>(N);                                                                                        \
    const float *np = N, *nm = N + 20;                                                                       \
    const float d0 = rcp(fmaf(np[16], nm[17], fmaf(nm[16], np[17], 1e-6f * np[17] * nm[17])));               \
    const float d1 = rcp(fmaf(np[18], nm[19], fmaf(nm[18], np[19], 1e-6f * np[19] * nm[19])));               \
    const float bp0 = nm[17] * d0, bm0 = np[17] * d0, bp1 = nm[19] * d1, bm1 = np[19] * d1;                  \
    _Pragma("unroll") for (int j = 0; j < 4; j++) {                                                          \
      o[2 * j] = pack2(fmaf(np[4 * j], bp0, nm[4 * j] * bm0), fmaf(np[4 * j + 1], bp0, nm[4 * j + 1] * bm0)); \
      o[2 * j + 1] = pack2(fmaf(np[4 * j + 2], bp1, nm[4 * j + 2] * bm1), fmaf(np[4 * j + 3], bp1, nm[4 * j + 3] * bm1)); \
    }                                                                                                        \
  } while (0)
#define O_STG(H, o)                                                                                          \
  _Pragma("unroll") for (int u = 0; u < 2; u++) {                                                            \
    uint32_t v_[4];                                                                                          \
    _Pragma("unroll") for (int j = 0; j < 4; j++) v_[j] = lop_select(o[2 * j + u], parm, vword == j);        \
    st_rlx128(ofr + ((H) >> 1) * 1024 + u * 64 + ((((H) & 1) * 4 + t) ^ g), v_[0], v_[1], v_[2], v_[3]);     \
  }
    uint32_t gf[32], ao[16];
    const uint32_t parm = 0u - par, vword = ((t ^ g) & 1) == (g >> 2) ? g & 3 : 4;
    const float rh0 = 0.5f * st0.y, rh1 = 0.5f * st1.y, mh0 = st0.x * rh0, mh1 = st1.x * rh1;
#define GATE_LD(J) ldsm4(sb + ((J) >> 2 ? SM_X1 : SM_X0) + sw128 + (((((J) & 3) * 2 + hi16) ^ x128) << 4), gf[4 * (J)], gf[4 * (J) + 1], gf[4 * (J) + 2], gf[4 * (J) + 3])
#define GATE(I0, I1)                                                                                         \
  _Pragma("unroll") for (int i = (I0); i < (I1); i++) {                                                      \
    const float rs = (i & 1) ? rh1 : rh0, mh = (i & 1) ? mh1 : mh0;                                          \
    const float h0 = fmaf(bf_lo(gf[i]), rs, mh), h1 = fmaf(bf_hi(gf[i]), rs, mh);                            \
    gf[i] = pack2(fmaf(h0, tanh_approx(h0), h0), fmaf(h1, tanh_approx(h1), h1));                             \
  }
#define GATE_PIN(I0, I1) do { uint32_t o_ = 0; _Pragma("unroll") for (int i = (I0); i < (I1); i++) o_ |= gf[i]; SCHED_PIN(__uint_as_float(o_)); } while (0)
    {
      float p[64], na[40], nb[40];
      uint32_t fa[16], fb[16];
      {
        uint32_t nq[4] = {0u, 0u, 0u, 0u};
        PHI_PROJ(p, q, 0, 2);
        SCHED_FENCE();
        PHI_PROJ(p, q, 2, 4);
        const bool unsafe = softmax_unsafe(nq, c0 * c0 * wn, c1 * c1 * wn);
        if (TW == 0) mbar_wait(bar + B_TILE, 0);
        wg_wait<0>();
        reg_fence<64>(p);
        PROFC(24);
        if (__builtin_expect(unsafe, 0)) softmax_shift(p, c0, c1);
      }
      float dn[32];
#define DN_PART(A, B)                                                                                        \
  do {                                                                                                       \
    wg_fence();                                                                                              \
    _Pragma("unroll") for (int i = (A); i < (B); i++)                                                        \
      wgmma_n8_ss_ta1_tb1(dn + 4 * (i >> 1), mkdesc(sb + (i >> 3) * Q_STAGE + (i & 7) * 2048, 16, 1024, 1, wg * (2 * Q_STAGE / 16)), \
                          mkdesc(sb + SM_HT + (i & 1) * 256, 128, 128, 0), i & 1);                           \
  } while (0)
#define F_PIN(F, A, B) do { uint32_t o_ = 0; _Pragma("unroll") for (int i = (A); i < (B); i++) o_ |= F[8 + i]; SCHED_PIN(__uint_as_float(o_)); } while (0)
#define RMMA(J, A, ACCUM)                                                                                    \
  do {                                                                                                       \
    wg_fence();                                                                                              \
    _Pragma("unroll") for (int k = 0; k < 4; k++)                                                            \
      wgmma_n128_rs_ta0_tb1(q, (A)[4 * k], (A)[4 * k + 1], (A)[4 * k + 2], (A)[4 * k + 3],                   \
                            mkdesc(sb + 16384 + k * 2048, 8192, 1024, 1, ((J) & 3) * (Q_STAGE / 16)), k ? 1 : (ACCUM)); \
    wg_commit();                                                                                             \
  } while (0)
#define RSTEP(J, A, ACCUM) do { QWAIT(J); RMMA(J, A, ACCUM); } while (0)
      PROFC(4);
      q_exp(p, c0, c1, fa);
      if (TW == 1) { F_PIN(fa, 0, 8); mbar_wait(bar + B_TILE, 0); }
      if (TW == 2) { q_exp(p + 16, c0, c1, fb); F_PIN(fb, 0, 8); mbar_wait(bar + B_TILE, 0); }
      O_MMA(0, fa, na);
      if (TW != 2) q_exp(p + 16, c0, c1, fb);
      O_MMA(1, fb, nb);
      PROFC(25);
      wg_wait<1>();
      O_FIN(0, na, ao);
      O_STG(0, ao);
      wg_wait<0>();
      O_FIN(1, nb, (ao + 8));
      O_STG(1, (ao + 8));
      PROFC(28);
      mbar_wait(bar + B_H, 0);
      mbar_wait(bar + B_DN, 0);
      PROFC(45);
      DN_PART(0, 16);
      wg_commit();
      wg_wait<0>();
      reg_fence<32>(dn);
#pragma unroll
      for (int i = 0; i < 4; i++) yp[i] = t & 2 ? (t & 1 ? dn[24 + 2 * i] : dn[16 + 2 * i]) : (t & 1 ? dn[8 + 2 * i] : dn[2 * i]);
      RSTEP(16, ao, 0);
      SCHED_FENCE();
      q_exp(p + 32, c0, c1, fa);
      if (DNX == 1) { F_PIN(fa, 0, 8); if (lane == 0) mbar_arrive(bar + B_DND); }
      q_exp(p + 48, c0, c1, fb);
      F_PIN(fb, 0, 8);
      if (DNX == 2 && lane == 0) mbar_arrive(bar + B_DND);
      wg_wait<0>();
      QREL(16);
      PROFC(29);
      mbar_wait(bar + B_TILE + 8, 0);
      PROFC(23);
      if (bid < NFFN) {
        float* y = g_y[par ^ 1][bid & 7] + wg * 512 + t * 128 + w * 16 + g;
#pragma unroll
        for (int i = 0; i < 4; i++) red1(y + (i >> 1) * 64 + (i & 1) * 8, yp[i]);
      }
      SCHED_FENCE();
      O_MMA(2, fa, na);
      O_MMA(3, fb, nb);
      __syncwarp();
      if (lane == 0) mbar_arrive(bar + B_YD);
      wg_wait<1>();
      O_FIN(2, na, ao);
      O_STG(2, ao);
      wg_wait<0>();
      O_FIN(3, nb, (ao + 8));
      O_STG(3, (ao + 8));
      PROFC(6);
    }
    RSTEP(17, ao, 1);
    SCHED_FENCE();
    GATE_LD(0); GATE_LD(1);
    GATE(0, 4);
    GATE_PIN(0, 4);
#define GSTEP(J, I) do { QNEXT(J); if ((I) < 7) GATE_LD(((I) + 1) & 7); GATE(4 * (I), 4 * (I) + 4); GATE_PIN(4 * (I), 4 * (I) + 4); } while (0)
    GSTEP(18, 1); GSTEP(19, 2); GSTEP(20, 3); GSTEP(21, 4); GSTEP(22, 5); GSTEP(23, 6); GSTEP(24, 7);
#pragma unroll 1
    for (int j = 25; j < 32 - TAILN; j++) QPLAIN(j);
    if (wg == 1) bar_sync(6, 256);
#pragma unroll 1
    for (int j = 32 - TAILN; j < 32; j++) QSTEP_A(j, (j & 3) * (Q_STAGE / 16), 1);
    if (wg == 0) asm volatile("bar.arrive 6, 256;" ::: "memory");
    mbar_wait(bar + B_UPD, 0);
    {
      const int sel = __float_as_int(lds32(sb + SM_UPD + 256)) - (wg * 64 + w * 16 + g);
      if (sel == 0 || sel == 8) {
#pragma unroll
        for (int j = 0; j < 16; j++) {
          const uint32_t u = __float_as_uint(lds32(sb + SM_UPD + j * 16 + t * 4));
          if (sel) gf[2 * j + 1] = u; else gf[2 * j] = u;
        }
      }
      __syncwarp();
      uint32_t xf[32];
#pragma unroll
      for (int j = 0; j < 8; j++)
        ldsm4(sb + (j >> 2 ? SM_X1 : SM_X0) + sw128 + ((((j & 3) * 2 + hi16) ^ x128) << 4), xf[4 * j], xf[4 * j + 1], xf[4 * j + 2], xf[4 * j + 3]);
      wg_wait<0>();
      reg_fence<64>(q);
      PROFC(8);
#pragma unroll
      for (int j = 0; j < 8; j++) {
        uint32_t o[4];
#pragma unroll
        for (int i = 0; i < 4; i++) o[i] = badd2(xf[4 * j + i], bmul2(pack2(q[8 * j + 2 * i], q[8 * j + 2 * i + 1]), gf[4 * j + i]));
        stsm4(sb + (j >> 2 ? SM_X1 : SM_X0) + sw128 + ((((j & 3) * 2 + hi16) ^ x128) << 4), o[0], o[1], o[2], o[3]);
      }
    }
    fence_async_smem();
    bar_sync(2 + wg, 128);
    if (w == 0 && elect_one()) {
      tma_store2d(&mOut, sb + SM_X0 + wg * 8192, hg * 128, mb * 128 + wg * 64);
      tma_store2d(&mOut, sb + SM_X1 + wg * 8192, hg * 128 + 64, mb * 128 + wg * 64);
      bulk_commit();
      bulk_wait_read0();
      if (wg == 1) { PROF(9); PROFT(33); PROF_DUMP; }
    }
  }
}

typedef CUresult (*EncodeFn)(CUtensorMap*, CUtensorMapDataType, cuuint32_t, void*, const cuuint64_t*, const cuuint64_t*, const cuuint32_t*,
                             const cuuint32_t*, CUtensorMapInterleave, CUtensorMapSwizzle, CUtensorMapL2promotion, CUtensorMapFloatOOBfill);

CUtensorMap make_map(EncodeFn enc, const void* ptr, int rank, const cuuint64_t* dims, const cuuint64_t* strides, const cuuint32_t* box, CUtensorMapSwizzle sw) {
  CUtensorMap m;
  const cuuint32_t es[5] = {1, 1, 1, 1, 1};
  enc(&m, CU_TENSOR_MAP_DATA_TYPE_BFLOAT16, rank, (void*)ptr, dims, strides, box, es, CU_TENSOR_MAP_INTERLEAVE_NONE, sw,
      CU_TENSOR_MAP_L2_PROMOTION_L2_128B, CU_TENSOR_MAP_FLOAT_OOB_FILL_NONE);
  return m;
}

}

extern "C" void kernel_launch(void* const* d_in, const int* in_sizes, int n_in, void* d_out, int out_size) {
  static EncodeFn enc = nullptr;
  static int by_sm = 0;
  if (!enc) {
    void* fn = nullptr;
    cudaDriverEntryPointQueryResult qr;
    cudaGetDriverEntryPoint("cuTensorMapEncodeTiled", &fn, cudaEnableDefault, &qr);
    enc = (EncodeFn)fn;
    cudaFuncSetAttribute(fused_kernel<false>, cudaFuncAttributeMaxDynamicSharedMemorySize, SM_TOTAL);
    cudaFuncSetAttribute(fused_kernel<true>, cudaFuncAttributeMaxDynamicSharedMemorySize, SM_TOTAL);
    int dev = 0, sms = 0;
    cudaGetDevice(&dev);
    cudaDeviceGetAttribute(&sms, cudaDevAttrMultiProcessorCount, dev);
    by_sm = BY_SM && sms == NCTA + NSPARE;
  }
  Params P;
  P.x = (const __nv_bfloat16*)d_in[0];
  P.wqkv = (const __nv_bfloat16*)d_in[1];
  const void* wphi = d_in[2];
  P.wo = (const __nv_bfloat16*)d_in[3];
  P.w_r = (const __nv_bfloat16*)d_in[5];
  P.w_gate = (const __nv_bfloat16*)d_in[6];
  P.w_up = (const __nv_bfloat16*)d_in[7];
  P.w_down = (const __nv_bfloat16*)d_in[8];

  const cuuint64_t dX[2] = {DM, SEQ}, sX[1] = {DM * 2};
  const cuuint32_t b128[2] = {64, 128}, b64[2] = {64, 64};
  const cuuint64_t dW[4] = {64, DM, 16, 3}, sW[3] = {3 * DM * 2, 128, DM * 2};
  const cuuint32_t bKV[4] = {64, 64, 2, 2}, bQ[4] = {64, 64, 2, 1};
  const cuuint64_t dO[3] = {64, DM, 16}, sO[2] = {DM * 2, 128};
  const cuuint32_t bO[3] = {64, 64, 2};
  const cuuint64_t dP[2] = {32, 1024}, sP[1] = {64};
  const cuuint32_t bP[2] = {32, 128};
  CUtensorMap mX = make_map(enc, P.x, 2, dX, sX, b128, CU_TENSOR_MAP_SWIZZLE_128B);
  CUtensorMap mWkv = make_map(enc, P.wqkv, 4, dW, sW, bKV, CU_TENSOR_MAP_SWIZZLE_128B);
  CUtensorMap mWq = make_map(enc, P.wqkv, 4, dW, sW, bQ, CU_TENSOR_MAP_SWIZZLE_128B);
  CUtensorMap mWo = make_map(enc, P.wo, 3, dO, sO, bO, CU_TENSOR_MAP_SWIZZLE_128B);
  CUtensorMap mPhi = make_map(enc, wphi, 2, dP, sP, bP, CU_TENSOR_MAP_SWIZZLE_64B);
  const cuuint64_t dWp[5] = {DM, 2, 4, 4, DM / 32}, sWp[4] = {DM * 2, 8 * DM * 2, 2 * DM * 2, 32 * DM * 2};
  const cuuint32_t bWp[5] = {64, 2, 4, 4, 2};
  CUtensorMap mWp = make_map(enc, P.wo, 5, dWp, sWp, bWp, CU_TENSOR_MAP_SWIZZLE_128B);
  CUtensorMap mOut = make_map(enc, d_out, 2, dX, sX, b64, CU_TENSOR_MAP_SWIZZLE_128B);
  const cuuint64_t dWc[2] = {3 * DM, DM}, sWc[1] = {3 * DM * 2}, dG[2] = {FF, DM}, sG[1] = {FF * 2}, dD[3] = {64, FF, 16};
  const cuuint32_t b32[2] = {32, 32}, bD[3] = {64, 32, 4};
  CUtensorMap mWc = make_map(enc, P.wqkv, 2, dWc, sWc, b32, CU_TENSOR_MAP_SWIZZLE_NONE);
  CUtensorMap mG = make_map(enc, P.w_gate, 2, dG, sG, b32, CU_TENSOR_MAP_SWIZZLE_NONE);
  CUtensorMap mU = make_map(enc, P.w_up, 2, dG, sG, b32, CU_TENSOR_MAP_SWIZZLE_NONE);
  CUtensorMap mD = make_map(enc, P.w_down, 3, dD, sO, bD, CU_TENSOR_MAP_SWIZZLE_128B);
  const cuuint64_t dXs[3] = {256, SEQ, 4}, sXs[2] = {DM * 2, 512};
  const cuuint32_t bXs[3] = {256, 16, 2};
  CUtensorMap mXs = make_map(enc, P.x, 3, dXs, sXs, bXs, CU_TENSOR_MAP_SWIZZLE_NONE);
  const cuuint64_t dG2[4] = {64, DM, FF / 64, 1}, sG2[3] = {FF * 2, 128, (cuuint64_t)FF * DM * 2};
  CUtensorMap mG2 = make_map(enc, P.w_gate, 4, dG2, sG2, bQ, CU_TENSOR_MAP_SWIZZLE_128B);
  CUtensorMap mU2 = make_map(enc, P.w_up, 4, dG2, sG2, bQ, CU_TENSOR_MAP_SWIZZLE_128B);
  (by_sm ? fused_kernel<true> : fused_kernel<false>)<<<NCTA + NSPARE, 384, SM_TOTAL, cudaStreamPerThread>>>(mX, mWkv, mWq, mWo, mPhi, mWp, mOut, mWc, mG, mU, mD, mXs,
                                                                                                           mG2, mU2, P);
}
```

```cpp
#include <cuda_runtime.h>
#include <cuda_bf16.h>
#include <cuda.h>
#include <stdint.h>

namespace {

constexpr int SEQ = 2048, DM = 1024, FF = 3584;
constexpr int NCTA = 128;
constexpr int NSPARE = 4;
constexpr int NFFN = FF / 32;
#define GN 6
#define G8 2
constexpr int GROWS = (3 * GN + G8) * 32;
#define TAILN 2
#define XS_EARLY 1
#define PF_FIRST 2
#define PF_W 5
#define PFD 80
#define BY_SM 1
#define PTAB 0x73216540u
#define REG_C 224
#define REG_H 56
#define SP_DELAY 2000
#define XSTR 288
#define AM_NS 100
constexpr bool FFN_OFF = false;

static_assert(2 * REG_C + REG_H <= 3 * 168, "the register pool of the CTA is 384 x 168");

__device__ uint32_t g_epoch[(NCTA + NSPARE) * 32];
__device__ unsigned long long g_stat[SEQ];
__device__ __align__(128) unsigned long long g_best[NCTA];
__device__ __align__(16) float g_y[2][8][DM];
__device__ __align__(128) uint32_t g_ycnt[64];
__device__ __align__(1024) uint32_t g_xcnt[32 * XSTR];
#define XC1(HG, R) (g_xcnt + ((HG) * 2 + (R)) * XSTR)
#define XC2(HG, R) (g_xcnt + (16 + (HG) * 2 + (R)) * XSTR)
__device__ __align__(128) uint4 g_res[2][32 * 256];
__device__ __align__(16) float g_cs[5 * DM];
__device__ __align__(128) float g_gp[2 * FF];
__device__ uint4 g_part[8 * 2 * 16 * 16 * 32];
__device__ __align__(16) float g_zpart[8 * 2 * 16 * 16 * 8];
__device__ __align__(128) float g_zres[32 * 64];
__device__ __align__(1024) uint4 g_ofr[16 * 16 * 1024];
#define PROF(i)
#define PROFT(i)
#define PROFC(i)
#define PROF_DUMP
#define PW0(J)
#define PW1(J)

constexpr uint32_t KV_STAGE = 49152, Q_STAGE = 32768;
constexpr uint32_t SM_V = 147456;
constexpr uint32_t SM_PHI = 163840;
constexpr uint32_t SM_XST = 147456;
constexpr uint32_t SM_FST = 172032;
constexpr uint32_t SM_PST0 = 196608, SM_PST1 = SM_PHI + 8192;
constexpr uint32_t SM_X0 = 131072, SM_X1 = SM_PHI + 16384;
constexpr uint32_t SM_WPHI = 204800;
constexpr uint32_t SM_ZT = 212992;
constexpr uint32_t SM_SDT = 217088;
constexpr uint32_t SM_CST = 219136;
constexpr uint32_t SM_HT = 222720;
constexpr uint32_t SM_STAT = 223232;
constexpr uint32_t SM_XSEL = 224256;
constexpr uint32_t SM_RED = 228352;
constexpr uint32_t SM_ROWS = SM_RED + 832;
constexpr uint32_t SM_GRED = SM_XSEL + 3072;
static_assert(GROWS <= 768, "xsel area");
constexpr uint32_t SM_UPD = 229632;
constexpr uint32_t SM_BAR = 230016;
constexpr uint32_t SM_PROF = 230464;
constexpr uint32_t SM_SINK = 231104;
constexpr uint32_t SM_TOTAL = 231616;
constexpr uint32_t SB = 1024;
constexpr uint32_t B_FULLKV = 0  , B_FST = 24  , B_XST = 104  , B_WPHI = 120, B_CS = 128, B_CSQ = 136, B_UPD = 144,
                   B_H = 152, B_DN = 160, B_XS = 168, B_TILE = 176  , B_RES = 192  , B_PART = 208  , B_AIN = 224  ,
                   B_FULLQ = 288  ,
                   B_FFN = 320,
                   B_EMPTYKV = 328  , B_EMPTYQ = 352  , B_KVST = 384  , B_YD = 400, B_PHI = 408  , B_DND = 424, B_END = 432;

__device__ __forceinline__ uint32_t smem_u32(const void* p) { return (uint32_t)__cvta_generic_to_shared(p); }
__device__ __forceinline__ void mbar_init(uint32_t bar, uint32_t cnt) { asm volatile("mbarrier.init.shared::cta.b64 [%0], %1;" ::"r"(bar), "r"(cnt) : "memory"); }
__device__ __forceinline__ void mbar_expect_tx(uint32_t bar, uint32_t bytes) { asm volatile("mbarrier.arrive.expect_tx.shared::cta.b64 _, [%0], %1;" ::"r"(bar), "r"(bytes) : "memory"); }
__device__ __forceinline__ void mbar_arrive2(uint32_t bar) { asm volatile("mbarrier.arrive.shared::cta.b64 _, [%0], 2;" ::"r"(bar) : "memory"); }
__device__ __forceinline__ void mbar_arrive(uint32_t bar) { asm volatile("mbarrier.arrive.shared::cta.b64 _, [%0];" ::"r"(bar) : "memory"); }
__device__ __forceinline__ void mbar_wait(uint32_t bar, uint32_t parity) {
  asm volatile("{\n.reg .pred p;\nLW:\nmbarrier.try_wait.parity.shared::cta.b64 p, [%0], %1;\n@!p bra LW;\n}" ::"r"(bar), "r"(parity) : "memory");
}
__device__ __forceinline__ bool mbar_test(uint32_t bar, uint32_t parity) {
  uint32_t ok;
  asm volatile("{\n.reg .pred p;\nmbarrier.test_wait.parity.shared::cta.b64 p, [%1], %2;\nselp.u32 %0, 1, 0, p;\n}" : "=r"(ok) : "r"(bar), "r"(parity) : "memory");
  return ok;
}
__device__ __forceinline__ int lane_id() { int l; asm volatile("mov.u32 %0, %%laneid;" : "=r"(l)); return l; }
template <int C> __device__ __forceinline__ void sched_fence_(int zero) {
  asm volatile("{\n.reg .pred p;\nsetp.eq.s32 p, %0, %1;\n@p trap;\n}" ::"r"(zero), "n"(C) : "memory");
}
#define SCHED_FENCE() sched_fence_<1000 + __COUNTER__>(zero)
#define SCHED_PIN(V) sched_fence_<1000 + __COUNTER__>(zero & __float_as_int(V))
__device__ __forceinline__ bool elect_one() {
  uint32_t p; asm volatile("{ .reg .pred P; elect.sync _|P, 0xffffffff; selp.u32 %0, 1, 0, P; }" : "=r"(p)); return p;
}
__device__ __forceinline__ void tma2d(uint32_t dst, const CUtensorMap* m, int x, int y, uint32_t bar) {
  asm volatile("cp.async.bulk.tensor.2d.shared::cluster.global.mbarrier::complete_tx::bytes [%0], [%1, {%3, %4}], [%2];" ::"r"(dst), "l"(m), "r"(bar), "r"(x), "r"(y) : "memory");
}
__device__ __forceinline__ void tma3d(uint32_t dst, const CUtensorMap* m, int x, int y, int z, uint32_t bar) {
  asm volatile("cp.async.bulk.tensor.3d.shared::cluster.global.mbarrier::complete_tx::bytes [%0], [%1, {%3, %4, %5}], [%2];" ::"r"(dst), "l"(m), "r"(bar), "r"(x), "r"(y), "r"(z) : "memory");
}
__device__ __forceinline__ void tma4d(uint32_t dst, const CUtensorMap* m, int x, int y, int z, int w, uint32_t bar) {
  asm volatile("cp.async.bulk.tensor.4d.shared::cluster.global.mbarrier::complete_tx::bytes [%0], [%1, {%3, %4, %5, %6}], [%2];" ::"r"(dst), "l"(m), "r"(bar), "r"(x), "r"(y), "r"(z), "r"(w) : "memory");
}
__device__ __forceinline__ void tma5d(uint32_t dst, const CUtensorMap* m, int x, int v, uint32_t bar) {
  asm volatile("cp.async.bulk.tensor.5d.shared::cluster.global.mbarrier::complete_tx::bytes [%0], [%1, {%3, %5, %5, %5, %4}], [%2];" ::"r"(dst), "l"(m), "r"(bar), "r"(x), "r"(v), "r"(0) : "memory");
}
__device__ __forceinline__ void tma_store2d(const CUtensorMap* m, uint32_t src, int x, int y) {
  asm volatile("cp.async.bulk.tensor.2d.global.shared::cta.bulk_group [%0, {%2, %3}], [%1];" ::"l"(m), "r"(src), "r"(x), "r"(y) : "memory");
}
__device__ __forceinline__ void bulk_load(uint32_t dst, const void* src, uint32_t bytes, uint32_t bar) {
  asm volatile("cp.async.bulk.shared::cluster.global.mbarrier::complete_tx::bytes [%0], [%1], %2, [%3];" ::"r"(dst), "l"(src), "r"(bytes), "r"(bar) : "memory");
}
__device__ __forceinline__ void bulk_commit() { asm volatile("cp.async.bulk.commit_group;" ::: "memory"); }
__device__ __forceinline__ void bulk_wait_read0() { asm volatile("cp.async.bulk.wait_group.read 0;" ::: "memory"); }
__device__ __forceinline__ void prefetch_l2(const void* p) { asm volatile("prefetch.global.L2 [%0];" ::"l"(p) : "memory"); }
__device__ __forceinline__ void touch_l2(const void* p, int lane) { asm volatile("cp.async.cg.shared.global.L2::128B [%0], [%1], 16;" ::"r"(SB + SM_SINK + lane * 16), "l"(p) : "memory"); }
__device__ __forceinline__ void cp_async16(uint32_t dst, const void* src) { asm volatile("cp.async.cg.shared.global [%0], [%1], 16;" ::"r"(dst), "l"(src) : "memory"); }
__device__ __forceinline__ void prefetch_map(const CUtensorMap* m) { asm volatile("prefetch.tensormap [%0];" ::"l"(m) : "memory"); }
__device__ __forceinline__ void fence_async_smem() { asm volatile("fence.proxy.async.shared::cta;" ::: "memory"); }
__device__ __forceinline__ void fence_async_global() { asm volatile("fence.proxy.async.global;" ::: "memory"); }
__device__ __forceinline__ void bar_sync(int id, int n) { asm volatile("bar.sync %0, %1;" ::"r"(id), "r"(n) : "memory"); }
__device__ __forceinline__ void wg_fence() { asm volatile("wgmma.fence.sync.aligned;" ::: "memory"); }
__device__ __forceinline__ void wg_commit() { asm volatile("wgmma.commit_group.sync.aligned;" ::: "memory"); }
template <int N> __device__ __forceinline__ void wg_wait() { asm volatile("wgmma.wait_group.sync.aligned %0;" ::"n"(N) : "memory"); }
template <int N> __device__ __forceinline__ void reg_fence(uint32_t* r) {
#pragma unroll
  for (int i = 0; i < N; i++) asm volatile("" : "+r"(r[i])::"memory");
}
template <int N> __device__ __forceinline__ void reg_fence(float* r) {
#pragma unroll
  for (int i = 0; i < N; i++) asm volatile("" : "+f"(r[i])::"memory");
}
__device__ __forceinline__ uint64_t mkdesc(uint32_t addr, uint32_t lbo, uint32_t sbo, uint32_t swz, uint32_t dyn = 0) {
  const uint32_t lo = ((addr >> 4) | ((lbo >> 4) << 16)) + dyn;
  const uint32_t hi = (sbo >> 4) | (swz << 30);
  uint64_t d;
  asm("mov.b64 %0, {%1, %2};" : "=l"(d) : "r"(lo), "r"(hi));
  return d;
}
__device__ __forceinline__ void stsm4(uint32_t addr, uint32_t a, uint32_t b, uint32_t c, uint32_t d) {
  asm volatile("stmatrix.sync.aligned.m8n8.x4.shared.b16 [%0], {%1, %2, %3, %4};" ::"r"(addr), "r"(a), "r"(b), "r"(c), "r"(d) : "memory");
}
__device__ __forceinline__ void ldsm4(uint32_t addr, uint32_t& a, uint32_t& b, uint32_t& c, uint32_t& d) {
  asm volatile("ldmatrix.sync.aligned.m8n8.x4.shared.b16 {%0, %1, %2, %3}, [%4];" : "=r"(a), "=r"(b), "=r"(c), "=r"(d) : "r"(addr) : "memory");
}
__device__ __forceinline__ uint32_t pack2(float lo, float hi) { uint32_t r; asm("cvt.rn.bf16x2.f32 %0, %1, %2;" : "=r"(r) : "f"(hi), "f"(lo)); return r; }
__device__ __forceinline__ uint32_t bsub2(uint32_t a, uint32_t b) { uint32_t r; asm("sub.rn.bf16x2 %0, %1, %2;" : "=r"(r) : "r"(a), "r"(b)); return r; }
__device__ __forceinline__ uint32_t badd2(uint32_t a, uint32_t b) { uint32_t r; asm("add.rn.bf16x2 %0, %1, %2;" : "=r"(r) : "r"(a), "r"(b)); return r; }
__device__ __forceinline__ uint32_t bmul2(uint32_t a, uint32_t b) { uint32_t r; asm("mul.rn.bf16x2 %0, %1, %2;" : "=r"(r) : "r"(a), "r"(b)); return r; }
__device__ __forceinline__ float bf_lo(uint32_t v) { return __uint_as_float(v << 16); }
__device__ __forceinline__ float bf_hi(uint32_t v) { return __uint_as_float(v & 0xffff0000u); }
__device__ __forceinline__ float bf_round(float v) { return bf_lo(pack2(v, 0.f)); }
__device__ __forceinline__ float ex2(float v) { float r; asm("ex2.approx.ftz.f32 %0, %1;" : "=f"(r) : "f"(v)); return r; }
__device__ __forceinline__ float rcp(float v) { float r; asm("rcp.approx.ftz.f32 %0, %1;" : "=f"(r) : "f"(v)); return r; }
__device__ __forceinline__ float sqrt_approx(float v) { float r; asm("sqrt.approx.f32 %0, %1;" : "=f"(r) : "f"(v)); return r; }
__device__ __forceinline__ float4 lds128(uint32_t a) { float4 v; asm volatile("ld.shared.v4.f32 {%0, %1, %2, %3}, [%4];" : "=f"(v.x), "=f"(v.y), "=f"(v.z), "=f"(v.w) : "r"(a) : "memory"); return v; }
__device__ __forceinline__ uint4 lds128u(uint32_t a) { uint4 v; asm volatile("ld.shared.v4.u32 {%0, %1, %2, %3}, [%4];" : "=r"(v.x), "=r"(v.y), "=r"(v.z), "=r"(v.w) : "r"(a) : "memory"); return v; }
__device__ __forceinline__ float2 lds64(uint32_t a) { float2 v; asm volatile("ld.shared.v2.f32 {%0, %1}, [%2];" : "=f"(v.x), "=f"(v.y) : "r"(a) : "memory"); return v; }
__device__ __forceinline__ float lds32(uint32_t a) { float v; asm volatile("ld.shared.f32 %0, [%1];" : "=f"(v) : "r"(a) : "memory"); return v; }
__device__ __forceinline__ void sts32(uint32_t a, float v) { asm volatile("st.shared.f32 [%0], %1;" ::"r"(a), "f"(v) : "memory"); }
__device__ __forceinline__ void sts64(uint32_t a, float x, float y) { asm volatile("st.shared.v2.f32 [%0], {%1, %2};" ::"r"(a), "f"(x), "f"(y) : "memory"); }
__device__ __forceinline__ void sts128(uint32_t a, float x, float y, float z, float w) { asm volatile("st.shared.v4.f32 [%0], {%1, %2, %3, %4};" ::"r"(a), "f"(x), "f"(y), "f"(z), "f"(w) : "memory"); }
__device__ __forceinline__ void sts64u(uint32_t a, uint32_t x, uint32_t y) { asm volatile("st.shared.v2.u32 [%0], {%1, %2};" ::"r"(a), "r"(x), "r"(y) : "memory"); }
__device__ __forceinline__ void sts128u(uint32_t a, uint32_t x, uint32_t y, uint32_t z, uint32_t w) { asm volatile("st.shared.v4.u32 [%0], {%1, %2, %3, %4};" ::"r"(a), "r"(x), "r"(y), "r"(z), "r"(w) : "memory"); }
__device__ __forceinline__ uint4 ldg_nc(const void* p) { uint4 v; asm volatile("ld.global.nc.L1::no_allocate.v4.u32 {%0, %1, %2, %3}, [%4];" : "=r"(v.x), "=r"(v.y), "=r"(v.z), "=r"(v.w) : "l"(p)); return v; }
__device__ __forceinline__ float4 ldg_cg4(const float* p) { float4 v; asm volatile("ld.global.cg.v4.f32 {%0, %1, %2, %3}, [%4];" : "=f"(v.x), "=f"(v.y), "=f"(v.z), "=f"(v.w) : "l"(p) : "memory"); return v; }
__device__ __forceinline__ uint32_t ld_acq(const uint32_t* p) { uint32_t v; asm volatile("ld.acquire.gpu.global.u32 %0, [%1];" : "=r"(v) : "l"(p) : "memory"); return v; }
__device__ __forceinline__ unsigned long long ld_rlx64(const unsigned long long* p) { unsigned long long v; asm volatile("ld.relaxed.gpu.global.u64 %0, [%1];" : "=l"(v) : "l"(p) : "memory"); return v; }
__device__ __forceinline__ void st_rlx64(unsigned long long* p, unsigned long long v) { asm volatile("st.relaxed.gpu.global.u64 [%0], %1;" ::"l"(p), "l"(v) : "memory"); }
__device__ __forceinline__ uint4 ld_rlx128(const void* p) {
  uint4 v;
  asm volatile("{ .reg .b128 t; .reg .b64 a, b; ld.relaxed.gpu.global.b128 t, [%4]; mov.b128 {a, b}, t; mov.b64 {%0, %1}, a; mov.b64 {%2, %3}, b; }"
               : "=r"(v.x), "=r"(v.y), "=r"(v.z), "=r"(v.w) : "l"(p) : "memory");
  return v;
}
__device__ __forceinline__ void st_rlx128(void* p, uint32_t x, uint32_t y, uint32_t z, uint32_t w) {
  asm volatile("{ .reg .b128 t; .reg .b64 a, b; mov.b64 a, {%1, %2}; mov.b64 b, {%3, %4}; mov.b128 t, {a, b}; st.relaxed.gpu.global.b128 [%0], t; }"
               ::"l"(p), "r"(x), "r"(y), "r"(z), "r"(w) : "memory");
}
__device__ __forceinline__ void st_rlx(void* p, uint32_t v) { asm volatile("st.relaxed.gpu.global.u32 [%0], %1;" ::"l"(p), "r"(v) : "memory"); }
__device__ __forceinline__ uint32_t lop_select(uint32_t a, uint32_t b, uint32_t m) { uint32_t r; asm("lop3.b32 %0, %1, %2, %3, 0xd8;" : "=r"(r) : "r"(a), "r"(b), "r"(m)); return r; }
__device__ __forceinline__ float unmark(uint32_t v) { return __uint_as_float(v & ~1u); }
__device__ __forceinline__ uint32_t mark(uint32_t v, uint32_t par) { return (v & ~1u) | par; }
__device__ __forceinline__ float tanh_approx(float v) { float r; asm("tanh.approx.f32 %0, %1;" : "=f"(r) : "f"(v)); return r; }
__device__ __forceinline__ void red1(float* p, float a) { asm volatile("red.global.add.f32 [%0], %1;" ::"l"(p), "f"(a) : "memory"); }
__device__ __forceinline__ void red_inc(uint32_t* p) { asm volatile("red.relaxed.gpu.global.add.u32 [%0], 1;" ::"l"(p) : "memory"); }
__device__ __forceinline__ void red_rel(uint32_t* p) { asm volatile("red.release.gpu.global.add.u32 [%0], 1;" ::"l"(p) : "memory"); }
constexpr int SPIN_MAX = 100000;
__device__ __forceinline__ uint32_t ld_rlx(const uint32_t* p) { uint32_t v; asm volatile("ld.relaxed.gpu.global.u32 %0, [%1];" : "=r"(v) : "l"(p) : "memory"); return v; }
template <int NS = 0> __device__ __forceinline__ void wait_hint(const uint32_t* p, uint32_t target) {
#pragma unroll 1
  for (int i = 0; i < SPIN_MAX; i++) { if ((int)(ld_rlx(p) - target) >= 0) break; if (NS) __nanosleep(NS); }
}
template <int NS> __device__ __forceinline__ void wait_cnt(const uint32_t* p, uint32_t target) {
#pragma unroll 1
  for (int i = 0; i < SPIN_MAX; i++) { if ((int)(ld_rlx(p) - target) >= 0) break; if (NS) __nanosleep(NS); }
  (void)ld_acq(p);
}
template <int NS> __device__ __forceinline__ unsigned long long wait_tag(const unsigned long long* p, uint32_t tag) {
  unsigned long long v = 0;
#pragma unroll 1
  for (int i = 0; i < SPIN_MAX; i++) { v = ld_rlx64(p); if ((uint32_t)(v >> 32) == tag) break; if (NS) __nanosleep(NS); }
  return v;
}
__device__ __forceinline__ float silu_f(float v) { return v * rcp(1.f + ex2(-1.4426950408889634f * v)); }

__device__ __forceinline__ void wgmma_n8_ss_ta1_tb0(float* d, uint64_t da, uint64_t db, bool accumulate) {
  if (accumulate) {
    asm volatile("{\n.reg .pred p;\nsetp.ne.b32 p, 1, 0;\n"
      "wgmma.mma_async.sync.aligned.m64n8k16.f32.bf16.bf16 "
      "{%0, %1, %2, %3}, "
      "%4, %5, p, 1, 1, 1, 0;\n}\n"
      : "+f"(d[0]), "+f"(d[1]), "+f"(d[2]), "+f"(d[3])
      : "l"(da), "l"(db));
  } else {
    asm volatile("{\n.reg .pred p;\nsetp.ne.b32 p, 0, 0;\n"
      "wgmma.mma_async.sync.aligned.m64n8k16.f32.bf16.bf16 "
      "{%0, %1, %2, %3}, "
      "%4, %5, p, 1, 1, 1, 0;\n}\n"
      : "=f"(d[0]), "=f"(d[1]), "=f"(d[2]), "=f"(d[3])
      : "l"(da), "l"(db));
  }
}
__device__ __forceinline__ void wgmma_n8_ss_ta1_tb1(float* d, uint64_t da, uint64_t db, bool accumulate) {
  if (accumulate) {
    asm volatile("{\n.reg .pred p;\nsetp.ne.b32 p, 1, 0;\n"
      "wgmma.mma_async.sync.aligned.m64n8k16.f32.bf16.bf16 "
      "{%0, %1, %2, %3}, "
      "%4, %5, p, 1, 1, 1, 1;\n}\n"
      : "+f"(d[0]), "+f"(d[1]), "+f"(d[2]), "+f"(d[3])
      : "l"(da), "l"(db));
  } else {
    asm volatile("{\n.reg .pred p;\nsetp.ne.b32 p, 0, 0;\n"
      "wgmma.mma_async.sync.aligned.m64n8k16.f32.bf16.bf16 "
      "{%0, %1, %2, %3}, "
      "%4, %5, p, 1, 1, 1, 1;\n}\n"
      : "=f"(d[0]), "=f"(d[1]), "=f"(d[2]), "=f"(d[3])
      : "l"(da), "l"(db));
  }
}
__device__ __forceinline__ void wgmma_n32_rs_ta0_tb1(float* d, uint32_t a0, uint32_t a1, uint32_t a2, uint32_t a3, uint64_t db, bool accumulate) {
  if (accumulate) {
    asm volatile("{\n.reg .pred p;\nsetp.ne.b32 p, 1, 0;\n"
      "wgmma.mma_async.sync.aligned.m64n32k16.f32.bf16.bf16 "
      "{%0, %1, %2, %3, %4, %5, %6, %7, %8, %9, %10, %11, %12, %13, %14, %15}, "
      "{%16, %17, %18, %19}, %20, p, 1, 1, 1;\n}\n"
      : "+f"(d[0]), "+f"(d[1]), "+f"(d[2]), "+f"(d[3]), "+f"(d[4]), "+f"(d[5]), "+f"(d[6]), "+f"(d[7]), "+f"(d[8]), "+f"(d[9]), "+f"(d[10]), "+f"(d[11]), "+f"(d[12]), "+f"(d[13]), "+f"(d[14]), "+f"(d[15])
      : "r"(a0), "r"(a1), "r"(a2), "r"(a3), "l"(db));
  } else {
    asm volatile("{\n.reg .pred p;\nsetp.ne.b32 p, 0, 0;\n"
      "wgmma.mma_async.sync.aligned.m64n32k16.f32.bf16.bf16 "
      "{%0, %1, %2, %3, %4, %5, %6, %7, %8, %9, %10, %11, %12, %13, %14, %15}, "
      "{%16, %17, %18, %19}, %20, p, 1, 1, 1;\n}\n"
      : "=f"(d[0]), "=f"(d[1]), "=f"(d[2]), "=f"(d[3]), "=f"(d[4]), "=f"(d[5]), "=f"(d[6]), "=f"(d[7]), "=f"(d[8]), "=f"(d[9]), "=f"(d[10]), "=f"(d[11]), "=f"(d[12]), "=f"(d[13]), "=f"(d[14]), "=f"(d[15])
      : "r"(a0), "r"(a1), "r"(a2), "r"(a3), "l"(db));
  }
}
__device__ __forceinline__ void wgmma_n40_rs_ta0_tb1(float* d, uint32_t a0, uint32_t a1, uint32_t a2, uint32_t a3, uint64_t db, bool accumulate) {
  if (accumulate) {
    asm volatile("{\n.reg .pred p;\nsetp.ne.b32 p, 1, 0;\n"
      "wgmma.mma_async.sync.aligned.m64n40k16.f32.bf16.bf16 "
      "{%0, %1, %2, %3, %4, %5, %6, %7, %8, %9, %10, %11, %12, %13, %14, %15, %16, %17, %18, %19}, "
      "{%20, %21, %22, %23}, %24, p, 1, 1, 1;\n}\n"
      : "+f"(d[0]), "+f"(d[1]), "+f"(d[2]), "+f"(d[3]), "+f"(d[4]), "+f"(d[5]), "+f"(d[6]), "+f"(d[7]), "+f"(d[8]), "+f"(d[9]), "+f"(d[10]), "+f"(d[11]), "+f"(d[12]), "+f"(d[13]), "+f"(d[14]), "+f"(d[15]), "+f"(d[16]), "+f"(d[17]), "+f"(d[18]), "+f"(d[19])
      : "r"(a0), "r"(a1), "r"(a2), "r"(a3), "l"(db));
  } else {
    asm volatile("{\n.reg .pred p;\nsetp.ne.b32 p, 0, 0;\n"
      "wgmma.mma_async.sync.aligned.m64n40k16.f32.bf16.bf16 "
      "{%0, %1, %2, %3, %4, %5, %6, %7, %8, %9, %10, %11, %12, %13, %14, %15, %16, %17, %18, %19}, "
      "{%20, %21, %22, %23}, %24, p, 1, 1, 1;\n}\n"
      : "=f"(d[0]), "=f"(d[1]), "=f"(d[2]), "=f"(d[3]), "=f"(d[4]), "=f"(d[5]), "=f"(d[6]), "=f"(d[7]), "=f"(d[8]), "=f"(d[9]), "=f"(d[10]), "=f"(d[11]), "=f"(d[12]), "=f"(d[13]), "=f"(d[14]), "=f"(d[15]), "=f"(d[16]), "=f"(d[17]), "=f"(d[18]), "=f"(d[19])
      : "r"(a0), "r"(a1), "r"(a2), "r"(a3), "l"(db));
  }
}
__device__ __forceinline__ void wgmma_n40_ss_ta1_tb1(float* d, uint64_t da, uint64_t db, bool accumulate) {
  if (accumulate) {
    asm volatile("{\n.reg .pred p;\nsetp.ne.b32 p, 1, 0;\n"
      "wgmma.mma_async.sync.aligned.m64n40k16.f32.bf16.bf16 "
      "{%0, %1, %2, %3, %4, %5, %6, %7, %8, %9, %10, %11, %12, %13, %14, %15, %16, %17, %18, %19}, "
      "%20, %21, p, 1, 1, 1, 1;\n}\n"
      : "+f"(d[0]), "+f"(d[1]), "+f"(d[2]), "+f"(d[3]), "+f"(d[4]), "+f"(d[5]), "+f"(d[6]), "+f"(d[7]), "+f"(d[8]), "+f"(d[9]), "+f"(d[10]), "+f"(d[11]), "+f"(d[12]), "+f"(d[13]), "+f"(d[14]), "+f"(d[15]), "+f"(d[16]), "+f"(d[17]), "+f"(d[18]), "+f"(d[19])
      : "l"(da), "l"(db));
  } else {
    asm volatile("{\n.reg .pred p;\nsetp.ne.b32 p, 0, 0;\n"
      "wgmma.mma_async.sync.aligned.m64n40k16.f32.bf16.bf16 "
      "{%0, %1, %2, %3, %4, %5, %6, %7, %8, %9, %10, %11, %12, %13, %14, %15, %16, %17, %18, %19}, "
      "%20, %21, p, 1, 1, 1, 1;\n}\n"
      : "=f"(d[0]), "=f"(d[1]), "=f"(d[2]), "=f"(d[3]), "=f"(d[4]), "=f"(d[5]), "=f"(d[6]), "=f"(d[7]), "=f"(d[8]), "=f"(d[9]), "=f"(d[10]), "=f"(d[11]), "=f"(d[12]), "=f"(d[13]), "=f"(d[14]), "=f"(d[15]), "=f"(d[16]), "=f"(d[17]), "=f"(d[18]), "=f"(d[19])
      : "l"(da), "l"(db));
  }
}
__device__ __forceinline__ void wgmma_n128_rs_ta0_tb1(float* d, uint32_t a0, uint32_t a1, uint32_t a2, uint32_t a3, uint64_t db, bool accumulate) {
  if (accumulate) {
    asm volatile("{\n.reg .pred p;\nsetp.ne.b32 p, 1, 0;\n"
      "wgmma.mma_async.sync.aligned.m64n128k16.f32.bf16.bf16 "
      "{%0, %1, %2, %3, %4, %5, %6, %7, %8, %9, %10, %11, %12, %13, %14, %15, %16, %17, %18, %19, %20, %21, %22, %23, %24, %25, %26, %27, %28, %29, %30, %31, %32, %33, %34, %35, %36, %37, %38, %39, %40, %41, %42, %43, %44, %45, %46, %47, %48, %49, %50, %51, %52, %53, %54, %55, %56, %57, %58, %59, %60, %61, %62, %63}, "
      "{%64, %65, %66, %67}, %68, p, 1, 1, 1;\n}\n"
      : "+f"(d[0]), "+f"(d[1]), "+f"(d[2]), "+f"(d[3]), "+f"(d[4]), "+f"(d[5]), "+f"(d[6]), "+f"(d[7]), "+f"(d[8]), "+f"(d[9]), "+f"(d[10]), "+f"(d[11]), "+f"(d[12]), "+f"(d[13]), "+f"(d[14]), "+f"(d[15]), "+f"(d[16]), "+f"(d[17]), "+f"(d[18]), "+f"(d[19]), "+f"(d[20]), "+f"(d[21]), "+f"(d[22]), "+f"(d[23]), "+f"(d[24]), "+f"(d[25]), "+f"(d[26]), "+f"(d[27]), "+f"(d[28]), "+f"(d[29]), "+f"(d[30]), "+f"(d[31]), "+f"(d[32]), "+f"(d[33]), "+f"(d[34]), "+f"(d[35]), "+f"(d[36]), "+f"(d[37]), "+f"(d[38]), "+f"(d[39]), "+f"(d[40]), "+f"(d[41]), "+f"(d[42]), "+f"(d[43]), "+f"(d[44]), "+f"(d[45]), "+f"(d[46]), "+f"(d[47]), "+f"(d[48]), "+f"(d[49]), "+f"(d[50]), "+f"(d[51]), "+f"(d[52]), "+f"(d[53]), "+f"(d[54]), "+f"(d[55]), "+f"(d[56]), "+f"(d[57]), "+f"(d[58]), "+f"(d[59]), "+f"(d[60]), "+f"(d[61]), "+f"(d[62]), "+f"(d[63])
      : "r"(a0), "r"(a1), "r"(a2), "r"(a3), "l"(db));
  } else {
    asm volatile("{\n.reg .pred p;\nsetp.ne.b32 p, 0, 0;\n"
      "wgmma.mma_async.sync.aligned.m64n128k16.f32.bf16.bf16 "
      "{%0, %1, %2, %3, %4, %5, %6, %7, %8, %9, %10, %11, %12, %13, %14, %15, %16, %17, %18, %19, %20, %21, %22, %23, %24, %25, %26, %27, %28, %29, %30, %31, %32, %33, %34, %35, %36, %37, %38, %39, %40, %41, %42, %43, %44, %45, %46, %47, %48, %49, %50, %51, %52, %53, %54, %55, %56, %57, %58, %59, %60, %61, %62, %63}, "
      "{%64, %65, %66, %67}, %68, p, 1, 1, 1;\n}\n"
      : "=f"(d[0]), "=f"(d[1]), "=f"(d[2]), "=f"(d[3]), "=f"(d[4]), "=f"(d[5]), "=f"(d[6]), "=f"(d[7]), "=f"(d[8]), "=f"(d[9]), "=f"(d[10]), "=f"(d[11]), "=f"(d[12]), "=f"(d[13]), "=f"(d[14]), "=f"(d[15]), "=f"(d[16]), "=f"(d[17]), "=f"(d[18]), "=f"(d[19]), "=f"(d[20]), "=f"(d[21]), "=f"(d[22]), "=f"(d[23]), "=f"(d[24]), "=f"(d[25]), "=f"(d[26]), "=f"(d[27]), "=f"(d[28]), "=f"(d[29]), "=f"(d[30]), "=f"(d[31]), "=f"(d[32]), "=f"(d[33]), "=f"(d[34]), "=f"(d[35]), "=f"(d[36]), "=f"(d[37]), "=f"(d[38]), "=f"(d[39]), "=f"(d[40]), "=f"(d[41]), "=f"(d[42]), "=f"(d[43]), "=f"(d[44]), "=f"(d[45]), "=f"(d[46]), "=f"(d[47]), "=f"(d[48]), "=f"(d[49]), "=f"(d[50]), "=f"(d[51]), "=f"(d[52]), "=f"(d[53]), "=f"(d[54]), "=f"(d[55]), "=f"(d[56]), "=f"(d[57]), "=f"(d[58]), "=f"(d[59]), "=f"(d[60]), "=f"(d[61]), "=f"(d[62]), "=f"(d[63])
      : "r"(a0), "r"(a1), "r"(a2), "r"(a3), "l"(db));
  }
}
__device__ __forceinline__ void wgmma_n128_ss_ta0_tb1(float* d, uint64_t da, uint64_t db, bool accumulate) {
  if (accumulate) {
    asm volatile("{\n.reg .pred p;\nsetp.ne.b32 p, 1, 0;\n"
      "wgmma.mma_async.sync.aligned.m64n128k16.f32.bf16.bf16 "
      "{%0, %1, %2, %3, %4, %5, %6, %7, %8, %9, %10, %11, %12, %13, %14, %15, %16, %17, %18, %19, %20, %21, %22, %23, %24, %25, %26, %27, %28, %29, %30, %31, %32, %33, %34, %35, %36, %37, %38, %39, %40, %41, %42, %43, %44, %45, %46, %47, %48, %49, %50, %51, %52, %53, %54, %55, %56, %57, %58, %59, %60, %61, %62, %63}, "
      "%64, %65, p, 1, 1, 0, 1;\n}\n"
      : "+f"(d[0]), "+f"(d[1]), "+f"(d[2]), "+f"(d[3]), "+f"(d[4]), "+f"(d[5]), "+f"(d[6]), "+f"(d[7]), "+f"(d[8]), "+f"(d[9]), "+f"(d[10]), "+f"(d[11]), "+f"(d[12]), "+f"(d[13]), "+f"(d[14]), "+f"(d[15]), "+f"(d[16]), "+f"(d[17]), "+f"(d[18]), "+f"(d[19]), "+f"(d[20]), "+f"(d[21]), "+f"(d[22]), "+f"(d[23]), "+f"(d[24]), "+f"(d[25]), "+f"(d[26]), "+f"(d[27]), "+f"(d[28]), "+f"(d[29]), "+f"(d[30]), "+f"(d[31]), "+f"(d[32]), "+f"(d[33]), "+f"(d[34]), "+f"(d[35]), "+f"(d[36]), "+f"(d[37]), "+f"(d[38]), "+f"(d[39]), "+f"(d[40]), "+f"(d[41]), "+f"(d[42]), "+f"(d[43]), "+f"(d[44]), "+f"(d[45]), "+f"(d[46]), "+f"(d[47]), "+f"(d[48]), "+f"(d[49]), "+f"(d[50]), "+f"(d[51]), "+f"(d[52]), "+f"(d[53]), "+f"(d[54]), "+f"(d[55]), "+f"(d[56]), "+f"(d[57]), "+f"(d[58]), "+f"(d[59]), "+f"(d[60]), "+f"(d[61]), "+f"(d[62]), "+f"(d[63])
      : "l"(da), "l"(db));
  } else {
    asm volatile("{\n.reg .pred p;\nsetp.ne.b32 p, 0, 0;\n"
      "wgmma.mma_async.sync.aligned.m64n128k16.f32.bf16.bf16 "
      "{%0, %1, %2, %3, %4, %5, %6, %7, %8, %9, %10, %11, %12, %13, %14, %15, %16, %17, %18, %19, %20, %21, %22, %23, %24, %25, %26, %27, %28, %29, %30, %31, %32, %33, %34, %35, %36, %37, %38, %39, %40, %41, %42, %43, %44, %45, %46, %47, %48, %49, %50, %51, %52, %53, %54, %55, %56, %57, %58, %59, %60, %61, %62, %63}, "
      "%64, %65, p, 1, 1, 0, 1;\n}\n"
      : "=f"(d[0]), "=f"(d[1]), "=f"(d[2]), "=f"(d[3]), "=f"(d[4]), "=f"(d[5]), "=f"(d[6]), "=f"(d[7]), "=f"(d[8]), "=f"(d[9]), "=f"(d[10]), "=f"(d[11]), "=f"(d[12]), "=f"(d[13]), "=f"(d[14]), "=f"(d[15]), "=f"(d[16]), "=f"(d[17]), "=f"(d[18]), "=f"(d[19]), "=f"(d[20]), "=f"(d[21]), "=f"(d[22]), "=f"(d[23]), "=f"(d[24]), "=f"(d[25]), "=f"(d[26]), "=f"(d[27]), "=f"(d[28]), "=f"(d[29]), "=f"(d[30]), "=f"(d[31]), "=f"(d[32]), "=f"(d[33]), "=f"(d[34]), "=f"(d[35]), "=f"(d[36]), "=f"(d[37]), "=f"(d[38]), "=f"(d[39]), "=f"(d[40]), "=f"(d[41]), "=f"(d[42]), "=f"(d[43]), "=f"(d[44]), "=f"(d[45]), "=f"(d[46]), "=f"(d[47]), "=f"(d[48]), "=f"(d[49]), "=f"(d[50]), "=f"(d[51]), "=f"(d[52]), "=f"(d[53]), "=f"(d[54]), "=f"(d[55]), "=f"(d[56]), "=f"(d[57]), "=f"(d[58]), "=f"(d[59]), "=f"(d[60]), "=f"(d[61]), "=f"(d[62]), "=f"(d[63])
      : "l"(da), "l"(db));
  }
}
__device__ __forceinline__ void wgmma_n256_rs_ta0_tb1(float* d, uint32_t a0, uint32_t a1, uint32_t a2, uint32_t a3, uint64_t db, bool accumulate) {
  if (accumulate) {
    asm volatile("{\n.reg .pred p;\nsetp.ne.b32 p, 1, 0;\n"
      "wgmma.mma_async.sync.aligned.m64n256k16.f32.bf16.bf16 "
      "{%0, %1, %2, %3, %4, %5, %6, %7, %8, %9, %10, %11, %12, %13, %14, %15, %16, %17, %18, %19, %20, %21, %22, %23, %24, %25, %26, %27, %28, %29, %30, %31, %32, %33, %34, %35, %36, %37, %38, %39, %40, %41, %42, %43, %44, %45, %46, %47, %48, %49, %50, %51, %52, %53, %54, %55, %56, %57, %58, %59, %60, %61, %62, %63, %64, %65, %66, %67, %68, %69, %70, %71, %72, %73, %74, %75, %76, %77, %78, %79, %80, %81, %82, %83, %84, %85, %86, %87, %88, %89, %90, %91, %92, %93, %94, %95, %96, %97, %98, %99, %100, %101, %102, %103, %104, %105, %106, %107, %108, %109, %110, %111, %112, %113, %114, %115, %116, %117, %118, %119, %120, %121, %122, %123, %124, %125, %126, %127}, "
      "{%128, %129, %130, %131}, %132, p, 1, 1, 1;\n}\n"
      : "+f"(d[0]), "+f"(d[1]), "+f"(d[2]), "+f"(d[3]), "+f"(d[4]), "+f"(d[5]), "+f"(d[6]), "+f"(d[7]), "+f"(d[8]), "+f"(d[9]), "+f"(d[10]), "+f"(d[11]), "+f"(d[12]), "+f"(d[13]), "+f"(d[14]), "+f"(d[15]), "+f"(d[16]), "+f"(d[17]), "+f"(d[18]), "+f"(d[19]), "+f"(d[20]), "+f"(d[21]), "+f"(d[22]), "+f"(d[23]), "+f"(d[24]), "+f"(d[25]), "+f"(d[26]), "+f"(d[27]), "+f"(d[28]), "+f"(d[29]), "+f"(d[30]), "+f"(d[31]), "+f"(d[32]), "+f"(d[33]), "+f"(d[34]), "+f"(d[35]), "+f"(d[36]), "+f"(d[37]), "+f"(d[38]), "+f"(d[39]), "+f"(d[40]), "+f"(d[41]), "+f"(d[42]), "+f"(d[43]), "+f"(d[44]), "+f"(d[45]), "+f"(d[46]), "+f"(d[47]), "+f"(d[48]), "+f"(d[49]), "+f"(d[50]), "+f"(d[51]), "+f"(d[52]), "+f"(d[53]), "+f"(d[54]), "+f"(d[55]), "+f"(d[56]), "+f"(d[57]), "+f"(d[58]), "+f"(d[59]), "+f"(d[60]), "+f"(d[61]), "+f"(d[62]), "+f"(d[63]), "+f"(d[64]), "+f"(d[65]), "+f"(d[66]), "+f"(d[67]), "+f"(d[68]), "+f"(d[69]), "+f"(d[70]), "+f"(d[71]), "+f"(d[72]), "+f"(d[73]), "+f"(d[74]), "+f"(d[75]), "+f"(d[76]), "+f"(d[77]), "+f"(d[78]), "+f"(d[79]), "+f"(d[80]), "+f"(d[81]), "+f"(d[82]), "+f"(d[83]), "+f"(d[84]), "+f"(d[85]), "+f"(d[86]), "+f"(d[87]), "+f"(d[88]), "+f"(d[89]), "+f"(d[90]), "+f"(d[91]), "+f"(d[92]), "+f"(d[93]), "+f"(d[94]), "+f"(d[95]), "+f"(d[96]), "+f"(d[97]), "+f"(d[98]), "+f"(d[99]), "+f"(d[100]), "+f"(d[101]), "+f"(d[102]), "+f"(d[103]), "+f"(d[104]), "+f"(d[105]), "+f"(d[106]), "+f"(d[107]), "+f"(d[108]), "+f"(d[109]), "+f"(d[110]), "+f"(d[111]), "+f"(d[112]), "+f"(d[113]), "+f"(d[114]), "+f"(d[115]), "+f"(d[116]), "+f"(d[117]), "+f"(d[118]), "+f"(d[119]), "+f"(d[120]), "+f"(d[121]), "+f"(d[122]), "+f"(d[123]), "+f"(d[124]), "+f"(d[125]), "+f"(d[126]), "+f"(d[127])
      : "r"(a0), "r"(a1), "r"(a2), "r"(a3), "l"(db));
  } else {
    asm volatile("{\n.reg .pred p;\nsetp.ne.b32 p, 0, 0;\n"
      "wgmma.mma_async.sync.aligned.m64n256k16.f32.bf16.bf16 "
      "{%0, %1, %2, %3, %4, %5, %6, %7, %8, %9, %10, %11, %12, %13, %14, %15, %16, %17, %18, %19, %20, %21, %22, %23, %24, %25, %26, %27, %28, %29, %30, %31, %32, %33, %34, %35, %36, %37, %38, %39, %40, %41, %42, %43, %44, %45, %46, %47, %48, %49, %50, %51, %52, %53, %54, %55, %56, %57, %58, %59, %60, %61, %62, %63, %64, %65, %66, %67, %68, %69, %70, %71, %72, %73, %74, %75, %76, %77, %78, %79, %80, %81, %82, %83, %84, %85, %86, %87, %88, %89, %90, %91, %92, %93, %94, %95, %96, %97, %98, %99, %100, %101, %102, %103, %104, %105, %106, %107, %108, %109, %110, %111, %112, %113, %114, %115, %116, %117, %118, %119, %120, %121, %122, %123, %124, %125, %126, %127}, "
      "{%128, %129, %130, %131}, %132, p, 1, 1, 1;\n}\n"
      : "=f"(d[0]), "=f"(d[1]), "=f"(d[2]), "=f"(d[3]), "=f"(d[4]), "=f"(d[5]), "=f"(d[6]), "=f"(d[7]), "=f"(d[8]), "=f"(d[9]), "=f"(d[10]), "=f"(d[11]), "=f"(d[12]), "=f"(d[13]), "=f"(d[14]), "=f"(d[15]), "=f"(d[16]), "=f"(d[17]), "=f"(d[18]), "=f"(d[19]), "=f"(d[20]), "=f"(d[21]), "=f"(d[22]), "=f"(d[23]), "=f"(d[24]), "=f"(d[25]), "=f"(d[26]), "=f"(d[27]), "=f"(d[28]), "=f"(d[29]), "=f"(d[30]), "=f"(d[31]), "=f"(d[32]), "=f"(d[33]), "=f"(d[34]), "=f"(d[35]), "=f"(d[36]), "=f"(d[37]), "=f"(d[38]), "=f"(d[39]), "=f"(d[40]), "=f"(d[41]), "=f"(d[42]), "=f"(d[43]), "=f"(d[44]), "=f"(d[45]), "=f"(d[46]), "=f"(d[47]), "=f"(d[48]), "=f"(d[49]), "=f"(d[50]), "=f"(d[51]), "=f"(d[52]), "=f"(d[53]), "=f"(d[54]), "=f"(d[55]), "=f"(d[56]), "=f"(d[57]), "=f"(d[58]), "=f"(d[59]), "=f"(d[60]), "=f"(d[61]), "=f"(d[62]), "=f"(d[63]), "=f"(d[64]), "=f"(d[65]), "=f"(d[66]), "=f"(d[67]), "=f"(d[68]), "=f"(d[69]), "=f"(d[70]), "=f"(d[71]), "=f"(d[72]), "=f"(d[73]), "=f"(d[74]), "=f"(d[75]), "=f"(d[76]), "=f"(d[77]), "=f"(d[78]), "=f"(d[79]), "=f"(d[80]), "=f"(d[81]), "=f"(d[82]), "=f"(d[83]), "=f"(d[84]), "=f"(d[85]), "=f"(d[86]), "=f"(d[87]), "=f"(d[88]), "=f"(d[89]), "=f"(d[90]), "=f"(d[91]), "=f"(d[92]), "=f"(d[93]), "=f"(d[94]), "=f"(d[95]), "=f"(d[96]), "=f"(d[97]), "=f"(d[98]), "=f"(d[99]), "=f"(d[100]), "=f"(d[101]), "=f"(d[102]), "=f"(d[103]), "=f"(d[104]), "=f"(d[105]), "=f"(d[106]), "=f"(d[107]), "=f"(d[108]), "=f"(d[109]), "=f"(d[110]), "=f"(d[111]), "=f"(d[112]), "=f"(d[113]), "=f"(d[114]), "=f"(d[115]), "=f"(d[116]), "=f"(d[117]), "=f"(d[118]), "=f"(d[119]), "=f"(d[120]), "=f"(d[121]), "=f"(d[122]), "=f"(d[123]), "=f"(d[124]), "=f"(d[125]), "=f"(d[126]), "=f"(d[127])
      : "r"(a0), "r"(a1), "r"(a2), "r"(a3), "l"(db));
  }
}
__device__ __forceinline__ void wgmma_n256_ss_ta0_tb1(float* d, uint64_t da, uint64_t db, bool accumulate) {
  if (accumulate) {
    asm volatile("{\n.reg .pred p;\nsetp.ne.b32 p, 1, 0;\n"
      "wgmma.mma_async.sync.aligned.m64n256k16.f32.bf16.bf16 "
      "{%0, %1, %2, %3, %4, %5, %6, %7, %8, %9, %10, %11, %12, %13, %14, %15, %16, %17, %18, %19, %20, %21, %22, %23, %24, %25, %26, %27, %28, %29, %30, %31, %32, %33, %34, %35, %36, %37, %38, %39, %40, %41, %42, %43, %44, %45, %46, %47, %48, %49, %50, %51, %52, %53, %54, %55, %56, %57, %58, %59, %60, %61, %62, %63, %64, %65, %66, %67, %68, %69, %70, %71, %72, %73, %74, %75, %76, %77, %78, %79, %80, %81, %82, %83, %84, %85, %86, %87, %88, %89, %90, %91, %92, %93, %94, %95, %96, %97, %98, %99, %100, %101, %102, %103, %104, %105, %106, %107, %108, %109, %110, %111, %112, %113, %114, %115, %116, %117, %118, %119, %120, %121, %122, %123, %124, %125, %126, %127}, "
      "%128, %129, p, 1, 1, 0, 1;\n}\n"
      : "+f"(d[0]), "+f"(d[1]), "+f"(d[2]), "+f"(d[3]), "+f"(d[4]), "+f"(d[5]), "+f"(d[6]), "+f"(d[7]), "+f"(d[8]), "+f"(d[9]), "+f"(d[10]), "+f"(d[11]), "+f"(d[12]), "+f"(d[13]), "+f"(d[14]), "+f"(d[15]), "+f"(d[16]), "+f"(d[17]), "+f"(d[18]), "+f"(d[19]), "+f"(d[20]), "+f"(d[21]), "+f"(d[22]), "+f"(d[23]), "+f"(d[24]), "+f"(d[25]), "+f"(d[26]), "+f"(d[27]), "+f"(d[28]), "+f"(d[29]), "+f"(d[30]), "+f"(d[31]), "+f"(d[32]), "+f"(d[33]), "+f"(d[34]), "+f"(d[35]), "+f"(d[36]), "+f"(d[37]), "+f"(d[38]), "+f"(d[39]), "+f"(d[40]), "+f"(d[41]), "+f"(d[42]), "+f"(d[43]), "+f"(d[44]), "+f"(d[45]), "+f"(d[46]), "+f"(d[47]), "+f"(d[48]), "+f"(d[49]), "+f"(d[50]), "+f"(d[51]), "+f"(d[52]), "+f"(d[53]), "+f"(d[54]), "+f"(d[55]), "+f"(d[56]), "+f"(d[57]), "+f"(d[58]), "+f"(d[59]), "+f"(d[60]), "+f"(d[61]), "+f"(d[62]), "+f"(d[63]), "+f"(d[64]), "+f"(d[65]), "+f"(d[66]), "+f"(d[67]), "+f"(d[68]), "+f"(d[69]), "+f"(d[70]), "+f"(d[71]), "+f"(d[72]), "+f"(d[73]), "+f"(d[74]), "+f"(d[75]), "+f"(d[76]), "+f"(d[77]), "+f"(d[78]), "+f"(d[79]), "+f"(d[80]), "+f"(d[81]), "+f"(d[82]), "+f"(d[83]), "+f"(d[84]), "+f"(d[85]), "+f"(d[86]), "+f"(d[87]), "+f"(d[88]), "+f"(d[89]), "+f"(d[90]), "+f"(d[91]), "+f"(d[92]), "+f"(d[93]), "+f"(d[94]), "+f"(d[95]), "+f"(d[96]), "+f"(d[97]), "+f"(d[98]), "+f"(d[99]), "+f"(d[100]), "+f"(d[101]), "+f"(d[102]), "+f"(d[103]), "+f"(d[104]), "+f"(d[105]), "+f"(d[106]), "+f"(d[107]), "+f"(d[108]), "+f"(d[109]), "+f"(d[110]), "+f"(d[111]), "+f"(d[112]), "+f"(d[113]), "+f"(d[114]), "+f"(d[115]), "+f"(d[116]), "+f"(d[117]), "+f"(d[118]), "+f"(d[119]), "+f"(d[120]), "+f"(d[121]), "+f"(d[122]), "+f"(d[123]), "+f"(d[124]), "+f"(d[125]), "+f"(d[126]), "+f"(d[127])
      : "l"(da), "l"(db));
  } else {
    asm volatile("{\n.reg .pred p;\nsetp.ne.b32 p, 0, 0;\n"
      "wgmma.mma_async.sync.aligned.m64n256k16.f32.bf16.bf16 "
      "{%0, %1, %2, %3, %4, %5, %6, %7, %8, %9, %10, %11, %12, %13, %14, %15, %16, %17, %18, %19, %20, %21, %22, %23, %24, %25, %26, %27, %28, %29, %30, %31, %32, %33, %34, %35, %36, %37, %38, %39, %40, %41, %42, %43, %44, %45, %46, %47, %48, %49, %50, %51, %52, %53, %54, %55, %56, %57, %58, %59, %60, %61, %62, %63, %64, %65, %66, %67, %68, %69, %70, %71, %72, %73, %74, %75, %76, %77, %78, %79, %80, %81, %82, %83, %84, %85, %86, %87, %88, %89, %90, %91, %92, %93, %94, %95, %96, %97, %98, %99, %100, %101, %102, %103, %104, %105, %106, %107, %108, %109, %110, %111, %112, %113, %114, %115, %116, %117, %118, %119, %120, %121, %122, %123, %124, %125, %126, %127}, "
      "%128, %129, p, 1, 1, 0, 1;\n}\n"
      : "=f"(d[0]), "=f"(d[1]), "=f"(d[2]), "=f"(d[3]), "=f"(d[4]), "=f"(d[5]), "=f"(d[6]), "=f"(d[7]), "=f"(d[8]), "=f"(d[9]), "=f"(d[10]), "=f"(d[11]), "=f"(d[12]), "=f"(d[13]), "=f"(d[14]), "=f"(d[15]), "=f"(d[16]), "=f"(d[17]), "=f"(d[18]), "=f"(d[19]), "=f"(d[20]), "=f"(d[21]), "=f"(d[22]), "=f"(d[23]), "=f"(d[24]), "=f"(d[25]), "=f"(d[26]), "=f"(d[27]), "=f"(d[28]), "=f"(d[29]), "=f"(d[30]), "=f"(d[31]), "=f"(d[32]), "=f"(d[33]), "=f"(d[34]), "=f"(d[35]), "=f"(d[36]), "=f"(d[37]), "=f"(d[38]), "=f"(d[39]), "=f"(d[40]), "=f"(d[41]), "=f"(d[42]), "=f"(d[43]), "=f"(d[44]), "=f"(d[45]), "=f"(d[46]), "=f"(d[47]), "=f"(d[48]), "=f"(d[49]), "=f"(d[50]), "=f"(d[51]), "=f"(d[52]), "=f"(d[53]), "=f"(d[54]), "=f"(d[55]), "=f"(d[56]), "=f"(d[57]), "=f"(d[58]), "=f"(d[59]), "=f"(d[60]), "=f"(d[61]), "=f"(d[62]), "=f"(d[63]), "=f"(d[64]), "=f"(d[65]), "=f"(d[66]), "=f"(d[67]), "=f"(d[68]), "=f"(d[69]), "=f"(d[70]), "=f"(d[71]), "=f"(d[72]), "=f"(d[73]), "=f"(d[74]), "=f"(d[75]), "=f"(d[76]), "=f"(d[77]), "=f"(d[78]), "=f"(d[79]), "=f"(d[80]), "=f"(d[81]), "=f"(d[82]), "=f"(d[83]), "=f"(d[84]), "=f"(d[85]), "=f"(d[86]), "=f"(d[87]), "=f"(d[88]), "=f"(d[89]), "=f"(d[90]), "=f"(d[91]), "=f"(d[92]), "=f"(d[93]), "=f"(d[94]), "=f"(d[95]), "=f"(d[96]), "=f"(d[97]), "=f"(d[98]), "=f"(d[99]), "=f"(d[100]), "=f"(d[101]), "=f"(d[102]), "=f"(d[103]), "=f"(d[104]), "=f"(d[105]), "=f"(d[106]), "=f"(d[107]), "=f"(d[108]), "=f"(d[109]), "=f"(d[110]), "=f"(d[111]), "=f"(d[112]), "=f"(d[113]), "=f"(d[114]), "=f"(d[115]), "=f"(d[116]), "=f"(d[117]), "=f"(d[118]), "=f"(d[119]), "=f"(d[120]), "=f"(d[121]), "=f"(d[122]), "=f"(d[123]), "=f"(d[124]), "=f"(d[125]), "=f"(d[126]), "=f"(d[127])
      : "l"(da), "l"(db));
  }
}
__device__ __forceinline__ void wgmma_n256_ssp_ta0_tb1(float* d, uint64_t da, uint64_t db, int accumulate) {
    asm volatile("{\n.reg .pred p;\nsetp.ne.b32 p, %130, 0;\n"
      "wgmma.mma_async.sync.aligned.m64n256k16.f32.bf16.bf16 "
      "{%0, %1, %2, %3, %4, %5, %6, %7, %8, %9, %10, %11, %12, %13, %14, %15, %16, %17, %18, %19, %20, %21, %22, %23, %24, %25, %26, %27, %28, %29, %30, %31, %32, %33, %34, %35, %36, %37, %38, %39, %40, %41, %42, %43, %44, %45, %46, %47, %48, %49, %50, %51, %52, %53, %54, %55, %56, %57, %58, %59, %60, %61, %62, %63, %64, %65, %66, %67, %68, %69, %70, %71, %72, %73, %74, %75, %76, %77, %78, %79, %80, %81, %82, %83, %84, %85, %86, %87, %88, %89, %90, %91, %92, %93, %94, %95, %96, %97, %98, %99, %100, %101, %102, %103, %104, %105, %106, %107, %108, %109, %110, %111, %112, %113, %114, %115, %116, %117, %118, %119, %120, %121, %122, %123, %124, %125, %126, %127}, "
      "%128, %129, p, 1, 1, 0, 1;\n}\n"
      : "+f"(d[0]), "+f"(d[1]), "+f"(d[2]), "+f"(d[3]), "+f"(d[4]), "+f"(d[5]), "+f"(d[6]), "+f"(d[7]), "+f"(d[8]), "+f"(d[9]), "+f"(d[10]), "+f"(d[11]), "+f"(d[12]), "+f"(d[13]), "+f"(d[14]), "+f"(d[15]), "+f"(d[16]), "+f"(d[17]), "+f"(d[18]), "+f"(d[19]), "+f"(d[20]), "+f"(d[21]), "+f"(d[22]), "+f"(d[23]), "+f"(d[24]), "+f"(d[25]), "+f"(d[26]), "+f"(d[27]), "+f"(d[28]), "+f"(d[29]), "+f"(d[30]), "+f"(d[31]), "+f"(d[32]), "+f"(d[33]), "+f"(d[34]), "+f"(d[35]), "+f"(d[36]), "+f"(d[37]), "+f"(d[38]), "+f"(d[39]), "+f"(d[40]), "+f"(d[41]), "+f"(d[42]), "+f"(d[43]), "+f"(d[44]), "+f"(d[45]), "+f"(d[46]), "+f"(d[47]), "+f"(d[48]), "+f"(d[49]), "+f"(d[50]), "+f"(d[51]), "+f"(d[52]), "+f"(d[53]), "+f"(d[54]), "+f"(d[55]), "+f"(d[56]), "+f"(d[57]), "+f"(d[58]), "+f"(d[59]), "+f"(d[60]), "+f"(d[61]), "+f"(d[62]), "+f"(d[63]), "+f"(d[64]), "+f"(d[65]), "+f"(d[66]), "+f"(d[67]), "+f"(d[68]), "+f"(d[69]), "+f"(d[70]), "+f"(d[71]), "+f"(d[72]), "+f"(d[73]), "+f"(d[74]), "+f"(d[75]), "+f"(d[76]), "+f"(d[77]), "+f"(d[78]), "+f"(d[79]), "+f"(d[80]), "+f"(d[81]), "+f"(d[82]), "+f"(d[83]), "+f"(d[84]), "+f"(d[85]), "+f"(d[86]), "+f"(d[87]), "+f"(d[88]), "+f"(d[89]), "+f"(d[90]), "+f"(d[91]), "+f"(d[92]), "+f"(d[93]), "+f"(d[94]), "+f"(d[95]), "+f"(d[96]), "+f"(d[97]), "+f"(d[98]), "+f"(d[99]), "+f"(d[100]), "+f"(d[101]), "+f"(d[102]), "+f"(d[103]), "+f"(d[104]), "+f"(d[105]), "+f"(d[106]), "+f"(d[107]), "+f"(d[108]), "+f"(d[109]), "+f"(d[110]), "+f"(d[111]), "+f"(d[112]), "+f"(d[113]), "+f"(d[114]), "+f"(d[115]), "+f"(d[116]), "+f"(d[117]), "+f"(d[118]), "+f"(d[119]), "+f"(d[120]), "+f"(d[121]), "+f"(d[122]), "+f"(d[123]), "+f"(d[124]), "+f"(d[125]), "+f"(d[126]), "+f"(d[127])
      : "l"(da), "l"(db), "r"(accumulate));
}

template <int N> __device__ __forceinline__ void quad_sum(float* m) {
#pragma unroll
  for (int o = 1; o <= 2; o <<= 1) {
    float t[N];
#pragma unroll
    for (int i = 0; i < N; i++) t[i] = __shfl_xor_sync(~0u, m[i], o);
#pragma unroll
    for (int i = 0; i < N; i++) m[i] += t[i];
  }
}
__device__ __forceinline__ bool softmax_unsafe(const uint32_t* t, float l0, float l1) {
  const float m0 = fmaxf(bf_lo(t[0]) + bf_hi(t[0]), bf_lo(t[2]) + bf_hi(t[2])), m1 = fmaxf(bf_lo(t[1]) + bf_hi(t[1]), bf_lo(t[3]) + bf_hi(t[3]));
  return __any_sync(~0u, !(m0 * l0 < 2500.f) | !(m1 * l1 < 2500.f));
}
__device__ __forceinline__ void softmax_shift(float* p, float c0, float c1) {
#pragma unroll 1
  for (int it = 0; it < 8; it++) {
    float mx = p[0], mn = p[0];
#pragma unroll
    for (int j = 1; j < 8; j++) { mx = fmaxf(mx, p[(j >> 1) * 4 + (j & 1)]); mn = fminf(mn, p[(j >> 1) * 4 + (j & 1)]); }
#pragma unroll
    for (int o = 1; o <= 2; o <<= 1) { mx = fmaxf(mx, __shfl_xor_sync(~0u, mx, o)); mn = fminf(mn, __shfl_xor_sync(~0u, mn, o)); }
    const float half = fminf(0.5f * (mx - mn), 50.f * rcp(it & 1 ? c1 : c0));
    float r[8];
#pragma unroll
    for (int j = 0; j < 8; j++) {
      const float v = p[(j >> 1) * 4 + (j & 1)];
      r[j] = fmaxf(v - mx + half, 0.f) + fminf(v - mn - half, 0.f) + (v - v);
    }
#pragma unroll
    for (int k = 0; k < 7; k++)
#pragma unroll
      for (int j = 0; j < 8; j++) p[(k >> 1) * 16 + (k & 1) * 2 + (j >> 1) * 4 + (j & 1)] = p[((k + 1) >> 1) * 16 + ((k + 1) & 1) * 2 + (j >> 1) * 4 + (j & 1)];
#pragma unroll
    for (int j = 0; j < 8; j++) p[50 + (j >> 1) * 4 + (j & 1)] = r[j];
  }
}
template <int J0 = 0, int J1 = 8> __device__ __forceinline__ void k_exp(const float* p, float c0, float c1, float* e, float* s) {
#pragma unroll
  for (int j = J0; j < J1; j++) {
    e[2 * j] = ex2(p[2 * j] * (j & 1 ? c1 : c0));
    e[2 * j + 1] = ex2(p[2 * j + 1] * (j & 1 ? c1 : c0));
    e[16 + j] = rcp(e[2 * j] * e[2 * j + 1]);
    const float t = e[2 * j] + e[2 * j + 1];
    s[j & 1] = j < 2 ? t : s[j & 1] + t;
    s[2 + (j & 1)] = j < 2 ? e[16 + j] * t : fmaf(e[16 + j], t, s[2 + (j & 1)]);
  }
}
template <int J0 = 0, int J1 = 8> __device__ __forceinline__ void q_exp(const float* p, float c0, float c1, uint32_t* f) {
#pragma unroll
  for (int j = J0; j < J1; j++) {
    const float e0 = ex2(p[2 * j] * (j & 1 ? c1 : c0)), e1 = ex2(p[2 * j + 1] * (j & 1 ? c1 : c0)), r = rcp(e0 * e1);
    f[j] = pack2(e0, e1);
    f[8 + j] = bmul2(f[j], pack2(r, r));
  }
}

#define FMA8(A, U, X)                                                                                        \
  A[0] = fmaf(bf_lo(U.x), X, A[0]); A[1] = fmaf(bf_hi(U.x), X, A[1]); A[2] = fmaf(bf_lo(U.y), X, A[2]); A[3] = fmaf(bf_hi(U.y), X, A[3]); \
  A[4] = fmaf(bf_lo(U.z), X, A[4]); A[5] = fmaf(bf_hi(U.z), X, A[5]); A[6] = fmaf(bf_lo(U.w), X, A[6]); A[7] = fmaf(bf_hi(U.w), X, A[7])

__device__ __forceinline__ uint32_t routed_row(const __nv_bfloat16* x, uint32_t tag, int lane, uint4* xr) {
  uint32_t best = 0, sv = 0;
#pragma unroll 1
  for (int it = 0; it < SPIN_MAX; it++) {
    const int sel = 2047 - (best & 0x7ff);
#pragma unroll
    for (int i = 0; i < 4; i++) xr[i] = ldg_nc(x + (size_t)sel * DM + i * 256 + lane * 8);
    const unsigned long long st = ld_rlx64(g_stat + sel);
    const uint4 b0 = ld_rlx128(g_best + lane * 2), b1 = ld_rlx128(g_best + 64 + lane * 2);
    const uint32_t m = __reduce_max_sync(~0u, max(max(b0.y == tag ? b0.x : 0u, b0.w == tag ? b0.z : 0u), max(b1.y == tag ? b1.x : 0u, b1.w == tag ? b1.z : 0u)));
    sv = (uint32_t)st;
    if (__all_sync(~0u, b0.y == tag && b0.w == tag && b1.y == tag && b1.w == tag && m == best && (uint32_t)(st >> 32) == tag)) break;
    best = m;
    if (AM_NS) __nanosleep(AM_NS);
  }
  const uint32_t m2 = (sv & 0xffff0000u) | (sv >> 16);
  const float rs = rcp(bf_lo(sv));
#pragma unroll
  for (int i = 0; i < 4; i++) {
    const uint32_t d0 = bsub2(xr[i].x, m2), d1 = bsub2(xr[i].y, m2), d2 = bsub2(xr[i].z, m2), d3 = bsub2(xr[i].w, m2);
    xr[i] = make_uint4(pack2(bf_lo(d0) * rs, bf_hi(d0) * rs), pack2(bf_lo(d1) * rs, bf_hi(d1) * rs), pack2(bf_lo(d2) * rs, bf_hi(d2) * rs),
                       pack2(bf_lo(d3) * rs, bf_hi(d3) * rs));
  }
  return best;
}

struct Params {
  const __nv_bfloat16 *x, *wqkv, *wo, *w_r, *w_gate, *w_up, *w_down;
};

template <bool BY_SMID> __global__ void __launch_bounds__(384, 1)
fused_kernel(const __grid_constant__ CUtensorMap mX, const __grid_constant__ CUtensorMap mWkv, const __grid_constant__ CUtensorMap mWq,
             const __grid_constant__ CUtensorMap mWo, const __grid_constant__ CUtensorMap mPhi, const __grid_constant__ CUtensorMap mWp,
             const __grid_constant__ CUtensorMap mOut, const __grid_constant__ CUtensorMap mWc,
             const __grid_constant__ CUtensorMap mG, const __grid_constant__ CUtensorMap mU, const __grid_constant__ CUtensorMap mD,
             const __grid_constant__ CUtensorMap mXs, const __grid_constant__ CUtensorMap mG2, const __grid_constant__ CUtensorMap mU2, const Params P) {
  constexpr uint32_t sb = SB, bar = SB + SM_BAR;
  int bid = blockIdx.x;
  if (BY_SMID) {
    uint32_t sm;
    asm volatile("mov.u32 %0, %%smid;" : "=r"(sm));
    const uint32_t tq = (sm - 64) >> 1, q7 = (tq * 37) >> 8;
    const uint32_t gpc = sm < 64 ? (sm >> 1) & 7 : 1 + tq - 7 * q7, idx = (sm < 64 ? sm >> 4 : 4 + q7) * 2 + (sm & 1);
    bid = sm < 120 ? ((PTAB >> (4 * gpc)) & 7) * 16 + idx : sm < 124 ? sm + 8 : sm - 116;
  }
  const int hg = ((bid >> 2) & 3) + 4 * ((bid >> 4) & 1), mb = (bid & 3) + 4 * ((bid >> 5) & 3);
  if (bid < NCTA && threadIdx.x < 256) {
    const uint32_t r0 = threadIdx.x >> 3, c = threadIdx.x & 7, dst = sb + 2 * KV_STAGE + r0 * 128 + ((c ^ (r0 & 7)) << 4);
    const char* xs = (const char*)P.x + (size_t)(mb * 128 + r0) * 2048 + c * 16;
    const char* ws = (const char*)P.wqkv + (size_t)r0 * 6144 + 2048 + hg * 256 + c * 16;
#pragma unroll
    for (int i = 0; i < 4; i++) cp_async16(dst + i * 4096, xs + i * 65536);
#pragma unroll
    for (int i = 0; i < 8; i++) cp_async16(dst + 16384 + i * 4096, ws + (i & 1) * 196608 + (i >> 2) * 2048 + ((i >> 1) & 1) * 128);
  }
  extern __shared__ __align__(1024) uint8_t smem[];
  if (smem_u32(smem) != SB) __trap();
  const int warp = __shfl_sync(~0u, threadIdx.x >> 5, 0);

  if (bid >= NCTA) {
    constexpr uint32_t XV = SM_WPHI, ONES = SM_ZT, BF = bar, BE = bar + 48, BX = bar + 96;
    constexpr int NJ = (DM - GROWS) / 64;
    const int lane = lane_id(), sp = bid - NCTA;
    const uint32_t tag = ld_rlx(g_epoch + bid * 32 + lane) + 1;
    if (warp == 8 && elect_one()) {
#pragma unroll 1
      for (int i = 0; i < 13; i++) mbar_init(bar + 8 * i, i >= 6 && i < 12 ? 8 : 1);
    }
    if (warp == 9) { sts64u(sb + ONES + lane * 8, 0x3f803f80u, 0x3f803f80u); fence_async_smem(); }
    __syncthreads();
    if (warp == 8) {
      if (elect_one()) {
        uint32_t s = 0, ph = 1;
        for (const long long c0 = clock64(); clock64() - c0 < SP_DELAY;) {}
#pragma unroll 1
        for (int job = 0; job < 8; job++) {
          const CUtensorMap* m = job == 0 ? &mWq : sp & 2 ? &mU2 : &mG2;
          const int g0 = job ? (sp & 1) * 28 + job * 4 - 4 : sp * 4;
#pragma unroll 1
          for (int row = job ? GROWS : 0; row < DM; row += 64) {
            mbar_wait(BE + 8 * s, ph);
            mbar_expect_tx(BF + 8 * s, Q_STAGE);
            tma4d(sb + s * Q_STAGE, m, 0, row, g0, 0, BF + 8 * s);
            tma4d(sb + s * Q_STAGE + 16384, m, 0, row, g0 + 2, 0, BF + 8 * s);
            if (++s == 6) { s = 0; ph ^= 1; }
          }
        }
      }
    } else if (warp == 9) {
      uint4 xr[4];
      routed_row(P.x, tag, lane, xr);
#pragma unroll
      for (int i = 0; i < 4; i++) sts128u(sb + XV + i * 512 + lane * 16, xr[i].x, xr[i].y, xr[i].z, xr[i].w);
      fence_async_smem();
      __syncwarp();
      if (lane == 0) mbar_arrive(BX);
    } else if (warp < 8) {
      uint32_t s = 0, ph = 0;
#pragma unroll 1
      for (int job = 0; job < 8; job++) {
        float d[8] = {0.f, 0.f, 0.f, 0.f, 0.f, 0.f, 0.f, 0.f};
        if (job == 1) mbar_wait(BX, 0);
#pragma unroll 1
        for (int i = 0; i < (job ? NJ : 16); i++) {
          mbar_wait(BF + 8 * s, ph);
          wg_fence();
#pragma unroll
          for (int k = 0; k < 8; k++)
            wgmma_n8_ss_ta1_tb0(d + 4 * (k >> 2), mkdesc(sb + k * 2048, 16, 1024, 1, s * (Q_STAGE / 16) + (warp >> 2) * 1024),
                                mkdesc(sb, 16, 128, 0, job ? (XV + GROWS * 2) / 16 + i * 8 + (k & 3) * 2 : ONES / 16), 1);
          wg_commit();
          wg_wait<0>();
          if (lane == 0) mbar_arrive(BE + 8 * s);
          if (++s == 6) { s = 0; ph ^= 1; }
        }
        reg_fence<8>(d);
        float* dst = (job ? g_gp + sp * 1792 + job * 256 - 256 : g_cs + sp * 256) + (warp >> 2) * 128 + (warp & 3) * 16 + (lane >> 2);
        if ((lane & 3) == 0) {
#pragma unroll
          for (int i = 0; i < 4; i++) st_rlx(dst + (i >> 1) * 64 + (i & 1) * 8, mark(__float_as_uint(d[2 * i]), tag & 1));
        }
        __syncwarp();
      }
      if (warp == 0) g_epoch[bid * 32 + lane] = tag;
    }
    return;
  }
#define Q_SLAB(J) ((J) < 8 ? ((J) + 8 - 2 * (hg & 4)) & 15 : 2 * (hg & 4) + 2 * ((J) & 3) + ((J) >> 2 & 1))
#define Q_AOFF(J) ((J) == 8 + (hg & 3) ? SM_X0 : (J) == 12 + (hg & 3) ? SM_X1 : ((J) & 3) * Q_STAGE)
#define Q_LOAD(J)                                                                                            \
  do {                                                                                                       \
    const uint32_t fb_ = bar + B_FULLQ + 8 * ((J) & 3);                                                      \
    const int k_ = Q_SLAB(J) * 64;                                                                           \
    mbar_expect_tx(fb_, Q_STAGE);                                                                            \
    mbar_arrive2(fb_);                                                                                       \
    tma2d(sb + Q_AOFF(J), &mX, k_, mb * 128, fb_);                                                           \
    tma4d(sb + ((J) & 3) * Q_STAGE + 16384, &mWq, 0, k_, hg * 2, 0, fb_);                                    \
  } while (0)
  if (warp >= 8) {
    asm volatile("setmaxnreg.dec.sync.aligned.u32 %0;" ::"n"(REG_H));
    const int lane = lane_id();
    const int f = (warp - 9) & 3;
    if (f == 3) {
      if (elect_one()) {
        PROF(0); PROFT(32);
#pragma unroll
        for (int s = 0; s < 3; s++) mbar_init(bar + B_FULLKV + 8 * s, 1);
      }
      __syncwarp();
      asm volatile("bar.arrive 14, 288;" ::: "memory");
      if (elect_one()) {
#pragma unroll
        for (int s = 0; s < 2; s++) {
          mbar_expect_tx(bar + B_FULLKV + 8 * s, KV_STAGE);
          tma2d(sb + s * KV_STAGE, &mX, (s + 1) * 64, mb * 128, bar + B_FULLKV + 8 * s);
          tma4d(sb + s * KV_STAGE + 16384, &mWkv, 0, (s + 1) * 64, hg * 2, 1, bar + B_FULLKV + 8 * s);
        }
      }
      __syncwarp();
    }
    const uint32_t ep = ld_rlx(g_epoch + bid * 32 + lane);
    if (f < 2) {
#pragma unroll
      for (int i = 0; i < 2; i++) {
        const uint4 u = __ldg((const uint4*)P.w_r + (f * 2 + i) * 32 + lane);
        sts128u(sb + SM_XSEL + (f * 2 + i) * 512 + lane * 16, u.x, u.y, u.z, u.w);
      }
    }
    bar_sync(13, 384);
    const uint32_t tag = ep + 1, par = tag & 1;
    const bool ffn = bid < NFFN;
    const int fb = bid, cu = bid >> 1, ch = bid & 1;
#define CS_STORE(SEC, C)                                                                                     \
  _Pragma("unroll") for (int r = 0; r < 3; r++) {                                                            \
    const uint32_t h0 = pack2(C.x, C.y), h1 = pack2(C.z, C.w);                                               \
    sts64u(sb + SM_CST + (SEC) * 1024 + (lane >> 4) * 512 + (lane & 1) * 8 + r * 128 + ((((lane & 15) >> 1) ^ (r + (lane >> 4) * 4)) << 4), h0, h1); \
    C.x -= bf_lo(h0); C.y -= bf_hi(h0); C.z -= bf_lo(h1); C.w -= bf_hi(h1);                                  \
  }
#define BAD4(U) ((U.x ^ par) | (U.y ^ par) | (U.z ^ par) | (U.w ^ par))
    const int n0 = f < 2 ? 0 : 2 * f - 3, ne = FFN_OFF || !ffn ? 3 : f == 3 ? 3 + G8 : 3 + GN;
    const uint32_t fsb = sb + SM_FST + ((f + 1) & 3) * 8192, fbar = bar + B_FST + f * 16, fst = fsb + (lane >> 4) * 2048 + (lane & 15) * 16;
    const CUtensorMap *ma = &mWc, *mc = &mWc;
    int sx = 1024 + cu * 32, sy = ch * 512 + f * 192, sdy = 32;
#define STAGEG(N)                                                                                            \
  do {                                                                                                       \
    if ((N) == 3) { ma = &mG; mc = &mU; sx = fb * 32; sy = f * (GN * 32);  sdy = 0; }                        \
    if ((N) < ne && elect_one()) {                                                                           \
      const uint32_t dst_ = fsb + ((N) & 1) * 4096, b_ = fbar + ((N) & 1) * 8;                               \
      mbar_expect_tx(b_, 4096);                                                                              \
      tma2d(dst_, ma, sx, sy, b_);                                                                           \
      tma2d(dst_ + 2048, mc, sx, sy + sdy, b_);                                                              \
    }                                                                                                        \
    sy += 32 + sdy;                                                                                          \
  } while (0)
    float a[8], gsum = 0.f, usum = 0.f;
    {
      if (f == 3) {
        if (elect_one()) {
          if (XS_EARLY) { mbar_expect_tx(bar + B_XST, 16384); tma3d(sb + SM_XST, &mXs, 0, bid * 16, 0, bar + B_XST); }
          mbar_expect_tx(bar + B_WPHI, 8192);
          tma2d(sb + SM_WPHI, &mPhi, 0, hg * 128, bar + B_WPHI);
          prefetch_map(&mWq); prefetch_map(&mWo); prefetch_map(&mWp); prefetch_map(&mD);
          PROF(31);
        }
        __syncwarp();
      } else {
        if (lane == 0) prefetch_map(f == 0 ? &mWc : f == 1 ? &mG : &mU);
        if (f == 2) ((float2*)g_y[par])[bid * 32 + lane] = make_float2(0.f, 0.f);
      }
      float st[13];
#pragma unroll
      for (int i = 0; i < 13; i++) st[i] = 0.f;
#pragma unroll 1
      for (int i = 0; i < 4; i++) {
        mbar_wait(bar + B_XST + 8 * (i >> 1), 0);
        if (f == 0 && lane == 0 && i == 0) PROF(1);
        const uint4 wu = lds128u(sb + SM_XSEL + i * 512 + lane * 16);
        const float wf[8] = {bf_lo(wu.x), bf_hi(wu.x), bf_lo(wu.y), bf_hi(wu.y), bf_lo(wu.z), bf_hi(wu.z), bf_lo(wu.w), bf_hi(wu.w)};
        st[12] += ((wf[0] + wf[1]) + (wf[2] + wf[3])) + ((wf[4] + wf[5]) + (wf[6] + wf[7]));
#pragma unroll
        for (int r = 0; r < 4; r++) {
          const uint4 u = lds128u(sb + SM_XST + i * 8192 + (4 * f + r) * 512 + lane * 16);
          const float xf[8] = {bf_lo(u.x), bf_hi(u.x), bf_lo(u.y), bf_hi(u.y), bf_lo(u.z), bf_hi(u.z), bf_lo(u.w), bf_hi(u.w)};
#pragma unroll
          for (int k = 0; k < 8; k++) { st[r] += xf[k]; st[4 + r] = fmaf(xf[k], xf[k], st[4 + r]); st[8 + r] = fmaf(xf[k], wf[k], st[8 + r]); }
        }
        if (i >= 2 && f < 3) STAGEG(n0 + i - 2);
      }
      const bool up = lane & 16, up2 = lane & 8;
#pragma unroll
      for (int q = 0; q < 3; q++) {
        const float k0 = up ? st[4 * q + 2] : st[4 * q], k1 = up ? st[4 * q + 3] : st[4 * q + 1];
        const float o0 = up ? st[4 * q] : st[4 * q + 2], o1 = up ? st[4 * q + 1] : st[4 * q + 3];
        const float m0 = k0 + __shfl_xor_sync(~0u, o0, 16), m1 = k1 + __shfl_xor_sync(~0u, o1, 16);
        a[q] = (up2 ? m1 : m0) + __shfl_xor_sync(~0u, up2 ? m0 : m1, 8);
      }
      a[3] = st[12] + __shfl_xor_sync(~0u, st[12], 16);
      a[3] += __shfl_xor_sync(~0u, a[3], 8);
#pragma unroll
      for (int o = 4; o; o >>= 1)
#pragma unroll
        for (int q = 0; q < 4; q++) a[q] += __shfl_xor_sync(~0u, a[q], o);
      if ((lane & 7) == 0) sts128(sb + SM_ROWS + (4 * f + (lane >> 3)) * 16, a[0], a[1], a[2], a[3]);
      if (f < 3) asm volatile("bar.arrive 7, 128;" ::: "memory");
    }
    if (f == 3) {
      bar_sync(7, 128);
      const int row = bid * 16 + (lane & 15);
      const float4 v = lds128(sb + SM_ROWS + (lane & 15) * 16);
      const float mf = v.x * (1.f / DM), mean = bf_round(mf), var = fmaxf(fmaf(-mf, mf, v.y * (1.f / DM)), 0.f);
      const float sd = bf_round(sqrt_approx(bf_round(bf_round(var) + 1e-5f)));
      const uint32_t rb = pack2(fmaf(-mean, v.w, v.z) * rcp(sd), 0.f) & 0xffffu, ord = (rb & 0x8000u) ? (~rb & 0xffffu) : (rb | 0x8000u);
      uint32_t best = __reduce_max_sync(~0u, (ord << 16) | (uint32_t)(2047 - row));
      if (lane < 16) st_rlx64(g_stat + row, ((unsigned long long)tag << 32) | __float_as_uint(mean) | (__float_as_uint(sd) >> 16));
      if (lane == 0) { asm volatile("red.relaxed.gpu.global.max.u64 [%0], %1;" ::"l"(g_best + bid), "l"(((unsigned long long)tag << 32) | best) : "memory"); PROF(17); }
#pragma unroll 1
      for (int n = 3; n < 5; n++) STAGEG(n);
      {
        uint4 xr[4];
        best = routed_row(P.x, tag, lane, xr);
#pragma unroll
        for (int i = 0; i < (GROWS + 255) / 256; i++) {
          const uint32_t dst = sb + SM_XSEL + i * 1024 + (lane >> 2) * 128 + (lane & 3) * 8;
          sts64(dst, bf_lo(xr[i].x), bf_lo(xr[i].z)); sts64(dst + 32, bf_hi(xr[i].x), bf_hi(xr[i].z));
          sts64(dst + 64, bf_lo(xr[i].y), bf_lo(xr[i].w)); sts64(dst + 96, bf_hi(xr[i].y), bf_hi(xr[i].w));
        }
        sts64u(sb + SM_RED + 16, tag, best);
        __syncwarp();
        if (lane == 0) { mbar_arrive(bar + B_XS); PROF(19); }
      }
      unsigned long long sv4[4];
      uint4 u[4];
#pragma unroll 1
      for (int it = 0; it < SPIN_MAX; it++) {
#pragma unroll
        for (int i = 0; i < 4; i++) { u[i] = ld_rlx128(g_cs + (1 + i) * 1024 + hg * 128 + lane * 4); sv4[i] = ld_rlx64(g_stat + mb * 128 + i * 32 + lane); }
        bool ok = ((BAD4(u[0]) | BAD4(u[1]) | BAD4(u[2]) | BAD4(u[3])) & 1) == 0;
#pragma unroll
        for (int i = 0; i < 4; i++) ok = ok && (uint32_t)(sv4[i] >> 32) == tag;
        if (__all_sync(~0u, ok)) break;
        __nanosleep(200);
      }
#pragma unroll
      for (int i = 0; i < 4; i++) {
        const uint32_t sv = (uint32_t)sv4[i], sd2 = (sv << 16) | (sv & 0xffffu);
        sts64(sb + SM_STAT + (i * 32 + lane) * 8, -bf_hi(sv), rcp(bf_lo(sv)));
        sts128u(sb + SM_SDT + lane * 64 + ((i ^ ((lane >> 1) & 3)) << 4), sd2, sd2, sd2, sd2);
      }
#pragma unroll
      for (int i = 0; i < 2; i++) {
        float4 c = make_float4(unmark(u[i].x) + unmark(u[i + 2].x), unmark(u[i].y) + unmark(u[i + 2].y), unmark(u[i].z) + unmark(u[i + 2].z),
                               unmark(u[i].w) + unmark(u[i + 2].w));
        CS_STORE(i, c);
      }
      fence_async_smem();
      bar_sync(8, 64);
      if (lane == 0) { mbar_arrive(bar + B_CS); PROF(10); }
    }
    {
      uint32_t xa = sb + SM_RED + 32, xstep = 0;
      const uint32_t zero = __float_as_uint(lds32(sb + SM_RED + 12));
#pragma unroll 1
      for (int ph = f == 3; ph < 2; ph++) {
#pragma unroll
        for (int j = 0; j < 8; j++) a[j] = 0.f;
        if (ph && f == 0) {
        {
          mbar_wait(bar + B_WPHI, 0);
          float nq[8] = {0.f, 0.f, 0.f, 0.f, 0.f, 0.f, 0.f, 0.f};
  #pragma unroll 2
          for (int r = 0; r < 16; r++) {
            const uint4 u = lds128u(sb + SM_WPHI + ((lane >> 2) * 16 + r) * 64 + (((lane ^ (r >> 1)) & 3) << 4));
            nq[0] = fmaf(bf_lo(u.x), bf_lo(u.x), nq[0]); nq[1] = fmaf(bf_hi(u.x), bf_hi(u.x), nq[1]); nq[2] = fmaf(bf_lo(u.y), bf_lo(u.y), nq[2]);
            nq[3] = fmaf(bf_hi(u.y), bf_hi(u.y), nq[3]); nq[4] = fmaf(bf_lo(u.z), bf_lo(u.z), nq[4]); nq[5] = fmaf(bf_hi(u.z), bf_hi(u.z), nq[5]);
            nq[6] = fmaf(bf_lo(u.w), bf_lo(u.w), nq[6]); nq[7] = fmaf(bf_hi(u.w), bf_hi(u.w), nq[7]);
          }
          uint32_t m = 0;
  #pragma unroll
          for (int i = 0; i < 8; i++) m = max(m, __float_as_uint(nq[i] + __shfl_xor_sync(~0u, nq[i], 4)) & 0x7fffffffu);
          sts32(sb + SM_RED + 24, 4.2f * __uint_as_float(__reduce_max_sync(~0u, m)));
        }
          asm volatile("bar.arrive 8, 64;" ::: "memory");
        }
        if (ph) { mbar_wait(bar + B_XS, 0); xa = sb + SM_XSEL + f * (GN * 128) + ((lane >> 2) & 3) * 32; xstep = 128; }
#pragma unroll 1
        for (int n = ph ? 3 : n0; n < (ph ? ne : 3); n++) {
          const float4 x0 = lds128(xa), x1 = lds128(xa + 16);
          xa += xstep;
          mbar_wait(fbar + (n & 1) * 8, ((n - n0) >> 1) & 1);
          uint4 u[8];
#pragma unroll
          for (int j = 0; j < 8; j++) u[j] = lds128u(fst + (n & 1) * 4096 + j * 256);
          FMA8(a, u[0], x0.x); FMA8(a, u[1], x0.y); FMA8(a, u[2], x0.z); FMA8(a, u[3], x0.w);
          if (__any_sync(~0u, ((u[4].x | u[5].x | u[6].x | u[7].x | __float_as_uint(a[0]) | __float_as_uint(a[7])) & zero) == 0)) STAGEG(n + 2);
          FMA8(a, u[4], x1.x); FMA8(a, u[5], x1.y); FMA8(a, u[6], x1.z); FMA8(a, u[7], x1.w);
        }
#pragma unroll
        for (int o = 4; o <= 8; o <<= 1)
#pragma unroll
          for (int j = 0; j < 8; j++) a[j] += __shfl_xor_sync(~0u, a[j], o);
        if (ph && lane == 0) mbar_arrive(bar + B_FFN);
        const uint32_t red = ph ? sb + SM_GRED : sb + SM_RED + 64;
        if ((lane & 12) == 0) {
          const uint32_t d = red + f * 256 + (lane >> 4) * 128 + (lane & 3) * 32;
          sts128(d, a[0], a[1], a[2], a[3]); sts128(d + 16, a[4], a[5], a[6], a[7]);
        }
        if (f != 2) {
          asm volatile("bar.arrive %0, %1;" ::"r"(4 + ph), "r"(96 + 32 * ph) : "memory");
        } else {
          bar_sync(4 + ph, 96 + 32 * ph);
          const uint32_t ra = red + lane * 4;
          gsum = lds32(ra) + lds32(ra + 256) + lds32(ra + 512);
          usum = lds32(ra + 128) + lds32(ra + 384) + lds32(ra + 640);
          if (!ph) st_rlx(g_cs + 1024 + ch * 2048 + cu * 32 + lane, mark(__float_as_uint(gsum + usum), par));
          else { gsum += lds32(ra + 768); usum += lds32(ra + 896); }
          if (lane == 0) PROF(ph ? 34 : 18);
        }
      }
    }
    if (f == 3) {
      if (elect_one()) {
        PROF(7);
        mbar_wait(bar + B_FULLQ, 0);
#pragma unroll 1
        for (int j = 3; j < 16; j++) {
          mbar_wait(bar + (j < 4 ? B_EMPTYKV + 16 : B_EMPTYQ + 8 * (j & 3)), ((j >> 2) & 1) ^ 1);
          if (j == 12 + (hg & 3)) mbar_wait(bar + B_KVST + 8, 0);
          Q_LOAD(j);
        }
        PROF(47);
        mbar_expect_tx(bar + B_DN, 65536);
#pragma unroll 1
        for (int i = 0; i < 4; i++) {
          mbar_wait(bar + B_EMPTYQ + 8 * i, 1);
          tma3d(sb + i * Q_STAGE, &mD, 0, fb * 32, i * 4, bar + B_DN);
        }
        PROF(48);
#pragma unroll 1
        for (int i = 0; i < 16; i++) {
          const int s = i & 3, n = i < 9 ? i - 2 : i - 9, kb = i < 2 ? 2 * hg + i : 2 * (n + (n >= hg)) + (i >= 9);
          if (i >= 4) mbar_wait(bar + B_EMPTYQ + 8 * s, ((i >> 2) & 1) ^ 1);
          mbar_expect_tx(bar + B_FULLQ + 8 * s, 16384);
          if (i < 2) {
            mbar_arrive2(bar + B_FULLQ + 8 * s);
            tma3d(sb + s * Q_STAGE + 16384, &mWo, 0, kb * 64, hg * 2, bar + B_FULLQ + 8 * s);
          } else {
            tma5d(sb + s * Q_STAGE + 16384, &mWp, hg * 128, kb * 2, bar + B_FULLQ + 8 * s);
            tma5d(sb + s * Q_STAGE + 24576, &mWp, hg * 128 + 64, kb * 2, bar + B_FULLQ + 8 * s);
            if (i >= 3) {
              if (i == 3) { mbar_wait(bar + B_DND, 0); PROF(14); }
#pragma unroll 1
              for (int a = i == 3 ? 2 : i; a <= i; a++) {
                const uint4* src = g_ofr + (mb * 16 + (a == 2 ? (hg == 0 ? 2 : 0) : kb)) * 1024;
#pragma unroll
                for (int h = 0; h < 2; h++) {
                  mbar_expect_tx(bar + B_AIN + (a & 3) * 16 + h * 8, 8192);
                  bulk_load(sb + (a & 3) * Q_STAGE + h * 8192, src + h * 512, 8192, bar + B_AIN + (a & 3) * 16 + h * 8);
                }
              }
            }
          }
        }
      }
    } else {
      if (f == 2) {
        if (PFD && ffn) {
#pragma unroll 1
          for (int i = 0; i < 16; i++) { touch_l2((const char*)P.w_down + fb * 65536 + i * 4096 + lane * 128, lane); __nanosleep(PFD); }
        }
        {
#pragma unroll 1
          for (int i = 0; i < 8; i++) { touch_l2((const char*)P.wo + ((mb & 7) * 128 + i * 16 + (lane >> 1)) * 2048 + hg * 256 + (lane & 1) * 128, lane); __nanosleep(PFD); }
        }
        asm volatile("cp.async.wait_all;" ::: "memory");
        uint4 u;
#pragma unroll 1
        for (int it = 0; it < SPIN_MAX; it++) {
          u = ld_rlx128(g_cs + hg * 128 + lane * 4);
          if (__all_sync(~0u, !(BAD4(u) & 1))) break;
          __nanosleep(200);
        }
        mbar_wait(bar + B_PHI, 0);
        float4 c = make_float4(unmark(u.x), unmark(u.y), unmark(u.z), unmark(u.w));
        CS_STORE(2, c);
        fence_async_smem();
        __syncwarp();
        if (lane == 0) mbar_arrive(bar + B_CSQ);
      }
      const uint32_t target = __shfl_sync(~0u, tag, 0) * 16;
#pragma unroll 1
      for (int R = 0; R < 2; R++) {
        const uint32_t own = (hg * 2 + R) * 16 + mb, pst = sb + (R ? SM_PST1 : SM_PST0);
        if (f == R) {
          mbar_wait(bar + B_KVST + 8 * R, 0);
          if (f == 1 && lane == 0) PROF(11);
          wait_hint(XC1(hg, R) + mb, target);
          if (elect_one()) {
            PROF(35 + R);
            fence_async_global();
            mbar_expect_tx(bar + B_PART + 8 * R, 8192);
            bulk_load(pst, g_part + own * 512, 8192, bar + B_PART + 8 * R);
          }
          __syncwarp();
          uint4 uz;
#pragma unroll 1
          for (int it = 0; it < SPIN_MAX; it++) {
            uz = ld_rlx128(g_zpart + own * 128 + lane * 4);
            if (__all_sync(~0u, !(BAD4(uz) & 1))) break;
          }
          const bool b1 = lane & 2, b2 = lane & 4;
          const float z0 = unmark(b1 ? uz.z : uz.x) + __shfl_xor_sync(~0u, unmark(b1 ? uz.x : uz.z), 2);
          const float z1 = unmark(b1 ? uz.w : uz.y) + __shfl_xor_sync(~0u, unmark(b1 ? uz.y : uz.w), 2);
          float z = (b2 ? z1 : z0) + __shfl_xor_sync(~0u, b2 ? z0 : z1, 4);
          z += __shfl_xor_sync(~0u, z, 8);
          z += __shfl_xor_sync(~0u, z, 16);
          if (lane < 8) st_rlx(g_zres + own * 8 + (lane & 1) * 4 + (lane & 2) + (lane >> 2), mark(__float_as_uint(z), par));
          if (lane == 0) red_inc(XC2(hg, R));
          __syncwarp();
        }
        if (f == R || f == R + 1) {
          const uint32_t hf = f - R, m1 = ~lane & 1, gq = hf * 4 + (lane >> 3), ts = (lane >> 1) & 3;
          float a0 = 0.f, a1 = 0.f, a2 = 0.f, a3 = 0.f;
          mbar_wait(bar + B_PART + 8 * R, 0);
#pragma unroll 1
          for (int it = 0; it < SPIN_MAX; it++) {
            uint32_t bad = 0;
            a0 = a1 = a2 = a3 = 0.f;
#pragma unroll 1
            for (int b = 0; b < 16; b += 8) {
              uint2 u[8];
              if (it == 0) {
#pragma unroll
                for (int i = 0; i < 8; i++) { const float2 v = lds64(pst + (b + i) * 512 + hf * 256 + lane * 8); u[i] = make_uint2(__float_as_uint(v.x), __float_as_uint(v.y)); }
              } else {
#pragma unroll
                for (int i = 0; i < 8; i++) {
                  const unsigned long long v = ld_rlx64((const unsigned long long*)g_part + own * 1024 + (b + i) * 64 + hf * 32 + lane);
                  u[i] = make_uint2((uint32_t)v, (uint32_t)(v >> 32));
                }
              }
#pragma unroll
              for (int i = 0; i < 8; i++) {
                bad |= u[i].x ^ par;
                a0 += bf_lo(i & 1 ? u[i].x & ~m1 : u[i].x | m1); a1 += bf_hi(u[i].x); a2 += bf_lo(u[i].y); a3 += bf_hi(u[i].y);
              }
            }
            if (__all_sync(~0u, !(bad & m1))) break;
          }
          uint32_t* dst = (uint32_t*)g_res[par] + own * 128 + gq * 16 + ts;
          const uint32_t j0 = (lane & 1) * 2, vb = ts == (gq >> 1);
          st_rlx(dst + ((j0 ^ (gq >> 1)) & 3) * 4, pack2(a0, a1) | vb);
          st_rlx(dst + (((j0 + 1) ^ (gq >> 1)) & 3) * 4, pack2(a2, a3) | vb);
          ((uint2*)g_res[par ^ 1])[own * 64 + hf * 32 + lane] = make_uint2(0u, 0u);
          __syncwarp();
          if (lane == 0) { red_inc(XC2(hg, R)); if (!hf) PROF(R ? 12 : 30); }
        }
      }
      if (f == 2) {
        if (ffn && !FFN_OFF) {
#pragma unroll 1
          for (int it = 0; it < SPIN_MAX; it++) {
            const uint32_t pg = ld_rlx((const uint32_t*)g_gp + fb * 32 + lane), pu = ld_rlx((const uint32_t*)g_gp + FF + fb * 32 + lane);
            if (__all_sync(~0u, !(((pg ^ par) | (pu ^ par)) & 1))) { gsum += unmark(pg); usum += unmark(pu); break; }
            __nanosleep(200);
          }
        }
        const float h = bf_round(silu_f(bf_round(gsum))) * bf_round(usum);
        const uint32_t h2 = pack2(h, h);
        sts128u(sb + SM_HT + lane * 16, h2, h2, h2, h2);
        fence_async_smem();
        __syncwarp();
        if (lane == 0) { mbar_arrive(bar + B_H); PROF(20); }
      }
      if (f < 2) {
        wait_hint(XC2(hg, f), 3 * target);
        mbar_wait(bar + B_KVST + 8, 0);
        if (lane == 0) PROF(40 + f);
#pragma unroll 1
        for (int it = 0; it < SPIN_MAX; it++) {
          if (elect_one()) {
            fence_async_global();
            mbar_expect_tx(bar + B_RES + 8 * f, 8192);
            bulk_load(sb + SM_V + f * 8192, g_res[par] + (hg * 4 + f * 2) * 256, 8192, bar + B_RES + 8 * f);
          }
          __syncwarp();
          const uint4 uz = ld_rlx128(g_zres + (hg * 4 + f * 2) * 64 + lane * 4);
          const uint32_t zw[4] = {uz.x, uz.y, uz.z, uz.w};
#pragma unroll
          for (int j = 0; j < 4; j++) {
            const uint32_t zz = pack2(unmark(zw[j]), 1.f), row = (lane & 3) * 4 + j;
            sts128u(sb + SM_ZT + (2 * f + (lane >> 4)) * 1024 + row * 64 + ((((lane >> 2) ^ (row >> 1)) & 3) << 4), zz, zz, zz, zz);
          }
          uint32_t bad = BAD4(uz);
          mbar_wait(bar + B_RES + 8 * f, it & 1);
#pragma unroll
          for (int i = 0; i < 16; i++) bad |= ~__float_as_uint(lds32(sb + SM_V + f * 8192 + i * 512 + lane * 16 + (lane >> 3) * 4));
          if (__all_sync(~0u, !(bad & 1))) break;
        }
        fence_async_smem();
        __syncwarp();
        if (lane == 0) { mbar_arrive(bar + B_TILE + 8 * f); PROF(f ? 13 : 27); }
      }
      if (f < 2) {
        uint32_t phases = 0;
#pragma unroll 1
        for (int i = 2; i < 16; i++) {
          const int s = i & 3;
          const uint32_t ab = bar + B_AIN + s * 16 + f * 8, slot = sb + s * Q_STAGE + f * 8192;
#pragma unroll 1
          for (int it = 0; it < SPIN_MAX; it++) {
            mbar_wait(ab, (phases >> s) & 1);
            phases ^= 1u << s;
            uint32_t bad = 0;
#pragma unroll
            for (int n = 0; n < 8; n++) bad |= __float_as_uint(lds32(slot + n * 1024 + lane * 32 + (lane >> 2) * 4)) ^ par;
            if (__all_sync(~0u, !(bad & 1))) break;
            if (elect_one()) {
              const int n = i < 9 ? i - 2 : i - 9, kb = 2 * (n + (n >= hg)) + (i >= 9);
              PROF(49);
              mbar_expect_tx(ab, 8192);
              bulk_load(slot, g_ofr + (mb * 16 + kb) * 1024 + f * 512, 8192, ab);
            }
            __syncwarp();
          }
          if (lane == 0) { mbar_arrive(bar + B_FULLQ + 8 * s); if (i == 2 && f == 0) PROF(15); }
        }
        if (f == 0) g_epoch[bid * 32 + lane] = tag;
      } else {
        if (elect_one()) {
          prefetch_map(&mOut);
          if (ffn) { mbar_wait(bar + B_YD, 0); red_rel(g_ycnt); PROF(21); }
        }
        __syncwarp();
        if (f == 2) {
          const uint32_t best = __float_as_uint(lds32(sb + SM_RED + 20));
          const int sel = 2047 - (best & 0x7ff) - mb * 128;
          if (sel >= 0 && sel < 128) {
            const uint2 xr = __ldg((const uint2*)(P.x + (size_t)(mb * 128 + sel) * DM + hg * 128 + lane * 4));
            const float2 st = lds64(sb + SM_STAT + sel * 8);
            const uint32_t ord = best >> 16, rb = (ord & 0x8000u) ? (ord & 0x7fffu) : (~ord & 0xffffu);
            const float sg = rcp(1.f + ex2(-1.4426950408889634f * bf_lo(rb)));
            const uint32_t sg2 = pack2(sg, sg), nm2 = pack2(st.x, st.x);
            wait_cnt<0>(g_ycnt, tag * NFFN);
            float4 y = make_float4(0.f, 0.f, 0.f, 0.f);
#pragma unroll
            for (int i = 0; i < 8; i++) {
              const float4 c = ldg_cg4(g_y[par ^ 1][i] + hg * 128 + lane * 4);
              y.x += c.x; y.y += c.y; y.z += c.z; y.w += c.w;
            }
            uint32_t o[2];
#pragma unroll
            for (int i = 0; i < 2; i++) {
              const uint32_t d = badd2(i ? xr.y : xr.x, nm2);
              const uint32_t tt = badd2(pack2(bf_lo(d) * st.y, bf_hi(d) * st.y), bmul2(i ? pack2(y.z, y.w) : pack2(y.x, y.y), sg2));
              o[i] = pack2(silu_f(bf_lo(tt)), silu_f(bf_hi(tt)));
            }
            sts64u(sb + SM_UPD + lane * 8, o[0], o[1]);
          }
          if (lane == 0) sts32(sb + SM_UPD + 256, __int_as_float(sel));
          __syncwarp();
          if (lane == 0) { mbar_arrive(bar + B_UPD); PROF(22); }
        }
      }
    }
  } else {
    const int t7 = threadIdx.x & 127;
    const char* pfa = warp < 4 ? (const char*)P.x + bid * 32768 + (t7 & 15) * 2048 + (t7 >> 4) * 128
                               : (const char*)P.wqkv + (size_t)((t7 >> 4) * 64 + (bid >> 1)) * 6144 + 2048 + (bid & 1) * 2048 + (t7 & 15) * 128;
    if (t7 >= 16 && t7 < 16 * PF_FIRST) prefetch_l2(pfa);
    if (warp < 7) sts128(sb + SM_CST + threadIdx.x * 16, 0.f, 0.f, 0.f, 0.f);
    else sts32(sb + SM_RED + (threadIdx.x & 15) * 4, threadIdx.x & 8 ? 1.f : 0.f);
    if (elect_one()) {
#pragma unroll 1
      for (uint32_t b = B_FST + warp * 8; b < B_END; b += 64)
        mbar_init(bar + b, b < B_FULLQ ? 1 : b < B_FFN ? 3 : b < B_EMPTYKV ? 4 : 8);
    }
    __syncwarp();
    asm volatile("bar.arrive 13, 384;" ::: "memory");
    asm volatile("setmaxnreg.inc.sync.aligned.u32 %0;" ::"n"(REG_C));
    if (t7 >= 16 * PF_FIRST && threadIdx.x < 128 + 16 * PF_W) prefetch_l2(pfa);
    asm volatile("cp.async.wait_all;" ::: "memory");
    fence_async_smem();
    bar_sync(14, 288);
    if (threadIdx.x == 0) mbar_arrive(bar + B_FULLKV + 16);
    const int lane = lane_id();
    const int wg = warp >> 2, w = warp & 3, g = lane >> 2, t = lane & 3;
    float kv[128];
    {
      uint32_t s = 2, ph = 0, sp = 0, php = 0;
#pragma unroll 1
      for (int j = 0; j < 15; j++) {
        PW0(32 + j); mbar_wait(bar + B_FULLKV + 8 * s, ph); PW1(32 + j);
        if (wg == 1) bar_sync(10 + s, 256);
        wg_fence();
        wgmma_n256_ssp_ta0_tb1(kv, mkdesc(sb, 16, 1024, 1, wg * 512 + s * (KV_STAGE / 16)), mkdesc(sb + 16384, 8192, 1024, 1, s * (KV_STAGE / 16)), j);
#pragma unroll
        for (int k = 1; k < 4; k++)
          wgmma_n256_ss_ta0_tb1(kv, mkdesc(sb + k * 32, 16, 1024, 1, wg * 512 + s * (KV_STAGE / 16)),
                                mkdesc(sb + 16384 + k * 2048, 8192, 1024, 1, s * (KV_STAGE / 16)), 1);
        wg_commit();
        if (wg == 0) asm volatile("bar.arrive %0, 256;" ::"r"(10 + s) : "memory");
        if (warp == 0 && j) {
          mbar_wait(bar + B_EMPTYKV + 8 * sp, php);
          if (elect_one()) {
            if (j < 14) {
              mbar_expect_tx(bar + B_FULLKV + 8 * sp, KV_STAGE);
              tma2d(sb + sp * KV_STAGE, &mX, (j + 2) * 64, mb * 128, bar + B_FULLKV + 8 * sp);
              tma4d(sb + sp * KV_STAGE + 16384, &mWkv, 0, (j + 2) * 64, hg * 2, 1, bar + B_FULLKV + 8 * sp);
            } else {
              Q_LOAD(0);
            }
            if (j < 3 - XS_EARLY) {
              const int xh = j - 1 + XS_EARLY;
              mbar_expect_tx(bar + B_XST + 8 * xh, 16384);
              tma3d(sb + SM_XST + xh * 16384, &mXs, 0, bid * 16, 2 * xh, bar + B_XST + 8 * xh);
            }
          }
          __syncwarp();
        }
        if (j == 0) {
          if (wg == 0) prefetch_l2(pfa + 1024);
        } else if (wg == 1) {
          if (j < 3) {
            if (j == 2 || t7 >= 16 * PF_W) prefetch_l2(pfa + (j - 1) * (8 * 393216));
          } else if (j == 13) {
            prefetch_l2((const char*)P.wo + bid * 16384 + t7 * 128);
          }
        }
        wg_wait<0>();
        if (lane == 0) mbar_arrive(bar + B_EMPTYKV + 8 * s);
        sp = s; php = ph;
        ph ^= s == 1;
        s = s == 2 ? 0 : s + 1;
      }
    }
    const int lrow = wg * 64 + w * 16 + (lane & 15);
    const uint32_t sw128 = lrow * 128, x128 = (lrow & 7), hi16 = lane >> 4;
    mbar_wait(bar + B_CS, 0);
    const uint32_t tag = __float_as_uint(lds32(sb + SM_RED + 16));
    const int zero = __float_as_int(lds32(sb + SM_RED + 12));
    const float wn = lds32(sb + SM_RED + 24);
    const float2 st0 = lds64(sb + SM_STAT + (wg * 64 + w * 16 + g) * 8), st1 = lds64(sb + SM_STAT + (wg * 64 + w * 16 + g + 8) * 8);
    const float c0 = st0.y * 1.4426950408889634f, c1 = st1.y * 1.4426950408889634f;
    const uint32_t nm20 = pack2(st0.x, st0.x), nm21 = pack2(st1.x, st1.x), fmask = t == 0 ? ~0u : t == 1 ? 0xffffu : 0u;
    const uint32_t fa0 = nm20 & fmask, fa1 = nm21 & fmask;
    asm volatile("cp.async.wait_all;" ::: "memory");
    PW0(47); mbar_wait(bar + B_FULLKV + 16, 1); PW1(47);
    wg_fence();
    wgmma_n256_rs_ta0_tb1(kv, fa0, fa1, 0u, 0u, mkdesc(sb + SM_CST, 512, 0, 1), 1);
#pragma unroll
    for (int k = 0; k < 4; k++)
      wgmma_n256_ss_ta0_tb1(kv, mkdesc(sb + 2 * KV_STAGE + k * 32, 16, 1024, 1, wg * 512), mkdesc(sb + 2 * KV_STAGE + 16384 + k * 2048, 8192, 1024, 1), 1);
    wg_commit();
    if (warp == 0) {
      mbar_wait(bar + B_EMPTYKV + 8, 0);
      if (elect_one()) {
#pragma unroll 1
        for (int j = 1; j < 3; j++) Q_LOAD(j);
      }
      __syncwarp();
    }
    wg_wait<0>();
    reg_fence<128>(kv);
    if (lane == 0) mbar_arrive(bar + B_EMPTYKV + 16);
    PROFC(2);
    float q[64];
#define QMMA(J, AOFF16, ACCUM)                                                                                     \
  _Pragma("unroll") for (int k = 0; k < 4; k++)                                                                    \
      wgmma_n128_ss_ta0_tb1(q, mkdesc(sb + k * 32, 16, 1024, 1, wg * 512 + (AOFF16)),                              \
                            mkdesc(sb + 16384 + k * 2048, 8192, 1024, 1, ((J) & 3) * (Q_STAGE / 16)), k ? 1 : (ACCUM))
#define QWAIT(J) do { PW0(J); mbar_wait(bar + B_FULLQ + 8 * ((J) & 3), ((J) >> 2) & 1); PW1(J); } while (0)
#define QSTEP_A(J, AOFF16, ACCUM) do { QWAIT(J); wg_fence(); QMMA(J, AOFF16, ACCUM); wg_commit(); } while (0)
#define QREL(J) do { if (lane == 0) mbar_arrive(bar + B_EMPTYQ + 8 * ((J) & 3)); } while (0)
#define Q_OFF16(J) ((J) >= 8 && (J) < 16 ? Q_AOFF(J) / 16 : ((J) & 3) * (Q_STAGE / 16))
#define QPLAIN(J) do { QSTEP_A(J, Q_OFF16(J), 1); wg_wait<1>(); QREL((J) - 1); } while (0)
#define QNEXT(J) do { QPLAIN(J); SCHED_FENCE(); } while (0)
#define PHI_PROJ(DST, SRC, H0, H1)                                                                                 \
  do {                                                                                                             \
    uint32_t a_[32];                                                                                               \
    _Pragma("unroll") for (int j = 8 * (H0); j < 8 * (H1); j++) {                                                  \
      a_[j] = pack2(SRC[2 * j], SRC[2 * j + 1]);                                                                   \
      asm volatile("fma.rn.bf16x2 %0, %1, %1, %0;" : "+r"(nq[(j >> 4) * 2 + (j & 1)]) : "r"(a_[j]));               \
    }                                                                                                              \
    wg_fence();                                                                                                    \
    _Pragma("unroll") for (int hk = 2 * (H0); hk < 2 * (H1); hk++)                                                 \
        wgmma_n32_rs_ta0_tb1(DST + 16 * (hk >> 1), a_[4 * hk], a_[4 * hk + 1], a_[4 * hk + 2], a_[4 * hk + 3],     \
                             mkdesc(sb + SM_WPHI + hk * 1024, 16, 512, 2), hk & 1);                                \
    wg_commit();                                                                                                   \
  } while (0)
    {
      float p[64], ea[24], eb[24], sa[4], sc[4], kz[20];
      uint32_t vp[32];
#pragma unroll
      for (int j = 0; j < 32; j++) vp[j] = pack2(kv[64 + 2 * j], kv[65 + 2 * j]);
      const uint32_t vr = w * 16 + (lane & 15), vb = sb + SM_V + wg * 4096 + vr * 64, x64 = (vr >> 1) & 3;
#define V_STORE(R)                                                                                           \
  _Pragma("unroll") for (int j = 0; j < 4; j++)                                                              \
      stsm4(vb + (j >> 1) * 8192 + ((((j & 1) * 2 + hi16) ^ x64) << 4), vp[16 * (R) + 4 * j], vp[16 * (R) + 4 * j + 1], vp[16 * (R) + 4 * j + 2], vp[16 * (R) + 4 * j + 3])
      V_STORE(0);
      mbar_wait(bar + B_WPHI, 0);
      {
        uint32_t nq[4] = {0u, 0u, 0u, 0u};
        PHI_PROJ(p, kv, 0, 4);
        QSTEP_A(0, 0, 0);
        const bool unsafe = softmax_unsafe(nq, c0 * c0 * wn, c1 * c1 * wn);
        wg_wait<1>();
        reg_fence<64>(p);
        if (__builtin_expect(unsafe, 0)) softmax_shift(p, c0, c1);
      }
#define K_NORM(S) do { quad_sum<4>(S); _Pragma("unroll") for (int i = 0; i < 4; i++) S[i] = rcp(S[i]) * ((i & 1) ? st1.y : st0.y); } while (0)
#define K_STORE(SLOT, E, S) K_STORE_(SLOT, E, S, 0, 2)
#define K_STORE_(SLOT, E, S, J0, J1)                                                                         \
  _Pragma("unroll") for (int j = (J0); j < (J1); j++) {                                                      \
    uint32_t fp[4], fm[4];                                                                                   \
    _Pragma("unroll") for (int i = 0; i < 4; i++) {                                                          \
      const float e0 = E[8 * j + 2 * i], e1 = E[8 * j + 2 * i + 1], r = E[16 + 4 * j + i] * S[2 + (i & 1)];  \
      const uint32_t e2 = pack2(e0, e1);                                                                     \
      fp[i] = bmul2(e2, pack2(S[i & 1], S[i & 1]));                                                          \
      fm[i] = bmul2(e2, pack2(r, r));                                                                        \
    }                                                                                                        \
    stsm4(sb + SM_PHI + (SLOT) * 16384 + sw128 + (((2 * j + hi16) ^ x128) << 4), fp[0], fp[1], fp[2], fp[3]); \
    stsm4(sb + SM_PHI + (SLOT) * 16384 + sw128 + (((4 + 2 * j + hi16) ^ x128) << 4), fm[0], fm[1], fm[2], fm[3]); \
  }
#define KV_MMA(R)                                                                                            \
  do {                                                                                                       \
    mbar_wait(bar + B_PHI + 8 * (R), 0);                                                                     \
    wg_fence();                                                                                              \
    _Pragma("unroll") for (int k = 0; k < 8; k++) {                                                          \
      const uint32_t vs = SM_V + (k >> 2) * 4096 + (k & 3) * 1024;                                           \
      wgmma_n40_ss_ta1_tb1(kz, mkdesc(sb + SM_PHI + k * 2048, 16, 1024, 1, wg * 1024),                       \
                           mkdesc(sb + vs, SM_SDT + (k & 1) * 1024 + (k >> 1) * 16 - vs, 512, 2, wg * (512u - (512u << 16))), k); \
    }                                                                                                        \
    wg_commit();                                                                                             \
  } while (0)
#define QKV(J, R) do { KV_MMA(R); QSTEP_A(J, Q_OFF16(J), 1); wg_wait<2>(); QREL((J) - 1); SCHED_FENCE(); } while (0)
#define KV_SEND(R)                                                                                           \
  do {                                                                                                       \
    reg_fence<20>(kz);                                                                                       \
    if (lane == 0) mbar_arrive(bar + B_KVST + 8 * (R));                                                      \
    const uint32_t slot = ((hg * 2 + (R)) * 16 + warp * 2) * 16 + mb;                                        \
    _Pragma("unroll") for (int u = 0; u < 2; u++)                                                            \
      st_rlx128(g_part + (slot + u * 16) * 32 + lane, mark(pack2(kz[2 * u], kz[2 * u + 1]), tag & 1), pack2(kz[2 * u + 4], kz[2 * u + 5]), \
                pack2(kz[2 * u + 8], kz[2 * u + 9]), pack2(kz[2 * u + 12], kz[2 * u + 13]));                 \
    if (t < 2) st_rlx(g_zpart + (slot + t * 16) * 8 + g, mark(__float_as_uint(t ? kz[18] : kz[16]), tag & 1)); \
    if (lane < 2) red_inc(XC1(hg, R) + warp * 2 + lane);                                                          \
  } while (0)
#define K_PUB(R) do { fence_async_smem(); __syncwarp(); if (lane == 0) mbar_arrive(bar + B_PHI + 8 * (R)); } while (0)
#define S_PIN(S) SCHED_PIN(S[0] + S[1] + S[2] + S[3])
      k_exp(p, c0, c1, ea, sa);
      S_PIN(sa);
      QNEXT(1);
      K_NORM(sa);
      k_exp<0, 4>(p + 16, c0, c1, eb, sc);
      mbar_wait(bar + B_FFN, 0);
      K_STORE_(0, ea, sa, 0, 1);
      S_PIN(sc);
      QNEXT(2);
      K_STORE_(0, ea, sa, 1, 2);
      k_exp<4, 8>(p + 16, c0, c1, eb, sc);
      K_NORM(sc);
      S_PIN(sc);
      QNEXT(3);
      K_STORE(1, eb, sc);
      K_PUB(0);
      k_exp<0, 4>(p + 32, c0, c1, ea, sa);
      S_PIN(sa);
      QKV(4, 0);
      k_exp<4, 8>(p + 32, c0, c1, ea, sa);
      K_NORM(sa);
      k_exp<0, 4>(p + 48, c0, c1, eb, sc);
      SCHED_PIN(sa[0] + sa[1] + sa[2] + sa[3] + sc[2] + sc[3]);
      QNEXT(5);
      KV_SEND(0);
      k_exp<4, 8>(p + 48, c0, c1, eb, sc);
      S_PIN(sc);
      QNEXT(6);
      K_NORM(sc);
      mbar_wait(bar + B_KVST, 0);
      V_STORE(1);
      K_STORE(0, ea, sa);
      QNEXT(7);
      K_STORE(1, eb, sc);
      K_PUB(1);
      QKV(8, 1);
      QNEXT(9);
      KV_SEND(1);
    }
    PROFC(3);
#pragma unroll 1
    for (int j = 10; j < 15; j++) QPLAIN(j);
    mbar_wait(bar + B_CSQ, 0);
    QWAIT(15);
    if (wg == 1) bar_sync(6, 256);
    wg_fence();
    wgmma_n128_rs_ta0_tb1(q, fa0, fa1, 0u, 0u, mkdesc(sb + SM_CST + 2048, 512, 0, 1), 1);
    QMMA(15, Q_AOFF(15) / 16, 1);
    wg_commit();
    if (wg == 0) asm volatile("bar.arrive 6, 256;" ::: "memory");
    wg_wait<1>();
    QREL(14);
    wg_wait<0>();
    QREL(15);
    reg_fence<64>(q);
    PROFC(5);
    float yp[4];
    const uint32_t par = tag & 1;
    uint4* ofr = g_ofr + (mb * 16 + hg * 2) * 1024 + (warp * 16 + g) * 8;
#define O_MMA(H, F, N)                                                                                       \
  do {                                                                                                       \
    wg_fence();                                                                                              \
    _Pragma("unroll") for (int k = 0; k < 4; k++) {                                                          \
      const uint32_t ks = SM_V + (H) * 4096 + k * 1024;                                                      \
      wgmma_n40_rs_ta0_tb1(N + 20 * (k >> 1), F[4 * k], F[4 * k + 1], F[4 * k + 2], F[4 * k + 3],            \
                           mkdesc(sb + ks, SM_ZT + (H) * 1024 + k * 16 - ks, 512, 2), k & 1);                \
    }                                                                                                        \
    wg_commit();                                                                                             \
  } while (0)
#define O_FIN(H, N, o)                                                                                        \
  do {                                                                                                       \
    reg_fence<40>(N);                                                                                        \
    const float *np = N, *nm = N + 20;                                                                       \
    const float d0 = rcp(fmaf(np[16], nm[17], fmaf(nm[16], np[17], 1e-6f * np[17] * nm[17])));               \
    const float d1 = rcp(fmaf(np[18], nm[19], fmaf(nm[18], np[19], 1e-6f * np[19] * nm[19])));               \
    const float bp0 = nm[17] * d0, bm0 = np[17] * d0, bp1 = nm[19] * d1, bm1 = np[19] * d1;                  \
    _Pragma("unroll") for (int j = 0; j < 4; j++) {                                                          \
      o[2 * j] = pack2(fmaf(np[4 * j], bp0, nm[4 * j] * bm0), fmaf(np[4 * j + 1], bp0, nm[4 * j + 1] * bm0)); \
      o[2 * j + 1] = pack2(fmaf(np[4 * j + 2], bp1, nm[4 * j + 2] * bm1), fmaf(np[4 * j + 3], bp1, nm[4 * j + 3] * bm1)); \
    }                                                                                                        \
  } while (0)
#define O_STG(H, o)                                                                                          \
  _Pragma("unroll") for (int u = 0; u < 2; u++) {                                                            \
    uint32_t v_[4];                                                                                          \
    _Pragma("unroll") for (int j = 0; j < 4; j++) v_[j] = lop_select(o[2 * j + u], parm, vword == j);        \
    st_rlx128(ofr + ((H) >> 1) * 1024 + u * 64 + ((((H) & 1) * 4 + t) ^ g), v_[0], v_[1], v_[2], v_[3]);     \
  }
    uint32_t gf[32], ao[16];
    const uint32_t parm = 0u - par, vword = ((t ^ g) & 1) == (g >> 2) ? g & 3 : 4;
    const float rh0 = 0.5f * st0.y, rh1 = 0.5f * st1.y, mh0 = st0.x * rh0, mh1 = st1.x * rh1;
#define GATE_LD(J) ldsm4(sb + ((J) >> 2 ? SM_X1 : SM_X0) + sw128 + (((((J) & 3) * 2 + hi16) ^ x128) << 4), gf[4 * (J)], gf[4 * (J) + 1], gf[4 * (J) + 2], gf[4 * (J) + 3])
#define GATE(I0, I1)                                                                                         \
  _Pragma("unroll") for (int i = (I0); i < (I1); i++) {                                                      \
    const float rs = (i & 1) ? rh1 : rh0, mh = (i & 1) ? mh1 : mh0;                                          \
    const float h0 = fmaf(bf_lo(gf[i]), rs, mh), h1 = fmaf(bf_hi(gf[i]), rs, mh);                            \
    gf[i] = pack2(fmaf(h0, tanh_approx(h0), h0), fmaf(h1, tanh_approx(h1), h1));                             \
  }
#define GATE_PIN(I0, I1) do { uint32_t o_ = 0; _Pragma("unroll") for (int i = (I0); i < (I1); i++) o_ |= gf[i]; SCHED_PIN(__uint_as_float(o_)); } while (0)
    {
      float p[64], na[40], nb[40];
      uint32_t fa[16], fb[16];
      {
        uint32_t nq[4] = {0u, 0u, 0u, 0u};
        PHI_PROJ(p, q, 0, 2);
        SCHED_FENCE();
        PHI_PROJ(p, q, 2, 4);
        const bool unsafe = softmax_unsafe(nq, c0 * c0 * wn, c1 * c1 * wn);
        wg_wait<0>();
        reg_fence<64>(p);
        PROFC(24);
        if (__builtin_expect(unsafe, 0)) softmax_shift(p, c0, c1);
      }
      float dn[32];
#define DN_PART(A, B)                                                                                        \
  do {                                                                                                       \
    wg_fence();                                                                                              \
    _Pragma("unroll") for (int i = (A); i < (B); i++)                                                        \
      wgmma_n8_ss_ta1_tb1(dn + 4 * (i >> 1), mkdesc(sb + (i >> 3) * Q_STAGE + (i & 7) * 2048, 16, 1024, 1, wg * (2 * Q_STAGE / 16)), \
                          mkdesc(sb + SM_HT + (i & 1) * 256, 128, 128, 0), i & 1);                           \
  } while (0)
#define F_PIN(F, A, B) do { uint32_t o_ = 0; _Pragma("unroll") for (int i = (A); i < (B); i++) o_ |= F[8 + i]; SCHED_PIN(__uint_as_float(o_)); } while (0)
#define RMMA(J, A, ACCUM)                                                                                    \
  do {                                                                                                       \
    wg_fence();                                                                                              \
    _Pragma("unroll") for (int k = 0; k < 4; k++)                                                            \
      wgmma_n128_rs_ta0_tb1(q, (A)[4 * k], (A)[4 * k + 1], (A)[4 * k + 2], (A)[4 * k + 3],                   \
                            mkdesc(sb + 16384 + k * 2048, 8192, 1024, 1, ((J) & 3) * (Q_STAGE / 16)), k ? 1 : (ACCUM)); \
    wg_commit();                                                                                             \
  } while (0)
#define RSTEP(J, A, ACCUM) do { QWAIT(J); RMMA(J, A, ACCUM); } while (0)
      PROFC(4);
      q_exp(p, c0, c1, fa);
      q_exp(p + 16, c0, c1, fb);
      F_PIN(fb, 0, 8);
      mbar_wait(bar + B_TILE, 0);
      O_MMA(0, fa, na);
      O_MMA(1, fb, nb);
      PROFC(25);
      wg_wait<1>();
      O_FIN(0, na, ao);
      O_STG(0, ao);
      wg_wait<0>();
      O_FIN(1, nb, (ao + 8));
      O_STG(1, (ao + 8));
      PROFC(28);
      mbar_wait(bar + B_H, 0);
      mbar_wait(bar + B_DN, 0);
      PROFC(45);
      DN_PART(0, 16);
      wg_commit();
      wg_wait<0>();
      reg_fence<32>(dn);
#pragma unroll
      for (int i = 0; i < 4; i++) yp[i] = t & 2 ? (t & 1 ? dn[24 + 2 * i] : dn[16 + 2 * i]) : (t & 1 ? dn[8 + 2 * i] : dn[2 * i]);
      RSTEP(16, ao, 0);
      SCHED_FENCE();
      q_exp(p + 32, c0, c1, fa);
      F_PIN(fa, 0, 8);
      if (lane == 0) mbar_arrive(bar + B_DND);
      q_exp(p + 48, c0, c1, fb);
      F_PIN(fb, 0, 8);
      wg_wait<0>();
      QREL(16);
      PROFC(29);
      mbar_wait(bar + B_TILE + 8, 0);
      PROFC(23);
      if (bid < NFFN) {
        float* y = g_y[par ^ 1][bid & 7] + wg * 512 + t * 128 + w * 16 + g;
#pragma unroll
        for (int i = 0; i < 4; i++) red1(y + (i >> 1) * 64 + (i & 1) * 8, yp[i]);
      }
      SCHED_FENCE();
      O_MMA(2, fa, na);
      O_MMA(3, fb, nb);
      __syncwarp();
      if (lane == 0) mbar_arrive(bar + B_YD);
      wg_wait<1>();
      O_FIN(2, na, ao);
      O_STG(2, ao);
      wg_wait<0>();
      O_FIN(3, nb, (ao + 8));
      O_STG(3, (ao + 8));
      PROFC(6);
    }
    RSTEP(17, ao, 1);
    SCHED_FENCE();
    GATE_LD(0); GATE_LD(1);
    GATE(0, 4);
    GATE_PIN(0, 4);
#define GSTEP(J, I) do { QNEXT(J); if ((I) < 7) GATE_LD(((I) + 1) & 7); GATE(4 * (I), 4 * (I) + 4); GATE_PIN(4 * (I), 4 * (I) + 4); } while (0)
    GSTEP(18, 1); GSTEP(19, 2); GSTEP(20, 3); GSTEP(21, 4); GSTEP(22, 5); GSTEP(23, 6); GSTEP(24, 7);
#pragma unroll 1
    for (int j = 25; j < 32 - TAILN; j++) QPLAIN(j);
    if (wg == 1) bar_sync(6, 256);
#pragma unroll 1
    for (int j = 32 - TAILN; j < 32; j++) QSTEP_A(j, (j & 3) * (Q_STAGE / 16), 1);
    if (wg == 0) asm volatile("bar.arrive 6, 256;" ::: "memory");
    mbar_wait(bar + B_UPD, 0);
    {
      const int sel = __float_as_int(lds32(sb + SM_UPD + 256)) - (wg * 64 + w * 16 + g);
      if (sel == 0 || sel == 8) {
#pragma unroll
        for (int j = 0; j < 16; j++) {
          const uint32_t u = __float_as_uint(lds32(sb + SM_UPD + j * 16 + t * 4));
          if (sel) gf[2 * j + 1] = u; else gf[2 * j] = u;
        }
      }
      __syncwarp();
      uint32_t xf[32];
#pragma unroll
      for (int j = 0; j < 8; j++)
        ldsm4(sb + (j >> 2 ? SM_X1 : SM_X0) + sw128 + ((((j & 3) * 2 + hi16) ^ x128) << 4), xf[4 * j], xf[4 * j + 1], xf[4 * j + 2], xf[4 * j + 3]);
      wg_wait<0>();
      reg_fence<64>(q);
      PROFC(8);
#pragma unroll
      for (int j = 0; j < 8; j++) {
        uint32_t o[4];
#pragma unroll
        for (int i = 0; i < 4; i++) o[i] = badd2(xf[4 * j + i], bmul2(pack2(q[8 * j + 2 * i], q[8 * j + 2 * i + 1]), gf[4 * j + i]));
        stsm4(sb + (j >> 2 ? SM_X1 : SM_X0) + sw128 + ((((j & 3) * 2 + hi16) ^ x128) << 4), o[0], o[1], o[2], o[3]);
      }
    }
    fence_async_smem();
    bar_sync(2 + wg, 128);
    if (w == 0 && elect_one()) {
      tma_store2d(&mOut, sb + SM_X0 + wg * 8192, hg * 128, mb * 128 + wg * 64);
      tma_store2d(&mOut, sb + SM_X1 + wg * 8192, hg * 128 + 64, mb * 128 + wg * 64);
      bulk_commit();
      bulk_wait_read0();
      if (wg == 1) { PROF(9); PROFT(33); PROF_DUMP; }
    }
  }
}

typedef CUresult (*EncodeFn)(CUtensorMap*, CUtensorMapDataType, cuuint32_t, void*, const cuuint64_t*, const cuuint64_t*, const cuuint32_t*,
                             const cuuint32_t*, CUtensorMapInterleave, CUtensorMapSwizzle, CUtensorMapL2promotion, CUtensorMapFloatOOBfill);

CUtensorMap make_map(EncodeFn enc, const void* ptr, int rank, const cuuint64_t* dims, const cuuint64_t* strides, const cuuint32_t* box, CUtensorMapSwizzle sw) {
  CUtensorMap m;
  const cuuint32_t es[5] = {1, 1, 1, 1, 1};
  enc(&m, CU_TENSOR_MAP_DATA_TYPE_BFLOAT16, rank, (void*)ptr, dims, strides, box, es, CU_TENSOR_MAP_INTERLEAVE_NONE, sw,
      CU_TENSOR_MAP_L2_PROMOTION_L2_128B, CU_TENSOR_MAP_FLOAT_OOB_FILL_NONE);
  return m;
}

}

extern "C" void kernel_launch(void* const* d_in, const int* in_sizes, int n_in, void* d_out, int out_size) {
  static EncodeFn enc = nullptr;
  static int by_sm = 0;
  if (!enc) {
    void* fn = nullptr;
    cudaDriverEntryPointQueryResult qr;
    cudaGetDriverEntryPoint("cuTensorMapEncodeTiled", &fn, cudaEnableDefault, &qr);
    enc = (EncodeFn)fn;
    cudaFuncSetAttribute(fused_kernel<false>, cudaFuncAttributeMaxDynamicSharedMemorySize, SM_TOTAL);
    cudaFuncSetAttribute(fused_kernel<true>, cudaFuncAttributeMaxDynamicSharedMemorySize, SM_TOTAL);
    int dev = 0, sms = 0;
    cudaGetDevice(&dev);
    cudaDeviceGetAttribute(&sms, cudaDevAttrMultiProcessorCount, dev);
    by_sm = BY_SM && sms == NCTA + NSPARE;
  }
  Params P;
  P.x = (const __nv_bfloat16*)d_in[0];
  P.wqkv = (const __nv_bfloat16*)d_in[1];
  const void* wphi = d_in[2];
  P.wo = (const __nv_bfloat16*)d_in[3];
  P.w_r = (const __nv_bfloat16*)d_in[5];
  P.w_gate = (const __nv_bfloat16*)d_in[6];
  P.w_up = (const __nv_bfloat16*)d_in[7];
  P.w_down = (const __nv_bfloat16*)d_in[8];

  const cuuint64_t dX[2] = {DM, SEQ}, sX[1] = {DM * 2};
  const cuuint32_t b128[2] = {64, 128}, b64[2] = {64, 64};
  const cuuint64_t dW[4] = {64, DM, 16, 3}, sW[3] = {3 * DM * 2, 128, DM * 2};
  const cuuint32_t bKV[4] = {64, 64, 2, 2}, bQ[4] = {64, 64, 2, 1};
  const cuuint64_t dO[3] = {64, DM, 16}, sO[2] = {DM * 2, 128};
  const cuuint32_t bO[3] = {64, 64, 2};
  const cuuint64_t dP[2] = {32, 1024}, sP[1] = {64};
  const cuuint32_t bP[2] = {32, 128};
  CUtensorMap mX = make_map(enc, P.x, 2, dX, sX, b128, CU_TENSOR_MAP_SWIZZLE_128B);
  CUtensorMap mWkv = make_map(enc, P.wqkv, 4, dW, sW, bKV, CU_TENSOR_MAP_SWIZZLE_128B);
  CUtensorMap mWq = make_map(enc, P.wqkv, 4, dW, sW, bQ, CU_TENSOR_MAP_SWIZZLE_128B);
  CUtensorMap mWo = make_map(enc, P.wo, 3, dO, sO, bO, CU_TENSOR_MAP_SWIZZLE_128B);
  CUtensorMap mPhi = make_map(enc, wphi, 2, dP, sP, bP, CU_TENSOR_MAP_SWIZZLE_64B);
  const cuuint64_t dWp[5] = {DM, 2, 4, 4, DM / 32}, sWp[4] = {DM * 2, 8 * DM * 2, 2 * DM * 2, 32 * DM * 2};
  const cuuint32_t bWp[5] = {64, 2, 4, 4, 2};
  CUtensorMap mWp = make_map(enc, P.wo, 5, dWp, sWp, bWp, CU_TENSOR_MAP_SWIZZLE_128B);
  CUtensorMap mOut = make_map(enc, d_out, 2, dX, sX, b64, CU_TENSOR_MAP_SWIZZLE_128B);
  const cuuint64_t dWc[2] = {3 * DM, DM}, sWc[1] = {3 * DM * 2}, dG[2] = {FF, DM}, sG[1] = {FF * 2}, dD[3] = {64, FF, 16};
  const cuuint32_t b32[2] = {32, 32}, bD[3] = {64, 32, 4};
  CUtensorMap mWc = make_map(enc, P.wqkv, 2, dWc, sWc, b32, CU_TENSOR_MAP_SWIZZLE_NONE);
  CUtensorMap mG = make_map(enc, P.w_gate, 2, dG, sG, b32, CU_TENSOR_MAP_SWIZZLE_NONE);
  CUtensorMap mU = make_map(enc, P.w_up, 2, dG, sG, b32, CU_TENSOR_MAP_SWIZZLE_NONE);
  CUtensorMap mD = make_map(enc, P.w_down, 3, dD, sO, bD, CU_TENSOR_MAP_SWIZZLE_128B);
  const cuuint64_t dXs[3] = {256, SEQ, 4}, sXs[2] = {DM * 2, 512};
  const cuuint32_t bXs[3] = {256, 16, 2};
  CUtensorMap mXs = make_map(enc, P.x, 3, dXs, sXs, bXs, CU_TENSOR_MAP_SWIZZLE_NONE);
  const cuuint64_t dG2[4] = {64, DM, FF / 64, 1}, sG2[3] = {FF * 2, 128, (cuuint64_t)FF * DM * 2};
  CUtensorMap mG2 = make_map(enc, P.w_gate, 4, dG2, sG2, bQ, CU_TENSOR_MAP_SWIZZLE_128B);
  CUtensorMap mU2 = make_map(enc, P.w_up, 4, dG2, sG2, bQ, CU_TENSOR_MAP_SWIZZLE_128B);
  (by_sm ? fused_kernel<true> : fused_kernel<false>)<<<NCTA + NSPARE, 384, SM_TOTAL, cudaStreamPerThread>>>(mX, mWkv, mWq, mWo, mPhi, mWp, mOut, mWc, mG, mU, mD, mXs,
                                                                                                           mG2, mU2, P);
}
```

```cpp
#include <cuda_runtime.h>
#include <cuda_bf16.h>
#include <cuda.h>
#include <stdint.h>

namespace {

constexpr int SEQ = 2048, DM = 1024, FF = 3584;
constexpr int NCTA = 128;
constexpr int NSPARE = 4;
constexpr int NFFN = FF / 32;
#define GN 6
#define G8 2
constexpr int GROWS = (3 * GN + G8) * 32;
#define TAILN 2
#define XS_EARLY 1
#define PF_FIRST 2
#define PF_W 5
#define PFD 80
#define BY_SM 1
#define PTAB 0x73216540u
#define REG_C 224
#define REG_H 56
#define SP_DELAY 2000
#define XSTR 288
#define AM_NS 100
constexpr bool FFN_OFF = false;

static_assert(2 * REG_C + REG_H <= 3 * 168, "the register pool of the CTA is 384 x 168");

__device__ uint32_t g_epoch[(NCTA + NSPARE) * 32];
__device__ unsigned long long g_stat[SEQ];
__device__ __align__(128) unsigned long long g_best[NCTA];
__device__ __align__(16) float g_y[2][8][DM];
__device__ __align__(128) uint32_t g_ycnt[64];
__device__ __align__(1024) uint32_t g_xcnt[32 * XSTR];
#define XC1(HG, R) (g_xcnt + ((HG) * 2 + (R)) * XSTR)
#define XC2(HG, R) (g_xcnt + (16 + (HG) * 2 + (R)) * XSTR)
__device__ __align__(128) uint4 g_res[2][32 * 256];
__device__ __align__(16) float g_cs[5 * DM];
__device__ __align__(128) float g_gp[2 * FF];
__device__ uint4 g_part[8 * 2 * 16 * 16 * 32];
__device__ __align__(16) float g_zpart[8 * 2 * 16 * 16 * 8];
__device__ __align__(128) float g_zres[32 * 64];
__device__ __align__(1024) uint4 g_ofr[16 * 16 * 1024];
#define PROF(i)
#define PROFT(i)
#define PROFC(i)
#define PROF_DUMP
#define PW0(J)
#define PW1(J)

constexpr uint32_t KV_STAGE = 49152, Q_STAGE = 32768;
constexpr uint32_t SM_V = 147456;
constexpr uint32_t SM_PHI = 163840;
constexpr uint32_t SM_XST = 147456;
constexpr uint32_t SM_FST = 172032;
constexpr uint32_t SM_PST0 = 196608, SM_PST1 = SM_PHI + 8192;
constexpr uint32_t SM_X0 = 131072, SM_X1 = SM_PHI + 16384;
constexpr uint32_t SM_WPHI = 204800;
constexpr uint32_t SM_ZT = 212992;
constexpr uint32_t SM_SDT = 217088;
constexpr uint32_t SM_CST = 219136;
constexpr uint32_t SM_HT = 222720;
constexpr uint32_t SM_STAT = 223232;
constexpr uint32_t SM_XSEL = 224256;
constexpr uint32_t SM_RED = 228352;
constexpr uint32_t SM_ROWS = SM_RED + 832;
constexpr uint32_t SM_GRED = SM_XSEL + 3072;
static_assert(GROWS <= 768, "xsel area");
constexpr uint32_t SM_UPD = 229632;
constexpr uint32_t SM_BAR = 230016;
constexpr uint32_t SM_PROF = 230464;
constexpr uint32_t SM_SINK = 231104;
constexpr uint32_t SM_TOTAL = 231616;
constexpr uint32_t SB = 1024;
constexpr uint32_t B_FULLKV = 0  , B_FST = 24  , B_XST = 104  , B_WPHI = 120, B_CS = 128, B_CSQ = 136, B_UPD = 144,
                   B_H = 152, B_DN = 160, B_XS = 168, B_TILE = 176  , B_RES = 192  , B_PART = 208  , B_AIN = 224  ,
                   B_FULLQ = 288  ,
                   B_FFN = 320,
                   B_EMPTYKV = 328  , B_EMPTYQ = 352  , B_KVST = 384  , B_YD = 400, B_PHI = 408  , B_DND = 424, B_END = 432;

__device__ __forceinline__ uint32_t smem_u32(const void* p) { return (uint32_t)__cvta_generic_to_shared(p); }
__device__ __forceinline__ void mbar_init(uint32_t bar, uint32_t cnt) { asm volatile("mbarrier.init.shared::cta.b64 [%0], %1;" ::"r"(bar), "r"(cnt) : "memory"); }
__device__ __forceinline__ void mbar_expect_tx(uint32_t bar, uint32_t bytes) { asm volatile("mbarrier.arrive.expect_tx.shared::cta.b64 _, [%0], %1;" ::"r"(bar), "r"(bytes) : "memory"); }
__device__ __forceinline__ void mbar_arrive2(uint32_t bar) { asm volatile("mbarrier.arrive.shared::cta.b64 _, [%0], 2;" ::"r"(bar) : "memory"); }
__device__ __forceinline__ void mbar_arrive(uint32_t bar) { asm volatile("mbarrier.arrive.shared::cta.b64 _, [%0];" ::"r"(bar) : "memory"); }
__device__ __forceinline__ void mbar_wait(uint32_t bar, uint32_t parity) {
  asm volatile("{\n.reg .pred p;\nLW:\nmbarrier.try_wait.parity.shared::cta.b64 p, [%0], %1;\n@!p bra LW;\n}" ::"r"(bar), "r"(parity) : "memory");
}
__device__ __forceinline__ bool mbar_test(uint32_t bar, uint32_t parity) {
  uint32_t ok;
  asm volatile("{\n.reg .pred p;\nmbarrier.test_wait.parity.shared::cta.b64 p, [%1], %2;\nselp.u32 %0, 1, 0, p;\n}" : "=r"(ok) : "r"(bar), "r"(parity) : "memory");
  return ok;
}
__device__ __forceinline__ int lane_id() { int l; asm volatile("mov.u32 %0, %%laneid;" : "=r"(l)); return l; }
template <int C> __device__ __forceinline__ void sched_fence_(int zero) {
  asm volatile("{\n.reg .pred p;\nsetp.eq.s32 p, %0, %1;\n@p trap;\n}" ::"r"(zero), "n"(C) : "memory");
}
#define SCHED_FENCE() sched_fence_<1000 + __COUNTER__>(zero)
#define SCHED_PIN(V) sched_fence_<1000 + __COUNTER__>(zero & __float_as_int(V))
__device__ __forceinline__ bool elect_one() {
  uint32_t p; asm volatile("{ .reg .pred P; elect.sync _|P, 0xffffffff; selp.u32 %0, 1, 0, P; }" : "=r"(p)); return p;
}
__device__ __forceinline__ void tma2d(uint32_t dst, const CUtensorMap* m, int x, int y, uint32_t bar) {
  asm volatile("cp.async.bulk.tensor.2d.shared::cluster.global.mbarrier::complete_tx::bytes [%0], [%1, {%3, %4}], [%2];" ::"r"(dst), "l"(m), "r"(bar), "r"(x), "r"(y) : "memory");
}
__device__ __forceinline__ void tma3d(uint32_t dst, const CUtensorMap* m, int x, int y, int z, uint32_t bar) {
  asm volatile("cp.async.bulk.tensor.3d.shared::cluster.global.mbarrier::complete_tx::bytes [%0], [%1, {%3, %4, %5}], [%2];" ::"r"(dst), "l"(m), "r"(bar), "r"(x), "r"(y), "r"(z) : "memory");
}
__device__ __forceinline__ void tma4d(uint32_t dst, const CUtensorMap* m, int x, int y, int z, int w, uint32_t bar) {
  asm volatile("cp.async.bulk.tensor.4d.shared::cluster.global.mbarrier::complete_tx::bytes [%0], [%1, {%3, %4, %5, %6}], [%2];" ::"r"(dst), "l"(m), "r"(bar), "r"(x), "r"(y), "r"(z), "r"(w) : "memory");
}
__device__ __forceinline__ void tma5d(uint32_t dst, const CUtensorMap* m, int x, int v, uint32_t bar) {
  asm volatile("cp.async.bulk.tensor.5d.shared::cluster.global.mbarrier::complete_tx::bytes [%0], [%1, {%3, %5, %5, %5, %4}], [%2];" ::"r"(dst), "l"(m), "r"(bar), "r"(x), "r"(v), "r"(0) : "memory");
}
__device__ __forceinline__ void tma_store2d(const CUtensorMap* m, uint32_t src, int x, int y) {
  asm volatile("cp.async.bulk.tensor.2d.global.shared::cta.bulk_group [%0, {%2, %3}], [%1];" ::"l"(m), "r"(src), "r"(x), "r"(y) : "memory");
}
__device__ __forceinline__ void bulk_load(uint32_t dst, const void* src, uint32_t bytes, uint32_t bar) {
  asm volatile("cp.async.bulk.shared::cluster.global.mbarrier::complete_tx::bytes [%0], [%1], %2, [%3];" ::"r"(dst), "l"(src), "r"(bytes), "r"(bar) : "memory");
}
__device__ __forceinline__ void bulk_commit() { asm volatile("cp.async.bulk.commit_group;" ::: "memory"); }
__device__ __forceinline__ void bulk_wait_read0() { asm volatile("cp.async.bulk.wait_group.read 0;" ::: "memory"); }
__device__ __forceinline__ void prefetch_l2(const void* p) { asm volatile("prefetch.global.L2 [%0];" ::"l"(p) : "memory"); }
__device__ __forceinline__ void touch_l2(const void* p, int lane) { asm volatile("cp.async.cg.shared.global.L2::128B [%0], [%1], 16;" ::"r"(SB + SM_SINK + lane * 16), "l"(p) : "memory"); }
__device__ __forceinline__ void cp_async16(uint32_t dst, const void* src) { asm volatile("cp.async.cg.shared.global [%0], [%1], 16;" ::"r"(dst), "l"(src) : "memory"); }
__device__ __forceinline__ void prefetch_map(const CUtensorMap* m) { asm volatile("prefetch.tensormap [%0];" ::"l"(m) : "memory"); }
__device__ __forceinline__ void fence_async_smem() { asm volatile("fence.proxy.async.shared::cta;" ::: "memory"); }
__device__ __forceinline__ void fence_async_global() { asm volatile("fence.proxy.async.global;" ::: "memory"); }
__device__ __forceinline__ void bar_sync(int id, int n) { asm volatile("bar.sync %0, %1;" ::"r"(id), "r"(n) : "memory"); }
__device__ __forceinline__ void wg_fence() { asm volatile("wgmma.fence.sync.aligned;" ::: "memory"); }
__device__ __forceinline__ void wg_commit() { asm volatile("wgmma.commit_group.sync.aligned;" ::: "memory"); }
template <int N> __device__ __forceinline__ void wg_wait() { asm volatile("wgmma.wait_group.sync.aligned %0;" ::"n"(N) : "memory"); }
template <int N> __device__ __forceinline__ void reg_fence(uint32_t* r) {
#pragma unroll
  for (int i = 0; i < N; i++) asm volatile("" : "+r"(r[i])::"memory");
}
template <int N> __device__ __forceinline__ void reg_fence(float* r) {
#pragma unroll
  for (int i = 0; i < N; i++) asm volatile("" : "+f"(r[i])::"memory");
}
__device__ __forceinline__ uint64_t mkdesc(uint32_t addr, uint32_t lbo, uint32_t sbo, uint32_t swz, uint32_t dyn = 0) {
  const uint32_t lo = ((addr >> 4) | ((lbo >> 4) << 16)) + dyn;
  const uint32_t hi = (sbo >> 4) | (swz << 30);
  uint64_t d;
  asm("mov.b64 %0, {%1, %2};" : "=l"(d) : "r"(lo), "r"(hi));
  return d;
}
__device__ __forceinline__ void stsm4(uint32_t addr, uint32_t a, uint32_t b, uint32_t c, uint32_t d) {
  asm volatile("stmatrix.sync.aligned.m8n8.x4.shared.b16 [%0], {%1, %2, %3, %4};" ::"r"(addr), "r"(a), "r"(b), "r"(c), "r"(d) : "memory");
}
__device__ __forceinline__ void ldsm4(uint32_t addr, uint32_t& a, uint32_t& b, uint32_t& c, uint32_t& d) {
  asm volatile("ldmatrix.sync.aligned.m8n8.x4.shared.b16 {%0, %1, %2, %3}, [%4];" : "=r"(a), "=r"(b), "=r"(c), "=r"(d) : "r"(addr) : "memory");
}
__device__ __forceinline__ uint32_t pack2(float lo, float hi) { uint32_t r; asm("cvt.rn.bf16x2.f32 %0, %1, %2;" : "=r"(r) : "f"(hi), "f"(lo)); return r; }
__device__ __forceinline__ uint32_t bsub2(uint32_t a, uint32_t b) { uint32_t r; asm("sub.rn.bf16x2 %0, %1, %2;" : "=r"(r) : "r"(a), "r"(b)); return r; }
__device__ __forceinline__ uint32_t badd2(uint32_t a, uint32_t b) { uint32_t r; asm("add.rn.bf16x2 %0, %1, %2;" : "=r"(r) : "r"(a), "r"(b)); return r; }
__device__ __forceinline__ uint32_t bmul2(uint32_t a, uint32_t b) { uint32_t r; asm("mul.rn.bf16x2 %0, %1, %2;" : "=r"(r) : "r"(a), "r"(b)); return r; }
__device__ __forceinline__ float bf_lo(uint32_t v) { return __uint_as_float(v << 16); }
__device__ __forceinline__ float bf_hi(uint32_t v) { return __uint_as_float(v & 0xffff0000u); }
__device__ __forceinline__ float bf_round(float v) { return bf_lo(pack2(v, 0.f)); }
__device__ __forceinline__ float ex2(float v) { float r; asm("ex2.approx.ftz.f32 %0, %1;" : "=f"(r) : "f"(v)); return r; }
__device__ __forceinline__ float rcp(float v) { float r; asm("rcp.approx.ftz.f32 %0, %1;" : "=f"(r) : "f"(v)); return r; }
__device__ __forceinline__ float sqrt_approx(float v) { float r; asm("sqrt.approx.f32 %0, %1;" : "=f"(r) : "f"(v)); return r; }
__device__ __forceinline__ float4 lds128(uint32_t a) { float4 v; asm volatile("ld.shared.v4.f32 {%0, %1, %2, %3}, [%4];" : "=f"(v.x), "=f"(v.y), "=f"(v.z), "=f"(v.w) : "r"(a) : "memory"); return v; }
__device__ __forceinline__ uint4 lds128u(uint32_t a) { uint4 v; asm volatile("ld.shared.v4.u32 {%0, %1, %2, %3}, [%4];" : "=r"(v.x), "=r"(v.y), "=r"(v.z), "=r"(v.w) : "r"(a) : "memory"); return v; }
__device__ __forceinline__ float2 lds64(uint32_t a) { float2 v; asm volatile("ld.shared.v2.f32 {%0, %1}, [%2];" : "=f"(v.x), "=f"(v.y) : "r"(a) : "memory"); return v; }
__device__ __forceinline__ float lds32(uint32_t a) { float v; asm volatile("ld.shared.f32 %0, [%1];" : "=f"(v) : "r"(a) : "memory"); return v; }
__device__ __forceinline__ void sts32(uint32_t a, float v) { asm volatile("st.shared.f32 [%0], %1;" ::"r"(a), "f"(v) : "memory"); }
__device__ __forceinline__ void sts64(uint32_t a, float x, float y) { asm volatile("st.shared.v2.f32 [%0], {%1, %2};" ::"r"(a), "f"(x), "f"(y) : "memory"); }
__device__ __forceinline__ void sts128(uint32_t a, float x, float y, float z, float w) { asm volatile("st.shared.v4.f32 [%0], {%1, %2, %3, %4};" ::"r"(a), "f"(x), "f"(y), "f"(z), "f"(w) : "memory"); }
__device__ __forceinline__ void sts64u(uint32_t a, uint32_t x, uint32_t y) { asm volatile("st.shared.v2.u32 [%0], {%1, %2};" ::"r"(a), "r"(x), "r"(y) : "memory"); }
__device__ __forceinline__ void sts128u(uint32_t a, uint32_t x, uint32_t y, uint32_t z, uint32_t w) { asm volatile("st.shared.v4.u32 [%0], {%1, %2, %3, %4};" ::"r"(a), "r"(x), "r"(y), "r"(z), "r"(w) : "memory"); }
__device__ __forceinline__ uint4 ldg_nc(const void* p) { uint4 v; asm volatile("ld.global.nc.L1::no_allocate.v4.u32 {%0, %1, %2, %3}, [%4];" : "=r"(v.x), "=r"(v.y), "=r"(v.z), "=r"(v.w) : "l"(p)); return v; }
__device__ __forceinline__ float4 ldg_cg4(const float* p) { float4 v; asm volatile("ld.global.cg.v4.f32 {%0, %1, %2, %3}, [%4];" : "=f"(v.x), "=f"(v.y), "=f"(v.z), "=f"(v.w) : "l"(p) : "memory"); return v; }
__device__ __forceinline__ uint32_t ld_acq(const uint32_t* p) { uint32_t v; asm volatile("ld.acquire.gpu.global.u32 %0, [%1];" : "=r"(v) : "l"(p) : "memory"); return v; }
__device__ __forceinline__ unsigned long long ld_rlx64(const unsigned long long* p) { unsigned long long v; asm volatile("ld.relaxed.gpu.global.u64 %0, [%1];" : "=l"(v) : "l"(p) : "memory"); return v; }
__device__ __forceinline__ void st_rlx64(unsigned long long* p, unsigned long long v) { asm volatile("st.relaxed.gpu.global.u64 [%0], %1;" ::"l"(p), "l"(v) : "memory"); }
__device__ __forceinline__ uint4 ld_rlx128(const void* p) {
  uint4 v;
  asm volatile("{ .reg .b128 t; .reg .b64 a, b; ld.relaxed.gpu.global.b128 t, [%4]; mov.b128 {a, b}, t; mov.b64 {%0, %1}, a; mov.b64 {%2, %3}, b; }"
               : "=r"(v.x), "=r"(v.y), "=r"(v.z), "=r"(v.w) : "l"(p) : "memory");
  return v;
}
__device__ __forceinline__ void st_rlx128(void* p, uint32_t x, uint32_t y, uint32_t z, uint32_t w) {
  asm volatile("{ .reg .b128 t; .reg .b64 a, b; mov.b64 a, {%1, %2}; mov.b64 b, {%3, %4}; mov.b128 t, {a, b}; st.relaxed.gpu.global.b128 [%0], t; }"
               ::"l"(p), "r"(x), "r"(y), "r"(z), "r"(w) : "memory");
}
__device__ __forceinline__ void st_rlx(void* p, uint32_t v) { asm volatile("st.relaxed.gpu.global.u32 [%0], %1;" ::"l"(p), "r"(v) : "memory"); }
__device__ __forceinline__ uint32_t lop_select(uint32_t a, uint32_t b, uint32_t m) { uint32_t r; asm("lop3.b32 %0, %1, %2, %3, 0xd8;" : "=r"(r) : "r"(a), "r"(b), "r"(m)); return r; }
__device__ __forceinline__ float unmark(uint32_t v) { return __uint_as_float(v & ~1u); }
__device__ __forceinline__ uint32_t mark(uint32_t v, uint32_t par) { return (v & ~1u) | par; }
__device__ __forceinline__ float tanh_approx(float v) { float r; asm("tanh.approx.f32 %0, %1;" : "=f"(r) : "f"(v)); return r; }
__device__ __forceinline__ void red1(float* p, float a) { asm volatile("red.global.add.f32 [%0], %1;" ::"l"(p), "f"(a) : "memory"); }
__device__ __forceinline__ void red_inc(uint32_t* p) { asm volatile("red.relaxed.gpu.global.add.u32 [%0], 1;" ::"l"(p) : "memory"); }
__device__ __forceinline__ void red_rel(uint32_t* p) { asm volatile("red.release.gpu.global.add.u32 [%0], 1;" ::"l"(p) : "memory"); }
constexpr int SPIN_MAX = 100000;
__device__ __forceinline__ uint32_t ld_rlx(const uint32_t* p) { uint32_t v; asm volatile("ld.relaxed.gpu.global.u32 %0, [%1];" : "=r"(v) : "l"(p) : "memory"); return v; }
template <int NS = 0> __device__ __forceinline__ void wait_hint(const uint32_t* p, uint32_t target) {
#pragma unroll 1
  for (int i = 0; i < SPIN_MAX; i++) { if ((int)(ld_rlx(p) - target) >= 0) break; if (NS) __nanosleep(NS); }
}
template <int NS> __device__ __forceinline__ void wait_cnt(const uint32_t* p, uint32_t target) {
#pragma unroll 1
  for (int i = 0; i < SPIN_MAX; i++) { if ((int)(ld_rlx(p) - target) >= 0) break; if (NS) __nanosleep(NS); }
  (void)ld_acq(p);
}
template <int NS> __device__ __forceinline__ unsigned long long wait_tag(const unsigned long long* p, uint32_t tag) {
  unsigned long long v = 0;
#pragma unroll 1
  for (int i = 0; i < SPIN_MAX; i++) { v = ld_rlx64(p); if ((uint32_t)(v >> 32) == tag) break; if (NS) __nanosleep(NS); }
  return v;
}
__device__ __forceinline__ float silu_f(float v) { return v * rcp(1.f + ex2(-1.4426950408889634f * v)); }

__device__ __forceinline__ void wgmma_n8_ss_ta1_tb0(float* d, uint64_t da, uint64_t db, bool accumulate) {
  if (accumulate) {
    asm volatile("{\n.reg .pred p;\nsetp.ne.b32 p, 1, 0;\n"
      "wgmma.mma_async.sync.aligned.m64n8k16.f32.bf16.bf16 "
      "{%0, %1, %2, %3}, "
      "%4, %5, p, 1, 1, 1, 0;\n}\n"
      : "+f"(d[0]), "+f"(d[1]), "+f"(d[2]), "+f"(d[3])
      : "l"(da), "l"(db));
  } else {
    asm volatile("{\n.reg .pred p;\nsetp.ne.b32 p, 0, 0;\n"
      "wgmma.mma_async.sync.aligned.m64n8k16.f32.bf16.bf16 "
      "{%0, %1, %2, %3}, "
      "%4, %5, p, 1, 1, 1, 0;\n}\n"
      : "=f"(d[0]), "=f"(d[1]), "=f"(d[2]), "=f"(d[3])
      : "l"(da), "l"(db));
  }
}
__device__ __forceinline__ void wgmma_n8_ss_ta1_tb1(float* d, uint64_t da, uint64_t db, bool accumulate) {
  if (accumulate) {
    asm volatile("{\n.reg .pred p;\nsetp.ne.b32 p, 1, 0;\n"
      "wgmma.mma_async.sync.aligned.m64n8k16.f32.bf16.bf16 "
      "{%0, %1, %2, %3}, "
      "%4, %5, p, 1, 1, 1, 1;\n}\n"
      : "+f"(d[0]), "+f"(d[1]), "+f"(d[2]), "+f"(d[3])
      : "l"(da), "l"(db));
  } else {
    asm volatile("{\n.reg .pred p;\nsetp.ne.b32 p, 0, 0;\n"
      "wgmma.mma_async.sync.aligned.m64n8k16.f32.bf16.bf16 "
      "{%0, %1, %2, %3}, "
      "%4, %5, p, 1, 1, 1, 1;\n}\n"
      : "=f"(d[0]), "=f"(d[1]), "=f"(d[2]), "=f"(d[3])
      : "l"(da), "l"(db));
  }
}
__device__ __forceinline__ void wgmma_n32_rs_ta0_tb1(float* d, uint32_t a0, uint32_t a1, uint32_t a2, uint32_t a3, uint64_t db, bool accumulate) {
  if (accumulate) {
    asm volatile("{\n.reg .pred p;\nsetp.ne.b32 p, 1, 0;\n"
      "wgmma.mma_async.sync.aligned.m64n32k16.f32.bf16.bf16 "
      "{%0, %1, %2, %3, %4, %5, %6, %7, %8, %9, %10, %11, %12, %13, %14, %15}, "
      "{%16, %17, %18, %19}, %20, p, 1, 1, 1;\n}\n"
      : "+f"(d[0]), "+f"(d[1]), "+f"(d[2]), "+f"(d[3]), "+f"(d[4]), "+f"(d[5]), "+f"(d[6]), "+f"(d[7]), "+f"(d[8]), "+f"(d[9]), "+f"(d[10]), "+f"(d[11]), "+f"(d[12]), "+f"(d[13]), "+f"(d[14]), "+f"(d[15])
      : "r"(a0), "r"(a1), "r"(a2), "r"(a3), "l"(db));
  } else {
    asm volatile("{\n.reg .pred p;\nsetp.ne.b32 p, 0, 0;\n"
      "wgmma.mma_async.sync.aligned.m64n32k16.f32.bf16.bf16 "
      "{%0, %1, %2, %3, %4, %5, %6, %7, %8, %9, %10, %11, %12, %13, %14, %15}, "
      "{%16, %17, %18, %19}, %20, p, 1, 1, 1;\n}\n"
      : "=f"(d[0]), "=f"(d[1]), "=f"(d[2]), "=f"(d[3]), "=f"(d[4]), "=f"(d[5]), "=f"(d[6]), "=f"(d[7]), "=f"(d[8]), "=f"(d[9]), "=f"(d[10]), "=f"(d[11]), "=f"(d[12]), "=f"(d[13]), "=f"(d[14]), "=f"(d[15])
      : "r"(a0), "r"(a1), "r"(a2), "r"(a3), "l"(db));
  }
}
__device__ __forceinline__ void wgmma_n40_rs_ta0_tb1(float* d, uint32_t a0, uint32_t a1, uint32_t a2, uint32_t a3, uint64_t db, bool accumulate) {
  if (accumulate) {
    asm volatile("{\n.reg .pred p;\nsetp.ne.b32 p, 1, 0;\n"
      "wgmma.mma_async.sync.aligned.m64n40k16.f32.bf16.bf16 "
      "{%0, %1, %2, %3, %4, %5, %6, %7, %8, %9, %10, %11, %12, %13, %14, %15, %16, %17, %18, %19}, "
      "{%20, %21, %22, %23}, %24, p, 1, 1, 1;\n}\n"
      : "+f"(d[0]), "+f"(d[1]), "+f"(d[2]), "+f"(d[3]), "+f"(d[4]), "+f"(d[5]), "+f"(d[6]), "+f"(d[7]), "+f"(d[8]), "+f"(d[9]), "+f"(d[10]), "+f"(d[11]), "+f"(d[12]), "+f"(d[13]), "+f"(d[14]), "+f"(d[15]), "+f"(d[16]), "+f"(d[17]), "+f"(d[18]), "+f"(d[19])
      : "r"(a0), "r"(a1), "r"(a2), "r"(a3), "l"(db));
  } else {
    asm volatile("{\n.reg .pred p;\nsetp.ne.b32 p, 0, 0;\n"
      "wgmma.mma_async.sync.aligned.m64n40k16.f32.bf16.bf16 "
      "{%0, %1, %2, %3, %4, %5, %6, %7, %8, %9, %10, %11, %12, %13, %14, %15, %16, %17, %18, %19}, "
      "{%20, %21, %22, %23}, %24, p, 1, 1, 1;\n}\n"
      : "=f"(d[0]), "=f"(d[1]), "=f"(d[2]), "=f"(d[3]), "=f"(d[4]), "=f"(d[5]), "=f"(d[6]), "=f"(d[7]), "=f"(d[8]), "=f"(d[9]), "=f"(d[10]), "=f"(d[11]), "=f"(d[12]), "=f"(d[13]), "=f"(d[14]), "=f"(d[15]), "=f"(d[16]), "=f"(d[17]), "=f"(d[18]), "=f"(d[19])
      : "r"(a0), "r"(a1), "r"(a2), "r"(a3), "l"(db));
  }
}
__device__ __forceinline__ void wgmma_n40_ss_ta1_tb1(float* d, uint64_t da, uint64_t db, bool accumulate) {
  if (accumulate) {
    asm volatile("{\n.reg .pred p;\nsetp.ne.b32 p, 1, 0;\n"
      "wgmma.mma_async.sync.aligned.m64n40k16.f32.bf16.bf16 "
      "{%0, %1, %2, %3, %4, %5, %6, %7, %8, %9, %10, %11, %12, %13, %14, %15, %16, %17, %18, %19}, "
      "%20, %21, p, 1, 1, 1, 1;\n}\n"
      : "+f"(d[0]), "+f"(d[1]), "+f"(d[2]), "+f"(d[3]), "+f"(d[4]), "+f"(d[5]), "+f"(d[6]), "+f"(d[7]), "+f"(d[8]), "+f"(d[9]), "+f"(d[10]), "+f"(d[11]), "+f"(d[12]), "+f"(d[13]), "+f"(d[14]), "+f"(d[15]), "+f"(d[16]), "+f"(d[17]), "+f"(d[18]), "+f"(d[19])
      : "l"(da), "l"(db));
  } else {
    asm volatile("{\n.reg .pred p;\nsetp.ne.b32 p, 0, 0;\n"
      "wgmma.mma_async.sync.aligned.m64n40k16.f32.bf16.bf16 "
      "{%0, %1, %2, %3, %4, %5, %6, %7, %8, %9, %10, %11, %12, %13, %14, %15, %16, %17, %18, %19}, "
      "%20, %21, p, 1, 1, 1, 1;\n}\n"
      : "=f"(d[0]), "=f"(d[1]), "=f"(d[2]), "=f"(d[3]), "=f"(d[4]), "=f"(d[5]), "=f"(d[6]), "=f"(d[7]), "=f"(d[8]), "=f"(d[9]), "=f"(d[10]), "=f"(d[11]), "=f"(d[12]), "=f"(d[13]), "=f"(d[14]), "=f"(d[15]), "=f"(d[16]), "=f"(d[17]), "=f"(d[18]), "=f"(d[19])
      : "l"(da), "l"(db));
  }
}
__device__ __forceinline__ void wgmma_n128_rs_ta0_tb1(float* d, uint32_t a0, uint32_t a1, uint32_t a2, uint32_t a3, uint64_t db, bool accumulate) {
  if (accumulate) {
    asm volatile("{\n.reg .pred p;\nsetp.ne.b32 p, 1, 0;\n"
      "wgmma.mma_async.sync.aligned.m64n128k16.f32.bf16.bf16 "
      "{%0, %1, %2, %3, %4, %5, %6, %7, %8, %9, %10, %11, %12, %13, %14, %15, %16, %17, %18, %19, %20, %21, %22, %23, %24, %25, %26, %27, %28, %29, %30, %31, %32, %33, %34, %35, %36, %37, %38, %39, %40, %41, %42, %43, %44, %45, %46, %47, %48, %49, %50, %51, %52, %53, %54, %55, %56, %57, %58, %59, %60, %61, %62, %63}, "
      "{%64, %65, %66, %67}, %68, p, 1, 1, 1;\n}\n"
      : "+f"(d[0]), "+f"(d[1]), "+f"(d[2]), "+f"(d[3]), "+f"(d[4]), "+f"(d[5]), "+f"(d[6]), "+f"(d[7]), "+f"(d[8]), "+f"(d[9]), "+f"(d[10]), "+f"(d[11]), "+f"(d[12]), "+f"(d[13]), "+f"(d[14]), "+f"(d[15]), "+f"(d[16]), "+f"(d[17]), "+f"(d[18]), "+f"(d[19]), "+f"(d[20]), "+f"(d[21]), "+f"(d[22]), "+f"(d[23]), "+f"(d[24]), "+f"(d[25]), "+f"(d[26]), "+f"(d[27]), "+f"(d[28]), "+f"(d[29]), "+f"(d[30]), "+f"(d[31]), "+f"(d[32]), "+f"(d[33]), "+f"(d[34]), "+f"(d[35]), "+f"(d[36]), "+f"(d[37]), "+f"(d[38]), "+f"(d[39]), "+f"(d[40]), "+f"(d[41]), "+f"(d[42]), "+f"(d[43]), "+f"(d[44]), "+f"(d[45]), "+f"(d[46]), "+f"(d[47]), "+f"(d[48]), "+f"(d[49]), "+f"(d[50]), "+f"(d[51]), "+f"(d[52]), "+f"(d[53]), "+f"(d[54]), "+f"(d[55]), "+f"(d[56]), "+f"(d[57]), "+f"(d[58]), "+f"(d[59]), "+f"(d[60]), "+f"(d[61]), "+f"(d[62]), "+f"(d[63])
      : "r"(a0), "r"(a1), "r"(a2), "r"(a3), "l"(db));
  } else {
    asm volatile("{\n.reg .pred p;\nsetp.ne.b32 p, 0, 0;\n"
      "wgmma.mma_async.sync.aligned.m64n128k16.f32.bf16.bf16 "
      "{%0, %1, %2, %3, %4, %5, %6, %7, %8, %9, %10, %11, %12, %13, %14, %15, %16, %17, %18, %19, %20, %21, %22, %23, %24, %25, %26, %27, %28, %29, %30, %31, %32, %33, %34, %35, %36, %37, %38, %39, %40, %41, %42, %43, %44, %45, %46, %47, %48, %49, %50, %51, %52, %53, %54, %55, %56, %57, %58, %59, %60, %61, %62, %63}, "
      "{%64, %65, %66, %67}, %68, p, 1, 1, 1;\n}\n"
      : "=f"(d[0]), "=f"(d[1]), "=f"(d[2]), "=f"(d[3]), "=f"(d[4]), "=f"(d[5]), "=f"(d[6]), "=f"(d[7]), "=f"(d[8]), "=f"(d[9]), "=f"(d[10]), "=f"(d[11]), "=f"(d[12]), "=f"(d[13]), "=f"(d[14]), "=f"(d[15]), "=f"(d[16]), "=f"(d[17]), "=f"(d[18]), "=f"(d[19]), "=f"(d[20]), "=f"(d[21]), "=f"(d[22]), "=f"(d[23]), "=f"(d[24]), "=f"(d[25]), "=f"(d[26]), "=f"(d[27]), "=f"(d[28]), "=f"(d[29]), "=f"(d[30]), "=f"(d[31]), "=f"(d[32]), "=f"(d[33]), "=f"(d[34]), "=f"(d[35]), "=f"(d[36]), "=f"(d[37]), "=f"(d[38]), "=f"(d[39]), "=f"(d[40]), "=f"(d[41]), "=f"(d[42]), "=f"(d[43]), "=f"(d[44]), "=f"(d[45]), "=f"(d[46]), "=f"(d[47]), "=f"(d[48]), "=f"(d[49]), "=f"(d[50]), "=f"(d[51]), "=f"(d[52]), "=f"(d[53]), "=f"(d[54]), "=f"(d[55]), "=f"(d[56]), "=f"(d[57]), "=f"(d[58]), "=f"(d[59]), "=f"(d[60]), "=f"(d[61]), "=f"(d[62]), "=f"(d[63])
      : "r"(a0), "r"(a1), "r"(a2), "r"(a3), "l"(db));
  }
}
__device__ __forceinline__ void wgmma_n128_ss_ta0_tb1(float* d, uint64_t da, uint64_t db, bool accumulate) {
  if (accumulate) {
    asm volatile("{\n.reg .pred p;\nsetp.ne.b32 p, 1, 0;\n"
      "wgmma.mma_async.sync.aligned.m64n128k16.f32.bf16.bf16 "
      "{%0, %1, %2, %3, %4, %5, %6, %7, %8, %9, %10, %11, %12, %13, %14, %15, %16, %17, %18, %19, %20, %21, %22, %23, %24, %25, %26, %27, %28, %29, %30, %31, %32, %33, %34, %35, %36, %37, %38, %39, %40, %41, %42, %43, %44, %45, %46, %47, %48, %49, %50, %51, %52, %53, %54, %55, %56, %57, %58, %59, %60, %61, %62, %63}, "
      "%64, %65, p, 1, 1, 0, 1;\n}\n"
      : "+f"(d[0]), "+f"(d[1]), "+f"(d[2]), "+f"(d[3]), "+f"(d[4]), "+f"(d[5]), "+f"(d[6]), "+f"(d[7]), "+f"(d[8]), "+f"(d[9]), "+f"(d[10]), "+f"(d[11]), "+f"(d[12]), "+f"(d[13]), "+f"(d[14]), "+f"(d[15]), "+f"(d[16]), "+f"(d[17]), "+f"(d[18]), "+f"(d[19]), "+f"(d[20]), "+f"(d[21]), "+f"(d[22]), "+f"(d[23]), "+f"(d[24]), "+f"(d[25]), "+f"(d[26]), "+f"(d[27]), "+f"(d[28]), "+f"(d[29]), "+f"(d[30]), "+f"(d[31]), "+f"(d[32]), "+f"(d[33]), "+f"(d[34]), "+f"(d[35]), "+f"(d[36]), "+f"(d[37]), "+f"(d[38]), "+f"(d[39]), "+f"(d[40]), "+f"(d[41]), "+f"(d[42]), "+f"(d[43]), "+f"(d[44]), "+f"(d[45]), "+f"(d[46]), "+f"(d[47]), "+f"(d[48]), "+f"(d[49]), "+f"(d[50]), "+f"(d[51]), "+f"(d[52]), "+f"(d[53]), "+f"(d[54]), "+f"(d[55]), "+f"(d[56]), "+f"(d[57]), "+f"(d[58]), "+f"(d[59]), "+f"(d[60]), "+f"(d[61]), "+f"(d[62]), "+f"(d[63])
      : "l"(da), "l"(db));
  } else {
    asm volatile("{\n.reg .pred p;\nsetp.ne.b32 p, 0, 0;\n"
      "wgmma.mma_async.sync.aligned.m64n128k16.f32.bf16.bf16 "
      "{%0, %1, %2, %3, %4, %5, %6, %7, %8, %9, %10, %11, %12, %13, %14, %15, %16, %17, %18, %19, %20, %21, %22, %23, %24, %25, %26, %27, %28, %29, %30, %31, %32, %33, %34, %35, %36, %37, %38, %39, %40, %41, %42, %43, %44, %45, %46, %47, %48, %49, %50, %51, %52, %53, %54, %55, %56, %57, %58, %59, %60, %61, %62, %63}, "
      "%64, %65, p, 1, 1, 0, 1;\n}\n"
      : "=f"(d[0]), "=f"(d[1]), "=f"(d[2]), "=f"(d[3]), "=f"(d[4]), "=f"(d[5]), "=f"(d[6]), "=f"(d[7]), "=f"(d[8]), "=f"(d[9]), "=f"(d[10]), "=f"(d[11]), "=f"(d[12]), "=f"(d[13]), "=f"(d[14]), "=f"(d[15]), "=f"(d[16]), "=f"(d[17]), "=f"(d[18]), "=f"(d[19]), "=f"(d[20]), "=f"(d[21]), "=f"(d[22]), "=f"(d[23]), "=f"(d[24]), "=f"(d[25]), "=f"(d[26]), "=f"(d[27]), "=f"(d[28]), "=f"(d[29]), "=f"(d[30]), "=f"(d[31]), "=f"(d[32]), "=f"(d[33]), "=f"(d[34]), "=f"(d[35]), "=f"(d[36]), "=f"(d[37]), "=f"(d[38]), "=f"(d[39]), "=f"(d[40]), "=f"(d[41]), "=f"(d[42]), "=f"(d[43]), "=f"(d[44]), "=f"(d[45]), "=f"(d[46]), "=f"(d[47]), "=f"(d[48]), "=f"(d[49]), "=f"(d[50]), "=f"(d[51]), "=f"(d[52]), "=f"(d[53]), "=f"(d[54]), "=f"(d[55]), "=f"(d[56]), "=f"(d[57]), "=f"(d[58]), "=f"(d[59]), "=f"(d[60]), "=f"(d[61]), "=f"(d[62]), "=f"(d[63])
      : "l"(da), "l"(db));
  }
}
__device__ __forceinline__ void wgmma_n256_rs_ta0_tb1(float* d, uint32_t a0, uint32_t a1, uint32_t a2, uint32_t a3, uint64_t db, bool accumulate) {
  if (accumulate) {
    asm volatile("{\n.reg .pred p;\nsetp.ne.b32 p, 1, 0;\n"
      "wgmma.mma_async.sync.aligned.m64n256k16.f32.bf16.bf16 "
      "{%0, %1, %2, %3, %4, %5, %6, %7, %8, %9, %10, %11, %12, %13, %14, %15, %16, %17, %18, %19, %20, %21, %22, %23, %24, %25, %26, %27, %28, %29, %30, %31, %32, %33, %34, %35, %36, %37, %38, %39, %40, %41, %42, %43, %44, %45, %46, %47, %48, %49, %50, %51, %52, %53, %54, %55, %56, %57, %58, %59, %60, %61, %62, %63, %64, %65, %66, %67, %68, %69, %70, %71, %72, %73, %74, %75, %76, %77, %78, %79, %80, %81, %82, %83, %84, %85, %86, %87, %88, %89, %90, %91, %92, %93, %94, %95, %96, %97, %98, %99, %100, %101, %102, %103, %104, %105, %106, %107, %108, %109, %110, %111, %112, %113, %114, %115, %116, %117, %118, %119, %120, %121, %122, %123, %124, %125, %126, %127}, "
      "{%128, %129, %130, %131}, %132, p, 1, 1, 1;\n}\n"
      : "+f"(d[0]), "+f"(d[1]), "+f"(d[2]), "+f"(d[3]), "+f"(d[4]), "+f"(d[5]), "+f"(d[6]), "+f"(d[7]), "+f"(d[8]), "+f"(d[9]), "+f"(d[10]), "+f"(d[11]), "+f"(d[12]), "+f"(d[13]), "+f"(d[14]), "+f"(d[15]), "+f"(d[16]), "+f"(d[17]), "+f"(d[18]), "+f"(d[19]), "+f"(d[20]), "+f"(d[21]), "+f"(d[22]), "+f"(d[23]), "+f"(d[24]), "+f"(d[25]), "+f"(d[26]), "+f"(d[27]), "+f"(d[28]), "+f"(d[29]), "+f"(d[30]), "+f"(d[31]), "+f"(d[32]), "+f"(d[33]), "+f"(d[34]), "+f"(d[35]), "+f"(d[36]), "+f"(d[37]), "+f"(d[38]), "+f"(d[39]), "+f"(d[40]), "+f"(d[41]), "+f"(d[42]), "+f"(d[43]), "+f"(d[44]), "+f"(d[45]), "+f"(d[46]), "+f"(d[47]), "+f"(d[48]), "+f"(d[49]), "+f"(d[50]), "+f"(d[51]), "+f"(d[52]), "+f"(d[53]), "+f"(d[54]), "+f"(d[55]), "+f"(d[56]), "+f"(d[57]), "+f"(d[58]), "+f"(d[59]), "+f"(d[60]), "+f"(d[61]), "+f"(d[62]), "+f"(d[63]), "+f"(d[64]), "+f"(d[65]), "+f"(d[66]), "+f"(d[67]), "+f"(d[68]), "+f"(d[69]), "+f"(d[70]), "+f"(d[71]), "+f"(d[72]), "+f"(d[73]), "+f"(d[74]), "+f"(d[75]), "+f"(d[76]), "+f"(d[77]), "+f"(d[78]), "+f"(d[79]), "+f"(d[80]), "+f"(d[81]), "+f"(d[82]), "+f"(d[83]), "+f"(d[84]), "+f"(d[85]), "+f"(d[86]), "+f"(d[87]), "+f"(d[88]), "+f"(d[89]), "+f"(d[90]), "+f"(d[91]), "+f"(d[92]), "+f"(d[93]), "+f"(d[94]), "+f"(d[95]), "+f"(d[96]), "+f"(d[97]), "+f"(d[98]), "+f"(d[99]), "+f"(d[100]), "+f"(d[101]), "+f"(d[102]), "+f"(d[103]), "+f"(d[104]), "+f"(d[105]), "+f"(d[106]), "+f"(d[107]), "+f"(d[108]), "+f"(d[109]), "+f"(d[110]), "+f"(d[111]), "+f"(d[112]), "+f"(d[113]), "+f"(d[114]), "+f"(d[115]), "+f"(d[116]), "+f"(d[117]), "+f"(d[118]), "+f"(d[119]), "+f"(d[120]), "+f"(d[121]), "+f"(d[122]), "+f"(d[123]), "+f"(d[124]), "+f"(d[125]), "+f"(d[126]), "+f"(d[127])
      : "r"(a0), "r"(a1), "r"(a2), "r"(a3), "l"(db));
  } else {
    asm volatile("{\n.reg .pred p;\nsetp.ne.b32 p, 0, 0;\n"
      "wgmma.mma_async.sync.aligned.m64n256k16.f32.bf16.bf16 "
      "{%0, %1, %2, %3, %4, %5, %6, %7, %8, %9, %10, %11, %12, %13, %14, %15, %16, %17, %18, %19, %20, %21, %22, %23, %24, %25, %26, %27, %28, %29, %30, %31, %32, %33, %34, %35, %36, %37, %38, %39, %40, %41, %42, %43, %44, %45, %46, %47, %48, %49, %50, %51, %52, %53, %54, %55, %56, %57, %58, %59, %60, %61, %62, %63, %64, %65, %66, %67, %68, %69, %70, %71, %72, %73, %74, %75, %76, %77, %78, %79, %80, %81, %82, %83, %84, %85, %86, %87, %88, %89, %90, %91, %92, %93, %94, %95, %96, %97, %98, %99, %100, %101, %102, %103, %104, %105, %106, %107, %108, %109, %110, %111, %112, %113, %114, %115, %116, %117, %118, %119, %120, %121, %122, %123, %124, %125, %126, %127}, "
      "{%128, %129, %130, %131}, %132, p, 1, 1, 1;\n}\n"
      : "=f"(d[0]), "=f"(d[1]), "=f"(d[2]), "=f"(d[3]), "=f"(d[4]), "=f"(d[5]), "=f"(d[6]), "=f"(d[7]), "=f"(d[8]), "=f"(d[9]), "=f"(d[10]), "=f"(d[11]), "=f"(d[12]), "=f"(d[13]), "=f"(d[14]), "=f"(d[15]), "=f"(d[16]), "=f"(d[17]), "=f"(d[18]), "=f"(d[19]), "=f"(d[20]), "=f"(d[21]), "=f"(d[22]), "=f"(d[23]), "=f"(d[24]), "=f"(d[25]), "=f"(d[26]), "=f"(d[27]), "=f"(d[28]), "=f"(d[29]), "=f"(d[30]), "=f"(d[31]), "=f"(d[32]), "=f"(d[33]), "=f"(d[34]), "=f"(d[35]), "=f"(d[36]), "=f"(d[37]), "=f"(d[38]), "=f"(d[39]), "=f"(d[40]), "=f"(d[41]), "=f"(d[42]), "=f"(d[43]), "=f"(d[44]), "=f"(d[45]), "=f"(d[46]), "=f"(d[47]), "=f"(d[48]), "=f"(d[49]), "=f"(d[50]), "=f"(d[51]), "=f"(d[52]), "=f"(d[53]), "=f"(d[54]), "=f"(d[55]), "=f"(d[56]), "=f"(d[57]), "=f"(d[58]), "=f"(d[59]), "=f"(d[60]), "=f"(d[61]), "=f"(d[62]), "=f"(d[63]), "=f"(d[64]), "=f"(d[65]), "=f"(d[66]), "=f"(d[67]), "=f"(d[68]), "=f"(d[69]), "=f"(d[70]), "=f"(d[71]), "=f"(d[72]), "=f"(d[73]), "=f"(d[74]), "=f"(d[75]), "=f"(d[76]), "=f"(d[77]), "=f"(d[78]), "=f"(d[79]), "=f"(d[80]), "=f"(d[81]), "=f"(d[82]), "=f"(d[83]), "=f"(d[84]), "=f"(d[85]), "=f"(d[86]), "=f"(d[87]), "=f"(d[88]), "=f"(d[89]), "=f"(d[90]), "=f"(d[91]), "=f"(d[92]), "=f"(d[93]), "=f"(d[94]), "=f"(d[95]), "=f"(d[96]), "=f"(d[97]), "=f"(d[98]), "=f"(d[99]), "=f"(d[100]), "=f"(d[101]), "=f"(d[102]), "=f"(d[103]), "=f"(d[104]), "=f"(d[105]), "=f"(d[106]), "=f"(d[107]), "=f"(d[108]), "=f"(d[109]), "=f"(d[110]), "=f"(d[111]), "=f"(d[112]), "=f"(d[113]), "=f"(d[114]), "=f"(d[115]), "=f"(d[116]), "=f"(d[117]), "=f"(d[118]), "=f"(d[119]), "=f"(d[120]), "=f"(d[121]), "=f"(d[122]), "=f"(d[123]), "=f"(d[124]), "=f"(d[125]), "=f"(d[126]), "=f"(d[127])
      : "r"(a0), "r"(a1), "r"(a2), "r"(a3), "l"(db));
  }
}
__device__ __forceinline__ void wgmma_n256_ss_ta0_tb1(float* d, uint64_t da, uint64_t db, bool accumulate) {
  if (accumulate) {
    asm volatile("{\n.reg .pred p;\nsetp.ne.b32 p, 1, 0;\n"
      "wgmma.mma_async.sync.aligned.m64n256k16.f32.bf16.bf16 "
      "{%0, %1, %2, %3, %4, %5, %6, %7, %8, %9, %10, %11, %12, %13, %14, %15, %16, %17, %18, %19, %20, %21, %22, %23, %24, %25, %26, %27, %28, %29, %30, %31, %32, %33, %34, %35, %36, %37, %38, %39, %40, %41, %42, %43, %44, %45, %46, %47, %48, %49, %50, %51, %52, %53, %54, %55, %56, %57, %58, %59, %60, %61, %62, %63, %64, %65, %66, %67, %68, %69, %70, %71, %72, %73, %74, %75, %76, %77, %78, %79, %80, %81, %82, %83, %84, %85, %86, %87, %88, %89, %90, %91, %92, %93, %94, %95, %96, %97, %98, %99, %100, %101, %102, %103, %104, %105, %106, %107, %108, %109, %110, %111, %112, %113, %114, %115, %116, %117, %118, %119, %120, %121, %122, %123, %124, %125, %126, %127}, "
      "%128, %129, p, 1, 1, 0, 1;\n}\n"
      : "+f"(d[0]), "+f"(d[1]), "+f"(d[2]), "+f"(d[3]), "+f"(d[4]), "+f"(d[5]), "+f"(d[6]), "+f"(d[7]), "+f"(d[8]), "+f"(d[9]), "+f"(d[10]), "+f"(d[11]), "+f"(d[12]), "+f"(d[13]), "+f"(d[14]), "+f"(d[15]), "+f"(d[16]), "+f"(d[17]), "+f"(d[18]), "+f"(d[19]), "+f"(d[20]), "+f"(d[21]), "+f"(d[22]), "+f"(d[23]), "+f"(d[24]), "+f"(d[25]), "+f"(d[26]), "+f"(d[27]), "+f"(d[28]), "+f"(d[29]), "+f"(d[30]), "+f"(d[31]), "+f"(d[32]), "+f"(d[33]), "+f"(d[34]), "+f"(d[35]), "+f"(d[36]), "+f"(d[37]), "+f"(d[38]), "+f"(d[39]), "+f"(d[40]), "+f"(d[41]), "+f"(d[42]), "+f"(d[43]), "+f"(d[44]), "+f"(d[45]), "+f"(d[46]), "+f"(d[47]), "+f"(d[48]), "+f"(d[49]), "+f"(d[50]), "+f"(d[51]), "+f"(d[52]), "+f"(d[53]), "+f"(d[54]), "+f"(d[55]), "+f"(d[56]), "+f"(d[57]), "+f"(d[58]), "+f"(d[59]), "+f"(d[60]), "+f"(d[61]), "+f"(d[62]), "+f"(d[63]), "+f"(d[64]), "+f"(d[65]), "+f"(d[66]), "+f"(d[67]), "+f"(d[68]), "+f"(d[69]), "+f"(d[70]), "+f"(d[71]), "+f"(d[72]), "+f"(d[73]), "+f"(d[74]), "+f"(d[75]), "+f"(d[76]), "+f"(d[77]), "+f"(d[78]), "+f"(d[79]), "+f"(d[80]), "+f"(d[81]), "+f"(d[82]), "+f"(d[83]), "+f"(d[84]), "+f"(d[85]), "+f"(d[86]), "+f"(d[87]), "+f"(d[88]), "+f"(d[89]), "+f"(d[90]), "+f"(d[91]), "+f"(d[92]), "+f"(d[93]), "+f"(d[94]), "+f"(d[95]), "+f"(d[96]), "+f"(d[97]), "+f"(d[98]), "+f"(d[99]), "+f"(d[100]), "+f"(d[101]), "+f"(d[102]), "+f"(d[103]), "+f"(d[104]), "+f"(d[105]), "+f"(d[106]), "+f"(d[107]), "+f"(d[108]), "+f"(d[109]), "+f"(d[110]), "+f"(d[111]), "+f"(d[112]), "+f"(d[113]), "+f"(d[114]), "+f"(d[115]), "+f"(d[116]), "+f"(d[117]), "+f"(d[118]), "+f"(d[119]), "+f"(d[120]), "+f"(d[121]), "+f"(d[122]), "+f"(d[123]), "+f"(d[124]), "+f"(d[125]), "+f"(d[126]), "+f"(d[127])
      : "l"(da), "l"(db));
  } else {
    asm volatile("{\n.reg .pred p;\nsetp.ne.b32 p, 0, 0;\n"
      "wgmma.mma_async.sync.aligned.m64n256k16.f32.bf16.bf16 "
      "{%0, %1, %2, %3, %4, %5, %6, %7, %8, %9, %10, %11, %12, %13, %14, %15, %16, %17, %18, %19, %20, %21, %22, %23, %24, %25, %26, %27, %28, %29, %30, %31, %32, %33, %34, %35, %36, %37, %38, %39, %40, %41, %42, %43, %44, %45, %46, %47, %48, %49, %50, %51, %52, %53, %54, %55, %56, %57, %58, %59, %60, %61, %62, %63, %64, %65, %66, %67, %68, %69, %70, %71, %72, %73, %74, %75, %76, %77, %78, %79, %80, %81, %82, %83, %84, %85, %86, %87, %88, %89, %90, %91, %92, %93, %94, %95, %96, %97, %98, %99, %100, %101, %102, %103, %104, %105, %106, %107, %108, %109, %110, %111, %112, %113, %114, %115, %116, %117, %118, %119, %120, %121, %122, %123, %124, %125, %126, %127}, "
      "%128, %129, p, 1, 1, 0, 1;\n}\n"
      : "=f"(d[0]), "=f"(d[1]), "=f"(d[2]), "=f"(d[3]), "=f"(d[4]), "=f"(d[5]), "=f"(d[6]), "=f"(d[7]), "=f"(d[8]), "=f"(d[9]), "=f"(d[10]), "=f"(d[11]), "=f"(d[12]), "=f"(d[13]), "=f"(d[14]), "=f"(d[15]), "=f"(d[16]), "=f"(d[17]), "=f"(d[18]), "=f"(d[19]), "=f"(d[20]), "=f"(d[21]), "=f"(d[22]), "=f"(d[23]), "=f"(d[24]), "=f"(d[25]), "=f"(d[26]), "=f"(d[27]), "=f"(d[28]), "=f"(d[29]), "=f"(d[30]), "=f"(d[31]), "=f"(d[32]), "=f"(d[33]), "=f"(d[34]), "=f"(d[35]), "=f"(d[36]), "=f"(d[37]), "=f"(d[38]), "=f"(d[39]), "=f"(d[40]), "=f"(d[41]), "=f"(d[42]), "=f"(d[43]), "=f"(d[44]), "=f"(d[45]), "=f"(d[46]), "=f"(d[47]), "=f"(d[48]), "=f"(d[49]), "=f"(d[50]), "=f"(d[51]), "=f"(d[52]), "=f"(d[53]), "=f"(d[54]), "=f"(d[55]), "=f"(d[56]), "=f"(d[57]), "=f"(d[58]), "=f"(d[59]), "=f"(d[60]), "=f"(d[61]), "=f"(d[62]), "=f"(d[63]), "=f"(d[64]), "=f"(d[65]), "=f"(d[66]), "=f"(d[67]), "=f"(d[68]), "=f"(d[69]), "=f"(d[70]), "=f"(d[71]), "=f"(d[72]), "=f"(d[73]), "=f"(d[74]), "=f"(d[75]), "=f"(d[76]), "=f"(d[77]), "=f"(d[78]), "=f"(d[79]), "=f"(d[80]), "=f"(d[81]), "=f"(d[82]), "=f"(d[83]), "=f"(d[84]), "=f"(d[85]), "=f"(d[86]), "=f"(d[87]), "=f"(d[88]), "=f"(d[89]), "=f"(d[90]), "=f"(d[91]), "=f"(d[92]), "=f"(d[93]), "=f"(d[94]), "=f"(d[95]), "=f"(d[96]), "=f"(d[97]), "=f"(d[98]), "=f"(d[99]), "=f"(d[100]), "=f"(d[101]), "=f"(d[102]), "=f"(d[103]), "=f"(d[104]), "=f"(d[105]), "=f"(d[106]), "=f"(d[107]), "=f"(d[108]), "=f"(d[109]), "=f"(d[110]), "=f"(d[111]), "=f"(d[112]), "=f"(d[113]), "=f"(d[114]), "=f"(d[115]), "=f"(d[116]), "=f"(d[117]), "=f"(d[118]), "=f"(d[119]), "=f"(d[120]), "=f"(d[121]), "=f"(d[122]), "=f"(d[123]), "=f"(d[124]), "=f"(d[125]), "=f"(d[126]), "=f"(d[127])
      : "l"(da), "l"(db));
  }
}
__device__ __forceinline__ void wgmma_n256_ssp_ta0_tb1(float* d, uint64_t da, uint64_t db, int accumulate) {
    asm volatile("{\n.reg .pred p;\nsetp.ne.b32 p, %130, 0;\n"
      "wgmma.mma_async.sync.aligned.m64n256k16.f32.bf16.bf16 "
      "{%0, %1, %2, %3, %4, %5, %6, %7, %8, %9, %10, %11, %12, %13, %14, %15, %16, %17, %18, %19, %20, %21, %22, %23, %24, %25, %26, %27, %28, %29, %30, %31, %32, %33, %34, %35, %36, %37, %38, %39, %40, %41, %42, %43, %44, %45, %46, %47, %48, %49, %50, %51, %52, %53, %54, %55, %56, %57, %58, %59, %60, %61, %62, %63, %64, %65, %66, %67, %68, %69, %70, %71, %72, %73, %74, %75, %76, %77, %78, %79, %80, %81, %82, %83, %84, %85, %86, %87, %88, %89, %90, %91, %92, %93, %94, %95, %96, %97, %98, %99, %100, %101, %102, %103, %104, %105, %106, %107, %108, %109, %110, %111, %112, %113, %114, %115, %116, %117, %118, %119, %120, %121, %122, %123, %124, %125, %126, %127}, "
      "%128, %129, p, 1, 1, 0, 1;\n}\n"
      : "+f"(d[0]), "+f"(d[1]), "+f"(d[2]), "+f"(d[3]), "+f"(d[4]), "+f"(d[5]), "+f"(d[6]), "+f"(d[7]), "+f"(d[8]), "+f"(d[9]), "+f"(d[10]), "+f"(d[11]), "+f"(d[12]), "+f"(d[13]), "+f"(d[14]), "+f"(d[15]), "+f"(d[16]), "+f"(d[17]), "+f"(d[18]), "+f"(d[19]), "+f"(d[20]), "+f"(d[21]), "+f"(d[22]), "+f"(d[23]), "+f"(d[24]), "+f"(d[25]), "+f"(d[26]), "+f"(d[27]), "+f"(d[28]), "+f"(d[29]), "+f"(d[30]), "+f"(d[31]), "+f"(d[32]), "+f"(d[33]), "+f"(d[34]), "+f"(d[35]), "+f"(d[36]), "+f"(d[37]), "+f"(d[38]), "+f"(d[39]), "+f"(d[40]), "+f"(d[41]), "+f"(d[42]), "+f"(d[43]), "+f"(d[44]), "+f"(d[45]), "+f"(d[46]), "+f"(d[47]), "+f"(d[48]), "+f"(d[49]), "+f"(d[50]), "+f"(d[51]), "+f"(d[52]), "+f"(d[53]), "+f"(d[54]), "+f"(d[55]), "+f"(d[56]), "+f"(d[57]), "+f"(d[58]), "+f"(d[59]), "+f"(d[60]), "+f"(d[61]), "+f"(d[62]), "+f"(d[63]), "+f"(d[64]), "+f"(d[65]), "+f"(d[66]), "+f"(d[67]), "+f"(d[68]), "+f"(d[69]), "+f"(d[70]), "+f"(d[71]), "+f"(d[72]), "+f"(d[73]), "+f"(d[74]), "+f"(d[75]), "+f"(d[76]), "+f"(d[77]), "+f"(d[78]), "+f"(d[79]), "+f"(d[80]), "+f"(d[81]), "+f"(d[82]), "+f"(d[83]), "+f"(d[84]), "+f"(d[85]), "+f"(d[86]), "+f"(d[87]), "+f"(d[88]), "+f"(d[89]), "+f"(d[90]), "+f"(d[91]), "+f"(d[92]), "+f"(d[93]), "+f"(d[94]), "+f"(d[95]), "+f"(d[96]), "+f"(d[97]), "+f"(d[98]), "+f"(d[99]), "+f"(d[100]), "+f"(d[101]), "+f"(d[102]), "+f"(d[103]), "+f"(d[104]), "+f"(d[105]), "+f"(d[106]), "+f"(d[107]), "+f"(d[108]), "+f"(d[109]), "+f"(d[110]), "+f"(d[111]), "+f"(d[112]), "+f"(d[113]), "+f"(d[114]), "+f"(d[115]), "+f"(d[116]), "+f"(d[117]), "+f"(d[118]), "+f"(d[119]), "+f"(d[120]), "+f"(d[121]), "+f"(d[122]), "+f"(d[123]), "+f"(d[124]), "+f"(d[125]), "+f"(d[126]), "+f"(d[127])
      : "l"(da), "l"(db), "r"(accumulate));
}

template <int N> __device__ __forceinline__ void quad_sum(float* m) {
#pragma unroll
  for (int o = 1; o <= 2; o <<= 1) {
    float t[N];
#pragma unroll
    for (int i = 0; i < N; i++) t[i] = __shfl_xor_sync(~0u, m[i], o);
#pragma unroll
    for (int i = 0; i < N; i++) m[i] += t[i];
  }
}
__device__ __forceinline__ bool softmax_unsafe(const uint32_t* t, float l0, float l1) {
  const float m0 = fmaxf(bf_lo(t[0]) + bf_hi(t[0]), bf_lo(t[2]) + bf_hi(t[2])), m1 = fmaxf(bf_lo(t[1]) + bf_hi(t[1]), bf_lo(t[3]) + bf_hi(t[3]));
  return __any_sync(~0u, !(m0 * l0 < 2500.f) | !(m1 * l1 < 2500.f));
}
__device__ __forceinline__ void softmax_shift(float* p, float c0, float c1) {
#pragma unroll 1
  for (int it = 0; it < 8; it++) {
    float mx = p[0], mn = p[0];
#pragma unroll
    for (int j = 1; j < 8; j++) { mx = fmaxf(mx, p[(j >> 1) * 4 + (j & 1)]); mn = fminf(mn, p[(j >> 1) * 4 + (j & 1)]); }
#pragma unroll
    for (int o = 1; o <= 2; o <<= 1) { mx = fmaxf(mx, __shfl_xor_sync(~0u, mx, o)); mn = fminf(mn, __shfl_xor_sync(~0u, mn, o)); }
    const float half = fminf(0.5f * (mx - mn), 50.f * rcp(it & 1 ? c1 : c0));
    float r[8];
#pragma unroll
    for (int j = 0; j < 8; j++) {
      const float v = p[(j >> 1) * 4 + (j & 1)];
      r[j] = fmaxf(v - mx + half, 0.f) + fminf(v - mn - half, 0.f) + (v - v);
    }
#pragma unroll
    for (int k = 0; k < 7; k++)
#pragma unroll
      for (int j = 0; j < 8; j++) p[(k >> 1) * 16 + (k & 1) * 2 + (j >> 1) * 4 + (j & 1)] = p[((k + 1) >> 1) * 16 + ((k + 1) & 1) * 2 + (j >> 1) * 4 + (j & 1)];
#pragma unroll
    for (int j = 0; j < 8; j++) p[50 + (j >> 1) * 4 + (j & 1)] = r[j];
  }
}
template <int J0 = 0, int J1 = 8> __device__ __forceinline__ void k_exp(const float* p, float c0, float c1, float* e, float* s) {
#pragma unroll
  for (int j = J0; j < J1; j++) {
    e[2 * j] = ex2(p[2 * j] * (j & 1 ? c1 : c0));
    e[2 * j + 1] = ex2(p[2 * j + 1] * (j & 1 ? c1 : c0));
    e[16 + j] = rcp(e[2 * j] * e[2 * j + 1]);
    const float t = e[2 * j] + e[2 * j + 1];
    s[j & 1] = j < 2 ? t : s[j & 1] + t;
    s[2 + (j & 1)] = j < 2 ? e[16 + j] * t : fmaf(e[16 + j], t, s[2 + (j & 1)]);
  }
}
template <int J0 = 0, int J1 = 8> __device__ __forceinline__ void q_exp(const float* p, float c0, float c1, uint32_t* f) {
#pragma unroll
  for (int j = J0; j < J1; j++) {
    const float e0 = ex2(p[2 * j] * (j & 1 ? c1 : c0)), e1 = ex2(p[2 * j + 1] * (j & 1 ? c1 : c0)), r = rcp(e0 * e1);
    f[j] = pack2(e0, e1);
    f[8 + j] = bmul2(f[j], pack2(r, r));
  }
}

#define FMA8(A, U, X)                                                                                        \
  A[0] = fmaf(bf_lo(U.x), X, A[0]); A[1] = fmaf(bf_hi(U.x), X, A[1]); A[2] = fmaf(bf_lo(U.y), X, A[2]); A[3] = fmaf(bf_hi(U.y), X, A[3]); \
  A[4] = fmaf(bf_lo(U.z), X, A[4]); A[5] = fmaf(bf_hi(U.z), X, A[5]); A[6] = fmaf(bf_lo(U.w), X, A[6]); A[7] = fmaf(bf_hi(U.w), X, A[7])

__device__ __forceinline__ uint32_t routed_row(const __nv_bfloat16* x, uint32_t tag, int lane, uint4* xr) {
  uint32_t best = 0, sv = 0;
#pragma unroll 1
  for (int it = 0; it < SPIN_MAX; it++) {
    const int sel = 2047 - (best & 0x7ff);
#pragma unroll
    for (int i = 0; i < 4; i++) xr[i] = ldg_nc(x + (size_t)sel * DM + i * 256 + lane * 8);
    const unsigned long long st = ld_rlx64(g_stat + sel);
    const uint4 b0 = ld_rlx128(g_best + lane * 2), b1 = ld_rlx128(g_best + 64 + lane * 2);
    const uint32_t m = __reduce_max_sync(~0u, max(max(b0.y == tag ? b0.x : 0u, b0.w == tag ? b0.z : 0u), max(b1.y == tag ? b1.x : 0u, b1.w == tag ? b1.z : 0u)));
    sv = (uint32_t)st;
    if (__all_sync(~0u, b0.y == tag && b0.w == tag && b1.y == tag && b1.w == tag && m == best && (uint32_t)(st >> 32) == tag)) break;
    best = m;
    if (AM_NS) __nanosleep(AM_NS);
  }
  const uint32_t m2 = (sv & 0xffff0000u) | (sv >> 16);
  const float rs = rcp(bf_lo(sv));
#pragma unroll
  for (int i = 0; i < 4; i++) {
    const uint32_t d0 = bsub2(xr[i].x, m2), d1 = bsub2(xr[i].y, m2), d2 = bsub2(xr[i].z, m2), d3 = bsub2(xr[i].w, m2);
    xr[i] = make_uint4(pack2(bf_lo(d0) * rs, bf_hi(d0) * rs), pack2(bf_lo(d1) * rs, bf_hi(d1) * rs), pack2(bf_lo(d2) * rs, bf_hi(d2) * rs),
                       pack2(bf_lo(d3) * rs, bf_hi(d3) * rs));
  }
  return best;
}

struct Params {
  const __nv_bfloat16 *x, *wqkv, *wo, *w_r, *w_gate, *w_up, *w_down;
};

template <bool BY_SMID> __global__ void __launch_bounds__(384, 1)
fused_kernel(const __grid_constant__ CUtensorMap mX, const __grid_constant__ CUtensorMap mWkv, const __grid_constant__ CUtensorMap mWq,
             const __grid_constant__ CUtensorMap mWo, const __grid_constant__ CUtensorMap mPhi, const __grid_constant__ CUtensorMap mWp,
             const __grid_constant__ CUtensorMap mOut, const __grid_constant__ CUtensorMap mWc,
             const __grid_constant__ CUtensorMap mG, const __grid_constant__ CUtensorMap mU, const __grid_constant__ CUtensorMap mD,
             const __grid_constant__ CUtensorMap mXs, const __grid_constant__ CUtensorMap mG2, const __grid_constant__ CUtensorMap mU2, const Params P) {
  constexpr uint32_t sb = SB, bar = SB + SM_BAR;
  int bid = blockIdx.x;
  if (BY_SMID) {
    uint32_t sm;
    asm volatile("mov.u32 %0, %%smid;" : "=r"(sm));
    const uint32_t tq = (sm - 64) >> 1, q7 = (tq * 37) >> 8;
    const uint32_t gpc = sm < 64 ? (sm >> 1) & 7 : 1 + tq - 7 * q7, idx = (sm < 64 ? sm >> 4 : 4 + q7) * 2 + (sm & 1);
    bid = sm < 120 ? ((PTAB >> (4 * gpc)) & 7) * 16 + idx : sm < 124 ? sm + 8 : sm - 116;
  }
  const int hg = ((bid >> 2) & 3) + 4 * ((bid >> 4) & 1), mb = (bid & 3) + 4 * ((bid >> 5) & 3);
  if (bid < NCTA && threadIdx.x < 256) {
    const uint32_t r0 = threadIdx.x >> 3, c = threadIdx.x & 7, dst = sb + 2 * KV_STAGE + r0 * 128 + ((c ^ (r0 & 7)) << 4);
    const char* xs = (const char*)P.x + (size_t)(mb * 128 + r0) * 2048 + c * 16;
    const char* ws = (const char*)P.wqkv + (size_t)r0 * 6144 + 2048 + hg * 256 + c * 16;
#pragma unroll
    for (int i = 0; i < 4; i++) cp_async16(dst + i * 4096, xs + i * 65536);
#pragma unroll
    for (int i = 0; i < 8; i++) cp_async16(dst + 16384 + i * 4096, ws + (i & 1) * 196608 + (i >> 2) * 2048 + ((i >> 1) & 1) * 128);
  }
  extern __shared__ __align__(1024) uint8_t smem[];
  if (smem_u32(smem) != SB) __trap();
  const int warp = __shfl_sync(~0u, threadIdx.x >> 5, 0);

  if (bid >= NCTA) {
    constexpr uint32_t XV = SM_WPHI, ONES = SM_ZT, BF = bar, BE = bar + 48, BX = bar + 96;
    constexpr int NJ = (DM - GROWS) / 64;
    const int lane = lane_id(), sp = bid - NCTA;
    const uint32_t tag = ld_rlx(g_epoch + bid * 32 + lane) + 1;
    if (warp == 8 && elect_one()) {
#pragma unroll 1
      for (int i = 0; i < 13; i++) mbar_init(bar + 8 * i, i >= 6 && i < 12 ? 8 : 1);
    }
    if (warp == 9) { sts64u(sb + ONES + lane * 8, 0x3f803f80u, 0x3f803f80u); fence_async_smem(); }
    __syncthreads();
    if (warp == 8) {
      if (elect_one()) {
        uint32_t s = 0, ph = 1;
        for (const long long c0 = clock64(); clock64() - c0 < SP_DELAY;) {}
#pragma unroll 1
        for (int job = 0; job < 8; job++) {
          const CUtensorMap* m = job == 0 ? &mWq : sp & 2 ? &mU2 : &mG2;
          const int g0 = job ? (sp & 1) * 28 + job * 4 - 4 : sp * 4;
#pragma unroll 1
          for (int row = job ? GROWS : 0; row < DM; row += 64) {
            mbar_wait(BE + 8 * s, ph);
            mbar_expect_tx(BF + 8 * s, Q_STAGE);
            tma4d(sb + s * Q_STAGE, m, 0, row, g0, 0, BF + 8 * s);
            tma4d(sb + s * Q_STAGE + 16384, m, 0, row, g0 + 2, 0, BF + 8 * s);
            if (++s == 6) { s = 0; ph ^= 1; }
          }
        }
      }
    } else if (warp == 9) {
      uint4 xr[4];
      routed_row(P.x, tag, lane, xr);
#pragma unroll
      for (int i = 0; i < 4; i++) sts128u(sb + XV + i * 512 + lane * 16, xr[i].x, xr[i].y, xr[i].z, xr[i].w);
      fence_async_smem();
      __syncwarp();
      if (lane == 0) mbar_arrive(BX);
    } else if (warp < 8) {
      uint32_t s = 0, ph = 0;
#pragma unroll 1
      for (int job = 0; job < 8; job++) {
        float d[8] = {0.f, 0.f, 0.f, 0.f, 0.f, 0.f, 0.f, 0.f};
        if (job == 1) mbar_wait(BX, 0);
#pragma unroll 1
        for (int i = 0; i < (job ? NJ : 16); i++) {
          mbar_wait(BF + 8 * s, ph);
          wg_fence();
#pragma unroll
          for (int k = 0; k < 8; k++)
            wgmma_n8_ss_ta1_tb0(d + 4 * (k >> 2), mkdesc(sb + k * 2048, 16, 1024, 1, s * (Q_STAGE / 16) + (warp >> 2) * 1024),
                                mkdesc(sb, 16, 128, 0, job ? (XV + GROWS * 2) / 16 + i * 8 + (k & 3) * 2 : ONES / 16), 1);
          wg_commit();
          wg_wait<0>();
          if (lane == 0) mbar_arrive(BE + 8 * s);
          if (++s == 6) { s = 0; ph ^= 1; }
        }
        reg_fence<8>(d);
        float* dst = (job ? g_gp + sp * 1792 + job * 256 - 256 : g_cs + sp * 256) + (warp >> 2) * 128 + (warp & 3) * 16 + (lane >> 2);
        if ((lane & 3) == 0) {
#pragma unroll
          for (int i = 0; i < 4; i++) st_rlx(dst + (i >> 1) * 64 + (i & 1) * 8, mark(__float_as_uint(d[2 * i]), tag & 1));
        }
        __syncwarp();
      }
      if (warp == 0) g_epoch[bid * 32 + lane] = tag;
    }
    return;
  }
#define Q_SLAB(J) ((J) < 8 ? ((J) + 8 - 2 * (hg & 4)) & 15 : 2 * (hg & 4) + 2 * ((J) & 3) + ((J) >> 2 & 1))
#define Q_AOFF(J) ((J) == 8 + (hg & 3) ? SM_X0 : (J) == 12 + (hg & 3) ? SM_X1 : ((J) & 3) * Q_STAGE)
#define Q_LOAD(J)                                                                                            \
  do {                                                                                                       \
    const uint32_t fb_ = bar + B_FULLQ + 8 * ((J) & 3);                                                      \
    const int k_ = Q_SLAB(J) * 64;                                                                           \
    mbar_expect_tx(fb_, Q_STAGE);                                                                            \
    mbar_arrive2(fb_);                                                                                       \
    tma2d(sb + Q_AOFF(J), &mX, k_, mb * 128, fb_);                                                           \
    tma4d(sb + ((J) & 3) * Q_STAGE + 16384, &mWq, 0, k_, hg * 2, 0, fb_);                                    \
  } while (0)
  if (warp >= 8) {
    asm volatile("setmaxnreg.dec.sync.aligned.u32 %0;" ::"n"(REG_H));
    const int lane = lane_id();
    const int f = (warp - 9) & 3;
    if (f == 3) {
      if (elect_one()) {
        PROF(0); PROFT(32);
#pragma unroll
        for (int s = 0; s < 3; s++) mbar_init(bar + B_FULLKV + 8 * s, 1);
      }
      __syncwarp();
      asm volatile("bar.arrive 14, 288;" ::: "memory");
      if (elect_one()) {
#pragma unroll
        for (int s = 0; s < 2; s++) {
          mbar_expect_tx(bar + B_FULLKV + 8 * s, KV_STAGE);
          tma2d(sb + s * KV_STAGE, &mX, (s + 1) * 64, mb * 128, bar + B_FULLKV + 8 * s);
          tma4d(sb + s * KV_STAGE + 16384, &mWkv, 0, (s + 1) * 64, hg * 2, 1, bar + B_FULLKV + 8 * s);
        }
      }
      __syncwarp();
    }
    const uint32_t ep = ld_rlx(g_epoch + bid * 32 + lane);
    if (f < 2) {
#pragma unroll
      for (int i = 0; i < 2; i++) {
        const uint4 u = __ldg((const uint4*)P.w_r + (f * 2 + i) * 32 + lane);
        sts128u(sb + SM_XSEL + (f * 2 + i) * 512 + lane * 16, u.x, u.y, u.z, u.w);
      }
    }
    bar_sync(13, 384);
    const uint32_t tag = ep + 1, par = tag & 1;
    const bool ffn = bid < NFFN;
    const int fb = bid, cu = bid >> 1, ch = bid & 1;
#define CS_STORE(SEC, C)                                                                                     \
  _Pragma("unroll") for (int r = 0; r < 3; r++) {                                                            \
    const uint32_t h0 = pack2(C.x, C.y), h1 = pack2(C.z, C.w);                                               \
    sts64u(sb + SM_CST + (SEC) * 1024 + (lane >> 4) * 512 + (lane & 1) * 8 + r * 128 + ((((lane & 15) >> 1) ^ (r + (lane >> 4) * 4)) << 4), h0, h1); \
    C.x -= bf_lo(h0); C.y -= bf_hi(h0); C.z -= bf_lo(h1); C.w -= bf_hi(h1);                                  \
  }
#define BAD4(U) ((U.x ^ par) | (U.y ^ par) | (U.z ^ par) | (U.w ^ par))
    const int n0 = f < 2 ? 0 : 2 * f - 3, ne = FFN_OFF || !ffn ? 3 : f == 3 ? 3 + G8 : 3 + GN;
    const uint32_t fsb = sb + SM_FST + ((f + 1) & 3) * 8192, fbar = bar + B_FST + f * 16, fst = fsb + (lane >> 4) * 2048 + (lane & 15) * 16;
    const CUtensorMap *ma = &mWc, *mc = &mWc;
    int sx = 1024 + cu * 32, sy = ch * 512 + f * 192, sdy = 32;
#define STAGEG(N)                                                                                            \
  do {                                                                                                       \
    if ((N) == 3) { ma = &mG; mc = &mU; sx = fb * 32; sy = f * (GN * 32);  sdy = 0; }                        \
    if ((N) < ne && elect_one()) {                                                                           \
      const uint32_t dst_ = fsb + ((N) & 1) * 4096, b_ = fbar + ((N) & 1) * 8;                               \
      mbar_expect_tx(b_, 4096);                                                                              \
      tma2d(dst_, ma, sx, sy, b_);                                                                           \
      tma2d(dst_ + 2048, mc, sx, sy + sdy, b_);                                                              \
    }                                                                                                        \
    sy += 32 + sdy;                                                                                          \
  } while (0)
    float a[8], gsum = 0.f, usum = 0.f;
    {
      if (f == 3) {
        if (elect_one()) {
          if (XS_EARLY) { mbar_expect_tx(bar + B_XST, 16384); tma3d(sb + SM_XST, &mXs, 0, bid * 16, 0, bar + B_XST); }
          mbar_expect_tx(bar + B_WPHI, 8192);
          tma2d(sb + SM_WPHI, &mPhi, 0, hg * 128, bar + B_WPHI);
          prefetch_map(&mWq); prefetch_map(&mWo); prefetch_map(&mWp); prefetch_map(&mD);
          PROF(31);
        }
        __syncwarp();
      } else {
        if (lane == 0) prefetch_map(f == 0 ? &mWc : f == 1 ? &mG : &mU);
        if (f == 2) ((float2*)g_y[par])[bid * 32 + lane] = make_float2(0.f, 0.f);
      }
      float st[13];
#pragma unroll
      for (int i = 0; i < 13; i++) st[i] = 0.f;
#pragma unroll 1
      for (int i = 0; i < 4; i++) {
        mbar_wait(bar + B_XST + 8 * (i >> 1), 0);
        if (f == 0 && lane == 0 && i == 0) PROF(1);
        const uint4 wu = lds128u(sb + SM_XSEL + i * 512 + lane * 16);
        const float wf[8] = {bf_lo(wu.x), bf_hi(wu.x), bf_lo(wu.y), bf_hi(wu.y), bf_lo(wu.z), bf_hi(wu.z), bf_lo(wu.w), bf_hi(wu.w)};
        st[12] += ((wf[0] + wf[1]) + (wf[2] + wf[3])) + ((wf[4] + wf[5]) + (wf[6] + wf[7]));
#pragma unroll
        for (int r = 0; r < 4; r++) {
          const uint4 u = lds128u(sb + SM_XST + i * 8192 + (4 * f + r) * 512 + lane * 16);
          const float xf[8] = {bf_lo(u.x), bf_hi(u.x), bf_lo(u.y), bf_hi(u.y), bf_lo(u.z), bf_hi(u.z), bf_lo(u.w), bf_hi(u.w)};
#pragma unroll
          for (int k = 0; k < 8; k++) { st[r] += xf[k]; st[4 + r] = fmaf(xf[k], xf[k], st[4 + r]); st[8 + r] = fmaf(xf[k], wf[k], st[8 + r]); }
        }
        if (i >= 2 && f < 3) STAGEG(n0 + i - 2);
      }
      const bool up = lane & 16, up2 = lane & 8;
#pragma unroll
      for (int q = 0; q < 3; q++) {
        const float k0 = up ? st[4 * q + 2] : st[4 * q], k1 = up ? st[4 * q + 3] : st[4 * q + 1];
        const float o0 = up ? st[4 * q] : st[4 * q + 2], o1 = up ? st[4 * q + 1] : st[4 * q + 3];
        const float m0 = k0 + __shfl_xor_sync(~0u, o0, 16), m1 = k1 + __shfl_xor_sync(~0u, o1, 16);
        a[q] = (up2 ? m1 : m0) + __shfl_xor_sync(~0u, up2 ? m0 : m1, 8);
      }
      a[3] = st[12] + __shfl_xor_sync(~0u, st[12], 16);
      a[3] += __shfl_xor_sync(~0u, a[3], 8);
#pragma unroll
      for (int o = 4; o; o >>= 1)
#pragma unroll
        for (int q = 0; q < 4; q++) a[q] += __shfl_xor_sync(~0u, a[q], o);
      if ((lane & 7) == 0) sts128(sb + SM_ROWS + (4 * f + (lane >> 3)) * 16, a[0], a[1], a[2], a[3]);
      if (f < 3) asm volatile("bar.arrive 7, 128;" ::: "memory");
    }
    if (f == 3) {
      bar_sync(7, 128);
      const int row = bid * 16 + (lane & 15);
      const float4 v = lds128(sb + SM_ROWS + (lane & 15) * 16);
      const float mf = v.x * (1.f / DM), mean = bf_round(mf), var = fmaxf(fmaf(-mf, mf, v.y * (1.f / DM)), 0.f);
      const float sd = bf_round(sqrt_approx(bf_round(bf_round(var) + 1e-5f)));
      const uint32_t rb = pack2(fmaf(-mean, v.w, v.z) * rcp(sd), 0.f) & 0xffffu, ord = (rb & 0x8000u) ? (~rb & 0xffffu) : (rb | 0x8000u);
      uint32_t best = __reduce_max_sync(~0u, (ord << 16) | (uint32_t)(2047 - row));
      if (lane < 16) st_rlx64(g_stat + row, ((unsigned long long)tag << 32) | __float_as_uint(mean) | (__float_as_uint(sd) >> 16));
      if (lane == 0) { asm volatile("red.relaxed.gpu.global.max.u64 [%0], %1;" ::"l"(g_best + bid), "l"(((unsigned long long)tag << 32) | best) : "memory"); PROF(17); }
#pragma unroll 1
      for (int n = 3; n < 5; n++) STAGEG(n);
      {
        uint4 xr[4];
        best = routed_row(P.x, tag, lane, xr);
#pragma unroll
        for (int i = 0; i < (GROWS + 255) / 256; i++) {
          const uint32_t dst = sb + SM_XSEL + i * 1024 + (lane >> 2) * 128 + (lane & 3) * 8;
          sts64(dst, bf_lo(xr[i].x), bf_lo(xr[i].z)); sts64(dst + 32, bf_hi(xr[i].x), bf_hi(xr[i].z));
          sts64(dst + 64, bf_lo(xr[i].y), bf_lo(xr[i].w)); sts64(dst + 96, bf_hi(xr[i].y), bf_hi(xr[i].w));
        }
        sts64u(sb + SM_RED + 16, tag, best);
        __syncwarp();
        if (lane == 0) { mbar_arrive(bar + B_XS); PROF(19); }
      }
      unsigned long long sv4[4];
      uint4 u[4];
#pragma unroll 1
      for (int it = 0; it < SPIN_MAX; it++) {
#pragma unroll
        for (int i = 0; i < 4; i++) { u[i] = ld_rlx128(g_cs + (1 + i) * 1024 + hg * 128 + lane * 4); sv4[i] = ld_rlx64(g_stat + mb * 128 + i * 32 + lane); }
        bool ok = ((BAD4(u[0]) | BAD4(u[1]) | BAD4(u[2]) | BAD4(u[3])) & 1) == 0;
#pragma unroll
        for (int i = 0; i < 4; i++) ok = ok && (uint32_t)(sv4[i] >> 32) == tag;
        if (__all_sync(~0u, ok)) break;
        __nanosleep(200);
      }
#pragma unroll
      for (int i = 0; i < 4; i++) {
        const uint32_t sv = (uint32_t)sv4[i], sd2 = (sv << 16) | (sv & 0xffffu);
        sts64(sb + SM_STAT + (i * 32 + lane) * 8, -bf_hi(sv), rcp(bf_lo(sv)));
        sts128u(sb + SM_SDT + lane * 64 + ((i ^ ((lane >> 1) & 3)) << 4), sd2, sd2, sd2, sd2);
      }
#pragma unroll
      for (int i = 0; i < 2; i++) {
        float4 c = make_float4(unmark(u[i].x) + unmark(u[i + 2].x), unmark(u[i].y) + unmark(u[i + 2].y), unmark(u[i].z) + unmark(u[i + 2].z),
                               unmark(u[i].w) + unmark(u[i + 2].w));
        CS_STORE(i, c);
      }
      fence_async_smem();
      bar_sync(8, 64);
      if (lane == 0) { mbar_arrive(bar + B_CS); PROF(10); }
    }
    {
      uint32_t xa = sb + SM_RED + 32, xstep = 0;
      const uint32_t zero = __float_as_uint(lds32(sb + SM_RED + 12));
#pragma unroll 1
      for (int ph = f == 3; ph < 2; ph++) {
#pragma unroll
        for (int j = 0; j < 8; j++) a[j] = 0.f;
        if (ph && f == 0) {
        {
          mbar_wait(bar + B_WPHI, 0);
          float nq[8] = {0.f, 0.f, 0.f, 0.f, 0.f, 0.f, 0.f, 0.f};
  #pragma unroll 2
          for (int r = 0; r < 16; r++) {
            const uint4 u = lds128u(sb + SM_WPHI + ((lane >> 2) * 16 + r) * 64 + (((lane ^ (r >> 1)) & 3) << 4));
            nq[0] = fmaf(bf_lo(u.x), bf_lo(u.x), nq[0]); nq[1] = fmaf(bf_hi(u.x), bf_hi(u.x), nq[1]); nq[2] = fmaf(bf_lo(u.y), bf_lo(u.y), nq[2]);
            nq[3] = fmaf(bf_hi(u.y), bf_hi(u.y), nq[3]); nq[4] = fmaf(bf_lo(u.z), bf_lo(u.z), nq[4]); nq[5] = fmaf(bf_hi(u.z), bf_hi(u.z), nq[5]);
            nq[6] = fmaf(bf_lo(u.w), bf_lo(u.w), nq[6]); nq[7] = fmaf(bf_hi(u.w), bf_hi(u.w), nq[7]);
          }
          uint32_t m = 0;
  #pragma unroll
          for (int i = 0; i < 8; i++) m = max(m, __float_as_uint(nq[i] + __shfl_xor_sync(~0u, nq[i], 4)) & 0x7fffffffu);
          sts32(sb + SM_RED + 24, 4.2f * __uint_as_float(__reduce_max_sync(~0u, m)));
        }
          asm volatile("bar.arrive 8, 64;" ::: "memory");
        }
        if (ph) { mbar_wait(bar + B_XS, 0); xa = sb + SM_XSEL + f * (GN * 128) + ((lane >> 2) & 3) * 32; xstep = 128; }
#pragma unroll 1
        for (int n = ph ? 3 : n0; n < (ph ? ne : 3); n++) {
          const float4 x0 = lds128(xa), x1 = lds128(xa + 16);
          xa += xstep;
          mbar_wait(fbar + (n & 1) * 8, ((n - n0) >> 1) & 1);
          uint4 u[8];
#pragma unroll
          for (int j = 0; j < 8; j++) u[j] = lds128u(fst + (n & 1) * 4096 + j * 256);
          FMA8(a, u[0], x0.x); FMA8(a, u[1], x0.y); FMA8(a, u[2], x0.z); FMA8(a, u[3], x0.w);
          if (__any_sync(~0u, ((u[4].x | u[5].x | u[6].x | u[7].x | __float_as_uint(a[0]) | __float_as_uint(a[7])) & zero) == 0)) STAGEG(n + 2);
          FMA8(a, u[4], x1.x); FMA8(a, u[5], x1.y); FMA8(a, u[6], x1.z); FMA8(a, u[7], x1.w);
        }
#pragma unroll
        for (int o = 4; o <= 8; o <<= 1)
#pragma unroll
          for (int j = 0; j < 8; j++) a[j] += __shfl_xor_sync(~0u, a[j], o);
        if (ph && lane == 0) mbar_arrive(bar + B_FFN);
        const uint32_t red = ph ? sb + SM_GRED : sb + SM_RED + 64;
        if ((lane & 12) == 0) {
          const uint32_t d = red + f * 256 + (lane >> 4) * 128 + (lane & 3) * 32;
          sts128(d, a[0], a[1], a[2], a[3]); sts128(d + 16, a[4], a[5], a[6], a[7]);
        }
        if (f != 2) {
          asm volatile("bar.arrive %0, %1;" ::"r"(4 + ph), "r"(96 + 32 * ph) : "memory");
        } else {
          bar_sync(4 + ph, 96 + 32 * ph);
          const uint32_t ra = red + lane * 4;
          gsum = lds32(ra) + lds32(ra + 256) + lds32(ra + 512);
          usum = lds32(ra + 128) + lds32(ra + 384) + lds32(ra + 640);
          if (!ph) st_rlx(g_cs + 1024 + ch * 2048 + cu * 32 + lane, mark(__float_as_uint(gsum + usum), par));
          else { gsum += lds32(ra + 768); usum += lds32(ra + 896); }
          if (lane == 0) PROF(ph ? 34 : 18);
        }
      }
    }
    if (f == 3) {
      if (elect_one()) {
        PROF(7);
        mbar_wait(bar + B_FULLQ, 0);
#pragma unroll 1
        for (int j = 3; j < 16; j++) {
          mbar_wait(bar + (j < 4 ? B_EMPTYKV + 16 : B_EMPTYQ + 8 * (j & 3)), ((j >> 2) & 1) ^ 1);
          if (j == 12 + (hg & 3)) mbar_wait(bar + B_KVST + 8, 0);
          Q_LOAD(j);
        }
        PROF(47);
        mbar_expect_tx(bar + B_DN, 65536);
#pragma unroll 1
        for (int i = 0; i < 4; i++) {
          mbar_wait(bar + B_EMPTYQ + 8 * i, 1);
          tma3d(sb + i * Q_STAGE, &mD, 0, fb * 32, i * 4, bar + B_DN);
        }
        PROF(48);
#pragma unroll 1
        for (int i = 0; i < 16; i++) {
          const int s = i & 3, n = i < 9 ? i - 2 : i - 9, kb = i < 2 ? 2 * hg + i : 2 * (n + (n >= hg)) + (i >= 9);
          if (i >= 4) mbar_wait(bar + B_EMPTYQ + 8 * s, ((i >> 2) & 1) ^ 1);
          mbar_expect_tx(bar + B_FULLQ + 8 * s, 16384);
          if (i < 2) {
            mbar_arrive2(bar + B_FULLQ + 8 * s);
            tma3d(sb + s * Q_STAGE + 16384, &mWo, 0, kb * 64, hg * 2, bar + B_FULLQ + 8 * s);
          } else {
            tma5d(sb + s * Q_STAGE + 16384, &mWp, hg * 128, kb * 2, bar + B_FULLQ + 8 * s);
            tma5d(sb + s * Q_STAGE + 24576, &mWp, hg * 128 + 64, kb * 2, bar + B_FULLQ + 8 * s);
            if (i >= 3) {
              if (i == 3) { mbar_wait(bar + B_DND, 0); PROF(14); }
#pragma unroll 1
              for (int a = i == 3 ? 2 : i; a <= i; a++) {
                const uint4* src = g_ofr + (mb * 16 + (a == 2 ? (hg == 0 ? 2 : 0) : kb)) * 1024;
#pragma unroll
                for (int h = 0; h < 2; h++) {
                  mbar_expect_tx(bar + B_AIN + (a & 3) * 16 + h * 8, 8192);
                  bulk_load(sb + (a & 3) * Q_STAGE + h * 8192, src + h * 512, 8192, bar + B_AIN + (a & 3) * 16 + h * 8);
                }
              }
            }
          }
        }
      }
    } else {
      if (f == 2) {
        if (PFD && ffn) {
#pragma unroll 1
          for (int i = 0; i < 16; i++) { touch_l2((const char*)P.w_down + fb * 65536 + i * 4096 + lane * 128, lane); __nanosleep(PFD); }
        }
        {
#pragma unroll 1
          for (int i = 0; i < 8; i++) { touch_l2((const char*)P.wo + ((mb & 7) * 128 + i * 16 + (lane >> 1)) * 2048 + hg * 256 + (lane & 1) * 128, lane); __nanosleep(PFD); }
        }
        asm volatile("cp.async.wait_all;" ::: "memory");
        uint4 u;
#pragma unroll 1
        for (int it = 0; it < SPIN_MAX; it++) {
          u = ld_rlx128(g_cs + hg * 128 + lane * 4);
          if (__all_sync(~0u, !(BAD4(u) & 1))) break;
          __nanosleep(200);
        }
        mbar_wait(bar + B_PHI, 0);
        float4 c = make_float4(unmark(u.x), unmark(u.y), unmark(u.z), unmark(u.w));
        CS_STORE(2, c);
        fence_async_smem();
        __syncwarp();
        if (lane == 0) mbar_arrive(bar + B_CSQ);
      }
      const uint32_t target = __shfl_sync(~0u, tag, 0) * 16;
#pragma unroll 1
      for (int R = 0; R < 2; R++) {
        const uint32_t own = (hg * 2 + R) * 16 + mb, pst = sb + (R ? SM_PST1 : SM_PST0);
        if (f == R) {
          mbar_wait(bar + B_KVST + 8 * R, 0);
          if (f == 1 && lane == 0) PROF(11);
          wait_hint(XC1(hg, R) + mb, target);
          if (elect_one()) {
            PROF(35 + R);
            fence_async_global();
            mbar_expect_tx(bar + B_PART + 8 * R, 8192);
            bulk_load(pst, g_part + own * 512, 8192, bar + B_PART + 8 * R);
          }
          __syncwarp();
          uint4 uz;
#pragma unroll 1
          for (int it = 0; it < SPIN_MAX; it++) {
            uz = ld_rlx128(g_zpart + own * 128 + lane * 4);
            if (__all_sync(~0u, !(BAD4(uz) & 1))) break;
          }
          const bool b1 = lane & 2, b2 = lane & 4;
          const float z0 = unmark(b1 ? uz.z : uz.x) + __shfl_xor_sync(~0u, unmark(b1 ? uz.x : uz.z), 2);
          const float z1 = unmark(b1 ? uz.w : uz.y) + __shfl_xor_sync(~0u, unmark(b1 ? uz.y : uz.w), 2);
          float z = (b2 ? z1 : z0) + __shfl_xor_sync(~0u, b2 ? z0 : z1, 4);
          z += __shfl_xor_sync(~0u, z, 8);
          z += __shfl_xor_sync(~0u, z, 16);
          if (lane < 8) st_rlx(g_zres + own * 8 + (lane & 1) * 4 + (lane & 2) + (lane >> 2), mark(__float_as_uint(z), par));
          if (lane == 0) red_inc(XC2(hg, R));
          __syncwarp();
        }
        if (f == R || f == R + 1) {
          const uint32_t hf = f - R, m1 = ~lane & 1, gq = hf * 4 + (lane >> 3), ts = (lane >> 1) & 3;
          float a0 = 0.f, a1 = 0.f, a2 = 0.f, a3 = 0.f;
          mbar_wait(bar + B_PART + 8 * R, 0);
#pragma unroll 1
          for (int it = 0; it < SPIN_MAX; it++) {
            uint32_t bad = 0;
            a0 = a1 = a2 = a3 = 0.f;
#pragma unroll 1
            for (int b = 0; b < 16; b += 8) {
              uint2 u[8];
              if (it == 0) {
#pragma unroll
                for (int i = 0; i < 8; i++) { const float2 v = lds64(pst + (b + i) * 512 + hf * 256 + lane * 8); u[i] = make_uint2(__float_as_uint(v.x), __float_as_uint(v.y)); }
              } else {
#pragma unroll
                for (int i = 0; i < 8; i++) {
                  const unsigned long long v = ld_rlx64((const unsigned long long*)g_part + own * 1024 + (b + i) * 64 + hf * 32 + lane);
                  u[i] = make_uint2((uint32_t)v, (uint32_t)(v >> 32));
                }
              }
#pragma unroll
              for (int i = 0; i < 8; i++) {
                bad |= u[i].x ^ par;
                a0 += bf_lo(i & 1 ? u[i].x & ~m1 : u[i].x | m1); a1 += bf_hi(u[i].x); a2 += bf_lo(u[i].y); a3 += bf_hi(u[i].y);
              }
            }
            if (__all_sync(~0u, !(bad & m1))) break;
          }
          uint32_t* dst = (uint32_t*)g_res[par] + own * 128 + gq * 16 + ts;
          const uint32_t j0 = (lane & 1) * 2, vb = ts == (gq >> 1);
          st_rlx(dst + ((j0 ^ (gq >> 1)) & 3) * 4, pack2(a0, a1) | vb);
          st_rlx(dst + (((j0 + 1) ^ (gq >> 1)) & 3) * 4, pack2(a2, a3) | vb);
          ((uint2*)g_res[par ^ 1])[own * 64 + hf * 32 + lane] = make_uint2(0u, 0u);
          __syncwarp();
          if (lane == 0) { red_inc(XC2(hg, R)); if (!hf) PROF(R ? 12 : 30); }
        }
      }
      if (f == 2) {
        if (ffn && !FFN_OFF) {
#pragma unroll 1
          for (int it = 0; it < SPIN_MAX; it++) {
            const uint32_t pg = ld_rlx((const uint32_t*)g_gp + fb * 32 + lane), pu = ld_rlx((const uint32_t*)g_gp + FF + fb * 32 + lane);
            if (__all_sync(~0u, !(((pg ^ par) | (pu ^ par)) & 1))) { gsum += unmark(pg); usum += unmark(pu); break; }
            __nanosleep(200);
          }
        }
        const float h = bf_round(silu_f(bf_round(gsum))) * bf_round(usum);
        const uint32_t h2 = pack2(h, h);
        sts128u(sb + SM_HT + lane * 16, h2, h2, h2, h2);
        fence_async_smem();
        __syncwarp();
        if (lane == 0) { mbar_arrive(bar + B_H); PROF(20); }
      }
      if (f < 2) {
        wait_hint(XC2(hg, f), 3 * target);
        mbar_wait(bar + B_KVST + 8, 0);
        if (lane == 0) PROF(40 + f);
#pragma unroll 1
        for (int it = 0; it < SPIN_MAX; it++) {
          if (elect_one()) {
            fence_async_global();
            mbar_expect_tx(bar + B_RES + 8 * f, 8192);
            bulk_load(sb + SM_V + f * 8192, g_res[par] + (hg * 4 + f * 2) * 256, 8192, bar + B_RES + 8 * f);
          }
          __syncwarp();
          const uint4 uz = ld_rlx128(g_zres + (hg * 4 + f * 2) * 64 + lane * 4);
          const uint32_t zw[4] = {uz.x, uz.y, uz.z, uz.w};
#pragma unroll
          for (int j = 0; j < 4; j++) {
            const uint32_t zz = pack2(unmark(zw[j]), 1.f), row = (lane & 3) * 4 + j;
            sts128u(sb + SM_ZT + (2 * f + (lane >> 4)) * 1024 + row * 64 + ((((lane >> 2) ^ (row >> 1)) & 3) << 4), zz, zz, zz, zz);
          }
          uint32_t bad = BAD4(uz);
          mbar_wait(bar + B_RES + 8 * f, it & 1);
#pragma unroll
          for (int i = 0; i < 16; i++) bad |= ~__float_as_uint(lds32(sb + SM_V + f * 8192 + i * 512 + lane * 16 + (lane >> 3) * 4));
          if (__all_sync(~0u, !(bad & 1))) break;
        }
        fence_async_smem();
        __syncwarp();
        if (lane == 0) { mbar_arrive(bar + B_TILE + 8 * f); PROF(f ? 13 : 27); }
      }
      if (f < 2) {
        uint32_t phases = 0;
#pragma unroll 1
        for (int i = 2; i < 16; i++) {
          const int s = i & 3;
          const uint32_t ab = bar + B_AIN + s * 16 + f * 8, slot = sb + s * Q_STAGE + f * 8192;
#pragma unroll 1
          for (int it = 0; it < SPIN_MAX; it++) {
            mbar_wait(ab, (phases >> s) & 1);
            phases ^= 1u << s;
            uint32_t bad = 0;
#pragma unroll
            for (int n = 0; n < 8; n++) bad |= __float_as_uint(lds32(slot + n * 1024 + lane * 32 + (lane >> 2) * 4)) ^ par;
            if (__all_sync(~0u, !(bad & 1))) break;
            if (elect_one()) {
              const int n = i < 9 ? i - 2 : i - 9, kb = 2 * (n + (n >= hg)) + (i >= 9);
              PROF(49);
              mbar_expect_tx(ab, 8192);
              bulk_load(slot, g_ofr + (mb * 16 + kb) * 1024 + f * 512, 8192, ab);
            }
            __syncwarp();
          }
          if (lane == 0) { mbar_arrive(bar + B_FULLQ + 8 * s); if (i == 2 && f == 0) PROF(15); }
        }
        if (f == 0) g_epoch[bid * 32 + lane] = tag;
      } else {
        if (elect_one()) {
          prefetch_map(&mOut);
          if (ffn) { mbar_wait(bar + B_YD, 0); red_rel(g_ycnt); PROF(21); }
        }
        __syncwarp();
        if (f == 2) {
          const uint32_t best = __float_as_uint(lds32(sb + SM_RED + 20));
          const int sel = 2047 - (best & 0x7ff) - mb * 128;
          if (sel >= 0 && sel < 128) {
            const uint2 xr = __ldg((const uint2*)(P.x + (size_t)(mb * 128 + sel) * DM + hg * 128 + lane * 4));
            const float2 st = lds64(sb + SM_STAT + sel * 8);
            const uint32_t ord = best >> 16, rb = (ord & 0x8000u) ? (ord & 0x7fffu) : (~ord & 0xffffu);
            const float sg = rcp(1.f + ex2(-1.4426950408889634f * bf_lo(rb)));
            const uint32_t sg2 = pack2(sg, sg), nm2 = pack2(st.x, st.x);
            wait_cnt<0>(g_ycnt, tag * NFFN);
            float4 y = make_float4(0.f, 0.f, 0.f, 0.f);
#pragma unroll
            for (int i = 0; i < 8; i++) {
              const float4 c = ldg_cg4(g_y[par ^ 1][i] + hg * 128 + lane * 4);
              y.x += c.x; y.y += c.y; y.z += c.z; y.w += c.w;
            }
            uint32_t o[2];
#pragma unroll
            for (int i = 0; i < 2; i++) {
              const uint32_t d = badd2(i ? xr.y : xr.x, nm2);
              const uint32_t tt = badd2(pack2(bf_lo(d) * st.y, bf_hi(d) * st.y), bmul2(i ? pack2(y.z, y.w) : pack2(y.x, y.y), sg2));
              o[i] = pack2(silu_f(bf_lo(tt)), silu_f(bf_hi(tt)));
            }
            sts64u(sb + SM_UPD + lane * 8, o[0], o[1]);
          }
          if (lane == 0) sts32(sb + SM_UPD + 256, __int_as_float(sel));
          __syncwarp();
          if (lane == 0) { mbar_arrive(bar + B_UPD); PROF(22); }
        }
      }
    }
  } else {
    const int t7 = threadIdx.x & 127;
    const char* pfa = warp < 4 ? (const char*)P.x + bid * 32768 + (t7 & 15) * 2048 + (t7 >> 4) * 128
                               : (const char*)P.wqkv + (size_t)((t7 >> 4) * 64 + (bid >> 1)) * 6144 + 2048 + (bid & 1) * 2048 + (t7 & 15) * 128;
    if (t7 >= 16 && t7 < 16 * PF_FIRST) prefetch_l2(pfa);
    if (warp < 7) sts128(sb + SM_CST + threadIdx.x * 16, 0.f, 0.f, 0.f, 0.f);
    else sts32(sb + SM_RED + (threadIdx.x & 15) * 4, threadIdx.x & 8 ? 1.f : 0.f);
    if (elect_one()) {
#pragma unroll 1
      for (uint32_t b = B_FST + warp * 8; b < B_END; b += 64)
        mbar_init(bar + b, b < B_FULLQ ? 1 : b < B_FFN ? 3 : b < B_EMPTYKV ? 4 : 8);
    }
    __syncwarp();
    asm volatile("bar.arrive 13, 384;" ::: "memory");
    asm volatile("setmaxnreg.inc.sync.aligned.u32 %0;" ::"n"(REG_C));
    if (t7 >= 16 * PF_FIRST && threadIdx.x < 128 + 16 * PF_W) prefetch_l2(pfa);
    asm volatile("cp.async.wait_all;" ::: "memory");
    fence_async_smem();
    bar_sync(14, 288);
    if (threadIdx.x == 0) mbar_arrive(bar + B_FULLKV + 16);
    const int lane = lane_id();
    const int wg = warp >> 2, w = warp & 3, g = lane >> 2, t = lane & 3;
    float kv[128];
    {
      uint32_t s = 2, ph = 0, sp = 0, php = 0;
#pragma unroll 1
      for (int j = 0; j < 15; j++) {
        PW0(32 + j); mbar_wait(bar + B_FULLKV + 8 * s, ph); PW1(32 + j);
        if (wg == 1) bar_sync(10 + s, 256);
        wg_fence();
        wgmma_n256_ssp_ta0_tb1(kv, mkdesc(sb, 16, 1024, 1, wg * 512 + s * (KV_STAGE / 16)), mkdesc(sb + 16384, 8192, 1024, 1, s * (KV_STAGE / 16)), j);
#pragma unroll
        for (int k = 1; k < 4; k++)
          wgmma_n256_ss_ta0_tb1(kv, mkdesc(sb + k * 32, 16, 1024, 1, wg * 512 + s * (KV_STAGE / 16)),
                                mkdesc(sb + 16384 + k * 2048, 8192, 1024, 1, s * (KV_STAGE / 16)), 1);
        wg_commit();
        if (wg == 0) asm volatile("bar.arrive %0, 256;" ::"r"(10 + s) : "memory");
        if (warp == 0 && j) {
          mbar_wait(bar + B_EMPTYKV + 8 * sp, php);
          if (elect_one()) {
            if (j < 14) {
              mbar_expect_tx(bar + B_FULLKV + 8 * sp, KV_STAGE);
              tma2d(sb + sp * KV_STAGE, &mX, (j + 2) * 64, mb * 128, bar + B_FULLKV + 8 * sp);
              tma4d(sb + sp * KV_STAGE + 16384, &mWkv, 0, (j + 2) * 64, hg * 2, 1, bar + B_FULLKV + 8 * sp);
            } else {
              Q_LOAD(0);
            }
            if (j < 3 - XS_EARLY) {
              const int xh = j - 1 + XS_EARLY;
              mbar_expect_tx(bar + B_XST + 8 * xh, 16384);
              tma3d(sb + SM_XST + xh * 16384, &mXs, 0, bid * 16, 2 * xh, bar + B_XST + 8 * xh);
            }
          }
          __syncwarp();
        }
        if (j == 0) {
          if (wg == 0) prefetch_l2(pfa + 1024);
        } else if (wg == 1) {
          if (j < 3) {
            if (j == 2 || t7 >= 16 * PF_W) prefetch_l2(pfa + (j - 1) * (8 * 393216));
          } else if (j == 13) {
            prefetch_l2((const char*)P.wo + bid * 16384 + t7 * 128);
          }
        }
        wg_wait<0>();
        if (lane == 0) mbar_arrive(bar + B_EMPTYKV + 8 * s);
        sp = s; php = ph;
        ph ^= s == 1;
        s = s == 2 ? 0 : s + 1;
      }
    }
    const int lrow = wg * 64 + w * 16 + (lane & 15);
    const uint32_t sw128 = lrow * 128, x128 = (lrow & 7), hi16 = lane >> 4;
    mbar_wait(bar + B_CS, 0);
    const uint32_t tag = __float_as_uint(lds32(sb + SM_RED + 16));
    const int zero = __float_as_int(lds32(sb + SM_RED + 12));
    const float wn = lds32(sb + SM_RED + 24);
    const float2 st0 = lds64(sb + SM_STAT + (wg * 64 + w * 16 + g) * 8), st1 = lds64(sb + SM_STAT + (wg * 64 + w * 16 + g + 8) * 8);
    const float c0 = st0.y * 1.4426950408889634f, c1 = st1.y * 1.4426950408889634f;
    const uint32_t nm20 = pack2(st0.x, st0.x), nm21 = pack2(st1.x, st1.x), fmask = t == 0 ? ~0u : t == 1 ? 0xffffu : 0u;
    const uint32_t fa0 = nm20 & fmask, fa1 = nm21 & fmask;
    asm volatile("cp.async.wait_all;" ::: "memory");
    PW0(47); mbar_wait(bar + B_FULLKV + 16, 1); PW1(47);
    wg_fence();
    wgmma_n256_rs_ta0_tb1(kv, fa0, fa1, 0u, 0u, mkdesc(sb + SM_CST, 512, 0, 1), 1);
#pragma unroll
    for (int k = 0; k < 4; k++)
      wgmma_n256_ss_ta0_tb1(kv, mkdesc(sb + 2 * KV_STAGE + k * 32, 16, 1024, 1, wg * 512), mkdesc(sb + 2 * KV_STAGE + 16384 + k * 2048, 8192, 1024, 1), 1);
    wg_commit();
    if (warp == 0) {
      mbar_wait(bar + B_EMPTYKV + 8, 0);
      if (elect_one()) {
#pragma unroll 1
        for (int j = 1; j < 3; j++) Q_LOAD(j);
      }
      __syncwarp();
    }
    wg_wait<0>();
    reg_fence<128>(kv);
    if (lane == 0) mbar_arrive(bar + B_EMPTYKV + 16);
    PROFC(2);
    float q[64];
#define QMMA(J, AOFF16, ACCUM)                                                                                     \
  _Pragma("unroll") for (int k = 0; k < 4; k++)                                                                    \
      wgmma_n128_ss_ta0_tb1(q, mkdesc(sb + k * 32, 16, 1024, 1, wg * 512 + (AOFF16)),                              \
                            mkdesc(sb + 16384 + k * 2048, 8192, 1024, 1, ((J) & 3) * (Q_STAGE / 16)), k ? 1 : (ACCUM))
#define QWAIT(J) do { PW0(J); mbar_wait(bar + B_FULLQ + 8 * ((J) & 3), ((J) >> 2) & 1); PW1(J); } while (0)
#define QSTEP_A(J, AOFF16, ACCUM) do { QWAIT(J); wg_fence(); QMMA(J, AOFF16, ACCUM); wg_commit(); } while (0)
#define QREL(J) do { if (lane == 0) mbar_arrive(bar + B_EMPTYQ + 8 * ((J) & 3)); } while (0)
#define Q_OFF16(J) ((J) >= 8 && (J) < 16 ? Q_AOFF(J) / 16 : ((J) & 3) * (Q_STAGE / 16))
#define QPLAIN(J) do { QSTEP_A(J, Q_OFF16(J), 1); wg_wait<1>(); QREL((J) - 1); } while (0)
#define QNEXT(J) do { QPLAIN(J); SCHED_FENCE(); } while (0)
#define PHI_PROJ(DST, SRC, H0, H1)                                                                                 \
  do {                                                                                                             \
    uint32_t a_[32];                                                                                               \
    _Pragma("unroll") for (int j = 8 * (H0); j < 8 * (H1); j++) {                                                  \
      a_[j] = pack2(SRC[2 * j], SRC[2 * j + 1]);                                                                   \
      asm volatile("fma.rn.bf16x2 %0, %1, %1, %0;" : "+r"(nq[(j >> 4) * 2 + (j & 1)]) : "r"(a_[j]));               \
    }                                                                                                              \
    wg_fence();                                                                                                    \
    _Pragma("unroll") for (int hk = 2 * (H0); hk < 2 * (H1); hk++)                                                 \
        wgmma_n32_rs_ta0_tb1(DST + 16 * (hk >> 1), a_[4 * hk], a_[4 * hk + 1], a_[4 * hk + 2], a_[4 * hk + 3],     \
                             mkdesc(sb + SM_WPHI + hk * 1024, 16, 512, 2), hk & 1);                                \
    wg_commit();                                                                                                   \
  } while (0)
    {
      float p[64], ea[24], eb[24], sa[4], sc[4], kz[20];
      uint32_t vp[32];
#pragma unroll
      for (int j = 0; j < 32; j++) vp[j] = pack2(kv[64 + 2 * j], kv[65 + 2 * j]);
      const uint32_t vr = w * 16 + (lane & 15), vb = sb + SM_V + wg * 4096 + vr * 64, x64 = (vr >> 1) & 3;
#define V_STORE(R)                                                                                           \
  _Pragma("unroll") for (int j = 0; j < 4; j++)                                                              \
      stsm4(vb + (j >> 1) * 8192 + ((((j & 1) * 2 + hi16) ^ x64) << 4), vp[16 * (R) + 4 * j], vp[16 * (R) + 4 * j + 1], vp[16 * (R) + 4 * j + 2], vp[16 * (R) + 4 * j + 3])
      V_STORE(0);
      mbar_wait(bar + B_WPHI, 0);
      {
        uint32_t nq[4] = {0u, 0u, 0u, 0u};
        PHI_PROJ(p, kv, 0, 4);
        QSTEP_A(0, 0, 0);
        const bool unsafe = softmax_unsafe(nq, c0 * c0 * wn, c1 * c1 * wn);
        wg_wait<1>();
        reg_fence<64>(p);
        if (__builtin_expect(unsafe, 0)) softmax_shift(p, c0, c1);
      }
#define K_NORM(S) do { quad_sum<4>(S); _Pragma("unroll") for (int i = 0; i < 4; i++) S[i] = rcp(S[i]) * ((i & 1) ? st1.y : st0.y); } while (0)
#define K_STORE(SLOT, E, S) K_STORE_(SLOT, E, S, 0, 2)
#define K_STORE_(SLOT, E, S, J0, J1)                                                                         \
  _Pragma("unroll") for (int j = (J0); j < (J1); j++) {                                                      \
    uint32_t fp[4], fm[4];                                                                                   \
    _Pragma("unroll") for (int i = 0; i < 4; i++) {                                                          \
      const float e0 = E[8 * j + 2 * i], e1 = E[8 * j + 2 * i + 1], r = E[16 + 4 * j + i] * S[2 + (i & 1)];  \
      const uint32_t e2 = pack2(e0, e1);                                                                     \
      fp[i] = bmul2(e2, pack2(S[i & 1], S[i & 1]));                                                          \
      fm[i] = bmul2(e2, pack2(r, r));                                                                        \
    }                                                                                                        \
    stsm4(sb + SM_PHI + (SLOT) * 16384 + sw128 + (((2 * j + hi16) ^ x128) << 4), fp[0], fp[1], fp[2], fp[3]); \
    stsm4(sb + SM_PHI + (SLOT) * 16384 + sw128 + (((4 + 2 * j + hi16) ^ x128) << 4), fm[0], fm[1], fm[2], fm[3]); \
  }
#define KV_MMA(R)                                                                                            \
  do {                                                                                                       \
    mbar_wait(bar + B_PHI + 8 * (R), 0);                                                                     \
    wg_fence();                                                                                              \
    _Pragma("unroll") for (int k = 0; k < 8; k++) {                                                          \
      const uint32_t vs = SM_V + (k >> 2) * 4096 + (k & 3) * 1024;                                           \
      wgmma_n40_ss_ta1_tb1(kz, mkdesc(sb + SM_PHI + k * 2048, 16, 1024, 1, wg * 1024),                       \
                           mkdesc(sb + vs, SM_SDT + (k & 1) * 1024 + (k >> 1) * 16 - vs, 512, 2, wg * (512u - (512u << 16))), k); \
    }                                                                                                        \
    wg_commit();                                                                                             \
  } while (0)
#define QKV(J, R) do { KV_MMA(R); QSTEP_A(J, Q_OFF16(J), 1); wg_wait<2>(); QREL((J) - 1); SCHED_FENCE(); } while (0)
#define KV_SEND(R)                                                                                           \
  do {                                                                                                       \
    reg_fence<20>(kz);                                                                                       \
    if (lane == 0) mbar_arrive(bar + B_KVST + 8 * (R));                                                      \
    const uint32_t slot = ((hg * 2 + (R)) * 16 + warp * 2) * 16 + mb;                                        \
    _Pragma("unroll") for (int u = 0; u < 2; u++)                                                            \
      st_rlx128(g_part + (slot + u * 16) * 32 + lane, mark(pack2(kz[2 * u], kz[2 * u + 1]), tag & 1), pack2(kz[2 * u + 4], kz[2 * u + 5]), \
                pack2(kz[2 * u + 8], kz[2 * u + 9]), pack2(kz[2 * u + 12], kz[2 * u + 13]));                 \
    if (t < 2) st_rlx(g_zpart + (slot + t * 16) * 8 + g, mark(__float_as_uint(t ? kz[18] : kz[16]), tag & 1)); \
    if (lane < 2) red_inc(XC1(hg, R) + warp * 2 + lane);                                                          \
  } while (0)
#define K_PUB(R) do { fence_async_smem(); __syncwarp(); if (lane == 0) mbar_arrive(bar + B_PHI + 8 * (R)); } while (0)
#define S_PIN(S) SCHED_PIN(S[0] + S[1] + S[2] + S[3])
      k_exp(p, c0, c1, ea, sa);
      S_PIN(sa);
      QNEXT(1);
      K_NORM(sa);
      k_exp<0, 4>(p + 16, c0, c1, eb, sc);
      mbar_wait(bar + B_FFN, 0);
      K_STORE_(0, ea, sa, 0, 1);
      S_PIN(sc);
      QNEXT(2);
      K_STORE_(0, ea, sa, 1, 2);
      k_exp<4, 8>(p + 16, c0, c1, eb, sc);
      K_NORM(sc);
      S_PIN(sc);
      QNEXT(3);
      K_STORE(1, eb, sc);
      K_PUB(0);
      k_exp<0, 4>(p + 32, c0, c1, ea, sa);
      S_PIN(sa);
      QKV(4, 0);
      k_exp<4, 8>(p + 32, c0, c1, ea, sa);
      K_NORM(sa);
      k_exp<0, 4>(p + 48, c0, c1, eb, sc);
      SCHED_PIN(sa[0] + sa[1] + sa[2] + sa[3] + sc[2] + sc[3]);
      QNEXT(5);
      KV_SEND(0);
      k_exp<4, 8>(p + 48, c0, c1, eb, sc);
      S_PIN(sc);
      QNEXT(6);
      K_NORM(sc);
      mbar_wait(bar + B_KVST, 0);
      V_STORE(1);
      K_STORE(0, ea, sa);
      QNEXT(7);
      K_STORE(1, eb, sc);
      K_PUB(1);
      QKV(8, 1);
      QNEXT(9);
      KV_SEND(1);
    }
    PROFC(3);
#pragma unroll 1
    for (int j = 10; j < 15; j++) QPLAIN(j);
    mbar_wait(bar + B_CSQ, 0);
    QWAIT(15);
    if (wg == 1) bar_sync(6, 256);
    wg_fence();
    wgmma_n128_rs_ta0_tb1(q, fa0, fa1, 0u, 0u, mkdesc(sb + SM_CST + 2048, 512, 0, 1), 1);
    QMMA(15, Q_AOFF(15) / 16, 1);
    wg_commit();
    if (wg == 0) asm volatile("bar.arrive 6, 256;" ::: "memory");
    wg_wait<1>();
    QREL(14);
    wg_wait<0>();
    QREL(15);
    reg_fence<64>(q);
    PROFC(5);
    float yp[4];
    const uint32_t par = tag & 1;
    uint4* ofr = g_ofr + (mb * 16 + hg * 2) * 1024 + (warp * 16 + g) * 8;
#define O_MMA(H, F, N)                                                                                       \
  do {                                                                                                       \
    wg_fence();                                                                                              \
    _Pragma("unroll") for (int k = 0; k < 4; k++) {                                                          \
      const uint32_t ks = SM_V + (H) * 4096 + k * 1024;                                                      \
      wgmma_n40_rs_ta0_tb1(N + 20 * (k >> 1), F[4 * k], F[4 * k + 1], F[4 * k + 2], F[4 * k + 3],            \
                           mkdesc(sb + ks, SM_ZT + (H) * 1024 + k * 16 - ks, 512, 2), k & 1);                \
    }                                                                                                        \
    wg_commit();                                                                                             \
  } while (0)
#define O_FIN(H, N, o)                                                                                        \
  do {                                                                                                       \
    reg_fence<40>(N);                                                                                        \
    const float *np = N, *nm = N + 20;                                                                       \
    const float d0 = rcp(fmaf(np[16], nm[17], fmaf(nm[16], np[17], 1e-6f * np[17] * nm[17])));               \
    const float d1 = rcp(fmaf(np[18], nm[19], fmaf(nm[18], np[19], 1e-6f * np[19] * nm[19])));               \
    const float bp0 = nm[17] * d0, bm0 = np[17] * d0, bp1 = nm[19] * d1, bm1 = np[19] * d1;                  \
    _Pragma("unroll") for (int j = 0; j < 4; j++) {                                                          \
      o[2 * j] = pack2(fmaf(np[4 * j], bp0, nm[4 * j] * bm0), fmaf(np[4 * j + 1], bp0, nm[4 * j + 1] * bm0)); \
      o[2 * j + 1] = pack2(fmaf(np[4 * j + 2], bp1, nm[4 * j + 2] * bm1), fmaf(np[4 * j + 3], bp1, nm[4 * j + 3] * bm1)); \
    }                                                                                                        \
  } while (0)
#define O_STG(H, o)                                                                                          \
  _Pragma("unroll") for (int u = 0; u < 2; u++) {                                                            \
    uint32_t v_[4];                                                                                          \
    _Pragma("unroll") for (int j = 0; j < 4; j++) v_[j] = lop_select(o[2 * j + u], parm, vword == j);        \
    st_rlx128(ofr + ((H) >> 1) * 1024 + u * 64 + ((((H) & 1) * 4 + t) ^ g), v_[0], v_[1], v_[2], v_[3]);     \
  }
    uint32_t gf[32], ao[16];
    const uint32_t parm = 0u - par, vword = ((t ^ g) & 1) == (g >> 2) ? g & 3 : 4;
    const float rh0 = 0.5f * st0.y, rh1 = 0.5f * st1.y, mh0 = st0.x * rh0, mh1 = st1.x * rh1;
#define GATE_LD(J) ldsm4(sb + ((J) >> 2 ? SM_X1 : SM_X0) + sw128 + (((((J) & 3) * 2 + hi16) ^ x128) << 4), gf[4 * (J)], gf[4 * (J) + 1], gf[4 * (J) + 2], gf[4 * (J) + 3])
#define GATE(I0, I1)                                                                                         \
  _Pragma("unroll") for (int i = (I0); i < (I1); i++) {                                                      \
    const float rs = (i & 1) ? rh1 : rh0, mh = (i & 1) ? mh1 : mh0;                                          \
    const float h0 = fmaf(bf_lo(gf[i]), rs, mh), h1 = fmaf(bf_hi(gf[i]), rs, mh);                            \
    gf[i] = pack2(fmaf(h0, tanh_approx(h0), h0), fmaf(h1, tanh_approx(h1), h1));                             \
  }
#define GATE_PIN(I0, I1) do { uint32_t o_ = 0; _Pragma("unroll") for (int i = (I0); i < (I1); i++) o_ |= gf[i]; SCHED_PIN(__uint_as_float(o_)); } while (0)
    {
      float p[64], na[40], nb[40];
      uint32_t fa[16], fb[16];
      {
        uint32_t nq[4] = {0u, 0u, 0u, 0u};
        PHI_PROJ(p, q, 0, 2);
        SCHED_FENCE();
        PHI_PROJ(p, q, 2, 4);
        const bool unsafe = softmax_unsafe(nq, c0 * c0 * wn, c1 * c1 * wn);
        wg_wait<0>();
        reg_fence<64>(p);
        PROFC(24);
        if (__builtin_expect(unsafe, 0)) softmax_shift(p, c0, c1);
      }
      float dn[32];
#define DN_PART(A, B)                                                                                        \
  do {                                                                                                       \
    wg_fence();                                                                                              \
    _Pragma("unroll") for (int i = (A); i < (B); i++)                                                        \
      wgmma_n8_ss_ta1_tb1(dn + 4 * (i >> 1), mkdesc(sb + (i >> 3) * Q_STAGE + (i & 7) * 2048, 16, 1024, 1, wg * (2 * Q_STAGE / 16)), \
                          mkdesc(sb + SM_HT + (i & 1) * 256, 128, 128, 0), i & 1);                           \
  } while (0)
#define F_PIN(F, A, B) do { uint32_t o_ = 0; _Pragma("unroll") for (int i = (A); i < (B); i++) o_ |= F[8 + i]; SCHED_PIN(__uint_as_float(o_)); } while (0)
#define RMMA(J, A, ACCUM)                                                                                    \
  do {                                                                                                       \
    wg_fence();                                                                                              \
    _Pragma("unroll") for (int k = 0; k < 4; k++)                                                            \
      wgmma_n128_rs_ta0_tb1(q, (A)[4 * k], (A)[4 * k + 1], (A)[4 * k + 2], (A)[4 * k + 3],                   \
                            mkdesc(sb + 16384 + k * 2048, 8192, 1024, 1, ((J) & 3) * (Q_STAGE / 16)), k ? 1 : (ACCUM)); \
    wg_commit();                                                                                             \
  } while (0)
#define RSTEP(J, A, ACCUM) do { QWAIT(J); RMMA(J, A, ACCUM); } while (0)
      PROFC(4);
      q_exp(p, c0, c1, fa);
      q_exp(p + 16, c0, c1, fb);
      F_PIN(fb, 0, 8);
      mbar_wait(bar + B_TILE, 0);
      O_MMA(0, fa, na);
      O_MMA(1, fb, nb);
      PROFC(25);
      wg_wait<1>();
      O_FIN(0, na, ao);
      O_STG(0, ao);
      wg_wait<0>();
      O_FIN(1, nb, (ao + 8));
      O_STG(1, (ao + 8));
      PROFC(28);
      mbar_wait(bar + B_H, 0);
      mbar_wait(bar + B_DN, 0);
      PROFC(45);
      DN_PART(0, 16);
      wg_commit();
      wg_wait<0>();
      reg_fence<32>(dn);
#pragma unroll
      for (int i = 0; i < 4; i++) yp[i] = t & 2 ? (t & 1 ? dn[24 + 2 * i] : dn[16 + 2 * i]) : (t & 1 ? dn[8 + 2 * i] : dn[2 * i]);
      RSTEP(16, ao, 0);
      SCHED_FENCE();
      q_exp(p + 32, c0, c1, fa);
      F_PIN(fa, 0, 8);
      if (lane == 0) mbar_arrive(bar + B_DND);
      q_exp(p + 48, c0, c1, fb);
      F_PIN(fb, 0, 8);
      wg_wait<0>();
      QREL(16);
      PROFC(29);
      mbar_wait(bar + B_TILE + 8, 0);
      PROFC(23);
      if (bid < NFFN) {
        float* y = g_y[par ^ 1][bid & 7] + wg * 512 + t * 128 + w * 16 + g;
#pragma unroll
        for (int i = 0; i < 4; i++) red1(y + (i >> 1) * 64 + (i & 1) * 8, yp[i]);
      }
      SCHED_FENCE();
      O_MMA(2, fa, na);
      O_MMA(3, fb, nb);
      __syncwarp();
      if (lane == 0) mbar_arrive(bar + B_YD);
      wg_wait<1>();
      O_FIN(2, na, ao);
      O_STG(2, ao);
      wg_wait<0>();
      O_FIN(3, nb, (ao + 8));
      O_STG(3, (ao + 8));
      PROFC(6);
    }
    RSTEP(17, ao, 1);
    SCHED_FENCE();
    GATE_LD(0); GATE_LD(1);
    GATE(0, 4);
    GATE_PIN(0, 4);
#define GSTEP(J, I) do { QNEXT(J); if ((I) < 7) GATE_LD(((I) + 1) & 7); GATE(4 * (I), 4 * (I) + 4); GATE_PIN(4 * (I), 4 * (I) + 4); } while (0)
    GSTEP(18, 1); GSTEP(19, 2); GSTEP(20, 3); GSTEP(21, 4); GSTEP(22, 5); GSTEP(23, 6); GSTEP(24, 7);
#pragma unroll 1
    for (int j = 25; j < 32 - TAILN; j++) QPLAIN(j);
    if (wg == 1) bar_sync(6, 256);
#pragma unroll 1
    for (int j = 32 - TAILN; j < 32; j++) QSTEP_A(j, (j & 3) * (Q_STAGE / 16), 1);
    if (wg == 0) asm volatile("bar.arrive 6, 256;" ::: "memory");
    mbar_wait(bar + B_UPD, 0);
    {
      const int sel = __float_as_int(lds32(sb + SM_UPD + 256)) - (wg * 64 + w * 16 + g);
      if (sel == 0 || sel == 8) {
#pragma unroll
        for (int j = 0; j < 16; j++) {
          const uint32_t u = __float_as_uint(lds32(sb + SM_UPD + j * 16 + t * 4));
          if (sel) gf[2 * j + 1] = u; else gf[2 * j] = u;
        }
      }
      __syncwarp();
      uint32_t xf[32];
#pragma unroll
      for (int j = 0; j < 8; j++)
        ldsm4(sb + (j >> 2 ? SM_X1 : SM_X0) + sw128 + ((((j & 3) * 2 + hi16) ^ x128) << 4), xf[4 * j], xf[4 * j + 1], xf[4 * j + 2], xf[4 * j + 3]);
      wg_wait<0>();
      reg_fence<64>(q);
      PROFC(8);
#pragma unroll
      for (int j = 0; j < 8; j++) {
        uint32_t o[4];
#pragma unroll
        for (int i = 0; i < 4; i++) o[i] = badd2(xf[4 * j + i], bmul2(pack2(q[8 * j + 2 * i], q[8 * j + 2 * i + 1]), gf[4 * j + i]));
        stsm4(sb + (j >> 2 ? SM_X1 : SM_X0) + sw128 + ((((j & 3) * 2 + hi16) ^ x128) << 4), o[0], o[1], o[2], o[3]);
        if ((j & 3) == 3) {
          fence_async_smem();
          __syncwarp();
          if (elect_one()) {
            tma_store2d(&mOut, sb + (j >> 2 ? SM_X1 : SM_X0) + warp * 2048, hg * 128 + (j >> 2) * 64, mb * 128 + warp * 16);
            bulk_commit();
          }
          __syncwarp();
        }
      }
    }
    bulk_wait_read0();
    if (warp == 7 && lane == 0) { PROF(9); PROFT(33); PROF_DUMP; }
  }
}

typedef CUresult (*EncodeFn)(CUtensorMap*, CUtensorMapDataType, cuuint32_t, void*, const cuuint64_t*, const cuuint64_t*, const cuuint32_t*,
                             const cuuint32_t*, CUtensorMapInterleave, CUtensorMapSwizzle, CUtensorMapL2promotion, CUtensorMapFloatOOBfill);

CUtensorMap make_map(EncodeFn enc, const void* ptr, int rank, const cuuint64_t* dims, const cuuint64_t* strides, const cuuint32_t* box, CUtensorMapSwizzle sw) {
  CUtensorMap m;
  const cuuint32_t es[5] = {1, 1, 1, 1, 1};
  enc(&m, CU_TENSOR_MAP_DATA_TYPE_BFLOAT16, rank, (void*)ptr, dims, strides, box, es, CU_TENSOR_MAP_INTERLEAVE_NONE, sw,
      CU_TENSOR_MAP_L2_PROMOTION_L2_128B, CU_TENSOR_MAP_FLOAT_OOB_FILL_NONE);
  return m;
}

}

extern "C" void kernel_launch(void* const* d_in, const int* in_sizes, int n_in, void* d_out, int out_size) {
  static EncodeFn enc = nullptr;
  static int by_sm = 0;
  if (!enc) {
    void* fn = nullptr;
    cudaDriverEntryPointQueryResult qr;
    cudaGetDriverEntryPoint("cuTensorMapEncodeTiled", &fn, cudaEnableDefault, &qr);
    enc = (EncodeFn)fn;
    cudaFuncSetAttribute(fused_kernel<false>, cudaFuncAttributeMaxDynamicSharedMemorySize, SM_TOTAL);
    cudaFuncSetAttribute(fused_kernel<true>, cudaFuncAttributeMaxDynamicSharedMemorySize, SM_TOTAL);
    int dev = 0, sms = 0;
    cudaGetDevice(&dev);
    cudaDeviceGetAttribute(&sms, cudaDevAttrMultiProcessorCount, dev);
    by_sm = BY_SM && sms == NCTA + NSPARE;
  }
  Params P;
  P.x = (const __nv_bfloat16*)d_in[0];
  P.wqkv = (const __nv_bfloat16*)d_in[1];
  const void* wphi = d_in[2];
  P.wo = (const __nv_bfloat16*)d_in[3];
  P.w_r = (const __nv_bfloat16*)d_in[5];
  P.w_gate = (const __nv_bfloat16*)d_in[6];
  P.w_up = (const __nv_bfloat16*)d_in[7];
  P.w_down = (const __nv_bfloat16*)d_in[8];

  const cuuint64_t dX[2] = {DM, SEQ}, sX[1] = {DM * 2};
  const cuuint32_t b128[2] = {64, 128};
  const cuuint64_t dW[4] = {64, DM, 16, 3}, sW[3] = {3 * DM * 2, 128, DM * 2};
  const cuuint32_t bKV[4] = {64, 64, 2, 2}, bQ[4] = {64, 64, 2, 1};
  const cuuint64_t dO[3] = {64, DM, 16}, sO[2] = {DM * 2, 128};
  const cuuint32_t bO[3] = {64, 64, 2};
  const cuuint64_t dP[2] = {32, 1024}, sP[1] = {64};
  const cuuint32_t bP[2] = {32, 128};
  CUtensorMap mX = make_map(enc, P.x, 2, dX, sX, b128, CU_TENSOR_MAP_SWIZZLE_128B);
  CUtensorMap mWkv = make_map(enc, P.wqkv, 4, dW, sW, bKV, CU_TENSOR_MAP_SWIZZLE_128B);
  CUtensorMap mWq = make_map(enc, P.wqkv, 4, dW, sW, bQ, CU_TENSOR_MAP_SWIZZLE_128B);
  CUtensorMap mWo = make_map(enc, P.wo, 3, dO, sO, bO, CU_TENSOR_MAP_SWIZZLE_128B);
  CUtensorMap mPhi = make_map(enc, wphi, 2, dP, sP, bP, CU_TENSOR_MAP_SWIZZLE_64B);
  const cuuint64_t dWp[5] = {DM, 2, 4, 4, DM / 32}, sWp[4] = {DM * 2, 8 * DM * 2, 2 * DM * 2, 32 * DM * 2};
  const cuuint32_t bWp[5] = {64, 2, 4, 4, 2};
  CUtensorMap mWp = make_map(enc, P.wo, 5, dWp, sWp, bWp, CU_TENSOR_MAP_SWIZZLE_128B);
  const cuuint32_t b16[2] = {64, 16};
  CUtensorMap mOut = make_map(enc, d_out, 2, dX, sX, b16, CU_TENSOR_MAP_SWIZZLE_128B);
  const cuuint64_t dWc[2] = {3 * DM, DM}, sWc[1] = {3 * DM * 2}, dG[2] = {FF, DM}, sG[1] = {FF * 2}, dD[3] = {64, FF, 16};
  const cuuint32_t b32[2] = {32, 32}, bD[3] = {64, 32, 4};
  CUtensorMap mWc = make_map(enc, P.wqkv, 2, dWc, sWc, b32, CU_TENSOR_MAP_SWIZZLE_NONE);
  CUtensorMap mG = make_map(enc, P.w_gate, 2, dG, sG, b32, CU_TENSOR_MAP_SWIZZLE_NONE);
  CUtensorMap mU = make_map(enc, P.w_up, 2, dG, sG, b32, CU_TENSOR_MAP_SWIZZLE_NONE);
  CUtensorMap mD = make_map(enc, P.w_down, 3, dD, sO, bD, CU_TENSOR_MAP_SWIZZLE_128B);
  const cuuint64_t dXs[3] = {256, SEQ, 4}, sXs[2] = {DM * 2, 512};
  const cuuint32_t bXs[3] = {256, 16, 2};
  CUtensorMap mXs = make_map(enc, P.x, 3, dXs, sXs, bXs, CU_TENSOR_MAP_SWIZZLE_NONE);
  const cuuint64_t dG2[4] = {64, DM, FF / 64, 1}, sG2[3] = {FF * 2, 128, (cuuint64_t)FF * DM * 2};
  CUtensorMap mG2 = make_map(enc, P.w_gate, 4, dG2, sG2, bQ, CU_TENSOR_MAP_SWIZZLE_128B);
  CUtensorMap mU2 = make_map(enc, P.w_up, 4, dG2, sG2, bQ, CU_TENSOR_MAP_SWIZZLE_128B);
  (by_sm ? fused_kernel<true> : fused_kernel<false>)<<<NCTA + NSPARE, 384, SM_TOTAL, cudaStreamPerThread>>>(mX, mWkv, mWq, mWo, mPhi, mWp, mOut, mWc, mG, mU, mD, mXs,
                                                                                                           mG2, mU2, P);
}
```

```cpp
#include <cuda_runtime.h>
#include <cuda_bf16.h>
#include <cuda.h>
#include <stdint.h>

namespace {

constexpr int SEQ = 2048, DM = 1024, FF = 3584;
constexpr int NCTA = 128;
constexpr int NSPARE = 4;
constexpr int NFFN = FF / 32;
#define GN 6
#define G8 2
constexpr int GROWS = (3 * GN + G8) * 32;
#define TAILN 2
#define XS_EARLY 1
#define PF_FIRST 2
#define PF_W 5
#define PFD 80
#define BY_SM 1
#define PTAB 0x73216540u
#define REG_C 224
#define REG_H 56
#define SP_DELAY 2000
#define XSTR 288
#define AM_NS 100
constexpr bool FFN_OFF = false;

static_assert(2 * REG_C + REG_H <= 3 * 168, "the register pool of the CTA is 384 x 168");

__device__ uint32_t g_epoch[(NCTA + NSPARE) * 32];
__device__ unsigned long long g_stat[SEQ];
__device__ __align__(128) unsigned long long g_best[NCTA];
__device__ __align__(16) float g_y[2][8][DM];
__device__ __align__(128) uint32_t g_ycnt[64];
__device__ __align__(1024) uint32_t g_xcnt[32 * XSTR];
#define XC1(HG, R) (g_xcnt + ((HG) * 2 + (R)) * XSTR)
#define XC2(HG, R) (g_xcnt + (16 + (HG) * 2 + (R)) * XSTR)
__device__ __align__(128) uint4 g_res[2][32 * 256];
__device__ __align__(16) float g_cs[5 * DM];
__device__ __align__(128) float g_gp[2 * FF];
__device__ uint4 g_part[8 * 2 * 16 * 16 * 32];
__device__ __align__(16) float g_zpart[8 * 2 * 16 * 16 * 8];
__device__ __align__(128) float g_zres[32 * 64];
__device__ __align__(1024) uint4 g_ofr[16 * 16 * 1024];
#define PROF(i)
#define PROFT(i)
#define PROFC(i)
#define PROF_DUMP
#define PW0(J)
#define PW1(J)

constexpr uint32_t KV_STAGE = 49152, Q_STAGE = 32768;
constexpr uint32_t SM_V = 147456;
constexpr uint32_t SM_PHI = 163840;
constexpr uint32_t SM_XST = 147456;
constexpr uint32_t SM_FST = 172032;
constexpr uint32_t SM_PST0 = 196608, SM_PST1 = SM_PHI + 8192;
constexpr uint32_t SM_X0 = 131072, SM_X1 = SM_PHI + 16384;
constexpr uint32_t SM_WPHI = 204800;
constexpr uint32_t SM_ZT = 212992;
constexpr uint32_t SM_SDT = 217088;
constexpr uint32_t SM_CST = 219136;
constexpr uint32_t SM_HT = 222720;
constexpr uint32_t SM_STAT = 223232;
constexpr uint32_t SM_XSEL = 224256;
constexpr uint32_t SM_RED = 228352;
constexpr uint32_t SM_ROWS = SM_RED + 832;
constexpr uint32_t SM_GRED = SM_XSEL + 3072;
static_assert(GROWS <= 768, "xsel area");
constexpr uint32_t SM_UPD = 229632;
constexpr uint32_t SM_BAR = 230016;
constexpr uint32_t SM_PROF = 230464;
constexpr uint32_t SM_SINK = 231104;
constexpr uint32_t SM_TOTAL = 231616;
constexpr uint32_t SB = 1024;
constexpr uint32_t B_FULLKV = 0  , B_FST = 24  , B_XST = 104  , B_WPHI = 120, B_CS = 128, B_CSQ = 136, B_UPD = 144,
                   B_H = 152, B_DN = 160, B_XS = 168, B_TILE = 176  , B_RES = 192  , B_PART = 208  , B_AIN = 224  ,
                   B_FULLQ = 288  ,
                   B_FFN = 320,
                   B_EMPTYKV = 328  , B_EMPTYQ = 352  , B_KVST = 384  , B_YD = 400, B_PHI = 408  , B_DND = 424, B_END = 432;

__device__ __forceinline__ uint32_t smem_u32(const void* p) { return (uint32_t)__cvta_generic_to_shared(p); }
__device__ __forceinline__ void mbar_init(uint32_t bar, uint32_t cnt) { asm volatile("mbarrier.init.shared::cta.b64 [%0], %1;" ::"r"(bar), "r"(cnt) : "memory"); }
__device__ __forceinline__ void mbar_expect_tx(uint32_t bar, uint32_t bytes) { asm volatile("mbarrier.arrive.expect_tx.shared::cta.b64 _, [%0], %1;" ::"r"(bar), "r"(bytes) : "memory"); }
__device__ __forceinline__ void mbar_arrive2(uint32_t bar) { asm volatile("mbarrier.arrive.shared::cta.b64 _, [%0], 2;" ::"r"(bar) : "memory"); }
__device__ __forceinline__ void mbar_arrive(uint32_t bar) { asm volatile("mbarrier.arrive.shared::cta.b64 _, [%0];" ::"r"(bar) : "memory"); }
__device__ __forceinline__ void mbar_wait(uint32_t bar, uint32_t parity) {
  asm volatile("{\n.reg .pred p;\nLW:\nmbarrier.try_wait.parity.shared::cta.b64 p, [%0], %1;\n@!p bra LW;\n}" ::"r"(bar), "r"(parity) : "memory");
}
__device__ __forceinline__ bool mbar_test(uint32_t bar, uint32_t parity) {
  uint32_t ok;
  asm volatile("{\n.reg .pred p;\nmbarrier.test_wait.parity.shared::cta.b64 p, [%1], %2;\nselp.u32 %0, 1, 0, p;\n}" : "=r"(ok) : "r"(bar), "r"(parity) : "memory");
  return ok;
}
__device__ __forceinline__ int lane_id() { int l; asm volatile("mov.u32 %0, %%laneid;" : "=r"(l)); return l; }
template <int C> __device__ __forceinline__ void sched_fence_(int zero) {
  asm volatile("{\n.reg .pred p;\nsetp.eq.s32 p, %0, %1;\n@p trap;\n}" ::"r"(zero), "n"(C) : "memory");
}
#define SCHED_FENCE() sched_fence_<1000 + __COUNTER__>(zero)
#define SCHED_PIN(V) sched_fence_<1000 + __COUNTER__>(zero & __float_as_int(V))
__device__ __forceinline__ bool elect_one() {
  uint32_t p; asm volatile("{ .reg .pred P; elect.sync _|P, 0xffffffff; selp.u32 %0, 1, 0, P; }" : "=r"(p)); return p;
}
__device__ __forceinline__ void tma2d(uint32_t dst, const CUtensorMap* m, int x, int y, uint32_t bar) {
  asm volatile("cp.async.bulk.tensor.2d.shared::cluster.global.mbarrier::complete_tx::bytes [%0], [%1, {%3, %4}], [%2];" ::"r"(dst), "l"(m), "r"(bar), "r"(x), "r"(y) : "memory");
}
__device__ __forceinline__ void tma3d(uint32_t dst, const CUtensorMap* m, int x, int y, int z, uint32_t bar) {
  asm volatile("cp.async.bulk.tensor.3d.shared::cluster.global.mbarrier::complete_tx::bytes [%0], [%1, {%3, %4, %5}], [%2];" ::"r"(dst), "l"(m), "r"(bar), "r"(x), "r"(y), "r"(z) : "memory");
}
__device__ __forceinline__ void tma4d(uint32_t dst, const CUtensorMap* m, int x, int y, int z, int w, uint32_t bar) {
  asm volatile("cp.async.bulk.tensor.4d.shared::cluster.global.mbarrier::complete_tx::bytes [%0], [%1, {%3, %4, %5, %6}], [%2];" ::"r"(dst), "l"(m), "r"(bar), "r"(x), "r"(y), "r"(z), "r"(w) : "memory");
}
__device__ __forceinline__ void tma5d(uint32_t dst, const CUtensorMap* m, int x, int v, uint32_t bar) {
  asm volatile("cp.async.bulk.tensor.5d.shared::cluster.global.mbarrier::complete_tx::bytes [%0], [%1, {%3, %5, %5, %5, %4}], [%2];" ::"r"(dst), "l"(m), "r"(bar), "r"(x), "r"(v), "r"(0) : "memory");
}
__device__ __forceinline__ void tma_store2d(const CUtensorMap* m, uint32_t src, int x, int y) {
  asm volatile("cp.async.bulk.tensor.2d.global.shared::cta.bulk_group [%0, {%2, %3}], [%1];" ::"l"(m), "r"(src), "r"(x), "r"(y) : "memory");
}
__device__ __forceinline__ void bulk_load(uint32_t dst, const void* src, uint32_t bytes, uint32_t bar) {
  asm volatile("cp.async.bulk.shared::cluster.global.mbarrier::complete_tx::bytes [%0], [%1], %2, [%3];" ::"r"(dst), "l"(src), "r"(bytes), "r"(bar) : "memory");
}
__device__ __forceinline__ void bulk_commit() { asm volatile("cp.async.bulk.commit_group;" ::: "memory"); }
__device__ __forceinline__ void bulk_wait_read0() { asm volatile("cp.async.bulk.wait_group.read 0;" ::: "memory"); }
__device__ __forceinline__ void prefetch_l2(const void* p) { asm volatile("prefetch.global.L2 [%0];" ::"l"(p) : "memory"); }
__device__ __forceinline__ void touch_l2(const void* p, int lane) { asm volatile("cp.async.cg.shared.global.L2::128B [%0], [%1], 16;" ::"r"(SB + SM_SINK + lane * 16), "l"(p) : "memory"); }
__device__ __forceinline__ void cp_async16(uint32_t dst, const void* src) { asm volatile("cp.async.cg.shared.global [%0], [%1], 16;" ::"r"(dst), "l"(src) : "memory"); }
__device__ __forceinline__ void prefetch_map(const CUtensorMap* m) { asm volatile("prefetch.tensormap [%0];" ::"l"(m) : "memory"); }
__device__ __forceinline__ void fence_async_smem() { asm volatile("fence.proxy.async.shared::cta;" ::: "memory"); }
__device__ __forceinline__ void fence_async_global() { asm volatile("fence.proxy.async.global;" ::: "memory"); }
__device__ __forceinline__ void bar_sync(int id, int n) { asm volatile("bar.sync %0, %1;" ::"r"(id), "r"(n) : "memory"); }
__device__ __forceinline__ void wg_fence() { asm volatile("wgmma.fence.sync.aligned;" ::: "memory"); }
__device__ __forceinline__ void wg_commit() { asm volatile("wgmma.commit_group.sync.aligned;" ::: "memory"); }
template <int N> __device__ __forceinline__ void wg_wait() { asm volatile("wgmma.wait_group.sync.aligned %0;" ::"n"(N) : "memory"); }
template <int N> __device__ __forceinline__ void reg_fence(uint32_t* r) {
#pragma unroll
  for (int i = 0; i < N; i++) asm volatile("" : "+r"(r[i])::"memory");
}
template <int N> __device__ __forceinline__ void reg_fence(float* r) {
#pragma unroll
  for (int i = 0; i < N; i++) asm volatile("" : "+f"(r[i])::"memory");
}
__device__ __forceinline__ uint64_t mkdesc(uint32_t addr, uint32_t lbo, uint32_t sbo, uint32_t swz, uint32_t dyn = 0) {
  const uint32_t lo = ((addr >> 4) | ((lbo >> 4) << 16)) + dyn;
  const uint32_t hi = (sbo >> 4) | (swz << 30);
  uint64_t d;
  asm("mov.b64 %0, {%1, %2};" : "=l"(d) : "r"(lo), "r"(hi));
  return d;
}
__device__ __forceinline__ void stsm4(uint32_t addr, uint32_t a, uint32_t b, uint32_t c, uint32_t d) {
  asm volatile("stmatrix.sync.aligned.m8n8.x4.shared.b16 [%0], {%1, %2, %3, %4};" ::"r"(addr), "r"(a), "r"(b), "r"(c), "r"(d) : "memory");
}
__device__ __forceinline__ void ldsm4(uint32_t addr, uint32_t& a, uint32_t& b, uint32_t& c, uint32_t& d) {
  asm volatile("ldmatrix.sync.aligned.m8n8.x4.shared.b16 {%0, %1, %2, %3}, [%4];" : "=r"(a), "=r"(b), "=r"(c), "=r"(d) : "r"(addr) : "memory");
}
__device__ __forceinline__ uint32_t pack2(float lo, float hi) { uint32_t r; asm("cvt.rn.bf16x2.f32 %0, %1, %2;" : "=r"(r) : "f"(hi), "f"(lo)); return r; }
__device__ __forceinline__ uint32_t bsub2(uint32_t a, uint32_t b) { uint32_t r; asm("sub.rn.bf16x2 %0, %1, %2;" : "=r"(r) : "r"(a), "r"(b)); return r; }
__device__ __forceinline__ uint32_t badd2(uint32_t a, uint32_t b) { uint32_t r; asm("add.rn.bf16x2 %0, %1, %2;" : "=r"(r) : "r"(a), "r"(b)); return r; }
__device__ __forceinline__ uint32_t bmul2(uint32_t a, uint32_t b) { uint32_t r; asm("mul.rn.bf16x2 %0, %1, %2;" : "=r"(r) : "r"(a), "r"(b)); return r; }
__device__ __forceinline__ float bf_lo(uint32_t v) { return __uint_as_float(v << 16); }
__device__ __forceinline__ float bf_hi(uint32_t v) { return __uint_as_float(v & 0xffff0000u); }
__device__ __forceinline__ float bf_round(float v) { return bf_lo(pack2(v, 0.f)); }
__device__ __forceinline__ float ex2(float v) { float r; asm("ex2.approx.ftz.f32 %0, %1;" : "=f"(r) : "f"(v)); return r; }
__device__ __forceinline__ float rcp(float v) { float r; asm("rcp.approx.ftz.f32 %0, %1;" : "=f"(r) : "f"(v)); return r; }
__device__ __forceinline__ float sqrt_approx(float v) { float r; asm("sqrt.approx.f32 %0, %1;" : "=f"(r) : "f"(v)); return r; }
__device__ __forceinline__ float4 lds128(uint32_t a) { float4 v; asm volatile("ld.shared.v4.f32 {%0, %1, %2, %3}, [%4];" : "=f"(v.x), "=f"(v.y), "=f"(v.z), "=f"(v.w) : "r"(a) : "memory"); return v; }
__device__ __forceinline__ uint4 lds128u(uint32_t a) { uint4 v; asm volatile("ld.shared.v4.u32 {%0, %1, %2, %3}, [%4];" : "=r"(v.x), "=r"(v.y), "=r"(v.z), "=r"(v.w) : "r"(a) : "memory"); return v; }
__device__ __forceinline__ float2 lds64(uint32_t a) { float2 v; asm volatile("ld.shared.v2.f32 {%0, %1}, [%2];" : "=f"(v.x), "=f"(v.y) : "r"(a) : "memory"); return v; }
__device__ __forceinline__ float lds32(uint32_t a) { float v; asm volatile("ld.shared.f32 %0, [%1];" : "=f"(v) : "r"(a) : "memory"); return v; }
__device__ __forceinline__ void sts32(uint32_t a, float v) { asm volatile("st.shared.f32 [%0], %1;" ::"r"(a), "f"(v) : "memory"); }
__device__ __forceinline__ void sts64(uint32_t a, float x, float y) { asm volatile("st.shared.v2.f32 [%0], {%1, %2};" ::"r"(a), "f"(x), "f"(y) : "memory"); }
__device__ __forceinline__ void sts128(uint32_t a, float x, float y, float z, float w) { asm volatile("st.shared.v4.f32 [%0], {%1, %2, %3, %4};" ::"r"(a), "f"(x), "f"(y), "f"(z), "f"(w) : "memory"); }
__device__ __forceinline__ void sts64u(uint32_t a, uint32_t x, uint32_t y) { asm volatile("st.shared.v2.u32 [%0], {%1, %2};" ::"r"(a), "r"(x), "r"(y) : "memory"); }
__device__ __forceinline__ void sts128u(uint32_t a, uint32_t x, uint32_t y, uint32_t z, uint32_t w) { asm volatile("st.shared.v4.u32 [%0], {%1, %2, %3, %4};" ::"r"(a), "r"(x), "r"(y), "r"(z), "r"(w) : "memory"); }
__device__ __forceinline__ uint4 ldg_nc(const void* p) { uint4 v; asm volatile("ld.global.nc.L1::no_allocate.v4.u32 {%0, %1, %2, %3}, [%4];" : "=r"(v.x), "=r"(v.y), "=r"(v.z), "=r"(v.w) : "l"(p)); return v; }
__device__ __forceinline__ float4 ldg_cg4(const float* p) { float4 v; asm volatile("ld.global.cg.v4.f32 {%0, %1, %2, %3}, [%4];" : "=f"(v.x), "=f"(v.y), "=f"(v.z), "=f"(v.w) : "l"(p) : "memory"); return v; }
__device__ __forceinline__ uint32_t ld_acq(const uint32_t* p) { uint32_t v; asm volatile("ld.acquire.gpu.global.u32 %0, [%1];" : "=r"(v) : "l"(p) : "memory"); return v; }
__device__ __forceinline__ unsigned long long ld_rlx64(const unsigned long long* p) { unsigned long long v; asm volatile("ld.relaxed.gpu.global.u64 %0, [%1];" : "=l"(v) : "l"(p) : "memory"); return v; }
__device__ __forceinline__ void st_rlx64(unsigned long long* p, unsigned long long v) { asm volatile("st.relaxed.gpu.global.u64 [%0], %1;" ::"l"(p), "l"(v) : "memory"); }
__device__ __forceinline__ uint4 ld_rlx128(const void* p) {
  uint4 v;
  asm volatile("{ .reg .b128 t; .reg .b64 a, b; ld.relaxed.gpu.global.b128 t, [%4]; mov.b128 {a, b}, t; mov.b64 {%0, %1}, a; mov.b64 {%2, %3}, b; }"
               : "=r"(v.x), "=r"(v.y), "=r"(v.z), "=r"(v.w) : "l"(p) : "memory");
  return v;
}
__device__ __forceinline__ void st_rlx128(void* p, uint32_t x, uint32_t y, uint32_t z, uint32_t w) {
  asm volatile("{ .reg .b128 t; .reg .b64 a, b; mov.b64 a, {%1, %2}; mov.b64 b, {%3, %4}; mov.b128 t, {a, b}; st.relaxed.gpu.global.b128 [%0], t; }"
               ::"l"(p), "r"(x), "r"(y), "r"(z), "r"(w) : "memory");
}
__device__ __forceinline__ void st_rlx(void* p, uint32_t v) { asm volatile("st.relaxed.gpu.global.u32 [%0], %1;" ::"l"(p), "r"(v) : "memory"); }
__device__ __forceinline__ uint32_t lop_select(uint32_t a, uint32_t b, uint32_t m) { uint32_t r; asm("lop3.b32 %0, %1, %2, %3, 0xd8;" : "=r"(r) : "r"(a), "r"(b), "r"(m)); return r; }
__device__ __forceinline__ float unmark(uint32_t v) { return __uint_as_float(v & ~1u); }
__device__ __forceinline__ uint32_t mark(uint32_t v, uint32_t par) { return (v & ~1u) | par; }
__device__ __forceinline__ float tanh_approx(float v) { float r; asm("tanh.approx.f32 %0, %1;" : "=f"(r) : "f"(v)); return r; }
__device__ __forceinline__ void red1(float* p, float a) { asm volatile("red.global.add.f32 [%0], %1;" ::"l"(p), "f"(a) : "memory"); }
__device__ __forceinline__ void red_inc(uint32_t* p) { asm volatile("red.relaxed.gpu.global.add.u32 [%0], 1;" ::"l"(p) : "memory"); }
__device__ __forceinline__ void red_rel(uint32_t* p) { asm volatile("red.release.gpu.global.add.u32 [%0], 1;" ::"l"(p) : "memory"); }
constexpr int SPIN_MAX = 100000;
__device__ __forceinline__ uint32_t ld_rlx(const uint32_t* p) { uint32_t v; asm volatile("ld.relaxed.gpu.global.u32 %0, [%1];" : "=r"(v) : "l"(p) : "memory"); return v; }
template <int NS = 0> __device__ __forceinline__ void wait_hint(const uint32_t* p, uint32_t target) {
#pragma unroll 1
  for (int i = 0; i < SPIN_MAX; i++) { if ((int)(ld_rlx(p) - target) >= 0) break; if (NS) __nanosleep(NS); }
}
template <int NS> __device__ __forceinline__ void wait_cnt(const uint32_t* p, uint32_t target) {
#pragma unroll 1
  for (int i = 0; i < SPIN_MAX; i++) { if ((int)(ld_rlx(p) - target) >= 0) break; if (NS) __nanosleep(NS); }
  (void)ld_acq(p);
}
template <int NS> __device__ __forceinline__ unsigned long long wait_tag(const unsigned long long* p, uint32_t tag) {
  unsigned long long v = 0;
#pragma unroll 1
  for (int i = 0; i < SPIN_MAX; i++) { v = ld_rlx64(p); if ((uint32_t)(v >> 32) == tag) break; if (NS) __nanosleep(NS); }
  return v;
}
__device__ __forceinline__ float silu_f(float v) { return v * rcp(1.f + ex2(-1.4426950408889634f * v)); }

__device__ __forceinline__ void wgmma_n8_ss_ta1_tb0(float* d, uint64_t da, uint64_t db, bool accumulate) {
  if (accumulate) {
    asm volatile("{\n.reg .pred p;\nsetp.ne.b32 p, 1, 0;\n"
      "wgmma.mma_async.sync.aligned.m64n8k16.f32.bf16.bf16 "
      "{%0, %1, %2, %3}, "
      "%4, %5, p, 1, 1, 1, 0;\n}\n"
      : "+f"(d[0]), "+f"(d[1]), "+f"(d[2]), "+f"(d[3])
      : "l"(da), "l"(db));
  } else {
    asm volatile("{\n.reg .pred p;\nsetp.ne.b32 p, 0, 0;\n"
      "wgmma.mma_async.sync.aligned.m64n8k16.f32.bf16.bf16 "
      "{%0, %1, %2, %3}, "
      "%4, %5, p, 1, 1, 1, 0;\n}\n"
      : "=f"(d[0]), "=f"(d[1]), "=f"(d[2]), "=f"(d[3])
      : "l"(da), "l"(db));
  }
}
__device__ __forceinline__ void wgmma_n8_ss_ta1_tb1(float* d, uint64_t da, uint64_t db, bool accumulate) {
  if (accumulate) {
    asm volatile("{\n.reg .pred p;\nsetp.ne.b32 p, 1, 0;\n"
      "wgmma.mma_async.sync.aligned.m64n8k16.f32.bf16.bf16 "
      "{%0, %1, %2, %3}, "
      "%4, %5, p, 1, 1, 1, 1;\n}\n"
      : "+f"(d[0]), "+f"(d[1]), "+f"(d[2]), "+f"(d[3])
      : "l"(da), "l"(db));
  } else {
    asm volatile("{\n.reg .pred p;\nsetp.ne.b32 p, 0, 0;\n"
      "wgmma.mma_async.sync.aligned.m64n8k16.f32.bf16.bf16 "
      "{%0, %1, %2, %3}, "
      "%4, %5, p, 1, 1, 1, 1;\n}\n"
      : "=f"(d[0]), "=f"(d[1]), "=f"(d[2]), "=f"(d[3])
      : "l"(da), "l"(db));
  }
}
__device__ __forceinline__ void wgmma_n32_rs_ta0_tb1(float* d, uint32_t a0, uint32_t a1, uint32_t a2, uint32_t a3, uint64_t db, bool accumulate) {
  if (accumulate) {
    asm volatile("{\n.reg .pred p;\nsetp.ne.b32 p, 1, 0;\n"
      "wgmma.mma_async.sync.aligned.m64n32k16.f32.bf16.bf16 "
      "{%0, %1, %2, %3, %4, %5, %6, %7, %8, %9, %10, %11, %12, %13, %14, %15}, "
      "{%16, %17, %18, %19}, %20, p, 1, 1, 1;\n}\n"
      : "+f"(d[0]), "+f"(d[1]), "+f"(d[2]), "+f"(d[3]), "+f"(d[4]), "+f"(d[5]), "+f"(d[6]), "+f"(d[7]), "+f"(d[8]), "+f"(d[9]), "+f"(d[10]), "+f"(d[11]), "+f"(d[12]), "+f"(d[13]), "+f"(d[14]), "+f"(d[15])
      : "r"(a0), "r"(a1), "r"(a2), "r"(a3), "l"(db));
  } else {
    asm volatile("{\n.reg .pred p;\nsetp.ne.b32 p, 0, 0;\n"
      "wgmma.mma_async.sync.aligned.m64n32k16.f32.bf16.bf16 "
      "{%0, %1, %2, %3, %4, %5, %6, %7, %8, %9, %10, %11, %12, %13, %14, %15}, "
      "{%16, %17, %18, %19}, %20, p, 1, 1, 1;\n}\n"
      : "=f"(d[0]), "=f"(d[1]), "=f"(d[2]), "=f"(d[3]), "=f"(d[4]), "=f"(d[5]), "=f"(d[6]), "=f"(d[7]), "=f"(d[8]), "=f"(d[9]), "=f"(d[10]), "=f"(d[11]), "=f"(d[12]), "=f"(d[13]), "=f"(d[14]), "=f"(d[15])
      : "r"(a0), "r"(a1), "r"(a2), "r"(a3), "l"(db));
  }
}
__device__ __forceinline__ void wgmma_n40_rs_ta0_tb1(float* d, uint32_t a0, uint32_t a1, uint32_t a2, uint32_t a3, uint64_t db, bool accumulate) {
  if (accumulate) {
    asm volatile("{\n.reg .pred p;\nsetp.ne.b32 p, 1, 0;\n"
      "wgmma.mma_async.sync.aligned.m64n40k16.f32.bf16.bf16 "
      "{%0, %1, %2, %3, %4, %5, %6, %7, %8, %9, %10, %11, %12, %13, %14, %15, %16, %17, %18, %19}, "
      "{%20, %21, %22, %23}, %24, p, 1, 1, 1;\n}\n"
      : "+f"(d[0]), "+f"(d[1]), "+f"(d[2]), "+f"(d[3]), "+f"(d[4]), "+f"(d[5]), "+f"(d[6]), "+f"(d[7]), "+f"(d[8]), "+f"(d[9]), "+f"(d[10]), "+f"(d[11]), "+f"(d[12]), "+f"(d[13]), "+f"(d[14]), "+f"(d[15]), "+f"(d[16]), "+f"(d[17]), "+f"(d[18]), "+f"(d[19])
      : "r"(a0), "r"(a1), "r"(a2), "r"(a3), "l"(db));
  } else {
    asm volatile("{\n.reg .pred p;\nsetp.ne.b32 p, 0, 0;\n"
      "wgmma.mma_async.sync.aligned.m64n40k16.f32.bf16.bf16 "
      "{%0, %1, %2, %3, %4, %5, %6, %7, %8, %9, %10, %11, %12, %13, %14, %15, %16, %17, %18, %19}, "
      "{%20, %21, %22, %23}, %24, p, 1, 1, 1;\n}\n"
      : "=f"(d[0]), "=f"(d[1]), "=f"(d[2]), "=f"(d[3]), "=f"(d[4]), "=f"(d[5]), "=f"(d[6]), "=f"(d[7]), "=f"(d[8]), "=f"(d[9]), "=f"(d[10]), "=f"(d[11]), "=f"(d[12]), "=f"(d[13]), "=f"(d[14]), "=f"(d[15]), "=f"(d[16]), "=f"(d[17]), "=f"(d[18]), "=f"(d[19])
      : "r"(a0), "r"(a1), "r"(a2), "r"(a3), "l"(db));
  }
}
__device__ __forceinline__ void wgmma_n40_ss_ta1_tb1(float* d, uint64_t da, uint64_t db, bool accumulate) {
  if (accumulate) {
    asm volatile("{\n.reg .pred p;\nsetp.ne.b32 p, 1, 0;\n"
      "wgmma.mma_async.sync.aligned.m64n40k16.f32.bf16.bf16 "
      "{%0, %1, %2, %3, %4, %5, %6, %7, %8, %9, %10, %11, %12, %13, %14, %15, %16, %17, %18, %19}, "
      "%20, %21, p, 1, 1, 1, 1;\n}\n"
      : "+f"(d[0]), "+f"(d[1]), "+f"(d[2]), "+f"(d[3]), "+f"(d[4]), "+f"(d[5]), "+f"(d[6]), "+f"(d[7]), "+f"(d[8]), "+f"(d[9]), "+f"(d[10]), "+f"(d[11]), "+f"(d[12]), "+f"(d[13]), "+f"(d[14]), "+f"(d[15]), "+f"(d[16]), "+f"(d[17]), "+f"(d[18]), "+f"(d[19])
      : "l"(da), "l"(db));
  } else {
    asm volatile("{\n.reg .pred p;\nsetp.ne.b32 p, 0, 0;\n"
      "wgmma.mma_async.sync.aligned.m64n40k16.f32.bf16.bf16 "
      "{%0, %1, %2, %3, %4, %5, %6, %7, %8, %9, %10, %11, %12, %13, %14, %15, %16, %17, %18, %19}, "
      "%20, %21, p, 1, 1, 1, 1;\n}\n"
      : "=f"(d[0]), "=f"(d[1]), "=f"(d[2]), "=f"(d[3]), "=f"(d[4]), "=f"(d[5]), "=f"(d[6]), "=f"(d[7]), "=f"(d[8]), "=f"(d[9]), "=f"(d[10]), "=f"(d[11]), "=f"(d[12]), "=f"(d[13]), "=f"(d[14]), "=f"(d[15]), "=f"(d[16]), "=f"(d[17]), "=f"(d[18]), "=f"(d[19])
      : "l"(da), "l"(db));
  }
}
__device__ __forceinline__ void wgmma_n128_rs_ta0_tb1(float* d, uint32_t a0, uint32_t a1, uint32_t a2, uint32_t a3, uint64_t db, bool accumulate) {
  if (accumulate) {
    asm volatile("{\n.reg .pred p;\nsetp.ne.b32 p, 1, 0;\n"
      "wgmma.mma_async.sync.aligned.m64n128k16.f32.bf16.bf16 "
      "{%0, %1, %2, %3, %4, %5, %6, %7, %8, %9, %10, %11, %12, %13, %14, %15, %16, %17, %18, %19, %20, %21, %22, %23, %24, %25, %26, %27, %28, %29, %30, %31, %32, %33, %34, %35, %36, %37, %38, %39, %40, %41, %42, %43, %44, %45, %46, %47, %48, %49, %50, %51, %52, %53, %54, %55, %56, %57, %58, %59, %60, %61, %62, %63}, "
      "{%64, %65, %66, %67}, %68, p, 1, 1, 1;\n}\n"
      : "+f"(d[0]), "+f"(d[1]), "+f"(d[2]), "+f"(d[3]), "+f"(d[4]), "+f"(d[5]), "+f"(d[6]), "+f"(d[7]), "+f"(d[8]), "+f"(d[9]), "+f"(d[10]), "+f"(d[11]), "+f"(d[12]), "+f"(d[13]), "+f"(d[14]), "+f"(d[15]), "+f"(d[16]), "+f"(d[17]), "+f"(d[18]), "+f"(d[19]), "+f"(d[20]), "+f"(d[21]), "+f"(d[22]), "+f"(d[23]), "+f"(d[24]), "+f"(d[25]), "+f"(d[26]), "+f"(d[27]), "+f"(d[28]), "+f"(d[29]), "+f"(d[30]), "+f"(d[31]), "+f"(d[32]), "+f"(d[33]), "+f"(d[34]), "+f"(d[35]), "+f"(d[36]), "+f"(d[37]), "+f"(d[38]), "+f"(d[39]), "+f"(d[40]), "+f"(d[41]), "+f"(d[42]), "+f"(d[43]), "+f"(d[44]), "+f"(d[45]), "+f"(d[46]), "+f"(d[47]), "+f"(d[48]), "+f"(d[49]), "+f"(d[50]), "+f"(d[51]), "+f"(d[52]), "+f"(d[53]), "+f"(d[54]), "+f"(d[55]), "+f"(d[56]), "+f"(d[57]), "+f"(d[58]), "+f"(d[59]), "+f"(d[60]), "+f"(d[61]), "+f"(d[62]), "+f"(d[63])
      : "r"(a0), "r"(a1), "r"(a2), "r"(a3), "l"(db));
  } else {
    asm volatile("{\n.reg .pred p;\nsetp.ne.b32 p, 0, 0;\n"
      "wgmma.mma_async.sync.aligned.m64n128k16.f32.bf16.bf16 "
      "{%0, %1, %2, %3, %4, %5, %6, %7, %8, %9, %10, %11, %12, %13, %14, %15, %16, %17, %18, %19, %20, %21, %22, %23, %24, %25, %26, %27, %28, %29, %30, %31, %32, %33, %34, %35, %36, %37, %38, %39, %40, %41, %42, %43, %44, %45, %46, %47, %48, %49, %50, %51, %52, %53, %54, %55, %56, %57, %58, %59, %60, %61, %62, %63}, "
      "{%64, %65, %66, %67}, %68, p, 1, 1, 1;\n}\n"
      : "=f"(d[0]), "=f"(d[1]), "=f"(d[2]), "=f"(d[3]), "=f"(d[4]), "=f"(d[5]), "=f"(d[6]), "=f"(d[7]), "=f"(d[8]), "=f"(d[9]), "=f"(d[10]), "=f"(d[11]), "=f"(d[12]), "=f"(d[13]), "=f"(d[14]), "=f"(d[15]), "=f"(d[16]), "=f"(d[17]), "=f"(d[18]), "=f"(d[19]), "=f"(d[20]), "=f"(d[21]), "=f"(d[22]), "=f"(d[23]), "=f"(d[24]), "=f"(d[25]), "=f"(d[26]), "=f"(d[27]), "=f"(d[28]), "=f"(d[29]), "=f"(d[30]), "=f"(d[31]), "=f"(d[32]), "=f"(d[33]), "=f"(d[34]), "=f"(d[35]), "=f"(d[36]), "=f"(d[37]), "=f"(d[38]), "=f"(d[39]), "=f"(d[40]), "=f"(d[41]), "=f"(d[42]), "=f"(d[43]), "=f"(d[44]), "=f"(d[45]), "=f"(d[46]), "=f"(d[47]), "=f"(d[48]), "=f"(d[49]), "=f"(d[50]), "=f"(d[51]), "=f"(d[52]), "=f"(d[53]), "=f"(d[54]), "=f"(d[55]), "=f"(d[56]), "=f"(d[57]), "=f"(d[58]), "=f"(d[59]), "=f"(d[60]), "=f"(d[61]), "=f"(d[62]), "=f"(d[63])
      : "r"(a0), "r"(a1), "r"(a2), "r"(a3), "l"(db));
  }
}
__device__ __forceinline__ void wgmma_n128_ss_ta0_tb1(float* d, uint64_t da, uint64_t db, bool accumulate) {
  if (accumulate) {
    asm volatile("{\n.reg .pred p;\nsetp.ne.b32 p, 1, 0;\n"
      "wgmma.mma_async.sync.aligned.m64n128k16.f32.bf16.bf16 "
      "{%0, %1, %2, %3, %4, %5, %6, %7, %8, %9, %10, %11, %12, %13, %14, %15, %16, %17, %18, %19, %20, %21, %22, %23, %24, %25, %26, %27, %28, %29, %30, %31, %32, %33, %34, %35, %36, %37, %38, %39, %40, %41, %42, %43, %44, %45, %46, %47, %48, %49, %50, %51, %52, %53, %54, %55, %56, %57, %58, %59, %60, %61, %62, %63}, "
      "%64, %65, p, 1, 1, 0, 1;\n}\n"
      : "+f"(d[0]), "+f"(d[1]), "+f"(d[2]), "+f"(d[3]), "+f"(d[4]), "+f"(d[5]), "+f"(d[6]), "+f"(d[7]), "+f"(d[8]), "+f"(d[9]), "+f"(d[10]), "+f"(d[11]), "+f"(d[12]), "+f"(d[13]), "+f"(d[14]), "+f"(d[15]), "+f"(d[16]), "+f"(d[17]), "+f"(d[18]), "+f"(d[19]), "+f"(d[20]), "+f"(d[21]), "+f"(d[22]), "+f"(d[23]), "+f"(d[24]), "+f"(d[25]), "+f"(d[26]), "+f"(d[27]), "+f"(d[28]), "+f"(d[29]), "+f"(d[30]), "+f"(d[31]), "+f"(d[32]), "+f"(d[33]), "+f"(d[34]), "+f"(d[35]), "+f"(d[36]), "+f"(d[37]), "+f"(d[38]), "+f"(d[39]), "+f"(d[40]), "+f"(d[41]), "+f"(d[42]), "+f"(d[43]), "+f"(d[44]), "+f"(d[45]), "+f"(d[46]), "+f"(d[47]), "+f"(d[48]), "+f"(d[49]), "+f"(d[50]), "+f"(d[51]), "+f"(d[52]), "+f"(d[53]), "+f"(d[54]), "+f"(d[55]), "+f"(d[56]), "+f"(d[57]), "+f"(d[58]), "+f"(d[59]), "+f"(d[60]), "+f"(d[61]), "+f"(d[62]), "+f"(d[63])
      : "l"(da), "l"(db));
  } else {
    asm volatile("{\n.reg .pred p;\nsetp.ne.b32 p, 0, 0;\n"
      "wgmma.mma_async.sync.aligned.m64n128k16.f32.bf16.bf16 "
      "{%0, %1, %2, %3, %4, %5, %6, %7, %8, %9, %10, %11, %12, %13, %14, %15, %16, %17, %18, %19, %20, %21, %22, %23, %24, %25, %26, %27, %28, %29, %30, %31, %32, %33, %34, %35, %36, %37, %38, %39, %40, %41, %42, %43, %44, %45, %46, %47, %48, %49, %50, %51, %52, %53, %54, %55, %56, %57, %58, %59, %60, %61, %62, %63}, "
      "%64, %65, p, 1, 1, 0, 1;\n}\n"
      : "=f"(d[0]), "=f"(d[1]), "=f"(d[2]), "=f"(d[3]), "=f"(d[4]), "=f"(d[5]), "=f"(d[6]), "=f"(d[7]), "=f"(d[8]), "=f"(d[9]), "=f"(d[10]), "=f"(d[11]), "=f"(d[12]), "=f"(d[13]), "=f"(d[14]), "=f"(d[15]), "=f"(d[16]), "=f"(d[17]), "=f"(d[18]), "=f"(d[19]), "=f"(d[20]), "=f"(d[21]), "=f"(d[22]), "=f"(d[23]), "=f"(d[24]), "=f"(d[25]), "=f"(d[26]), "=f"(d[27]), "=f"(d[28]), "=f"(d[29]), "=f"(d[30]), "=f"(d[31]), "=f"(d[32]), "=f"(d[33]), "=f"(d[34]), "=f"(d[35]), "=f"(d[36]), "=f"(d[37]), "=f"(d[38]), "=f"(d[39]), "=f"(d[40]), "=f"(d[41]), "=f"(d[42]), "=f"(d[43]), "=f"(d[44]), "=f"(d[45]), "=f"(d[46]), "=f"(d[47]), "=f"(d[48]), "=f"(d[49]), "=f"(d[50]), "=f"(d[51]), "=f"(d[52]), "=f"(d[53]), "=f"(d[54]), "=f"(d[55]), "=f"(d[56]), "=f"(d[57]), "=f"(d[58]), "=f"(d[59]), "=f"(d[60]), "=f"(d[61]), "=f"(d[62]), "=f"(d[63])
      : "l"(da), "l"(db));
  }
}
__device__ __forceinline__ void wgmma_n256_rs_ta0_tb1(float* d, uint32_t a0, uint32_t a1, uint32_t a2, uint32_t a3, uint64_t db, bool accumulate) {
  if (accumulate) {
    asm volatile("{\n.reg .pred p;\nsetp.ne.b32 p, 1, 0;\n"
      "wgmma.mma_async.sync.aligned.m64n256k16.f32.bf16.bf16 "
      "{%0, %1, %2, %3, %4, %5, %6, %7, %8, %9, %10, %11, %12, %13, %14, %15, %16, %17, %18, %19, %20, %21, %22, %23, %24, %25, %26, %27, %28, %29, %30, %31, %32, %33, %34, %35, %36, %37, %38, %39, %40, %41, %42, %43, %44, %45, %46, %47, %48, %49, %50, %51, %52, %53, %54, %55, %56, %57, %58, %59, %60, %61, %62, %63, %64, %65, %66, %67, %68, %69, %70, %71, %72, %73, %74, %75, %76, %77, %78, %79, %80, %81, %82, %83, %84, %85, %86, %87, %88, %89, %90, %91, %92, %93, %94, %95, %96, %97, %98, %99, %100, %101, %102, %103, %104, %105, %106, %107, %108, %109, %110, %111, %112, %113, %114, %115, %116, %117, %118, %119, %120, %121, %122, %123, %124, %125, %126, %127}, "
      "{%128, %129, %130, %131}, %132, p, 1, 1, 1;\n}\n"
      : "+f"(d[0]), "+f"(d[1]), "+f"(d[2]), "+f"(d[3]), "+f"(d[4]), "+f"(d[5]), "+f"(d[6]), "+f"(d[7]), "+f"(d[8]), "+f"(d[9]), "+f"(d[10]), "+f"(d[11]), "+f"(d[12]), "+f"(d[13]), "+f"(d[14]), "+f"(d[15]), "+f"(d[16]), "+f"(d[17]), "+f"(d[18]), "+f"(d[19]), "+f"(d[20]), "+f"(d[21]), "+f"(d[22]), "+f"(d[23]), "+f"(d[24]), "+f"(d[25]), "+f"(d[26]), "+f"(d[27]), "+f"(d[28]), "+f"(d[29]), "+f"(d[30]), "+f"(d[31]), "+f"(d[32]), "+f"(d[33]), "+f"(d[34]), "+f"(d[35]), "+f"(d[36]), "+f"(d[37]), "+f"(d[38]), "+f"(d[39]), "+f"(d[40]), "+f"(d[41]), "+f"(d[42]), "+f"(d[43]), "+f"(d[44]), "+f"(d[45]), "+f"(d[46]), "+f"(d[47]), "+f"(d[48]), "+f"(d[49]), "+f"(d[50]), "+f"(d[51]), "+f"(d[52]), "+f"(d[53]), "+f"(d[54]), "+f"(d[55]), "+f"(d[56]), "+f"(d[57]), "+f"(d[58]), "+f"(d[59]), "+f"(d[60]), "+f"(d[61]), "+f"(d[62]), "+f"(d[63]), "+f"(d[64]), "+f"(d[65]), "+f"(d[66]), "+f"(d[67]), "+f"(d[68]), "+f"(d[69]), "+f"(d[70]), "+f"(d[71]), "+f"(d[72]), "+f"(d[73]), "+f"(d[74]), "+f"(d[75]), "+f"(d[76]), "+f"(d[77]), "+f"(d[78]), "+f"(d[79]), "+f"(d[80]), "+f"(d[81]), "+f"(d[82]), "+f"(d[83]), "+f"(d[84]), "+f"(d[85]), "+f"(d[86]), "+f"(d[87]), "+f"(d[88]), "+f"(d[89]), "+f"(d[90]), "+f"(d[91]), "+f"(d[92]), "+f"(d[93]), "+f"(d[94]), "+f"(d[95]), "+f"(d[96]), "+f"(d[97]), "+f"(d[98]), "+f"(d[99]), "+f"(d[100]), "+f"(d[101]), "+f"(d[102]), "+f"(d[103]), "+f"(d[104]), "+f"(d[105]), "+f"(d[106]), "+f"(d[107]), "+f"(d[108]), "+f"(d[109]), "+f"(d[110]), "+f"(d[111]), "+f"(d[112]), "+f"(d[113]), "+f"(d[114]), "+f"(d[115]), "+f"(d[116]), "+f"(d[117]), "+f"(d[118]), "+f"(d[119]), "+f"(d[120]), "+f"(d[121]), "+f"(d[122]), "+f"(d[123]), "+f"(d[124]), "+f"(d[125]), "+f"(d[126]), "+f"(d[127])
      : "r"(a0), "r"(a1), "r"(a2), "r"(a3), "l"(db));
  } else {
    asm volatile("{\n.reg .pred p;\nsetp.ne.b32 p, 0, 0;\n"
      "wgmma.mma_async.sync.aligned.m64n256k16.f32.bf16.bf16 "
      "{%0, %1, %2, %3, %4, %5, %6, %7, %8, %9, %10, %11, %12, %13, %14, %15, %16, %17, %18, %19, %20, %21, %22, %23, %24, %25, %26, %27, %28, %29, %30, %31, %32, %33, %34, %35, %36, %37, %38, %39, %40, %41, %42, %43, %44, %45, %46, %47, %48, %49, %50, %51, %52, %53, %54, %55, %56, %57, %58, %59, %60, %61, %62, %63, %64, %65, %66, %67, %68, %69, %70, %71, %72, %73, %74, %75, %76, %77, %78, %79, %80, %81, %82, %83, %84, %85, %86, %87, %88, %89, %90, %91, %92, %93, %94, %95, %96, %97, %98, %99, %100, %101, %102, %103, %104, %105, %106, %107, %108, %109, %110, %111, %112, %113, %114, %115, %116, %117, %118, %119, %120, %121, %122, %123, %124, %125, %126, %127}, "
      "{%128, %129, %130, %131}, %132, p, 1, 1, 1;\n}\n"
      : "=f"(d[0]), "=f"(d[1]), "=f"(d[2]), "=f"(d[3]), "=f"(d[4]), "=f"(d[5]), "=f"(d[6]), "=f"(d[7]), "=f"(d[8]), "=f"(d[9]), "=f"(d[10]), "=f"(d[11]), "=f"(d[12]), "=f"(d[13]), "=f"(d[14]), "=f"(d[15]), "=f"(d[16]), "=f"(d[17]), "=f"(d[18]), "=f"(d[19]), "=f"(d[20]), "=f"(d[21]), "=f"(d[22]), "=f"(d[23]), "=f"(d[24]), "=f"(d[25]), "=f"(d[26]), "=f"(d[27]), "=f"(d[28]), "=f"(d[29]), "=f"(d[30]), "=f"(d[31]), "=f"(d[32]), "=f"(d[33]), "=f"(d[34]), "=f"(d[35]), "=f"(d[36]), "=f"(d[37]), "=f"(d[38]), "=f"(d[39]), "=f"(d[40]), "=f"(d[41]), "=f"(d[42]), "=f"(d[43]), "=f"(d[44]), "=f"(d[45]), "=f"(d[46]), "=f"(d[47]), "=f"(d[48]), "=f"(d[49]), "=f"(d[50]), "=f"(d[51]), "=f"(d[52]), "=f"(d[53]), "=f"(d[54]), "=f"(d[55]), "=f"(d[56]), "=f"(d[57]), "=f"(d[58]), "=f"(d[59]), "=f"(d[60]), "=f"(d[61]), "=f"(d[62]), "=f"(d[63]), "=f"(d[64]), "=f"(d[65]), "=f"(d[66]), "=f"(d[67]), "=f"(d[68]), "=f"(d[69]), "=f"(d[70]), "=f"(d[71]), "=f"(d[72]), "=f"(d[73]), "=f"(d[74]), "=f"(d[75]), "=f"(d[76]), "=f"(d[77]), "=f"(d[78]), "=f"(d[79]), "=f"(d[80]), "=f"(d[81]), "=f"(d[82]), "=f"(d[83]), "=f"(d[84]), "=f"(d[85]), "=f"(d[86]), "=f"(d[87]), "=f"(d[88]), "=f"(d[89]), "=f"(d[90]), "=f"(d[91]), "=f"(d[92]), "=f"(d[93]), "=f"(d[94]), "=f"(d[95]), "=f"(d[96]), "=f"(d[97]), "=f"(d[98]), "=f"(d[99]), "=f"(d[100]), "=f"(d[101]), "=f"(d[102]), "=f"(d[103]), "=f"(d[104]), "=f"(d[105]), "=f"(d[106]), "=f"(d[107]), "=f"(d[108]), "=f"(d[109]), "=f"(d[110]), "=f"(d[111]), "=f"(d[112]), "=f"(d[113]), "=f"(d[114]), "=f"(d[115]), "=f"(d[116]), "=f"(d[117]), "=f"(d[118]), "=f"(d[119]), "=f"(d[120]), "=f"(d[121]), "=f"(d[122]), "=f"(d[123]), "=f"(d[124]), "=f"(d[125]), "=f"(d[126]), "=f"(d[127])
      : "r"(a0), "r"(a1), "r"(a2), "r"(a3), "l"(db));
  }
}
__device__ __forceinline__ void wgmma_n256_ss_ta0_tb1(float* d, uint64_t da, uint64_t db, bool accumulate) {
  if (accumulate) {
    asm volatile("{\n.reg .pred p;\nsetp.ne.b32 p, 1, 0;\n"
      "wgmma.mma_async.sync.aligned.m64n256k16.f32.bf16.bf16 "
      "{%0, %1, %2, %3, %4, %5, %6, %7, %8, %9, %10, %11, %12, %13, %14, %15, %16, %17, %18, %19, %20, %21, %22, %23, %24, %25, %26, %27, %28, %29, %30, %31, %32, %33, %34, %35, %36, %37, %38, %39, %40, %41, %42, %43, %44, %45, %46, %47, %48, %49, %50, %51, %52, %53, %54, %55, %56, %57, %58, %59, %60, %61, %62, %63, %64, %65, %66, %67, %68, %69, %70, %71, %72, %73, %74, %75, %76, %77, %78, %79, %80, %81, %82, %83, %84, %85, %86, %87, %88, %89, %90, %91, %92, %93, %94, %95, %96, %97, %98, %99, %100, %101, %102, %103, %104, %105, %106, %107, %108, %109, %110, %111, %112, %113, %114, %115, %116, %117, %118, %119, %120, %121, %122, %123, %124, %125, %126, %127}, "
      "%128, %129, p, 1, 1, 0, 1;\n}\n"
      : "+f"(d[0]), "+f"(d[1]), "+f"(d[2]), "+f"(d[3]), "+f"(d[4]), "+f"(d[5]), "+f"(d[6]), "+f"(d[7]), "+f"(d[8]), "+f"(d[9]), "+f"(d[10]), "+f"(d[11]), "+f"(d[12]), "+f"(d[13]), "+f"(d[14]), "+f"(d[15]), "+f"(d[16]), "+f"(d[17]), "+f"(d[18]), "+f"(d[19]), "+f"(d[20]), "+f"(d[21]), "+f"(d[22]), "+f"(d[23]), "+f"(d[24]), "+f"(d[25]), "+f"(d[26]), "+f"(d[27]), "+f"(d[28]), "+f"(d[29]), "+f"(d[30]), "+f"(d[31]), "+f"(d[32]), "+f"(d[33]), "+f"(d[34]), "+f"(d[35]), "+f"(d[36]), "+f"(d[37]), "+f"(d[38]), "+f"(d[39]), "+f"(d[40]), "+f"(d[41]), "+f"(d[42]), "+f"(d[43]), "+f"(d[44]), "+f"(d[45]), "+f"(d[46]), "+f"(d[47]), "+f"(d[48]), "+f"(d[49]), "+f"(d[50]), "+f"(d[51]), "+f"(d[52]), "+f"(d[53]), "+f"(d[54]), "+f"(d[55]), "+f"(d[56]), "+f"(d[57]), "+f"(d[58]), "+f"(d[59]), "+f"(d[60]), "+f"(d[61]), "+f"(d[62]), "+f"(d[63]), "+f"(d[64]), "+f"(d[65]), "+f"(d[66]), "+f"(d[67]), "+f"(d[68]), "+f"(d[69]), "+f"(d[70]), "+f"(d[71]), "+f"(d[72]), "+f"(d[73]), "+f"(d[74]), "+f"(d[75]), "+f"(d[76]), "+f"(d[77]), "+f"(d[78]), "+f"(d[79]), "+f"(d[80]), "+f"(d[81]), "+f"(d[82]), "+f"(d[83]), "+f"(d[84]), "+f"(d[85]), "+f"(d[86]), "+f"(d[87]), "+f"(d[88]), "+f"(d[89]), "+f"(d[90]), "+f"(d[91]), "+f"(d[92]), "+f"(d[93]), "+f"(d[94]), "+f"(d[95]), "+f"(d[96]), "+f"(d[97]), "+f"(d[98]), "+f"(d[99]), "+f"(d[100]), "+f"(d[101]), "+f"(d[102]), "+f"(d[103]), "+f"(d[104]), "+f"(d[105]), "+f"(d[106]), "+f"(d[107]), "+f"(d[108]), "+f"(d[109]), "+f"(d[110]), "+f"(d[111]), "+f"(d[112]), "+f"(d[113]), "+f"(d[114]), "+f"(d[115]), "+f"(d[116]), "+f"(d[117]), "+f"(d[118]), "+f"(d[119]), "+f"(d[120]), "+f"(d[121]), "+f"(d[122]), "+f"(d[123]), "+f"(d[124]), "+f"(d[125]), "+f"(d[126]), "+f"(d[127])
      : "l"(da), "l"(db));
  } else {
    asm volatile("{\n.reg .pred p;\nsetp.ne.b32 p, 0, 0;\n"
      "wgmma.mma_async.sync.aligned.m64n256k16.f32.bf16.bf16 "
      "{%0, %1, %2, %3, %4, %5, %6, %7, %8, %9, %10, %11, %12, %13, %14, %15, %16, %17, %18, %19, %20, %21, %22, %23, %24, %25, %26, %27, %28, %29, %30, %31, %32, %33, %34, %35, %36, %37, %38, %39, %40, %41, %42, %43, %44, %45, %46, %47, %48, %49, %50, %51, %52, %53, %54, %55, %56, %57, %58, %59, %60, %61, %62, %63, %64, %65, %66, %67, %68, %69, %70, %71, %72, %73, %74, %75, %76, %77, %78, %79, %80, %81, %82, %83, %84, %85, %86, %87, %88, %89, %90, %91, %92, %93, %94, %95, %96, %97, %98, %99, %100, %101, %102, %103, %104, %105, %106, %107, %108, %109, %110, %111, %112, %113, %114, %115, %116, %117, %118, %119, %120, %121, %122, %123, %124, %125, %126, %127}, "
      "%128, %129, p, 1, 1, 0, 1;\n}\n"
      : "=f"(d[0]), "=f"(d[1]), "=f"(d[2]), "=f"(d[3]), "=f"(d[4]), "=f"(d[5]), "=f"(d[6]), "=f"(d[7]), "=f"(d[8]), "=f"(d[9]), "=f"(d[10]), "=f"(d[11]), "=f"(d[12]), "=f"(d[13]), "=f"(d[14]), "=f"(d[15]), "=f"(d[16]), "=f"(d[17]), "=f"(d[18]), "=f"(d[19]), "=f"(d[20]), "=f"(d[21]), "=f"(d[22]), "=f"(d[23]), "=f"(d[24]), "=f"(d[25]), "=f"(d[26]), "=f"(d[27]), "=f"(d[28]), "=f"(d[29]), "=f"(d[30]), "=f"(d[31]), "=f"(d[32]), "=f"(d[33]), "=f"(d[34]), "=f"(d[35]), "=f"(d[36]), "=f"(d[37]), "=f"(d[38]), "=f"(d[39]), "=f"(d[40]), "=f"(d[41]), "=f"(d[42]), "=f"(d[43]), "=f"(d[44]), "=f"(d[45]), "=f"(d[46]), "=f"(d[47]), "=f"(d[48]), "=f"(d[49]), "=f"(d[50]), "=f"(d[51]), "=f"(d[52]), "=f"(d[53]), "=f"(d[54]), "=f"(d[55]), "=f"(d[56]), "=f"(d[57]), "=f"(d[58]), "=f"(d[59]), "=f"(d[60]), "=f"(d[61]), "=f"(d[62]), "=f"(d[63]), "=f"(d[64]), "=f"(d[65]), "=f"(d[66]), "=f"(d[67]), "=f"(d[68]), "=f"(d[69]), "=f"(d[70]), "=f"(d[71]), "=f"(d[72]), "=f"(d[73]), "=f"(d[74]), "=f"(d[75]), "=f"(d[76]), "=f"(d[77]), "=f"(d[78]), "=f"(d[79]), "=f"(d[80]), "=f"(d[81]), "=f"(d[82]), "=f"(d[83]), "=f"(d[84]), "=f"(d[85]), "=f"(d[86]), "=f"(d[87]), "=f"(d[88]), "=f"(d[89]), "=f"(d[90]), "=f"(d[91]), "=f"(d[92]), "=f"(d[93]), "=f"(d[94]), "=f"(d[95]), "=f"(d[96]), "=f"(d[97]), "=f"(d[98]), "=f"(d[99]), "=f"(d[100]), "=f"(d[101]), "=f"(d[102]), "=f"(d[103]), "=f"(d[104]), "=f"(d[105]), "=f"(d[106]), "=f"(d[107]), "=f"(d[108]), "=f"(d[109]), "=f"(d[110]), "=f"(d[111]), "=f"(d[112]), "=f"(d[113]), "=f"(d[114]), "=f"(d[115]), "=f"(d[116]), "=f"(d[117]), "=f"(d[118]), "=f"(d[119]), "=f"(d[120]), "=f"(d[121]), "=f"(d[122]), "=f"(d[123]), "=f"(d[124]), "=f"(d[125]), "=f"(d[126]), "=f"(d[127])
      : "l"(da), "l"(db));
  }
}
__device__ __forceinline__ void wgmma_n256_ssp_ta0_tb1(float* d, uint64_t da, uint64_t db, int accumulate) {
    asm volatile("{\n.reg .pred p;\nsetp.ne.b32 p, %130, 0;\n"
      "wgmma.mma_async.sync.aligned.m64n256k16.f32.bf16.bf16 "
      "{%0, %1, %2, %3, %4, %5, %6, %7, %8, %9, %10, %11, %12, %13, %14, %15, %16, %17, %18, %19, %20, %21, %22, %23, %24, %25, %26, %27, %28, %29, %30, %31, %32, %33, %34, %35, %36, %37, %38, %39, %40, %41, %42, %43, %44, %45, %46, %47, %48, %49, %50, %51, %52, %53, %54, %55, %56, %57, %58, %59, %60, %61, %62, %63, %64, %65, %66, %67, %68, %69, %70, %71, %72, %73, %74, %75, %76, %77, %78, %79, %80, %81, %82, %83, %84, %85, %86, %87, %88, %89, %90, %91, %92, %93, %94, %95, %96, %97, %98, %99, %100, %101, %102, %103, %104, %105, %106, %107, %108, %109, %110, %111, %112, %113, %114, %115, %116, %117, %118, %119, %120, %121, %122, %123, %124, %125, %126, %127}, "
      "%128, %129, p, 1, 1, 0, 1;\n}\n"
      : "+f"(d[0]), "+f"(d[1]), "+f"(d[2]), "+f"(d[3]), "+f"(d[4]), "+f"(d[5]), "+f"(d[6]), "+f"(d[7]), "+f"(d[8]), "+f"(d[9]), "+f"(d[10]), "+f"(d[11]), "+f"(d[12]), "+f"(d[13]), "+f"(d[14]), "+f"(d[15]), "+f"(d[16]), "+f"(d[17]), "+f"(d[18]), "+f"(d[19]), "+f"(d[20]), "+f"(d[21]), "+f"(d[22]), "+f"(d[23]), "+f"(d[24]), "+f"(d[25]), "+f"(d[26]), "+f"(d[27]), "+f"(d[28]), "+f"(d[29]), "+f"(d[30]), "+f"(d[31]), "+f"(d[32]), "+f"(d[33]), "+f"(d[34]), "+f"(d[35]), "+f"(d[36]), "+f"(d[37]), "+f"(d[38]), "+f"(d[39]), "+f"(d[40]), "+f"(d[41]), "+f"(d[42]), "+f"(d[43]), "+f"(d[44]), "+f"(d[45]), "+f"(d[46]), "+f"(d[47]), "+f"(d[48]), "+f"(d[49]), "+f"(d[50]), "+f"(d[51]), "+f"(d[52]), "+f"(d[53]), "+f"(d[54]), "+f"(d[55]), "+f"(d[56]), "+f"(d[57]), "+f"(d[58]), "+f"(d[59]), "+f"(d[60]), "+f"(d[61]), "+f"(d[62]), "+f"(d[63]), "+f"(d[64]), "+f"(d[65]), "+f"(d[66]), "+f"(d[67]), "+f"(d[68]), "+f"(d[69]), "+f"(d[70]), "+f"(d[71]), "+f"(d[72]), "+f"(d[73]), "+f"(d[74]), "+f"(d[75]), "+f"(d[76]), "+f"(d[77]), "+f"(d[78]), "+f"(d[79]), "+f"(d[80]), "+f"(d[81]), "+f"(d[82]), "+f"(d[83]), "+f"(d[84]), "+f"(d[85]), "+f"(d[86]), "+f"(d[87]), "+f"(d[88]), "+f"(d[89]), "+f"(d[90]), "+f"(d[91]), "+f"(d[92]), "+f"(d[93]), "+f"(d[94]), "+f"(d[95]), "+f"(d[96]), "+f"(d[97]), "+f"(d[98]), "+f"(d[99]), "+f"(d[100]), "+f"(d[101]), "+f"(d[102]), "+f"(d[103]), "+f"(d[104]), "+f"(d[105]), "+f"(d[106]), "+f"(d[107]), "+f"(d[108]), "+f"(d[109]), "+f"(d[110]), "+f"(d[111]), "+f"(d[112]), "+f"(d[113]), "+f"(d[114]), "+f"(d[115]), "+f"(d[116]), "+f"(d[117]), "+f"(d[118]), "+f"(d[119]), "+f"(d[120]), "+f"(d[121]), "+f"(d[122]), "+f"(d[123]), "+f"(d[124]), "+f"(d[125]), "+f"(d[126]), "+f"(d[127])
      : "l"(da), "l"(db), "r"(accumulate));
}

template <int N> __device__ __forceinline__ void quad_sum(float* m) {
#pragma unroll
  for (int o = 1; o <= 2; o <<= 1) {
    float t[N];
#pragma unroll
    for (int i = 0; i < N; i++) t[i] = __shfl_xor_sync(~0u, m[i], o);
#pragma unroll
    for (int i = 0; i < N; i++) m[i] += t[i];
  }
}
__device__ __forceinline__ bool softmax_unsafe(const uint32_t* t, float l0, float l1) {
  const float m0 = fmaxf(bf_lo(t[0]) + bf_hi(t[0]), bf_lo(t[2]) + bf_hi(t[2])), m1 = fmaxf(bf_lo(t[1]) + bf_hi(t[1]), bf_lo(t[3]) + bf_hi(t[3]));
  return __any_sync(~0u, !(m0 * l0 < 2500.f) | !(m1 * l1 < 2500.f));
}
__device__ __forceinline__ void softmax_shift(float* p, float c0, float c1) {
#pragma unroll 1
  for (int it = 0; it < 8; it++) {
    float mx = p[0], mn = p[0];
#pragma unroll
    for (int j = 1; j < 8; j++) { mx = fmaxf(mx, p[(j >> 1) * 4 + (j & 1)]); mn = fminf(mn, p[(j >> 1) * 4 + (j & 1)]); }
#pragma unroll
    for (int o = 1; o <= 2; o <<= 1) { mx = fmaxf(mx, __shfl_xor_sync(~0u, mx, o)); mn = fminf(mn, __shfl_xor_sync(~0u, mn, o)); }
    const float half = fminf(0.5f * (mx - mn), 50.f * rcp(it & 1 ? c1 : c0));
    float r[8];
#pragma unroll
    for (int j = 0; j < 8; j++) {
      const float v = p[(j >> 1) * 4 + (j & 1)];
      r[j] = fmaxf(v - mx + half, 0.f) + fminf(v - mn - half, 0.f) + (v - v);
    }
#pragma unroll
    for (int k = 0; k < 7; k++)
#pragma unroll
      for (int j = 0; j < 8; j++) p[(k >> 1) * 16 + (k & 1) * 2 + (j >> 1) * 4 + (j & 1)] = p[((k + 1) >> 1) * 16 + ((k + 1) & 1) * 2 + (j >> 1) * 4 + (j & 1)];
#pragma unroll
    for (int j = 0; j < 8; j++) p[50 + (j >> 1) * 4 + (j & 1)] = r[j];
  }
}
template <int J0 = 0, int J1 = 8> __device__ __forceinline__ void k_exp(const float* p, float c0, float c1, float* e, float* s) {
#pragma unroll
  for (int j = J0; j < J1; j++) {
    e[2 * j] = ex2(p[2 * j] * (j & 1 ? c1 : c0));
    e[2 * j + 1] = ex2(p[2 * j + 1] * (j & 1 ? c1 : c0));
    e[16 + j] = rcp(e[2 * j] * e[2 * j + 1]);
    const float t = e[2 * j] + e[2 * j + 1];
    s[j & 1] = j < 2 ? t : s[j & 1] + t;
    s[2 + (j & 1)] = j < 2 ? e[16 + j] * t : fmaf(e[16 + j], t, s[2 + (j & 1)]);
  }
}
template <int J0 = 0, int J1 = 8> __device__ __forceinline__ void q_exp(const float* p, float c0, float c1, uint32_t* f) {
#pragma unroll
  for (int j = J0; j < J1; j++) {
    const float e0 = ex2(p[2 * j] * (j & 1 ? c1 : c0)), e1 = ex2(p[2 * j + 1] * (j & 1 ? c1 : c0)), r = rcp(e0 * e1);
    f[j] = pack2(e0, e1);
    f[8 + j] = bmul2(f[j], pack2(r, r));
  }
}

#define FMA8(A, U, X)                                                                                        \
  A[0] = fmaf(bf_lo(U.x), X, A[0]); A[1] = fmaf(bf_hi(U.x), X, A[1]); A[2] = fmaf(bf_lo(U.y), X, A[2]); A[3] = fmaf(bf_hi(U.y), X, A[3]); \
  A[4] = fmaf(bf_lo(U.z), X, A[4]); A[5] = fmaf(bf_hi(U.z), X, A[5]); A[6] = fmaf(bf_lo(U.w), X, A[6]); A[7] = fmaf(bf_hi(U.w), X, A[7])

__device__ __forceinline__ uint32_t routed_row(const __nv_bfloat16* x, uint32_t tag, int lane, uint4* xr) {
  uint32_t best = 0, sv = 0;
#pragma unroll 1
  for (int it = 0; it < SPIN_MAX; it++) {
    const int sel = 2047 - (best & 0x7ff);
#pragma unroll
    for (int i = 0; i < 4; i++) xr[i] = ldg_nc(x + (size_t)sel * DM + i * 256 + lane * 8);
    const unsigned long long st = ld_rlx64(g_stat + sel);
    const uint4 b0 = ld_rlx128(g_best + lane * 2), b1 = ld_rlx128(g_best + 64 + lane * 2);
    const uint32_t m = __reduce_max_sync(~0u, max(max(b0.y == tag ? b0.x : 0u, b0.w == tag ? b0.z : 0u), max(b1.y == tag ? b1.x : 0u, b1.w == tag ? b1.z : 0u)));
    sv = (uint32_t)st;
    if (__all_sync(~0u, b0.y == tag && b0.w == tag && b1.y == tag && b1.w == tag && m == best && (uint32_t)(st >> 32) == tag)) break;
    best = m;
    if (AM_NS) __nanosleep(AM_NS);
  }
  const uint32_t m2 = (sv & 0xffff0000u) | (sv >> 16);
  const float rs = rcp(bf_lo(sv));
#pragma unroll
  for (int i = 0; i < 4; i++) {
    const uint32_t d0 = bsub2(xr[i].x, m2), d1 = bsub2(xr[i].y, m2), d2 = bsub2(xr[i].z, m2), d3 = bsub2(xr[i].w, m2);
    xr[i] = make_uint4(pack2(bf_lo(d0) * rs, bf_hi(d0) * rs), pack2(bf_lo(d1) * rs, bf_hi(d1) * rs), pack2(bf_lo(d2) * rs, bf_hi(d2) * rs),
                       pack2(bf_lo(d3) * rs, bf_hi(d3) * rs));
  }
  return best;
}

struct Params {
  const __nv_bfloat16 *x, *wqkv, *wo, *w_r, *w_down;
};

template <bool BY_SMID> __global__ void __launch_bounds__(384, 1)
fused_kernel(const Params P, const __grid_constant__ CUtensorMap mX, const __grid_constant__ CUtensorMap mWkv, const __grid_constant__ CUtensorMap mWq,
             const __grid_constant__ CUtensorMap mWo, const __grid_constant__ CUtensorMap mPhi, const __grid_constant__ CUtensorMap mWp,
             const __grid_constant__ CUtensorMap mOut, const __grid_constant__ CUtensorMap mWc,
             const __grid_constant__ CUtensorMap mG, const __grid_constant__ CUtensorMap mU, const __grid_constant__ CUtensorMap mD,
             const __grid_constant__ CUtensorMap mXs, const __grid_constant__ CUtensorMap mG2, const __grid_constant__ CUtensorMap mU2) {
  constexpr uint32_t sb = SB, bar = SB + SM_BAR;
  int bid = blockIdx.x;
  if (BY_SMID) {
    uint32_t sm;
    asm volatile("mov.u32 %0, %%smid;" : "=r"(sm));
    const uint32_t tq = (sm - 64) >> 1, q7 = (tq * 37) >> 8;
    const uint32_t gpc = sm < 64 ? (sm >> 1) & 7 : 1 + tq - 7 * q7, idx = (sm < 64 ? sm >> 4 : 4 + q7) * 2 + (sm & 1);
    bid = sm < 120 ? ((PTAB >> (4 * gpc)) & 7) * 16 + idx : sm < 124 ? sm + 8 : sm - 116;
  }
  const int hg = ((bid >> 2) & 3) + 4 * ((bid >> 4) & 1), mb = (bid & 3) + 4 * ((bid >> 5) & 3);
  if (bid < NCTA && threadIdx.x < 256) {
    const uint32_t r0 = threadIdx.x >> 3, c = threadIdx.x & 7, dst = sb + 2 * KV_STAGE + r0 * 128 + ((c ^ (r0 & 7)) << 4);
    const char* xs = (const char*)P.x + (size_t)(mb * 128 + r0) * 2048 + c * 16;
    const char* ws = (const char*)P.wqkv + (size_t)r0 * 6144 + 2048 + hg * 256 + c * 16;
#pragma unroll
    for (int i = 0; i < 4; i++) cp_async16(dst + i * 4096, xs + i * 65536);
#pragma unroll
    for (int i = 0; i < 8; i++) cp_async16(dst + 16384 + i * 4096, ws + (i & 1) * 196608 + (i >> 2) * 2048 + ((i >> 1) & 1) * 128);
  }
  extern __shared__ __align__(1024) uint8_t smem[];
  if (smem_u32(smem) != SB) __trap();
  const int warp = __shfl_sync(~0u, threadIdx.x >> 5, 0);

  if (bid >= NCTA) {
    constexpr uint32_t XV = SM_WPHI, ONES = SM_ZT, BF = bar, BE = bar + 48, BX = bar + 96;
    constexpr int NJ = (DM - GROWS) / 64;
    const int lane = lane_id(), sp = bid - NCTA;
    const uint32_t tag = ld_rlx(g_epoch + bid * 32 + lane) + 1;
    if (warp == 8 && elect_one()) {
#pragma unroll 1
      for (int i = 0; i < 13; i++) mbar_init(bar + 8 * i, i >= 6 && i < 12 ? 8 : 1);
    }
    if (warp == 9) { sts64u(sb + ONES + lane * 8, 0x3f803f80u, 0x3f803f80u); fence_async_smem(); }
    __syncthreads();
    if (warp == 8) {
      if (elect_one()) {
        uint32_t s = 0, ph = 1;
        for (const long long c0 = clock64(); clock64() - c0 < SP_DELAY;) {}
#pragma unroll 1
        for (int job = 0; job < 8; job++) {
          const CUtensorMap* m = job == 0 ? &mWq : sp & 2 ? &mU2 : &mG2;
          const int g0 = job ? (sp & 1) * 28 + job * 4 - 4 : sp * 4;
#pragma unroll 1
          for (int row = job ? GROWS : 0; row < DM; row += 64) {
            mbar_wait(BE + 8 * s, ph);
            mbar_expect_tx(BF + 8 * s, Q_STAGE);
            tma4d(sb + s * Q_STAGE, m, 0, row, g0, 0, BF + 8 * s);
            tma4d(sb + s * Q_STAGE + 16384, m, 0, row, g0 + 2, 0, BF + 8 * s);
            if (++s == 6) { s = 0; ph ^= 1; }
          }
        }
      }
    } else if (warp == 9) {
      uint4 xr[4];
      routed_row(P.x, tag, lane, xr);
#pragma unroll
      for (int i = 0; i < 4; i++) sts128u(sb + XV + i * 512 + lane * 16, xr[i].x, xr[i].y, xr[i].z, xr[i].w);
      fence_async_smem();
      __syncwarp();
      if (lane == 0) mbar_arrive(BX);
    } else if (warp < 8) {
      uint32_t s = 0, ph = 0;
#pragma unroll 1
      for (int job = 0; job < 8; job++) {
        float d[8] = {0.f, 0.f, 0.f, 0.f, 0.f, 0.f, 0.f, 0.f};
        if (job == 1) mbar_wait(BX, 0);
#pragma unroll 1
        for (int i = 0; i < (job ? NJ : 16); i++) {
          mbar_wait(BF + 8 * s, ph);
          wg_fence();
#pragma unroll
          for (int k = 0; k < 8; k++)
            wgmma_n8_ss_ta1_tb0(d + 4 * (k >> 2), mkdesc(sb + k * 2048, 16, 1024, 1, s * (Q_STAGE / 16) + (warp >> 2) * 1024),
                                mkdesc(sb, 16, 128, 0, job ? (XV + GROWS * 2) / 16 + i * 8 + (k & 3) * 2 : ONES / 16), 1);
          wg_commit();
          wg_wait<0>();
          if (lane == 0) mbar_arrive(BE + 8 * s);
          if (++s == 6) { s = 0; ph ^= 1; }
        }
        reg_fence<8>(d);
        float* dst = (job ? g_gp + sp * 1792 + job * 256 - 256 : g_cs + sp * 256) + (warp >> 2) * 128 + (warp & 3) * 16 + (lane >> 2);
        if ((lane & 3) == 0) {
#pragma unroll
          for (int i = 0; i < 4; i++) st_rlx(dst + (i >> 1) * 64 + (i & 1) * 8, mark(__float_as_uint(d[2 * i]), tag & 1));
        }
        __syncwarp();
      }
      if (warp == 0) g_epoch[bid * 32 + lane] = tag;
    }
    return;
  }
#define Q_SLAB(J) ((J) < 8 ? ((J) + 8 - 2 * (hg & 4)) & 15 : 2 * (hg & 4) + 2 * ((J) & 3) + ((J) >> 2 & 1))
#define Q_AOFF(J) ((J) == 8 + (hg & 3) ? SM_X0 : (J) == 12 + (hg & 3) ? SM_X1 : ((J) & 3) * Q_STAGE)
#define Q_LOAD(J)                                                                                            \
  do {                                                                                                       \
    const uint32_t fb_ = bar + B_FULLQ + 8 * ((J) & 3);                                                      \
    const int k_ = Q_SLAB(J) * 64;                                                                           \
    mbar_expect_tx(fb_, Q_STAGE);                                                                            \
    mbar_arrive2(fb_);                                                                                       \
    tma2d(sb + Q_AOFF(J), &mX, k_, mb * 128, fb_);                                                           \
    tma4d(sb + ((J) & 3) * Q_STAGE + 16384, &mWq, 0, k_, hg * 2, 0, fb_);                                    \
  } while (0)
  if (warp >= 8) {
    asm volatile("setmaxnreg.dec.sync.aligned.u32 %0;" ::"n"(REG_H));
    const int lane = lane_id();
    const int f = (warp - 9) & 3;
    if (f == 3) {
      if (elect_one()) {
        PROF(0); PROFT(32);
#pragma unroll
        for (int s = 0; s < 3; s++) mbar_init(bar + B_FULLKV + 8 * s, 1);
      }
      __syncwarp();
      asm volatile("bar.arrive 14, 288;" ::: "memory");
      if (elect_one()) {
#pragma unroll
        for (int s = 0; s < 2; s++) {
          mbar_expect_tx(bar + B_FULLKV + 8 * s, KV_STAGE);
          tma2d(sb + s * KV_STAGE, &mX, (s + 1) * 64, mb * 128, bar + B_FULLKV + 8 * s);
          tma4d(sb + s * KV_STAGE + 16384, &mWkv, 0, (s + 1) * 64, hg * 2, 1, bar + B_FULLKV + 8 * s);
        }
      }
      __syncwarp();
    }
    const uint32_t ep = ld_rlx(g_epoch + bid * 32 + lane);
    if (f < 2) {
#pragma unroll
      for (int i = 0; i < 2; i++) {
        const uint4 u = __ldg((const uint4*)P.w_r + (f * 2 + i) * 32 + lane);
        sts128u(sb + SM_XSEL + (f * 2 + i) * 512 + lane * 16, u.x, u.y, u.z, u.w);
      }
    }
    bar_sync(13, 384);
    const uint32_t tag = ep + 1, par = tag & 1;
    const bool ffn = bid < NFFN;
    const int fb = bid, cu = bid >> 1, ch = bid & 1;
#define CS_STORE(SEC, C)                                                                                     \
  _Pragma("unroll") for (int r = 0; r < 3; r++) {                                                            \
    const uint32_t h0 = pack2(C.x, C.y), h1 = pack2(C.z, C.w);                                               \
    sts64u(sb + SM_CST + (SEC) * 1024 + (lane >> 4) * 512 + (lane & 1) * 8 + r * 128 + ((((lane & 15) >> 1) ^ (r + (lane >> 4) * 4)) << 4), h0, h1); \
    C.x -= bf_lo(h0); C.y -= bf_hi(h0); C.z -= bf_lo(h1); C.w -= bf_hi(h1);                                  \
  }
#define BAD4(U) ((U.x ^ par) | (U.y ^ par) | (U.z ^ par) | (U.w ^ par))
    const int n0 = f < 2 ? 0 : 2 * f - 3, ne = FFN_OFF || !ffn ? 3 : f == 3 ? 3 + G8 : 3 + GN;
    const uint32_t fsb = sb + SM_FST + ((f + 1) & 3) * 8192, fbar = bar + B_FST + f * 16, fst = fsb + (lane >> 4) * 2048 + (lane & 15) * 16;
    const CUtensorMap *ma = &mWc, *mc = &mWc;
    int sx = 1024 + cu * 32, sy = ch * 512 + f * 192, sdy = 32;
#define STAGEG(N)                                                                                            \
  do {                                                                                                       \
    if ((N) == 3) { ma = &mG; mc = &mU; sx = fb * 32; sy = f * (GN * 32);  sdy = 0; }                        \
    if ((N) < ne && elect_one()) {                                                                           \
      const uint32_t dst_ = fsb + ((N) & 1) * 4096, b_ = fbar + ((N) & 1) * 8;                               \
      mbar_expect_tx(b_, 4096);                                                                              \
      tma2d(dst_, ma, sx, sy, b_);                                                                           \
      tma2d(dst_ + 2048, mc, sx, sy + sdy, b_);                                                              \
    }                                                                                                        \
    sy += 32 + sdy;                                                                                          \
  } while (0)
    float a[8], gsum = 0.f, usum = 0.f;
    {
      if (f == 3) {
        if (elect_one()) {
          if (XS_EARLY) { mbar_expect_tx(bar + B_XST, 16384); tma3d(sb + SM_XST, &mXs, 0, bid * 16, 0, bar + B_XST); }
          mbar_expect_tx(bar + B_WPHI, 8192);
          tma2d(sb + SM_WPHI, &mPhi, 0, hg * 128, bar + B_WPHI);
          prefetch_map(&mWq); prefetch_map(&mWo); prefetch_map(&mWp); prefetch_map(&mD);
          PROF(31);
        }
        __syncwarp();
      } else {
        if (lane == 0) prefetch_map(f == 0 ? &mWc : f == 1 ? &mG : &mU);
        if (f == 2) ((float2*)g_y[par])[bid * 32 + lane] = make_float2(0.f, 0.f);
      }
      float st[13];
#pragma unroll
      for (int i = 0; i < 13; i++) st[i] = 0.f;
#pragma unroll 1
      for (int i = 0; i < 4; i++) {
        mbar_wait(bar + B_XST + 8 * (i >> 1), 0);
        if (f == 0 && lane == 0 && i == 0) PROF(1);
        const uint4 wu = lds128u(sb + SM_XSEL + i * 512 + lane * 16);
        const float wf[8] = {bf_lo(wu.x), bf_hi(wu.x), bf_lo(wu.y), bf_hi(wu.y), bf_lo(wu.z), bf_hi(wu.z), bf_lo(wu.w), bf_hi(wu.w)};
        st[12] += ((wf[0] + wf[1]) + (wf[2] + wf[3])) + ((wf[4] + wf[5]) + (wf[6] + wf[7]));
#pragma unroll
        for (int r = 0; r < 4; r++) {
          const uint4 u = lds128u(sb + SM_XST + i * 8192 + (4 * f + r) * 512 + lane * 16);
          const float xf[8] = {bf_lo(u.x), bf_hi(u.x), bf_lo(u.y), bf_hi(u.y), bf_lo(u.z), bf_hi(u.z), bf_lo(u.w), bf_hi(u.w)};
#pragma unroll
          for (int k = 0; k < 8; k++) { st[r] += xf[k]; st[4 + r] = fmaf(xf[k], xf[k], st[4 + r]); st[8 + r] = fmaf(xf[k], wf[k], st[8 + r]); }
        }
        if (i >= 2 && f < 3) STAGEG(n0 + i - 2);
      }
      const bool up = lane & 16, up2 = lane & 8;
#pragma unroll
      for (int q = 0; q < 3; q++) {
        const float k0 = up ? st[4 * q + 2] : st[4 * q], k1 = up ? st[4 * q + 3] : st[4 * q + 1];
        const float o0 = up ? st[4 * q] : st[4 * q + 2], o1 = up ? st[4 * q + 1] : st[4 * q + 3];
        const float m0 = k0 + __shfl_xor_sync(~0u, o0, 16), m1 = k1 + __shfl_xor_sync(~0u, o1, 16);
        a[q] = (up2 ? m1 : m0) + __shfl_xor_sync(~0u, up2 ? m0 : m1, 8);
      }
      a[3] = st[12] + __shfl_xor_sync(~0u, st[12], 16);
      a[3] += __shfl_xor_sync(~0u, a[3], 8);
#pragma unroll
      for (int o = 4; o; o >>= 1)
#pragma unroll
        for (int q = 0; q < 4; q++) a[q] += __shfl_xor_sync(~0u, a[q], o);
      if ((lane & 7) == 0) sts128(sb + SM_ROWS + (4 * f + (lane >> 3)) * 16, a[0], a[1], a[2], a[3]);
      if (f < 3) asm volatile("bar.arrive 7, 128;" ::: "memory");
    }
    if (f == 3) {
      bar_sync(7, 128);
      const int row = bid * 16 + (lane & 15);
      const float4 v = lds128(sb + SM_ROWS + (lane & 15) * 16);
      const float mf = v.x * (1.f / DM), mean = bf_round(mf), var = fmaxf(fmaf(-mf, mf, v.y * (1.f / DM)), 0.f);
      const float sd = bf_round(sqrt_approx(bf_round(bf_round(var) + 1e-5f)));
      const uint32_t rb = pack2(fmaf(-mean, v.w, v.z) * rcp(sd), 0.f) & 0xffffu, ord = (rb & 0x8000u) ? (~rb & 0xffffu) : (rb | 0x8000u);
      uint32_t best = __reduce_max_sync(~0u, (ord << 16) | (uint32_t)(2047 - row));
      if (lane < 16) st_rlx64(g_stat + row, ((unsigned long long)tag << 32) | __float_as_uint(mean) | (__float_as_uint(sd) >> 16));
      if (lane == 0) { asm volatile("red.relaxed.gpu.global.max.u64 [%0], %1;" ::"l"(g_best + bid), "l"(((unsigned long long)tag << 32) | best) : "memory"); PROF(17); }
#pragma unroll 1
      for (int n = 3; n < 5; n++) STAGEG(n);
      {
        uint4 xr[4];
        best = routed_row(P.x, tag, lane, xr);
#pragma unroll
        for (int i = 0; i < (GROWS + 255) / 256; i++) {
          const uint32_t dst = sb + SM_XSEL + i * 1024 + (lane >> 2) * 128 + (lane & 3) * 8;
          sts64(dst, bf_lo(xr[i].x), bf_lo(xr[i].z)); sts64(dst + 32, bf_hi(xr[i].x), bf_hi(xr[i].z));
          sts64(dst + 64, bf_lo(xr[i].y), bf_lo(xr[i].w)); sts64(dst + 96, bf_hi(xr[i].y), bf_hi(xr[i].w));
        }
        sts64u(sb + SM_RED + 16, tag, best);
        __syncwarp();
        if (lane == 0) { mbar_arrive(bar + B_XS); PROF(19); }
      }
      unsigned long long sv4[4];
      uint4 u[4];
#pragma unroll 1
      for (int it = 0; it < SPIN_MAX; it++) {
#pragma unroll
        for (int i = 0; i < 4; i++) { u[i] = ld_rlx128(g_cs + (1 + i) * 1024 + hg * 128 + lane * 4); sv4[i] = ld_rlx64(g_stat + mb * 128 + i * 32 + lane); }
        bool ok = ((BAD4(u[0]) | BAD4(u[1]) | BAD4(u[2]) | BAD4(u[3])) & 1) == 0;
#pragma unroll
        for (int i = 0; i < 4; i++) ok = ok && (uint32_t)(sv4[i] >> 32) == tag;
        if (__all_sync(~0u, ok)) break;
        __nanosleep(200);
      }
#pragma unroll
      for (int i = 0; i < 4; i++) {
        const uint32_t sv = (uint32_t)sv4[i], sd2 = (sv << 16) | (sv & 0xffffu);
        sts64(sb + SM_STAT + (i * 32 + lane) * 8, -bf_hi(sv), rcp(bf_lo(sv)));
        sts128u(sb + SM_SDT + lane * 64 + ((i ^ ((lane >> 1) & 3)) << 4), sd2, sd2, sd2, sd2);
      }
#pragma unroll
      for (int i = 0; i < 2; i++) {
        float4 c = make_float4(unmark(u[i].x) + unmark(u[i + 2].x), unmark(u[i].y) + unmark(u[i + 2].y), unmark(u[i].z) + unmark(u[i + 2].z),
                               unmark(u[i].w) + unmark(u[i + 2].w));
        CS_STORE(i, c);
      }
      fence_async_smem();
      bar_sync(8, 64);
      if (lane == 0) { mbar_arrive(bar + B_CS); PROF(10); }
    }
    {
      uint32_t xa = sb + SM_RED + 32, xstep = 0;
      const uint32_t zero = __float_as_uint(lds32(sb + SM_RED + 12));
#pragma unroll 1
      for (int ph = f == 3; ph < 2; ph++) {
#pragma unroll
        for (int j = 0; j < 8; j++) a[j] = 0.f;
        if (ph && f == 0) {
        {
          mbar_wait(bar + B_WPHI, 0);
          float nq[8] = {0.f, 0.f, 0.f, 0.f, 0.f, 0.f, 0.f, 0.f};
  #pragma unroll 2
          for (int r = 0; r < 16; r++) {
            const uint4 u = lds128u(sb + SM_WPHI + ((lane >> 2) * 16 + r) * 64 + (((lane ^ (r >> 1)) & 3) << 4));
            nq[0] = fmaf(bf_lo(u.x), bf_lo(u.x), nq[0]); nq[1] = fmaf(bf_hi(u.x), bf_hi(u.x), nq[1]); nq[2] = fmaf(bf_lo(u.y), bf_lo(u.y), nq[2]);
            nq[3] = fmaf(bf_hi(u.y), bf_hi(u.y), nq[3]); nq[4] = fmaf(bf_lo(u.z), bf_lo(u.z), nq[4]); nq[5] = fmaf(bf_hi(u.z), bf_hi(u.z), nq[5]);
            nq[6] = fmaf(bf_lo(u.w), bf_lo(u.w), nq[6]); nq[7] = fmaf(bf_hi(u.w), bf_hi(u.w), nq[7]);
          }
          uint32_t m = 0;
  #pragma unroll
          for (int i = 0; i < 8; i++) m = max(m, __float_as_uint(nq[i] + __shfl_xor_sync(~0u, nq[i], 4)) & 0x7fffffffu);
          sts32(sb + SM_RED + 24, 4.2f * __uint_as_float(__reduce_max_sync(~0u, m)));
        }
          asm volatile("bar.arrive 8, 64;" ::: "memory");
        }
        if (ph) { mbar_wait(bar + B_XS, 0); xa = sb + SM_XSEL + f * (GN * 128) + ((lane >> 2) & 3) * 32; xstep = 128; }
#pragma unroll 1
        for (int n = ph ? 3 : n0; n < (ph ? ne : 3); n++) {
          const float4 x0 = lds128(xa), x1 = lds128(xa + 16);
          xa += xstep;
          mbar_wait(fbar + (n & 1) * 8, ((n - n0) >> 1) & 1);
          uint4 u[8];
#pragma unroll
          for (int j = 0; j < 8; j++) u[j] = lds128u(fst + (n & 1) * 4096 + j * 256);
          FMA8(a, u[0], x0.x); FMA8(a, u[1], x0.y); FMA8(a, u[2], x0.z); FMA8(a, u[3], x0.w);
          if (__any_sync(~0u, ((u[4].x | u[5].x | u[6].x | u[7].x | __float_as_uint(a[0]) | __float_as_uint(a[7])) & zero) == 0)) STAGEG(n + 2);
          FMA8(a, u[4], x1.x); FMA8(a, u[5], x1.y); FMA8(a, u[6], x1.z); FMA8(a, u[7], x1.w);
        }
#pragma unroll
        for (int o = 4; o <= 8; o <<= 1)
#pragma unroll
          for (int j = 0; j < 8; j++) a[j] += __shfl_xor_sync(~0u, a[j], o);
        if (ph && lane == 0) mbar_arrive(bar + B_FFN);
        const uint32_t red = ph ? sb + SM_GRED : sb + SM_RED + 64;
        if ((lane & 12) == 0) {
          const uint32_t d = red + f * 256 + (lane >> 4) * 128 + (lane & 3) * 32;
          sts128(d, a[0], a[1], a[2], a[3]); sts128(d + 16, a[4], a[5], a[6], a[7]);
        }
        if (f != 2) {
          asm volatile("bar.arrive %0, %1;" ::"r"(4 + ph), "r"(96 + 32 * ph) : "memory");
        } else {
          bar_sync(4 + ph, 96 + 32 * ph);
          const uint32_t ra = red + lane * 4;
          gsum = lds32(ra) + lds32(ra + 256) + lds32(ra + 512);
          usum = lds32(ra + 128) + lds32(ra + 384) + lds32(ra + 640);
          if (!ph) st_rlx(g_cs + 1024 + ch * 2048 + cu * 32 + lane, mark(__float_as_uint(gsum + usum), par));
          else { gsum += lds32(ra + 768); usum += lds32(ra + 896); }
          if (lane == 0) PROF(ph ? 34 : 18);
        }
      }
    }
    if (f == 3) {
      if (elect_one()) {
        PROF(7);
        mbar_wait(bar + B_FULLQ, 0);
#pragma unroll 1
        for (int j = 3; j < 16; j++) {
          mbar_wait(bar + (j < 4 ? B_EMPTYKV + 16 : B_EMPTYQ + 8 * (j & 3)), ((j >> 2) & 1) ^ 1);
          if (j == 12 + (hg & 3)) mbar_wait(bar + B_KVST + 8, 0);
          Q_LOAD(j);
        }
        PROF(47);
        mbar_expect_tx(bar + B_DN, 65536);
#pragma unroll 1
        for (int i = 0; i < 4; i++) {
          mbar_wait(bar + B_EMPTYQ + 8 * i, 1);
          tma3d(sb + i * Q_STAGE, &mD, 0, fb * 32, i * 4, bar + B_DN);
        }
        PROF(48);
#pragma unroll 1
        for (int i = 0; i < 16; i++) {
          const int s = i & 3, n = i < 9 ? i - 2 : i - 9, kb = i < 2 ? 2 * hg + i : 2 * (n + (n >= hg)) + (i >= 9);
          if (i >= 4) mbar_wait(bar + B_EMPTYQ + 8 * s, ((i >> 2) & 1) ^ 1);
          mbar_expect_tx(bar + B_FULLQ + 8 * s, 16384);
          if (i < 2) {
            mbar_arrive2(bar + B_FULLQ + 8 * s);
            tma3d(sb + s * Q_STAGE + 16384, &mWo, 0, kb * 64, hg * 2, bar + B_FULLQ + 8 * s);
          } else {
            tma5d(sb + s * Q_STAGE + 16384, &mWp, hg * 128, kb * 2, bar + B_FULLQ + 8 * s);
            tma5d(sb + s * Q_STAGE + 24576, &mWp, hg * 128 + 64, kb * 2, bar + B_FULLQ + 8 * s);
            if (i >= 3) {
              if (i == 3) { mbar_wait(bar + B_DND, 0); PROF(14); }
#pragma unroll 1
              for (int a = i == 3 ? 2 : i; a <= i; a++) {
                const uint4* src = g_ofr + (mb * 16 + (a == 2 ? (hg == 0 ? 2 : 0) : kb)) * 1024;
#pragma unroll
                for (int h = 0; h < 2; h++) {
                  mbar_expect_tx(bar + B_AIN + (a & 3) * 16 + h * 8, 8192);
                  bulk_load(sb + (a & 3) * Q_STAGE + h * 8192, src + h * 512, 8192, bar + B_AIN + (a & 3) * 16 + h * 8);
                }
              }
            }
          }
        }
      }
    } else {
      if (f == 2) {
        if (PFD && ffn) {
#pragma unroll 1
          for (int i = 0; i < 16; i++) { touch_l2((const char*)P.w_down + fb * 65536 + i * 4096 + lane * 128, lane); __nanosleep(PFD); }
        }
        {
#pragma unroll 1
          for (int i = 0; i < 8; i++) { touch_l2((const char*)P.wo + ((mb & 7) * 128 + i * 16 + (lane >> 1)) * 2048 + hg * 256 + (lane & 1) * 128, lane); __nanosleep(PFD); }
        }
        asm volatile("cp.async.wait_all;" ::: "memory");
        uint4 u;
#pragma unroll 1
        for (int it = 0; it < SPIN_MAX; it++) {
          u = ld_rlx128(g_cs + hg * 128 + lane * 4);
          if (__all_sync(~0u, !(BAD4(u) & 1))) break;
          __nanosleep(200);
        }
        mbar_wait(bar + B_PHI, 0);
        float4 c = make_float4(unmark(u.x), unmark(u.y), unmark(u.z), unmark(u.w));
        CS_STORE(2, c);
        fence_async_smem();
        __syncwarp();
        if (lane == 0) mbar_arrive(bar + B_CSQ);
      }
      const uint32_t target = __shfl_sync(~0u, tag, 0) * 16;
#pragma unroll 1
      for (int R = 0; R < 2; R++) {
        const uint32_t own = (hg * 2 + R) * 16 + mb, pst = sb + (R ? SM_PST1 : SM_PST0);
        if (f == R) {
          mbar_wait(bar + B_KVST + 8 * R, 0);
          if (f == 1 && lane == 0) PROF(11);
          wait_hint(XC1(hg, R) + mb, target);
          if (elect_one()) {
            PROF(35 + R);
            fence_async_global();
            mbar_expect_tx(bar + B_PART + 8 * R, 8192);
            bulk_load(pst, g_part + own * 512, 8192, bar + B_PART + 8 * R);
          }
          __syncwarp();
          uint4 uz;
#pragma unroll 1
          for (int it = 0; it < SPIN_MAX; it++) {
            uz = ld_rlx128(g_zpart + own * 128 + lane * 4);
            if (__all_sync(~0u, !(BAD4(uz) & 1))) break;
          }
          const bool b1 = lane & 2, b2 = lane & 4;
          const float z0 = unmark(b1 ? uz.z : uz.x) + __shfl_xor_sync(~0u, unmark(b1 ? uz.x : uz.z), 2);
          const float z1 = unmark(b1 ? uz.w : uz.y) + __shfl_xor_sync(~0u, unmark(b1 ? uz.y : uz.w), 2);
          float z = (b2 ? z1 : z0) + __shfl_xor_sync(~0u, b2 ? z0 : z1, 4);
          z += __shfl_xor_sync(~0u, z, 8);
          z += __shfl_xor_sync(~0u, z, 16);
          if (lane < 8) st_rlx(g_zres + own * 8 + (lane & 1) * 4 + (lane & 2) + (lane >> 2), mark(__float_as_uint(z), par));
          if (lane == 0) red_inc(XC2(hg, R));
          __syncwarp();
        }
        if (f == R || f == R + 1) {
          const uint32_t hf = f - R, m1 = ~lane & 1, gq = hf * 4 + (lane >> 3), ts = (lane >> 1) & 3;
          float a0 = 0.f, a1 = 0.f, a2 = 0.f, a3 = 0.f;
          mbar_wait(bar + B_PART + 8 * R, 0);
#pragma unroll 1
          for (int it = 0; it < SPIN_MAX; it++) {
            uint32_t bad = 0;
            a0 = a1 = a2 = a3 = 0.f;
#pragma unroll 1
            for (int b = 0; b < 16; b += 8) {
              uint2 u[8];
              if (it == 0) {
#pragma unroll
                for (int i = 0; i < 8; i++) { const float2 v = lds64(pst + (b + i) * 512 + hf * 256 + lane * 8); u[i] = make_uint2(__float_as_uint(v.x), __float_as_uint(v.y)); }
              } else {
#pragma unroll
                for (int i = 0; i < 8; i++) {
                  const unsigned long long v = ld_rlx64((const unsigned long long*)g_part + own * 1024 + (b + i) * 64 + hf * 32 + lane);
                  u[i] = make_uint2((uint32_t)v, (uint32_t)(v >> 32));
                }
              }
#pragma unroll
              for (int i = 0; i < 8; i++) {
                bad |= u[i].x ^ par;
                a0 += bf_lo(i & 1 ? u[i].x & ~m1 : u[i].x | m1); a1 += bf_hi(u[i].x); a2 += bf_lo(u[i].y); a3 += bf_hi(u[i].y);
              }
            }
            if (__all_sync(~0u, !(bad & m1))) break;
          }
          uint32_t* dst = (uint32_t*)g_res[par] + own * 128 + gq * 16 + ts;
          const uint32_t j0 = (lane & 1) * 2, vb = ts == (gq >> 1);
          st_rlx(dst + ((j0 ^ (gq >> 1)) & 3) * 4, pack2(a0, a1) | vb);
          st_rlx(dst + (((j0 + 1) ^ (gq >> 1)) & 3) * 4, pack2(a2, a3) | vb);
          ((uint2*)g_res[par ^ 1])[own * 64 + hf * 32 + lane] = make_uint2(0u, 0u);
          __syncwarp();
          if (lane == 0) { red_inc(XC2(hg, R)); if (!hf) PROF(R ? 12 : 30); }
        }
      }
      if (f == 2) {
        if (ffn && !FFN_OFF) {
#pragma unroll 1
          for (int it = 0; it < SPIN_MAX; it++) {
            const uint32_t pg = ld_rlx((const uint32_t*)g_gp + fb * 32 + lane), pu = ld_rlx((const uint32_t*)g_gp + FF + fb * 32 + lane);
            if (__all_sync(~0u, !(((pg ^ par) | (pu ^ par)) & 1))) { gsum += unmark(pg); usum += unmark(pu); break; }
            __nanosleep(200);
          }
        }
        const float h = bf_round(silu_f(bf_round(gsum))) * bf_round(usum);
        const uint32_t h2 = pack2(h, h);
        sts128u(sb + SM_HT + lane * 16, h2, h2, h2, h2);
        fence_async_smem();
        __syncwarp();
        if (lane == 0) { mbar_arrive(bar + B_H); PROF(20); }
      }
      if (f < 2) {
        wait_hint(XC2(hg, f), 3 * target);
        mbar_wait(bar + B_KVST + 8, 0);
        if (lane == 0) PROF(40 + f);
#pragma unroll 1
        for (int it = 0; it < SPIN_MAX; it++) {
          if (elect_one()) {
            fence_async_global();
            mbar_expect_tx(bar + B_RES + 8 * f, 8192);
            bulk_load(sb + SM_V + f * 8192, g_res[par] + (hg * 4 + f * 2) * 256, 8192, bar + B_RES + 8 * f);
          }
          __syncwarp();
          const uint4 uz = ld_rlx128(g_zres + (hg * 4 + f * 2) * 64 + lane * 4);
          const uint32_t zw[4] = {uz.x, uz.y, uz.z, uz.w};
#pragma unroll
          for (int j = 0; j < 4; j++) {
            const uint32_t zz = pack2(unmark(zw[j]), 1.f), row = (lane & 3) * 4 + j;
            sts128u(sb + SM_ZT + (2 * f + (lane >> 4)) * 1024 + row * 64 + ((((lane >> 2) ^ (row >> 1)) & 3) << 4), zz, zz, zz, zz);
          }
          uint32_t bad = BAD4(uz);
          mbar_wait(bar + B_RES + 8 * f, it & 1);
#pragma unroll
          for (int i = 0; i < 16; i++) bad |= ~__float_as_uint(lds32(sb + SM_V + f * 8192 + i * 512 + lane * 16 + (lane >> 3) * 4));
          if (__all_sync(~0u, !(bad & 1))) break;
        }
        fence_async_smem();
        __syncwarp();
        if (lane == 0) { mbar_arrive(bar + B_TILE + 8 * f); PROF(f ? 13 : 27); }
      }
      if (f < 2) {
        uint32_t phases = 0;
#pragma unroll 1
        for (int i = 2; i < 16; i++) {
          const int s = i & 3;
          const uint32_t ab = bar + B_AIN + s * 16 + f * 8, slot = sb + s * Q_STAGE + f * 8192;
#pragma unroll 1
          for (int it = 0; it < SPIN_MAX; it++) {
            mbar_wait(ab, (phases >> s) & 1);
            phases ^= 1u << s;
            uint32_t bad = 0;
#pragma unroll
            for (int n = 0; n < 8; n++) bad |= __float_as_uint(lds32(slot + n * 1024 + lane * 32 + (lane >> 2) * 4)) ^ par;
            if (__all_sync(~0u, !(bad & 1))) break;
            if (elect_one()) {
              const int n = i < 9 ? i - 2 : i - 9, kb = 2 * (n + (n >= hg)) + (i >= 9);
              PROF(49);
              mbar_expect_tx(ab, 8192);
              bulk_load(slot, g_ofr + (mb * 16 + kb) * 1024 + f * 512, 8192, ab);
            }
            __syncwarp();
          }
          if (lane == 0) { mbar_arrive(bar + B_FULLQ + 8 * s); if (i == 2 && f == 0) PROF(15); }
        }
        if (f == 0) g_epoch[bid * 32 + lane] = tag;
      } else {
        if (elect_one()) {
          prefetch_map(&mOut);
          if (ffn) { mbar_wait(bar + B_YD, 0); red_rel(g_ycnt); PROF(21); }
        }
        __syncwarp();
        if (f == 2) {
          const uint32_t best = __float_as_uint(lds32(sb + SM_RED + 20));
          const int sel = 2047 - (best & 0x7ff) - mb * 128;
          if (sel >= 0 && sel < 128) {
            const uint2 xr = __ldg((const uint2*)(P.x + (size_t)(mb * 128 + sel) * DM + hg * 128 + lane * 4));
            const float2 st = lds64(sb + SM_STAT + sel * 8);
            const uint32_t ord = best >> 16, rb = (ord & 0x8000u) ? (ord & 0x7fffu) : (~ord & 0xffffu);
            const float sg = rcp(1.f + ex2(-1.4426950408889634f * bf_lo(rb)));
            const uint32_t sg2 = pack2(sg, sg), nm2 = pack2(st.x, st.x);
            wait_cnt<0>(g_ycnt, tag * NFFN);
            float4 y = make_float4(0.f, 0.f, 0.f, 0.f);
#pragma unroll
            for (int i = 0; i < 8; i++) {
              const float4 c = ldg_cg4(g_y[par ^ 1][i] + hg * 128 + lane * 4);
              y.x += c.x; y.y += c.y; y.z += c.z; y.w += c.w;
            }
            uint32_t o[2];
#pragma unroll
            for (int i = 0; i < 2; i++) {
              const uint32_t d = badd2(i ? xr.y : xr.x, nm2);
              const uint32_t tt = badd2(pack2(bf_lo(d) * st.y, bf_hi(d) * st.y), bmul2(i ? pack2(y.z, y.w) : pack2(y.x, y.y), sg2));
              o[i] = pack2(silu_f(bf_lo(tt)), silu_f(bf_hi(tt)));
            }
            sts64u(sb + SM_UPD + lane * 8, o[0], o[1]);
          }
          if (lane == 0) sts32(sb + SM_UPD + 256, __int_as_float(sel));
          __syncwarp();
          if (lane == 0) { mbar_arrive(bar + B_UPD); PROF(22); }
        }
      }
    }
  } else {
    const int t7 = threadIdx.x & 127;
    const char* pfa = warp < 4 ? (const char*)P.x + bid * 32768 + (t7 & 15) * 2048 + (t7 >> 4) * 128
                               : (const char*)P.wqkv + (size_t)((t7 >> 4) * 64 + (bid >> 1)) * 6144 + 2048 + (bid & 1) * 2048 + (t7 & 15) * 128;
    if (t7 >= 16 && t7 < 16 * PF_FIRST) prefetch_l2(pfa);
    if (warp < 7) sts128(sb + SM_CST + threadIdx.x * 16, 0.f, 0.f, 0.f, 0.f);
    else sts32(sb + SM_RED + (threadIdx.x & 15) * 4, threadIdx.x & 8 ? 1.f : 0.f);
    if (elect_one()) {
#pragma unroll 1
      for (uint32_t b = B_FST + warp * 8; b < B_END; b += 64)
        mbar_init(bar + b, b < B_FULLQ ? 1 : b < B_FFN ? 3 : b < B_EMPTYKV ? 4 : 8);
    }
    __syncwarp();
    asm volatile("bar.arrive 13, 384;" ::: "memory");
    asm volatile("setmaxnreg.inc.sync.aligned.u32 %0;" ::"n"(REG_C));
    if (t7 >= 16 * PF_FIRST && threadIdx.x < 128 + 16 * PF_W) prefetch_l2(pfa);
    asm volatile("cp.async.wait_all;" ::: "memory");
    fence_async_smem();
    bar_sync(14, 288);
    if (threadIdx.x == 0) mbar_arrive(bar + B_FULLKV + 16);
    const int lane = lane_id();
    const int wg = warp >> 2, w = warp & 3, g = lane >> 2, t = lane & 3;
    float kv[128];
    {
      uint32_t s = 2, ph = 0, sp = 0, php = 0;
#pragma unroll 1
      for (int j = 0; j < 15; j++) {
        PW0(32 + j); mbar_wait(bar + B_FULLKV + 8 * s, ph); PW1(32 + j);
        if (wg == 1) bar_sync(10 + s, 256);
        wg_fence();
        wgmma_n256_ssp_ta0_tb1(kv, mkdesc(sb, 16, 1024, 1, wg * 512 + s * (KV_STAGE / 16)), mkdesc(sb + 16384, 8192, 1024, 1, s * (KV_STAGE / 16)), j);
#pragma unroll
        for (int k = 1; k < 4; k++)
          wgmma_n256_ss_ta0_tb1(kv, mkdesc(sb + k * 32, 16, 1024, 1, wg * 512 + s * (KV_STAGE / 16)),
                                mkdesc(sb + 16384 + k * 2048, 8192, 1024, 1, s * (KV_STAGE / 16)), 1);
        wg_commit();
        if (wg == 0) asm volatile("bar.arrive %0, 256;" ::"r"(10 + s) : "memory");
        if (warp == 0 && j) {
          mbar_wait(bar + B_EMPTYKV + 8 * sp, php);
          if (elect_one()) {
            if (j < 14) {
              mbar_expect_tx(bar + B_FULLKV + 8 * sp, KV_STAGE);
              tma2d(sb + sp * KV_STAGE, &mX, (j + 2) * 64, mb * 128, bar + B_FULLKV + 8 * sp);
              tma4d(sb + sp * KV_STAGE + 16384, &mWkv, 0, (j + 2) * 64, hg * 2, 1, bar + B_FULLKV + 8 * sp);
            } else {
              Q_LOAD(0);
            }
            if (j < 3 - XS_EARLY) {
              const int xh = j - 1 + XS_EARLY;
              mbar_expect_tx(bar + B_XST + 8 * xh, 16384);
              tma3d(sb + SM_XST + xh * 16384, &mXs, 0, bid * 16, 2 * xh, bar + B_XST + 8 * xh);
            }
          }
          __syncwarp();
        }
        if (j == 0) {
          if (wg == 0) prefetch_l2(pfa + 1024);
        } else if (wg == 1) {
          if (j < 3) {
            if (j == 2 || t7 >= 16 * PF_W) prefetch_l2(pfa + (j - 1) * (8 * 393216));
          } else if (j == 13) {
            prefetch_l2((const char*)P.wo + bid * 16384 + t7 * 128);
          }
        }
        wg_wait<0>();
        if (lane == 0) mbar_arrive(bar + B_EMPTYKV + 8 * s);
        sp = s; php = ph;
        ph ^= s == 1;
        s = s == 2 ? 0 : s + 1;
      }
    }
    const int lrow = wg * 64 + w * 16 + (lane & 15);
    const uint32_t sw128 = lrow * 128, x128 = (lrow & 7), hi16 = lane >> 4;
    mbar_wait(bar + B_CS, 0);
    const uint32_t tag = __float_as_uint(lds32(sb + SM_RED + 16));
    const int zero = __float_as_int(lds32(sb + SM_RED + 12));
    const float wn = lds32(sb + SM_RED + 24);
    const float2 st0 = lds64(sb + SM_STAT + (wg * 64 + w * 16 + g) * 8), st1 = lds64(sb + SM_STAT + (wg * 64 + w * 16 + g + 8) * 8);
    const float c0 = st0.y * 1.4426950408889634f, c1 = st1.y * 1.4426950408889634f;
    const uint32_t nm20 = pack2(st0.x, st0.x), nm21 = pack2(st1.x, st1.x), fmask = t == 0 ? ~0u : t == 1 ? 0xffffu : 0u;
    const uint32_t fa0 = nm20 & fmask, fa1 = nm21 & fmask;
    asm volatile("cp.async.wait_all;" ::: "memory");
    PW0(47); mbar_wait(bar + B_FULLKV + 16, 1); PW1(47);
    wg_fence();
    wgmma_n256_rs_ta0_tb1(kv, fa0, fa1, 0u, 0u, mkdesc(sb + SM_CST, 512, 0, 1), 1);
#pragma unroll
    for (int k = 0; k < 4; k++)
      wgmma_n256_ss_ta0_tb1(kv, mkdesc(sb + 2 * KV_STAGE + k * 32, 16, 1024, 1, wg * 512), mkdesc(sb + 2 * KV_STAGE + 16384 + k * 2048, 8192, 1024, 1), 1);
    wg_commit();
    if (warp == 0) {
      mbar_wait(bar + B_EMPTYKV + 8, 0);
      if (elect_one()) {
#pragma unroll 1
        for (int j = 1; j < 3; j++) Q_LOAD(j);
      }
      __syncwarp();
    }
    wg_wait<0>();
    reg_fence<128>(kv);
    if (lane == 0) mbar_arrive(bar + B_EMPTYKV + 16);
    PROFC(2);
    float q[64];
#define QMMA(J, AOFF16, ACCUM)                                                                                     \
  _Pragma("unroll") for (int k = 0; k < 4; k++)                                                                    \
      wgmma_n128_ss_ta0_tb1(q, mkdesc(sb + k * 32, 16, 1024, 1, wg * 512 + (AOFF16)),                              \
                            mkdesc(sb + 16384 + k * 2048, 8192, 1024, 1, ((J) & 3) * (Q_STAGE / 16)), k ? 1 : (ACCUM))
#define QWAIT(J) do { PW0(J); mbar_wait(bar + B_FULLQ + 8 * ((J) & 3), ((J) >> 2) & 1); PW1(J); } while (0)
#define QSTEP_A(J, AOFF16, ACCUM) do { QWAIT(J); wg_fence(); QMMA(J, AOFF16, ACCUM); wg_commit(); } while (0)
#define QREL(J) do { if (lane == 0) mbar_arrive(bar + B_EMPTYQ + 8 * ((J) & 3)); } while (0)
#define Q_OFF16(J) ((J) >= 8 && (J) < 16 ? Q_AOFF(J) / 16 : ((J) & 3) * (Q_STAGE / 16))
#define QPLAIN(J) do { QSTEP_A(J, Q_OFF16(J), 1); wg_wait<1>(); QREL((J) - 1); } while (0)
#define QNEXT(J) do { QPLAIN(J); SCHED_FENCE(); } while (0)
#define PHI_PROJ(DST, SRC, H0, H1)                                                                                 \
  do {                                                                                                             \
    uint32_t a_[32];                                                                                               \
    _Pragma("unroll") for (int j = 8 * (H0); j < 8 * (H1); j++) {                                                  \
      a_[j] = pack2(SRC[2 * j], SRC[2 * j + 1]);                                                                   \
      asm volatile("fma.rn.bf16x2 %0, %1, %1, %0;" : "+r"(nq[(j >> 4) * 2 + (j & 1)]) : "r"(a_[j]));               \
    }                                                                                                              \
    wg_fence();                                                                                                    \
    _Pragma("unroll") for (int hk = 2 * (H0); hk < 2 * (H1); hk++)                                                 \
        wgmma_n32_rs_ta0_tb1(DST + 16 * (hk >> 1), a_[4 * hk], a_[4 * hk + 1], a_[4 * hk + 2], a_[4 * hk + 3],     \
                             mkdesc(sb + SM_WPHI + hk * 1024, 16, 512, 2), hk & 1);                                \
    wg_commit();                                                                                                   \
  } while (0)
    {
      float p[64], ea[24], eb[24], sa[4], sc[4], kz[20];
      uint32_t vp[32];
#pragma unroll
      for (int j = 0; j < 32; j++) vp[j] = pack2(kv[64 + 2 * j], kv[65 + 2 * j]);
      const uint32_t vr = w * 16 + (lane & 15), vb = sb + SM_V + wg * 4096 + vr * 64, x64 = (vr >> 1) & 3;
#define V_STORE(R)                                                                                           \
  _Pragma("unroll") for (int j = 0; j < 4; j++)                                                              \
      stsm4(vb + (j >> 1) * 8192 + ((((j & 1) * 2 + hi16) ^ x64) << 4), vp[16 * (R) + 4 * j], vp[16 * (R) + 4 * j + 1], vp[16 * (R) + 4 * j + 2], vp[16 * (R) + 4 * j + 3])
      V_STORE(0);
      mbar_wait(bar + B_WPHI, 0);
      {
        uint32_t nq[4] = {0u, 0u, 0u, 0u};
        PHI_PROJ(p, kv, 0, 4);
        QSTEP_A(0, 0, 0);
        const bool unsafe = softmax_unsafe(nq, c0 * c0 * wn, c1 * c1 * wn);
        wg_wait<1>();
        reg_fence<64>(p);
        if (__builtin_expect(unsafe, 0)) softmax_shift(p, c0, c1);
      }
#define K_NORM(S) do { quad_sum<4>(S); _Pragma("unroll") for (int i = 0; i < 4; i++) S[i] = rcp(S[i]) * ((i & 1) ? st1.y : st0.y); } while (0)
#define K_STORE(SLOT, E, S) K_STORE_(SLOT, E, S, 0, 2)
#define K_STORE_(SLOT, E, S, J0, J1)                                                                         \
  _Pragma("unroll") for (int j = (J0); j < (J1); j++) {                                                      \
    uint32_t fp[4], fm[4];                                                                                   \
    _Pragma("unroll") for (int i = 0; i < 4; i++) {                                                          \
      const float e0 = E[8 * j + 2 * i], e1 = E[8 * j + 2 * i + 1], r = E[16 + 4 * j + i] * S[2 + (i & 1)];  \
      const uint32_t e2 = pack2(e0, e1);                                                                     \
      fp[i] = bmul2(e2, pack2(S[i & 1], S[i & 1]));                                                          \
      fm[i] = bmul2(e2, pack2(r, r));                                                                        \
    }                                                                                                        \
    stsm4(sb + SM_PHI + (SLOT) * 16384 + sw128 + (((2 * j + hi16) ^ x128) << 4), fp[0], fp[1], fp[2], fp[3]); \
    stsm4(sb + SM_PHI + (SLOT) * 16384 + sw128 + (((4 + 2 * j + hi16) ^ x128) << 4), fm[0], fm[1], fm[2], fm[3]); \
  }
#define KV_MMA(R)                                                                                            \
  do {                                                                                                       \
    mbar_wait(bar + B_PHI + 8 * (R), 0);                                                                     \
    wg_fence();                                                                                              \
    _Pragma("unroll") for (int k = 0; k < 8; k++) {                                                          \
      const uint32_t vs = SM_V + (k >> 2) * 4096 + (k & 3) * 1024;                                           \
      wgmma_n40_ss_ta1_tb1(kz, mkdesc(sb + SM_PHI + k * 2048, 16, 1024, 1, wg * 1024),                       \
                           mkdesc(sb + vs, SM_SDT + (k & 1) * 1024 + (k >> 1) * 16 - vs, 512, 2, wg * (512u - (512u << 16))), k); \
    }                                                                                                        \
    wg_commit();                                                                                             \
  } while (0)
#define QKV(J, R) do { KV_MMA(R); QSTEP_A(J, Q_OFF16(J), 1); wg_wait<2>(); QREL((J) - 1); SCHED_FENCE(); } while (0)
#define KV_SEND(R)                                                                                           \
  do {                                                                                                       \
    reg_fence<20>(kz);                                                                                       \
    if (lane == 0) mbar_arrive(bar + B_KVST + 8 * (R));                                                      \
    const uint32_t slot = ((hg * 2 + (R)) * 16 + warp * 2) * 16 + mb;                                        \
    _Pragma("unroll") for (int u = 0; u < 2; u++)                                                            \
      st_rlx128(g_part + (slot + u * 16) * 32 + lane, mark(pack2(kz[2 * u], kz[2 * u + 1]), tag & 1), pack2(kz[2 * u + 4], kz[2 * u + 5]), \
                pack2(kz[2 * u + 8], kz[2 * u + 9]), pack2(kz[2 * u + 12], kz[2 * u + 13]));                 \
    if (t < 2) st_rlx(g_zpart + (slot + t * 16) * 8 + g, mark(__float_as_uint(t ? kz[18] : kz[16]), tag & 1)); \
    if (lane < 2) red_inc(XC1(hg, R) + warp * 2 + lane);                                                          \
  } while (0)
#define K_PUB(R) do { fence_async_smem(); __syncwarp(); if (lane == 0) mbar_arrive(bar + B_PHI + 8 * (R)); } while (0)
#define S_PIN(S) SCHED_PIN(S[0] + S[1] + S[2] + S[3])
      k_exp(p, c0, c1, ea, sa);
      S_PIN(sa);
      QNEXT(1);
      K_NORM(sa);
      k_exp<0, 4>(p + 16, c0, c1, eb, sc);
      mbar_wait(bar + B_FFN, 0);
      K_STORE_(0, ea, sa, 0, 1);
      S_PIN(sc);
      QNEXT(2);
      K_STORE_(0, ea, sa, 1, 2);
      k_exp<4, 8>(p + 16, c0, c1, eb, sc);
      K_NORM(sc);
      S_PIN(sc);
      QNEXT(3);
      K_STORE(1, eb, sc);
      K_PUB(0);
      k_exp<0, 4>(p + 32, c0, c1, ea, sa);
      S_PIN(sa);
      QKV(4, 0);
      k_exp<4, 8>(p + 32, c0, c1, ea, sa);
      K_NORM(sa);
      S_PIN(sa);
      wg_wait<1>();
      KV_SEND(0);
      QNEXT(5);
      k_exp(p + 48, c0, c1, eb, sc);
      S_PIN(sc);
      QNEXT(6);
      K_NORM(sc);
      mbar_wait(bar + B_KVST, 0);
      V_STORE(1);
      K_STORE(0, ea, sa);
      QNEXT(7);
      K_STORE(1, eb, sc);
      K_PUB(1);
      QKV(8, 1);
      QNEXT(9);
      KV_SEND(1);
    }
    PROFC(3);
#pragma unroll 1
    for (int j = 10; j < 15; j++) QPLAIN(j);
    mbar_wait(bar + B_CSQ, 0);
    QWAIT(15);
    if (wg == 1) bar_sync(6, 256);
    wg_fence();
    wgmma_n128_rs_ta0_tb1(q, fa0, fa1, 0u, 0u, mkdesc(sb + SM_CST + 2048, 512, 0, 1), 1);
    QMMA(15, Q_AOFF(15) / 16, 1);
    wg_commit();
    if (wg == 0) asm volatile("bar.arrive 6, 256;" ::: "memory");
    wg_wait<1>();
    QREL(14);
    wg_wait<0>();
    QREL(15);
    reg_fence<64>(q);
    PROFC(5);
    float yp[4];
    const uint32_t par = tag & 1;
    uint4* ofr = g_ofr + (mb * 16 + hg * 2) * 1024 + (warp * 16 + g) * 8;
#define O_MMA(H, F, N)                                                                                       \
  do {                                                                                                       \
    wg_fence();                                                                                              \
    _Pragma("unroll") for (int k = 0; k < 4; k++) {                                                          \
      const uint32_t ks = SM_V + (H) * 4096 + k * 1024;                                                      \
      wgmma_n40_rs_ta0_tb1(N + 20 * (k >> 1), F[4 * k], F[4 * k + 1], F[4 * k + 2], F[4 * k + 3],            \
                           mkdesc(sb + ks, SM_ZT + (H) * 1024 + k * 16 - ks, 512, 2), k & 1);                \
    }                                                                                                        \
    wg_commit();                                                                                             \
  } while (0)
#define O_FIN(H, N, o)                                                                                        \
  do {                                                                                                       \
    reg_fence<40>(N);                                                                                        \
    const float *np = N, *nm = N + 20;                                                                       \
    const float d0 = rcp(fmaf(np[16], nm[17], fmaf(nm[16], np[17], 1e-6f * np[17] * nm[17])));               \
    const float d1 = rcp(fmaf(np[18], nm[19], fmaf(nm[18], np[19], 1e-6f * np[19] * nm[19])));               \
    const float bp0 = nm[17] * d0, bm0 = np[17] * d0, bp1 = nm[19] * d1, bm1 = np[19] * d1;                  \
    _Pragma("unroll") for (int j = 0; j < 4; j++) {                                                          \
      o[2 * j] = pack2(fmaf(np[4 * j], bp0, nm[4 * j] * bm0), fmaf(np[4 * j + 1], bp0, nm[4 * j + 1] * bm0)); \
      o[2 * j + 1] = pack2(fmaf(np[4 * j + 2], bp1, nm[4 * j + 2] * bm1), fmaf(np[4 * j + 3], bp1, nm[4 * j + 3] * bm1)); \
    }                                                                                                        \
  } while (0)
#define O_STG(H, o)                                                                                          \
  _Pragma("unroll") for (int u = 0; u < 2; u++) {                                                            \
    uint32_t v_[4];                                                                                          \
    _Pragma("unroll") for (int j = 0; j < 4; j++) v_[j] = lop_select(o[2 * j + u], parm, vword == j);        \
    st_rlx128(ofr + ((H) >> 1) * 1024 + u * 64 + ((((H) & 1) * 4 + t) ^ g), v_[0], v_[1], v_[2], v_[3]);     \
  }
    uint32_t gf[32], ao[16];
    const uint32_t parm = 0u - par, vword = ((t ^ g) & 1) == (g >> 2) ? g & 3 : 4;
    const float rh0 = 0.5f * st0.y, rh1 = 0.5f * st1.y, mh0 = st0.x * rh0, mh1 = st1.x * rh1;
#define GATE_LD(J) ldsm4(sb + ((J) >> 2 ? SM_X1 : SM_X0) + sw128 + (((((J) & 3) * 2 + hi16) ^ x128) << 4), gf[4 * (J)], gf[4 * (J) + 1], gf[4 * (J) + 2], gf[4 * (J) + 3])
#define GATE(I0, I1)                                                                                         \
  _Pragma("unroll") for (int i = (I0); i < (I1); i++) {                                                      \
    const float rs = (i & 1) ? rh1 : rh0, mh = (i & 1) ? mh1 : mh0;                                          \
    const float h0 = fmaf(bf_lo(gf[i]), rs, mh), h1 = fmaf(bf_hi(gf[i]), rs, mh);                            \
    gf[i] = pack2(fmaf(h0, tanh_approx(h0), h0), fmaf(h1, tanh_approx(h1), h1));                             \
  }
#define GATE_PIN(I0, I1) do { uint32_t o_ = 0; _Pragma("unroll") for (int i = (I0); i < (I1); i++) o_ |= gf[i]; SCHED_PIN(__uint_as_float(o_)); } while (0)
    {
      float p[64], na[40], nb[40];
      uint32_t fa[16], fb[16];
      {
        uint32_t nq[4] = {0u, 0u, 0u, 0u};
        PHI_PROJ(p, q, 0, 2);
        SCHED_FENCE();
        PHI_PROJ(p, q, 2, 4);
        const bool unsafe = softmax_unsafe(nq, c0 * c0 * wn, c1 * c1 * wn);
        wg_wait<0>();
        reg_fence<64>(p);
        PROFC(24);
        if (__builtin_expect(unsafe, 0)) softmax_shift(p, c0, c1);
      }
      float dn[32];
#define DN_PART(A, B)                                                                                        \
  do {                                                                                                       \
    wg_fence();                                                                                              \
    _Pragma("unroll") for (int i = (A); i < (B); i++)                                                        \
      wgmma_n8_ss_ta1_tb1(dn + 4 * (i >> 1), mkdesc(sb + (i >> 3) * Q_STAGE + (i & 7) * 2048, 16, 1024, 1, wg * (2 * Q_STAGE / 16)), \
                          mkdesc(sb + SM_HT + (i & 1) * 256, 128, 128, 0), i & 1);                           \
  } while (0)
#define F_PIN(F, A, B) do { uint32_t o_ = 0; _Pragma("unroll") for (int i = (A); i < (B); i++) o_ |= F[8 + i]; SCHED_PIN(__uint_as_float(o_)); } while (0)
#define RMMA(J, A, ACCUM)                                                                                    \
  do {                                                                                                       \
    wg_fence();                                                                                              \
    _Pragma("unroll") for (int k = 0; k < 4; k++)                                                            \
      wgmma_n128_rs_ta0_tb1(q, (A)[4 * k], (A)[4 * k + 1], (A)[4 * k + 2], (A)[4 * k + 3],                   \
                            mkdesc(sb + 16384 + k * 2048, 8192, 1024, 1, ((J) & 3) * (Q_STAGE / 16)), k ? 1 : (ACCUM)); \
    wg_commit();                                                                                             \
  } while (0)
#define RSTEP(J, A, ACCUM) do { QWAIT(J); RMMA(J, A, ACCUM); } while (0)
      PROFC(4);
      q_exp(p, c0, c1, fa);
      q_exp(p + 16, c0, c1, fb);
      F_PIN(fb, 0, 8);
      mbar_wait(bar + B_TILE, 0);
      O_MMA(0, fa, na);
      O_MMA(1, fb, nb);
      PROFC(25);
      wg_wait<1>();
      O_FIN(0, na, ao);
      O_STG(0, ao);
      wg_wait<0>();
      O_FIN(1, nb, (ao + 8));
      O_STG(1, (ao + 8));
      PROFC(28);
      mbar_wait(bar + B_H, 0);
      mbar_wait(bar + B_DN, 0);
      PROFC(45);
      DN_PART(0, 16);
      wg_commit();
      wg_wait<0>();
      reg_fence<32>(dn);
#pragma unroll
      for (int i = 0; i < 4; i++) yp[i] = t & 2 ? (t & 1 ? dn[24 + 2 * i] : dn[16 + 2 * i]) : (t & 1 ? dn[8 + 2 * i] : dn[2 * i]);
      RSTEP(16, ao, 0);
      SCHED_FENCE();
      q_exp(p + 32, c0, c1, fa);
      F_PIN(fa, 0, 8);
      if (lane == 0) mbar_arrive(bar + B_DND);
      q_exp(p + 48, c0, c1, fb);
      F_PIN(fb, 0, 8);
      wg_wait<0>();
      QREL(16);
      PROFC(29);
      mbar_wait(bar + B_TILE + 8, 0);
      PROFC(23);
      if (bid < NFFN) {
        float* y = g_y[par ^ 1][bid & 7] + wg * 512 + t * 128 + w * 16 + g;
#pragma unroll
        for (int i = 0; i < 4; i++) red1(y + (i >> 1) * 64 + (i & 1) * 8, yp[i]);
      }
      SCHED_FENCE();
      O_MMA(2, fa, na);
      O_MMA(3, fb, nb);
      __syncwarp();
      if (lane == 0) mbar_arrive(bar + B_YD);
      wg_wait<1>();
      O_FIN(2, na, ao);
      O_STG(2, ao);
      wg_wait<0>();
      O_FIN(3, nb, (ao + 8));
      O_STG(3, (ao + 8));
      PROFC(6);
    }
    RSTEP(17, ao, 1);
    SCHED_FENCE();
    GATE_LD(0); GATE_LD(1);
    GATE(0, 4);
    GATE_PIN(0, 4);
#define GSTEP(J, I) do { QNEXT(J); if ((I) < 7) GATE_LD(((I) + 1) & 7); GATE(4 * (I), 4 * (I) + 4); GATE_PIN(4 * (I), 4 * (I) + 4); } while (0)
    GSTEP(18, 1); GSTEP(19, 2); GSTEP(20, 3); GSTEP(21, 4); GSTEP(22, 5); GSTEP(23, 6); GSTEP(24, 7);
#pragma unroll 1
    for (int j = 25; j < 32 - TAILN; j++) QPLAIN(j);
    if (wg == 1) bar_sync(6, 256);
#pragma unroll 1
    for (int j = 32 - TAILN; j < 32; j++) QSTEP_A(j, (j & 3) * (Q_STAGE / 16), 1);
    if (wg == 0) asm volatile("bar.arrive 6, 256;" ::: "memory");
    mbar_wait(bar + B_UPD, 0);
    {
      const int sel = __float_as_int(lds32(sb + SM_UPD + 256)) - (wg * 64 + w * 16 + g);
      if (sel == 0 || sel == 8) {
#pragma unroll
        for (int j = 0; j < 16; j++) {
          const uint32_t u = __float_as_uint(lds32(sb + SM_UPD + j * 16 + t * 4));
          if (sel) gf[2 * j + 1] = u; else gf[2 * j] = u;
        }
      }
      __syncwarp();
      uint32_t xf[32];
#pragma unroll
      for (int j = 0; j < 8; j++)
        ldsm4(sb + (j >> 2 ? SM_X1 : SM_X0) + sw128 + ((((j & 3) * 2 + hi16) ^ x128) << 4), xf[4 * j], xf[4 * j + 1], xf[4 * j + 2], xf[4 * j + 3]);
      wg_wait<0>();
      reg_fence<64>(q);
      PROFC(8);
#pragma unroll
      for (int j = 0; j < 8; j++) {
        uint32_t o[4];
#pragma unroll
        for (int i = 0; i < 4; i++) o[i] = badd2(xf[4 * j + i], bmul2(pack2(q[8 * j + 2 * i], q[8 * j + 2 * i + 1]), gf[4 * j + i]));
        stsm4(sb + (j >> 2 ? SM_X1 : SM_X0) + sw128 + ((((j & 3) * 2 + hi16) ^ x128) << 4), o[0], o[1], o[2], o[3]);
        if ((j & 3) == 3) {
          fence_async_smem();
          __syncwarp();
          if (elect_one()) {
            tma_store2d(&mOut, sb + (j >> 2 ? SM_X1 : SM_X0) + warp * 2048, hg * 128 + (j >> 2) * 64, mb * 128 + warp * 16);
            bulk_commit();
          }
          __syncwarp();
        }
      }
    }
    bulk_wait_read0();
    if (warp == 7 && lane == 0) { PROF(9); PROFT(33); PROF_DUMP; }
  }
}

typedef CUresult (*EncodeFn)(CUtensorMap*, CUtensorMapDataType, cuuint32_t, void*, const cuuint64_t*, const cuuint64_t*, const cuuint32_t*,
                             const cuuint32_t*, CUtensorMapInterleave, CUtensorMapSwizzle, CUtensorMapL2promotion, CUtensorMapFloatOOBfill);

CUtensorMap make_map(EncodeFn enc, const void* ptr, int rank, const cuuint64_t* dims, const cuuint64_t* strides, const cuuint32_t* box, CUtensorMapSwizzle sw) {
  CUtensorMap m;
  const cuuint32_t es[5] = {1, 1, 1, 1, 1};
  enc(&m, CU_TENSOR_MAP_DATA_TYPE_BFLOAT16, rank, (void*)ptr, dims, strides, box, es, CU_TENSOR_MAP_INTERLEAVE_NONE, sw,
      CU_TENSOR_MAP_L2_PROMOTION_L2_128B, CU_TENSOR_MAP_FLOAT_OOB_FILL_NONE);
  return m;
}

}

extern "C" void kernel_launch(void* const* d_in, const int* in_sizes, int n_in, void* d_out, int out_size) {
  static EncodeFn enc = nullptr;
  static int by_sm = 0;
  if (!enc) {
    void* fn = nullptr;
    cudaDriverEntryPointQueryResult qr;
    cudaGetDriverEntryPoint("cuTensorMapEncodeTiled", &fn, cudaEnableDefault, &qr);
    enc = (EncodeFn)fn;
    cudaFuncSetAttribute(fused_kernel<false>, cudaFuncAttributeMaxDynamicSharedMemorySize, SM_TOTAL);
    cudaFuncSetAttribute(fused_kernel<true>, cudaFuncAttributeMaxDynamicSharedMemorySize, SM_TOTAL);
    int dev = 0, sms = 0;
    cudaGetDevice(&dev);
    cudaDeviceGetAttribute(&sms, cudaDevAttrMultiProcessorCount, dev);
    by_sm = BY_SM && sms == NCTA + NSPARE;
  }
  Params P;
  P.x = (const __nv_bfloat16*)d_in[0];
  P.wqkv = (const __nv_bfloat16*)d_in[1];
  const void* wphi = d_in[2];
  P.wo = (const __nv_bfloat16*)d_in[3];
  P.w_r = (const __nv_bfloat16*)d_in[5];
  const void *w_gate = d_in[6], *w_up = d_in[7];
  P.w_down = (const __nv_bfloat16*)d_in[8];

  const cuuint64_t dX[2] = {DM, SEQ}, sX[1] = {DM * 2};
  const cuuint32_t b128[2] = {64, 128};
  const cuuint64_t dW[4] = {64, DM, 16, 3}, sW[3] = {3 * DM * 2, 128, DM * 2};
  const cuuint32_t bKV[4] = {64, 64, 2, 2}, bQ[4] = {64, 64, 2, 1};
  const cuuint64_t dO[3] = {64, DM, 16}, sO[2] = {DM * 2, 128};
  const cuuint32_t bO[3] = {64, 64, 2};
  const cuuint64_t dP[2] = {32, 1024}, sP[1] = {64};
  const cuuint32_t bP[2] = {32, 128};
  CUtensorMap mX = make_map(enc, P.x, 2, dX, sX, b128, CU_TENSOR_MAP_SWIZZLE_128B);
  CUtensorMap mWkv = make_map(enc, P.wqkv, 4, dW, sW, bKV, CU_TENSOR_MAP_SWIZZLE_128B);
  CUtensorMap mWq = make_map(enc, P.wqkv, 4, dW, sW, bQ, CU_TENSOR_MAP_SWIZZLE_128B);
  CUtensorMap mWo = make_map(enc, P.wo, 3, dO, sO, bO, CU_TENSOR_MAP_SWIZZLE_128B);
  CUtensorMap mPhi = make_map(enc, wphi, 2, dP, sP, bP, CU_TENSOR_MAP_SWIZZLE_64B);
  const cuuint64_t dWp[5] = {DM, 2, 4, 4, DM / 32}, sWp[4] = {DM * 2, 8 * DM * 2, 2 * DM * 2, 32 * DM * 2};
  const cuuint32_t bWp[5] = {64, 2, 4, 4, 2};
  CUtensorMap mWp = make_map(enc, P.wo, 5, dWp, sWp, bWp, CU_TENSOR_MAP_SWIZZLE_128B);
  const cuuint32_t b16[2] = {64, 16};
  CUtensorMap mOut = make_map(enc, d_out, 2, dX, sX, b16, CU_TENSOR_MAP_SWIZZLE_128B);
  const cuuint64_t dWc[2] = {3 * DM, DM}, sWc[1] = {3 * DM * 2}, dG[2] = {FF, DM}, sG[1] = {FF * 2}, dD[3] = {64, FF, 16};
  const cuuint32_t b32[2] = {32, 32}, bD[3] = {64, 32, 4};
  CUtensorMap mWc = make_map(enc, P.wqkv, 2, dWc, sWc, b32, CU_TENSOR_MAP_SWIZZLE_NONE);
  CUtensorMap mG = make_map(enc, w_gate, 2, dG, sG, b32, CU_TENSOR_MAP_SWIZZLE_NONE);
  CUtensorMap mU = make_map(enc, w_up, 2, dG, sG, b32, CU_TENSOR_MAP_SWIZZLE_NONE);
  CUtensorMap mD = make_map(enc, P.w_down, 3, dD, sO, bD, CU_TENSOR_MAP_SWIZZLE_128B);
  const cuuint64_t dXs[3] = {256, SEQ, 4}, sXs[2] = {DM * 2, 512};
  const cuuint32_t bXs[3] = {256, 16, 2};
  CUtensorMap mXs = make_map(enc, P.x, 3, dXs, sXs, bXs, CU_TENSOR_MAP_SWIZZLE_NONE);
  const cuuint64_t dG2[4] = {64, DM, FF / 64, 1}, sG2[3] = {FF * 2, 128, (cuuint64_t)FF * DM * 2};
  CUtensorMap mG2 = make_map(enc, w_gate, 4, dG2, sG2, bQ, CU_TENSOR_MAP_SWIZZLE_128B);
  CUtensorMap mU2 = make_map(enc, w_up, 4, dG2, sG2, bQ, CU_TENSOR_MAP_SWIZZLE_128B);
  (by_sm ? fused_kernel<true> : fused_kernel<false>)<<<NCTA + NSPARE, 384, SM_TOTAL, cudaStreamPerThread>>>(P, mX, mWkv, mWq, mWo, mPhi, mWp, mOut, mWc, mG, mU, mD, mXs,
                                                                                                           mG2, mU2);
}
```

```cpp
#include <cuda_runtime.h>
#include <cuda_bf16.h>
#include <cuda.h>
#include <stdint.h>

namespace {

constexpr int SEQ = 2048, DM = 1024, FF = 3584;
constexpr int NCTA = 128;
constexpr int NSPARE = 4;
constexpr int NFFN = FF / 32;
#define GN 6
#define G8 2
constexpr int GROWS = (3 * GN + G8) * 32;
#define TAILN 2
#define XS_EARLY 1
#define PF_FIRST 2
#define PF_W 5
#define PFD 80
#define BY_SM 1
#define PTAB 0x73216540u
#define REG_C 224
#define REG_H 56
#define SP_DELAY 2000
#define XSTR 288
#define AM_NS 100
constexpr bool FFN_OFF = false;

static_assert(2 * REG_C + REG_H <= 3 * 168, "the register pool of the CTA is 384 x 168");

__device__ uint32_t g_epoch[(NCTA + NSPARE) * 32];
__device__ unsigned long long g_stat[SEQ];
__device__ __align__(128) unsigned long long g_best[NCTA];
__device__ __align__(16) float g_y[2][8][DM];
__device__ __align__(128) uint32_t g_ycnt[64];
__device__ __align__(1024) uint32_t g_xcnt[32 * XSTR];
#define XC1(HG, R) (g_xcnt + ((HG) * 2 + (R)) * XSTR)
#define XC2(HG, R) (g_xcnt + (16 + (HG) * 2 + (R)) * XSTR)
__device__ __align__(128) uint4 g_res[2][32 * 256];
__device__ __align__(16) float g_cs[5 * DM];
__device__ __align__(128) float g_gp[2 * FF];
__device__ uint4 g_part[8 * 2 * 16 * 16 * 32];
__device__ __align__(16) float g_zpart[8 * 2 * 16 * 16 * 8];
__device__ __align__(128) float g_zres[32 * 64];
__device__ __align__(1024) uint4 g_ofr[16 * 16 * 1024];
#define PROF(i)
#define PROFT(i)
#define PROFC(i)
#define PROF_DUMP
#define PW0(J)
#define PW1(J)

constexpr uint32_t KV_STAGE = 49152, Q_STAGE = 32768;
constexpr uint32_t SM_V = 147456;
constexpr uint32_t SM_PHI = 163840;
constexpr uint32_t SM_XST = 147456;
constexpr uint32_t SM_FST = 172032;
constexpr uint32_t SM_PST0 = 196608, SM_PST1 = SM_PHI + 8192;
constexpr uint32_t SM_X0 = 131072, SM_X1 = SM_PHI + 16384;
constexpr uint32_t SM_WPHI = 204800;
constexpr uint32_t SM_ZT = 212992;
constexpr uint32_t SM_SDT = 217088;
constexpr uint32_t SM_CST = 219136;
constexpr uint32_t SM_HT = 222720;
constexpr uint32_t SM_STAT = 223232;
constexpr uint32_t SM_XSEL = 224256;
constexpr uint32_t SM_RED = 228352;
constexpr uint32_t SM_ROWS = SM_RED + 832;
constexpr uint32_t SM_GRED = SM_XSEL + 3072;
static_assert(GROWS <= 768, "xsel area");
constexpr uint32_t SM_UPD = 229632;
constexpr uint32_t SM_BAR = 230016;
constexpr uint32_t SM_PROF = 230464;
constexpr uint32_t SM_SINK = 231104;
constexpr uint32_t SM_TOTAL = 231616;
constexpr uint32_t SB = 1024;
constexpr uint32_t B_FULLKV = 0  , B_FST = 24  , B_XST = 104  , B_WPHI = 120, B_CS = 128, B_CSQ = 136, B_UPD = 144,
                   B_H = 152, B_DN = 160, B_XS = 168, B_TILE = 176  , B_RES = 192  , B_PART = 208  , B_AIN = 224  ,
                   B_FULLQ = 288  ,
                   B_FFN = 320,
                   B_EMPTYKV = 328  , B_EMPTYQ = 352  , B_KVST = 384  , B_YD = 400, B_PHI = 408  , B_DND = 424, B_END = 432;

__device__ __forceinline__ uint32_t smem_u32(const void* p) { return (uint32_t)__cvta_generic_to_shared(p); }
__device__ __forceinline__ void mbar_init(uint32_t bar, uint32_t cnt) { asm volatile("mbarrier.init.shared::cta.b64 [%0], %1;" ::"r"(bar), "r"(cnt) : "memory"); }
__device__ __forceinline__ void mbar_expect_tx(uint32_t bar, uint32_t bytes) { asm volatile("mbarrier.arrive.expect_tx.shared::cta.b64 _, [%0], %1;" ::"r"(bar), "r"(bytes) : "memory"); }
__device__ __forceinline__ void mbar_arrive2(uint32_t bar) { asm volatile("mbarrier.arrive.shared::cta.b64 _, [%0], 2;" ::"r"(bar) : "memory"); }
__device__ __forceinline__ void mbar_arrive(uint32_t bar) { asm volatile("mbarrier.arrive.shared::cta.b64 _, [%0];" ::"r"(bar) : "memory"); }
__device__ __forceinline__ void mbar_wait(uint32_t bar, uint32_t parity) {
  asm volatile("{\n.reg .pred p;\nLW:\nmbarrier.try_wait.parity.shared::cta.b64 p, [%0], %1;\n@!p bra LW;\n}" ::"r"(bar), "r"(parity) : "memory");
}
__device__ __forceinline__ bool mbar_test(uint32_t bar, uint32_t parity) {
  uint32_t ok;
  asm volatile("{\n.reg .pred p;\nmbarrier.test_wait.parity.shared::cta.b64 p, [%1], %2;\nselp.u32 %0, 1, 0, p;\n}" : "=r"(ok) : "r"(bar), "r"(parity) : "memory");
  return ok;
}
__device__ __forceinline__ int lane_id() { int l; asm volatile("mov.u32 %0, %%laneid;" : "=r"(l)); return l; }
template <int C> __device__ __forceinline__ void sched_fence_(int zero) {
  asm volatile("{\n.reg .pred p;\nsetp.eq.s32 p, %0, %1;\n@p trap;\n}" ::"r"(zero), "n"(C) : "memory");
}
#define SCHED_FENCE() sched_fence_<1000 + __COUNTER__>(zero)
#define SCHED_PIN(V) sched_fence_<1000 + __COUNTER__>(zero & __float_as_int(V))
__device__ __forceinline__ bool elect_one() {
  uint32_t p; asm volatile("{ .reg .pred P; elect.sync _|P, 0xffffffff; selp.u32 %0, 1, 0, P; }" : "=r"(p)); return p;
}
__device__ __forceinline__ void tma2d(uint32_t dst, const CUtensorMap* m, int x, int y, uint32_t bar) {
  asm volatile("cp.async.bulk.tensor.2d.shared::cluster.global.mbarrier::complete_tx::bytes [%0], [%1, {%3, %4}], [%2];" ::"r"(dst), "l"(m), "r"(bar), "r"(x), "r"(y) : "memory");
}
__device__ __forceinline__ void tma3d(uint32_t dst, const CUtensorMap* m, int x, int y, int z, uint32_t bar) {
  asm volatile("cp.async.bulk.tensor.3d.shared::cluster.global.mbarrier::complete_tx::bytes [%0], [%1, {%3, %4, %5}], [%2];" ::"r"(dst), "l"(m), "r"(bar), "r"(x), "r"(y), "r"(z) : "memory");
}
__device__ __forceinline__ void tma4d(uint32_t dst, const CUtensorMap* m, int x, int y, int z, int w, uint32_t bar) {
  asm volatile("cp.async.bulk.tensor.4d.shared::cluster.global.mbarrier::complete_tx::bytes [%0], [%1, {%3, %4, %5, %6}], [%2];" ::"r"(dst), "l"(m), "r"(bar), "r"(x), "r"(y), "r"(z), "r"(w) : "memory");
}
__device__ __forceinline__ void tma5d(uint32_t dst, const CUtensorMap* m, int x, int v, uint32_t bar) {
  asm volatile("cp.async.bulk.tensor.5d.shared::cluster.global.mbarrier::complete_tx::bytes [%0], [%1, {%3, %5, %5, %5, %4}], [%2];" ::"r"(dst), "l"(m), "r"(bar), "r"(x), "r"(v), "r"(0) : "memory");
}
__device__ __forceinline__ void tma_store2d(const CUtensorMap* m, uint32_t src, int x, int y) {
  asm volatile("cp.async.bulk.tensor.2d.global.shared::cta.bulk_group [%0, {%2, %3}], [%1];" ::"l"(m), "r"(src), "r"(x), "r"(y) : "memory");
}
__device__ __forceinline__ void bulk_load(uint32_t dst, const void* src, uint32_t bytes, uint32_t bar) {
  asm volatile("cp.async.bulk.shared::cluster.global.mbarrier::complete_tx::bytes [%0], [%1], %2, [%3];" ::"r"(dst), "l"(src), "r"(bytes), "r"(bar) : "memory");
}
__device__ __forceinline__ void bulk_commit() { asm volatile("cp.async.bulk.commit_group;" ::: "memory"); }
__device__ __forceinline__ void bulk_wait_read0() { asm volatile("cp.async.bulk.wait_group.read 0;" ::: "memory"); }
__device__ __forceinline__ void prefetch_l2(const void* p) { asm volatile("prefetch.global.L2 [%0];" ::"l"(p) : "memory"); }
__device__ __forceinline__ void touch_l2(const void* p, int lane) { asm volatile("cp.async.cg.shared.global.L2::128B [%0], [%1], 16;" ::"r"(SB + SM_SINK + lane * 16), "l"(p) : "memory"); }
__device__ __forceinline__ void cp_async16(uint32_t dst, const void* src) { asm volatile("cp.async.cg.shared.global [%0], [%1], 16;" ::"r"(dst), "l"(src) : "memory"); }
__device__ __forceinline__ void prefetch_map(const CUtensorMap* m) { asm volatile("prefetch.tensormap [%0];" ::"l"(m) : "memory"); }
__device__ __forceinline__ void fence_async_smem() { asm volatile("fence.proxy.async.shared::cta;" ::: "memory"); }
__device__ __forceinline__ void fence_async_global() { asm volatile("fence.proxy.async.global;" ::: "memory"); }
__device__ __forceinline__ void bar_sync(int id, int n) { asm volatile("bar.sync %0, %1;" ::"r"(id), "r"(n) : "memory"); }
__device__ __forceinline__ void wg_fence() { asm volatile("wgmma.fence.sync.aligned;" ::: "memory"); }
__device__ __forceinline__ void wg_commit() { asm volatile("wgmma.commit_group.sync.aligned;" ::: "memory"); }
template <int N> __device__ __forceinline__ void wg_wait() { asm volatile("wgmma.wait_group.sync.aligned %0;" ::"n"(N) : "memory"); }
template <int N> __device__ __forceinline__ void reg_fence(uint32_t* r) {
#pragma unroll
  for (int i = 0; i < N; i++) asm volatile("" : "+r"(r[i])::"memory");
}
template <int N> __device__ __forceinline__ void reg_fence(float* r) {
#pragma unroll
  for (int i = 0; i < N; i++) asm volatile("" : "+f"(r[i])::"memory");
}
__device__ __forceinline__ uint64_t mkdesc(uint32_t addr, uint32_t lbo, uint32_t sbo, uint32_t swz, uint32_t dyn = 0) {
  const uint32_t lo = ((addr >> 4) | ((lbo >> 4) << 16)) + dyn;
  const uint32_t hi = (sbo >> 4) | (swz << 30);
  uint64_t d;
  asm("mov.b64 %0, {%1, %2};" : "=l"(d) : "r"(lo), "r"(hi));
  return d;
}
template <uint32_t C> __device__ __forceinline__ uint32_t fresh_hi(uint32_t zero) { uint32_t h; asm volatile("or.b32 %0, %1, %2;" : "=r"(h) : "r"(zero), "n"(C)); return h; }
constexpr uint32_t H128 = (1024u >> 4) | (1u << 30), H64 = (512u >> 4) | (2u << 30), HNS = 128u >> 4;
__device__ __forceinline__ uint64_t mkdesch(uint32_t addr, uint32_t lbo, uint32_t hi, uint32_t dyn = 0) {
  const uint32_t lo = ((addr >> 4) | ((lbo >> 4) << 16)) + dyn;
  uint64_t d;
  asm("mov.b64 %0, {%1, %2};" : "=l"(d) : "r"(lo), "r"(hi));
  return d;
}
__device__ __forceinline__ void stsm4(uint32_t addr, uint32_t a, uint32_t b, uint32_t c, uint32_t d) {
  asm volatile("stmatrix.sync.aligned.m8n8.x4.shared.b16 [%0], {%1, %2, %3, %4};" ::"r"(addr), "r"(a), "r"(b), "r"(c), "r"(d) : "memory");
}
__device__ __forceinline__ void ldsm4(uint32_t addr, uint32_t& a, uint32_t& b, uint32_t& c, uint32_t& d) {
  asm volatile("ldmatrix.sync.aligned.m8n8.x4.shared.b16 {%0, %1, %2, %3}, [%4];" : "=r"(a), "=r"(b), "=r"(c), "=r"(d) : "r"(addr) : "memory");
}
__device__ __forceinline__ uint32_t pack2(float lo, float hi) { uint32_t r; asm("cvt.rn.bf16x2.f32 %0, %1, %2;" : "=r"(r) : "f"(hi), "f"(lo)); return r; }
__device__ __forceinline__ uint32_t bsub2(uint32_t a, uint32_t b) { uint32_t r; asm("sub.rn.bf16x2 %0, %1, %2;" : "=r"(r) : "r"(a), "r"(b)); return r; }
__device__ __forceinline__ uint32_t badd2(uint32_t a, uint32_t b) { uint32_t r; asm("add.rn.bf16x2 %0, %1, %2;" : "=r"(r) : "r"(a), "r"(b)); return r; }
__device__ __forceinline__ uint32_t bmul2(uint32_t a, uint32_t b) { uint32_t r; asm("mul.rn.bf16x2 %0, %1, %2;" : "=r"(r) : "r"(a), "r"(b)); return r; }
__device__ __forceinline__ float bf_lo(uint32_t v) { return __uint_as_float(v << 16); }
__device__ __forceinline__ float bf_hi(uint32_t v) { return __uint_as_float(v & 0xffff0000u); }
__device__ __forceinline__ float bf_round(float v) { return bf_lo(pack2(v, 0.f)); }
__device__ __forceinline__ float ex2(float v) { float r; asm("ex2.approx.ftz.f32 %0, %1;" : "=f"(r) : "f"(v)); return r; }
__device__ __forceinline__ float rcp(float v) { float r; asm("rcp.approx.ftz.f32 %0, %1;" : "=f"(r) : "f"(v)); return r; }
__device__ __forceinline__ float sqrt_approx(float v) { float r; asm("sqrt.approx.f32 %0, %1;" : "=f"(r) : "f"(v)); return r; }
__device__ __forceinline__ float4 lds128(uint32_t a) { float4 v; asm volatile("ld.shared.v4.f32 {%0, %1, %2, %3}, [%4];" : "=f"(v.x), "=f"(v.y), "=f"(v.z), "=f"(v.w) : "r"(a) : "memory"); return v; }
__device__ __forceinline__ uint4 lds128u(uint32_t a) { uint4 v; asm volatile("ld.shared.v4.u32 {%0, %1, %2, %3}, [%4];" : "=r"(v.x), "=r"(v.y), "=r"(v.z), "=r"(v.w) : "r"(a) : "memory"); return v; }
__device__ __forceinline__ float2 lds64(uint32_t a) { float2 v; asm volatile("ld.shared.v2.f32 {%0, %1}, [%2];" : "=f"(v.x), "=f"(v.y) : "r"(a) : "memory"); return v; }
__device__ __forceinline__ float lds32(uint32_t a) { float v; asm volatile("ld.shared.f32 %0, [%1];" : "=f"(v) : "r"(a) : "memory"); return v; }
__device__ __forceinline__ void sts32(uint32_t a, float v) { asm volatile("st.shared.f32 [%0], %1;" ::"r"(a), "f"(v) : "memory"); }
__device__ __forceinline__ void sts64(uint32_t a, float x, float y) { asm volatile("st.shared.v2.f32 [%0], {%1, %2};" ::"r"(a), "f"(x), "f"(y) : "memory"); }
__device__ __forceinline__ void sts128(uint32_t a, float x, float y, float z, float w) { asm volatile("st.shared.v4.f32 [%0], {%1, %2, %3, %4};" ::"r"(a), "f"(x), "f"(y), "f"(z), "f"(w) : "memory"); }
__device__ __forceinline__ void sts64u(uint32_t a, uint32_t x, uint32_t y) { asm volatile("st.shared.v2.u32 [%0], {%1, %2};" ::"r"(a), "r"(x), "r"(y) : "memory"); }
__device__ __forceinline__ void sts128u(uint32_t a, uint32_t x, uint32_t y, uint32_t z, uint32_t w) { asm volatile("st.shared.v4.u32 [%0], {%1, %2, %3, %4};" ::"r"(a), "r"(x), "r"(y), "r"(z), "r"(w) : "memory"); }
__device__ __forceinline__ uint4 ldg_nc(const void* p) { uint4 v; asm volatile("ld.global.nc.L1::no_allocate.v4.u32 {%0, %1, %2, %3}, [%4];" : "=r"(v.x), "=r"(v.y), "=r"(v.z), "=r"(v.w) : "l"(p)); return v; }
__device__ __forceinline__ float4 ldg_cg4(const float* p) { float4 v; asm volatile("ld.global.cg.v4.f32 {%0, %1, %2, %3}, [%4];" : "=f"(v.x), "=f"(v.y), "=f"(v.z), "=f"(v.w) : "l"(p) : "memory"); return v; }
__device__ __forceinline__ uint32_t ld_acq(const uint32_t* p) { uint32_t v; asm volatile("ld.acquire.gpu.global.u32 %0, [%1];" : "=r"(v) : "l"(p) : "memory"); return v; }
__device__ __forceinline__ unsigned long long ld_rlx64(const unsigned long long* p) { unsigned long long v; asm volatile("ld.relaxed.gpu.global.u64 %0, [%1];" : "=l"(v) : "l"(p) : "memory"); return v; }
__device__ __forceinline__ void st_rlx64(unsigned long long* p, unsigned long long v) { asm volatile("st.relaxed.gpu.global.u64 [%0], %1;" ::"l"(p), "l"(v) : "memory"); }
__device__ __forceinline__ uint4 ld_rlx128(const void* p) {
  uint4 v;
  asm volatile("{ .reg .b128 t; .reg .b64 a, b; ld.relaxed.gpu.global.b128 t, [%4]; mov.b128 {a, b}, t; mov.b64 {%0, %1}, a; mov.b64 {%2, %3}, b; }"
               : "=r"(v.x), "=r"(v.y), "=r"(v.z), "=r"(v.w) : "l"(p) : "memory");
  return v;
}
__device__ __forceinline__ void st_rlx128(void* p, uint32_t x, uint32_t y, uint32_t z, uint32_t w) {
  asm volatile("{ .reg .b128 t; .reg .b64 a, b; mov.b64 a, {%1, %2}; mov.b64 b, {%3, %4}; mov.b128 t, {a, b}; st.relaxed.gpu.global.b128 [%0], t; }"
               ::"l"(p), "r"(x), "r"(y), "r"(z), "r"(w) : "memory");
}
__device__ __forceinline__ void st_rlx(void* p, uint32_t v) { asm volatile("st.relaxed.gpu.global.u32 [%0], %1;" ::"l"(p), "r"(v) : "memory"); }
__device__ __forceinline__ uint32_t lop_select(uint32_t a, uint32_t b, uint32_t m) { uint32_t r; asm("lop3.b32 %0, %1, %2, %3, 0xd8;" : "=r"(r) : "r"(a), "r"(b), "r"(m)); return r; }
__device__ __forceinline__ float unmark(uint32_t v) { return __uint_as_float(v & ~1u); }
__device__ __forceinline__ uint32_t mark(uint32_t v, uint32_t par) { return (v & ~1u) | par; }
__device__ __forceinline__ float tanh_approx(float v) { float r; asm("tanh.approx.f32 %0, %1;" : "=f"(r) : "f"(v)); return r; }
__device__ __forceinline__ void red1(float* p, float a) { asm volatile("red.global.add.f32 [%0], %1;" ::"l"(p), "f"(a) : "memory"); }
__device__ __forceinline__ void red_inc(uint32_t* p) { asm volatile("red.relaxed.gpu.global.add.u32 [%0], 1;" ::"l"(p) : "memory"); }
__device__ __forceinline__ void red_rel(uint32_t* p) { asm volatile("red.release.gpu.global.add.u32 [%0], 1;" ::"l"(p) : "memory"); }
constexpr int SPIN_MAX = 100000;
__device__ __forceinline__ uint32_t ld_rlx(const uint32_t* p) { uint32_t v; asm volatile("ld.relaxed.gpu.global.u32 %0, [%1];" : "=r"(v) : "l"(p) : "memory"); return v; }
template <int NS = 0> __device__ __forceinline__ void wait_hint(const uint32_t* p, uint32_t target) {
#pragma unroll 1
  for (int i = 0; i < SPIN_MAX; i++) { if ((int)(ld_rlx(p) - target) >= 0) break; if (NS) __nanosleep(NS); }
}
template <int NS> __device__ __forceinline__ void wait_cnt(const uint32_t* p, uint32_t target) {
#pragma unroll 1
  for (int i = 0; i < SPIN_MAX; i++) { if ((int)(ld_rlx(p) - target) >= 0) break; if (NS) __nanosleep(NS); }
  (void)ld_acq(p);
}
template <int NS> __device__ __forceinline__ unsigned long long wait_tag(const unsigned long long* p, uint32_t tag) {
  unsigned long long v = 0;
#pragma unroll 1
  for (int i = 0; i < SPIN_MAX; i++) { v = ld_rlx64(p); if ((uint32_t)(v >> 32) == tag) break; if (NS) __nanosleep(NS); }
  return v;
}
__device__ __forceinline__ float silu_f(float v) { return v * rcp(1.f + ex2(-1.4426950408889634f * v)); }

__device__ __forceinline__ void wgmma_n8_ss_ta1_tb0(float* d, uint64_t da, uint64_t db, bool accumulate) {
  if (accumulate) {
    asm volatile("{\n.reg .pred p;\nsetp.ne.b32 p, 1, 0;\n"
      "wgmma.mma_async.sync.aligned.m64n8k16.f32.bf16.bf16 "
      "{%0, %1, %2, %3}, "
      "%4, %5, p, 1, 1, 1, 0;\n}\n"
      : "+f"(d[0]), "+f"(d[1]), "+f"(d[2]), "+f"(d[3])
      : "l"(da), "l"(db));
  } else {
    asm volatile("{\n.reg .pred p;\nsetp.ne.b32 p, 0, 0;\n"
      "wgmma.mma_async.sync.aligned.m64n8k16.f32.bf16.bf16 "
      "{%0, %1, %2, %3}, "
      "%4, %5, p, 1, 1, 1, 0;\n}\n"
      : "=f"(d[0]), "=f"(d[1]), "=f"(d[2]), "=f"(d[3])
      : "l"(da), "l"(db));
  }
}
__device__ __forceinline__ void wgmma_n8_ss_ta1_tb1(float* d, uint64_t da, uint64_t db, bool accumulate) {
  if (accumulate) {
    asm volatile("{\n.reg .pred p;\nsetp.ne.b32 p, 1, 0;\n"
      "wgmma.mma_async.sync.aligned.m64n8k16.f32.bf16.bf16 "
      "{%0, %1, %2, %3}, "
      "%4, %5, p, 1, 1, 1, 1;\n}\n"
      : "+f"(d[0]), "+f"(d[1]), "+f"(d[2]), "+f"(d[3])
      : "l"(da), "l"(db));
  } else {
    asm volatile("{\n.reg .pred p;\nsetp.ne.b32 p, 0, 0;\n"
      "wgmma.mma_async.sync.aligned.m64n8k16.f32.bf16.bf16 "
      "{%0, %1, %2, %3}, "
      "%4, %5, p, 1, 1, 1, 1;\n}\n"
      : "=f"(d[0]), "=f"(d[1]), "=f"(d[2]), "=f"(d[3])
      : "l"(da), "l"(db));
  }
}
__device__ __forceinline__ void wgmma_n32_rs_ta0_tb1(float* d, uint32_t a0, uint32_t a1, uint32_t a2, uint32_t a3, uint64_t db, bool accumulate) {
  if (accumulate) {
    asm volatile("{\n.reg .pred p;\nsetp.ne.b32 p, 1, 0;\n"
      "wgmma.mma_async.sync.aligned.m64n32k16.f32.bf16.bf16 "
      "{%0, %1, %2, %3, %4, %5, %6, %7, %8, %9, %10, %11, %12, %13, %14, %15}, "
      "{%16, %17, %18, %19}, %20, p, 1, 1, 1;\n}\n"
      : "+f"(d[0]), "+f"(d[1]), "+f"(d[2]), "+f"(d[3]), "+f"(d[4]), "+f"(d[5]), "+f"(d[6]), "+f"(d[7]), "+f"(d[8]), "+f"(d[9]), "+f"(d[10]), "+f"(d[11]), "+f"(d[12]), "+f"(d[13]), "+f"(d[14]), "+f"(d[15])
      : "r"(a0), "r"(a1), "r"(a2), "r"(a3), "l"(db));
  } else {
    asm volatile("{\n.reg .pred p;\nsetp.ne.b32 p, 0, 0;\n"
      "wgmma.mma_async.sync.aligned.m64n32k16.f32.bf16.bf16 "
      "{%0, %1, %2, %3, %4, %5, %6, %7, %8, %9, %10, %11, %12, %13, %14, %15}, "
      "{%16, %17, %18, %19}, %20, p, 1, 1, 1;\n}\n"
      : "=f"(d[0]), "=f"(d[1]), "=f"(d[2]), "=f"(d[3]), "=f"(d[4]), "=f"(d[5]), "=f"(d[6]), "=f"(d[7]), "=f"(d[8]), "=f"(d[9]), "=f"(d[10]), "=f"(d[11]), "=f"(d[12]), "=f"(d[13]), "=f"(d[14]), "=f"(d[15])
      : "r"(a0), "r"(a1), "r"(a2), "r"(a3), "l"(db));
  }
}
__device__ __forceinline__ void wgmma_n40_rs_ta0_tb1(float* d, uint32_t a0, uint32_t a1, uint32_t a2, uint32_t a3, uint64_t db, bool accumulate) {
  if (accumulate) {
    asm volatile("{\n.reg .pred p;\nsetp.ne.b32 p, 1, 0;\n"
      "wgmma.mma_async.sync.aligned.m64n40k16.f32.bf16.bf16 "
      "{%0, %1, %2, %3, %4, %5, %6, %7, %8, %9, %10, %11, %12, %13, %14, %15, %16, %17, %18, %19}, "
      "{%20, %21, %22, %23}, %24, p, 1, 1, 1;\n}\n"
      : "+f"(d[0]), "+f"(d[1]), "+f"(d[2]), "+f"(d[3]), "+f"(d[4]), "+f"(d[5]), "+f"(d[6]), "+f"(d[7]), "+f"(d[8]), "+f"(d[9]), "+f"(d[10]), "+f"(d[11]), "+f"(d[12]), "+f"(d[13]), "+f"(d[14]), "+f"(d[15]), "+f"(d[16]), "+f"(d[17]), "+f"(d[18]), "+f"(d[19])
      : "r"(a0), "r"(a1), "r"(a2), "r"(a3), "l"(db));
  } else {
    asm volatile("{\n.reg .pred p;\nsetp.ne.b32 p, 0, 0;\n"
      "wgmma.mma_async.sync.aligned.m64n40k16.f32.bf16.bf16 "
      "{%0, %1, %2, %3, %4, %5, %6, %7, %8, %9, %10, %11, %12, %13, %14, %15, %16, %17, %18, %19}, "
      "{%20, %21, %22, %23}, %24, p, 1, 1, 1;\n}\n"
      : "=f"(d[0]), "=f"(d[1]), "=f"(d[2]), "=f"(d[3]), "=f"(d[4]), "=f"(d[5]), "=f"(d[6]), "=f"(d[7]), "=f"(d[8]), "=f"(d[9]), "=f"(d[10]), "=f"(d[11]), "=f"(d[12]), "=f"(d[13]), "=f"(d[14]), "=f"(d[15]), "=f"(d[16]), "=f"(d[17]), "=f"(d[18]), "=f"(d[19])
      : "r"(a0), "r"(a1), "r"(a2), "r"(a3), "l"(db));
  }
}
__device__ __forceinline__ void wgmma_n40_ss_ta1_tb1(float* d, uint64_t da, uint64_t db, bool accumulate) {
  if (accumulate) {
    asm volatile("{\n.reg .pred p;\nsetp.ne.b32 p, 1, 0;\n"
      "wgmma.mma_async.sync.aligned.m64n40k16.f32.bf16.bf16 "
      "{%0, %1, %2, %3, %4, %5, %6, %7, %8, %9, %10, %11, %12, %13, %14, %15, %16, %17, %18, %19}, "
      "%20, %21, p, 1, 1, 1, 1;\n}\n"
      : "+f"(d[0]), "+f"(d[1]), "+f"(d[2]), "+f"(d[3]), "+f"(d[4]), "+f"(d[5]), "+f"(d[6]), "+f"(d[7]), "+f"(d[8]), "+f"(d[9]), "+f"(d[10]), "+f"(d[11]), "+f"(d[12]), "+f"(d[13]), "+f"(d[14]), "+f"(d[15]), "+f"(d[16]), "+f"(d[17]), "+f"(d[18]), "+f"(d[19])
      : "l"(da), "l"(db));
  } else {
    asm volatile("{\n.reg .pred p;\nsetp.ne.b32 p, 0, 0;\n"
      "wgmma.mma_async.sync.aligned.m64n40k16.f32.bf16.bf16 "
      "{%0, %1, %2, %3, %4, %5, %6, %7, %8, %9, %10, %11, %12, %13, %14, %15, %16, %17, %18, %19}, "
      "%20, %21, p, 1, 1, 1, 1;\n}\n"
      : "=f"(d[0]), "=f"(d[1]), "=f"(d[2]), "=f"(d[3]), "=f"(d[4]), "=f"(d[5]), "=f"(d[6]), "=f"(d[7]), "=f"(d[8]), "=f"(d[9]), "=f"(d[10]), "=f"(d[11]), "=f"(d[12]), "=f"(d[13]), "=f"(d[14]), "=f"(d[15]), "=f"(d[16]), "=f"(d[17]), "=f"(d[18]), "=f"(d[19])
      : "l"(da), "l"(db));
  }
}
__device__ __forceinline__ void wgmma_n128_rs_ta0_tb1(float* d, uint32_t a0, uint32_t a1, uint32_t a2, uint32_t a3, uint64_t db, bool accumulate) {
  if (accumulate) {
    asm volatile("{\n.reg .pred p;\nsetp.ne.b32 p, 1, 0;\n"
      "wgmma.mma_async.sync.aligned.m64n128k16.f32.bf16.bf16 "
      "{%0, %1, %2, %3, %4, %5, %6, %7, %8, %9, %10, %11, %12, %13, %14, %15, %16, %17, %18, %19, %20, %21, %22, %23, %24, %25, %26, %27, %28, %29, %30, %31, %32, %33, %34, %35, %36, %37, %38, %39, %40, %41, %42, %43, %44, %45, %46, %47, %48, %49, %50, %51, %52, %53, %54, %55, %56, %57, %58, %59, %60, %61, %62, %63}, "
      "{%64, %65, %66, %67}, %68, p, 1, 1, 1;\n}\n"
      : "+f"(d[0]), "+f"(d[1]), "+f"(d[2]), "+f"(d[3]), "+f"(d[4]), "+f"(d[5]), "+f"(d[6]), "+f"(d[7]), "+f"(d[8]), "+f"(d[9]), "+f"(d[10]), "+f"(d[11]), "+f"(d[12]), "+f"(d[13]), "+f"(d[14]), "+f"(d[15]), "+f"(d[16]), "+f"(d[17]), "+f"(d[18]), "+f"(d[19]), "+f"(d[20]), "+f"(d[21]), "+f"(d[22]), "+f"(d[23]), "+f"(d[24]), "+f"(d[25]), "+f"(d[26]), "+f"(d[27]), "+f"(d[28]), "+f"(d[29]), "+f"(d[30]), "+f"(d[31]), "+f"(d[32]), "+f"(d[33]), "+f"(d[34]), "+f"(d[35]), "+f"(d[36]), "+f"(d[37]), "+f"(d[38]), "+f"(d[39]), "+f"(d[40]), "+f"(d[41]), "+f"(d[42]), "+f"(d[43]), "+f"(d[44]), "+f"(d[45]), "+f"(d[46]), "+f"(d[47]), "+f"(d[48]), "+f"(d[49]), "+f"(d[50]), "+f"(d[51]), "+f"(d[52]), "+f"(d[53]), "+f"(d[54]), "+f"(d[55]), "+f"(d[56]), "+f"(d[57]), "+f"(d[58]), "+f"(d[59]), "+f"(d[60]), "+f"(d[61]), "+f"(d[62]), "+f"(d[63])
      : "r"(a0), "r"(a1), "r"(a2), "r"(a3), "l"(db));
  } else {
    asm volatile("{\n.reg .pred p;\nsetp.ne.b32 p, 0, 0;\n"
      "wgmma.mma_async.sync.aligned.m64n128k16.f32.bf16.bf16 "
      "{%0, %1, %2, %3, %4, %5, %6, %7, %8, %9, %10, %11, %12, %13, %14, %15, %16, %17, %18, %19, %20, %21, %22, %23, %24, %25, %26, %27, %28, %29, %30, %31, %32, %33, %34, %35, %36, %37, %38, %39, %40, %41, %42, %43, %44, %45, %46, %47, %48, %49, %50, %51, %52, %53, %54, %55, %56, %57, %58, %59, %60, %61, %62, %63}, "
      "{%64, %65, %66, %67}, %68, p, 1, 1, 1;\n}\n"
      : "=f"(d[0]), "=f"(d[1]), "=f"(d[2]), "=f"(d[3]), "=f"(d[4]), "=f"(d[5]), "=f"(d[6]), "=f"(d[7]), "=f"(d[8]), "=f"(d[9]), "=f"(d[10]), "=f"(d[11]), "=f"(d[12]), "=f"(d[13]), "=f"(d[14]), "=f"(d[15]), "=f"(d[16]), "=f"(d[17]), "=f"(d[18]), "=f"(d[19]), "=f"(d[20]), "=f"(d[21]), "=f"(d[22]), "=f"(d[23]), "=f"(d[24]), "=f"(d[25]), "=f"(d[26]), "=f"(d[27]), "=f"(d[28]), "=f"(d[29]), "=f"(d[30]), "=f"(d[31]), "=f"(d[32]), "=f"(d[33]), "=f"(d[34]), "=f"(d[35]), "=f"(d[36]), "=f"(d[37]), "=f"(d[38]), "=f"(d[39]), "=f"(d[40]), "=f"(d[41]), "=f"(d[42]), "=f"(d[43]), "=f"(d[44]), "=f"(d[45]), "=f"(d[46]), "=f"(d[47]), "=f"(d[48]), "=f"(d[49]), "=f"(d[50]), "=f"(d[51]), "=f"(d[52]), "=f"(d[53]), "=f"(d[54]), "=f"(d[55]), "=f"(d[56]), "=f"(d[57]), "=f"(d[58]), "=f"(d[59]), "=f"(d[60]), "=f"(d[61]), "=f"(d[62]), "=f"(d[63])
      : "r"(a0), "r"(a1), "r"(a2), "r"(a3), "l"(db));
  }
}
__device__ __forceinline__ void wgmma_n128_ss_ta0_tb1(float* d, uint64_t da, uint64_t db, bool accumulate) {
  if (accumulate) {
    asm volatile("{\n.reg .pred p;\nsetp.ne.b32 p, 1, 0;\n"
      "wgmma.mma_async.sync.aligned.m64n128k16.f32.bf16.bf16 "
      "{%0, %1, %2, %3, %4, %5, %6, %7, %8, %9, %10, %11, %12, %13, %14, %15, %16, %17, %18, %19, %20, %21, %22, %23, %24, %25, %26, %27, %28, %29, %30, %31, %32, %33, %34, %35, %36, %37, %38, %39, %40, %41, %42, %43, %44, %45, %46, %47, %48, %49, %50, %51, %52, %53, %54, %55, %56, %57, %58, %59, %60, %61, %62, %63}, "
      "%64, %65, p, 1, 1, 0, 1;\n}\n"
      : "+f"(d[0]), "+f"(d[1]), "+f"(d[2]), "+f"(d[3]), "+f"(d[4]), "+f"(d[5]), "+f"(d[6]), "+f"(d[7]), "+f"(d[8]), "+f"(d[9]), "+f"(d[10]), "+f"(d[11]), "+f"(d[12]), "+f"(d[13]), "+f"(d[14]), "+f"(d[15]), "+f"(d[16]), "+f"(d[17]), "+f"(d[18]), "+f"(d[19]), "+f"(d[20]), "+f"(d[21]), "+f"(d[22]), "+f"(d[23]), "+f"(d[24]), "+f"(d[25]), "+f"(d[26]), "+f"(d[27]), "+f"(d[28]), "+f"(d[29]), "+f"(d[30]), "+f"(d[31]), "+f"(d[32]), "+f"(d[33]), "+f"(d[34]), "+f"(d[35]), "+f"(d[36]), "+f"(d[37]), "+f"(d[38]), "+f"(d[39]), "+f"(d[40]), "+f"(d[41]), "+f"(d[42]), "+f"(d[43]), "+f"(d[44]), "+f"(d[45]), "+f"(d[46]), "+f"(d[47]), "+f"(d[48]), "+f"(d[49]), "+f"(d[50]), "+f"(d[51]), "+f"(d[52]), "+f"(d[53]), "+f"(d[54]), "+f"(d[55]), "+f"(d[56]), "+f"(d[57]), "+f"(d[58]), "+f"(d[59]), "+f"(d[60]), "+f"(d[61]), "+f"(d[62]), "+f"(d[63])
      : "l"(da), "l"(db));
  } else {
    asm volatile("{\n.reg .pred p;\nsetp.ne.b32 p, 0, 0;\n"
      "wgmma.mma_async.sync.aligned.m64n128k16.f32.bf16.bf16 "
      "{%0, %1, %2, %3, %4, %5, %6, %7, %8, %9, %10, %11, %12, %13, %14, %15, %16, %17, %18, %19, %20, %21, %22, %23, %24, %25, %26, %27, %28, %29, %30, %31, %32, %33, %34, %35, %36, %37, %38, %39, %40, %41, %42, %43, %44, %45, %46, %47, %48, %49, %50, %51, %52, %53, %54, %55, %56, %57, %58, %59, %60, %61, %62, %63}, "
      "%64, %65, p, 1, 1, 0, 1;\n}\n"
      : "=f"(d[0]), "=f"(d[1]), "=f"(d[2]), "=f"(d[3]), "=f"(d[4]), "=f"(d[5]), "=f"(d[6]), "=f"(d[7]), "=f"(d[8]), "=f"(d[9]), "=f"(d[10]), "=f"(d[11]), "=f"(d[12]), "=f"(d[13]), "=f"(d[14]), "=f"(d[15]), "=f"(d[16]), "=f"(d[17]), "=f"(d[18]), "=f"(d[19]), "=f"(d[20]), "=f"(d[21]), "=f"(d[22]), "=f"(d[23]), "=f"(d[24]), "=f"(d[25]), "=f"(d[26]), "=f"(d[27]), "=f"(d[28]), "=f"(d[29]), "=f"(d[30]), "=f"(d[31]), "=f"(d[32]), "=f"(d[33]), "=f"(d[34]), "=f"(d[35]), "=f"(d[36]), "=f"(d[37]), "=f"(d[38]), "=f"(d[39]), "=f"(d[40]), "=f"(d[41]), "=f"(d[42]), "=f"(d[43]), "=f"(d[44]), "=f"(d[45]), "=f"(d[46]), "=f"(d[47]), "=f"(d[48]), "=f"(d[49]), "=f"(d[50]), "=f"(d[51]), "=f"(d[52]), "=f"(d[53]), "=f"(d[54]), "=f"(d[55]), "=f"(d[56]), "=f"(d[57]), "=f"(d[58]), "=f"(d[59]), "=f"(d[60]), "=f"(d[61]), "=f"(d[62]), "=f"(d[63])
      : "l"(da), "l"(db));
  }
}
__device__ __forceinline__ void wgmma_n256_rs_ta0_tb1(float* d, uint32_t a0, uint32_t a1, uint32_t a2, uint32_t a3, uint64_t db, bool accumulate) {
  if (accumulate) {
    asm volatile("{\n.reg .pred p;\nsetp.ne.b32 p, 1, 0;\n"
      "wgmma.mma_async.sync.aligned.m64n256k16.f32.bf16.bf16 "
      "{%0, %1, %2, %3, %4, %5, %6, %7, %8, %9, %10, %11, %12, %13, %14, %15, %16, %17, %18, %19, %20, %21, %22, %23, %24, %25, %26, %27, %28, %29, %30, %31, %32, %33, %34, %35, %36, %37, %38, %39, %40, %41, %42, %43, %44, %45, %46, %47, %48, %49, %50, %51, %52, %53, %54, %55, %56, %57, %58, %59, %60, %61, %62, %63, %64, %65, %66, %67, %68, %69, %70, %71, %72, %73, %74, %75, %76, %77, %78, %79, %80, %81, %82, %83, %84, %85, %86, %87, %88, %89, %90, %91, %92, %93, %94, %95, %96, %97, %98, %99, %100, %101, %102, %103, %104, %105, %106, %107, %108, %109, %110, %111, %112, %113, %114, %115, %116, %117, %118, %119, %120, %121, %122, %123, %124, %125, %126, %127}, "
      "{%128, %129, %130, %131}, %132, p, 1, 1, 1;\n}\n"
      : "+f"(d[0]), "+f"(d[1]), "+f"(d[2]), "+f"(d[3]), "+f"(d[4]), "+f"(d[5]), "+f"(d[6]), "+f"(d[7]), "+f"(d[8]), "+f"(d[9]), "+f"(d[10]), "+f"(d[11]), "+f"(d[12]), "+f"(d[13]), "+f"(d[14]), "+f"(d[15]), "+f"(d[16]), "+f"(d[17]), "+f"(d[18]), "+f"(d[19]), "+f"(d[20]), "+f"(d[21]), "+f"(d[22]), "+f"(d[23]), "+f"(d[24]), "+f"(d[25]), "+f"(d[26]), "+f"(d[27]), "+f"(d[28]), "+f"(d[29]), "+f"(d[30]), "+f"(d[31]), "+f"(d[32]), "+f"(d[33]), "+f"(d[34]), "+f"(d[35]), "+f"(d[36]), "+f"(d[37]), "+f"(d[38]), "+f"(d[39]), "+f"(d[40]), "+f"(d[41]), "+f"(d[42]), "+f"(d[43]), "+f"(d[44]), "+f"(d[45]), "+f"(d[46]), "+f"(d[47]), "+f"(d[48]), "+f"(d[49]), "+f"(d[50]), "+f"(d[51]), "+f"(d[52]), "+f"(d[53]), "+f"(d[54]), "+f"(d[55]), "+f"(d[56]), "+f"(d[57]), "+f"(d[58]), "+f"(d[59]), "+f"(d[60]), "+f"(d[61]), "+f"(d[62]), "+f"(d[63]), "+f"(d[64]), "+f"(d[65]), "+f"(d[66]), "+f"(d[67]), "+f"(d[68]), "+f"(d[69]), "+f"(d[70]), "+f"(d[71]), "+f"(d[72]), "+f"(d[73]), "+f"(d[74]), "+f"(d[75]), "+f"(d[76]), "+f"(d[77]), "+f"(d[78]), "+f"(d[79]), "+f"(d[80]), "+f"(d[81]), "+f"(d[82]), "+f"(d[83]), "+f"(d[84]), "+f"(d[85]), "+f"(d[86]), "+f"(d[87]), "+f"(d[88]), "+f"(d[89]), "+f"(d[90]), "+f"(d[91]), "+f"(d[92]), "+f"(d[93]), "+f"(d[94]), "+f"(d[95]), "+f"(d[96]), "+f"(d[97]), "+f"(d[98]), "+f"(d[99]), "+f"(d[100]), "+f"(d[101]), "+f"(d[102]), "+f"(d[103]), "+f"(d[104]), "+f"(d[105]), "+f"(d[106]), "+f"(d[107]), "+f"(d[108]), "+f"(d[109]), "+f"(d[110]), "+f"(d[111]), "+f"(d[112]), "+f"(d[113]), "+f"(d[114]), "+f"(d[115]), "+f"(d[116]), "+f"(d[117]), "+f"(d[118]), "+f"(d[119]), "+f"(d[120]), "+f"(d[121]), "+f"(d[122]), "+f"(d[123]), "+f"(d[124]), "+f"(d[125]), "+f"(d[126]), "+f"(d[127])
      : "r"(a0), "r"(a1), "r"(a2), "r"(a3), "l"(db));
  } else {
    asm volatile("{\n.reg .pred p;\nsetp.ne.b32 p, 0, 0;\n"
      "wgmma.mma_async.sync.aligned.m64n256k16.f32.bf16.bf16 "
      "{%0, %1, %2, %3, %4, %5, %6, %7, %8, %9, %10, %11, %12, %13, %14, %15, %16, %17, %18, %19, %20, %21, %22, %23, %24, %25, %26, %27, %28, %29, %30, %31, %32, %33, %34, %35, %36, %37, %38, %39, %40, %41, %42, %43, %44, %45, %46, %47, %48, %49, %50, %51, %52, %53, %54, %55, %56, %57, %58, %59, %60, %61, %62, %63, %64, %65, %66, %67, %68, %69, %70, %71, %72, %73, %74, %75, %76, %77, %78, %79, %80, %81, %82, %83, %84, %85, %86, %87, %88, %89, %90, %91, %92, %93, %94, %95, %96, %97, %98, %99, %100, %101, %102, %103, %104, %105, %106, %107, %108, %109, %110, %111, %112, %113, %114, %115, %116, %117, %118, %119, %120, %121, %122, %123, %124, %125, %126, %127}, "
      "{%128, %129, %130, %131}, %132, p, 1, 1, 1;\n}\n"
      : "=f"(d[0]), "=f"(d[1]), "=f"(d[2]), "=f"(d[3]), "=f"(d[4]), "=f"(d[5]), "=f"(d[6]), "=f"(d[7]), "=f"(d[8]), "=f"(d[9]), "=f"(d[10]), "=f"(d[11]), "=f"(d[12]), "=f"(d[13]), "=f"(d[14]), "=f"(d[15]), "=f"(d[16]), "=f"(d[17]), "=f"(d[18]), "=f"(d[19]), "=f"(d[20]), "=f"(d[21]), "=f"(d[22]), "=f"(d[23]), "=f"(d[24]), "=f"(d[25]), "=f"(d[26]), "=f"(d[27]), "=f"(d[28]), "=f"(d[29]), "=f"(d[30]), "=f"(d[31]), "=f"(d[32]), "=f"(d[33]), "=f"(d[34]), "=f"(d[35]), "=f"(d[36]), "=f"(d[37]), "=f"(d[38]), "=f"(d[39]), "=f"(d[40]), "=f"(d[41]), "=f"(d[42]), "=f"(d[43]), "=f"(d[44]), "=f"(d[45]), "=f"(d[46]), "=f"(d[47]), "=f"(d[48]), "=f"(d[49]), "=f"(d[50]), "=f"(d[51]), "=f"(d[52]), "=f"(d[53]), "=f"(d[54]), "=f"(d[55]), "=f"(d[56]), "=f"(d[57]), "=f"(d[58]), "=f"(d[59]), "=f"(d[60]), "=f"(d[61]), "=f"(d[62]), "=f"(d[63]), "=f"(d[64]), "=f"(d[65]), "=f"(d[66]), "=f"(d[67]), "=f"(d[68]), "=f"(d[69]), "=f"(d[70]), "=f"(d[71]), "=f"(d[72]), "=f"(d[73]), "=f"(d[74]), "=f"(d[75]), "=f"(d[76]), "=f"(d[77]), "=f"(d[78]), "=f"(d[79]), "=f"(d[80]), "=f"(d[81]), "=f"(d[82]), "=f"(d[83]), "=f"(d[84]), "=f"(d[85]), "=f"(d[86]), "=f"(d[87]), "=f"(d[88]), "=f"(d[89]), "=f"(d[90]), "=f"(d[91]), "=f"(d[92]), "=f"(d[93]), "=f"(d[94]), "=f"(d[95]), "=f"(d[96]), "=f"(d[97]), "=f"(d[98]), "=f"(d[99]), "=f"(d[100]), "=f"(d[101]), "=f"(d[102]), "=f"(d[103]), "=f"(d[104]), "=f"(d[105]), "=f"(d[106]), "=f"(d[107]), "=f"(d[108]), "=f"(d[109]), "=f"(d[110]), "=f"(d[111]), "=f"(d[112]), "=f"(d[113]), "=f"(d[114]), "=f"(d[115]), "=f"(d[116]), "=f"(d[117]), "=f"(d[118]), "=f"(d[119]), "=f"(d[120]), "=f"(d[121]), "=f"(d[122]), "=f"(d[123]), "=f"(d[124]), "=f"(d[125]), "=f"(d[126]), "=f"(d[127])
      : "r"(a0), "r"(a1), "r"(a2), "r"(a3), "l"(db));
  }
}
__device__ __forceinline__ void wgmma_n256_ss_ta0_tb1(float* d, uint64_t da, uint64_t db, bool accumulate) {
  if (accumulate) {
    asm volatile("{\n.reg .pred p;\nsetp.ne.b32 p, 1, 0;\n"
      "wgmma.mma_async.sync.aligned.m64n256k16.f32.bf16.bf16 "
      "{%0, %1, %2, %3, %4, %5, %6, %7, %8, %9, %10, %11, %12, %13, %14, %15, %16, %17, %18, %19, %20, %21, %22, %23, %24, %25, %26, %27, %28, %29, %30, %31, %32, %33, %34, %35, %36, %37, %38, %39, %40, %41, %42, %43, %44, %45, %46, %47, %48, %49, %50, %51, %52, %53, %54, %55, %56, %57, %58, %59, %60, %61, %62, %63, %64, %65, %66, %67, %68, %69, %70, %71, %72, %73, %74, %75, %76, %77, %78, %79, %80, %81, %82, %83, %84, %85, %86, %87, %88, %89, %90, %91, %92, %93, %94, %95, %96, %97, %98, %99, %100, %101, %102, %103, %104, %105, %106, %107, %108, %109, %110, %111, %112, %113, %114, %115, %116, %117, %118, %119, %120, %121, %122, %123, %124, %125, %126, %127}, "
      "%128, %129, p, 1, 1, 0, 1;\n}\n"
      : "+f"(d[0]), "+f"(d[1]), "+f"(d[2]), "+f"(d[3]), "+f"(d[4]), "+f"(d[5]), "+f"(d[6]), "+f"(d[7]), "+f"(d[8]), "+f"(d[9]), "+f"(d[10]), "+f"(d[11]), "+f"(d[12]), "+f"(d[13]), "+f"(d[14]), "+f"(d[15]), "+f"(d[16]), "+f"(d[17]), "+f"(d[18]), "+f"(d[19]), "+f"(d[20]), "+f"(d[21]), "+f"(d[22]), "+f"(d[23]), "+f"(d[24]), "+f"(d[25]), "+f"(d[26]), "+f"(d[27]), "+f"(d[28]), "+f"(d[29]), "+f"(d[30]), "+f"(d[31]), "+f"(d[32]), "+f"(d[33]), "+f"(d[34]), "+f"(d[35]), "+f"(d[36]), "+f"(d[37]), "+f"(d[38]), "+f"(d[39]), "+f"(d[40]), "+f"(d[41]), "+f"(d[42]), "+f"(d[43]), "+f"(d[44]), "+f"(d[45]), "+f"(d[46]), "+f"(d[47]), "+f"(d[48]), "+f"(d[49]), "+f"(d[50]), "+f"(d[51]), "+f"(d[52]), "+f"(d[53]), "+f"(d[54]), "+f"(d[55]), "+f"(d[56]), "+f"(d[57]), "+f"(d[58]), "+f"(d[59]), "+f"(d[60]), "+f"(d[61]), "+f"(d[62]), "+f"(d[63]), "+f"(d[64]), "+f"(d[65]), "+f"(d[66]), "+f"(d[67]), "+f"(d[68]), "+f"(d[69]), "+f"(d[70]), "+f"(d[71]), "+f"(d[72]), "+f"(d[73]), "+f"(d[74]), "+f"(d[75]), "+f"(d[76]), "+f"(d[77]), "+f"(d[78]), "+f"(d[79]), "+f"(d[80]), "+f"(d[81]), "+f"(d[82]), "+f"(d[83]), "+f"(d[84]), "+f"(d[85]), "+f"(d[86]), "+f"(d[87]), "+f"(d[88]), "+f"(d[89]), "+f"(d[90]), "+f"(d[91]), "+f"(d[92]), "+f"(d[93]), "+f"(d[94]), "+f"(d[95]), "+f"(d[96]), "+f"(d[97]), "+f"(d[98]), "+f"(d[99]), "+f"(d[100]), "+f"(d[101]), "+f"(d[102]), "+f"(d[103]), "+f"(d[104]), "+f"(d[105]), "+f"(d[106]), "+f"(d[107]), "+f"(d[108]), "+f"(d[109]), "+f"(d[110]), "+f"(d[111]), "+f"(d[112]), "+f"(d[113]), "+f"(d[114]), "+f"(d[115]), "+f"(d[116]), "+f"(d[117]), "+f"(d[118]), "+f"(d[119]), "+f"(d[120]), "+f"(d[121]), "+f"(d[122]), "+f"(d[123]), "+f"(d[124]), "+f"(d[125]), "+f"(d[126]), "+f"(d[127])
      : "l"(da), "l"(db));
  } else {
    asm volatile("{\n.reg .pred p;\nsetp.ne.b32 p, 0, 0;\n"
      "wgmma.mma_async.sync.aligned.m64n256k16.f32.bf16.bf16 "
      "{%0, %1, %2, %3, %4, %5, %6, %7, %8, %9, %10, %11, %12, %13, %14, %15, %16, %17, %18, %19, %20, %21, %22, %23, %24, %25, %26, %27, %28, %29, %30, %31, %32, %33, %34, %35, %36, %37, %38, %39, %40, %41, %42, %43, %44, %45, %46, %47, %48, %49, %50, %51, %52, %53, %54, %55, %56, %57, %58, %59, %60, %61, %62, %63, %64, %65, %66, %67, %68, %69, %70, %71, %72, %73, %74, %75, %76, %77, %78, %79, %80, %81, %82, %83, %84, %85, %86, %87, %88, %89, %90, %91, %92, %93, %94, %95, %96, %97, %98, %99, %100, %101, %102, %103, %104, %105, %106, %107, %108, %109, %110, %111, %112, %113, %114, %115, %116, %117, %118, %119, %120, %121, %122, %123, %124, %125, %126, %127}, "
      "%128, %129, p, 1, 1, 0, 1;\n}\n"
      : "=f"(d[0]), "=f"(d[1]), "=f"(d[2]), "=f"(d[3]), "=f"(d[4]), "=f"(d[5]), "=f"(d[6]), "=f"(d[7]), "=f"(d[8]), "=f"(d[9]), "=f"(d[10]), "=f"(d[11]), "=f"(d[12]), "=f"(d[13]), "=f"(d[14]), "=f"(d[15]), "=f"(d[16]), "=f"(d[17]), "=f"(d[18]), "=f"(d[19]), "=f"(d[20]), "=f"(d[21]), "=f"(d[22]), "=f"(d[23]), "=f"(d[24]), "=f"(d[25]), "=f"(d[26]), "=f"(d[27]), "=f"(d[28]), "=f"(d[29]), "=f"(d[30]), "=f"(d[31]), "=f"(d[32]), "=f"(d[33]), "=f"(d[34]), "=f"(d[35]), "=f"(d[36]), "=f"(d[37]), "=f"(d[38]), "=f"(d[39]), "=f"(d[40]), "=f"(d[41]), "=f"(d[42]), "=f"(d[43]), "=f"(d[44]), "=f"(d[45]), "=f"(d[46]), "=f"(d[47]), "=f"(d[48]), "=f"(d[49]), "=f"(d[50]), "=f"(d[51]), "=f"(d[52]), "=f"(d[53]), "=f"(d[54]), "=f"(d[55]), "=f"(d[56]), "=f"(d[57]), "=f"(d[58]), "=f"(d[59]), "=f"(d[60]), "=f"(d[61]), "=f"(d[62]), "=f"(d[63]), "=f"(d[64]), "=f"(d[65]), "=f"(d[66]), "=f"(d[67]), "=f"(d[68]), "=f"(d[69]), "=f"(d[70]), "=f"(d[71]), "=f"(d[72]), "=f"(d[73]), "=f"(d[74]), "=f"(d[75]), "=f"(d[76]), "=f"(d[77]), "=f"(d[78]), "=f"(d[79]), "=f"(d[80]), "=f"(d[81]), "=f"(d[82]), "=f"(d[83]), "=f"(d[84]), "=f"(d[85]), "=f"(d[86]), "=f"(d[87]), "=f"(d[88]), "=f"(d[89]), "=f"(d[90]), "=f"(d[91]), "=f"(d[92]), "=f"(d[93]), "=f"(d[94]), "=f"(d[95]), "=f"(d[96]), "=f"(d[97]), "=f"(d[98]), "=f"(d[99]), "=f"(d[100]), "=f"(d[101]), "=f"(d[102]), "=f"(d[103]), "=f"(d[104]), "=f"(d[105]), "=f"(d[106]), "=f"(d[107]), "=f"(d[108]), "=f"(d[109]), "=f"(d[110]), "=f"(d[111]), "=f"(d[112]), "=f"(d[113]), "=f"(d[114]), "=f"(d[115]), "=f"(d[116]), "=f"(d[117]), "=f"(d[118]), "=f"(d[119]), "=f"(d[120]), "=f"(d[121]), "=f"(d[122]), "=f"(d[123]), "=f"(d[124]), "=f"(d[125]), "=f"(d[126]), "=f"(d[127])
      : "l"(da), "l"(db));
  }
}
__device__ __forceinline__ void wgmma_n256_ssp_ta0_tb1(float* d, uint64_t da, uint64_t db, int accumulate) {
    asm volatile("{\n.reg .pred p;\nsetp.ne.b32 p, %130, 0;\n"
      "wgmma.mma_async.sync.aligned.m64n256k16.f32.bf16.bf16 "
      "{%0, %1, %2, %3, %4, %5, %6, %7, %8, %9, %10, %11, %12, %13, %14, %15, %16, %17, %18, %19, %20, %21, %22, %23, %24, %25, %26, %27, %28, %29, %30, %31, %32, %33, %34, %35, %36, %37, %38, %39, %40, %41, %42, %43, %44, %45, %46, %47, %48, %49, %50, %51, %52, %53, %54, %55, %56, %57, %58, %59, %60, %61, %62, %63, %64, %65, %66, %67, %68, %69, %70, %71, %72, %73, %74, %75, %76, %77, %78, %79, %80, %81, %82, %83, %84, %85, %86, %87, %88, %89, %90, %91, %92, %93, %94, %95, %96, %97, %98, %99, %100, %101, %102, %103, %104, %105, %106, %107, %108, %109, %110, %111, %112, %113, %114, %115, %116, %117, %118, %119, %120, %121, %122, %123, %124, %125, %126, %127}, "
      "%128, %129, p, 1, 1, 0, 1;\n}\n"
      : "+f"(d[0]), "+f"(d[1]), "+f"(d[2]), "+f"(d[3]), "+f"(d[4]), "+f"(d[5]), "+f"(d[6]), "+f"(d[7]), "+f"(d[8]), "+f"(d[9]), "+f"(d[10]), "+f"(d[11]), "+f"(d[12]), "+f"(d[13]), "+f"(d[14]), "+f"(d[15]), "+f"(d[16]), "+f"(d[17]), "+f"(d[18]), "+f"(d[19]), "+f"(d[20]), "+f"(d[21]), "+f"(d[22]), "+f"(d[23]), "+f"(d[24]), "+f"(d[25]), "+f"(d[26]), "+f"(d[27]), "+f"(d[28]), "+f"(d[29]), "+f"(d[30]), "+f"(d[31]), "+f"(d[32]), "+f"(d[33]), "+f"(d[34]), "+f"(d[35]), "+f"(d[36]), "+f"(d[37]), "+f"(d[38]), "+f"(d[39]), "+f"(d[40]), "+f"(d[41]), "+f"(d[42]), "+f"(d[43]), "+f"(d[44]), "+f"(d[45]), "+f"(d[46]), "+f"(d[47]), "+f"(d[48]), "+f"(d[49]), "+f"(d[50]), "+f"(d[51]), "+f"(d[52]), "+f"(d[53]), "+f"(d[54]), "+f"(d[55]), "+f"(d[56]), "+f"(d[57]), "+f"(d[58]), "+f"(d[59]), "+f"(d[60]), "+f"(d[61]), "+f"(d[62]), "+f"(d[63]), "+f"(d[64]), "+f"(d[65]), "+f"(d[66]), "+f"(d[67]), "+f"(d[68]), "+f"(d[69]), "+f"(d[70]), "+f"(d[71]), "+f"(d[72]), "+f"(d[73]), "+f"(d[74]), "+f"(d[75]), "+f"(d[76]), "+f"(d[77]), "+f"(d[78]), "+f"(d[79]), "+f"(d[80]), "+f"(d[81]), "+f"(d[82]), "+f"(d[83]), "+f"(d[84]), "+f"(d[85]), "+f"(d[86]), "+f"(d[87]), "+f"(d[88]), "+f"(d[89]), "+f"(d[90]), "+f"(d[91]), "+f"(d[92]), "+f"(d[93]), "+f"(d[94]), "+f"(d[95]), "+f"(d[96]), "+f"(d[97]), "+f"(d[98]), "+f"(d[99]), "+f"(d[100]), "+f"(d[101]), "+f"(d[102]), "+f"(d[103]), "+f"(d[104]), "+f"(d[105]), "+f"(d[106]), "+f"(d[107]), "+f"(d[108]), "+f"(d[109]), "+f"(d[110]), "+f"(d[111]), "+f"(d[112]), "+f"(d[113]), "+f"(d[114]), "+f"(d[115]), "+f"(d[116]), "+f"(d[117]), "+f"(d[118]), "+f"(d[119]), "+f"(d[120]), "+f"(d[121]), "+f"(d[122]), "+f"(d[123]), "+f"(d[124]), "+f"(d[125]), "+f"(d[126]), "+f"(d[127])
      : "l"(da), "l"(db), "r"(accumulate));
}

template <int N> __device__ __forceinline__ void quad_sum(float* m) {
#pragma unroll
  for (int o = 1; o <= 2; o <<= 1) {
    float t[N];
#pragma unroll
    for (int i = 0; i < N; i++) t[i] = __shfl_xor_sync(~0u, m[i], o);
#pragma unroll
    for (int i = 0; i < N; i++) m[i] += t[i];
  }
}
__device__ __forceinline__ bool softmax_unsafe(const uint32_t* t, float l0, float l1) {
  const float m0 = fmaxf(bf_lo(t[0]) + bf_hi(t[0]), bf_lo(t[2]) + bf_hi(t[2])), m1 = fmaxf(bf_lo(t[1]) + bf_hi(t[1]), bf_lo(t[3]) + bf_hi(t[3]));
  return __any_sync(~0u, !(m0 * l0 < 2500.f) | !(m1 * l1 < 2500.f));
}
__device__ __forceinline__ void softmax_shift(float* p, float c0, float c1) {
#pragma unroll 1
  for (int it = 0; it < 8; it++) {
    float mx = p[0], mn = p[0];
#pragma unroll
    for (int j = 1; j < 8; j++) { mx = fmaxf(mx, p[(j >> 1) * 4 + (j & 1)]); mn = fminf(mn, p[(j >> 1) * 4 + (j & 1)]); }
#pragma unroll
    for (int o = 1; o <= 2; o <<= 1) { mx = fmaxf(mx, __shfl_xor_sync(~0u, mx, o)); mn = fminf(mn, __shfl_xor_sync(~0u, mn, o)); }
    const float half = fminf(0.5f * (mx - mn), 50.f * rcp(it & 1 ? c1 : c0));
    float r[8];
#pragma unroll
    for (int j = 0; j < 8; j++) {
      const float v = p[(j >> 1) * 4 + (j & 1)];
      r[j] = fmaxf(v - mx + half, 0.f) + fminf(v - mn - half, 0.f) + (v - v);
    }
#pragma unroll
    for (int k = 0; k < 7; k++)
#pragma unroll
      for (int j = 0; j < 8; j++) p[(k >> 1) * 16 + (k & 1) * 2 + (j >> 1) * 4 + (j & 1)] = p[((k + 1) >> 1) * 16 + ((k + 1) & 1) * 2 + (j >> 1) * 4 + (j & 1)];
#pragma unroll
    for (int j = 0; j < 8; j++) p[50 + (j >> 1) * 4 + (j & 1)] = r[j];
  }
}
template <int J0 = 0, int J1 = 8> __device__ __forceinline__ void k_exp(const float* p, float c0, float c1, float* e, float* s) {
#pragma unroll
  for (int j = J0; j < J1; j++) {
    e[2 * j] = ex2(p[2 * j] * (j & 1 ? c1 : c0));
    e[2 * j + 1] = ex2(p[2 * j + 1] * (j & 1 ? c1 : c0));
    e[16 + j] = rcp(e[2 * j] * e[2 * j + 1]);
    const float t = e[2 * j] + e[2 * j + 1];
    s[j & 1] = j < 2 ? t : s[j & 1] + t;
    s[2 + (j & 1)] = j < 2 ? e[16 + j] * t : fmaf(e[16 + j], t, s[2 + (j & 1)]);
  }
}
template <int J0 = 0, int J1 = 8> __device__ __forceinline__ void q_exp(const float* p, float c0, float c1, uint32_t* f) {
#pragma unroll
  for (int j = J0; j < J1; j++) {
    const float e0 = ex2(p[2 * j] * (j & 1 ? c1 : c0)), e1 = ex2(p[2 * j + 1] * (j & 1 ? c1 : c0)), r = rcp(e0 * e1);
    f[j] = pack2(e0, e1);
    f[8 + j] = bmul2(f[j], pack2(r, r));
  }
}

#define FMA8(A, U, X)                                                                                        \
  A[0] = fmaf(bf_lo(U.x), X, A[0]); A[1] = fmaf(bf_hi(U.x), X, A[1]); A[2] = fmaf(bf_lo(U.y), X, A[2]); A[3] = fmaf(bf_hi(U.y), X, A[3]); \
  A[4] = fmaf(bf_lo(U.z), X, A[4]); A[5] = fmaf(bf_hi(U.z), X, A[5]); A[6] = fmaf(bf_lo(U.w), X, A[6]); A[7] = fmaf(bf_hi(U.w), X, A[7])

__device__ __forceinline__ uint32_t routed_row(const __nv_bfloat16* x, uint32_t tag, int lane, uint4* xr) {
  uint32_t best = 0, sv = 0;
#pragma unroll 1
  for (int it = 0; it < SPIN_MAX; it++) {
    const int sel = 2047 - (best & 0x7ff);
#pragma unroll
    for (int i = 0; i < 4; i++) xr[i] = ldg_nc(x + (size_t)sel * DM + i * 256 + lane * 8);
    const unsigned long long st = ld_rlx64(g_stat + sel);
    const uint4 b0 = ld_rlx128(g_best + lane * 2), b1 = ld_rlx128(g_best + 64 + lane * 2);
    const uint32_t m = __reduce_max_sync(~0u, max(max(b0.y == tag ? b0.x : 0u, b0.w == tag ? b0.z : 0u), max(b1.y == tag ? b1.x : 0u, b1.w == tag ? b1.z : 0u)));
    sv = (uint32_t)st;
    if (__all_sync(~0u, b0.y == tag && b0.w == tag && b1.y == tag && b1.w == tag && m == best && (uint32_t)(st >> 32) == tag)) break;
    best = m;
    if (AM_NS) __nanosleep(AM_NS);
  }
  const uint32_t m2 = (sv & 0xffff0000u) | (sv >> 16);
  const float rs = rcp(bf_lo(sv));
#pragma unroll
  for (int i = 0; i < 4; i++) {
    const uint32_t d0 = bsub2(xr[i].x, m2), d1 = bsub2(xr[i].y, m2), d2 = bsub2(xr[i].z, m2), d3 = bsub2(xr[i].w, m2);
    xr[i] = make_uint4(pack2(bf_lo(d0) * rs, bf_hi(d0) * rs), pack2(bf_lo(d1) * rs, bf_hi(d1) * rs), pack2(bf_lo(d2) * rs, bf_hi(d2) * rs),
                       pack2(bf_lo(d3) * rs, bf_hi(d3) * rs));
  }
  return best;
}

struct Params {
  const __nv_bfloat16 *x, *wqkv, *wo, *w_r, *w_down;
  uint32_t zA, zB;
};

template <bool BY_SMID> __global__ void __launch_bounds__(384, 1)
fused_kernel(const Params P, const __grid_constant__ CUtensorMap mX, const __grid_constant__ CUtensorMap mWkv, const __grid_constant__ CUtensorMap mWq,
             const __grid_constant__ CUtensorMap mWo, const __grid_constant__ CUtensorMap mPhi, const __grid_constant__ CUtensorMap mWp,
             const __grid_constant__ CUtensorMap mOut, const __grid_constant__ CUtensorMap mWc,
             const __grid_constant__ CUtensorMap mG, const __grid_constant__ CUtensorMap mU, const __grid_constant__ CUtensorMap mD,
             const __grid_constant__ CUtensorMap mXs, const __grid_constant__ CUtensorMap mG2, const __grid_constant__ CUtensorMap mU2) {
  constexpr uint32_t sb = SB, bar = SB + SM_BAR;
  int bid = blockIdx.x;
  if (BY_SMID) {
    uint32_t sm;
    asm volatile("mov.u32 %0, %%smid;" : "=r"(sm));
    const uint32_t tq = (sm - 64) >> 1, q7 = (tq * 37) >> 8;
    const uint32_t gpc = sm < 64 ? (sm >> 1) & 7 : 1 + tq - 7 * q7, idx = (sm < 64 ? sm >> 4 : 4 + q7) * 2 + (sm & 1);
    bid = sm < 120 ? ((PTAB >> (4 * gpc)) & 7) * 16 + idx : sm < 124 ? sm + 8 : sm - 116;
  }
  const int hg = ((bid >> 2) & 3) + 4 * ((bid >> 4) & 1), mb = (bid & 3) + 4 * ((bid >> 5) & 3);
  if (bid < NCTA && threadIdx.x < 256) {
    const uint32_t r0 = threadIdx.x >> 3, c = threadIdx.x & 7, dst = sb + 2 * KV_STAGE + r0 * 128 + ((c ^ (r0 & 7)) << 4);
    const char* xs = (const char*)P.x + (size_t)(mb * 128 + r0) * 2048 + c * 16;
    const char* ws = (const char*)P.wqkv + (size_t)r0 * 6144 + 2048 + hg * 256 + c * 16;
#pragma unroll
    for (int i = 0; i < 4; i++) cp_async16(dst + i * 4096, xs + i * 65536);
#pragma unroll
    for (int i = 0; i < 8; i++) cp_async16(dst + 16384 + i * 4096, ws + (i & 1) * 196608 + (i >> 2) * 2048 + ((i >> 1) & 1) * 128);
  }
  extern __shared__ __align__(1024) uint8_t smem[];
  if (smem_u32(smem) != SB) __trap();
  const int warp = __shfl_sync(~0u, threadIdx.x >> 5, 0);

  if (bid >= NCTA) {
    constexpr uint32_t XV = SM_WPHI, ONES = SM_ZT, BF = bar, BE = bar + 48, BX = bar + 96;
    constexpr int NJ = (DM - GROWS) / 64;
    const int lane = lane_id(), sp = bid - NCTA;
    const uint32_t tag = ld_rlx(g_epoch + bid * 32 + lane) + 1;
    if (warp == 8 && elect_one()) {
#pragma unroll 1
      for (int i = 0; i < 13; i++) mbar_init(bar + 8 * i, i >= 6 && i < 12 ? 8 : 1);
    }
    if (warp == 9) { sts64u(sb + ONES + lane * 8, 0x3f803f80u, 0x3f803f80u); fence_async_smem(); }
    __syncthreads();
    if (warp == 8) {
      if (elect_one()) {
        uint32_t s = 0, ph = 1;
        for (const long long c0 = clock64(); clock64() - c0 < SP_DELAY;) {}
#pragma unroll 1
        for (int job = 0; job < 8; job++) {
          const CUtensorMap* m = job == 0 ? &mWq : sp & 2 ? &mU2 : &mG2;
          const int g0 = job ? (sp & 1) * 28 + job * 4 - 4 : sp * 4;
#pragma unroll 1
          for (int row = job ? GROWS : 0; row < DM; row += 64) {
            mbar_wait(BE + 8 * s, ph);
            mbar_expect_tx(BF + 8 * s, Q_STAGE);
            tma4d(sb + s * Q_STAGE, m, 0, row, g0, 0, BF + 8 * s);
            tma4d(sb + s * Q_STAGE + 16384, m, 0, row, g0 + 2, 0, BF + 8 * s);
            if (++s == 6) { s = 0; ph ^= 1; }
          }
        }
      }
    } else if (warp == 9) {
      uint4 xr[4];
      routed_row(P.x, tag, lane, xr);
#pragma unroll
      for (int i = 0; i < 4; i++) sts128u(sb + XV + i * 512 + lane * 16, xr[i].x, xr[i].y, xr[i].z, xr[i].w);
      fence_async_smem();
      __syncwarp();
      if (lane == 0) mbar_arrive(BX);
    } else if (warp < 8) {
      uint32_t s = 0, ph = 0;
#pragma unroll 1
      for (int job = 0; job < 8; job++) {
        float d[8] = {0.f, 0.f, 0.f, 0.f, 0.f, 0.f, 0.f, 0.f};
        if (job == 1) mbar_wait(BX, 0);
#pragma unroll 1
        for (int i = 0; i < (job ? NJ : 16); i++) {
          mbar_wait(BF + 8 * s, ph);
          wg_fence();
#pragma unroll
          for (int k = 0; k < 8; k++)
            wgmma_n8_ss_ta1_tb0(d + 4 * (k >> 2), mkdesc(sb + k * 2048, 16, 1024, 1, s * (Q_STAGE / 16) + (warp >> 2) * 1024),
                                mkdesc(sb, 16, 128, 0, job ? (XV + GROWS * 2) / 16 + i * 8 + (k & 3) * 2 : ONES / 16), 1);
          wg_commit();
          wg_wait<0>();
          if (lane == 0) mbar_arrive(BE + 8 * s);
          if (++s == 6) { s = 0; ph ^= 1; }
        }
        reg_fence<8>(d);
        float* dst = (job ? g_gp + sp * 1792 + job * 256 - 256 : g_cs + sp * 256) + (warp >> 2) * 128 + (warp & 3) * 16 + (lane >> 2);
        if ((lane & 3) == 0) {
#pragma unroll
          for (int i = 0; i < 4; i++) st_rlx(dst + (i >> 1) * 64 + (i & 1) * 8, mark(__float_as_uint(d[2 * i]), tag & 1));
        }
        __syncwarp();
      }
      if (warp == 0) g_epoch[bid * 32 + lane] = tag;
    }
    return;
  }
#define Q_SLAB(J) ((J) < 8 ? ((J) + 8 - 2 * (hg & 4)) & 15 : 2 * (hg & 4) + 2 * ((J) & 3) + ((J) >> 2 & 1))
#define Q_AOFF(J) ((J) == 8 + (hg & 3) ? SM_X0 : (J) == 12 + (hg & 3) ? SM_X1 : ((J) & 3) * Q_STAGE)
#define Q_LOAD(J)                                                                                            \
  do {                                                                                                       \
    const uint32_t fb_ = bar + B_FULLQ + 8 * ((J) & 3);                                                      \
    const int k_ = Q_SLAB(J) * 64;                                                                           \
    mbar_expect_tx(fb_, Q_STAGE);                                                                            \
    mbar_arrive2(fb_);                                                                                       \
    tma2d(sb + Q_AOFF(J), &mX, k_, mb * 128, fb_);                                                           \
    tma4d(sb + ((J) & 3) * Q_STAGE + 16384, &mWq, 0, k_, hg * 2, 0, fb_);                                    \
  } while (0)
  if (warp >= 8) {
    asm volatile("setmaxnreg.dec.sync.aligned.u32 %0;" ::"n"(REG_H));
    const int lane = lane_id();
    const int f = (warp - 9) & 3;
    if (f == 3) {
      if (elect_one()) {
        PROF(0); PROFT(32);
#pragma unroll
        for (int s = 0; s < 3; s++) mbar_init(bar + B_FULLKV + 8 * s, 1);
      }
      __syncwarp();
      asm volatile("bar.arrive 14, 288;" ::: "memory");
      if (elect_one()) {
#pragma unroll
        for (int s = 0; s < 2; s++) {
          mbar_expect_tx(bar + B_FULLKV + 8 * s, KV_STAGE);
          tma2d(sb + s * KV_STAGE, &mX, (s + 1) * 64, mb * 128, bar + B_FULLKV + 8 * s);
          tma4d(sb + s * KV_STAGE + 16384, &mWkv, 0, (s + 1) * 64, hg * 2, 1, bar + B_FULLKV + 8 * s);
        }
      }
      __syncwarp();
    }
    const uint32_t ep = ld_rlx(g_epoch + bid * 32 + lane);
    if (f < 2) {
#pragma unroll
      for (int i = 0; i < 2; i++) {
        const uint4 u = __ldg((const uint4*)P.w_r + (f * 2 + i) * 32 + lane);
        sts128u(sb + SM_XSEL + (f * 2 + i) * 512 + lane * 16, u.x, u.y, u.z, u.w);
      }
    }
    bar_sync(13, 384);
    const uint32_t tag = ep + 1, par = tag & 1;
    const bool ffn = bid < NFFN;
    const int fb = bid, cu = bid >> 1, ch = bid & 1;
#define CS_STORE(SEC, C)                                                                                     \
  _Pragma("unroll") for (int r = 0; r < 3; r++) {                                                            \
    const uint32_t h0 = pack2(C.x, C.y), h1 = pack2(C.z, C.w);                                               \
    sts64u(sb + SM_CST + (SEC) * 1024 + (lane >> 4) * 512 + (lane & 1) * 8 + r * 128 + ((((lane & 15) >> 1) ^ (r + (lane >> 4) * 4)) << 4), h0, h1); \
    C.x -= bf_lo(h0); C.y -= bf_hi(h0); C.z -= bf_lo(h1); C.w -= bf_hi(h1);                                  \
  }
#define BAD4(U) ((U.x ^ par) | (U.y ^ par) | (U.z ^ par) | (U.w ^ par))
    const int n0 = f < 2 ? 0 : 2 * f - 3, ne = FFN_OFF || !ffn ? 3 : f == 3 ? 3 + G8 : 3 + GN;
    const uint32_t fsb = sb + SM_FST + ((f + 1) & 3) * 8192, fbar = bar + B_FST + f * 16, fst = fsb + (lane >> 4) * 2048 + (lane & 15) * 16;
    const CUtensorMap *ma = &mWc, *mc = &mWc;
    int sx = 1024 + cu * 32, sy = ch * 512 + f * 192, sdy = 32;
#define STAGEG(N)                                                                                            \
  do {                                                                                                       \
    if ((N) == 3) { ma = &mG; mc = &mU; sx = fb * 32; sy = f * (GN * 32);  sdy = 0; }                        \
    if ((N) < ne && elect_one()) {                                                                           \
      const uint32_t dst_ = fsb + ((N) & 1) * 4096, b_ = fbar + ((N) & 1) * 8;                               \
      mbar_expect_tx(b_, 4096);                                                                              \
      tma2d(dst_, ma, sx, sy, b_);                                                                           \
      tma2d(dst_ + 2048, mc, sx, sy + sdy, b_);                                                              \
    }                                                                                                        \
    sy += 32 + sdy;                                                                                          \
  } while (0)
    float a[8], gsum = 0.f, usum = 0.f;
    {
      if (f == 3) {
        if (elect_one()) {
          if (XS_EARLY) { mbar_expect_tx(bar + B_XST, 16384); tma3d(sb + SM_XST, &mXs, 0, bid * 16, 0, bar + B_XST); }
          mbar_expect_tx(bar + B_WPHI, 8192);
          tma2d(sb + SM_WPHI, &mPhi, 0, hg * 128, bar + B_WPHI);
          prefetch_map(&mWq); prefetch_map(&mWo); prefetch_map(&mWp); prefetch_map(&mD);
          PROF(31);
        }
        __syncwarp();
      } else {
        if (lane == 0) prefetch_map(f == 0 ? &mWc : f == 1 ? &mG : &mU);
        if (f == 2) ((float2*)g_y[par])[bid * 32 + lane] = make_float2(0.f, 0.f);
      }
      float st[13];
#pragma unroll
      for (int i = 0; i < 13; i++) st[i] = 0.f;
#pragma unroll 1
      for (int i = 0; i < 4; i++) {
        mbar_wait(bar + B_XST + 8 * (i >> 1), 0);
        if (f == 0 && lane == 0 && i == 0) PROF(1);
        const uint4 wu = lds128u(sb + SM_XSEL + i * 512 + lane * 16);
        const float wf[8] = {bf_lo(wu.x), bf_hi(wu.x), bf_lo(wu.y), bf_hi(wu.y), bf_lo(wu.z), bf_hi(wu.z), bf_lo(wu.w), bf_hi(wu.w)};
        st[12] += ((wf[0] + wf[1]) + (wf[2] + wf[3])) + ((wf[4] + wf[5]) + (wf[6] + wf[7]));
#pragma unroll
        for (int r = 0; r < 4; r++) {
          const uint4 u = lds128u(sb + SM_XST + i * 8192 + (4 * f + r) * 512 + lane * 16);
          const float xf[8] = {bf_lo(u.x), bf_hi(u.x), bf_lo(u.y), bf_hi(u.y), bf_lo(u.z), bf_hi(u.z), bf_lo(u.w), bf_hi(u.w)};
#pragma unroll
          for (int k = 0; k < 8; k++) { st[r] += xf[k]; st[4 + r] = fmaf(xf[k], xf[k], st[4 + r]); st[8 + r] = fmaf(xf[k], wf[k], st[8 + r]); }
        }
        if (i >= 2 && f < 3) STAGEG(n0 + i - 2);
      }
      const bool up = lane & 16, up2 = lane & 8;
#pragma unroll
      for (int q = 0; q < 3; q++) {
        const float k0 = up ? st[4 * q + 2] : st[4 * q], k1 = up ? st[4 * q + 3] : st[4 * q + 1];
        const float o0 = up ? st[4 * q] : st[4 * q + 2], o1 = up ? st[4 * q + 1] : st[4 * q + 3];
        const float m0 = k0 + __shfl_xor_sync(~0u, o0, 16), m1 = k1 + __shfl_xor_sync(~0u, o1, 16);
        a[q] = (up2 ? m1 : m0) + __shfl_xor_sync(~0u, up2 ? m0 : m1, 8);
      }
      a[3] = st[12] + __shfl_xor_sync(~0u, st[12], 16);
      a[3] += __shfl_xor_sync(~0u, a[3], 8);
#pragma unroll
      for (int o = 4; o; o >>= 1)
#pragma unroll
        for (int q = 0; q < 4; q++) a[q] += __shfl_xor_sync(~0u, a[q], o);
      if ((lane & 7) == 0) sts128(sb + SM_ROWS + (4 * f + (lane >> 3)) * 16, a[0], a[1], a[2], a[3]);
      if (f < 3) asm volatile("bar.arrive 7, 128;" ::: "memory");
    }
    if (f == 3) {
      bar_sync(7, 128);
      const int row = bid * 16 + (lane & 15);
      const float4 v = lds128(sb + SM_ROWS + (lane & 15) * 16);
      const float mf = v.x * (1.f / DM), mean = bf_round(mf), var = fmaxf(fmaf(-mf, mf, v.y * (1.f / DM)), 0.f);
      const float sd = bf_round(sqrt_approx(bf_round(bf_round(var) + 1e-5f)));
      const uint32_t rb = pack2(fmaf(-mean, v.w, v.z) * rcp(sd), 0.f) & 0xffffu, ord = (rb & 0x8000u) ? (~rb & 0xffffu) : (rb | 0x8000u);
      uint32_t best = __reduce_max_sync(~0u, (ord << 16) | (uint32_t)(2047 - row));
      if (lane < 16) st_rlx64(g_stat + row, ((unsigned long long)tag << 32) | __float_as_uint(mean) | (__float_as_uint(sd) >> 16));
      if (lane == 0) { asm volatile("red.relaxed.gpu.global.max.u64 [%0], %1;" ::"l"(g_best + bid), "l"(((unsigned long long)tag << 32) | best) : "memory"); PROF(17); }
#pragma unroll 1
      for (int n = 3; n < 5; n++) STAGEG(n);
      {
        uint4 xr[4];
        best = routed_row(P.x, tag, lane, xr);
#pragma unroll
        for (int i = 0; i < (GROWS + 255) / 256; i++) {
          const uint32_t dst = sb + SM_XSEL + i * 1024 + (lane >> 2) * 128 + (lane & 3) * 8;
          sts64(dst, bf_lo(xr[i].x), bf_lo(xr[i].z)); sts64(dst + 32, bf_hi(xr[i].x), bf_hi(xr[i].z));
          sts64(dst + 64, bf_lo(xr[i].y), bf_lo(xr[i].w)); sts64(dst + 96, bf_hi(xr[i].y), bf_hi(xr[i].w));
        }
        sts64u(sb + SM_RED + 16, tag, best);
        __syncwarp();
        if (lane == 0) { mbar_arrive(bar + B_XS); PROF(19); }
      }
      unsigned long long sv4[4];
      uint4 u[4];
#pragma unroll 1
      for (int it = 0; it < SPIN_MAX; it++) {
#pragma unroll
        for (int i = 0; i < 4; i++) { u[i] = ld_rlx128(g_cs + (1 + i) * 1024 + hg * 128 + lane * 4); sv4[i] = ld_rlx64(g_stat + mb * 128 + i * 32 + lane); }
        bool ok = ((BAD4(u[0]) | BAD4(u[1]) | BAD4(u[2]) | BAD4(u[3])) & 1) == 0;
#pragma unroll
        for (int i = 0; i < 4; i++) ok = ok && (uint32_t)(sv4[i] >> 32) == tag;
        if (__all_sync(~0u, ok)) break;
        __nanosleep(200);
      }
#pragma unroll
      for (int i = 0; i < 4; i++) {
        const uint32_t sv = (uint32_t)sv4[i], sd2 = (sv << 16) | (sv & 0xffffu);
        sts64(sb + SM_STAT + (i * 32 + lane) * 8, -bf_hi(sv), rcp(bf_lo(sv)));
        sts128u(sb + SM_SDT + lane * 64 + ((i ^ ((lane >> 1) & 3)) << 4), sd2, sd2, sd2, sd2);
      }
#pragma unroll
      for (int i = 0; i < 2; i++) {
        float4 c = make_float4(unmark(u[i].x) + unmark(u[i + 2].x), unmark(u[i].y) + unmark(u[i + 2].y), unmark(u[i].z) + unmark(u[i + 2].z),
                               unmark(u[i].w) + unmark(u[i + 2].w));
        CS_STORE(i, c);
      }
      fence_async_smem();
      bar_sync(8, 64);
      if (lane == 0) { mbar_arrive(bar + B_CS); PROF(10); }
    }
    {
      uint32_t xa = sb + SM_RED + 32, xstep = 0;
      const uint32_t zero = __float_as_uint(lds32(sb + SM_RED + 12));
#pragma unroll 1
      for (int ph = f == 3; ph < 2; ph++) {
#pragma unroll
        for (int j = 0; j < 8; j++) a[j] = 0.f;
        if (ph && f == 0) {
        {
          mbar_wait(bar + B_WPHI, 0);
          float nq[8] = {0.f, 0.f, 0.f, 0.f, 0.f, 0.f, 0.f, 0.f};
  #pragma unroll 2
          for (int r = 0; r < 16; r++) {
            const uint4 u = lds128u(sb + SM_WPHI + ((lane >> 2) * 16 + r) * 64 + (((lane ^ (r >> 1)) & 3) << 4));
            nq[0] = fmaf(bf_lo(u.x), bf_lo(u.x), nq[0]); nq[1] = fmaf(bf_hi(u.x), bf_hi(u.x), nq[1]); nq[2] = fmaf(bf_lo(u.y), bf_lo(u.y), nq[2]);
            nq[3] = fmaf(bf_hi(u.y), bf_hi(u.y), nq[3]); nq[4] = fmaf(bf_lo(u.z), bf_lo(u.z), nq[4]); nq[5] = fmaf(bf_hi(u.z), bf_hi(u.z), nq[5]);
            nq[6] = fmaf(bf_lo(u.w), bf_lo(u.w), nq[6]); nq[7] = fmaf(bf_hi(u.w), bf_hi(u.w), nq[7]);
          }
          uint32_t m = 0;
  #pragma unroll
          for (int i = 0; i < 8; i++) m = max(m, __float_as_uint(nq[i] + __shfl_xor_sync(~0u, nq[i], 4)) & 0x7fffffffu);
          sts32(sb + SM_RED + 24, 4.2f * __uint_as_float(__reduce_max_sync(~0u, m)));
        }
          asm volatile("bar.arrive 8, 64;" ::: "memory");
        }
        if (ph) { mbar_wait(bar + B_XS, 0); xa = sb + SM_XSEL + f * (GN * 128) + ((lane >> 2) & 3) * 32; xstep = 128; }
#pragma unroll 1
        for (int n = ph ? 3 : n0; n < (ph ? ne : 3); n++) {
          const float4 x0 = lds128(xa), x1 = lds128(xa + 16);
          xa += xstep;
          mbar_wait(fbar + (n & 1) * 8, ((n - n0) >> 1) & 1);
          uint4 u[8];
#pragma unroll
          for (int j = 0; j < 8; j++) u[j] = lds128u(fst + (n & 1) * 4096 + j * 256);
          FMA8(a, u[0], x0.x); FMA8(a, u[1], x0.y); FMA8(a, u[2], x0.z); FMA8(a, u[3], x0.w);
          if (__any_sync(~0u, ((u[4].x | u[5].x | u[6].x | u[7].x | __float_as_uint(a[0]) | __float_as_uint(a[7])) & zero) == 0)) STAGEG(n + 2);
          FMA8(a, u[4], x1.x); FMA8(a, u[5], x1.y); FMA8(a, u[6], x1.z); FMA8(a, u[7], x1.w);
        }
#pragma unroll
        for (int o = 4; o <= 8; o <<= 1)
#pragma unroll
          for (int j = 0; j < 8; j++) a[j] += __shfl_xor_sync(~0u, a[j], o);
        if (ph && lane == 0) mbar_arrive(bar + B_FFN);
        const uint32_t red = ph ? sb + SM_GRED : sb + SM_RED + 64;
        if ((lane & 12) == 0) {
          const uint32_t d = red + f * 256 + (lane >> 4) * 128 + (lane & 3) * 32;
          sts128(d, a[0], a[1], a[2], a[3]); sts128(d + 16, a[4], a[5], a[6], a[7]);
        }
        if (f != 2) {
          asm volatile("bar.arrive %0, %1;" ::"r"(4 + ph), "r"(96 + 32 * ph) : "memory");
        } else {
          bar_sync(4 + ph, 96 + 32 * ph);
          const uint32_t ra = red + lane * 4;
          gsum = lds32(ra) + lds32(ra + 256) + lds32(ra + 512);
          usum = lds32(ra + 128) + lds32(ra + 384) + lds32(ra + 640);
          if (!ph) st_rlx(g_cs + 1024 + ch * 2048 + cu * 32 + lane, mark(__float_as_uint(gsum + usum), par));
          else { gsum += lds32(ra + 768); usum += lds32(ra + 896); }
          if (lane == 0) PROF(ph ? 34 : 18);
        }
      }
    }
    if (f == 3) {
      if (elect_one()) {
        PROF(7);
        mbar_wait(bar + B_FULLQ, 0);
#pragma unroll 1
        for (int j = 3; j < 16; j++) {
          mbar_wait(bar + (j < 4 ? B_EMPTYKV + 16 : B_EMPTYQ + 8 * (j & 3)), ((j >> 2) & 1) ^ 1);
          if (j == 12 + (hg & 3)) mbar_wait(bar + B_KVST + 8, 0);
          Q_LOAD(j);
        }
        PROF(47);
        mbar_expect_tx(bar + B_DN, 65536);
#pragma unroll 1
        for (int i = 0; i < 4; i++) {
          mbar_wait(bar + B_EMPTYQ + 8 * i, 1);
          tma3d(sb + i * Q_STAGE, &mD, 0, fb * 32, i * 4, bar + B_DN);
        }
        PROF(48);
#pragma unroll 1
        for (int i = 0; i < 16; i++) {
          const int s = i & 3, n = i < 9 ? i - 2 : i - 9, kb = i < 2 ? 2 * hg + i : 2 * (n + (n >= hg)) + (i >= 9);
          if (i >= 4) mbar_wait(bar + B_EMPTYQ + 8 * s, ((i >> 2) & 1) ^ 1);
          mbar_expect_tx(bar + B_FULLQ + 8 * s, 16384);
          if (i < 2) {
            mbar_arrive2(bar + B_FULLQ + 8 * s);
            tma3d(sb + s * Q_STAGE + 16384, &mWo, 0, kb * 64, hg * 2, bar + B_FULLQ + 8 * s);
          } else {
            tma5d(sb + s * Q_STAGE + 16384, &mWp, hg * 128, kb * 2, bar + B_FULLQ + 8 * s);
            tma5d(sb + s * Q_STAGE + 24576, &mWp, hg * 128 + 64, kb * 2, bar + B_FULLQ + 8 * s);
            if (i >= 3) {
              if (i == 3) { mbar_wait(bar + B_DND, 0); PROF(14); }
#pragma unroll 1
              for (int a = i == 3 ? 2 : i; a <= i; a++) {
                const uint4* src = g_ofr + (mb * 16 + (a == 2 ? (hg == 0 ? 2 : 0) : kb)) * 1024;
#pragma unroll
                for (int h = 0; h < 2; h++) {
                  mbar_expect_tx(bar + B_AIN + (a & 3) * 16 + h * 8, 8192);
                  bulk_load(sb + (a & 3) * Q_STAGE + h * 8192, src + h * 512, 8192, bar + B_AIN + (a & 3) * 16 + h * 8);
                }
              }
            }
          }
        }
      }
    } else {
      if (f == 2) {
        if (PFD && ffn) {
#pragma unroll 1
          for (int i = 0; i < 16; i++) { touch_l2((const char*)P.w_down + fb * 65536 + i * 4096 + lane * 128, lane); __nanosleep(PFD); }
        }
        {
#pragma unroll 1
          for (int i = 0; i < 8; i++) { touch_l2((const char*)P.wo + ((mb & 7) * 128 + i * 16 + (lane >> 1)) * 2048 + hg * 256 + (lane & 1) * 128, lane); __nanosleep(PFD); }
        }
        asm volatile("cp.async.wait_all;" ::: "memory");
        uint4 u;
#pragma unroll 1
        for (int it = 0; it < SPIN_MAX; it++) {
          u = ld_rlx128(g_cs + hg * 128 + lane * 4);
          if (__all_sync(~0u, !(BAD4(u) & 1))) break;
          __nanosleep(200);
        }
        mbar_wait(bar + B_PHI, 0);
        float4 c = make_float4(unmark(u.x), unmark(u.y), unmark(u.z), unmark(u.w));
        CS_STORE(2, c);
        fence_async_smem();
        __syncwarp();
        if (lane == 0) mbar_arrive(bar + B_CSQ);
      }
      const uint32_t target = __shfl_sync(~0u, tag, 0) * 16;
#pragma unroll 1
      for (int R = 0; R < 2; R++) {
        const uint32_t own = (hg * 2 + R) * 16 + mb, pst = sb + (R ? SM_PST1 : SM_PST0);
        if (f == R) {
          mbar_wait(bar + B_KVST + 8 * R, 0);
          if (f == 1 && lane == 0) PROF(11);
          wait_hint(XC1(hg, R) + mb, target);
          if (elect_one()) {
            PROF(35 + R);
            fence_async_global();
            mbar_expect_tx(bar + B_PART + 8 * R, 8192);
            bulk_load(pst, g_part + own * 512, 8192, bar + B_PART + 8 * R);
          }
          __syncwarp();
          uint4 uz;
#pragma unroll 1
          for (int it = 0; it < SPIN_MAX; it++) {
            uz = ld_rlx128(g_zpart + own * 128 + lane * 4);
            if (__all_sync(~0u, !(BAD4(uz) & 1))) break;
          }
          const bool b1 = lane & 2, b2 = lane & 4;
          const float z0 = unmark(b1 ? uz.z : uz.x) + __shfl_xor_sync(~0u, unmark(b1 ? uz.x : uz.z), 2);
          const float z1 = unmark(b1 ? uz.w : uz.y) + __shfl_xor_sync(~0u, unmark(b1 ? uz.y : uz.w), 2);
          float z = (b2 ? z1 : z0) + __shfl_xor_sync(~0u, b2 ? z0 : z1, 4);
          z += __shfl_xor_sync(~0u, z, 8);
          z += __shfl_xor_sync(~0u, z, 16);
          if (lane < 8) st_rlx(g_zres + own * 8 + (lane & 1) * 4 + (lane & 2) + (lane >> 2), mark(__float_as_uint(z), par));
          if (lane == 0) red_inc(XC2(hg, R));
          __syncwarp();
        }
        if (f == R || f == R + 1) {
          const uint32_t hf = f - R, m1 = ~lane & 1, gq = hf * 4 + (lane >> 3), ts = (lane >> 1) & 3;
          float a0 = 0.f, a1 = 0.f, a2 = 0.f, a3 = 0.f;
          mbar_wait(bar + B_PART + 8 * R, 0);
#pragma unroll 1
          for (int it = 0; it < SPIN_MAX; it++) {
            uint32_t bad = 0;
            a0 = a1 = a2 = a3 = 0.f;
#pragma unroll 1
            for (int b = 0; b < 16; b += 8) {
              uint2 u[8];
              if (it == 0) {
#pragma unroll
                for (int i = 0; i < 8; i++) { const float2 v = lds64(pst + (b + i) * 512 + hf * 256 + lane * 8); u[i] = make_uint2(__float_as_uint(v.x), __float_as_uint(v.y)); }
              } else {
#pragma unroll
                for (int i = 0; i < 8; i++) {
                  const unsigned long long v = ld_rlx64((const unsigned long long*)g_part + own * 1024 + (b + i) * 64 + hf * 32 + lane);
                  u[i] = make_uint2((uint32_t)v, (uint32_t)(v >> 32));
                }
              }
#pragma unroll
              for (int i = 0; i < 8; i++) {
                bad |= u[i].x ^ par;
                a0 += bf_lo(i & 1 ? u[i].x & ~m1 : u[i].x | m1); a1 += bf_hi(u[i].x); a2 += bf_lo(u[i].y); a3 += bf_hi(u[i].y);
              }
            }
            if (__all_sync(~0u, !(bad & m1))) break;
          }
          uint32_t* dst = (uint32_t*)g_res[par] + own * 128 + gq * 16 + ts;
          const uint32_t j0 = (lane & 1) * 2, vb = ts == (gq >> 1);
          st_rlx(dst + ((j0 ^ (gq >> 1)) & 3) * 4, pack2(a0, a1) | vb);
          st_rlx(dst + (((j0 + 1) ^ (gq >> 1)) & 3) * 4, pack2(a2, a3) | vb);
          ((uint2*)g_res[par ^ 1])[own * 64 + hf * 32 + lane] = make_uint2(0u, 0u);
          __syncwarp();
          if (lane == 0) { red_inc(XC2(hg, R)); if (!hf) PROF(R ? 12 : 30); }
        }
      }
      if (f == 2) {
        if (ffn && !FFN_OFF) {
#pragma unroll 1
          for (int it = 0; it < SPIN_MAX; it++) {
            const uint32_t pg = ld_rlx((const uint32_t*)g_gp + fb * 32 + lane), pu = ld_rlx((const uint32_t*)g_gp + FF + fb * 32 + lane);
            if (__all_sync(~0u, !(((pg ^ par) | (pu ^ par)) & 1))) { gsum += unmark(pg); usum += unmark(pu); break; }
            __nanosleep(200);
          }
        }
        const float h = bf_round(silu_f(bf_round(gsum))) * bf_round(usum);
        const uint32_t h2 = pack2(h, h);
        sts128u(sb + SM_HT + lane * 16, h2, h2, h2, h2);
        fence_async_smem();
        __syncwarp();
        if (lane == 0) { mbar_arrive(bar + B_H); PROF(20); }
      }
      if (f < 2) {
        wait_hint(XC2(hg, f), 3 * target);
        mbar_wait(bar + B_KVST + 8, 0);
        if (lane == 0) PROF(40 + f);
#pragma unroll 1
        for (int it = 0; it < SPIN_MAX; it++) {
          if (elect_one()) {
            fence_async_global();
            mbar_expect_tx(bar + B_RES + 8 * f, 8192);
            bulk_load(sb + SM_V + f * 8192, g_res[par] + (hg * 4 + f * 2) * 256, 8192, bar + B_RES + 8 * f);
          }
          __syncwarp();
          const uint4 uz = ld_rlx128(g_zres + (hg * 4 + f * 2) * 64 + lane * 4);
          const uint32_t zw[4] = {uz.x, uz.y, uz.z, uz.w};
#pragma unroll
          for (int j = 0; j < 4; j++) {
            const uint32_t zz = pack2(unmark(zw[j]), 1.f), row = (lane & 3) * 4 + j;
            sts128u(sb + SM_ZT + (2 * f + (lane >> 4)) * 1024 + row * 64 + ((((lane >> 2) ^ (row >> 1)) & 3) << 4), zz, zz, zz, zz);
          }
          uint32_t bad = BAD4(uz);
          mbar_wait(bar + B_RES + 8 * f, it & 1);
#pragma unroll
          for (int i = 0; i < 16; i++) bad |= ~__float_as_uint(lds32(sb + SM_V + f * 8192 + i * 512 + lane * 16 + (lane >> 3) * 4));
          if (__all_sync(~0u, !(bad & 1))) break;
        }
        fence_async_smem();
        __syncwarp();
        if (lane == 0) { mbar_arrive(bar + B_TILE + 8 * f); PROF(f ? 13 : 27); }
      }
      if (f < 2) {
        uint32_t phases = 0;
#pragma unroll 1
        for (int i = 2; i < 16; i++) {
          const int s = i & 3;
          const uint32_t ab = bar + B_AIN + s * 16 + f * 8, slot = sb + s * Q_STAGE + f * 8192;
#pragma unroll 1
          for (int it = 0; it < SPIN_MAX; it++) {
            mbar_wait(ab, (phases >> s) & 1);
            phases ^= 1u << s;
            uint32_t bad = 0;
#pragma unroll
            for (int n = 0; n < 8; n++) bad |= __float_as_uint(lds32(slot + n * 1024 + lane * 32 + (lane >> 2) * 4)) ^ par;
            if (__all_sync(~0u, !(bad & 1))) break;
            if (elect_one()) {
              const int n = i < 9 ? i - 2 : i - 9, kb = 2 * (n + (n >= hg)) + (i >= 9);
              PROF(49);
              mbar_expect_tx(ab, 8192);
              bulk_load(slot, g_ofr + (mb * 16 + kb) * 1024 + f * 512, 8192, ab);
            }
            __syncwarp();
          }
          if (lane == 0) { mbar_arrive(bar + B_FULLQ + 8 * s); if (i == 2 && f == 0) PROF(15); }
        }
        if (f == 0) g_epoch[bid * 32 + lane] = tag;
      } else {
        if (elect_one()) {
          prefetch_map(&mOut);
          if (ffn) { mbar_wait(bar + B_YD, 0); red_rel(g_ycnt); PROF(21); }
        }
        __syncwarp();
        if (f == 2) {
          const uint32_t best = __float_as_uint(lds32(sb + SM_RED + 20));
          const int sel = 2047 - (best & 0x7ff) - mb * 128;
          if (sel >= 0 && sel < 128) {
            const uint2 xr = __ldg((const uint2*)(P.x + (size_t)(mb * 128 + sel) * DM + hg * 128 + lane * 4));
            const float2 st = lds64(sb + SM_STAT + sel * 8);
            const uint32_t ord = best >> 16, rb = (ord & 0x8000u) ? (ord & 0x7fffu) : (~ord & 0xffffu);
            const float sg = rcp(1.f + ex2(-1.4426950408889634f * bf_lo(rb)));
            const uint32_t sg2 = pack2(sg, sg), nm2 = pack2(st.x, st.x);
            wait_cnt<0>(g_ycnt, tag * NFFN);
            float4 y = make_float4(0.f, 0.f, 0.f, 0.f);
#pragma unroll
            for (int i = 0; i < 8; i++) {
              const float4 c = ldg_cg4(g_y[par ^ 1][i] + hg * 128 + lane * 4);
              y.x += c.x; y.y += c.y; y.z += c.z; y.w += c.w;
            }
            uint32_t o[2];
#pragma unroll
            for (int i = 0; i < 2; i++) {
              const uint32_t d = badd2(i ? xr.y : xr.x, nm2);
              const uint32_t tt = badd2(pack2(bf_lo(d) * st.y, bf_hi(d) * st.y), bmul2(i ? pack2(y.z, y.w) : pack2(y.x, y.y), sg2));
              o[i] = pack2(silu_f(bf_lo(tt)), silu_f(bf_hi(tt)));
            }
            sts64u(sb + SM_UPD + lane * 8, o[0], o[1]);
          }
          if (lane == 0) sts32(sb + SM_UPD + 256, __int_as_float(sel));
          __syncwarp();
          if (lane == 0) { mbar_arrive(bar + B_UPD); PROF(22); }
        }
      }
    }
  } else {
    const int t7 = threadIdx.x & 127;
    const char* pfa = warp < 4 ? (const char*)P.x + bid * 32768 + (t7 & 15) * 2048 + (t7 >> 4) * 128
                               : (const char*)P.wqkv + (size_t)((t7 >> 4) * 64 + (bid >> 1)) * 6144 + 2048 + (bid & 1) * 2048 + (t7 & 15) * 128;
    if (t7 >= 16 && t7 < 16 * PF_FIRST) prefetch_l2(pfa);
    if (warp < 7) sts128(sb + SM_CST + threadIdx.x * 16, 0.f, 0.f, 0.f, 0.f);
    else sts32(sb + SM_RED + (threadIdx.x & 15) * 4, threadIdx.x & 8 ? 1.f : 0.f);
    if (elect_one()) {
#pragma unroll 1
      for (uint32_t b = B_FST + warp * 8; b < B_END; b += 64)
        mbar_init(bar + b, b < B_FULLQ ? 1 : b < B_FFN ? 3 : b < B_EMPTYKV ? 4 : 8);
    }
    __syncwarp();
    asm volatile("bar.arrive 13, 384;" ::: "memory");
    asm volatile("setmaxnreg.inc.sync.aligned.u32 %0;" ::"n"(REG_C));
    if (t7 >= 16 * PF_FIRST && threadIdx.x < 128 + 16 * PF_W) prefetch_l2(pfa);
    asm volatile("cp.async.wait_all;" ::: "memory");
    fence_async_smem();
    bar_sync(14, 288);
    if (threadIdx.x == 0) mbar_arrive(bar + B_FULLKV + 16);
    const int lane = lane_id();
    const int wg = warp >> 2, w = warp & 3, g = lane >> 2, t = lane & 3;
    float kv[128];
    {
      uint32_t s = 2, ph = 0, sp = 0, php = 0;
#pragma unroll 1
      for (int j = 0; j < 15; j++) {
        PW0(32 + j); mbar_wait(bar + B_FULLKV + 8 * s, ph); PW1(32 + j);
        if (wg == 1) bar_sync(10 + s, 256);
        wg_fence();
        const uint32_t hA = fresh_hi<H128>(P.zA), hB = fresh_hi<H128>(P.zB);
        wgmma_n256_ssp_ta0_tb1(kv, mkdesch(sb, 16, hA, wg * 512 + s * (KV_STAGE / 16)), mkdesch(sb + 16384, 8192, hB, s * (KV_STAGE / 16)), j);
#pragma unroll
        for (int k = 1; k < 4; k++)
          wgmma_n256_ss_ta0_tb1(kv, mkdesch(sb + k * 32, 16, hA, wg * 512 + s * (KV_STAGE / 16)),
                                mkdesch(sb + 16384 + k * 2048, 8192, hB, s * (KV_STAGE / 16)), 1);
        wg_commit();
        if (wg == 0) asm volatile("bar.arrive %0, 256;" ::"r"(10 + s) : "memory");
        if (warp == 0 && j) {
          mbar_wait(bar + B_EMPTYKV + 8 * sp, php);
          if (elect_one()) {
            if (j < 14) {
              mbar_expect_tx(bar + B_FULLKV + 8 * sp, KV_STAGE);
              tma2d(sb + sp * KV_STAGE, &mX, (j + 2) * 64, mb * 128, bar + B_FULLKV + 8 * sp);
              tma4d(sb + sp * KV_STAGE + 16384, &mWkv, 0, (j + 2) * 64, hg * 2, 1, bar + B_FULLKV + 8 * sp);
            } else {
              Q_LOAD(0);
            }
            if (j < 3 - XS_EARLY) {
              const int xh = j - 1 + XS_EARLY;
              mbar_expect_tx(bar + B_XST + 8 * xh, 16384);
              tma3d(sb + SM_XST + xh * 16384, &mXs, 0, bid * 16, 2 * xh, bar + B_XST + 8 * xh);
            }
          }
          __syncwarp();
        }
        if (j == 0) {
          if (wg == 0) prefetch_l2(pfa + 1024);
        } else if (wg == 1) {
          if (j < 3) {
            if (j == 2 || t7 >= 16 * PF_W) prefetch_l2(pfa + (j - 1) * (8 * 393216));
          } else if (j == 13) {
            prefetch_l2((const char*)P.wo + bid * 16384 + t7 * 128);
          }
        }
        wg_wait<0>();
        if (lane == 0) mbar_arrive(bar + B_EMPTYKV + 8 * s);
        sp = s; php = ph;
        ph ^= s == 1;
        s = s == 2 ? 0 : s + 1;
      }
    }
    const int lrow = wg * 64 + w * 16 + (lane & 15);
    const uint32_t sw128 = lrow * 128, x128 = (lrow & 7), hi16 = lane >> 4;
    mbar_wait(bar + B_CS, 0);
    const uint32_t tag = __float_as_uint(lds32(sb + SM_RED + 16));
    const int zero = __float_as_int(lds32(sb + SM_RED + 12));
    const float wn = lds32(sb + SM_RED + 24);
    const float2 st0 = lds64(sb + SM_STAT + (wg * 64 + w * 16 + g) * 8), st1 = lds64(sb + SM_STAT + (wg * 64 + w * 16 + g + 8) * 8);
    const float c0 = st0.y * 1.4426950408889634f, c1 = st1.y * 1.4426950408889634f;
    const uint32_t nm20 = pack2(st0.x, st0.x), nm21 = pack2(st1.x, st1.x), fmask = t == 0 ? ~0u : t == 1 ? 0xffffu : 0u;
    const uint32_t fa0 = nm20 & fmask, fa1 = nm21 & fmask;
    asm volatile("cp.async.wait_all;" ::: "memory");
    PW0(47); mbar_wait(bar + B_FULLKV + 16, 1); PW1(47);
    wg_fence();
    wgmma_n256_rs_ta0_tb1(kv, fa0, fa1, 0u, 0u, mkdesc(sb + SM_CST, 512, 0, 1), 1);
    {
      const uint32_t hA = fresh_hi<H128>(P.zA), hB = fresh_hi<H128>(P.zB);
#pragma unroll
      for (int k = 0; k < 4; k++)
        wgmma_n256_ss_ta0_tb1(kv, mkdesch(sb + 2 * KV_STAGE + k * 32, 16, hA, wg * 512), mkdesch(sb + 2 * KV_STAGE + 16384 + k * 2048, 8192, hB), 1);
    }
    wg_commit();
    if (warp == 0) {
      mbar_wait(bar + B_EMPTYKV + 8, 0);
      if (elect_one()) {
#pragma unroll 1
        for (int j = 1; j < 3; j++) Q_LOAD(j);
      }
      __syncwarp();
    }
    wg_wait<0>();
    reg_fence<128>(kv);
    if (lane == 0) mbar_arrive(bar + B_EMPTYKV + 16);
    PROFC(2);
    float q[64];
#define QMMA(J, AOFF16, ACCUM)                                                                                     \
  do {                                                                                                             \
    const uint32_t hA_ = fresh_hi<H128>(P.zA), hB_ = fresh_hi<H128>(P.zB);                                         \
    _Pragma("unroll") for (int k = 0; k < 4; k++)                                                                  \
      wgmma_n128_ss_ta0_tb1(q, mkdesch(sb + k * 32, 16, hA_, wg * 512 + (AOFF16)),                                 \
                            mkdesch(sb + 16384 + k * 2048, 8192, hB_, ((J) & 3) * (Q_STAGE / 16)), k ? 1 : (ACCUM)); \
  } while (0)
#define QWAIT(J) do { PW0(J); mbar_wait(bar + B_FULLQ + 8 * ((J) & 3), ((J) >> 2) & 1); PW1(J); } while (0)
#define QSTEP_A(J, AOFF16, ACCUM) do { QWAIT(J); wg_fence(); QMMA(J, AOFF16, ACCUM); wg_commit(); } while (0)
#define QREL(J) do { if (lane == 0) mbar_arrive(bar + B_EMPTYQ + 8 * ((J) & 3)); } while (0)
#define Q_OFF16(J) ((J) >= 8 && (J) < 16 ? Q_AOFF(J) / 16 : ((J) & 3) * (Q_STAGE / 16))
#define QPLAIN(J) do { QSTEP_A(J, Q_OFF16(J), 1); wg_wait<1>(); QREL((J) - 1); } while (0)
#define QNEXT(J) do { QPLAIN(J); SCHED_FENCE(); } while (0)
#define PHI_PROJ(DST, SRC, H0, H1)                                                                                 \
  do {                                                                                                             \
    uint32_t a_[32];                                                                                               \
    _Pragma("unroll") for (int j = 8 * (H0); j < 8 * (H1); j++) {                                                  \
      a_[j] = pack2(SRC[2 * j], SRC[2 * j + 1]);                                                                   \
      asm volatile("fma.rn.bf16x2 %0, %1, %1, %0;" : "+r"(nq[(j >> 4) * 2 + (j & 1)]) : "r"(a_[j]));               \
    }                                                                                                              \
    wg_fence();                                                                                                    \
    const uint32_t hB_ = fresh_hi<H64>(P.zB);                                                                      \
    _Pragma("unroll") for (int hk = 2 * (H0); hk < 2 * (H1); hk++)                                                 \
        wgmma_n32_rs_ta0_tb1(DST + 16 * (hk >> 1), a_[4 * hk], a_[4 * hk + 1], a_[4 * hk + 2], a_[4 * hk + 3],     \
                             mkdesch(sb + SM_WPHI + hk * 1024, 16, hB_), hk & 1);                                \
    wg_commit();                                                                                                   \
  } while (0)
    {
      float p[64], ea[24], eb[24], sa[4], sc[4], kz[20];
      uint32_t vp[32];
#pragma unroll
      for (int j = 0; j < 32; j++) vp[j] = pack2(kv[64 + 2 * j], kv[65 + 2 * j]);
      const uint32_t vr = w * 16 + (lane & 15), vb = sb + SM_V + wg * 4096 + vr * 64, x64 = (vr >> 1) & 3;
#define V_STORE(R)                                                                                           \
  _Pragma("unroll") for (int j = 0; j < 4; j++)                                                              \
      stsm4(vb + (j >> 1) * 8192 + ((((j & 1) * 2 + hi16) ^ x64) << 4), vp[16 * (R) + 4 * j], vp[16 * (R) + 4 * j + 1], vp[16 * (R) + 4 * j + 2], vp[16 * (R) + 4 * j + 3])
      V_STORE(0);
      mbar_wait(bar + B_WPHI, 0);
      {
        uint32_t nq[4] = {0u, 0u, 0u, 0u};
        PHI_PROJ(p, kv, 0, 4);
        QSTEP_A(0, 0, 0);
        const bool unsafe = softmax_unsafe(nq, c0 * c0 * wn, c1 * c1 * wn);
        wg_wait<1>();
        reg_fence<64>(p);
        if (__builtin_expect(unsafe, 0)) softmax_shift(p, c0, c1);
      }
#define K_NORM(S) do { quad_sum<4>(S); _Pragma("unroll") for (int i = 0; i < 4; i++) S[i] = rcp(S[i]) * ((i & 1) ? st1.y : st0.y); } while (0)
#define K_STORE(SLOT, E, S) K_STORE_(SLOT, E, S, 0, 2)
#define K_STORE_(SLOT, E, S, J0, J1)                                                                         \
  _Pragma("unroll") for (int j = (J0); j < (J1); j++) {                                                      \
    uint32_t fp[4], fm[4];                                                                                   \
    _Pragma("unroll") for (int i = 0; i < 4; i++) {                                                          \
      const float e0 = E[8 * j + 2 * i], e1 = E[8 * j + 2 * i + 1], r = E[16 + 4 * j + i] * S[2 + (i & 1)];  \
      const uint32_t e2 = pack2(e0, e1);                                                                     \
      fp[i] = bmul2(e2, pack2(S[i & 1], S[i & 1]));                                                          \
      fm[i] = bmul2(e2, pack2(r, r));                                                                        \
    }                                                                                                        \
    stsm4(sb + SM_PHI + (SLOT) * 16384 + sw128 + (((2 * j + hi16) ^ x128) << 4), fp[0], fp[1], fp[2], fp[3]); \
    stsm4(sb + SM_PHI + (SLOT) * 16384 + sw128 + (((4 + 2 * j + hi16) ^ x128) << 4), fm[0], fm[1], fm[2], fm[3]); \
  }
#define KV_MMA(R)                                                                                            \
  do {                                                                                                       \
    mbar_wait(bar + B_PHI + 8 * (R), 0);                                                                     \
    wg_fence();                                                                                              \
    const uint32_t hA_ = fresh_hi<H128>(P.zA), hB_ = fresh_hi<H64>(P.zB);                                    \
    _Pragma("unroll") for (int k = 0; k < 8; k++) {                                                          \
      const uint32_t vs = SM_V + (k >> 2) * 4096 + (k & 3) * 1024;                                           \
      wgmma_n40_ss_ta1_tb1(kz, mkdesch(sb + SM_PHI + k * 2048, 16, hA_, wg * 1024),                       \
                           mkdesch(sb + vs, SM_SDT + (k & 1) * 1024 + (k >> 1) * 16 - vs, hB_, wg * (512u - (512u << 16))), k); \
    }                                                                                                        \
    wg_commit();                                                                                             \
  } while (0)
#define QKV(J, R) do { KV_MMA(R); QSTEP_A(J, Q_OFF16(J), 1); wg_wait<2>(); QREL((J) - 1); SCHED_FENCE(); } while (0)
#define KV_SEND(R)                                                                                           \
  do {                                                                                                       \
    reg_fence<20>(kz);                                                                                       \
    if (lane == 0) mbar_arrive(bar + B_KVST + 8 * (R));                                                      \
    const uint32_t slot = ((hg * 2 + (R)) * 16 + warp * 2) * 16 + mb;                                        \
    _Pragma("unroll") for (int u = 0; u < 2; u++)                                                            \
      st_rlx128(g_part + (slot + u * 16) * 32 + lane, mark(pack2(kz[2 * u], kz[2 * u + 1]), tag & 1), pack2(kz[2 * u + 4], kz[2 * u + 5]), \
                pack2(kz[2 * u + 8], kz[2 * u + 9]), pack2(kz[2 * u + 12], kz[2 * u + 13]));                 \
    if (t < 2) st_rlx(g_zpart + (slot + t * 16) * 8 + g, mark(__float_as_uint(t ? kz[18] : kz[16]), tag & 1)); \
    if (lane < 2) red_inc(XC1(hg, R) + warp * 2 + lane);                                                          \
  } while (0)
#define K_PUB(R) do { fence_async_smem(); __syncwarp(); if (lane == 0) mbar_arrive(bar + B_PHI + 8 * (R)); } while (0)
#define S_PIN(S) SCHED_PIN(S[0] + S[1] + S[2] + S[3])
      k_exp(p, c0, c1, ea, sa);
      S_PIN(sa);
      QNEXT(1);
      K_NORM(sa);
      k_exp<0, 4>(p + 16, c0, c1, eb, sc);
      mbar_wait(bar + B_FFN, 0);
      K_STORE_(0, ea, sa, 0, 1);
      S_PIN(sc);
      QNEXT(2);
      K_STORE_(0, ea, sa, 1, 2);
      k_exp<4, 8>(p + 16, c0, c1, eb, sc);
      K_NORM(sc);
      S_PIN(sc);
      QNEXT(3);
      K_STORE(1, eb, sc);
      K_PUB(0);
      k_exp<0, 4>(p + 32, c0, c1, ea, sa);
      S_PIN(sa);
      QKV(4, 0);
      k_exp<4, 8>(p + 32, c0, c1, ea, sa);
      K_NORM(sa);
      S_PIN(sa);
      wg_wait<1>();
      KV_SEND(0);
      QNEXT(5);
      k_exp(p + 48, c0, c1, eb, sc);
      S_PIN(sc);
      QNEXT(6);
      K_NORM(sc);
      mbar_wait(bar + B_KVST, 0);
      V_STORE(1);
      K_STORE(0, ea, sa);
      QNEXT(7);
      K_STORE(1, eb, sc);
      K_PUB(1);
      QKV(8, 1);
      QNEXT(9);
      KV_SEND(1);
    }
    PROFC(3);
#pragma unroll 1
    for (int j = 10; j < 15; j++) QPLAIN(j);
    mbar_wait(bar + B_CSQ, 0);
    QWAIT(15);
    if (wg == 1) bar_sync(6, 256);
    wg_fence();
    wgmma_n128_rs_ta0_tb1(q, fa0, fa1, 0u, 0u, mkdesc(sb + SM_CST + 2048, 512, 0, 1), 1);
    QMMA(15, Q_AOFF(15) / 16, 1);
    wg_commit();
    if (wg == 0) asm volatile("bar.arrive 6, 256;" ::: "memory");
    wg_wait<1>();
    QREL(14);
    wg_wait<0>();
    QREL(15);
    reg_fence<64>(q);
    PROFC(5);
    float yp[4];
    const uint32_t par = tag & 1;
    uint4* ofr = g_ofr + (mb * 16 + hg * 2) * 1024 + (warp * 16 + g) * 8;
#define O_MMA(H, F, N)                                                                                       \
  do {                                                                                                       \
    wg_fence();                                                                                              \
    const uint32_t hB_ = fresh_hi<H64>(P.zB);                                                                \
    _Pragma("unroll") for (int k = 0; k < 4; k++) {                                                          \
      const uint32_t ks = SM_V + (H) * 4096 + k * 1024;                                                      \
      wgmma_n40_rs_ta0_tb1(N + 20 * (k >> 1), F[4 * k], F[4 * k + 1], F[4 * k + 2], F[4 * k + 3],            \
                           mkdesch(sb + ks, SM_ZT + (H) * 1024 + k * 16 - ks, hB_), k & 1);                \
    }                                                                                                        \
    wg_commit();                                                                                             \
  } while (0)
#define O_FIN(H, N, o)                                                                                        \
  do {                                                                                                       \
    reg_fence<40>(N);                                                                                        \
    const float *np = N, *nm = N + 20;                                                                       \
    const float d0 = rcp(fmaf(np[16], nm[17], fmaf(nm[16], np[17], 1e-6f * np[17] * nm[17])));               \
    const float d1 = rcp(fmaf(np[18], nm[19], fmaf(nm[18], np[19], 1e-6f * np[19] * nm[19])));               \
    const float bp0 = nm[17] * d0, bm0 = np[17] * d0, bp1 = nm[19] * d1, bm1 = np[19] * d1;                  \
    _Pragma("unroll") for (int j = 0; j < 4; j++) {                                                          \
      o[2 * j] = pack2(fmaf(np[4 * j], bp0, nm[4 * j] * bm0), fmaf(np[4 * j + 1], bp0, nm[4 * j + 1] * bm0)); \
      o[2 * j + 1] = pack2(fmaf(np[4 * j + 2], bp1, nm[4 * j + 2] * bm1), fmaf(np[4 * j + 3], bp1, nm[4 * j + 3] * bm1)); \
    }                                                                                                        \
  } while (0)
#define O_STG(H, o)                                                                                          \
  _Pragma("unroll") for (int u = 0; u < 2; u++) {                                                            \
    uint32_t v_[4];                                                                                          \
    _Pragma("unroll") for (int j = 0; j < 4; j++) v_[j] = lop_select(o[2 * j + u], parm, vword == j);        \
    st_rlx128(ofr + ((H) >> 1) * 1024 + u * 64 + ((((H) & 1) * 4 + t) ^ g), v_[0], v_[1], v_[2], v_[3]);     \
  }
    uint32_t gf[32], ao[16];
    const uint32_t parm = 0u - par, vword = ((t ^ g) & 1) == (g >> 2) ? g & 3 : 4;
    const float rh0 = 0.5f * st0.y, rh1 = 0.5f * st1.y, mh0 = st0.x * rh0, mh1 = st1.x * rh1;
#define GATE_LD(J) ldsm4(sb + ((J) >> 2 ? SM_X1 : SM_X0) + sw128 + (((((J) & 3) * 2 + hi16) ^ x128) << 4), gf[4 * (J)], gf[4 * (J) + 1], gf[4 * (J) + 2], gf[4 * (J) + 3])
#define GATE(I0, I1)                                                                                         \
  _Pragma("unroll") for (int i = (I0); i < (I1); i++) {                                                      \
    const float rs = (i & 1) ? rh1 : rh0, mh = (i & 1) ? mh1 : mh0;                                          \
    const float h0 = fmaf(bf_lo(gf[i]), rs, mh), h1 = fmaf(bf_hi(gf[i]), rs, mh);                            \
    gf[i] = pack2(fmaf(h0, tanh_approx(h0), h0), fmaf(h1, tanh_approx(h1), h1));                             \
  }
#define GATE_PIN(I0, I1) do { uint32_t o_ = 0; _Pragma("unroll") for (int i = (I0); i < (I1); i++) o_ |= gf[i]; SCHED_PIN(__uint_as_float(o_)); } while (0)
    {
      float p[64], na[40], nb[40];
      uint32_t fa[16], fb[16];
      {
        uint32_t nq[4] = {0u, 0u, 0u, 0u};
        PHI_PROJ(p, q, 0, 2);
        SCHED_FENCE();
        PHI_PROJ(p, q, 2, 4);
        const bool unsafe = softmax_unsafe(nq, c0 * c0 * wn, c1 * c1 * wn);
        wg_wait<0>();
        reg_fence<64>(p);
        PROFC(24);
        if (__builtin_expect(unsafe, 0)) softmax_shift(p, c0, c1);
      }
      float dn[32];
#define DN_PART(A, B)                                                                                        \
  do {                                                                                                       \
    wg_fence();                                                                                              \
    const uint32_t hA_ = fresh_hi<H128>(P.zA), hB_ = fresh_hi<HNS>(P.zB);                                    \
    _Pragma("unroll") for (int i = (A); i < (B); i++)                                                        \
      wgmma_n8_ss_ta1_tb1(dn + 4 * (i >> 1), mkdesch(sb + (i >> 3) * Q_STAGE + (i & 7) * 2048, 16, hA_, wg * (2 * Q_STAGE / 16)), \
                          mkdesch(sb + SM_HT + (i & 1) * 256, 128, hB_), i & 1);                           \
  } while (0)
#define F_PIN(F, A, B) do { uint32_t o_ = 0; _Pragma("unroll") for (int i = (A); i < (B); i++) o_ |= F[8 + i]; SCHED_PIN(__uint_as_float(o_)); } while (0)
#define RMMA(J, A, ACCUM)                                                                                    \
  do {                                                                                                       \
    wg_fence();                                                                                              \
    const uint32_t hB_ = fresh_hi<H128>(P.zB);                                                               \
    _Pragma("unroll") for (int k = 0; k < 4; k++)                                                            \
      wgmma_n128_rs_ta0_tb1(q, (A)[4 * k], (A)[4 * k + 1], (A)[4 * k + 2], (A)[4 * k + 3],                   \
                            mkdesch(sb + 16384 + k * 2048, 8192, hB_, ((J) & 3) * (Q_STAGE / 16)), k ? 1 : (ACCUM)); \
    wg_commit();                                                                                             \
  } while (0)
#define RSTEP(J, A, ACCUM) do { QWAIT(J); RMMA(J, A, ACCUM); } while (0)
      PROFC(4);
      q_exp(p, c0, c1, fa);
      q_exp(p + 16, c0, c1, fb);
      F_PIN(fb, 0, 8);
      mbar_wait(bar + B_TILE, 0);
      O_MMA(0, fa, na);
      O_MMA(1, fb, nb);
      PROFC(25);
      wg_wait<1>();
      O_FIN(0, na, ao);
      O_STG(0, ao);
      wg_wait<0>();
      O_FIN(1, nb, (ao + 8));
      O_STG(1, (ao + 8));
      PROFC(28);
      mbar_wait(bar + B_H, 0);
      mbar_wait(bar + B_DN, 0);
      PROFC(45);
      DN_PART(0, 16);
      wg_commit();
      wg_wait<0>();
      reg_fence<32>(dn);
#pragma unroll
      for (int i = 0; i < 4; i++) yp[i] = t & 2 ? (t & 1 ? dn[24 + 2 * i] : dn[16 + 2 * i]) : (t & 1 ? dn[8 + 2 * i] : dn[2 * i]);
      RSTEP(16, ao, 0);
      SCHED_FENCE();
      q_exp(p + 32, c0, c1, fa);
      F_PIN(fa, 0, 8);
      if (lane == 0) mbar_arrive(bar + B_DND);
      q_exp(p + 48, c0, c1, fb);
      F_PIN(fb, 0, 8);
      wg_wait<0>();
      QREL(16);
      PROFC(29);
      mbar_wait(bar + B_TILE + 8, 0);
      PROFC(23);
      if (bid < NFFN) {
        float* y = g_y[par ^ 1][bid & 7] + wg * 512 + t * 128 + w * 16 + g;
#pragma unroll
        for (int i = 0; i < 4; i++) red1(y + (i >> 1) * 64 + (i & 1) * 8, yp[i]);
      }
      SCHED_FENCE();
      O_MMA(2, fa, na);
      O_MMA(3, fb, nb);
      __syncwarp();
      if (lane == 0) mbar_arrive(bar + B_YD);
      wg_wait<1>();
      O_FIN(2, na, ao);
      O_STG(2, ao);
      wg_wait<0>();
      O_FIN(3, nb, (ao + 8));
      O_STG(3, (ao + 8));
      PROFC(6);
    }
    RSTEP(17, ao, 1);
    SCHED_FENCE();
    GATE_LD(0); GATE_LD(1);
    GATE(0, 4);
    GATE_PIN(0, 4);
#define GSTEP(J, I) do { QNEXT(J); if ((I) < 7) GATE_LD(((I) + 1) & 7); GATE(4 * (I), 4 * (I) + 4); GATE_PIN(4 * (I), 4 * (I) + 4); } while (0)
    GSTEP(18, 1); GSTEP(19, 2); GSTEP(20, 3); GSTEP(21, 4); GSTEP(22, 5); GSTEP(23, 6); GSTEP(24, 7);
#pragma unroll 1
    for (int j = 25; j < 32 - TAILN; j++) QPLAIN(j);
    if (wg == 1) bar_sync(6, 256);
#pragma unroll 1
    for (int j = 32 - TAILN; j < 32; j++) QSTEP_A(j, (j & 3) * (Q_STAGE / 16), 1);
    if (wg == 0) asm volatile("bar.arrive 6, 256;" ::: "memory");
    mbar_wait(bar + B_UPD, 0);
    {
      const int sel = __float_as_int(lds32(sb + SM_UPD + 256)) - (wg * 64 + w * 16 + g);
      if (sel == 0 || sel == 8) {
#pragma unroll
        for (int j = 0; j < 16; j++) {
          const uint32_t u = __float_as_uint(lds32(sb + SM_UPD + j * 16 + t * 4));
          if (sel) gf[2 * j + 1] = u; else gf[2 * j] = u;
        }
      }
      __syncwarp();
      uint32_t xf[32];
#pragma unroll
      for (int j = 0; j < 8; j++)
        ldsm4(sb + (j >> 2 ? SM_X1 : SM_X0) + sw128 + ((((j & 3) * 2 + hi16) ^ x128) << 4), xf[4 * j], xf[4 * j + 1], xf[4 * j + 2], xf[4 * j + 3]);
      wg_wait<0>();
      reg_fence<64>(q);
      PROFC(8);
#pragma unroll
      for (int j = 0; j < 8; j++) {
        uint32_t o[4];
#pragma unroll
        for (int i = 0; i < 4; i++) o[i] = badd2(xf[4 * j + i], bmul2(pack2(q[8 * j + 2 * i], q[8 * j + 2 * i + 1]), gf[4 * j + i]));
        stsm4(sb + (j >> 2 ? SM_X1 : SM_X0) + sw128 + ((((j & 3) * 2 + hi16) ^ x128) << 4), o[0], o[1], o[2], o[3]);
        if ((j & 3) == 3) {
          fence_async_smem();
          __syncwarp();
          if (elect_one()) {
            tma_store2d(&mOut, sb + (j >> 2 ? SM_X1 : SM_X0) + warp * 2048, hg * 128 + (j >> 2) * 64, mb * 128 + warp * 16);
            bulk_commit();
          }
          __syncwarp();
        }
      }
    }
    bulk_wait_read0();
    if (warp == 7 && lane == 0) { PROF(9); PROFT(33); PROF_DUMP; }
  }
}

typedef CUresult (*EncodeFn)(CUtensorMap*, CUtensorMapDataType, cuuint32_t, void*, const cuuint64_t*, const cuuint64_t*, const cuuint32_t*,
                             const cuuint32_t*, CUtensorMapInterleave, CUtensorMapSwizzle, CUtensorMapL2promotion, CUtensorMapFloatOOBfill);

CUtensorMap make_map(EncodeFn enc, const void* ptr, int rank, const cuuint64_t* dims, const cuuint64_t* strides, const cuuint32_t* box, CUtensorMapSwizzle sw) {
  CUtensorMap m;
  const cuuint32_t es[5] = {1, 1, 1, 1, 1};
  enc(&m, CU_TENSOR_MAP_DATA_TYPE_BFLOAT16, rank, (void*)ptr, dims, strides, box, es, CU_TENSOR_MAP_INTERLEAVE_NONE, sw,
      CU_TENSOR_MAP_L2_PROMOTION_L2_128B, CU_TENSOR_MAP_FLOAT_OOB_FILL_NONE);
  return m;
}

}

extern "C" void kernel_launch(void* const* d_in, const int* in_sizes, int n_in, void* d_out, int out_size) {
  static EncodeFn enc = nullptr;
  static int by_sm = 0;
  if (!enc) {
    void* fn = nullptr;
    cudaDriverEntryPointQueryResult qr;
    cudaGetDriverEntryPoint("cuTensorMapEncodeTiled", &fn, cudaEnableDefault, &qr);
    enc = (EncodeFn)fn;
    cudaFuncSetAttribute(fused_kernel<false>, cudaFuncAttributeMaxDynamicSharedMemorySize, SM_TOTAL);
    cudaFuncSetAttribute(fused_kernel<true>, cudaFuncAttributeMaxDynamicSharedMemorySize, SM_TOTAL);
    int dev = 0, sms = 0;
    cudaGetDevice(&dev);
    cudaDeviceGetAttribute(&sms, cudaDevAttrMultiProcessorCount, dev);
    by_sm = BY_SM && sms == NCTA + NSPARE;
  }
  Params P;
  P.zA = P.zB = 0;
  P.x = (const __nv_bfloat16*)d_in[0];
  P.wqkv = (const __nv_bfloat16*)d_in[1];
  const void* wphi = d_in[2];
  P.wo = (const __nv_bfloat16*)d_in[3];
  P.w_r = (const __nv_bfloat16*)d_in[5];
  const void *w_gate = d_in[6], *w_up = d_in[7];
  P.w_down = (const __nv_bfloat16*)d_in[8];

  const cuuint64_t dX[2] = {DM, SEQ}, sX[1] = {DM * 2};
  const cuuint32_t b128[2] = {64, 128};
  const cuuint64_t dW[4] = {64, DM, 16, 3}, sW[3] = {3 * DM * 2, 128, DM * 2};
  const cuuint32_t bKV[4] = {64, 64, 2, 2}, bQ[4] = {64, 64, 2, 1};
  const cuuint64_t dO[3] = {64, DM, 16}, sO[2] = {DM * 2, 128};
  const cuuint32_t bO[3] = {64, 64, 2};
  const cuuint64_t dP[2] = {32, 1024}, sP[1] = {64};
  const cuuint32_t bP[2] = {32, 128};
  CUtensorMap mX = make_map(enc, P.x, 2, dX, sX, b128, CU_TENSOR_MAP_SWIZZLE_128B);
  CUtensorMap mWkv = make_map(enc, P.wqkv, 4, dW, sW, bKV, CU_TENSOR_MAP_SWIZZLE_128B);
  CUtensorMap mWq = make_map(enc, P.wqkv, 4, dW, sW, bQ, CU_TENSOR_MAP_SWIZZLE_128B);
  CUtensorMap mWo = make_map(enc, P.wo, 3, dO, sO, bO, CU_TENSOR_MAP_SWIZZLE_128B);
  CUtensorMap mPhi = make_map(enc, wphi, 2, dP, sP, bP, CU_TENSOR_MAP_SWIZZLE_64B);
  const cuuint64_t dWp[5] = {DM, 2, 4, 4, DM / 32}, sWp[4] = {DM * 2, 8 * DM * 2, 2 * DM * 2, 32 * DM * 2};
  const cuuint32_t bWp[5] = {64, 2, 4, 4, 2};
  CUtensorMap mWp = make_map(enc, P.wo, 5, dWp, sWp, bWp, CU_TENSOR_MAP_SWIZZLE_128B);
  const cuuint32_t b16[2] = {64, 16};
  CUtensorMap mOut = make_map(enc, d_out, 2, dX, sX, b16, CU_TENSOR_MAP_SWIZZLE_128B);
  const cuuint64_t dWc[2] = {3 * DM, DM}, sWc[1] = {3 * DM * 2}, dG[2] = {FF, DM}, sG[1] = {FF * 2}, dD[3] = {64, FF, 16};
  const cuuint32_t b32[2] = {32, 32}, bD[3] = {64, 32, 4};
  CUtensorMap mWc = make_map(enc, P.wqkv, 2, dWc, sWc, b32, CU_TENSOR_MAP_SWIZZLE_NONE);
  CUtensorMap mG = make_map(enc, w_gate, 2, dG, sG, b32, CU_TENSOR_MAP_SWIZZLE_NONE);
  CUtensorMap mU = make_map(enc, w_up, 2, dG, sG, b32, CU_TENSOR_MAP_SWIZZLE_NONE);
  CUtensorMap mD = make_map(enc, P.w_down, 3, dD, sO, bD, CU_TENSOR_MAP_SWIZZLE_128B);
  const cuuint64_t dXs[3] = {256, SEQ, 4}, sXs[2] = {DM * 2, 512};
  const cuuint32_t bXs[3] = {256, 16, 2};
  CUtensorMap mXs = make_map(enc, P.x, 3, dXs, sXs, bXs, CU_TENSOR_MAP_SWIZZLE_NONE);
  const cuuint64_t dG2[4] = {64, DM, FF / 64, 1}, sG2[3] = {FF * 2, 128, (cuuint64_t)FF * DM * 2};
  CUtensorMap mG2 = make_map(enc, w_gate, 4, dG2, sG2, bQ, CU_TENSOR_MAP_SWIZZLE_128B);
  CUtensorMap mU2 = make_map(enc, w_up, 4, dG2, sG2, bQ, CU_TENSOR_MAP_SWIZZLE_128B);
  (by_sm ? fused_kernel<true> : fused_kernel<false>)<<<NCTA + NSPARE, 384, SM_TOTAL, cudaStreamPerThread>>>(P, mX, mWkv, mWq, mWo, mPhi, mWp, mOut, mWc, mG, mU, mD, mXs,
                                                                                                           mG2, mU2);
}
```

```cpp
#include <cuda_runtime.h>
#include <cuda_bf16.h>
#include <cuda.h>
#include <stdint.h>

namespace {

constexpr int SEQ = 2048, DM = 1024, FF = 3584;
constexpr int NCTA = 128;
constexpr int NSPARE = 4;
constexpr int NFFN = FF / 32;
#define GN 6
#define G8 2
constexpr int GROWS = (3 * GN + G8) * 32;
#define TAILN 2
#define XS_EARLY 1
#define PF_FIRST 2
#define PF_W 5
#define PFD 80
#define BY_SM 1
#define PTAB 0x73216540u
#define REG_C 224
#define REG_H 56
#define SP_DELAY 2000
#define XSTR 288
#define AM_NS 100
constexpr bool FFN_OFF = false;

static_assert(2 * REG_C + REG_H <= 3 * 168, "the register pool of the CTA is 384 x 168");

__device__ uint32_t g_epoch[(NCTA + NSPARE) * 32];
__device__ unsigned long long g_stat[SEQ];
__device__ __align__(128) unsigned long long g_best[NCTA];
__device__ __align__(16) float g_y[2][8][DM];
__device__ __align__(128) uint32_t g_ycnt[64];
__device__ __align__(1024) uint32_t g_xcnt[32 * XSTR];
#define XC1(HG, R) (g_xcnt + ((HG) * 2 + (R)) * XSTR)
#define XC2(HG, R) (g_xcnt + (16 + (HG) * 2 + (R)) * XSTR)
__device__ __align__(128) uint4 g_res[2][32 * 256];
__device__ __align__(16) float g_cs[5 * DM];
__device__ __align__(128) float g_gp[2 * FF];
__device__ uint4 g_part[8 * 2 * 16 * 16 * 32];
__device__ __align__(16) float g_zpart[8 * 2 * 16 * 16 * 8];
__device__ __align__(128) uint4 g_zres[2][32 * 64];
__device__ __align__(1024) uint4 g_ofr[16 * 16 * 1024];
#define PROF(i)
#define PROFT(i)
#define PROFC(i)
#define PROF_DUMP
#define PW0(J)
#define PW1(J)

constexpr uint32_t KV_STAGE = 49152, Q_STAGE = 32768;
constexpr uint32_t SM_V = 147456;
constexpr uint32_t SM_PHI = 163840;
constexpr uint32_t SM_XST = 147456;
constexpr uint32_t SM_FST = 172032;
constexpr uint32_t SM_PST0 = 196608, SM_PST1 = SM_PHI + 8192;
constexpr uint32_t SM_X0 = 131072, SM_X1 = SM_PHI + 16384;
constexpr uint32_t SM_WPHI = 204800;
constexpr uint32_t SM_ZT = 212992;
constexpr uint32_t SM_SDT = 217088;
constexpr uint32_t SM_CST = 219136;
constexpr uint32_t SM_HT = 222720;
constexpr uint32_t SM_STAT = 223232;
constexpr uint32_t SM_XSEL = 224256;
constexpr uint32_t SM_RED = 228352;
constexpr uint32_t SM_ROWS = SM_RED + 832;
constexpr uint32_t SM_GRED = SM_XSEL + 3072;
static_assert(GROWS <= 768, "xsel area");
constexpr uint32_t SM_UPD = 229632;
constexpr uint32_t SM_BAR = 230016;
constexpr uint32_t SM_PROF = 230464;
constexpr uint32_t SM_SINK = 231104;
constexpr uint32_t SM_TOTAL = 231616;
constexpr uint32_t SB = 1024;
constexpr uint32_t B_FULLKV = 0  , B_FST = 24  , B_XST = 104  , B_WPHI = 120, B_CS = 128, B_CSQ = 136, B_UPD = 144,
                   B_H = 152, B_DN = 160, B_XS = 168, B_TILE = 176  , B_RES = 192  , B_PART = 208  , B_AIN = 224  ,
                   B_FULLQ = 288  ,
                   B_FFN = 320,
                   B_EMPTYKV = 328  , B_EMPTYQ = 352  , B_KVST = 384  , B_YD = 400, B_PHI = 408  , B_DND = 424, B_END = 432;

__device__ __forceinline__ uint32_t smem_u32(const void* p) { return (uint32_t)__cvta_generic_to_shared(p); }
__device__ __forceinline__ void mbar_init(uint32_t bar, uint32_t cnt) { asm volatile("mbarrier.init.shared::cta.b64 [%0], %1;" ::"r"(bar), "r"(cnt) : "memory"); }
__device__ __forceinline__ void mbar_expect_tx(uint32_t bar, uint32_t bytes) { asm volatile("mbarrier.arrive.expect_tx.shared::cta.b64 _, [%0], %1;" ::"r"(bar), "r"(bytes) : "memory"); }
__device__ __forceinline__ void mbar_arrive2(uint32_t bar) { asm volatile("mbarrier.arrive.shared::cta.b64 _, [%0], 2;" ::"r"(bar) : "memory"); }
__device__ __forceinline__ void mbar_arrive(uint32_t bar) { asm volatile("mbarrier.arrive.shared::cta.b64 _, [%0];" ::"r"(bar) : "memory"); }
__device__ __forceinline__ void mbar_wait(uint32_t bar, uint32_t parity) {
  asm volatile("{\n.reg .pred p;\nLW:\nmbarrier.try_wait.parity.shared::cta.b64 p, [%0], %1;\n@!p bra LW;\n}" ::"r"(bar), "r"(parity) : "memory");
}
__device__ __forceinline__ bool mbar_test(uint32_t bar, uint32_t parity) {
  uint32_t ok;
  asm volatile("{\n.reg .pred p;\nmbarrier.test_wait.parity.shared::cta.b64 p, [%1], %2;\nselp.u32 %0, 1, 0, p;\n}" : "=r"(ok) : "r"(bar), "r"(parity) : "memory");
  return ok;
}
__device__ __forceinline__ int lane_id() { int l; asm volatile("mov.u32 %0, %%laneid;" : "=r"(l)); return l; }
template <int C> __device__ __forceinline__ void sched_fence_(int zero) {
  asm volatile("{\n.reg .pred p;\nsetp.eq.s32 p, %0, %1;\n@p trap;\n}" ::"r"(zero), "n"(C) : "memory");
}
#define SCHED_FENCE() sched_fence_<1000 + __COUNTER__>(zero)
#define SCHED_PIN(V) sched_fence_<1000 + __COUNTER__>(zero & __float_as_int(V))
__device__ __forceinline__ bool elect_one() {
  uint32_t p; asm volatile("{ .reg .pred P; elect.sync _|P, 0xffffffff; selp.u32 %0, 1, 0, P; }" : "=r"(p)); return p;
}
__device__ __forceinline__ void tma2d(uint32_t dst, const CUtensorMap* m, int x, int y, uint32_t bar) {
  asm volatile("cp.async.bulk.tensor.2d.shared::cluster.global.mbarrier::complete_tx::bytes [%0], [%1, {%3, %4}], [%2];" ::"r"(dst), "l"(m), "r"(bar), "r"(x), "r"(y) : "memory");
}
__device__ __forceinline__ void tma3d(uint32_t dst, const CUtensorMap* m, int x, int y, int z, uint32_t bar) {
  asm volatile("cp.async.bulk.tensor.3d.shared::cluster.global.mbarrier::complete_tx::bytes [%0], [%1, {%3, %4, %5}], [%2];" ::"r"(dst), "l"(m), "r"(bar), "r"(x), "r"(y), "r"(z) : "memory");
}
__device__ __forceinline__ void tma4d(uint32_t dst, const CUtensorMap* m, int x, int y, int z, int w, uint32_t bar) {
  asm volatile("cp.async.bulk.tensor.4d.shared::cluster.global.mbarrier::complete_tx::bytes [%0], [%1, {%3, %4, %5, %6}], [%2];" ::"r"(dst), "l"(m), "r"(bar), "r"(x), "r"(y), "r"(z), "r"(w) : "memory");
}
__device__ __forceinline__ void tma5d(uint32_t dst, const CUtensorMap* m, int x, int v, uint32_t bar) {
  asm volatile("cp.async.bulk.tensor.5d.shared::cluster.global.mbarrier::complete_tx::bytes [%0], [%1, {%3, %5, %5, %5, %4}], [%2];" ::"r"(dst), "l"(m), "r"(bar), "r"(x), "r"(v), "r"(0) : "memory");
}
__device__ __forceinline__ void tma_store2d(const CUtensorMap* m, uint32_t src, int x, int y) {
  asm volatile("cp.async.bulk.tensor.2d.global.shared::cta.bulk_group [%0, {%2, %3}], [%1];" ::"l"(m), "r"(src), "r"(x), "r"(y) : "memory");
}
__device__ __forceinline__ void bulk_load(uint32_t dst, const void* src, uint32_t bytes, uint32_t bar) {
  asm volatile("cp.async.bulk.shared::cluster.global.mbarrier::complete_tx::bytes [%0], [%1], %2, [%3];" ::"r"(dst), "l"(src), "r"(bytes), "r"(bar) : "memory");
}
__device__ __forceinline__ void bulk_commit() { asm volatile("cp.async.bulk.commit_group;" ::: "memory"); }
__device__ __forceinline__ void bulk_wait_read0() { asm volatile("cp.async.bulk.wait_group.read 0;" ::: "memory"); }
__device__ __forceinline__ void prefetch_l2(const void* p) { asm volatile("prefetch.global.L2 [%0];" ::"l"(p) : "memory"); }
__device__ __forceinline__ void touch_l2(const void* p, int lane) { asm volatile("cp.async.cg.shared.global.L2::128B [%0], [%1], 16;" ::"r"(SB + SM_SINK + lane * 16), "l"(p) : "memory"); }
__device__ __forceinline__ void cp_async16(uint32_t dst, const void* src) { asm volatile("cp.async.cg.shared.global [%0], [%1], 16;" ::"r"(dst), "l"(src) : "memory"); }
__device__ __forceinline__ void prefetch_map(const CUtensorMap* m) { asm volatile("prefetch.tensormap [%0];" ::"l"(m) : "memory"); }
__device__ __forceinline__ void fence_async_smem() { asm volatile("fence.proxy.async.shared::cta;" ::: "memory"); }
__device__ __forceinline__ void fence_async_global() { asm volatile("fence.proxy.async.global;" ::: "memory"); }
__device__ __forceinline__ void bar_sync(int id, int n) { asm volatile("bar.sync %0, %1;" ::"r"(id), "r"(n) : "memory"); }
__device__ __forceinline__ void wg_fence() { asm volatile("wgmma.fence.sync.aligned;" ::: "memory"); }
__device__ __forceinline__ void wg_commit() { asm volatile("wgmma.commit_group.sync.aligned;" ::: "memory"); }
template <int N> __device__ __forceinline__ void wg_wait() { asm volatile("wgmma.wait_group.sync.aligned %0;" ::"n"(N) : "memory"); }
template <int N> __device__ __forceinline__ void reg_fence(uint32_t* r) {
#pragma unroll
  for (int i = 0; i < N; i++) asm volatile("" : "+r"(r[i])::"memory");
}
template <int N> __device__ __forceinline__ void reg_fence(float* r) {
#pragma unroll
  for (int i = 0; i < N; i++) asm volatile("" : "+f"(r[i])::"memory");
}
__device__ __forceinline__ uint64_t mkdesc(uint32_t addr, uint32_t lbo, uint32_t sbo, uint32_t swz, uint32_t dyn = 0) {
  const uint32_t lo = ((addr >> 4) | ((lbo >> 4) << 16)) + dyn;
  const uint32_t hi = (sbo >> 4) | (swz << 30);
  uint64_t d;
  asm("mov.b64 %0, {%1, %2};" : "=l"(d) : "r"(lo), "r"(hi));
  return d;
}
template <uint32_t C> __device__ __forceinline__ uint32_t fresh_hi(uint32_t zero) { uint32_t h; asm volatile("or.b32 %0, %1, %2;" : "=r"(h) : "r"(zero), "n"(C)); return h; }
constexpr uint32_t H128 = (1024u >> 4) | (1u << 30), H64 = (512u >> 4) | (2u << 30), HNS = 128u >> 4;
__device__ __forceinline__ uint64_t mkdesch(uint32_t addr, uint32_t lbo, uint32_t hi, uint32_t dyn = 0) {
  const uint32_t lo = ((addr >> 4) | ((lbo >> 4) << 16)) + dyn;
  uint64_t d;
  asm("mov.b64 %0, {%1, %2};" : "=l"(d) : "r"(lo), "r"(hi));
  return d;
}
__device__ __forceinline__ void stsm4(uint32_t addr, uint32_t a, uint32_t b, uint32_t c, uint32_t d) {
  asm volatile("stmatrix.sync.aligned.m8n8.x4.shared.b16 [%0], {%1, %2, %3, %4};" ::"r"(addr), "r"(a), "r"(b), "r"(c), "r"(d) : "memory");
}
__device__ __forceinline__ void ldsm4(uint32_t addr, uint32_t& a, uint32_t& b, uint32_t& c, uint32_t& d) {
  asm volatile("ldmatrix.sync.aligned.m8n8.x4.shared.b16 {%0, %1, %2, %3}, [%4];" : "=r"(a), "=r"(b), "=r"(c), "=r"(d) : "r"(addr) : "memory");
}
__device__ __forceinline__ uint32_t pack2(float lo, float hi) { uint32_t r; asm("cvt.rn.bf16x2.f32 %0, %1, %2;" : "=r"(r) : "f"(hi), "f"(lo)); return r; }
__device__ __forceinline__ uint32_t bsub2(uint32_t a, uint32_t b) { uint32_t r; asm("sub.rn.bf16x2 %0, %1, %2;" : "=r"(r) : "r"(a), "r"(b)); return r; }
__device__ __forceinline__ uint32_t badd2(uint32_t a, uint32_t b) { uint32_t r; asm("add.rn.bf16x2 %0, %1, %2;" : "=r"(r) : "r"(a), "r"(b)); return r; }
__device__ __forceinline__ uint32_t bmul2(uint32_t a, uint32_t b) { uint32_t r; asm("mul.rn.bf16x2 %0, %1, %2;" : "=r"(r) : "r"(a), "r"(b)); return r; }
__device__ __forceinline__ float bf_lo(uint32_t v) { return __uint_as_float(v << 16); }
__device__ __forceinline__ float bf_hi(uint32_t v) { return __uint_as_float(v & 0xffff0000u); }
__device__ __forceinline__ float bf_round(float v) { return bf_lo(pack2(v, 0.f)); }
__device__ __forceinline__ float ex2(float v) { float r; asm("ex2.approx.ftz.f32 %0, %1;" : "=f"(r) : "f"(v)); return r; }
__device__ __forceinline__ float rcp(float v) { float r; asm("rcp.approx.ftz.f32 %0, %1;" : "=f"(r) : "f"(v)); return r; }
__device__ __forceinline__ float sqrt_approx(float v) { float r; asm("sqrt.approx.f32 %0, %1;" : "=f"(r) : "f"(v)); return r; }
__device__ __forceinline__ float4 lds128(uint32_t a) { float4 v; asm volatile("ld.shared.v4.f32 {%0, %1, %2, %3}, [%4];" : "=f"(v.x), "=f"(v.y), "=f"(v.z), "=f"(v.w) : "r"(a) : "memory"); return v; }
__device__ __forceinline__ uint4 lds128u(uint32_t a) { uint4 v; asm volatile("ld.shared.v4.u32 {%0, %1, %2, %3}, [%4];" : "=r"(v.x), "=r"(v.y), "=r"(v.z), "=r"(v.w) : "r"(a) : "memory"); return v; }
__device__ __forceinline__ float2 lds64(uint32_t a) { float2 v; asm volatile("ld.shared.v2.f32 {%0, %1}, [%2];" : "=f"(v.x), "=f"(v.y) : "r"(a) : "memory"); return v; }
__device__ __forceinline__ float lds32(uint32_t a) { float v; asm volatile("ld.shared.f32 %0, [%1];" : "=f"(v) : "r"(a) : "memory"); return v; }
__device__ __forceinline__ void sts32(uint32_t a, float v) { asm volatile("st.shared.f32 [%0], %1;" ::"r"(a), "f"(v) : "memory"); }
__device__ __forceinline__ void sts64(uint32_t a, float x, float y) { asm volatile("st.shared.v2.f32 [%0], {%1, %2};" ::"r"(a), "f"(x), "f"(y) : "memory"); }
__device__ __forceinline__ void sts128(uint32_t a, float x, float y, float z, float w) { asm volatile("st.shared.v4.f32 [%0], {%1, %2, %3, %4};" ::"r"(a), "f"(x), "f"(y), "f"(z), "f"(w) : "memory"); }
__device__ __forceinline__ void sts64u(uint32_t a, uint32_t x, uint32_t y) { asm volatile("st.shared.v2.u32 [%0], {%1, %2};" ::"r"(a), "r"(x), "r"(y) : "memory"); }
__device__ __forceinline__ void sts128u(uint32_t a, uint32_t x, uint32_t y, uint32_t z, uint32_t w) { asm volatile("st.shared.v4.u32 [%0], {%1, %2, %3, %4};" ::"r"(a), "r"(x), "r"(y), "r"(z), "r"(w) : "memory"); }
__device__ __forceinline__ uint4 ldg_nc(const void* p) { uint4 v; asm volatile("ld.global.nc.L1::no_allocate.v4.u32 {%0, %1, %2, %3}, [%4];" : "=r"(v.x), "=r"(v.y), "=r"(v.z), "=r"(v.w) : "l"(p)); return v; }
__device__ __forceinline__ float4 ldg_cg4(const float* p) { float4 v; asm volatile("ld.global.cg.v4.f32 {%0, %1, %2, %3}, [%4];" : "=f"(v.x), "=f"(v.y), "=f"(v.z), "=f"(v.w) : "l"(p) : "memory"); return v; }
__device__ __forceinline__ uint32_t ld_acq(const uint32_t* p) { uint32_t v; asm volatile("ld.acquire.gpu.global.u32 %0, [%1];" : "=r"(v) : "l"(p) : "memory"); return v; }
__device__ __forceinline__ unsigned long long ld_rlx64(const unsigned long long* p) { unsigned long long v; asm volatile("ld.relaxed.gpu.global.u64 %0, [%1];" : "=l"(v) : "l"(p) : "memory"); return v; }
__device__ __forceinline__ void st_rlx64(unsigned long long* p, unsigned long long v) { asm volatile("st.relaxed.gpu.global.u64 [%0], %1;" ::"l"(p), "l"(v) : "memory"); }
__device__ __forceinline__ uint4 ld_rlx128(const void* p) {
  uint4 v;
  asm volatile("{ .reg .b128 t; .reg .b64 a, b; ld.relaxed.gpu.global.b128 t, [%4]; mov.b128 {a, b}, t; mov.b64 {%0, %1}, a; mov.b64 {%2, %3}, b; }"
               : "=r"(v.x), "=r"(v.y), "=r"(v.z), "=r"(v.w) : "l"(p) : "memory");
  return v;
}
__device__ __forceinline__ void st_rlx128(void* p, uint32_t x, uint32_t y, uint32_t z, uint32_t w) {
  asm volatile("{ .reg .b128 t; .reg .b64 a, b; mov.b64 a, {%1, %2}; mov.b64 b, {%3, %4}; mov.b128 t, {a, b}; st.relaxed.gpu.global.b128 [%0], t; }"
               ::"l"(p), "r"(x), "r"(y), "r"(z), "r"(w) : "memory");
}
__device__ __forceinline__ void st_rlx(void* p, uint32_t v) { asm volatile("st.relaxed.gpu.global.u32 [%0], %1;" ::"l"(p), "r"(v) : "memory"); }
__device__ __forceinline__ uint32_t lop_select(uint32_t a, uint32_t b, uint32_t m) { uint32_t r; asm("lop3.b32 %0, %1, %2, %3, 0xd8;" : "=r"(r) : "r"(a), "r"(b), "r"(m)); return r; }
__device__ __forceinline__ float unmark(uint32_t v) { return __uint_as_float(v & ~1u); }
__device__ __forceinline__ uint32_t mark(uint32_t v, uint32_t par) { return (v & ~1u) | par; }
__device__ __forceinline__ float tanh_approx(float v) { float r; asm("tanh.approx.f32 %0, %1;" : "=f"(r) : "f"(v)); return r; }
__device__ __forceinline__ void red1(float* p, float a) { asm volatile("red.global.add.f32 [%0], %1;" ::"l"(p), "f"(a) : "memory"); }
__device__ __forceinline__ void red_inc(uint32_t* p) { asm volatile("red.relaxed.gpu.global.add.u32 [%0], 1;" ::"l"(p) : "memory"); }
__device__ __forceinline__ void red_rel(uint32_t* p) { asm volatile("red.release.gpu.global.add.u32 [%0], 1;" ::"l"(p) : "memory"); }
constexpr int SPIN_MAX = 100000;
__device__ __forceinline__ uint32_t ld_rlx(const uint32_t* p) { uint32_t v; asm volatile("ld.relaxed.gpu.global.u32 %0, [%1];" : "=r"(v) : "l"(p) : "memory"); return v; }
template <int NS = 0> __device__ __forceinline__ void wait_hint(const uint32_t* p, uint32_t target) {
#pragma unroll 1
  for (int i = 0; i < SPIN_MAX; i++) { if ((int)(ld_rlx(p) - target) >= 0) break; if (NS) __nanosleep(NS); }
}
template <int NS> __device__ __forceinline__ void wait_cnt(const uint32_t* p, uint32_t target) {
#pragma unroll 1
  for (int i = 0; i < SPIN_MAX; i++) { if ((int)(ld_rlx(p) - target) >= 0) break; if (NS) __nanosleep(NS); }
  (void)ld_acq(p);
}
template <int NS> __device__ __forceinline__ unsigned long long wait_tag(const unsigned long long* p, uint32_t tag) {
  unsigned long long v = 0;
#pragma unroll 1
  for (int i = 0; i < SPIN_MAX; i++) { v = ld_rlx64(p); if ((uint32_t)(v >> 32) == tag) break; if (NS) __nanosleep(NS); }
  return v;
}
__device__ __forceinline__ float silu_f(float v) { return v * rcp(1.f + ex2(-1.4426950408889634f * v)); }

__device__ __forceinline__ void wgmma_n8_ss_ta1_tb0(float* d, uint64_t da, uint64_t db, bool accumulate) {
  if (accumulate) {
    asm volatile("{\n.reg .pred p;\nsetp.ne.b32 p, 1, 0;\n"
      "wgmma.mma_async.sync.aligned.m64n8k16.f32.bf16.bf16 "
      "{%0, %1, %2, %3}, "
      "%4, %5, p, 1, 1, 1, 0;\n}\n"
      : "+f"(d[0]), "+f"(d[1]), "+f"(d[2]), "+f"(d[3])
      : "l"(da), "l"(db));
  } else {
    asm volatile("{\n.reg .pred p;\nsetp.ne.b32 p, 0, 0;\n"
      "wgmma.mma_async.sync.aligned.m64n8k16.f32.bf16.bf16 "
      "{%0, %1, %2, %3}, "
      "%4, %5, p, 1, 1, 1, 0;\n}\n"
      : "=f"(d[0]), "=f"(d[1]), "=f"(d[2]), "=f"(d[3])
      : "l"(da), "l"(db));
  }
}
__device__ __forceinline__ void wgmma_n8_ss_ta1_tb1(float* d, uint64_t da, uint64_t db, bool accumulate) {
  if (accumulate) {
    asm volatile("{\n.reg .pred p;\nsetp.ne.b32 p, 1, 0;\n"
      "wgmma.mma_async.sync.aligned.m64n8k16.f32.bf16.bf16 "
      "{%0, %1, %2, %3}, "
      "%4, %5, p, 1, 1, 1, 1;\n}\n"
      : "+f"(d[0]), "+f"(d[1]), "+f"(d[2]), "+f"(d[3])
      : "l"(da), "l"(db));
  } else {
    asm volatile("{\n.reg .pred p;\nsetp.ne.b32 p, 0, 0;\n"
      "wgmma.mma_async.sync.aligned.m64n8k16.f32.bf16.bf16 "
      "{%0, %1, %2, %3}, "
      "%4, %5, p, 1, 1, 1, 1;\n}\n"
      : "=f"(d[0]), "=f"(d[1]), "=f"(d[2]), "=f"(d[3])
      : "l"(da), "l"(db));
  }
}
__device__ __forceinline__ void wgmma_n32_rs_ta0_tb1(float* d, uint32_t a0, uint32_t a1, uint32_t a2, uint32_t a3, uint64_t db, bool accumulate) {
  if (accumulate) {
    asm volatile("{\n.reg .pred p;\nsetp.ne.b32 p, 1, 0;\n"
      "wgmma.mma_async.sync.aligned.m64n32k16.f32.bf16.bf16 "
      "{%0, %1, %2, %3, %4, %5, %6, %7, %8, %9, %10, %11, %12, %13, %14, %15}, "
      "{%16, %17, %18, %19}, %20, p, 1, 1, 1;\n}\n"
      : "+f"(d[0]), "+f"(d[1]), "+f"(d[2]), "+f"(d[3]), "+f"(d[4]), "+f"(d[5]), "+f"(d[6]), "+f"(d[7]), "+f"(d[8]), "+f"(d[9]), "+f"(d[10]), "+f"(d[11]), "+f"(d[12]), "+f"(d[13]), "+f"(d[14]), "+f"(d[15])
      : "r"(a0), "r"(a1), "r"(a2), "r"(a3), "l"(db));
  } else {
    asm volatile("{\n.reg .pred p;\nsetp.ne.b32 p, 0, 0;\n"
      "wgmma.mma_async.sync.aligned.m64n32k16.f32.bf16.bf16 "
      "{%0, %1, %2, %3, %4, %5, %6, %7, %8, %9, %10, %11, %12, %13, %14, %15}, "
      "{%16, %17, %18, %19}, %20, p, 1, 1, 1;\n}\n"
      : "=f"(d[0]), "=f"(d[1]), "=f"(d[2]), "=f"(d[3]), "=f"(d[4]), "=f"(d[5]), "=f"(d[6]), "=f"(d[7]), "=f"(d[8]), "=f"(d[9]), "=f"(d[10]), "=f"(d[11]), "=f"(d[12]), "=f"(d[13]), "=f"(d[14]), "=f"(d[15])
      : "r"(a0), "r"(a1), "r"(a2), "r"(a3), "l"(db));
  }
}
__device__ __forceinline__ void wgmma_n40_rs_ta0_tb1(float* d, uint32_t a0, uint32_t a1, uint32_t a2, uint32_t a3, uint64_t db, bool accumulate) {
  if (accumulate) {
    asm volatile("{\n.reg .pred p;\nsetp.ne.b32 p, 1, 0;\n"
      "wgmma.mma_async.sync.aligned.m64n40k16.f32.bf16.bf16 "
      "{%0, %1, %2, %3, %4, %5, %6, %7, %8, %9, %10, %11, %12, %13, %14, %15, %16, %17, %18, %19}, "
      "{%20, %21, %22, %23}, %24, p, 1, 1, 1;\n}\n"
      : "+f"(d[0]), "+f"(d[1]), "+f"(d[2]), "+f"(d[3]), "+f"(d[4]), "+f"(d[5]), "+f"(d[6]), "+f"(d[7]), "+f"(d[8]), "+f"(d[9]), "+f"(d[10]), "+f"(d[11]), "+f"(d[12]), "+f"(d[13]), "+f"(d[14]), "+f"(d[15]), "+f"(d[16]), "+f"(d[17]), "+f"(d[18]), "+f"(d[19])
      : "r"(a0), "r"(a1), "r"(a2), "r"(a3), "l"(db));
  } else {
    asm volatile("{\n.reg .pred p;\nsetp.ne.b32 p, 0, 0;\n"
      "wgmma.mma_async.sync.aligned.m64n40k16.f32.bf16.bf16 "
      "{%0, %1, %2, %3, %4, %5, %6, %7, %8, %9, %10, %11, %12, %13, %14, %15, %16, %17, %18, %19}, "
      "{%20, %21, %22, %23}, %24, p, 1, 1, 1;\n}\n"
      : "=f"(d[0]), "=f"(d[1]), "=f"(d[2]), "=f"(d[3]), "=f"(d[4]), "=f"(d[5]), "=f"(d[6]), "=f"(d[7]), "=f"(d[8]), "=f"(d[9]), "=f"(d[10]), "=f"(d[11]), "=f"(d[12]), "=f"(d[13]), "=f"(d[14]), "=f"(d[15]), "=f"(d[16]), "=f"(d[17]), "=f"(d[18]), "=f"(d[19])
      : "r"(a0), "r"(a1), "r"(a2), "r"(a3), "l"(db));
  }
}
__device__ __forceinline__ void wgmma_n40_ss_ta1_tb1(float* d, uint64_t da, uint64_t db, bool accumulate) {
  if (accumulate) {
    asm volatile("{\n.reg .pred p;\nsetp.ne.b32 p, 1, 0;\n"
      "wgmma.mma_async.sync.aligned.m64n40k16.f32.bf16.bf16 "
      "{%0, %1, %2, %3, %4, %5, %6, %7, %8, %9, %10, %11, %12, %13, %14, %15, %16, %17, %18, %19}, "
      "%20, %21, p, 1, 1, 1, 1;\n}\n"
      : "+f"(d[0]), "+f"(d[1]), "+f"(d[2]), "+f"(d[3]), "+f"(d[4]), "+f"(d[5]), "+f"(d[6]), "+f"(d[7]), "+f"(d[8]), "+f"(d[9]), "+f"(d[10]), "+f"(d[11]), "+f"(d[12]), "+f"(d[13]), "+f"(d[14]), "+f"(d[15]), "+f"(d[16]), "+f"(d[17]), "+f"(d[18]), "+f"(d[19])
      : "l"(da), "l"(db));
  } else {
    asm volatile("{\n.reg .pred p;\nsetp.ne.b32 p, 0, 0;\n"
      "wgmma.mma_async.sync.aligned.m64n40k16.f32.bf16.bf16 "
      "{%0, %1, %2, %3, %4, %5, %6, %7, %8, %9, %10, %11, %12, %13, %14, %15, %16, %17, %18, %19}, "
      "%20, %21, p, 1, 1, 1, 1;\n}\n"
      : "=f"(d[0]), "=f"(d[1]), "=f"(d[2]), "=f"(d[3]), "=f"(d[4]), "=f"(d[5]), "=f"(d[6]), "=f"(d[7]), "=f"(d[8]), "=f"(d[9]), "=f"(d[10]), "=f"(d[11]), "=f"(d[12]), "=f"(d[13]), "=f"(d[14]), "=f"(d[15]), "=f"(d[16]), "=f"(d[17]), "=f"(d[18]), "=f"(d[19])
      : "l"(da), "l"(db));
  }
}
__device__ __forceinline__ void wgmma_n128_rs_ta0_tb1(float* d, uint32_t a0, uint32_t a1, uint32_t a2, uint32_t a3, uint64_t db, bool accumulate) {
  if (accumulate) {
    asm volatile("{\n.reg .pred p;\nsetp.ne.b32 p, 1, 0;\n"
      "wgmma.mma_async.sync.aligned.m64n128k16.f32.bf16.bf16 "
      "{%0, %1, %2, %3, %4, %5, %6, %7, %8, %9, %10, %11, %12, %13, %14, %15, %16, %17, %18, %19, %20, %21, %22, %23, %24, %25, %26, %27, %28, %29, %30, %31, %32, %33, %34, %35, %36, %37, %38, %39, %40, %41, %42, %43, %44, %45, %46, %47, %48, %49, %50, %51, %52, %53, %54, %55, %56, %57, %58, %59, %60, %61, %62, %63}, "
      "{%64, %65, %66, %67}, %68, p, 1, 1, 1;\n}\n"
      : "+f"(d[0]), "+f"(d[1]), "+f"(d[2]), "+f"(d[3]), "+f"(d[4]), "+f"(d[5]), "+f"(d[6]), "+f"(d[7]), "+f"(d[8]), "+f"(d[9]), "+f"(d[10]), "+f"(d[11]), "+f"(d[12]), "+f"(d[13]), "+f"(d[14]), "+f"(d[15]), "+f"(d[16]), "+f"(d[17]), "+f"(d[18]), "+f"(d[19]), "+f"(d[20]), "+f"(d[21]), "+f"(d[22]), "+f"(d[23]), "+f"(d[24]), "+f"(d[25]), "+f"(d[26]), "+f"(d[27]), "+f"(d[28]), "+f"(d[29]), "+f"(d[30]), "+f"(d[31]), "+f"(d[32]), "+f"(d[33]), "+f"(d[34]), "+f"(d[35]), "+f"(d[36]), "+f"(d[37]), "+f"(d[38]), "+f"(d[39]), "+f"(d[40]), "+f"(d[41]), "+f"(d[42]), "+f"(d[43]), "+f"(d[44]), "+f"(d[45]), "+f"(d[46]), "+f"(d[47]), "+f"(d[48]), "+f"(d[49]), "+f"(d[50]), "+f"(d[51]), "+f"(d[52]), "+f"(d[53]), "+f"(d[54]), "+f"(d[55]), "+f"(d[56]), "+f"(d[57]), "+f"(d[58]), "+f"(d[59]), "+f"(d[60]), "+f"(d[61]), "+f"(d[62]), "+f"(d[63])
      : "r"(a0), "r"(a1), "r"(a2), "r"(a3), "l"(db));
  } else {
    asm volatile("{\n.reg .pred p;\nsetp.ne.b32 p, 0, 0;\n"
      "wgmma.mma_async.sync.aligned.m64n128k16.f32.bf16.bf16 "
      "{%0, %1, %2, %3, %4, %5, %6, %7, %8, %9, %10, %11, %12, %13, %14, %15, %16, %17, %18, %19, %20, %21, %22, %23, %24, %25, %26, %27, %28, %29, %30, %31, %32, %33, %34, %35, %36, %37, %38, %39, %40, %41, %42, %43, %44, %45, %46, %47, %48, %49, %50, %51, %52, %53, %54, %55, %56, %57, %58, %59, %60, %61, %62, %63}, "
      "{%64, %65, %66, %67}, %68, p, 1, 1, 1;\n}\n"
      : "=f"(d[0]), "=f"(d[1]), "=f"(d[2]), "=f"(d[3]), "=f"(d[4]), "=f"(d[5]), "=f"(d[6]), "=f"(d[7]), "=f"(d[8]), "=f"(d[9]), "=f"(d[10]), "=f"(d[11]), "=f"(d[12]), "=f"(d[13]), "=f"(d[14]), "=f"(d[15]), "=f"(d[16]), "=f"(d[17]), "=f"(d[18]), "=f"(d[19]), "=f"(d[20]), "=f"(d[21]), "=f"(d[22]), "=f"(d[23]), "=f"(d[24]), "=f"(d[25]), "=f"(d[26]), "=f"(d[27]), "=f"(d[28]), "=f"(d[29]), "=f"(d[30]), "=f"(d[31]), "=f"(d[32]), "=f"(d[33]), "=f"(d[34]), "=f"(d[35]), "=f"(d[36]), "=f"(d[37]), "=f"(d[38]), "=f"(d[39]), "=f"(d[40]), "=f"(d[41]), "=f"(d[42]), "=f"(d[43]), "=f"(d[44]), "=f"(d[45]), "=f"(d[46]), "=f"(d[47]), "=f"(d[48]), "=f"(d[49]), "=f"(d[50]), "=f"(d[51]), "=f"(d[52]), "=f"(d[53]), "=f"(d[54]), "=f"(d[55]), "=f"(d[56]), "=f"(d[57]), "=f"(d[58]), "=f"(d[59]), "=f"(d[60]), "=f"(d[61]), "=f"(d[62]), "=f"(d[63])
      : "r"(a0), "r"(a1), "r"(a2), "r"(a3), "l"(db));
  }
}
__device__ __forceinline__ void wgmma_n128_ss_ta0_tb1(float* d, uint64_t da, uint64_t db, bool accumulate) {
  if (accumulate) {
    asm volatile("{\n.reg .pred p;\nsetp.ne.b32 p, 1, 0;\n"
      "wgmma.mma_async.sync.aligned.m64n128k16.f32.bf16.bf16 "
      "{%0, %1, %2, %3, %4, %5, %6, %7, %8, %9, %10, %11, %12, %13, %14, %15, %16, %17, %18, %19, %20, %21, %22, %23, %24, %25, %26, %27, %28, %29, %30, %31, %32, %33, %34, %35, %36, %37, %38, %39, %40, %41, %42, %43, %44, %45, %46, %47, %48, %49, %50, %51, %52, %53, %54, %55, %56, %57, %58, %59, %60, %61, %62, %63}, "
      "%64, %65, p, 1, 1, 0, 1;\n}\n"
      : "+f"(d[0]), "+f"(d[1]), "+f"(d[2]), "+f"(d[3]), "+f"(d[4]), "+f"(d[5]), "+f"(d[6]), "+f"(d[7]), "+f"(d[8]), "+f"(d[9]), "+f"(d[10]), "+f"(d[11]), "+f"(d[12]), "+f"(d[13]), "+f"(d[14]), "+f"(d[15]), "+f"(d[16]), "+f"(d[17]), "+f"(d[18]), "+f"(d[19]), "+f"(d[20]), "+f"(d[21]), "+f"(d[22]), "+f"(d[23]), "+f"(d[24]), "+f"(d[25]), "+f"(d[26]), "+f"(d[27]), "+f"(d[28]), "+f"(d[29]), "+f"(d[30]), "+f"(d[31]), "+f"(d[32]), "+f"(d[33]), "+f"(d[34]), "+f"(d[35]), "+f"(d[36]), "+f"(d[37]), "+f"(d[38]), "+f"(d[39]), "+f"(d[40]), "+f"(d[41]), "+f"(d[42]), "+f"(d[43]), "+f"(d[44]), "+f"(d[45]), "+f"(d[46]), "+f"(d[47]), "+f"(d[48]), "+f"(d[49]), "+f"(d[50]), "+f"(d[51]), "+f"(d[52]), "+f"(d[53]), "+f"(d[54]), "+f"(d[55]), "+f"(d[56]), "+f"(d[57]), "+f"(d[58]), "+f"(d[59]), "+f"(d[60]), "+f"(d[61]), "+f"(d[62]), "+f"(d[63])
      : "l"(da), "l"(db));
  } else {
    asm volatile("{\n.reg .pred p;\nsetp.ne.b32 p, 0, 0;\n"
      "wgmma.mma_async.sync.aligned.m64n128k16.f32.bf16.bf16 "
      "{%0, %1, %2, %3, %4, %5, %6, %7, %8, %9, %10, %11, %12, %13, %14, %15, %16, %17, %18, %19, %20, %21, %22, %23, %24, %25, %26, %27, %28, %29, %30, %31, %32, %33, %34, %35, %36, %37, %38, %39, %40, %41, %42, %43, %44, %45, %46, %47, %48, %49, %50, %51, %52, %53, %54, %55, %56, %57, %58, %59, %60, %61, %62, %63}, "
      "%64, %65, p, 1, 1, 0, 1;\n}\n"
      : "=f"(d[0]), "=f"(d[1]), "=f"(d[2]), "=f"(d[3]), "=f"(d[4]), "=f"(d[5]), "=f"(d[6]), "=f"(d[7]), "=f"(d[8]), "=f"(d[9]), "=f"(d[10]), "=f"(d[11]), "=f"(d[12]), "=f"(d[13]), "=f"(d[14]), "=f"(d[15]), "=f"(d[16]), "=f"(d[17]), "=f"(d[18]), "=f"(d[19]), "=f"(d[20]), "=f"(d[21]), "=f"(d[22]), "=f"(d[23]), "=f"(d[24]), "=f"(d[25]), "=f"(d[26]), "=f"(d[27]), "=f"(d[28]), "=f"(d[29]), "=f"(d[30]), "=f"(d[31]), "=f"(d[32]), "=f"(d[33]), "=f"(d[34]), "=f"(d[35]), "=f"(d[36]), "=f"(d[37]), "=f"(d[38]), "=f"(d[39]), "=f"(d[40]), "=f"(d[41]), "=f"(d[42]), "=f"(d[43]), "=f"(d[44]), "=f"(d[45]), "=f"(d[46]), "=f"(d[47]), "=f"(d[48]), "=f"(d[49]), "=f"(d[50]), "=f"(d[51]), "=f"(d[52]), "=f"(d[53]), "=f"(d[54]), "=f"(d[55]), "=f"(d[56]), "=f"(d[57]), "=f"(d[58]), "=f"(d[59]), "=f"(d[60]), "=f"(d[61]), "=f"(d[62]), "=f"(d[63])
      : "l"(da), "l"(db));
  }
}
__device__ __forceinline__ void wgmma_n256_rs_ta0_tb1(float* d, uint32_t a0, uint32_t a1, uint32_t a2, uint32_t a3, uint64_t db, bool accumulate) {
  if (accumulate) {
    asm volatile("{\n.reg .pred p;\nsetp.ne.b32 p, 1, 0;\n"
      "wgmma.mma_async.sync.aligned.m64n256k16.f32.bf16.bf16 "
      "{%0, %1, %2, %3, %4, %5, %6, %7, %8, %9, %10, %11, %12, %13, %14, %15, %16, %17, %18, %19, %20, %21, %22, %23, %24, %25, %26, %27, %28, %29, %30, %31, %32, %33, %34, %35, %36, %37, %38, %39, %40, %41, %42, %43, %44, %45, %46, %47, %48, %49, %50, %51, %52, %53, %54, %55, %56, %57, %58, %59, %60, %61, %62, %63, %64, %65, %66, %67, %68, %69, %70, %71, %72, %73, %74, %75, %76, %77, %78, %79, %80, %81, %82, %83, %84, %85, %86, %87, %88, %89, %90, %91, %92, %93, %94, %95, %96, %97, %98, %99, %100, %101, %102, %103, %104, %105, %106, %107, %108, %109, %110, %111, %112, %113, %114, %115, %116, %117, %118, %119, %120, %121, %122, %123, %124, %125, %126, %127}, "
      "{%128, %129, %130, %131}, %132, p, 1, 1, 1;\n}\n"
      : "+f"(d[0]), "+f"(d[1]), "+f"(d[2]), "+f"(d[3]), "+f"(d[4]), "+f"(d[5]), "+f"(d[6]), "+f"(d[7]), "+f"(d[8]), "+f"(d[9]), "+f"(d[10]), "+f"(d[11]), "+f"(d[12]), "+f"(d[13]), "+f"(d[14]), "+f"(d[15]), "+f"(d[16]), "+f"(d[17]), "+f"(d[18]), "+f"(d[19]), "+f"(d[20]), "+f"(d[21]), "+f"(d[22]), "+f"(d[23]), "+f"(d[24]), "+f"(d[25]), "+f"(d[26]), "+f"(d[27]), "+f"(d[28]), "+f"(d[29]), "+f"(d[30]), "+f"(d[31]), "+f"(d[32]), "+f"(d[33]), "+f"(d[34]), "+f"(d[35]), "+f"(d[36]), "+f"(d[37]), "+f"(d[38]), "+f"(d[39]), "+f"(d[40]), "+f"(d[41]), "+f"(d[42]), "+f"(d[43]), "+f"(d[44]), "+f"(d[45]), "+f"(d[46]), "+f"(d[47]), "+f"(d[48]), "+f"(d[49]), "+f"(d[50]), "+f"(d[51]), "+f"(d[52]), "+f"(d[53]), "+f"(d[54]), "+f"(d[55]), "+f"(d[56]), "+f"(d[57]), "+f"(d[58]), "+f"(d[59]), "+f"(d[60]), "+f"(d[61]), "+f"(d[62]), "+f"(d[63]), "+f"(d[64]), "+f"(d[65]), "+f"(d[66]), "+f"(d[67]), "+f"(d[68]), "+f"(d[69]), "+f"(d[70]), "+f"(d[71]), "+f"(d[72]), "+f"(d[73]), "+f"(d[74]), "+f"(d[75]), "+f"(d[76]), "+f"(d[77]), "+f"(d[78]), "+f"(d[79]), "+f"(d[80]), "+f"(d[81]), "+f"(d[82]), "+f"(d[83]), "+f"(d[84]), "+f"(d[85]), "+f"(d[86]), "+f"(d[87]), "+f"(d[88]), "+f"(d[89]), "+f"(d[90]), "+f"(d[91]), "+f"(d[92]), "+f"(d[93]), "+f"(d[94]), "+f"(d[95]), "+f"(d[96]), "+f"(d[97]), "+f"(d[98]), "+f"(d[99]), "+f"(d[100]), "+f"(d[101]), "+f"(d[102]), "+f"(d[103]), "+f"(d[104]), "+f"(d[105]), "+f"(d[106]), "+f"(d[107]), "+f"(d[108]), "+f"(d[109]), "+f"(d[110]), "+f"(d[111]), "+f"(d[112]), "+f"(d[113]), "+f"(d[114]), "+f"(d[115]), "+f"(d[116]), "+f"(d[117]), "+f"(d[118]), "+f"(d[119]), "+f"(d[120]), "+f"(d[121]), "+f"(d[122]), "+f"(d[123]), "+f"(d[124]), "+f"(d[125]), "+f"(d[126]), "+f"(d[127])
      : "r"(a0), "r"(a1), "r"(a2), "r"(a3), "l"(db));
  } else {
    asm volatile("{\n.reg .pred p;\nsetp.ne.b32 p, 0, 0;\n"
      "wgmma.mma_async.sync.aligned.m64n256k16.f32.bf16.bf16 "
      "{%0, %1, %2, %3, %4, %5, %6, %7, %8, %9, %10, %11, %12, %13, %14, %15, %16, %17, %18, %19, %20, %21, %22, %23, %24, %25, %26, %27, %28, %29, %30, %31, %32, %33, %34, %35, %36, %37, %38, %39, %40, %41, %42, %43, %44, %45, %46, %47, %48, %49, %50, %51, %52, %53, %54, %55, %56, %57, %58, %59, %60, %61, %62, %63, %64, %65, %66, %67, %68, %69, %70, %71, %72, %73, %74, %75, %76, %77, %78, %79, %80, %81, %82, %83, %84, %85, %86, %87, %88, %89, %90, %91, %92, %93, %94, %95, %96, %97, %98, %99, %100, %101, %102, %103, %104, %105, %106, %107, %108, %109, %110, %111, %112, %113, %114, %115, %116, %117, %118, %119, %120, %121, %122, %123, %124, %125, %126, %127}, "
      "{%128, %129, %130, %131}, %132, p, 1, 1, 1;\n}\n"
      : "=f"(d[0]), "=f"(d[1]), "=f"(d[2]), "=f"(d[3]), "=f"(d[4]), "=f"(d[5]), "=f"(d[6]), "=f"(d[7]), "=f"(d[8]), "=f"(d[9]), "=f"(d[10]), "=f"(d[11]), "=f"(d[12]), "=f"(d[13]), "=f"(d[14]), "=f"(d[15]), "=f"(d[16]), "=f"(d[17]), "=f"(d[18]), "=f"(d[19]), "=f"(d[20]), "=f"(d[21]), "=f"(d[22]), "=f"(d[23]), "=f"(d[24]), "=f"(d[25]), "=f"(d[26]), "=f"(d[27]), "=f"(d[28]), "=f"(d[29]), "=f"(d[30]), "=f"(d[31]), "=f"(d[32]), "=f"(d[33]), "=f"(d[34]), "=f"(d[35]), "=f"(d[36]), "=f"(d[37]), "=f"(d[38]), "=f"(d[39]), "=f"(d[40]), "=f"(d[41]), "=f"(d[42]), "=f"(d[43]), "=f"(d[44]), "=f"(d[45]), "=f"(d[46]), "=f"(d[47]), "=f"(d[48]), "=f"(d[49]), "=f"(d[50]), "=f"(d[51]), "=f"(d[52]), "=f"(d[53]), "=f"(d[54]), "=f"(d[55]), "=f"(d[56]), "=f"(d[57]), "=f"(d[58]), "=f"(d[59]), "=f"(d[60]), "=f"(d[61]), "=f"(d[62]), "=f"(d[63]), "=f"(d[64]), "=f"(d[65]), "=f"(d[66]), "=f"(d[67]), "=f"(d[68]), "=f"(d[69]), "=f"(d[70]), "=f"(d[71]), "=f"(d[72]), "=f"(d[73]), "=f"(d[74]), "=f"(d[75]), "=f"(d[76]), "=f"(d[77]), "=f"(d[78]), "=f"(d[79]), "=f"(d[80]), "=f"(d[81]), "=f"(d[82]), "=f"(d[83]), "=f"(d[84]), "=f"(d[85]), "=f"(d[86]), "=f"(d[87]), "=f"(d[88]), "=f"(d[89]), "=f"(d[90]), "=f"(d[91]), "=f"(d[92]), "=f"(d[93]), "=f"(d[94]), "=f"(d[95]), "=f"(d[96]), "=f"(d[97]), "=f"(d[98]), "=f"(d[99]), "=f"(d[100]), "=f"(d[101]), "=f"(d[102]), "=f"(d[103]), "=f"(d[104]), "=f"(d[105]), "=f"(d[106]), "=f"(d[107]), "=f"(d[108]), "=f"(d[109]), "=f"(d[110]), "=f"(d[111]), "=f"(d[112]), "=f"(d[113]), "=f"(d[114]), "=f"(d[115]), "=f"(d[116]), "=f"(d[117]), "=f"(d[118]), "=f"(d[119]), "=f"(d[120]), "=f"(d[121]), "=f"(d[122]), "=f"(d[123]), "=f"(d[124]), "=f"(d[125]), "=f"(d[126]), "=f"(d[127])
      : "r"(a0), "r"(a1), "r"(a2), "r"(a3), "l"(db));
  }
}
__device__ __forceinline__ void wgmma_n256_ss_ta0_tb1(float* d, uint64_t da, uint64_t db, bool accumulate) {
  if (accumulate) {
    asm volatile("{\n.reg .pred p;\nsetp.ne.b32 p, 1, 0;\n"
      "wgmma.mma_async.sync.aligned.m64n256k16.f32.bf16.bf16 "
      "{%0, %1, %2, %3, %4, %5, %6, %7, %8, %9, %10, %11, %12, %13, %14, %15, %16, %17, %18, %19, %20, %21, %22, %23, %24, %25, %26, %27, %28, %29, %30, %31, %32, %33, %34, %35, %36, %37, %38, %39, %40, %41, %42, %43, %44, %45, %46, %47, %48, %49, %50, %51, %52, %53, %54, %55, %56, %57, %58, %59, %60, %61, %62, %63, %64, %65, %66, %67, %68, %69, %70, %71, %72, %73, %74, %75, %76, %77, %78, %79, %80, %81, %82, %83, %84, %85, %86, %87, %88, %89, %90, %91, %92, %93, %94, %95, %96, %97, %98, %99, %100, %101, %102, %103, %104, %105, %106, %107, %108, %109, %110, %111, %112, %113, %114, %115, %116, %117, %118, %119, %120, %121, %122, %123, %124, %125, %126, %127}, "
      "%128, %129, p, 1, 1, 0, 1;\n}\n"
      : "+f"(d[0]), "+f"(d[1]), "+f"(d[2]), "+f"(d[3]), "+f"(d[4]), "+f"(d[5]), "+f"(d[6]), "+f"(d[7]), "+f"(d[8]), "+f"(d[9]), "+f"(d[10]), "+f"(d[11]), "+f"(d[12]), "+f"(d[13]), "+f"(d[14]), "+f"(d[15]), "+f"(d[16]), "+f"(d[17]), "+f"(d[18]), "+f"(d[19]), "+f"(d[20]), "+f"(d[21]), "+f"(d[22]), "+f"(d[23]), "+f"(d[24]), "+f"(d[25]), "+f"(d[26]), "+f"(d[27]), "+f"(d[28]), "+f"(d[29]), "+f"(d[30]), "+f"(d[31]), "+f"(d[32]), "+f"(d[33]), "+f"(d[34]), "+f"(d[35]), "+f"(d[36]), "+f"(d[37]), "+f"(d[38]), "+f"(d[39]), "+f"(d[40]), "+f"(d[41]), "+f"(d[42]), "+f"(d[43]), "+f"(d[44]), "+f"(d[45]), "+f"(d[46]), "+f"(d[47]), "+f"(d[48]), "+f"(d[49]), "+f"(d[50]), "+f"(d[51]), "+f"(d[52]), "+f"(d[53]), "+f"(d[54]), "+f"(d[55]), "+f"(d[56]), "+f"(d[57]), "+f"(d[58]), "+f"(d[59]), "+f"(d[60]), "+f"(d[61]), "+f"(d[62]), "+f"(d[63]), "+f"(d[64]), "+f"(d[65]), "+f"(d[66]), "+f"(d[67]), "+f"(d[68]), "+f"(d[69]), "+f"(d[70]), "+f"(d[71]), "+f"(d[72]), "+f"(d[73]), "+f"(d[74]), "+f"(d[75]), "+f"(d[76]), "+f"(d[77]), "+f"(d[78]), "+f"(d[79]), "+f"(d[80]), "+f"(d[81]), "+f"(d[82]), "+f"(d[83]), "+f"(d[84]), "+f"(d[85]), "+f"(d[86]), "+f"(d[87]), "+f"(d[88]), "+f"(d[89]), "+f"(d[90]), "+f"(d[91]), "+f"(d[92]), "+f"(d[93]), "+f"(d[94]), "+f"(d[95]), "+f"(d[96]), "+f"(d[97]), "+f"(d[98]), "+f"(d[99]), "+f"(d[100]), "+f"(d[101]), "+f"(d[102]), "+f"(d[103]), "+f"(d[104]), "+f"(d[105]), "+f"(d[106]), "+f"(d[107]), "+f"(d[108]), "+f"(d[109]), "+f"(d[110]), "+f"(d[111]), "+f"(d[112]), "+f"(d[113]), "+f"(d[114]), "+f"(d[115]), "+f"(d[116]), "+f"(d[117]), "+f"(d[118]), "+f"(d[119]), "+f"(d[120]), "+f"(d[121]), "+f"(d[122]), "+f"(d[123]), "+f"(d[124]), "+f"(d[125]), "+f"(d[126]), "+f"(d[127])
      : "l"(da), "l"(db));
  } else {
    asm volatile("{\n.reg .pred p;\nsetp.ne.b32 p, 0, 0;\n"
      "wgmma.mma_async.sync.aligned.m64n256k16.f32.bf16.bf16 "
      "{%0, %1, %2, %3, %4, %5, %6, %7, %8, %9, %10, %11, %12, %13, %14, %15, %16, %17, %18, %19, %20, %21, %22, %23, %24, %25, %26, %27, %28, %29, %30, %31, %32, %33, %34, %35, %36, %37, %38, %39, %40, %41, %42, %43, %44, %45, %46, %47, %48, %49, %50, %51, %52, %53, %54, %55, %56, %57, %58, %59, %60, %61, %62, %63, %64, %65, %66, %67, %68, %69, %70, %71, %72, %73, %74, %75, %76, %77, %78, %79, %80, %81, %82, %83, %84, %85, %86, %87, %88, %89, %90, %91, %92, %93, %94, %95, %96, %97, %98, %99, %100, %101, %102, %103, %104, %105, %106, %107, %108, %109, %110, %111, %112, %113, %114, %115, %116, %117, %118, %119, %120, %121, %122, %123, %124, %125, %126, %127}, "
      "%128, %129, p, 1, 1, 0, 1;\n}\n"
      : "=f"(d[0]), "=f"(d[1]), "=f"(d[2]), "=f"(d[3]), "=f"(d[4]), "=f"(d[5]), "=f"(d[6]), "=f"(d[7]), "=f"(d[8]), "=f"(d[9]), "=f"(d[10]), "=f"(d[11]), "=f"(d[12]), "=f"(d[13]), "=f"(d[14]), "=f"(d[15]), "=f"(d[16]), "=f"(d[17]), "=f"(d[18]), "=f"(d[19]), "=f"(d[20]), "=f"(d[21]), "=f"(d[22]), "=f"(d[23]), "=f"(d[24]), "=f"(d[25]), "=f"(d[26]), "=f"(d[27]), "=f"(d[28]), "=f"(d[29]), "=f"(d[30]), "=f"(d[31]), "=f"(d[32]), "=f"(d[33]), "=f"(d[34]), "=f"(d[35]), "=f"(d[36]), "=f"(d[37]), "=f"(d[38]), "=f"(d[39]), "=f"(d[40]), "=f"(d[41]), "=f"(d[42]), "=f"(d[43]), "=f"(d[44]), "=f"(d[45]), "=f"(d[46]), "=f"(d[47]), "=f"(d[48]), "=f"(d[49]), "=f"(d[50]), "=f"(d[51]), "=f"(d[52]), "=f"(d[53]), "=f"(d[54]), "=f"(d[55]), "=f"(d[56]), "=f"(d[57]), "=f"(d[58]), "=f"(d[59]), "=f"(d[60]), "=f"(d[61]), "=f"(d[62]), "=f"(d[63]), "=f"(d[64]), "=f"(d[65]), "=f"(d[66]), "=f"(d[67]), "=f"(d[68]), "=f"(d[69]), "=f"(d[70]), "=f"(d[71]), "=f"(d[72]), "=f"(d[73]), "=f"(d[74]), "=f"(d[75]), "=f"(d[76]), "=f"(d[77]), "=f"(d[78]), "=f"(d[79]), "=f"(d[80]), "=f"(d[81]), "=f"(d[82]), "=f"(d[83]), "=f"(d[84]), "=f"(d[85]), "=f"(d[86]), "=f"(d[87]), "=f"(d[88]), "=f"(d[89]), "=f"(d[90]), "=f"(d[91]), "=f"(d[92]), "=f"(d[93]), "=f"(d[94]), "=f"(d[95]), "=f"(d[96]), "=f"(d[97]), "=f"(d[98]), "=f"(d[99]), "=f"(d[100]), "=f"(d[101]), "=f"(d[102]), "=f"(d[103]), "=f"(d[104]), "=f"(d[105]), "=f"(d[106]), "=f"(d[107]), "=f"(d[108]), "=f"(d[109]), "=f"(d[110]), "=f"(d[111]), "=f"(d[112]), "=f"(d[113]), "=f"(d[114]), "=f"(d[115]), "=f"(d[116]), "=f"(d[117]), "=f"(d[118]), "=f"(d[119]), "=f"(d[120]), "=f"(d[121]), "=f"(d[122]), "=f"(d[123]), "=f"(d[124]), "=f"(d[125]), "=f"(d[126]), "=f"(d[127])
      : "l"(da), "l"(db));
  }
}
__device__ __forceinline__ void wgmma_n256_ssp_ta0_tb1(float* d, uint64_t da, uint64_t db, int accumulate) {
    asm volatile("{\n.reg .pred p;\nsetp.ne.b32 p, %130, 0;\n"
      "wgmma.mma_async.sync.aligned.m64n256k16.f32.bf16.bf16 "
      "{%0, %1, %2, %3, %4, %5, %6, %7, %8, %9, %10, %11, %12, %13, %14, %15, %16, %17, %18, %19, %20, %21, %22, %23, %24, %25, %26, %27, %28, %29, %30, %31, %32, %33, %34, %35, %36, %37, %38, %39, %40, %41, %42, %43, %44, %45, %46, %47, %48, %49, %50, %51, %52, %53, %54, %55, %56, %57, %58, %59, %60, %61, %62, %63, %64, %65, %66, %67, %68, %69, %70, %71, %72, %73, %74, %75, %76, %77, %78, %79, %80, %81, %82, %83, %84, %85, %86, %87, %88, %89, %90, %91, %92, %93, %94, %95, %96, %97, %98, %99, %100, %101, %102, %103, %104, %105, %106, %107, %108, %109, %110, %111, %112, %113, %114, %115, %116, %117, %118, %119, %120, %121, %122, %123, %124, %125, %126, %127}, "
      "%128, %129, p, 1, 1, 0, 1;\n}\n"
      : "+f"(d[0]), "+f"(d[1]), "+f"(d[2]), "+f"(d[3]), "+f"(d[4]), "+f"(d[5]), "+f"(d[6]), "+f"(d[7]), "+f"(d[8]), "+f"(d[9]), "+f"(d[10]), "+f"(d[11]), "+f"(d[12]), "+f"(d[13]), "+f"(d[14]), "+f"(d[15]), "+f"(d[16]), "+f"(d[17]), "+f"(d[18]), "+f"(d[19]), "+f"(d[20]), "+f"(d[21]), "+f"(d[22]), "+f"(d[23]), "+f"(d[24]), "+f"(d[25]), "+f"(d[26]), "+f"(d[27]), "+f"(d[28]), "+f"(d[29]), "+f"(d[30]), "+f"(d[31]), "+f"(d[32]), "+f"(d[33]), "+f"(d[34]), "+f"(d[35]), "+f"(d[36]), "+f"(d[37]), "+f"(d[38]), "+f"(d[39]), "+f"(d[40]), "+f"(d[41]), "+f"(d[42]), "+f"(d[43]), "+f"(d[44]), "+f"(d[45]), "+f"(d[46]), "+f"(d[47]), "+f"(d[48]), "+f"(d[49]), "+f"(d[50]), "+f"(d[51]), "+f"(d[52]), "+f"(d[53]), "+f"(d[54]), "+f"(d[55]), "+f"(d[56]), "+f"(d[57]), "+f"(d[58]), "+f"(d[59]), "+f"(d[60]), "+f"(d[61]), "+f"(d[62]), "+f"(d[63]), "+f"(d[64]), "+f"(d[65]), "+f"(d[66]), "+f"(d[67]), "+f"(d[68]), "+f"(d[69]), "+f"(d[70]), "+f"(d[71]), "+f"(d[72]), "+f"(d[73]), "+f"(d[74]), "+f"(d[75]), "+f"(d[76]), "+f"(d[77]), "+f"(d[78]), "+f"(d[79]), "+f"(d[80]), "+f"(d[81]), "+f"(d[82]), "+f"(d[83]), "+f"(d[84]), "+f"(d[85]), "+f"(d[86]), "+f"(d[87]), "+f"(d[88]), "+f"(d[89]), "+f"(d[90]), "+f"(d[91]), "+f"(d[92]), "+f"(d[93]), "+f"(d[94]), "+f"(d[95]), "+f"(d[96]), "+f"(d[97]), "+f"(d[98]), "+f"(d[99]), "+f"(d[100]), "+f"(d[101]), "+f"(d[102]), "+f"(d[103]), "+f"(d[104]), "+f"(d[105]), "+f"(d[106]), "+f"(d[107]), "+f"(d[108]), "+f"(d[109]), "+f"(d[110]), "+f"(d[111]), "+f"(d[112]), "+f"(d[113]), "+f"(d[114]), "+f"(d[115]), "+f"(d[116]), "+f"(d[117]), "+f"(d[118]), "+f"(d[119]), "+f"(d[120]), "+f"(d[121]), "+f"(d[122]), "+f"(d[123]), "+f"(d[124]), "+f"(d[125]), "+f"(d[126]), "+f"(d[127])
      : "l"(da), "l"(db), "r"(accumulate));
}

template <int N> __device__ __forceinline__ void quad_sum(float* m) {
#pragma unroll
  for (int o = 1; o <= 2; o <<= 1) {
    float t[N];
#pragma unroll
    for (int i = 0; i < N; i++) t[i] = __shfl_xor_sync(~0u, m[i], o);
#pragma unroll
    for (int i = 0; i < N; i++) m[i] += t[i];
  }
}
__device__ __forceinline__ bool softmax_unsafe(const uint32_t* t, float l0, float l1) {
  const float m0 = fmaxf(bf_lo(t[0]) + bf_hi(t[0]), bf_lo(t[2]) + bf_hi(t[2])), m1 = fmaxf(bf_lo(t[1]) + bf_hi(t[1]), bf_lo(t[3]) + bf_hi(t[3]));
  return __any_sync(~0u, !(m0 * l0 < 2500.f) | !(m1 * l1 < 2500.f));
}
__device__ __forceinline__ void softmax_shift(float* p, float c0, float c1) {
#pragma unroll 1
  for (int it = 0; it < 8; it++) {
    float mx = p[0], mn = p[0];
#pragma unroll
    for (int j = 1; j < 8; j++) { mx = fmaxf(mx, p[(j >> 1) * 4 + (j & 1)]); mn = fminf(mn, p[(j >> 1) * 4 + (j & 1)]); }
#pragma unroll
    for (int o = 1; o <= 2; o <<= 1) { mx = fmaxf(mx, __shfl_xor_sync(~0u, mx, o)); mn = fminf(mn, __shfl_xor_sync(~0u, mn, o)); }
    const float half = fminf(0.5f * (mx - mn), 50.f * rcp(it & 1 ? c1 : c0));
    float r[8];
#pragma unroll
    for (int j = 0; j < 8; j++) {
      const float v = p[(j >> 1) * 4 + (j & 1)];
      r[j] = fmaxf(v - mx + half, 0.f) + fminf(v - mn - half, 0.f) + (v - v);
    }
#pragma unroll
    for (int k = 0; k < 7; k++)
#pragma unroll
      for (int j = 0; j < 8; j++) p[(k >> 1) * 16 + (k & 1) * 2 + (j >> 1) * 4 + (j & 1)] = p[((k + 1) >> 1) * 16 + ((k + 1) & 1) * 2 + (j >> 1) * 4 + (j & 1)];
#pragma unroll
    for (int j = 0; j < 8; j++) p[50 + (j >> 1) * 4 + (j & 1)] = r[j];
  }
}
template <int J0 = 0, int J1 = 8> __device__ __forceinline__ void k_exp(const float* p, float c0, float c1, float* e, float* s) {
#pragma unroll
  for (int j = J0; j < J1; j++) {
    e[2 * j] = ex2(p[2 * j] * (j & 1 ? c1 : c0));
    e[2 * j + 1] = ex2(p[2 * j + 1] * (j & 1 ? c1 : c0));
    e[16 + j] = rcp(e[2 * j] * e[2 * j + 1]);
    const float t = e[2 * j] + e[2 * j + 1];
    s[j & 1] = j < 2 ? t : s[j & 1] + t;
    s[2 + (j & 1)] = j < 2 ? e[16 + j] * t : fmaf(e[16 + j], t, s[2 + (j & 1)]);
  }
}
template <int J0 = 0, int J1 = 8> __device__ __forceinline__ void q_exp(const float* p, float c0, float c1, uint32_t* f) {
#pragma unroll
  for (int j = J0; j < J1; j++) {
    const float e0 = ex2(p[2 * j] * (j & 1 ? c1 : c0)), e1 = ex2(p[2 * j + 1] * (j & 1 ? c1 : c0)), r = rcp(e0 * e1);
    f[j] = pack2(e0, e1);
    f[8 + j] = bmul2(f[j], pack2(r, r));
  }
}

#define FMA8(A, U, X)                                                                                        \
  A[0] = fmaf(bf_lo(U.x), X, A[0]); A[1] = fmaf(bf_hi(U.x), X, A[1]); A[2] = fmaf(bf_lo(U.y), X, A[2]); A[3] = fmaf(bf_hi(U.y), X, A[3]); \
  A[4] = fmaf(bf_lo(U.z), X, A[4]); A[5] = fmaf(bf_hi(U.z), X, A[5]); A[6] = fmaf(bf_lo(U.w), X, A[6]); A[7] = fmaf(bf_hi(U.w), X, A[7])

__device__ __forceinline__ uint32_t routed_row(const __nv_bfloat16* x, uint32_t tag, int lane, uint4* xr) {
  uint32_t best = 0, sv = 0;
#pragma unroll 1
  for (int it = 0; it < SPIN_MAX; it++) {
    const int sel = 2047 - (best & 0x7ff);
#pragma unroll
    for (int i = 0; i < 4; i++) xr[i] = ldg_nc(x + (size_t)sel * DM + i * 256 + lane * 8);
    const unsigned long long st = ld_rlx64(g_stat + sel);
    const uint4 b0 = ld_rlx128(g_best + lane * 2), b1 = ld_rlx128(g_best + 64 + lane * 2);
    const uint32_t m = __reduce_max_sync(~0u, max(max(b0.y == tag ? b0.x : 0u, b0.w == tag ? b0.z : 0u), max(b1.y == tag ? b1.x : 0u, b1.w == tag ? b1.z : 0u)));
    sv = (uint32_t)st;
    if (__all_sync(~0u, b0.y == tag && b0.w == tag && b1.y == tag && b1.w == tag && m == best && (uint32_t)(st >> 32) == tag)) break;
    best = m;
    if (AM_NS) __nanosleep(AM_NS);
  }
  const uint32_t m2 = (sv & 0xffff0000u) | (sv >> 16);
  const float rs = rcp(bf_lo(sv));
#pragma unroll
  for (int i = 0; i < 4; i++) {
    const uint32_t d0 = bsub2(xr[i].x, m2), d1 = bsub2(xr[i].y, m2), d2 = bsub2(xr[i].z, m2), d3 = bsub2(xr[i].w, m2);
    xr[i] = make_uint4(pack2(bf_lo(d0) * rs, bf_hi(d0) * rs), pack2(bf_lo(d1) * rs, bf_hi(d1) * rs), pack2(bf_lo(d2) * rs, bf_hi(d2) * rs),
                       pack2(bf_lo(d3) * rs, bf_hi(d3) * rs));
  }
  return best;
}

struct Params {
  const __nv_bfloat16 *x, *wqkv, *wo, *w_r, *w_down;
  uint32_t zA, zB;
};

template <bool BY_SMID> __global__ void __launch_bounds__(384, 1)
fused_kernel(const Params P, const __grid_constant__ CUtensorMap mX, const __grid_constant__ CUtensorMap mWkv, const __grid_constant__ CUtensorMap mWq,
             const __grid_constant__ CUtensorMap mWo, const __grid_constant__ CUtensorMap mPhi, const __grid_constant__ CUtensorMap mWp,
             const __grid_constant__ CUtensorMap mOut, const __grid_constant__ CUtensorMap mWc,
             const __grid_constant__ CUtensorMap mG, const __grid_constant__ CUtensorMap mU, const __grid_constant__ CUtensorMap mD,
             const __grid_constant__ CUtensorMap mXs, const __grid_constant__ CUtensorMap mG2, const __grid_constant__ CUtensorMap mU2) {
  constexpr uint32_t sb = SB, bar = SB + SM_BAR;
  int bid = blockIdx.x;
  if (BY_SMID) {
    uint32_t sm;
    asm volatile("mov.u32 %0, %%smid;" : "=r"(sm));
    const uint32_t tq = (sm - 64) >> 1, q7 = (tq * 37) >> 8;
    const uint32_t gpc = sm < 64 ? (sm >> 1) & 7 : 1 + tq - 7 * q7, idx = (sm < 64 ? sm >> 4 : 4 + q7) * 2 + (sm & 1);
    bid = sm < 120 ? ((PTAB >> (4 * gpc)) & 7) * 16 + idx : sm < 124 ? sm + 8 : sm - 116;
  }
  const int hg = ((bid >> 2) & 3) + 4 * ((bid >> 4) & 1), mb = (bid & 3) + 4 * ((bid >> 5) & 3);
  if (bid < NCTA && threadIdx.x < 256) {
    const uint32_t r0 = threadIdx.x >> 3, c = threadIdx.x & 7, dst = sb + 2 * KV_STAGE + r0 * 128 + ((c ^ (r0 & 7)) << 4);
    const char* xs = (const char*)P.x + (size_t)(mb * 128 + r0) * 2048 + c * 16;
    const char* ws = (const char*)P.wqkv + (size_t)r0 * 6144 + 2048 + hg * 256 + c * 16;
#pragma unroll
    for (int i = 0; i < 4; i++) cp_async16(dst + i * 4096, xs + i * 65536);
#pragma unroll
    for (int i = 0; i < 8; i++) cp_async16(dst + 16384 + i * 4096, ws + (i & 1) * 196608 + (i >> 2) * 2048 + ((i >> 1) & 1) * 128);
  }
  extern __shared__ __align__(1024) uint8_t smem[];
  if (smem_u32(smem) != SB) __trap();
  const int warp = __shfl_sync(~0u, threadIdx.x >> 5, 0);

  if (bid >= NCTA) {
    constexpr uint32_t XV = SM_WPHI, ONES = SM_ZT, BF = bar, BE = bar + 48, BX = bar + 96;
    constexpr int NJ = (DM - GROWS) / 64;
    const int lane = lane_id(), sp = bid - NCTA;
    const uint32_t tag = ld_rlx(g_epoch + bid * 32 + lane) + 1;
    if (warp == 8 && elect_one()) {
#pragma unroll 1
      for (int i = 0; i < 13; i++) mbar_init(bar + 8 * i, i >= 6 && i < 12 ? 8 : 1);
    }
    if (warp == 9) { sts64u(sb + ONES + lane * 8, 0x3f803f80u, 0x3f803f80u); fence_async_smem(); }
    __syncthreads();
    if (warp == 8) {
      if (elect_one()) {
        uint32_t s = 0, ph = 1;
        for (const long long c0 = clock64(); clock64() - c0 < SP_DELAY;) {}
#pragma unroll 1
        for (int job = 0; job < 8; job++) {
          const CUtensorMap* m = job == 0 ? &mWq : sp & 2 ? &mU2 : &mG2;
          const int g0 = job ? (sp & 1) * 28 + job * 4 - 4 : sp * 4;
#pragma unroll 1
          for (int row = job ? GROWS : 0; row < DM; row += 64) {
            mbar_wait(BE + 8 * s, ph);
            mbar_expect_tx(BF + 8 * s, Q_STAGE);
            tma4d(sb + s * Q_STAGE, m, 0, row, g0, 0, BF + 8 * s);
            tma4d(sb + s * Q_STAGE + 16384, m, 0, row, g0 + 2, 0, BF + 8 * s);
            if (++s == 6) { s = 0; ph ^= 1; }
          }
        }
      }
    } else if (warp == 9) {
      uint4 xr[4];
      routed_row(P.x, tag, lane, xr);
#pragma unroll
      for (int i = 0; i < 4; i++) sts128u(sb + XV + i * 512 + lane * 16, xr[i].x, xr[i].y, xr[i].z, xr[i].w);
      fence_async_smem();
      __syncwarp();
      if (lane == 0) mbar_arrive(BX);
    } else if (warp < 8) {
      uint32_t s = 0, ph = 0;
#pragma unroll 1
      for (int job = 0; job < 8; job++) {
        float d[8] = {0.f, 0.f, 0.f, 0.f, 0.f, 0.f, 0.f, 0.f};
        if (job == 1) mbar_wait(BX, 0);
#pragma unroll 1
        for (int i = 0; i < (job ? NJ : 16); i++) {
          mbar_wait(BF + 8 * s, ph);
          wg_fence();
#pragma unroll
          for (int k = 0; k < 8; k++)
            wgmma_n8_ss_ta1_tb0(d + 4 * (k >> 2), mkdesc(sb + k * 2048, 16, 1024, 1, s * (Q_STAGE / 16) + (warp >> 2) * 1024),
                                mkdesc(sb, 16, 128, 0, job ? (XV + GROWS * 2) / 16 + i * 8 + (k & 3) * 2 : ONES / 16), 1);
          wg_commit();
          wg_wait<0>();
          if (lane == 0) mbar_arrive(BE + 8 * s);
          if (++s == 6) { s = 0; ph ^= 1; }
        }
        reg_fence<8>(d);
        float* dst = (job ? g_gp + sp * 1792 + job * 256 - 256 : g_cs + sp * 256) + (warp >> 2) * 128 + (warp & 3) * 16 + (lane >> 2);
        if ((lane & 3) == 0) {
#pragma unroll
          for (int i = 0; i < 4; i++) st_rlx(dst + (i >> 1) * 64 + (i & 1) * 8, mark(__float_as_uint(d[2 * i]), tag & 1));
        }
        __syncwarp();
      }
      if (warp == 0) g_epoch[bid * 32 + lane] = tag;
    }
    return;
  }
#define Q_SLAB(J) ((J) < 8 ? ((J) + 8 - 2 * (hg & 4)) & 15 : 2 * (hg & 4) + 2 * ((J) & 3) + ((J) >> 2 & 1))
#define Q_AOFF(J) ((J) == 8 + (hg & 3) ? SM_X0 : (J) == 12 + (hg & 3) ? SM_X1 : ((J) & 3) * Q_STAGE)
#define Q_LOAD(J)                                                                                            \
  do {                                                                                                       \
    const uint32_t fb_ = bar + B_FULLQ + 8 * ((J) & 3);                                                      \
    const int k_ = Q_SLAB(J) * 64;                                                                           \
    mbar_expect_tx(fb_, Q_STAGE);                                                                            \
    mbar_arrive2(fb_);                                                                                       \
    tma2d(sb + Q_AOFF(J), &mX, k_, mb * 128, fb_);                                                           \
    tma4d(sb + ((J) & 3) * Q_STAGE + 16384, &mWq, 0, k_, hg * 2, 0, fb_);                                    \
  } while (0)
  if (warp >= 8) {
    asm volatile("setmaxnreg.dec.sync.aligned.u32 %0;" ::"n"(REG_H));
    const int lane = lane_id();
    const int f = (warp - 9) & 3;
    if (f == 3) {
      if (elect_one()) {
        PROF(0); PROFT(32);
#pragma unroll
        for (int s = 0; s < 3; s++) mbar_init(bar + B_FULLKV + 8 * s, 1);
      }
      __syncwarp();
      asm volatile("bar.arrive 14, 288;" ::: "memory");
      if (elect_one()) {
#pragma unroll
        for (int s = 0; s < 2; s++) {
          mbar_expect_tx(bar + B_FULLKV + 8 * s, KV_STAGE);
          tma2d(sb + s * KV_STAGE, &mX, (s + 1) * 64, mb * 128, bar + B_FULLKV + 8 * s);
          tma4d(sb + s * KV_STAGE + 16384, &mWkv, 0, (s + 1) * 64, hg * 2, 1, bar + B_FULLKV + 8 * s);
        }
      }
      __syncwarp();
    }
    const uint32_t ep = ld_rlx(g_epoch + bid * 32 + lane);
    if (f < 2) {
#pragma unroll
      for (int i = 0; i < 2; i++) {
        const uint4 u = __ldg((const uint4*)P.w_r + (f * 2 + i) * 32 + lane);
        sts128u(sb + SM_XSEL + (f * 2 + i) * 512 + lane * 16, u.x, u.y, u.z, u.w);
      }
    }
    bar_sync(13, 384);
    const uint32_t tag = ep + 1, par = tag & 1;
    const bool ffn = bid < NFFN;
    const int fb = bid, cu = bid >> 1, ch = bid & 1;
#define CS_STORE(SEC, C)                                                                                     \
  _Pragma("unroll") for (int r = 0; r < 3; r++) {                                                            \
    const uint32_t h0 = pack2(C.x, C.y), h1 = pack2(C.z, C.w);                                               \
    sts64u(sb + SM_CST + (SEC) * 1024 + (lane >> 4) * 512 + (lane & 1) * 8 + r * 128 + ((((lane & 15) >> 1) ^ (r + (lane >> 4) * 4)) << 4), h0, h1); \
    C.x -= bf_lo(h0); C.y -= bf_hi(h0); C.z -= bf_lo(h1); C.w -= bf_hi(h1);                                  \
  }
#define BAD4(U) ((U.x ^ par) | (U.y ^ par) | (U.z ^ par) | (U.w ^ par))
    const int n0 = f < 2 ? 0 : 2 * f - 3, ne = FFN_OFF || !ffn ? 3 : f == 3 ? 3 + G8 : 3 + GN;
    const uint32_t fsb = sb + SM_FST + ((f + 1) & 3) * 8192, fbar = bar + B_FST + f * 16, fst = fsb + (lane >> 4) * 2048 + (lane & 15) * 16;
    const CUtensorMap *ma = &mWc, *mc = &mWc;
    int sx = 1024 + cu * 32, sy = ch * 512 + f * 192, sdy = 32;
#define STAGEG(N)                                                                                            \
  do {                                                                                                       \
    if ((N) == 3) { ma = &mG; mc = &mU; sx = fb * 32; sy = f * (GN * 32);  sdy = 0; }                        \
    if ((N) < ne && elect_one()) {                                                                           \
      const uint32_t dst_ = fsb + ((N) & 1) * 4096, b_ = fbar + ((N) & 1) * 8;                               \
      mbar_expect_tx(b_, 4096);                                                                              \
      tma2d(dst_, ma, sx, sy, b_);                                                                           \
      tma2d(dst_ + 2048, mc, sx, sy + sdy, b_);                                                              \
    }                                                                                                        \
    sy += 32 + sdy;                                                                                          \
  } while (0)
    float a[8], gsum = 0.f, usum = 0.f;
    {
      if (f == 3) {
        if (elect_one()) {
          if (XS_EARLY) { mbar_expect_tx(bar + B_XST, 16384); tma3d(sb + SM_XST, &mXs, 0, bid * 16, 0, bar + B_XST); }
          mbar_expect_tx(bar + B_WPHI, 8192);
          tma2d(sb + SM_WPHI, &mPhi, 0, hg * 128, bar + B_WPHI);
          prefetch_map(&mWq); prefetch_map(&mWo); prefetch_map(&mWp); prefetch_map(&mD);
          PROF(31);
        }
        __syncwarp();
      } else {
        if (lane == 0) prefetch_map(f == 0 ? &mWc : f == 1 ? &mG : &mU);
        if (f == 2) ((float2*)g_y[par])[bid * 32 + lane] = make_float2(0.f, 0.f);
      }
      float st[13];
#pragma unroll
      for (int i = 0; i < 13; i++) st[i] = 0.f;
#pragma unroll 1
      for (int i = 0; i < 4; i++) {
        mbar_wait(bar + B_XST + 8 * (i >> 1), 0);
        if (f == 0 && lane == 0 && i == 0) PROF(1);
        const uint4 wu = lds128u(sb + SM_XSEL + i * 512 + lane * 16);
        const float wf[8] = {bf_lo(wu.x), bf_hi(wu.x), bf_lo(wu.y), bf_hi(wu.y), bf_lo(wu.z), bf_hi(wu.z), bf_lo(wu.w), bf_hi(wu.w)};
        st[12] += ((wf[0] + wf[1]) + (wf[2] + wf[3])) + ((wf[4] + wf[5]) + (wf[6] + wf[7]));
#pragma unroll
        for (int r = 0; r < 4; r++) {
          const uint4 u = lds128u(sb + SM_XST + i * 8192 + (4 * f + r) * 512 + lane * 16);
          const float xf[8] = {bf_lo(u.x), bf_hi(u.x), bf_lo(u.y), bf_hi(u.y), bf_lo(u.z), bf_hi(u.z), bf_lo(u.w), bf_hi(u.w)};
#pragma unroll
          for (int k = 0; k < 8; k++) { st[r] += xf[k]; st[4 + r] = fmaf(xf[k], xf[k], st[4 + r]); st[8 + r] = fmaf(xf[k], wf[k], st[8 + r]); }
        }
        if (i >= 2 && f < 3) STAGEG(n0 + i - 2);
      }
      const bool up = lane & 16, up2 = lane & 8;
#pragma unroll
      for (int q = 0; q < 3; q++) {
        const float k0 = up ? st[4 * q + 2] : st[4 * q], k1 = up ? st[4 * q + 3] : st[4 * q + 1];
        const float o0 = up ? st[4 * q] : st[4 * q + 2], o1 = up ? st[4 * q + 1] : st[4 * q + 3];
        const float m0 = k0 + __shfl_xor_sync(~0u, o0, 16), m1 = k1 + __shfl_xor_sync(~0u, o1, 16);
        a[q] = (up2 ? m1 : m0) + __shfl_xor_sync(~0u, up2 ? m0 : m1, 8);
      }
      a[3] = st[12] + __shfl_xor_sync(~0u, st[12], 16);
      a[3] += __shfl_xor_sync(~0u, a[3], 8);
#pragma unroll
      for (int o = 4; o; o >>= 1)
#pragma unroll
        for (int q = 0; q < 4; q++) a[q] += __shfl_xor_sync(~0u, a[q], o);
      if ((lane & 7) == 0) sts128(sb + SM_ROWS + (4 * f + (lane >> 3)) * 16, a[0], a[1], a[2], a[3]);
      if (f < 3) asm volatile("bar.arrive 7, 128;" ::: "memory");
    }
    if (f == 3) {
      bar_sync(7, 128);
      const int row = bid * 16 + (lane & 15);
      const float4 v = lds128(sb + SM_ROWS + (lane & 15) * 16);
      const float mf = v.x * (1.f / DM), mean = bf_round(mf), var = fmaxf(fmaf(-mf, mf, v.y * (1.f / DM)), 0.f);
      const float sd = bf_round(sqrt_approx(bf_round(bf_round(var) + 1e-5f)));
      const uint32_t rb = pack2(fmaf(-mean, v.w, v.z) * rcp(sd), 0.f) & 0xffffu, ord = (rb & 0x8000u) ? (~rb & 0xffffu) : (rb | 0x8000u);
      uint32_t best = __reduce_max_sync(~0u, (ord << 16) | (uint32_t)(2047 - row));
      if (lane < 16) st_rlx64(g_stat + row, ((unsigned long long)tag << 32) | __float_as_uint(mean) | (__float_as_uint(sd) >> 16));
      if (lane == 0) { asm volatile("red.relaxed.gpu.global.max.u64 [%0], %1;" ::"l"(g_best + bid), "l"(((unsigned long long)tag << 32) | best) : "memory"); PROF(17); }
#pragma unroll 1
      for (int n = 3; n < 5; n++) STAGEG(n);
      {
        uint4 xr[4];
        best = routed_row(P.x, tag, lane, xr);
#pragma unroll
        for (int i = 0; i < (GROWS + 255) / 256; i++) {
          const uint32_t dst = sb + SM_XSEL + i * 1024 + (lane >> 2) * 128 + (lane & 3) * 8;
          sts64(dst, bf_lo(xr[i].x), bf_lo(xr[i].z)); sts64(dst + 32, bf_hi(xr[i].x), bf_hi(xr[i].z));
          sts64(dst + 64, bf_lo(xr[i].y), bf_lo(xr[i].w)); sts64(dst + 96, bf_hi(xr[i].y), bf_hi(xr[i].w));
        }
        sts64u(sb + SM_RED + 16, tag, best);
        __syncwarp();
        if (lane == 0) { mbar_arrive(bar + B_XS); PROF(19); }
      }
      unsigned long long sv4[4];
      uint4 u[4];
#pragma unroll 1
      for (int it = 0; it < SPIN_MAX; it++) {
#pragma unroll
        for (int i = 0; i < 4; i++) { u[i] = ld_rlx128(g_cs + (1 + i) * 1024 + hg * 128 + lane * 4); sv4[i] = ld_rlx64(g_stat + mb * 128 + i * 32 + lane); }
        bool ok = ((BAD4(u[0]) | BAD4(u[1]) | BAD4(u[2]) | BAD4(u[3])) & 1) == 0;
#pragma unroll
        for (int i = 0; i < 4; i++) ok = ok && (uint32_t)(sv4[i] >> 32) == tag;
        if (__all_sync(~0u, ok)) break;
        __nanosleep(200);
      }
#pragma unroll
      for (int i = 0; i < 4; i++) {
        const uint32_t sv = (uint32_t)sv4[i], sd2 = (sv << 16) | (sv & 0xffffu);
        sts64(sb + SM_STAT + (i * 32 + lane) * 8, -bf_hi(sv), rcp(bf_lo(sv)));
        sts128u(sb + SM_SDT + lane * 64 + ((i ^ ((lane >> 1) & 3)) << 4), sd2, sd2, sd2, sd2);
      }
#pragma unroll
      for (int i = 0; i < 2; i++) {
        float4 c = make_float4(unmark(u[i].x) + unmark(u[i + 2].x), unmark(u[i].y) + unmark(u[i + 2].y), unmark(u[i].z) + unmark(u[i + 2].z),
                               unmark(u[i].w) + unmark(u[i + 2].w));
        CS_STORE(i, c);
      }
      fence_async_smem();
      bar_sync(8, 64);
      if (lane == 0) { mbar_arrive(bar + B_CS); PROF(10); }
    }
    {
      uint32_t xa = sb + SM_RED + 32, xstep = 0;
      const uint32_t zero = __float_as_uint(lds32(sb + SM_RED + 12));
#pragma unroll 1
      for (int ph = f == 3; ph < 2; ph++) {
#pragma unroll
        for (int j = 0; j < 8; j++) a[j] = 0.f;
        if (ph && f == 0) {
        {
          mbar_wait(bar + B_WPHI, 0);
          float nq[8] = {0.f, 0.f, 0.f, 0.f, 0.f, 0.f, 0.f, 0.f};
  #pragma unroll 2
          for (int r = 0; r < 16; r++) {
            const uint4 u = lds128u(sb + SM_WPHI + ((lane >> 2) * 16 + r) * 64 + (((lane ^ (r >> 1)) & 3) << 4));
            nq[0] = fmaf(bf_lo(u.x), bf_lo(u.x), nq[0]); nq[1] = fmaf(bf_hi(u.x), bf_hi(u.x), nq[1]); nq[2] = fmaf(bf_lo(u.y), bf_lo(u.y), nq[2]);
            nq[3] = fmaf(bf_hi(u.y), bf_hi(u.y), nq[3]); nq[4] = fmaf(bf_lo(u.z), bf_lo(u.z), nq[4]); nq[5] = fmaf(bf_hi(u.z), bf_hi(u.z), nq[5]);
            nq[6] = fmaf(bf_lo(u.w), bf_lo(u.w), nq[6]); nq[7] = fmaf(bf_hi(u.w), bf_hi(u.w), nq[7]);
          }
          uint32_t m = 0;
  #pragma unroll
          for (int i = 0; i < 8; i++) m = max(m, __float_as_uint(nq[i] + __shfl_xor_sync(~0u, nq[i], 4)) & 0x7fffffffu);
          sts32(sb + SM_RED + 24, 4.2f * __uint_as_float(__reduce_max_sync(~0u, m)));
        }
          asm volatile("bar.arrive 8, 64;" ::: "memory");
        }
        if (ph) { mbar_wait(bar + B_XS, 0); xa = sb + SM_XSEL + f * (GN * 128) + ((lane >> 2) & 3) * 32; xstep = 128; }
#pragma unroll 1
        for (int n = ph ? 3 : n0; n < (ph ? ne : 3); n++) {
          const float4 x0 = lds128(xa), x1 = lds128(xa + 16);
          xa += xstep;
          mbar_wait(fbar + (n & 1) * 8, ((n - n0) >> 1) & 1);
          uint4 u[8];
#pragma unroll
          for (int j = 0; j < 8; j++) u[j] = lds128u(fst + (n & 1) * 4096 + j * 256);
          FMA8(a, u[0], x0.x); FMA8(a, u[1], x0.y); FMA8(a, u[2], x0.z); FMA8(a, u[3], x0.w);
          if (__any_sync(~0u, ((u[4].x | u[5].x | u[6].x | u[7].x | __float_as_uint(a[0]) | __float_as_uint(a[7])) & zero) == 0)) STAGEG(n + 2);
          FMA8(a, u[4], x1.x); FMA8(a, u[5], x1.y); FMA8(a, u[6], x1.z); FMA8(a, u[7], x1.w);
        }
#pragma unroll
        for (int o = 4; o <= 8; o <<= 1)
#pragma unroll
          for (int j = 0; j < 8; j++) a[j] += __shfl_xor_sync(~0u, a[j], o);
        if (ph && lane == 0) mbar_arrive(bar + B_FFN);
        const uint32_t red = ph ? sb + SM_GRED : sb + SM_RED + 64;
        if ((lane & 12) == 0) {
          const uint32_t d = red + f * 256 + (lane >> 4) * 128 + (lane & 3) * 32;
          sts128(d, a[0], a[1], a[2], a[3]); sts128(d + 16, a[4], a[5], a[6], a[7]);
        }
        if (f != 2) {
          asm volatile("bar.arrive %0, %1;" ::"r"(4 + ph), "r"(96 + 32 * ph) : "memory");
        } else {
          bar_sync(4 + ph, 96 + 32 * ph);
          const uint32_t ra = red + lane * 4;
          gsum = lds32(ra) + lds32(ra + 256) + lds32(ra + 512);
          usum = lds32(ra + 128) + lds32(ra + 384) + lds32(ra + 640);
          if (!ph) st_rlx(g_cs + 1024 + ch * 2048 + cu * 32 + lane, mark(__float_as_uint(gsum + usum), par));
          else { gsum += lds32(ra + 768); usum += lds32(ra + 896); }
          if (lane == 0) PROF(ph ? 34 : 18);
        }
      }
    }
    if (f == 3) {
      if (elect_one()) {
        PROF(7);
        mbar_wait(bar + B_FULLQ, 0);
#pragma unroll 1
        for (int j = 3; j < 16; j++) {
          mbar_wait(bar + (j < 4 ? B_EMPTYKV + 16 : B_EMPTYQ + 8 * (j & 3)), ((j >> 2) & 1) ^ 1);
          if (j == 12 + (hg & 3)) mbar_wait(bar + B_KVST + 8, 0);
          Q_LOAD(j);
        }
        PROF(47);
        mbar_expect_tx(bar + B_DN, 65536);
#pragma unroll 1
        for (int i = 0; i < 4; i++) {
          mbar_wait(bar + B_EMPTYQ + 8 * i, 1);
          tma3d(sb + i * Q_STAGE, &mD, 0, fb * 32, i * 4, bar + B_DN);
        }
        PROF(48);
#pragma unroll 1
        for (int i = 0; i < 16; i++) {
          const int s = i & 3, n = i < 9 ? i - 2 : i - 9, kb = i < 2 ? 2 * hg + i : 2 * (n + (n >= hg)) + (i >= 9);
          if (i >= 4) mbar_wait(bar + B_EMPTYQ + 8 * s, ((i >> 2) & 1) ^ 1);
          mbar_expect_tx(bar + B_FULLQ + 8 * s, 16384);
          if (i < 2) {
            mbar_arrive2(bar + B_FULLQ + 8 * s);
            tma3d(sb + s * Q_STAGE + 16384, &mWo, 0, kb * 64, hg * 2, bar + B_FULLQ + 8 * s);
          } else {
            tma5d(sb + s * Q_STAGE + 16384, &mWp, hg * 128, kb * 2, bar + B_FULLQ + 8 * s);
            tma5d(sb + s * Q_STAGE + 24576, &mWp, hg * 128 + 64, kb * 2, bar + B_FULLQ + 8 * s);
            if (i >= 3) {
              if (i == 3) { mbar_wait(bar + B_DND, 0); PROF(14); }
#pragma unroll 1
              for (int a = i == 3 ? 2 : i; a <= i; a++) {
                const uint4* src = g_ofr + (mb * 16 + (a == 2 ? (hg == 0 ? 2 : 0) : kb)) * 1024;
#pragma unroll
                for (int h = 0; h < 2; h++) {
                  mbar_expect_tx(bar + B_AIN + (a & 3) * 16 + h * 8, 8192);
                  bulk_load(sb + (a & 3) * Q_STAGE + h * 8192, src + h * 512, 8192, bar + B_AIN + (a & 3) * 16 + h * 8);
                }
              }
            }
          }
        }
      }
    } else {
      if (f == 2) {
        if (PFD && ffn) {
#pragma unroll 1
          for (int i = 0; i < 16; i++) { touch_l2((const char*)P.w_down + fb * 65536 + i * 4096 + lane * 128, lane); __nanosleep(PFD); }
        }
        {
#pragma unroll 1
          for (int i = 0; i < 8; i++) { touch_l2((const char*)P.wo + ((mb & 7) * 128 + i * 16 + (lane >> 1)) * 2048 + hg * 256 + (lane & 1) * 128, lane); __nanosleep(PFD); }
        }
        asm volatile("cp.async.wait_all;" ::: "memory");
        uint4 u;
#pragma unroll 1
        for (int it = 0; it < SPIN_MAX; it++) {
          u = ld_rlx128(g_cs + hg * 128 + lane * 4);
          if (__all_sync(~0u, !(BAD4(u) & 1))) break;
          __nanosleep(200);
        }
        mbar_wait(bar + B_PHI, 0);
        float4 c = make_float4(unmark(u.x), unmark(u.y), unmark(u.z), unmark(u.w));
        CS_STORE(2, c);
        fence_async_smem();
        __syncwarp();
        if (lane == 0) mbar_arrive(bar + B_CSQ);
      }
      const uint32_t target = __shfl_sync(~0u, tag, 0) * 16;
#pragma unroll 1
      for (int R = 0; R < 2; R++) {
        const uint32_t own = (hg * 2 + R) * 16 + mb, pst = sb + (R ? SM_PST1 : SM_PST0);
        if (f == R) {
          mbar_wait(bar + B_KVST + 8 * R, 0);
          if (f == 1 && lane == 0) PROF(11);
          wait_hint(XC1(hg, R) + mb, target);
          if (elect_one()) {
            PROF(35 + R);
            fence_async_global();
            mbar_expect_tx(bar + B_PART + 8 * R, 8192);
            bulk_load(pst, g_part + own * 512, 8192, bar + B_PART + 8 * R);
          }
          __syncwarp();
          uint4 uz;
#pragma unroll 1
          for (int it = 0; it < SPIN_MAX; it++) {
            uz = ld_rlx128(g_zpart + own * 128 + lane * 4);
            if (__all_sync(~0u, !(BAD4(uz) & 1))) break;
          }
          const bool b1 = lane & 2, b2 = lane & 4;
          const float z0 = unmark(b1 ? uz.z : uz.x) + __shfl_xor_sync(~0u, unmark(b1 ? uz.x : uz.z), 2);
          const float z1 = unmark(b1 ? uz.w : uz.y) + __shfl_xor_sync(~0u, unmark(b1 ? uz.y : uz.w), 2);
          float z = (b2 ? z1 : z0) + __shfl_xor_sync(~0u, b2 ? z0 : z1, 4);
          z += __shfl_xor_sync(~0u, z, 8);
          z += __shfl_xor_sync(~0u, z, 16);
          if (lane < 8) {
            const uint32_t ft = (own & 7) * 8 + (lane & 1) * 4 + (lane & 2) + (lane >> 2), zz = pack2(z, 1.f);
            const uint32_t pos = (own >> 3) * 64 + (ft & 15) * 4 + (((ft >> 4) ^ (ft >> 1)) & 3);
            st_rlx128(g_zres[par] + pos, zz, zz, zz, zz);
            g_zres[par ^ 1][pos] = make_uint4(0u, 0u, 0u, 0u);
          }
          if (lane == 0) red_inc(XC2(hg, R));
          __syncwarp();
        }
        if (f == R || f == R + 1) {
          const uint32_t hf = f - R, m1 = ~lane & 1, gq = hf * 4 + (lane >> 3), ts = (lane >> 1) & 3;
          float a0 = 0.f, a1 = 0.f, a2 = 0.f, a3 = 0.f;
          mbar_wait(bar + B_PART + 8 * R, 0);
#pragma unroll 1
          for (int it = 0; it < SPIN_MAX; it++) {
            uint32_t bad = 0;
            a0 = a1 = a2 = a3 = 0.f;
#pragma unroll 1
            for (int b = 0; b < 16; b += 8) {
              uint2 u[8];
              if (it == 0) {
#pragma unroll
                for (int i = 0; i < 8; i++) { const float2 v = lds64(pst + (b + i) * 512 + hf * 256 + lane * 8); u[i] = make_uint2(__float_as_uint(v.x), __float_as_uint(v.y)); }
              } else {
#pragma unroll
                for (int i = 0; i < 8; i++) {
                  const unsigned long long v = ld_rlx64((const unsigned long long*)g_part + own * 1024 + (b + i) * 64 + hf * 32 + lane);
                  u[i] = make_uint2((uint32_t)v, (uint32_t)(v >> 32));
                }
              }
#pragma unroll
              for (int i = 0; i < 8; i++) {
                bad |= u[i].x ^ par;
                a0 += bf_lo(i & 1 ? u[i].x & ~m1 : u[i].x | m1); a1 += bf_hi(u[i].x); a2 += bf_lo(u[i].y); a3 += bf_hi(u[i].y);
              }
            }
            if (__all_sync(~0u, !(bad & m1))) break;
          }
          uint32_t* dst = (uint32_t*)g_res[par] + own * 128 + gq * 16 + ts;
          const uint32_t j0 = (lane & 1) * 2, vb = ts == (gq >> 1);
          st_rlx(dst + ((j0 ^ (gq >> 1)) & 3) * 4, pack2(a0, a1) | vb);
          st_rlx(dst + (((j0 + 1) ^ (gq >> 1)) & 3) * 4, pack2(a2, a3) | vb);
          ((uint2*)g_res[par ^ 1])[own * 64 + hf * 32 + lane] = make_uint2(0u, 0u);
          __syncwarp();
          if (lane == 0) { red_inc(XC2(hg, R)); if (!hf) PROF(R ? 12 : 30); }
        }
      }
      if (f == 2) {
        if (ffn && !FFN_OFF) {
#pragma unroll 1
          for (int it = 0; it < SPIN_MAX; it++) {
            const uint32_t pg = ld_rlx((const uint32_t*)g_gp + fb * 32 + lane), pu = ld_rlx((const uint32_t*)g_gp + FF + fb * 32 + lane);
            if (__all_sync(~0u, !(((pg ^ par) | (pu ^ par)) & 1))) { gsum += unmark(pg); usum += unmark(pu); break; }
            __nanosleep(200);
          }
        }
        const float h = bf_round(silu_f(bf_round(gsum))) * bf_round(usum);
        const uint32_t h2 = pack2(h, h);
        sts128u(sb + SM_HT + lane * 16, h2, h2, h2, h2);
        fence_async_smem();
        __syncwarp();
        if (lane == 0) { mbar_arrive(bar + B_H); PROF(20); }
      }
      if (f < 2) {
        wait_hint(XC2(hg, f), 3 * target);
        mbar_wait(bar + B_KVST + 8, 0);
        if (lane == 0) PROF(40 + f);
#pragma unroll 1
        for (int it = 0; it < SPIN_MAX; it++) {
          if (elect_one()) {
            fence_async_global();
            mbar_expect_tx(bar + B_RES + 8 * f, 8192 + 2048);
            bulk_load(sb + SM_V + f * 8192, g_res[par] + (hg * 4 + f * 2) * 256, 8192, bar + B_RES + 8 * f);
            bulk_load(sb + SM_ZT + f * 2048, g_zres[par] + (hg * 4 + f * 2) * 64, 2048, bar + B_RES + 8 * f);
          }
          __syncwarp();
          mbar_wait(bar + B_RES + 8 * f, it & 1);
          uint32_t ok = ~0u;
#pragma unroll
          for (int i = 0; i < 16; i++) ok &= __float_as_uint(lds32(sb + SM_V + f * 8192 + i * 512 + lane * 16 + (lane >> 3) * 4));
#pragma unroll
          for (int i = 0; i < 4; i++) ok &= __float_as_uint(lds32(sb + SM_ZT + f * 2048 + i * 512 + lane * 16 + (lane >> 3) * 4)) >> 23;
          if (__all_sync(~0u, ok & 1)) break;
        }
        if (lane == 0) { mbar_arrive(bar + B_TILE + 8 * f); PROF(f ? 13 : 27); }
      }
      if (f < 2) {
        uint32_t phases = 0;
#pragma unroll 1
        for (int i = 2; i < 16; i++) {
          const int s = i & 3;
          const uint32_t ab = bar + B_AIN + s * 16 + f * 8, slot = sb + s * Q_STAGE + f * 8192;
#pragma unroll 1
          for (int it = 0; it < SPIN_MAX; it++) {
            mbar_wait(ab, (phases >> s) & 1);
            phases ^= 1u << s;
            uint32_t bad = 0;
#pragma unroll
            for (int n = 0; n < 8; n++) bad |= __float_as_uint(lds32(slot + n * 1024 + lane * 32 + (lane >> 2) * 4)) ^ par;
            if (__all_sync(~0u, !(bad & 1))) break;
            if (elect_one()) {
              const int n = i < 9 ? i - 2 : i - 9, kb = 2 * (n + (n >= hg)) + (i >= 9);
              PROF(49);
              mbar_expect_tx(ab, 8192);
              bulk_load(slot, g_ofr + (mb * 16 + kb) * 1024 + f * 512, 8192, ab);
            }
            __syncwarp();
          }
          if (lane == 0) { mbar_arrive(bar + B_FULLQ + 8 * s); if (i == 2 && f == 0) PROF(15); }
        }
        if (f == 0) g_epoch[bid * 32 + lane] = tag;
      } else {
        if (elect_one()) {
          prefetch_map(&mOut);
          if (ffn) { mbar_wait(bar + B_YD, 0); red_rel(g_ycnt); PROF(21); }
        }
        __syncwarp();
        if (f == 2) {
          const uint32_t best = __float_as_uint(lds32(sb + SM_RED + 20));
          const int sel = 2047 - (best & 0x7ff) - mb * 128;
          if (sel >= 0 && sel < 128) {
            const uint2 xr = __ldg((const uint2*)(P.x + (size_t)(mb * 128 + sel) * DM + hg * 128 + lane * 4));
            const float2 st = lds64(sb + SM_STAT + sel * 8);
            const uint32_t ord = best >> 16, rb = (ord & 0x8000u) ? (ord & 0x7fffu) : (~ord & 0xffffu);
            const float sg = rcp(1.f + ex2(-1.4426950408889634f * bf_lo(rb)));
            const uint32_t sg2 = pack2(sg, sg), nm2 = pack2(st.x, st.x);
            wait_cnt<0>(g_ycnt, tag * NFFN);
            float4 y = make_float4(0.f, 0.f, 0.f, 0.f);
#pragma unroll
            for (int i = 0; i < 8; i++) {
              const float4 c = ldg_cg4(g_y[par ^ 1][i] + hg * 128 + lane * 4);
              y.x += c.x; y.y += c.y; y.z += c.z; y.w += c.w;
            }
            uint32_t o[2];
#pragma unroll
            for (int i = 0; i < 2; i++) {
              const uint32_t d = badd2(i ? xr.y : xr.x, nm2);
              const uint32_t tt = badd2(pack2(bf_lo(d) * st.y, bf_hi(d) * st.y), bmul2(i ? pack2(y.z, y.w) : pack2(y.x, y.y), sg2));
              o[i] = pack2(silu_f(bf_lo(tt)), silu_f(bf_hi(tt)));
            }
            sts64u(sb + SM_UPD + lane * 8, o[0], o[1]);
          }
          if (lane == 0) sts32(sb + SM_UPD + 256, __int_as_float(sel));
          __syncwarp();
          if (lane == 0) { mbar_arrive(bar + B_UPD); PROF(22); }
        }
      }
    }
  } else {
    const int t7 = threadIdx.x & 127;
    const char* pfa = warp < 4 ? (const char*)P.x + bid * 32768 + (t7 & 15) * 2048 + (t7 >> 4) * 128
                               : (const char*)P.wqkv + (size_t)((t7 >> 4) * 64 + (bid >> 1)) * 6144 + 2048 + (bid & 1) * 2048 + (t7 & 15) * 128;
    if (t7 >= 16 && t7 < 16 * PF_FIRST) prefetch_l2(pfa);
    if (warp < 7) sts128(sb + SM_CST + threadIdx.x * 16, 0.f, 0.f, 0.f, 0.f);
    else sts32(sb + SM_RED + (threadIdx.x & 15) * 4, threadIdx.x & 8 ? 1.f : 0.f);
    if (elect_one()) {
#pragma unroll 1
      for (uint32_t b = B_FST + warp * 8; b < B_END; b += 64)
        mbar_init(bar + b, b < B_FULLQ ? 1 : b < B_FFN ? 3 : b < B_EMPTYKV ? 4 : 8);
    }
    __syncwarp();
    asm volatile("bar.arrive 13, 384;" ::: "memory");
    asm volatile("setmaxnreg.inc.sync.aligned.u32 %0;" ::"n"(REG_C));
    if (t7 >= 16 * PF_FIRST && threadIdx.x < 128 + 16 * PF_W) prefetch_l2(pfa);
    asm volatile("cp.async.wait_all;" ::: "memory");
    fence_async_smem();
    bar_sync(14, 288);
    if (threadIdx.x == 0) mbar_arrive(bar + B_FULLKV + 16);
    const int lane = lane_id();
    const int wg = warp >> 2, w = warp & 3, g = lane >> 2, t = lane & 3;
    float kv[128];
    {
      uint32_t s = 2, ph = 0, sp = 0, php = 0;
#pragma unroll 1
      for (int j = 0; j < 15; j++) {
        PW0(32 + j); mbar_wait(bar + B_FULLKV + 8 * s, ph); PW1(32 + j);
        if (wg == 1) bar_sync(10 + s, 256);
        wg_fence();
        const uint32_t hA = fresh_hi<H128>(P.zA), hB = fresh_hi<H128>(P.zB);
        wgmma_n256_ssp_ta0_tb1(kv, mkdesch(sb, 16, hA, wg * 512 + s * (KV_STAGE / 16)), mkdesch(sb + 16384, 8192, hB, s * (KV_STAGE / 16)), j);
#pragma unroll
        for (int k = 1; k < 4; k++)
          wgmma_n256_ss_ta0_tb1(kv, mkdesch(sb + k * 32, 16, hA, wg * 512 + s * (KV_STAGE / 16)),
                                mkdesch(sb + 16384 + k * 2048, 8192, hB, s * (KV_STAGE / 16)), 1);
        wg_commit();
        if (wg == 0) asm volatile("bar.arrive %0, 256;" ::"r"(10 + s) : "memory");
        if (warp == 0 && j) {
          mbar_wait(bar + B_EMPTYKV + 8 * sp, php);
          if (elect_one()) {
            if (j < 14) {
              mbar_expect_tx(bar + B_FULLKV + 8 * sp, KV_STAGE);
              tma2d(sb + sp * KV_STAGE, &mX, (j + 2) * 64, mb * 128, bar + B_FULLKV + 8 * sp);
              tma4d(sb + sp * KV_STAGE + 16384, &mWkv, 0, (j + 2) * 64, hg * 2, 1, bar + B_FULLKV + 8 * sp);
            } else {
              Q_LOAD(0);
            }
            if (j < 3 - XS_EARLY) {
              const int xh = j - 1 + XS_EARLY;
              mbar_expect_tx(bar + B_XST + 8 * xh, 16384);
              tma3d(sb + SM_XST + xh * 16384, &mXs, 0, bid * 16, 2 * xh, bar + B_XST + 8 * xh);
            }
          }
          __syncwarp();
        }
        if (j == 0) {
          if (wg == 0) prefetch_l2(pfa + 1024);
        } else if (wg == 1) {
          if (j < 3) {
            if (j == 2 || t7 >= 16 * PF_W) prefetch_l2(pfa + (j - 1) * (8 * 393216));
          } else if (j == 13) {
            prefetch_l2((const char*)P.wo + bid * 16384 + t7 * 128);
          }
        }
        wg_wait<0>();
        if (lane == 0) mbar_arrive(bar + B_EMPTYKV + 8 * s);
        sp = s; php = ph;
        ph ^= s == 1;
        s = s == 2 ? 0 : s + 1;
      }
    }
    const int lrow = wg * 64 + w * 16 + (lane & 15);
    const uint32_t sw128 = lrow * 128, x128 = (lrow & 7), hi16 = lane >> 4;
    mbar_wait(bar + B_CS, 0);
    const uint32_t tag = __float_as_uint(lds32(sb + SM_RED + 16));
    const int zero = __float_as_int(lds32(sb + SM_RED + 12));
    const float wn = lds32(sb + SM_RED + 24);
    const float2 st0 = lds64(sb + SM_STAT + (wg * 64 + w * 16 + g) * 8), st1 = lds64(sb + SM_STAT + (wg * 64 + w * 16 + g + 8) * 8);
    const float c0 = st0.y * 1.4426950408889634f, c1 = st1.y * 1.4426950408889634f;
    const uint32_t nm20 = pack2(st0.x, st0.x), nm21 = pack2(st1.x, st1.x), fmask = t == 0 ? ~0u : t == 1 ? 0xffffu : 0u;
    const uint32_t fa0 = nm20 & fmask, fa1 = nm21 & fmask;
    asm volatile("cp.async.wait_all;" ::: "memory");
    PW0(47); mbar_wait(bar + B_FULLKV + 16, 1); PW1(47);
    wg_fence();
    wgmma_n256_rs_ta0_tb1(kv, fa0, fa1, 0u, 0u, mkdesc(sb + SM_CST, 512, 0, 1), 1);
    {
      const uint32_t hA = fresh_hi<H128>(P.zA), hB = fresh_hi<H128>(P.zB);
#pragma unroll
      for (int k = 0; k < 4; k++)
        wgmma_n256_ss_ta0_tb1(kv, mkdesch(sb + 2 * KV_STAGE + k * 32, 16, hA, wg * 512), mkdesch(sb + 2 * KV_STAGE + 16384 + k * 2048, 8192, hB), 1);
    }
    wg_commit();
    if (warp == 0) {
      mbar_wait(bar + B_EMPTYKV + 8, 0);
      if (elect_one()) {
#pragma unroll 1
        for (int j = 1; j < 3; j++) Q_LOAD(j);
      }
      __syncwarp();
    }
    wg_wait<0>();
    reg_fence<128>(kv);
    if (lane == 0) mbar_arrive(bar + B_EMPTYKV + 16);
    PROFC(2);
    float q[64];
#define QMMA(J, AOFF16, ACCUM)                                                                                     \
  do {                                                                                                             \
    const uint32_t hA_ = fresh_hi<H128>(P.zA), hB_ = fresh_hi<H128>(P.zB);                                         \
    _Pragma("unroll") for (int k = 0; k < 4; k++)                                                                  \
      wgmma_n128_ss_ta0_tb1(q, mkdesch(sb + k * 32, 16, hA_, wg * 512 + (AOFF16)),                                 \
                            mkdesch(sb + 16384 + k * 2048, 8192, hB_, ((J) & 3) * (Q_STAGE / 16)), k ? 1 : (ACCUM)); \
  } while (0)
#define QWAIT(J) do { PW0(J); mbar_wait(bar + B_FULLQ + 8 * ((J) & 3), ((J) >> 2) & 1); PW1(J); } while (0)
#define QSTEP_A(J, AOFF16, ACCUM) do { QWAIT(J); wg_fence(); QMMA(J, AOFF16, ACCUM); wg_commit(); } while (0)
#define QREL(J) do { if (lane == 0) mbar_arrive(bar + B_EMPTYQ + 8 * ((J) & 3)); } while (0)
#define Q_OFF16(J) ((J) >= 8 && (J) < 16 ? Q_AOFF(J) / 16 : ((J) & 3) * (Q_STAGE / 16))
#define QPLAIN(J) do { QSTEP_A(J, Q_OFF16(J), 1); wg_wait<1>(); QREL((J) - 1); } while (0)
#define QNEXT(J) do { QPLAIN(J); SCHED_FENCE(); } while (0)
#define PHI_PROJ(DST, SRC, H0, H1)                                                                                 \
  do {                                                                                                             \
    uint32_t a_[32];                                                                                               \
    _Pragma("unroll") for (int j = 8 * (H0); j < 8 * (H1); j++) {                                                  \
      a_[j] = pack2(SRC[2 * j], SRC[2 * j + 1]);                                                                   \
      asm volatile("fma.rn.bf16x2 %0, %1, %1, %0;" : "+r"(nq[(j >> 4) * 2 + (j & 1)]) : "r"(a_[j]));               \
    }                                                                                                              \
    wg_fence();                                                                                                    \
    const uint32_t hB_ = fresh_hi<H64>(P.zB);                                                                      \
    _Pragma("unroll") for (int hk = 2 * (H0); hk < 2 * (H1); hk++)                                                 \
        wgmma_n32_rs_ta0_tb1(DST + 16 * (hk >> 1), a_[4 * hk], a_[4 * hk + 1], a_[4 * hk + 2], a_[4 * hk + 3],     \
                             mkdesch(sb + SM_WPHI + hk * 1024, 16, hB_), hk & 1);                                \
    wg_commit();                                                                                                   \
  } while (0)
    {
      float p[64], ea[24], eb[24], sa[4], sc[4], kz[20];
      uint32_t vp[32];
#pragma unroll
      for (int j = 0; j < 32; j++) vp[j] = pack2(kv[64 + 2 * j], kv[65 + 2 * j]);
      const uint32_t vr = w * 16 + (lane & 15), vb = sb + SM_V + wg * 4096 + vr * 64, x64 = (vr >> 1) & 3;
#define V_STORE(R)                                                                                           \
  _Pragma("unroll") for (int j = 0; j < 4; j++)                                                              \
      stsm4(vb + (j >> 1) * 8192 + ((((j & 1) * 2 + hi16) ^ x64) << 4), vp[16 * (R) + 4 * j], vp[16 * (R) + 4 * j + 1], vp[16 * (R) + 4 * j + 2], vp[16 * (R) + 4 * j + 3])
      V_STORE(0);
      mbar_wait(bar + B_WPHI, 0);
      {
        uint32_t nq[4] = {0u, 0u, 0u, 0u};
        PHI_PROJ(p, kv, 0, 4);
        QSTEP_A(0, 0, 0);
        const bool unsafe = softmax_unsafe(nq, c0 * c0 * wn, c1 * c1 * wn);
        wg_wait<1>();
        reg_fence<64>(p);
        if (__builtin_expect(unsafe, 0)) softmax_shift(p, c0, c1);
      }
#define K_NORM(S) do { quad_sum<4>(S); _Pragma("unroll") for (int i = 0; i < 4; i++) S[i] = rcp(S[i]) * ((i & 1) ? st1.y : st0.y); } while (0)
#define K_STORE(SLOT, E, S) K_STORE_(SLOT, E, S, 0, 2)
#define K_STORE_(SLOT, E, S, J0, J1)                                                                         \
  _Pragma("unroll") for (int j = (J0); j < (J1); j++) {                                                      \
    uint32_t fp[4], fm[4];                                                                                   \
    _Pragma("unroll") for (int i = 0; i < 4; i++) {                                                          \
      const float e0 = E[8 * j + 2 * i], e1 = E[8 * j + 2 * i + 1], r = E[16 + 4 * j + i] * S[2 + (i & 1)];  \
      const uint32_t e2 = pack2(e0, e1);                                                                     \
      fp[i] = bmul2(e2, pack2(S[i & 1], S[i & 1]));                                                          \
      fm[i] = bmul2(e2, pack2(r, r));                                                                        \
    }                                                                                                        \
    stsm4(sb + SM_PHI + (SLOT) * 16384 + sw128 + (((2 * j + hi16) ^ x128) << 4), fp[0], fp[1], fp[2], fp[3]); \
    stsm4(sb + SM_PHI + (SLOT) * 16384 + sw128 + (((4 + 2 * j + hi16) ^ x128) << 4), fm[0], fm[1], fm[2], fm[3]); \
  }
#define KV_MMA(R)                                                                                            \
  do {                                                                                                       \
    mbar_wait(bar + B_PHI + 8 * (R), 0);                                                                     \
    wg_fence();                                                                                              \
    const uint32_t hA_ = fresh_hi<H128>(P.zA), hB_ = fresh_hi<H64>(P.zB);                                    \
    _Pragma("unroll") for (int k = 0; k < 8; k++) {                                                          \
      const uint32_t vs = SM_V + (k >> 2) * 4096 + (k & 3) * 1024;                                           \
      wgmma_n40_ss_ta1_tb1(kz, mkdesch(sb + SM_PHI + k * 2048, 16, hA_, wg * 1024),                       \
                           mkdesch(sb + vs, SM_SDT + (k & 1) * 1024 + (k >> 1) * 16 - vs, hB_, wg * (512u - (512u << 16))), k); \
    }                                                                                                        \
    wg_commit();                                                                                             \
  } while (0)
#define QKV(J, R) do { KV_MMA(R); QSTEP_A(J, Q_OFF16(J), 1); wg_wait<2>(); QREL((J) - 1); SCHED_FENCE(); } while (0)
#define KV_SEND(R)                                                                                           \
  do {                                                                                                       \
    reg_fence<20>(kz);                                                                                       \
    if (lane == 0) mbar_arrive(bar + B_KVST + 8 * (R));                                                      \
    const uint32_t slot = ((hg * 2 + (R)) * 16 + warp * 2) * 16 + mb;                                        \
    _Pragma("unroll") for (int u = 0; u < 2; u++)                                                            \
      st_rlx128(g_part + (slot + u * 16) * 32 + lane, mark(pack2(kz[2 * u], kz[2 * u + 1]), tag & 1), pack2(kz[2 * u + 4], kz[2 * u + 5]), \
                pack2(kz[2 * u + 8], kz[2 * u + 9]), pack2(kz[2 * u + 12], kz[2 * u + 13]));                 \
    if (t < 2) st_rlx(g_zpart + (slot + t * 16) * 8 + g, mark(__float_as_uint(t ? kz[18] : kz[16]), tag & 1)); \
    if (lane < 2) red_inc(XC1(hg, R) + warp * 2 + lane);                                                          \
  } while (0)
#define K_PUB(R) do { fence_async_smem(); __syncwarp(); if (lane == 0) mbar_arrive(bar + B_PHI + 8 * (R)); } while (0)
#define S_PIN(S) SCHED_PIN(S[0] + S[1] + S[2] + S[3])
      k_exp(p, c0, c1, ea, sa);
      S_PIN(sa);
      QNEXT(1);
      K_NORM(sa);
      k_exp<0, 4>(p + 16, c0, c1, eb, sc);
      mbar_wait(bar + B_FFN, 0);
      K_STORE_(0, ea, sa, 0, 1);
      S_PIN(sc);
      QNEXT(2);
      K_STORE_(0, ea, sa, 1, 2);
      k_exp<4, 8>(p + 16, c0, c1, eb, sc);
      K_NORM(sc);
      S_PIN(sc);
      QNEXT(3);
      K_STORE(1, eb, sc);
      K_PUB(0);
      k_exp<0, 4>(p + 32, c0, c1, ea, sa);
      S_PIN(sa);
      QKV(4, 0);
      k_exp<4, 8>(p + 32, c0, c1, ea, sa);
      K_NORM(sa);
      S_PIN(sa);
      wg_wait<1>();
      KV_SEND(0);
      QNEXT(5);
      k_exp(p + 48, c0, c1, eb, sc);
      S_PIN(sc);
      QNEXT(6);
      K_NORM(sc);
      mbar_wait(bar + B_KVST, 0);
      V_STORE(1);
      K_STORE(0, ea, sa);
      QNEXT(7);
      K_STORE(1, eb, sc);
      K_PUB(1);
      QKV(8, 1);
      QNEXT(9);
      KV_SEND(1);
    }
    PROFC(3);
#pragma unroll 1
    for (int j = 10; j < 15; j++) QPLAIN(j);
    mbar_wait(bar + B_CSQ, 0);
    QWAIT(15);
    if (wg == 1) bar_sync(6, 256);
    wg_fence();
    wgmma_n128_rs_ta0_tb1(q, fa0, fa1, 0u, 0u, mkdesc(sb + SM_CST + 2048, 512, 0, 1), 1);
    QMMA(15, Q_AOFF(15) / 16, 1);
    wg_commit();
    if (wg == 0) asm volatile("bar.arrive 6, 256;" ::: "memory");
    wg_wait<1>();
    QREL(14);
    wg_wait<0>();
    QREL(15);
    reg_fence<64>(q);
    PROFC(5);
    float yp[4];
    const uint32_t par = tag & 1;
    uint4* ofr = g_ofr + (mb * 16 + hg * 2) * 1024 + (warp * 16 + g) * 8;
#define O_MMA(H, F, N)                                                                                       \
  do {                                                                                                       \
    wg_fence();                                                                                              \
    const uint32_t hB_ = fresh_hi<H64>(P.zB);                                                                \
    _Pragma("unroll") for (int k = 0; k < 4; k++) {                                                          \
      const uint32_t ks = SM_V + (H) * 4096 + k * 1024;                                                      \
      wgmma_n40_rs_ta0_tb1(N + 20 * (k >> 1), F[4 * k], F[4 * k + 1], F[4 * k + 2], F[4 * k + 3],            \
                           mkdesch(sb + ks, SM_ZT + (H) * 1024 + k * 16 - ks, hB_), k & 1);                \
    }                                                                                                        \
    wg_commit();                                                                                             \
  } while (0)
#define O_FIN(H, N, o)                                                                                        \
  do {                                                                                                       \
    reg_fence<40>(N);                                                                                        \
    const float *np = N, *nm = N + 20;                                                                       \
    const float d0 = rcp(fmaf(np[16], nm[17], fmaf(nm[16], np[17], 1e-6f * np[17] * nm[17])));               \
    const float d1 = rcp(fmaf(np[18], nm[19], fmaf(nm[18], np[19], 1e-6f * np[19] * nm[19])));               \
    const float bp0 = nm[17] * d0, bm0 = np[17] * d0, bp1 = nm[19] * d1, bm1 = np[19] * d1;                  \
    _Pragma("unroll") for (int j = 0; j < 4; j++) {                                                          \
      o[2 * j] = pack2(fmaf(np[4 * j], bp0, nm[4 * j] * bm0), fmaf(np[4 * j + 1], bp0, nm[4 * j + 1] * bm0)); \
      o[2 * j + 1] = pack2(fmaf(np[4 * j + 2], bp1, nm[4 * j + 2] * bm1), fmaf(np[4 * j + 3], bp1, nm[4 * j + 3] * bm1)); \
    }                                                                                                        \
  } while (0)
#define O_STG(H, o)                                                                                          \
  _Pragma("unroll") for (int u = 0; u < 2; u++) {                                                            \
    uint32_t v_[4];                                                                                          \
    _Pragma("unroll") for (int j = 0; j < 4; j++) v_[j] = lop_select(o[2 * j + u], parm, vword == j);        \
    st_rlx128(ofr + ((H) >> 1) * 1024 + u * 64 + ((((H) & 1) * 4 + t) ^ g), v_[0], v_[1], v_[2], v_[3]);     \
  }
    uint32_t gf[32], ao[16];
    const uint32_t parm = 0u - par, vword = ((t ^ g) & 1) == (g >> 2) ? g & 3 : 4;
    const float rh0 = 0.5f * st0.y, rh1 = 0.5f * st1.y, mh0 = st0.x * rh0, mh1 = st1.x * rh1;
#define GATE_LD(J) ldsm4(sb + ((J) >> 2 ? SM_X1 : SM_X0) + sw128 + (((((J) & 3) * 2 + hi16) ^ x128) << 4), gf[4 * (J)], gf[4 * (J) + 1], gf[4 * (J) + 2], gf[4 * (J) + 3])
#define GATE(I0, I1)                                                                                         \
  _Pragma("unroll") for (int i = (I0); i < (I1); i++) {                                                      \
    const float rs = (i & 1) ? rh1 : rh0, mh = (i & 1) ? mh1 : mh0;                                          \
    const float h0 = fmaf(bf_lo(gf[i]), rs, mh), h1 = fmaf(bf_hi(gf[i]), rs, mh);                            \
    gf[i] = pack2(fmaf(h0, tanh_approx(h0), h0), fmaf(h1, tanh_approx(h1), h1));                             \
  }
#define GATE_PIN(I0, I1) do { uint32_t o_ = 0; _Pragma("unroll") for (int i = (I0); i < (I1); i++) o_ |= gf[i]; SCHED_PIN(__uint_as_float(o_)); } while (0)
    {
      float p[64], na[40], nb[40];
      uint32_t fa[16], fb[16];
      {
        uint32_t nq[4] = {0u, 0u, 0u, 0u};
        PHI_PROJ(p, q, 0, 2);
        SCHED_FENCE();
        PHI_PROJ(p, q, 2, 4);
        const bool unsafe = softmax_unsafe(nq, c0 * c0 * wn, c1 * c1 * wn);
        wg_wait<0>();
        reg_fence<64>(p);
        PROFC(24);
        if (__builtin_expect(unsafe, 0)) softmax_shift(p, c0, c1);
      }
      float dn[32];
#define DN_PART(A, B)                                                                                        \
  do {                                                                                                       \
    wg_fence();                                                                                              \
    const uint32_t hA_ = fresh_hi<H128>(P.zA), hB_ = fresh_hi<HNS>(P.zB);                                    \
    _Pragma("unroll") for (int i = (A); i < (B); i++)                                                        \
      wgmma_n8_ss_ta1_tb1(dn + 4 * (i >> 1), mkdesch(sb + (i >> 3) * Q_STAGE + (i & 7) * 2048, 16, hA_, wg * (2 * Q_STAGE / 16)), \
                          mkdesch(sb + SM_HT + (i & 1) * 256, 128, hB_), i & 1);                           \
  } while (0)
#define F_PIN(F, A, B) do { uint32_t o_ = 0; _Pragma("unroll") for (int i = (A); i < (B); i++) o_ |= F[8 + i]; SCHED_PIN(__uint_as_float(o_)); } while (0)
#define RMMA(J, A, ACCUM)                                                                                    \
  do {                                                                                                       \
    wg_fence();                                                                                              \
    const uint32_t hB_ = fresh_hi<H128>(P.zB);                                                               \
    _Pragma("unroll") for (int k = 0; k < 4; k++)                                                            \
      wgmma_n128_rs_ta0_tb1(q, (A)[4 * k], (A)[4 * k + 1], (A)[4 * k + 2], (A)[4 * k + 3],                   \
                            mkdesch(sb + 16384 + k * 2048, 8192, hB_, ((J) & 3) * (Q_STAGE / 16)), k ? 1 : (ACCUM)); \
    wg_commit();                                                                                             \
  } while (0)
#define RSTEP(J, A, ACCUM) do { QWAIT(J); RMMA(J, A, ACCUM); } while (0)
      PROFC(4);
      q_exp(p, c0, c1, fa);
      q_exp(p + 16, c0, c1, fb);
      F_PIN(fb, 0, 8);
      mbar_wait(bar + B_TILE, 0);
      O_MMA(0, fa, na);
      O_MMA(1, fb, nb);
      PROFC(25);
      wg_wait<1>();
      O_FIN(0, na, ao);
      O_STG(0, ao);
      wg_wait<0>();
      O_FIN(1, nb, (ao + 8));
      O_STG(1, (ao + 8));
      PROFC(28);
      mbar_wait(bar + B_H, 0);
      mbar_wait(bar + B_DN, 0);
      PROFC(45);
      DN_PART(0, 16);
      wg_commit();
      wg_wait<0>();
      reg_fence<32>(dn);
#pragma unroll
      for (int i = 0; i < 4; i++) yp[i] = t & 2 ? (t & 1 ? dn[24 + 2 * i] : dn[16 + 2 * i]) : (t & 1 ? dn[8 + 2 * i] : dn[2 * i]);
      RSTEP(16, ao, 0);
      SCHED_FENCE();
      q_exp(p + 32, c0, c1, fa);
      F_PIN(fa, 0, 8);
      if (lane == 0) mbar_arrive(bar + B_DND);
      q_exp(p + 48, c0, c1, fb);
      F_PIN(fb, 0, 8);
      wg_wait<0>();
      QREL(16);
      PROFC(29);
      mbar_wait(bar + B_TILE + 8, 0);
      PROFC(23);
      if (bid < NFFN) {
        float* y = g_y[par ^ 1][bid & 7] + wg * 512 + t * 128 + w * 16 + g;
#pragma unroll
        for (int i = 0; i < 4; i++) red1(y + (i >> 1) * 64 + (i & 1) * 8, yp[i]);
      }
      SCHED_FENCE();
      O_MMA(2, fa, na);
      O_MMA(3, fb, nb);
      __syncwarp();
      if (lane == 0) mbar_arrive(bar + B_YD);
      wg_wait<1>();
      O_FIN(2, na, ao);
      O_STG(2, ao);
      wg_wait<0>();
      O_FIN(3, nb, (ao + 8));
      O_STG(3, (ao + 8));
      PROFC(6);
    }
    RSTEP(17, ao, 1);
    SCHED_FENCE();
    GATE_LD(0); GATE_LD(1);
    GATE(0, 4);
    GATE_PIN(0, 4);
#define GSTEP(J, I) do { QNEXT(J); if ((I) < 7) GATE_LD(((I) + 1) & 7); GATE(4 * (I), 4 * (I) + 4); GATE_PIN(4 * (I), 4 * (I) + 4); } while (0)
    GSTEP(18, 1); GSTEP(19, 2); GSTEP(20, 3); GSTEP(21, 4); GSTEP(22, 5); GSTEP(23, 6); GSTEP(24, 7);
#pragma unroll 1
    for (int j = 25; j < 32 - TAILN; j++) QPLAIN(j);
    if (wg == 1) bar_sync(6, 256);
#pragma unroll 1
    for (int j = 32 - TAILN; j < 32; j++) QSTEP_A(j, (j & 3) * (Q_STAGE / 16), 1);
    if (wg == 0) asm volatile("bar.arrive 6, 256;" ::: "memory");
    mbar_wait(bar + B_UPD, 0);
    {
      const int sel = __float_as_int(lds32(sb + SM_UPD + 256)) - (wg * 64 + w * 16 + g);
      if (sel == 0 || sel == 8) {
#pragma unroll
        for (int j = 0; j < 16; j++) {
          const uint32_t u = __float_as_uint(lds32(sb + SM_UPD + j * 16 + t * 4));
          if (sel) gf[2 * j + 1] = u; else gf[2 * j] = u;
        }
      }
      __syncwarp();
      uint32_t xf[32];
#pragma unroll
      for (int j = 0; j < 8; j++)
        ldsm4(sb + (j >> 2 ? SM_X1 : SM_X0) + sw128 + ((((j & 3) * 2 + hi16) ^ x128) << 4), xf[4 * j], xf[4 * j + 1], xf[4 * j + 2], xf[4 * j + 3]);
      wg_wait<0>();
      reg_fence<64>(q);
      PROFC(8);
#pragma unroll
      for (int j = 0; j < 8; j++) {
        uint32_t o[4];
#pragma unroll
        for (int i = 0; i < 4; i++) o[i] = badd2(xf[4 * j + i], bmul2(pack2(q[8 * j + 2 * i], q[8 * j + 2 * i + 1]), gf[4 * j + i]));
        stsm4(sb + (j >> 2 ? SM_X1 : SM_X0) + sw128 + ((((j & 3) * 2 + hi16) ^ x128) << 4), o[0], o[1], o[2], o[3]);
        if ((j & 3) == 3) {
          fence_async_smem();
          __syncwarp();
          if (elect_one()) {
            tma_store2d(&mOut, sb + (j >> 2 ? SM_X1 : SM_X0) + warp * 2048, hg * 128 + (j >> 2) * 64, mb * 128 + warp * 16);
            bulk_commit();
          }
          __syncwarp();
        }
      }
    }
    bulk_wait_read0();
    if (warp == 7 && lane == 0) { PROF(9); PROFT(33); PROF_DUMP; }
  }
}

typedef CUresult (*EncodeFn)(CUtensorMap*, CUtensorMapDataType, cuuint32_t, void*, const cuuint64_t*, const cuuint64_t*, const cuuint32_t*,
                             const cuuint32_t*, CUtensorMapInterleave, CUtensorMapSwizzle, CUtensorMapL2promotion, CUtensorMapFloatOOBfill);

CUtensorMap make_map(EncodeFn enc, const void* ptr, int rank, const cuuint64_t* dims, const cuuint64_t* strides, const cuuint32_t* box, CUtensorMapSwizzle sw) {
  CUtensorMap m;
  const cuuint32_t es[5] = {1, 1, 1, 1, 1};
  enc(&m, CU_TENSOR_MAP_DATA_TYPE_BFLOAT16, rank, (void*)ptr, dims, strides, box, es, CU_TENSOR_MAP_INTERLEAVE_NONE, sw,
      CU_TENSOR_MAP_L2_PROMOTION_L2_128B, CU_TENSOR_MAP_FLOAT_OOB_FILL_NONE);
  return m;
}

}

extern "C" void kernel_launch(void* const* d_in, const int* in_sizes, int n_in, void* d_out, int out_size) {
  static EncodeFn enc = nullptr;
  static int by_sm = 0;
  if (!enc) {
    void* fn = nullptr;
    cudaDriverEntryPointQueryResult qr;
    cudaGetDriverEntryPoint("cuTensorMapEncodeTiled", &fn, cudaEnableDefault, &qr);
    enc = (EncodeFn)fn;
    cudaFuncSetAttribute(fused_kernel<false>, cudaFuncAttributeMaxDynamicSharedMemorySize, SM_TOTAL);
    cudaFuncSetAttribute(fused_kernel<true>, cudaFuncAttributeMaxDynamicSharedMemorySize, SM_TOTAL);
    int dev = 0, sms = 0;
    cudaGetDevice(&dev);
    cudaDeviceGetAttribute(&sms, cudaDevAttrMultiProcessorCount, dev);
    by_sm = BY_SM && sms == NCTA + NSPARE;
  }
  Params P;
  P.zA = P.zB = 0;
  P.x = (const __nv_bfloat16*)d_in[0];
  P.wqkv = (const __nv_bfloat16*)d_in[1];
  const void* wphi = d_in[2];
  P.wo = (const __nv_bfloat16*)d_in[3];
  P.w_r = (const __nv_bfloat16*)d_in[5];
  const void *w_gate = d_in[6], *w_up = d_in[7];
  P.w_down = (const __nv_bfloat16*)d_in[8];

  const cuuint64_t dX[2] = {DM, SEQ}, sX[1] = {DM * 2};
  const cuuint32_t b128[2] = {64, 128};
  const cuuint64_t dW[4] = {64, DM, 16, 3}, sW[3] = {3 * DM * 2, 128, DM * 2};
  const cuuint32_t bKV[4] = {64, 64, 2, 2}, bQ[4] = {64, 64, 2, 1};
  const cuuint64_t dO[3] = {64, DM, 16}, sO[2] = {DM * 2, 128};
  const cuuint32_t bO[3] = {64, 64, 2};
  const cuuint64_t dP[2] = {32, 1024}, sP[1] = {64};
  const cuuint32_t bP[2] = {32, 128};
  CUtensorMap mX = make_map(enc, P.x, 2, dX, sX, b128, CU_TENSOR_MAP_SWIZZLE_128B);
  CUtensorMap mWkv = make_map(enc, P.wqkv, 4, dW, sW, bKV, CU_TENSOR_MAP_SWIZZLE_128B);
  CUtensorMap mWq = make_map(enc, P.wqkv, 4, dW, sW, bQ, CU_TENSOR_MAP_SWIZZLE_128B);
  CUtensorMap mWo = make_map(enc, P.wo, 3, dO, sO, bO, CU_TENSOR_MAP_SWIZZLE_128B);
  CUtensorMap mPhi = make_map(enc, wphi, 2, dP, sP, bP, CU_TENSOR_MAP_SWIZZLE_64B);
  const cuuint64_t dWp[5] = {DM, 2, 4, 4, DM / 32}, sWp[4] = {DM * 2, 8 * DM * 2, 2 * DM * 2, 32 * DM * 2};
  const cuuint32_t bWp[5] = {64, 2, 4, 4, 2};
  CUtensorMap mWp = make_map(enc, P.wo, 5, dWp, sWp, bWp, CU_TENSOR_MAP_SWIZZLE_128B);
  const cuuint32_t b16[2] = {64, 16};
  CUtensorMap mOut = make_map(enc, d_out, 2, dX, sX, b16, CU_TENSOR_MAP_SWIZZLE_128B);
  const cuuint64_t dWc[2] = {3 * DM, DM}, sWc[1] = {3 * DM * 2}, dG[2] = {FF, DM}, sG[1] = {FF * 2}, dD[3] = {64, FF, 16};
  const cuuint32_t b32[2] = {32, 32}, bD[3] = {64, 32, 4};
  CUtensorMap mWc = make_map(enc, P.wqkv, 2, dWc, sWc, b32, CU_TENSOR_MAP_SWIZZLE_NONE);
  CUtensorMap mG = make_map(enc, w_gate, 2, dG, sG, b32, CU_TENSOR_MAP_SWIZZLE_NONE);
  CUtensorMap mU = make_map(enc, w_up, 2, dG, sG, b32, CU_TENSOR_MAP_SWIZZLE_NONE);
  CUtensorMap mD = make_map(enc, P.w_down, 3, dD, sO, bD, CU_TENSOR_MAP_SWIZZLE_128B);
  const cuuint64_t dXs[3] = {256, SEQ, 4}, sXs[2] = {DM * 2, 512};
  const cuuint32_t bXs[3] = {256, 16, 2};
  CUtensorMap mXs = make_map(enc, P.x, 3, dXs, sXs, bXs, CU_TENSOR_MAP_SWIZZLE_NONE);
  const cuuint64_t dG2[4] = {64, DM, FF / 64, 1}, sG2[3] = {FF * 2, 128, (cuuint64_t)FF * DM * 2};
  CUtensorMap mG2 = make_map(enc, w_gate, 4, dG2, sG2, bQ, CU_TENSOR_MAP_SWIZZLE_128B);
  CUtensorMap mU2 = make_map(enc, w_up, 4, dG2, sG2, bQ, CU_TENSOR_MAP_SWIZZLE_128B);
  (by_sm ? fused_kernel<true> : fused_kernel<false>)<<<NCTA + NSPARE, 384, SM_TOTAL, cudaStreamPerThread>>>(P, mX, mWkv, mWq, mWo, mPhi, mWp, mOut, mWc, mG, mU, mD, mXs,
                                                                                                           mG2, mU2);
}
```

```cpp
#include <cuda_runtime.h>
#include <cuda_bf16.h>
#include <cuda.h>
#include <stdint.h>

namespace {

constexpr int SEQ = 2048, DM = 1024, FF = 3584;
constexpr int NCTA = 128;
constexpr int NSPARE = 4;
constexpr int NFFN = FF / 32;
#define GN 6
#define G8 2
constexpr int GROWS = (3 * GN + G8) * 32;
#define TAILN 2
#define PF_FIRST 2
#define PF_W 5
#define PFD 80
#define BY_SM 1
#define PTAB 0x73216540u
#define REG_C 224
#define REG_H 56
#define SP_DELAY 2000
#define XSTR 288
#define AM_NS 100
constexpr bool FFN_OFF = false;

static_assert(2 * REG_C + REG_H <= 3 * 168, "the register pool of the CTA is 384 x 168");

__device__ uint32_t g_epoch[(NCTA + NSPARE) * 32];
__device__ unsigned long long g_stat[SEQ];
__device__ __align__(128) unsigned long long g_best[NCTA];
__device__ __align__(16) float g_y[2][8][DM];
__device__ __align__(128) uint32_t g_ycnt[64];
__device__ __align__(1024) uint32_t g_xcnt[32 * XSTR];
#define XC1(HG, R) (g_xcnt + ((HG) * 2 + (R)) * XSTR)
#define XC2(HG, R) (g_xcnt + (16 + (HG) * 2 + (R)) * XSTR)
__device__ __align__(128) uint4 g_res[2][32 * 256];
__device__ __align__(16) float g_cs[5 * DM];
__device__ __align__(128) float g_gp[2 * FF];
__device__ uint4 g_part[8 * 2 * 16 * 16 * 32];
__device__ __align__(16) float g_zpart[8 * 2 * 16 * 16 * 8];
__device__ __align__(128) uint4 g_zres[2][32 * 64];
__device__ __align__(1024) uint4 g_ofr[16 * 16 * 1024];
#define PROF(i)
#define PROFT(i)
#define PROFC(i)
#define PROF_DUMP
#define PW0(J)
#define PW1(J)

constexpr uint32_t KV_STAGE = 49152, Q_STAGE = 32768;
constexpr uint32_t SM_V = 147456;
constexpr uint32_t SM_PHI = 163840;
constexpr uint32_t SM_XST = 147456;
constexpr uint32_t SM_FST = 172032;
constexpr uint32_t SM_PST0 = 196608, SM_PST1 = SM_PHI + 8192;
constexpr uint32_t SM_X0 = 131072, SM_X1 = SM_PHI + 16384;
constexpr uint32_t SM_WPHI = 204800;
constexpr uint32_t SM_ZT = 212992;
constexpr uint32_t SM_SDT = 217088;
constexpr uint32_t SM_CST = 219136;
constexpr uint32_t SM_HT = 222720;
constexpr uint32_t SM_STAT = 223232;
constexpr uint32_t SM_XSEL = 224256;
constexpr uint32_t SM_RED = 228352;
constexpr uint32_t SM_ROWS = SM_RED + 832;
constexpr uint32_t SM_GRED = SM_XSEL + 3072;
static_assert(GROWS <= 768, "xsel area");
constexpr uint32_t SM_UPD = 229632;
constexpr uint32_t SM_BAR = 230016;
constexpr uint32_t SM_PROF = 230464;
constexpr uint32_t SM_SINK = 231104;
constexpr uint32_t SM_TOTAL = 231616;
constexpr uint32_t SB = 1024;
constexpr uint32_t B_FULLKV = 0  , B_FST = 24  , B_XST = 104  , B_WPHI = 120, B_CS = 128, B_CSQ = 136, B_UPD = 144,
                   B_H = 152, B_DN = 160, B_XS = 168, B_TILE = 176  , B_RES = 192  , B_PART = 208  , B_AIN = 224  ,
                   B_FULLQ = 288  ,
                   B_FFN = 320,
                   B_EMPTYKV = 328  , B_EMPTYQ = 352  , B_KVST = 384  , B_YD = 400, B_PHI = 408  , B_DND = 424, B_END = 432;

__device__ __forceinline__ uint32_t smem_u32(const void* p) { return (uint32_t)__cvta_generic_to_shared(p); }
__device__ __forceinline__ void mbar_init(uint32_t bar, uint32_t cnt) { asm volatile("mbarrier.init.shared::cta.b64 [%0], %1;" ::"r"(bar), "r"(cnt) : "memory"); }
__device__ __forceinline__ void mbar_expect_tx(uint32_t bar, uint32_t bytes) { asm volatile("mbarrier.arrive.expect_tx.shared::cta.b64 _, [%0], %1;" ::"r"(bar), "r"(bytes) : "memory"); }
__device__ __forceinline__ void mbar_arrive2(uint32_t bar) { asm volatile("mbarrier.arrive.shared::cta.b64 _, [%0], 2;" ::"r"(bar) : "memory"); }
__device__ __forceinline__ void mbar_arrive(uint32_t bar) { asm volatile("mbarrier.arrive.shared::cta.b64 _, [%0];" ::"r"(bar) : "memory"); }
__device__ __forceinline__ void mbar_wait(uint32_t bar, uint32_t parity) {
  asm volatile("{\n.reg .pred p;\nLW:\nmbarrier.try_wait.parity.shared::cta.b64 p, [%0], %1;\n@!p bra LW;\n}" ::"r"(bar), "r"(parity) : "memory");
}
__device__ __forceinline__ bool mbar_test(uint32_t bar, uint32_t parity) {
  uint32_t ok;
  asm volatile("{\n.reg .pred p;\nmbarrier.test_wait.parity.shared::cta.b64 p, [%1], %2;\nselp.u32 %0, 1, 0, p;\n}" : "=r"(ok) : "r"(bar), "r"(parity) : "memory");
  return ok;
}
__device__ __forceinline__ int lane_id() { int l; asm volatile("mov.u32 %0, %%laneid;" : "=r"(l)); return l; }
template <int C> __device__ __forceinline__ void sched_fence_(int zero) {
  asm volatile("{\n.reg .pred p;\nsetp.eq.s32 p, %0, %1;\n@p trap;\n}" ::"r"(zero), "n"(C) : "memory");
}
#define SCHED_FENCE() sched_fence_<1000 + __COUNTER__>(zero)
#define SCHED_PIN(V) sched_fence_<1000 + __COUNTER__>(zero & __float_as_int(V))
__device__ __forceinline__ bool elect_one() {
  uint32_t p; asm volatile("{ .reg .pred P; elect.sync _|P, 0xffffffff; selp.u32 %0, 1, 0, P; }" : "=r"(p)); return p;
}
__device__ __forceinline__ void tma2d(uint32_t dst, const CUtensorMap* m, int x, int y, uint32_t bar) {
  asm volatile("cp.async.bulk.tensor.2d.shared::cluster.global.mbarrier::complete_tx::bytes [%0], [%1, {%3, %4}], [%2];" ::"r"(dst), "l"(m), "r"(bar), "r"(x), "r"(y) : "memory");
}
__device__ __forceinline__ void tma3d(uint32_t dst, const CUtensorMap* m, int x, int y, int z, uint32_t bar) {
  asm volatile("cp.async.bulk.tensor.3d.shared::cluster.global.mbarrier::complete_tx::bytes [%0], [%1, {%3, %4, %5}], [%2];" ::"r"(dst), "l"(m), "r"(bar), "r"(x), "r"(y), "r"(z) : "memory");
}
__device__ __forceinline__ void tma4d(uint32_t dst, const CUtensorMap* m, int x, int y, int z, int w, uint32_t bar) {
  asm volatile("cp.async.bulk.tensor.4d.shared::cluster.global.mbarrier::complete_tx::bytes [%0], [%1, {%3, %4, %5, %6}], [%2];" ::"r"(dst), "l"(m), "r"(bar), "r"(x), "r"(y), "r"(z), "r"(w) : "memory");
}
__device__ __forceinline__ void tma5d(uint32_t dst, const CUtensorMap* m, int x, int v, uint32_t bar) {
  asm volatile("cp.async.bulk.tensor.5d.shared::cluster.global.mbarrier::complete_tx::bytes [%0], [%1, {%3, %5, %5, %5, %4}], [%2];" ::"r"(dst), "l"(m), "r"(bar), "r"(x), "r"(v), "r"(0) : "memory");
}
__device__ __forceinline__ void tma_store2d(const CUtensorMap* m, uint32_t src, int x, int y) {
  asm volatile("cp.async.bulk.tensor.2d.global.shared::cta.bulk_group [%0, {%2, %3}], [%1];" ::"l"(m), "r"(src), "r"(x), "r"(y) : "memory");
}
__device__ __forceinline__ void bulk_load(uint32_t dst, const void* src, uint32_t bytes, uint32_t bar) {
  asm volatile("cp.async.bulk.shared::cluster.global.mbarrier::complete_tx::bytes [%0], [%1], %2, [%3];" ::"r"(dst), "l"(src), "r"(bytes), "r"(bar) : "memory");
}
__device__ __forceinline__ void bulk_commit() { asm volatile("cp.async.bulk.commit_group;" ::: "memory"); }
__device__ __forceinline__ void bulk_wait_read0() { asm volatile("cp.async.bulk.wait_group.read 0;" ::: "memory"); }
__device__ __forceinline__ void prefetch_l2(const void* p) { asm volatile("prefetch.global.L2 [%0];" ::"l"(p) : "memory"); }
__device__ __forceinline__ void touch_l2(const void* p, int lane) { asm volatile("cp.async.cg.shared.global.L2::128B [%0], [%1], 16;" ::"r"(SB + SM_SINK + lane * 16), "l"(p) : "memory"); }
__device__ __forceinline__ void cp_async16(uint32_t dst, const void* src) { asm volatile("cp.async.cg.shared.global [%0], [%1], 16;" ::"r"(dst), "l"(src) : "memory"); }
__device__ __forceinline__ void prefetch_map(const CUtensorMap* m) { asm volatile("prefetch.tensormap [%0];" ::"l"(m) : "memory"); }
__device__ __forceinline__ void fence_async_smem() { asm volatile("fence.proxy.async.shared::cta;" ::: "memory"); }
__device__ __forceinline__ void fence_async_global() { asm volatile("fence.proxy.async.global;" ::: "memory"); }
__device__ __forceinline__ void bar_sync(int id, int n) { asm volatile("bar.sync %0, %1;" ::"r"(id), "r"(n) : "memory"); }
__device__ __forceinline__ void wg_fence() { asm volatile("wgmma.fence.sync.aligned;" ::: "memory"); }
__device__ __forceinline__ void wg_commit() { asm volatile("wgmma.commit_group.sync.aligned;" ::: "memory"); }
template <int N> __device__ __forceinline__ void wg_wait() { asm volatile("wgmma.wait_group.sync.aligned %0;" ::"n"(N) : "memory"); }
template <int N> __device__ __forceinline__ void reg_fence(uint32_t* r) {
#pragma unroll
  for (int i = 0; i < N; i++) asm volatile("" : "+r"(r[i])::"memory");
}
template <int N> __device__ __forceinline__ void reg_fence(float* r) {
#pragma unroll
  for (int i = 0; i < N; i++) asm volatile("" : "+f"(r[i])::"memory");
}
__device__ __forceinline__ uint64_t mkdesc(uint32_t addr, uint32_t lbo, uint32_t sbo, uint32_t swz, uint32_t dyn = 0) {
  const uint32_t lo = ((addr >> 4) | ((lbo >> 4) << 16)) + dyn;
  const uint32_t hi = (sbo >> 4) | (swz << 30);
  uint64_t d;
  asm("mov.b64 %0, {%1, %2};" : "=l"(d) : "r"(lo), "r"(hi));
  return d;
}
template <uint32_t C> __device__ __forceinline__ uint32_t fresh_hi(uint32_t zero) { uint32_t h; asm volatile("or.b32 %0, %1, %2;" : "=r"(h) : "r"(zero), "n"(C)); return h; }
constexpr uint32_t H128 = (1024u >> 4) | (1u << 30), H64 = (512u >> 4) | (2u << 30), HNS = 128u >> 4;
__device__ __forceinline__ uint64_t mkdesch(uint32_t addr, uint32_t lbo, uint32_t hi, uint32_t dyn = 0) {
  const uint32_t lo = ((addr >> 4) | ((lbo >> 4) << 16)) + dyn;
  uint64_t d;
  asm("mov.b64 %0, {%1, %2};" : "=l"(d) : "r"(lo), "r"(hi));
  return d;
}
__device__ __forceinline__ void stsm4(uint32_t addr, uint32_t a, uint32_t b, uint32_t c, uint32_t d) {
  asm volatile("stmatrix.sync.aligned.m8n8.x4.shared.b16 [%0], {%1, %2, %3, %4};" ::"r"(addr), "r"(a), "r"(b), "r"(c), "r"(d) : "memory");
}
__device__ __forceinline__ void ldsm4(uint32_t addr, uint32_t& a, uint32_t& b, uint32_t& c, uint32_t& d) {
  asm volatile("ldmatrix.sync.aligned.m8n8.x4.shared.b16 {%0, %1, %2, %3}, [%4];" : "=r"(a), "=r"(b), "=r"(c), "=r"(d) : "r"(addr) : "memory");
}
__device__ __forceinline__ uint32_t pack2(float lo, float hi) { uint32_t r; asm("cvt.rn.bf16x2.f32 %0, %1, %2;" : "=r"(r) : "f"(hi), "f"(lo)); return r; }
__device__ __forceinline__ uint32_t bsub2(uint32_t a, uint32_t b) { uint32_t r; asm("sub.rn.bf16x2 %0, %1, %2;" : "=r"(r) : "r"(a), "r"(b)); return r; }
__device__ __forceinline__ uint32_t badd2(uint32_t a, uint32_t b) { uint32_t r; asm("add.rn.bf16x2 %0, %1, %2;" : "=r"(r) : "r"(a), "r"(b)); return r; }
__device__ __forceinline__ uint32_t bmul2(uint32_t a, uint32_t b) { uint32_t r; asm("mul.rn.bf16x2 %0, %1, %2;" : "=r"(r) : "r"(a), "r"(b)); return r; }
__device__ __forceinline__ float bf_lo(uint32_t v) { return __uint_as_float(v << 16); }
__device__ __forceinline__ float bf_hi(uint32_t v) { return __uint_as_float(v & 0xffff0000u); }
__device__ __forceinline__ float bf_round(float v) { return bf_lo(pack2(v, 0.f)); }
__device__ __forceinline__ float ex2(float v) { float r; asm("ex2.approx.ftz.f32 %0, %1;" : "=f"(r) : "f"(v)); return r; }
__device__ __forceinline__ float rcp(float v) { float r; asm("rcp.approx.ftz.f32 %0, %1;" : "=f"(r) : "f"(v)); return r; }
__device__ __forceinline__ float sqrt_approx(float v) { float r; asm("sqrt.approx.f32 %0, %1;" : "=f"(r) : "f"(v)); return r; }
__device__ __forceinline__ float4 lds128(uint32_t a) { float4 v; asm volatile("ld.shared.v4.f32 {%0, %1, %2, %3}, [%4];" : "=f"(v.x), "=f"(v.y), "=f"(v.z), "=f"(v.w) : "r"(a) : "memory"); return v; }
__device__ __forceinline__ uint4 lds128u(uint32_t a) { uint4 v; asm volatile("ld.shared.v4.u32 {%0, %1, %2, %3}, [%4];" : "=r"(v.x), "=r"(v.y), "=r"(v.z), "=r"(v.w) : "r"(a) : "memory"); return v; }
__device__ __forceinline__ float2 lds64(uint32_t a) { float2 v; asm volatile("ld.shared.v2.f32 {%0, %1}, [%2];" : "=f"(v.x), "=f"(v.y) : "r"(a) : "memory"); return v; }
__device__ __forceinline__ float lds32(uint32_t a) { float v; asm volatile("ld.shared.f32 %0, [%1];" : "=f"(v) : "r"(a) : "memory"); return v; }
__device__ __forceinline__ void sts32(uint32_t a, float v) { asm volatile("st.shared.f32 [%0], %1;" ::"r"(a), "f"(v) : "memory"); }
__device__ __forceinline__ void sts64(uint32_t a, float x, float y) { asm volatile("st.shared.v2.f32 [%0], {%1, %2};" ::"r"(a), "f"(x), "f"(y) : "memory"); }
__device__ __forceinline__ void sts128(uint32_t a, float x, float y, float z, float w) { asm volatile("st.shared.v4.f32 [%0], {%1, %2, %3, %4};" ::"r"(a), "f"(x), "f"(y), "f"(z), "f"(w) : "memory"); }
__device__ __forceinline__ void sts64u(uint32_t a, uint32_t x, uint32_t y) { asm volatile("st.shared.v2.u32 [%0], {%1, %2};" ::"r"(a), "r"(x), "r"(y) : "memory"); }
__device__ __forceinline__ void sts128u(uint32_t a, uint32_t x, uint32_t y, uint32_t z, uint32_t w) { asm volatile("st.shared.v4.u32 [%0], {%1, %2, %3, %4};" ::"r"(a), "r"(x), "r"(y), "r"(z), "r"(w) : "memory"); }
__device__ __forceinline__ uint4 ldg_nc(const void* p) { uint4 v; asm volatile("ld.global.nc.L1::no_allocate.v4.u32 {%0, %1, %2, %3}, [%4];" : "=r"(v.x), "=r"(v.y), "=r"(v.z), "=r"(v.w) : "l"(p)); return v; }
__device__ __forceinline__ float4 ldg_cg4(const float* p) { float4 v; asm volatile("ld.global.cg.v4.f32 {%0, %1, %2, %3}, [%4];" : "=f"(v.x), "=f"(v.y), "=f"(v.z), "=f"(v.w) : "l"(p) : "memory"); return v; }
__device__ __forceinline__ uint32_t ld_acq(const uint32_t* p) { uint32_t v; asm volatile("ld.acquire.gpu.global.u32 %0, [%1];" : "=r"(v) : "l"(p) : "memory"); return v; }
__device__ __forceinline__ unsigned long long ld_rlx64(const unsigned long long* p) { unsigned long long v; asm volatile("ld.relaxed.gpu.global.u64 %0, [%1];" : "=l"(v) : "l"(p) : "memory"); return v; }
__device__ __forceinline__ void st_rlx64(unsigned long long* p, unsigned long long v) { asm volatile("st.relaxed.gpu.global.u64 [%0], %1;" ::"l"(p), "l"(v) : "memory"); }
__device__ __forceinline__ uint4 ld_rlx128(const void* p) {
  uint4 v;
  asm volatile("{ .reg .b128 t; .reg .b64 a, b; ld.relaxed.gpu.global.b128 t, [%4]; mov.b128 {a, b}, t; mov.b64 {%0, %1}, a; mov.b64 {%2, %3}, b; }"
               : "=r"(v.x), "=r"(v.y), "=r"(v.z), "=r"(v.w) : "l"(p) : "memory");
  return v;
}
__device__ __forceinline__ void st_rlx128(void* p, uint32_t x, uint32_t y, uint32_t z, uint32_t w) {
  asm volatile("{ .reg .b128 t; .reg .b64 a, b; mov.b64 a, {%1, %2}; mov.b64 b, {%3, %4}; mov.b128 t, {a, b}; st.relaxed.gpu.global.b128 [%0], t; }"
               ::"l"(p), "r"(x), "r"(y), "r"(z), "r"(w) : "memory");
}
__device__ __forceinline__ void st_rlx(void* p, uint32_t v) { asm volatile("st.relaxed.gpu.global.u32 [%0], %1;" ::"l"(p), "r"(v) : "memory"); }
__device__ __forceinline__ uint32_t lop_select(uint32_t a, uint32_t b, uint32_t m) { uint32_t r; asm("lop3.b32 %0, %1, %2, %3, 0xd8;" : "=r"(r) : "r"(a), "r"(b), "r"(m)); return r; }
__device__ __forceinline__ float unmark(uint32_t v) { return __uint_as_float(v & ~1u); }
__device__ __forceinline__ uint32_t mark(uint32_t v, uint32_t par) { return (v & ~1u) | par; }
__device__ __forceinline__ float tanh_approx(float v) { float r; asm("tanh.approx.f32 %0, %1;" : "=f"(r) : "f"(v)); return r; }
__device__ __forceinline__ void red1(float* p, float a) { asm volatile("red.global.add.f32 [%0], %1;" ::"l"(p), "f"(a) : "memory"); }
__device__ __forceinline__ void red_inc(uint32_t* p) { asm volatile("red.relaxed.gpu.global.add.u32 [%0], 1;" ::"l"(p) : "memory"); }
__device__ __forceinline__ void red_rel(uint32_t* p) { asm volatile("red.release.gpu.global.add.u32 [%0], 1;" ::"l"(p) : "memory"); }
constexpr int SPIN_MAX = 100000;
__device__ __forceinline__ uint32_t ld_rlx(const uint32_t* p) { uint32_t v; asm volatile("ld.relaxed.gpu.global.u32 %0, [%1];" : "=r"(v) : "l"(p) : "memory"); return v; }
template <int NS = 0> __device__ __forceinline__ void wait_hint(const uint32_t* p, uint32_t target) {
#pragma unroll 1
  for (int i = 0; i < SPIN_MAX; i++) { if ((int)(ld_rlx(p) - target) >= 0) break; if (NS) __nanosleep(NS); }
}
template <int NS> __device__ __forceinline__ void wait_cnt(const uint32_t* p, uint32_t target) {
#pragma unroll 1
  for (int i = 0; i < SPIN_MAX; i++) { if ((int)(ld_rlx(p) - target) >= 0) break; if (NS) __nanosleep(NS); }
  (void)ld_acq(p);
}
template <int NS> __device__ __forceinline__ unsigned long long wait_tag(const unsigned long long* p, uint32_t tag) {
  unsigned long long v = 0;
#pragma unroll 1
  for (int i = 0; i < SPIN_MAX; i++) { v = ld_rlx64(p); if ((uint32_t)(v >> 32) == tag) break; if (NS) __nanosleep(NS); }
  return v;
}
__device__ __forceinline__ float silu_f(float v) { return v * rcp(1.f + ex2(-1.4426950408889634f * v)); }

__device__ __forceinline__ void wgmma_n8_ss_ta1_tb0(float* d, uint64_t da, uint64_t db, bool accumulate) {
  if (accumulate) {
    asm volatile("{\n.reg .pred p;\nsetp.ne.b32 p, 1, 0;\n"
      "wgmma.mma_async.sync.aligned.m64n8k16.f32.bf16.bf16 "
      "{%0, %1, %2, %3}, "
      "%4, %5, p, 1, 1, 1, 0;\n}\n"
      : "+f"(d[0]), "+f"(d[1]), "+f"(d[2]), "+f"(d[3])
      : "l"(da), "l"(db));
  } else {
    asm volatile("{\n.reg .pred p;\nsetp.ne.b32 p, 0, 0;\n"
      "wgmma.mma_async.sync.aligned.m64n8k16.f32.bf16.bf16 "
      "{%0, %1, %2, %3}, "
      "%4, %5, p, 1, 1, 1, 0;\n}\n"
      : "=f"(d[0]), "=f"(d[1]), "=f"(d[2]), "=f"(d[3])
      : "l"(da), "l"(db));
  }
}
__device__ __forceinline__ void wgmma_n8_ss_ta1_tb1(float* d, uint64_t da, uint64_t db, bool accumulate) {
  if (accumulate) {
    asm volatile("{\n.reg .pred p;\nsetp.ne.b32 p, 1, 0;\n"
      "wgmma.mma_async.sync.aligned.m64n8k16.f32.bf16.bf16 "
      "{%0, %1, %2, %3}, "
      "%4, %5, p, 1, 1, 1, 1;\n}\n"
      : "+f"(d[0]), "+f"(d[1]), "+f"(d[2]), "+f"(d[3])
      : "l"(da), "l"(db));
  } else {
    asm volatile("{\n.reg .pred p;\nsetp.ne.b32 p, 0, 0;\n"
      "wgmma.mma_async.sync.aligned.m64n8k16.f32.bf16.bf16 "
      "{%0, %1, %2, %3}, "
      "%4, %5, p, 1, 1, 1, 1;\n}\n"
      : "=f"(d[0]), "=f"(d[1]), "=f"(d[2]), "=f"(d[3])
      : "l"(da), "l"(db));
  }
}
__device__ __forceinline__ void wgmma_n32_rs_ta0_tb1(float* d, uint32_t a0, uint32_t a1, uint32_t a2, uint32_t a3, uint64_t db, bool accumulate) {
  if (accumulate) {
    asm volatile("{\n.reg .pred p;\nsetp.ne.b32 p, 1, 0;\n"
      "wgmma.mma_async.sync.aligned.m64n32k16.f32.bf16.bf16 "
      "{%0, %1, %2, %3, %4, %5, %6, %7, %8, %9, %10, %11, %12, %13, %14, %15}, "
      "{%16, %17, %18, %19}, %20, p, 1, 1, 1;\n}\n"
      : "+f"(d[0]), "+f"(d[1]), "+f"(d[2]), "+f"(d[3]), "+f"(d[4]), "+f"(d[5]), "+f"(d[6]), "+f"(d[7]), "+f"(d[8]), "+f"(d[9]), "+f"(d[10]), "+f"(d[11]), "+f"(d[12]), "+f"(d[13]), "+f"(d[14]), "+f"(d[15])
      : "r"(a0), "r"(a1), "r"(a2), "r"(a3), "l"(db));
  } else {
    asm volatile("{\n.reg .pred p;\nsetp.ne.b32 p, 0, 0;\n"
      "wgmma.mma_async.sync.aligned.m64n32k16.f32.bf16.bf16 "
      "{%0, %1, %2, %3, %4, %5, %6, %7, %8, %9, %10, %11, %12, %13, %14, %15}, "
      "{%16, %17, %18, %19}, %20, p, 1, 1, 1;\n}\n"
      : "=f"(d[0]), "=f"(d[1]), "=f"(d[2]), "=f"(d[3]), "=f"(d[4]), "=f"(d[5]), "=f"(d[6]), "=f"(d[7]), "=f"(d[8]), "=f"(d[9]), "=f"(d[10]), "=f"(d[11]), "=f"(d[12]), "=f"(d[13]), "=f"(d[14]), "=f"(d[15])
      : "r"(a0), "r"(a1), "r"(a2), "r"(a3), "l"(db));
  }
}
__device__ __forceinline__ void wgmma_n40_rs_ta0_tb1(float* d, uint32_t a0, uint32_t a1, uint32_t a2, uint32_t a3, uint64_t db, bool accumulate) {
  if (accumulate) {
    asm volatile("{\n.reg .pred p;\nsetp.ne.b32 p, 1, 0;\n"
      "wgmma.mma_async.sync.aligned.m64n40k16.f32.bf16.bf16 "
      "{%0, %1, %2, %3, %4, %5, %6, %7, %8, %9, %10, %11, %12, %13, %14, %15, %16, %17, %18, %19}, "
      "{%20, %21, %22, %23}, %24, p, 1, 1, 1;\n}\n"
      : "+f"(d[0]), "+f"(d[1]), "+f"(d[2]), "+f"(d[3]), "+f"(d[4]), "+f"(d[5]), "+f"(d[6]), "+f"(d[7]), "+f"(d[8]), "+f"(d[9]), "+f"(d[10]), "+f"(d[11]), "+f"(d[12]), "+f"(d[13]), "+f"(d[14]), "+f"(d[15]), "+f"(d[16]), "+f"(d[17]), "+f"(d[18]), "+f"(d[19])
      : "r"(a0), "r"(a1), "r"(a2), "r"(a3), "l"(db));
  } else {
    asm volatile("{\n.reg .pred p;\nsetp.ne.b32 p, 0, 0;\n"
      "wgmma.mma_async.sync.aligned.m64n40k16.f32.bf16.bf16 "
      "{%0, %1, %2, %3, %4, %5, %6, %7, %8, %9, %10, %11, %12, %13, %14, %15, %16, %17, %18, %19}, "
      "{%20, %21, %22, %23}, %24, p, 1, 1, 1;\n}\n"
      : "=f"(d[0]), "=f"(d[1]), "=f"(d[2]), "=f"(d[3]), "=f"(d[4]), "=f"(d[5]), "=f"(d[6]), "=f"(d[7]), "=f"(d[8]), "=f"(d[9]), "=f"(d[10]), "=f"(d[11]), "=f"(d[12]), "=f"(d[13]), "=f"(d[14]), "=f"(d[15]), "=f"(d[16]), "=f"(d[17]), "=f"(d[18]), "=f"(d[19])
      : "r"(a0), "r"(a1), "r"(a2), "r"(a3), "l"(db));
  }
}
__device__ __forceinline__ void wgmma_n40_ss_ta1_tb1(float* d, uint64_t da, uint64_t db, bool accumulate) {
  if (accumulate) {
    asm volatile("{\n.reg .pred p;\nsetp.ne.b32 p, 1, 0;\n"
      "wgmma.mma_async.sync.aligned.m64n40k16.f32.bf16.bf16 "
      "{%0, %1, %2, %3, %4, %5, %6, %7, %8, %9, %10, %11, %12, %13, %14, %15, %16, %17, %18, %19}, "
      "%20, %21, p, 1, 1, 1, 1;\n}\n"
      : "+f"(d[0]), "+f"(d[1]), "+f"(d[2]), "+f"(d[3]), "+f"(d[4]), "+f"(d[5]), "+f"(d[6]), "+f"(d[7]), "+f"(d[8]), "+f"(d[9]), "+f"(d[10]), "+f"(d[11]), "+f"(d[12]), "+f"(d[13]), "+f"(d[14]), "+f"(d[15]), "+f"(d[16]), "+f"(d[17]), "+f"(d[18]), "+f"(d[19])
      : "l"(da), "l"(db));
  } else {
    asm volatile("{\n.reg .pred p;\nsetp.ne.b32 p, 0, 0;\n"
      "wgmma.mma_async.sync.aligned.m64n40k16.f32.bf16.bf16 "
      "{%0, %1, %2, %3, %4, %5, %6, %7, %8, %9, %10, %11, %12, %13, %14, %15, %16, %17, %18, %19}, "
      "%20, %21, p, 1, 1, 1, 1;\n}\n"
      : "=f"(d[0]), "=f"(d[1]), "=f"(d[2]), "=f"(d[3]), "=f"(d[4]), "=f"(d[5]), "=f"(d[6]), "=f"(d[7]), "=f"(d[8]), "=f"(d[9]), "=f"(d[10]), "=f"(d[11]), "=f"(d[12]), "=f"(d[13]), "=f"(d[14]), "=f"(d[15]), "=f"(d[16]), "=f"(d[17]), "=f"(d[18]), "=f"(d[19])
      : "l"(da), "l"(db));
  }
}
__device__ __forceinline__ void wgmma_n128_rs_ta0_tb1(float* d, uint32_t a0, uint32_t a1, uint32_t a2, uint32_t a3, uint64_t db, bool accumulate) {
  if (accumulate) {
    asm volatile("{\n.reg .pred p;\nsetp.ne.b32 p, 1, 0;\n"
      "wgmma.mma_async.sync.aligned.m64n128k16.f32.bf16.bf16 "
      "{%0, %1, %2, %3, %4, %5, %6, %7, %8, %9, %10, %11, %12, %13, %14, %15, %16, %17, %18, %19, %20, %21, %22, %23, %24, %25, %26, %27, %28, %29, %30, %31, %32, %33, %34, %35, %36, %37, %38, %39, %40, %41, %42, %43, %44, %45, %46, %47, %48, %49, %50, %51, %52, %53, %54, %55, %56, %57, %58, %59, %60, %61, %62, %63}, "
      "{%64, %65, %66, %67}, %68, p, 1, 1, 1;\n}\n"
      : "+f"(d[0]), "+f"(d[1]), "+f"(d[2]), "+f"(d[3]), "+f"(d[4]), "+f"(d[5]), "+f"(d[6]), "+f"(d[7]), "+f"(d[8]), "+f"(d[9]), "+f"(d[10]), "+f"(d[11]), "+f"(d[12]), "+f"(d[13]), "+f"(d[14]), "+f"(d[15]), "+f"(d[16]), "+f"(d[17]), "+f"(d[18]), "+f"(d[19]), "+f"(d[20]), "+f"(d[21]), "+f"(d[22]), "+f"(d[23]), "+f"(d[24]), "+f"(d[25]), "+f"(d[26]), "+f"(d[27]), "+f"(d[28]), "+f"(d[29]), "+f"(d[30]), "+f"(d[31]), "+f"(d[32]), "+f"(d[33]), "+f"(d[34]), "+f"(d[35]), "+f"(d[36]), "+f"(d[37]), "+f"(d[38]), "+f"(d[39]), "+f"(d[40]), "+f"(d[41]), "+f"(d[42]), "+f"(d[43]), "+f"(d[44]), "+f"(d[45]), "+f"(d[46]), "+f"(d[47]), "+f"(d[48]), "+f"(d[49]), "+f"(d[50]), "+f"(d[51]), "+f"(d[52]), "+f"(d[53]), "+f"(d[54]), "+f"(d[55]), "+f"(d[56]), "+f"(d[57]), "+f"(d[58]), "+f"(d[59]), "+f"(d[60]), "+f"(d[61]), "+f"(d[62]), "+f"(d[63])
      : "r"(a0), "r"(a1), "r"(a2), "r"(a3), "l"(db));
  } else {
    asm volatile("{\n.reg .pred p;\nsetp.ne.b32 p, 0, 0;\n"
      "wgmma.mma_async.sync.aligned.m64n128k16.f32.bf16.bf16 "
      "{%0, %1, %2, %3, %4, %5, %6, %7, %8, %9, %10, %11, %12, %13, %14, %15, %16, %17, %18, %19, %20, %21, %22, %23, %24, %25, %26, %27, %28, %29, %30, %31, %32, %33, %34, %35, %36, %37, %38, %39, %40, %41, %42, %43, %44, %45, %46, %47, %48, %49, %50, %51, %52, %53, %54, %55, %56, %57, %58, %59, %60, %61, %62, %63}, "
      "{%64, %65, %66, %67}, %68, p, 1, 1, 1;\n}\n"
      : "=f"(d[0]), "=f"(d[1]), "=f"(d[2]), "=f"(d[3]), "=f"(d[4]), "=f"(d[5]), "=f"(d[6]), "=f"(d[7]), "=f"(d[8]), "=f"(d[9]), "=f"(d[10]), "=f"(d[11]), "=f"(d[12]), "=f"(d[13]), "=f"(d[14]), "=f"(d[15]), "=f"(d[16]), "=f"(d[17]), "=f"(d[18]), "=f"(d[19]), "=f"(d[20]), "=f"(d[21]), "=f"(d[22]), "=f"(d[23]), "=f"(d[24]), "=f"(d[25]), "=f"(d[26]), "=f"(d[27]), "=f"(d[28]), "=f"(d[29]), "=f"(d[30]), "=f"(d[31]), "=f"(d[32]), "=f"(d[33]), "=f"(d[34]), "=f"(d[35]), "=f"(d[36]), "=f"(d[37]), "=f"(d[38]), "=f"(d[39]), "=f"(d[40]), "=f"(d[41]), "=f"(d[42]), "=f"(d[43]), "=f"(d[44]), "=f"(d[45]), "=f"(d[46]), "=f"(d[47]), "=f"(d[48]), "=f"(d[49]), "=f"(d[50]), "=f"(d[51]), "=f"(d[52]), "=f"(d[53]), "=f"(d[54]), "=f"(d[55]), "=f"(d[56]), "=f"(d[57]), "=f"(d[58]), "=f"(d[59]), "=f"(d[60]), "=f"(d[61]), "=f"(d[62]), "=f"(d[63])
      : "r"(a0), "r"(a1), "r"(a2), "r"(a3), "l"(db));
  }
}
__device__ __forceinline__ void wgmma_n128_ss_ta0_tb1(float* d, uint64_t da, uint64_t db, bool accumulate) {
  if (accumulate) {
    asm volatile("{\n.reg .pred p;\nsetp.ne.b32 p, 1, 0;\n"
      "wgmma.mma_async.sync.aligned.m64n128k16.f32.bf16.bf16 "
      "{%0, %1, %2, %3, %4, %5, %6, %7, %8, %9, %10, %11, %12, %13, %14, %15, %16, %17, %18, %19, %20, %21, %22, %23, %24, %25, %26, %27, %28, %29, %30, %31, %32, %33, %34, %35, %36, %37, %38, %39, %40, %41, %42, %43, %44, %45, %46, %47, %48, %49, %50, %51, %52, %53, %54, %55, %56, %57, %58, %59, %60, %61, %62, %63}, "
      "%64, %65, p, 1, 1, 0, 1;\n}\n"
      : "+f"(d[0]), "+f"(d[1]), "+f"(d[2]), "+f"(d[3]), "+f"(d[4]), "+f"(d[5]), "+f"(d[6]), "+f"(d[7]), "+f"(d[8]), "+f"(d[9]), "+f"(d[10]), "+f"(d[11]), "+f"(d[12]), "+f"(d[13]), "+f"(d[14]), "+f"(d[15]), "+f"(d[16]), "+f"(d[17]), "+f"(d[18]), "+f"(d[19]), "+f"(d[20]), "+f"(d[21]), "+f"(d[22]), "+f"(d[23]), "+f"(d[24]), "+f"(d[25]), "+f"(d[26]), "+f"(d[27]), "+f"(d[28]), "+f"(d[29]), "+f"(d[30]), "+f"(d[31]), "+f"(d[32]), "+f"(d[33]), "+f"(d[34]), "+f"(d[35]), "+f"(d[36]), "+f"(d[37]), "+f"(d[38]), "+f"(d[39]), "+f"(d[40]), "+f"(d[41]), "+f"(d[42]), "+f"(d[43]), "+f"(d[44]), "+f"(d[45]), "+f"(d[46]), "+f"(d[47]), "+f"(d[48]), "+f"(d[49]), "+f"(d[50]), "+f"(d[51]), "+f"(d[52]), "+f"(d[53]), "+f"(d[54]), "+f"(d[55]), "+f"(d[56]), "+f"(d[57]), "+f"(d[58]), "+f"(d[59]), "+f"(d[60]), "+f"(d[61]), "+f"(d[62]), "+f"(d[63])
      : "l"(da), "l"(db));
  } else {
    asm volatile("{\n.reg .pred p;\nsetp.ne.b32 p, 0, 0;\n"
      "wgmma.mma_async.sync.aligned.m64n128k16.f32.bf16.bf16 "
      "{%0, %1, %2, %3, %4, %5, %6, %7, %8, %9, %10, %11, %12, %13, %14, %15, %16, %17, %18, %19, %20, %21, %22, %23, %24, %25, %26, %27, %28, %29, %30, %31, %32, %33, %34, %35, %36, %37, %38, %39, %40, %41, %42, %43, %44, %45, %46, %47, %48, %49, %50, %51, %52, %53, %54, %55, %56, %57, %58, %59, %60, %61, %62, %63}, "
      "%64, %65, p, 1, 1, 0, 1;\n}\n"
      : "=f"(d[0]), "=f"(d[1]), "=f"(d[2]), "=f"(d[3]), "=f"(d[4]), "=f"(d[5]), "=f"(d[6]), "=f"(d[7]), "=f"(d[8]), "=f"(d[9]), "=f"(d[10]), "=f"(d[11]), "=f"(d[12]), "=f"(d[13]), "=f"(d[14]), "=f"(d[15]), "=f"(d[16]), "=f"(d[17]), "=f"(d[18]), "=f"(d[19]), "=f"(d[20]), "=f"(d[21]), "=f"(d[22]), "=f"(d[23]), "=f"(d[24]), "=f"(d[25]), "=f"(d[26]), "=f"(d[27]), "=f"(d[28]), "=f"(d[29]), "=f"(d[30]), "=f"(d[31]), "=f"(d[32]), "=f"(d[33]), "=f"(d[34]), "=f"(d[35]), "=f"(d[36]), "=f"(d[37]), "=f"(d[38]), "=f"(d[39]), "=f"(d[40]), "=f"(d[41]), "=f"(d[42]), "=f"(d[43]), "=f"(d[44]), "=f"(d[45]), "=f"(d[46]), "=f"(d[47]), "=f"(d[48]), "=f"(d[49]), "=f"(d[50]), "=f"(d[51]), "=f"(d[52]), "=f"(d[53]), "=f"(d[54]), "=f"(d[55]), "=f"(d[56]), "=f"(d[57]), "=f"(d[58]), "=f"(d[59]), "=f"(d[60]), "=f"(d[61]), "=f"(d[62]), "=f"(d[63])
      : "l"(da), "l"(db));
  }
}
__device__ __forceinline__ void wgmma_n256_rs_ta0_tb1(float* d, uint32_t a0, uint32_t a1, uint32_t a2, uint32_t a3, uint64_t db, bool accumulate) {
  if (accumulate) {
    asm volatile("{\n.reg .pred p;\nsetp.ne.b32 p, 1, 0;\n"
      "wgmma.mma_async.sync.aligned.m64n256k16.f32.bf16.bf16 "
      "{%0, %1, %2, %3, %4, %5, %6, %7, %8, %9, %10, %11, %12, %13, %14, %15, %16, %17, %18, %19, %20, %21, %22, %23, %24, %25, %26, %27, %28, %29, %30, %31, %32, %33, %34, %35, %36, %37, %38, %39, %40, %41, %42, %43, %44, %45, %46, %47, %48, %49, %50, %51, %52, %53, %54, %55, %56, %57, %58, %59, %60, %61, %62, %63, %64, %65, %66, %67, %68, %69, %70, %71, %72, %73, %74, %75, %76, %77, %78, %79, %80, %81, %82, %83, %84, %85, %86, %87, %88, %89, %90, %91, %92, %93, %94, %95, %96, %97, %98, %99, %100, %101, %102, %103, %104, %105, %106, %107, %108, %109, %110, %111, %112, %113, %114, %115, %116, %117, %118, %119, %120, %121, %122, %123, %124, %125, %126, %127}, "
      "{%128, %129, %130, %131}, %132, p, 1, 1, 1;\n}\n"
      : "+f"(d[0]), "+f"(d[1]), "+f"(d[2]), "+f"(d[3]), "+f"(d[4]), "+f"(d[5]), "+f"(d[6]), "+f"(d[7]), "+f"(d[8]), "+f"(d[9]), "+f"(d[10]), "+f"(d[11]), "+f"(d[12]), "+f"(d[13]), "+f"(d[14]), "+f"(d[15]), "+f"(d[16]), "+f"(d[17]), "+f"(d[18]), "+f"(d[19]), "+f"(d[20]), "+f"(d[21]), "+f"(d[22]), "+f"(d[23]), "+f"(d[24]), "+f"(d[25]), "+f"(d[26]), "+f"(d[27]), "+f"(d[28]), "+f"(d[29]), "+f"(d[30]), "+f"(d[31]), "+f"(d[32]), "+f"(d[33]), "+f"(d[34]), "+f"(d[35]), "+f"(d[36]), "+f"(d[37]), "+f"(d[38]), "+f"(d[39]), "+f"(d[40]), "+f"(d[41]), "+f"(d[42]), "+f"(d[43]), "+f"(d[44]), "+f"(d[45]), "+f"(d[46]), "+f"(d[47]), "+f"(d[48]), "+f"(d[49]), "+f"(d[50]), "+f"(d[51]), "+f"(d[52]), "+f"(d[53]), "+f"(d[54]), "+f"(d[55]), "+f"(d[56]), "+f"(d[57]), "+f"(d[58]), "+f"(d[59]), "+f"(d[60]), "+f"(d[61]), "+f"(d[62]), "+f"(d[63]), "+f"(d[64]), "+f"(d[65]), "+f"(d[66]), "+f"(d[67]), "+f"(d[68]), "+f"(d[69]), "+f"(d[70]), "+f"(d[71]), "+f"(d[72]), "+f"(d[73]), "+f"(d[74]), "+f"(d[75]), "+f"(d[76]), "+f"(d[77]), "+f"(d[78]), "+f"(d[79]), "+f"(d[80]), "+f"(d[81]), "+f"(d[82]), "+f"(d[83]), "+f"(d[84]), "+f"(d[85]), "+f"(d[86]), "+f"(d[87]), "+f"(d[88]), "+f"(d[89]), "+f"(d[90]), "+f"(d[91]), "+f"(d[92]), "+f"(d[93]), "+f"(d[94]), "+f"(d[95]), "+f"(d[96]), "+f"(d[97]), "+f"(d[98]), "+f"(d[99]), "+f"(d[100]), "+f"(d[101]), "+f"(d[102]), "+f"(d[103]), "+f"(d[104]), "+f"(d[105]), "+f"(d[106]), "+f"(d[107]), "+f"(d[108]), "+f"(d[109]), "+f"(d[110]), "+f"(d[111]), "+f"(d[112]), "+f"(d[113]), "+f"(d[114]), "+f"(d[115]), "+f"(d[116]), "+f"(d[117]), "+f"(d[118]), "+f"(d[119]), "+f"(d[120]), "+f"(d[121]), "+f"(d[122]), "+f"(d[123]), "+f"(d[124]), "+f"(d[125]), "+f"(d[126]), "+f"(d[127])
      : "r"(a0), "r"(a1), "r"(a2), "r"(a3), "l"(db));
  } else {
    asm volatile("{\n.reg .pred p;\nsetp.ne.b32 p, 0, 0;\n"
      "wgmma.mma_async.sync.aligned.m64n256k16.f32.bf16.bf16 "
      "{%0, %1, %2, %3, %4, %5, %6, %7, %8, %9, %10, %11, %12, %13, %14, %15, %16, %17, %18, %19, %20, %21, %22, %23, %24, %25, %26, %27, %28, %29, %30, %31, %32, %33, %34, %35, %36, %37, %38, %39, %40, %41, %42, %43, %44, %45, %46, %47, %48, %49, %50, %51, %52, %53, %54, %55, %56, %57, %58, %59, %60, %61, %62, %63, %64, %65, %66, %67, %68, %69, %70, %71, %72, %73, %74, %75, %76, %77, %78, %79, %80, %81, %82, %83, %84, %85, %86, %87, %88, %89, %90, %91, %92, %93, %94, %95, %96, %97, %98, %99, %100, %101, %102, %103, %104, %105, %106, %107, %108, %109, %110, %111, %112, %113, %114, %115, %116, %117, %118, %119, %120, %121, %122, %123, %124, %125, %126, %127}, "
      "{%128, %129, %130, %131}, %132, p, 1, 1, 1;\n}\n"
      : "=f"(d[0]), "=f"(d[1]), "=f"(d[2]), "=f"(d[3]), "=f"(d[4]), "=f"(d[5]), "=f"(d[6]), "=f"(d[7]), "=f"(d[8]), "=f"(d[9]), "=f"(d[10]), "=f"(d[11]), "=f"(d[12]), "=f"(d[13]), "=f"(d[14]), "=f"(d[15]), "=f"(d[16]), "=f"(d[17]), "=f"(d[18]), "=f"(d[19]), "=f"(d[20]), "=f"(d[21]), "=f"(d[22]), "=f"(d[23]), "=f"(d[24]), "=f"(d[25]), "=f"(d[26]), "=f"(d[27]), "=f"(d[28]), "=f"(d[29]), "=f"(d[30]), "=f"(d[31]), "=f"(d[32]), "=f"(d[33]), "=f"(d[34]), "=f"(d[35]), "=f"(d[36]), "=f"(d[37]), "=f"(d[38]), "=f"(d[39]), "=f"(d[40]), "=f"(d[41]), "=f"(d[42]), "=f"(d[43]), "=f"(d[44]), "=f"(d[45]), "=f"(d[46]), "=f"(d[47]), "=f"(d[48]), "=f"(d[49]), "=f"(d[50]), "=f"(d[51]), "=f"(d[52]), "=f"(d[53]), "=f"(d[54]), "=f"(d[55]), "=f"(d[56]), "=f"(d[57]), "=f"(d[58]), "=f"(d[59]), "=f"(d[60]), "=f"(d[61]), "=f"(d[62]), "=f"(d[63]), "=f"(d[64]), "=f"(d[65]), "=f"(d[66]), "=f"(d[67]), "=f"(d[68]), "=f"(d[69]), "=f"(d[70]), "=f"(d[71]), "=f"(d[72]), "=f"(d[73]), "=f"(d[74]), "=f"(d[75]), "=f"(d[76]), "=f"(d[77]), "=f"(d[78]), "=f"(d[79]), "=f"(d[80]), "=f"(d[81]), "=f"(d[82]), "=f"(d[83]), "=f"(d[84]), "=f"(d[85]), "=f"(d[86]), "=f"(d[87]), "=f"(d[88]), "=f"(d[89]), "=f"(d[90]), "=f"(d[91]), "=f"(d[92]), "=f"(d[93]), "=f"(d[94]), "=f"(d[95]), "=f"(d[96]), "=f"(d[97]), "=f"(d[98]), "=f"(d[99]), "=f"(d[100]), "=f"(d[101]), "=f"(d[102]), "=f"(d[103]), "=f"(d[104]), "=f"(d[105]), "=f"(d[106]), "=f"(d[107]), "=f"(d[108]), "=f"(d[109]), "=f"(d[110]), "=f"(d[111]), "=f"(d[112]), "=f"(d[113]), "=f"(d[114]), "=f"(d[115]), "=f"(d[116]), "=f"(d[117]), "=f"(d[118]), "=f"(d[119]), "=f"(d[120]), "=f"(d[121]), "=f"(d[122]), "=f"(d[123]), "=f"(d[124]), "=f"(d[125]), "=f"(d[126]), "=f"(d[127])
      : "r"(a0), "r"(a1), "r"(a2), "r"(a3), "l"(db));
  }
}
__device__ __forceinline__ void wgmma_n256_ss_ta0_tb1(float* d, uint64_t da, uint64_t db, bool accumulate) {
  if (accumulate) {
    asm volatile("{\n.reg .pred p;\nsetp.ne.b32 p, 1, 0;\n"
      "wgmma.mma_async.sync.aligned.m64n256k16.f32.bf16.bf16 "
      "{%0, %1, %2, %3, %4, %5, %6, %7, %8, %9, %10, %11, %12, %13, %14, %15, %16, %17, %18, %19, %20, %21, %22, %23, %24, %25, %26, %27, %28, %29, %30, %31, %32, %33, %34, %35, %36, %37, %38, %39, %40, %41, %42, %43, %44, %45, %46, %47, %48, %49, %50, %51, %52, %53, %54, %55, %56, %57, %58, %59, %60, %61, %62, %63, %64, %65, %66, %67, %68, %69, %70, %71, %72, %73, %74, %75, %76, %77, %78, %79, %80, %81, %82, %83, %84, %85, %86, %87, %88, %89, %90, %91, %92, %93, %94, %95, %96, %97, %98, %99, %100, %101, %102, %103, %104, %105, %106, %107, %108, %109, %110, %111, %112, %113, %114, %115, %116, %117, %118, %119, %120, %121, %122, %123, %124, %125, %126, %127}, "
      "%128, %129, p, 1, 1, 0, 1;\n}\n"
      : "+f"(d[0]), "+f"(d[1]), "+f"(d[2]), "+f"(d[3]), "+f"(d[4]), "+f"(d[5]), "+f"(d[6]), "+f"(d[7]), "+f"(d[8]), "+f"(d[9]), "+f"(d[10]), "+f"(d[11]), "+f"(d[12]), "+f"(d[13]), "+f"(d[14]), "+f"(d[15]), "+f"(d[16]), "+f"(d[17]), "+f"(d[18]), "+f"(d[19]), "+f"(d[20]), "+f"(d[21]), "+f"(d[22]), "+f"(d[23]), "+f"(d[24]), "+f"(d[25]), "+f"(d[26]), "+f"(d[27]), "+f"(d[28]), "+f"(d[29]), "+f"(d[30]), "+f"(d[31]), "+f"(d[32]), "+f"(d[33]), "+f"(d[34]), "+f"(d[35]), "+f"(d[36]), "+f"(d[37]), "+f"(d[38]), "+f"(d[39]), "+f"(d[40]), "+f"(d[41]), "+f"(d[42]), "+f"(d[43]), "+f"(d[44]), "+f"(d[45]), "+f"(d[46]), "+f"(d[47]), "+f"(d[48]), "+f"(d[49]), "+f"(d[50]), "+f"(d[51]), "+f"(d[52]), "+f"(d[53]), "+f"(d[54]), "+f"(d[55]), "+f"(d[56]), "+f"(d[57]), "+f"(d[58]), "+f"(d[59]), "+f"(d[60]), "+f"(d[61]), "+f"(d[62]), "+f"(d[63]), "+f"(d[64]), "+f"(d[65]), "+f"(d[66]), "+f"(d[67]), "+f"(d[68]), "+f"(d[69]), "+f"(d[70]), "+f"(d[71]), "+f"(d[72]), "+f"(d[73]), "+f"(d[74]), "+f"(d[75]), "+f"(d[76]), "+f"(d[77]), "+f"(d[78]), "+f"(d[79]), "+f"(d[80]), "+f"(d[81]), "+f"(d[82]), "+f"(d[83]), "+f"(d[84]), "+f"(d[85]), "+f"(d[86]), "+f"(d[87]), "+f"(d[88]), "+f"(d[89]), "+f"(d[90]), "+f"(d[91]), "+f"(d[92]), "+f"(d[93]), "+f"(d[94]), "+f"(d[95]), "+f"(d[96]), "+f"(d[97]), "+f"(d[98]), "+f"(d[99]), "+f"(d[100]), "+f"(d[101]), "+f"(d[102]), "+f"(d[103]), "+f"(d[104]), "+f"(d[105]), "+f"(d[106]), "+f"(d[107]), "+f"(d[108]), "+f"(d[109]), "+f"(d[110]), "+f"(d[111]), "+f"(d[112]), "+f"(d[113]), "+f"(d[114]), "+f"(d[115]), "+f"(d[116]), "+f"(d[117]), "+f"(d[118]), "+f"(d[119]), "+f"(d[120]), "+f"(d[121]), "+f"(d[122]), "+f"(d[123]), "+f"(d[124]), "+f"(d[125]), "+f"(d[126]), "+f"(d[127])
      : "l"(da), "l"(db));
  } else {
    asm volatile("{\n.reg .pred p;\nsetp.ne.b32 p, 0, 0;\n"
      "wgmma.mma_async.sync.aligned.m64n256k16.f32.bf16.bf16 "
      "{%0, %1, %2, %3, %4, %5, %6, %7, %8, %9, %10, %11, %12, %13, %14, %15, %16, %17, %18, %19, %20, %21, %22, %23, %24, %25, %26, %27, %28, %29, %30, %31, %32, %33, %34, %35, %36, %37, %38, %39, %40, %41, %42, %43, %44, %45, %46, %47, %48, %49, %50, %51, %52, %53, %54, %55, %56, %57, %58, %59, %60, %61, %62, %63, %64, %65, %66, %67, %68, %69, %70, %71, %72, %73, %74, %75, %76, %77, %78, %79, %80, %81, %82, %83, %84, %85, %86, %87, %88, %89, %90, %91, %92, %93, %94, %95, %96, %97, %98, %99, %100, %101, %102, %103, %104, %105, %106, %107, %108, %109, %110, %111, %112, %113, %114, %115, %116, %117, %118, %119, %120, %121, %122, %123, %124, %125, %126, %127}, "
      "%128, %129, p, 1, 1, 0, 1;\n}\n"
      : "=f"(d[0]), "=f"(d[1]), "=f"(d[2]), "=f"(d[3]), "=f"(d[4]), "=f"(d[5]), "=f"(d[6]), "=f"(d[7]), "=f"(d[8]), "=f"(d[9]), "=f"(d[10]), "=f"(d[11]), "=f"(d[12]), "=f"(d[13]), "=f"(d[14]), "=f"(d[15]), "=f"(d[16]), "=f"(d[17]), "=f"(d[18]), "=f"(d[19]), "=f"(d[20]), "=f"(d[21]), "=f"(d[22]), "=f"(d[23]), "=f"(d[24]), "=f"(d[25]), "=f"(d[26]), "=f"(d[27]), "=f"(d[28]), "=f"(d[29]), "=f"(d[30]), "=f"(d[31]), "=f"(d[32]), "=f"(d[33]), "=f"(d[34]), "=f"(d[35]), "=f"(d[36]), "=f"(d[37]), "=f"(d[38]), "=f"(d[39]), "=f"(d[40]), "=f"(d[41]), "=f"(d[42]), "=f"(d[43]), "=f"(d[44]), "=f"(d[45]), "=f"(d[46]), "=f"(d[47]), "=f"(d[48]), "=f"(d[49]), "=f"(d[50]), "=f"(d[51]), "=f"(d[52]), "=f"(d[53]), "=f"(d[54]), "=f"(d[55]), "=f"(d[56]), "=f"(d[57]), "=f"(d[58]), "=f"(d[59]), "=f"(d[60]), "=f"(d[61]), "=f"(d[62]), "=f"(d[63]), "=f"(d[64]), "=f"(d[65]), "=f"(d[66]), "=f"(d[67]), "=f"(d[68]), "=f"(d[69]), "=f"(d[70]), "=f"(d[71]), "=f"(d[72]), "=f"(d[73]), "=f"(d[74]), "=f"(d[75]), "=f"(d[76]), "=f"(d[77]), "=f"(d[78]), "=f"(d[79]), "=f"(d[80]), "=f"(d[81]), "=f"(d[82]), "=f"(d[83]), "=f"(d[84]), "=f"(d[85]), "=f"(d[86]), "=f"(d[87]), "=f"(d[88]), "=f"(d[89]), "=f"(d[90]), "=f"(d[91]), "=f"(d[92]), "=f"(d[93]), "=f"(d[94]), "=f"(d[95]), "=f"(d[96]), "=f"(d[97]), "=f"(d[98]), "=f"(d[99]), "=f"(d[100]), "=f"(d[101]), "=f"(d[102]), "=f"(d[103]), "=f"(d[104]), "=f"(d[105]), "=f"(d[106]), "=f"(d[107]), "=f"(d[108]), "=f"(d[109]), "=f"(d[110]), "=f"(d[111]), "=f"(d[112]), "=f"(d[113]), "=f"(d[114]), "=f"(d[115]), "=f"(d[116]), "=f"(d[117]), "=f"(d[118]), "=f"(d[119]), "=f"(d[120]), "=f"(d[121]), "=f"(d[122]), "=f"(d[123]), "=f"(d[124]), "=f"(d[125]), "=f"(d[126]), "=f"(d[127])
      : "l"(da), "l"(db));
  }
}
__device__ __forceinline__ void wgmma_n256_ssp_ta0_tb1(float* d, uint64_t da, uint64_t db, int accumulate) {
    asm volatile("{\n.reg .pred p;\nsetp.ne.b32 p, %130, 0;\n"
      "wgmma.mma_async.sync.aligned.m64n256k16.f32.bf16.bf16 "
      "{%0, %1, %2, %3, %4, %5, %6, %7, %8, %9, %10, %11, %12, %13, %14, %15, %16, %17, %18, %19, %20, %21, %22, %23, %24, %25, %26, %27, %28, %29, %30, %31, %32, %33, %34, %35, %36, %37, %38, %39, %40, %41, %42, %43, %44, %45, %46, %47, %48, %49, %50, %51, %52, %53, %54, %55, %56, %57, %58, %59, %60, %61, %62, %63, %64, %65, %66, %67, %68, %69, %70, %71, %72, %73, %74, %75, %76, %77, %78, %79, %80, %81, %82, %83, %84, %85, %86, %87, %88, %89, %90, %91, %92, %93, %94, %95, %96, %97, %98, %99, %100, %101, %102, %103, %104, %105, %106, %107, %108, %109, %110, %111, %112, %113, %114, %115, %116, %117, %118, %119, %120, %121, %122, %123, %124, %125, %126, %127}, "
      "%128, %129, p, 1, 1, 0, 1;\n}\n"
      : "+f"(d[0]), "+f"(d[1]), "+f"(d[2]), "+f"(d[3]), "+f"(d[4]), "+f"(d[5]), "+f"(d[6]), "+f"(d[7]), "+f"(d[8]), "+f"(d[9]), "+f"(d[10]), "+f"(d[11]), "+f"(d[12]), "+f"(d[13]), "+f"(d[14]), "+f"(d[15]), "+f"(d[16]), "+f"(d[17]), "+f"(d[18]), "+f"(d[19]), "+f"(d[20]), "+f"(d[21]), "+f"(d[22]), "+f"(d[23]), "+f"(d[24]), "+f"(d[25]), "+f"(d[26]), "+f"(d[27]), "+f"(d[28]), "+f"(d[29]), "+f"(d[30]), "+f"(d[31]), "+f"(d[32]), "+f"(d[33]), "+f"(d[34]), "+f"(d[35]), "+f"(d[36]), "+f"(d[37]), "+f"(d[38]), "+f"(d[39]), "+f"(d[40]), "+f"(d[41]), "+f"(d[42]), "+f"(d[43]), "+f"(d[44]), "+f"(d[45]), "+f"(d[46]), "+f"(d[47]), "+f"(d[48]), "+f"(d[49]), "+f"(d[50]), "+f"(d[51]), "+f"(d[52]), "+f"(d[53]), "+f"(d[54]), "+f"(d[55]), "+f"(d[56]), "+f"(d[57]), "+f"(d[58]), "+f"(d[59]), "+f"(d[60]), "+f"(d[61]), "+f"(d[62]), "+f"(d[63]), "+f"(d[64]), "+f"(d[65]), "+f"(d[66]), "+f"(d[67]), "+f"(d[68]), "+f"(d[69]), "+f"(d[70]), "+f"(d[71]), "+f"(d[72]), "+f"(d[73]), "+f"(d[74]), "+f"(d[75]), "+f"(d[76]), "+f"(d[77]), "+f"(d[78]), "+f"(d[79]), "+f"(d[80]), "+f"(d[81]), "+f"(d[82]), "+f"(d[83]), "+f"(d[84]), "+f"(d[85]), "+f"(d[86]), "+f"(d[87]), "+f"(d[88]), "+f"(d[89]), "+f"(d[90]), "+f"(d[91]), "+f"(d[92]), "+f"(d[93]), "+f"(d[94]), "+f"(d[95]), "+f"(d[96]), "+f"(d[97]), "+f"(d[98]), "+f"(d[99]), "+f"(d[100]), "+f"(d[101]), "+f"(d[102]), "+f"(d[103]), "+f"(d[104]), "+f"(d[105]), "+f"(d[106]), "+f"(d[107]), "+f"(d[108]), "+f"(d[109]), "+f"(d[110]), "+f"(d[111]), "+f"(d[112]), "+f"(d[113]), "+f"(d[114]), "+f"(d[115]), "+f"(d[116]), "+f"(d[117]), "+f"(d[118]), "+f"(d[119]), "+f"(d[120]), "+f"(d[121]), "+f"(d[122]), "+f"(d[123]), "+f"(d[124]), "+f"(d[125]), "+f"(d[126]), "+f"(d[127])
      : "l"(da), "l"(db), "r"(accumulate));
}

template <int N> __device__ __forceinline__ void quad_sum(float* m) {
#pragma unroll
  for (int o = 1; o <= 2; o <<= 1) {
    float t[N];
#pragma unroll
    for (int i = 0; i < N; i++) t[i] = __shfl_xor_sync(~0u, m[i], o);
#pragma unroll
    for (int i = 0; i < N; i++) m[i] += t[i];
  }
}
__device__ __forceinline__ bool softmax_unsafe(const uint32_t* t, float l0, float l1) {
  const float m0 = fmaxf(bf_lo(t[0]) + bf_hi(t[0]), bf_lo(t[2]) + bf_hi(t[2])), m1 = fmaxf(bf_lo(t[1]) + bf_hi(t[1]), bf_lo(t[3]) + bf_hi(t[3]));
  return __any_sync(~0u, !(m0 * l0 < 2500.f) | !(m1 * l1 < 2500.f));
}
__device__ __forceinline__ void softmax_shift(float* p, float c0, float c1) {
#pragma unroll 1
  for (int it = 0; it < 8; it++) {
    float mx = p[0], mn = p[0];
#pragma unroll
    for (int j = 1; j < 8; j++) { mx = fmaxf(mx, p[(j >> 1) * 4 + (j & 1)]); mn = fminf(mn, p[(j >> 1) * 4 + (j & 1)]); }
#pragma unroll
    for (int o = 1; o <= 2; o <<= 1) { mx = fmaxf(mx, __shfl_xor_sync(~0u, mx, o)); mn = fminf(mn, __shfl_xor_sync(~0u, mn, o)); }
    const float half = fminf(0.5f * (mx - mn), 50.f * rcp(it & 1 ? c1 : c0));
    float r[8];
#pragma unroll
    for (int j = 0; j < 8; j++) {
      const float v = p[(j >> 1) * 4 + (j & 1)];
      r[j] = fmaxf(v - mx + half, 0.f) + fminf(v - mn - half, 0.f) + (v - v);
    }
#pragma unroll
    for (int k = 0; k < 7; k++)
#pragma unroll
      for (int j = 0; j < 8; j++) p[(k >> 1) * 16 + (k & 1) * 2 + (j >> 1) * 4 + (j & 1)] = p[((k + 1) >> 1) * 16 + ((k + 1) & 1) * 2 + (j >> 1) * 4 + (j & 1)];
#pragma unroll
    for (int j = 0; j < 8; j++) p[50 + (j >> 1) * 4 + (j & 1)] = r[j];
  }
}
template <int J0 = 0, int J1 = 8> __device__ __forceinline__ void k_exp(const float* p, float c0, float c1, float* e, float* s) {
#pragma unroll
  for (int j = J0; j < J1; j++) {
    e[2 * j] = ex2(p[2 * j] * (j & 1 ? c1 : c0));
    e[2 * j + 1] = ex2(p[2 * j + 1] * (j & 1 ? c1 : c0));
    e[16 + j] = rcp(e[2 * j] * e[2 * j + 1]);
    const float t = e[2 * j] + e[2 * j + 1];
    s[j & 1] = j < 2 ? t : s[j & 1] + t;
    s[2 + (j & 1)] = j < 2 ? e[16 + j] * t : fmaf(e[16 + j], t, s[2 + (j & 1)]);
  }
}
template <int J0 = 0, int J1 = 8> __device__ __forceinline__ void q_exp(const float* p, float c0, float c1, uint32_t* f) {
#pragma unroll
  for (int j = J0; j < J1; j++) {
    const float e0 = ex2(p[2 * j] * (j & 1 ? c1 : c0)), e1 = ex2(p[2 * j + 1] * (j & 1 ? c1 : c0)), r = rcp(e0 * e1);
    f[j] = pack2(e0, e1);
    f[8 + j] = bmul2(f[j], pack2(r, r));
  }
}

#define FMA8(A, U, X)                                                                                        \
  A[0] = fmaf(bf_lo(U.x), X, A[0]); A[1] = fmaf(bf_hi(U.x), X, A[1]); A[2] = fmaf(bf_lo(U.y), X, A[2]); A[3] = fmaf(bf_hi(U.y), X, A[3]); \
  A[4] = fmaf(bf_lo(U.z), X, A[4]); A[5] = fmaf(bf_hi(U.z), X, A[5]); A[6] = fmaf(bf_lo(U.w), X, A[6]); A[7] = fmaf(bf_hi(U.w), X, A[7])

__device__ __forceinline__ uint32_t routed_row(const __nv_bfloat16* x, uint32_t tag, int lane, uint4* xr) {
  uint32_t best = 0, sv = 0;
#pragma unroll 1
  for (int it = 0; it < SPIN_MAX; it++) {
    const int sel = 2047 - (best & 0x7ff);
#pragma unroll
    for (int i = 0; i < 4; i++) xr[i] = ldg_nc(x + (size_t)sel * DM + i * 256 + lane * 8);
    const unsigned long long st = ld_rlx64(g_stat + sel);
    const uint4 b0 = ld_rlx128(g_best + lane * 2), b1 = ld_rlx128(g_best + 64 + lane * 2);
    const uint32_t m = __reduce_max_sync(~0u, max(max(b0.y == tag ? b0.x : 0u, b0.w == tag ? b0.z : 0u), max(b1.y == tag ? b1.x : 0u, b1.w == tag ? b1.z : 0u)));
    sv = (uint32_t)st;
    if (__all_sync(~0u, b0.y == tag && b0.w == tag && b1.y == tag && b1.w == tag && m == best && (uint32_t)(st >> 32) == tag)) break;
    best = m;
    if (AM_NS) __nanosleep(AM_NS);
  }
  const uint32_t m2 = (sv & 0xffff0000u) | (sv >> 16);
  const float rs = rcp(bf_lo(sv));
#pragma unroll
  for (int i = 0; i < 4; i++) {
    const uint32_t d0 = bsub2(xr[i].x, m2), d1 = bsub2(xr[i].y, m2), d2 = bsub2(xr[i].z, m2), d3 = bsub2(xr[i].w, m2);
    xr[i] = make_uint4(pack2(bf_lo(d0) * rs, bf_hi(d0) * rs), pack2(bf_lo(d1) * rs, bf_hi(d1) * rs), pack2(bf_lo(d2) * rs, bf_hi(d2) * rs),
                       pack2(bf_lo(d3) * rs, bf_hi(d3) * rs));
  }
  return best;
}

struct Params {
  const __nv_bfloat16 *x, *wqkv, *wo, *w_r, *w_down;
  uint32_t zA, zB;
};

template <bool BY_SMID> __global__ void __launch_bounds__(384, 1)
fused_kernel(const Params P, const __grid_constant__ CUtensorMap mX, const __grid_constant__ CUtensorMap mWkv, const __grid_constant__ CUtensorMap mWq,
             const __grid_constant__ CUtensorMap mWo, const __grid_constant__ CUtensorMap mPhi, const __grid_constant__ CUtensorMap mWp,
             const __grid_constant__ CUtensorMap mOut, const __grid_constant__ CUtensorMap mWc,
             const __grid_constant__ CUtensorMap mG, const __grid_constant__ CUtensorMap mU, const __grid_constant__ CUtensorMap mD,
             const __grid_constant__ CUtensorMap mXs, const __grid_constant__ CUtensorMap mG2, const __grid_constant__ CUtensorMap mU2) {
  constexpr uint32_t sb = SB, bar = SB + SM_BAR;
  int bid = blockIdx.x;
  if (BY_SMID) {
    uint32_t sm;
    asm volatile("mov.u32 %0, %%smid;" : "=r"(sm));
    const uint32_t tq = (sm - 64) >> 1, q7 = (tq * 37) >> 8;
    const uint32_t gpc = sm < 64 ? (sm >> 1) & 7 : 1 + tq - 7 * q7, idx = (sm < 64 ? sm >> 4 : 4 + q7) * 2 + (sm & 1);
    bid = sm < 120 ? ((PTAB >> (4 * gpc)) & 7) * 16 + idx : sm < 124 ? sm + 8 : sm - 116;
  }
  const int hg = ((bid >> 2) & 3) + 4 * ((bid >> 4) & 1), mb = (bid & 3) + 4 * ((bid >> 5) & 3);
  if (bid < NCTA && threadIdx.x < 256) {
    const uint32_t r0 = threadIdx.x >> 3, c = threadIdx.x & 7, dst = sb + 2 * KV_STAGE + r0 * 128 + ((c ^ (r0 & 7)) << 4);
    const char* xs = (const char*)P.x + (size_t)(mb * 128 + r0) * 2048 + c * 16;
    const char* ws = (const char*)P.wqkv + (size_t)r0 * 6144 + 2048 + hg * 256 + c * 16;
#pragma unroll
    for (int i = 0; i < 4; i++) cp_async16(dst + i * 4096, xs + i * 65536);
#pragma unroll
    for (int i = 0; i < 8; i++) cp_async16(dst + 16384 + i * 4096, ws + (i & 1) * 196608 + (i >> 2) * 2048 + ((i >> 1) & 1) * 128);
  }
  extern __shared__ __align__(1024) uint8_t smem[];
  if (smem_u32(smem) != SB) __trap();
  const int warp = __shfl_sync(~0u, threadIdx.x >> 5, 0);

  if (bid >= NCTA) {
    constexpr uint32_t XV = SM_WPHI, ONES = SM_ZT, BF = bar, BE = bar + 48, BX = bar + 96;
    constexpr int NJ = (DM - GROWS) / 64;
    const int lane = lane_id(), sp = bid - NCTA;
    const uint32_t tag = ld_rlx(g_epoch + bid * 32 + lane) + 1;
    if (warp == 8 && elect_one()) {
#pragma unroll 1
      for (int i = 0; i < 13; i++) mbar_init(bar + 8 * i, i >= 6 && i < 12 ? 8 : 1);
    }
    if (warp == 9) { sts64u(sb + ONES + lane * 8, 0x3f803f80u, 0x3f803f80u); fence_async_smem(); }
    __syncthreads();
    if (warp == 8) {
      if (elect_one()) {
        uint32_t s = 0, ph = 1;
        for (const long long c0 = clock64(); clock64() - c0 < SP_DELAY;) {}
#pragma unroll 1
        for (int job = 0; job < 8; job++) {
          const CUtensorMap* m = job == 0 ? &mWq : sp & 2 ? &mU2 : &mG2;
          const int g0 = job ? (sp & 1) * 28 + job * 4 - 4 : sp * 4;
#pragma unroll 1
          for (int row = job ? GROWS : 0; row < DM; row += 64) {
            mbar_wait(BE + 8 * s, ph);
            mbar_expect_tx(BF + 8 * s, Q_STAGE);
            tma4d(sb + s * Q_STAGE, m, 0, row, g0, 0, BF + 8 * s);
            tma4d(sb + s * Q_STAGE + 16384, m, 0, row, g0 + 2, 0, BF + 8 * s);
            if (++s == 6) { s = 0; ph ^= 1; }
          }
        }
      }
    } else if (warp == 9) {
      uint4 xr[4];
      routed_row(P.x, tag, lane, xr);
#pragma unroll
      for (int i = 0; i < 4; i++) sts128u(sb + XV + i * 512 + lane * 16, xr[i].x, xr[i].y, xr[i].z, xr[i].w);
      fence_async_smem();
      __syncwarp();
      if (lane == 0) mbar_arrive(BX);
    } else if (warp < 8) {
      uint32_t s = 0, ph = 0;
#pragma unroll 1
      for (int job = 0; job < 8; job++) {
        float d[8] = {0.f, 0.f, 0.f, 0.f, 0.f, 0.f, 0.f, 0.f};
        if (job == 1) mbar_wait(BX, 0);
#pragma unroll 1
        for (int i = 0; i < (job ? NJ : 16); i++) {
          mbar_wait(BF + 8 * s, ph);
          wg_fence();
#pragma unroll
          for (int k = 0; k < 8; k++)
            wgmma_n8_ss_ta1_tb0(d + 4 * (k >> 2), mkdesc(sb + k * 2048, 16, 1024, 1, s * (Q_STAGE / 16) + (warp >> 2) * 1024),
                                mkdesc(sb, 16, 128, 0, job ? (XV + GROWS * 2) / 16 + i * 8 + (k & 3) * 2 : ONES / 16), 1);
          wg_commit();
          wg_wait<0>();
          if (lane == 0) mbar_arrive(BE + 8 * s);
          if (++s == 6) { s = 0; ph ^= 1; }
        }
        reg_fence<8>(d);
        float* dst = (job ? g_gp + sp * 1792 + job * 256 - 256 : g_cs + sp * 256) + (warp >> 2) * 128 + (warp & 3) * 16 + (lane >> 2);
        if ((lane & 3) == 0) {
#pragma unroll
          for (int i = 0; i < 4; i++) st_rlx(dst + (i >> 1) * 64 + (i & 1) * 8, mark(__float_as_uint(d[2 * i]), tag & 1));
        }
        __syncwarp();
      }
      if (warp == 0) g_epoch[bid * 32 + lane] = tag;
    }
    return;
  }
#define Q_SLAB(J) ((J) < 8 ? ((J) + 8 - 2 * (hg & 4)) & 15 : 2 * (hg & 4) + 2 * ((J) & 3) + ((J) >> 2 & 1))
#define Q_AOFF(J) ((J) == 8 + (hg & 3) ? SM_X0 : (J) == 12 + (hg & 3) ? SM_X1 : ((J) & 3) * Q_STAGE)
#define Q_LOAD(J)                                                                                            \
  do {                                                                                                       \
    const uint32_t fb_ = bar + B_FULLQ + 8 * ((J) & 3);                                                      \
    const int k_ = Q_SLAB(J) * 64;                                                                           \
    mbar_expect_tx(fb_, Q_STAGE);                                                                            \
    mbar_arrive2(fb_);                                                                                       \
    tma2d(sb + Q_AOFF(J), &mX, k_, mb * 128, fb_);                                                           \
    tma4d(sb + ((J) & 3) * Q_STAGE + 16384, &mWq, 0, k_, hg * 2, 0, fb_);                                    \
  } while (0)
  if (warp >= 8) {
    asm volatile("setmaxnreg.dec.sync.aligned.u32 %0;" ::"n"(REG_H));
    const int lane = lane_id();
    const int f = (warp - 9) & 3;
    if (f == 3) {
      if (elect_one()) {
        PROF(0); PROFT(32);
#pragma unroll
        for (int s = 0; s < 3; s++) mbar_init(bar + B_FULLKV + 8 * s, 1);
      }
      __syncwarp();
      asm volatile("bar.arrive 14, 288;" ::: "memory");
      if (elect_one()) {
#pragma unroll
        for (int s = 0; s < 2; s++) {
          mbar_expect_tx(bar + B_FULLKV + 8 * s, KV_STAGE);
          tma2d(sb + s * KV_STAGE, &mX, (s + 1) * 64, mb * 128, bar + B_FULLKV + 8 * s);
          tma4d(sb + s * KV_STAGE + 16384, &mWkv, 0, (s + 1) * 64, hg * 2, 1, bar + B_FULLKV + 8 * s);
        }
      }
      __syncwarp();
    }
    const uint32_t ep = ld_rlx(g_epoch + bid * 32 + lane);
    if (f < 2) {
#pragma unroll
      for (int i = 0; i < 2; i++) {
        const uint4 u = __ldg((const uint4*)P.w_r + (f * 2 + i) * 32 + lane);
        sts128u(sb + SM_XSEL + (f * 2 + i) * 512 + lane * 16, u.x, u.y, u.z, u.w);
      }
    }
    bar_sync(13, 384);
    const uint32_t tag = ep + 1, par = tag & 1;
    const bool ffn = bid < NFFN;
    const int fb = bid, cu = bid >> 1, ch = bid & 1;
#define CS_STORE(SEC, C)                                                                                     \
  _Pragma("unroll") for (int r = 0; r < 3; r++) {                                                            \
    const uint32_t h0 = pack2(C.x, C.y), h1 = pack2(C.z, C.w);                                               \
    sts64u(sb + SM_CST + (SEC) * 1024 + (lane >> 4) * 512 + (lane & 1) * 8 + r * 128 + ((((lane & 15) >> 1) ^ (r + (lane >> 4) * 4)) << 4), h0, h1); \
    C.x -= bf_lo(h0); C.y -= bf_hi(h0); C.z -= bf_lo(h1); C.w -= bf_hi(h1);                                  \
  }
#define BAD4(U) ((U.x ^ par) | (U.y ^ par) | (U.z ^ par) | (U.w ^ par))
    const int n0 = f < 2 ? 0 : 2 * f - 3, ne = FFN_OFF || !ffn ? 3 : f == 3 ? 3 + G8 : 3 + GN;
    const uint32_t fsb = sb + SM_FST + ((f + 1) & 3) * 8192, fbar = bar + B_FST + f * 16, fst = fsb + (lane >> 4) * 2048 + (lane & 15) * 16;
    const CUtensorMap *ma = &mWc, *mc = &mWc;
    int sx = 1024 + cu * 32, sy = ch * 512 + f * 192, sdy = 32;
#define STAGEG(N)                                                                                            \
  do {                                                                                                       \
    if ((N) == 3) { ma = &mG; mc = &mU; sx = fb * 32; sy = f * (GN * 32);  sdy = 0; }                        \
    if ((N) < ne && elect_one()) {                                                                           \
      const uint32_t dst_ = fsb + ((N) & 1) * 4096, b_ = fbar + ((N) & 1) * 8;                               \
      mbar_expect_tx(b_, 4096);                                                                              \
      tma2d(dst_, ma, sx, sy, b_);                                                                           \
      tma2d(dst_ + 2048, mc, sx, sy + sdy, b_);                                                              \
    }                                                                                                        \
    sy += 32 + sdy;                                                                                          \
  } while (0)
    float a[8], gsum = 0.f, usum = 0.f;
    {
      if (f == 3) {
        if (elect_one()) {
          mbar_expect_tx(bar + B_XST, 16384);
          tma3d(sb + SM_XST, &mXs, 0, bid * 16, 0, bar + B_XST);
          mbar_expect_tx(bar + B_WPHI, 8192);
          tma2d(sb + SM_WPHI, &mPhi, 0, hg * 128, bar + B_WPHI);
          prefetch_map(&mWq); prefetch_map(&mWo); prefetch_map(&mWp); prefetch_map(&mD);
          PROF(31);
        }
        __syncwarp();
      } else {
        if (lane == 0) prefetch_map(f == 0 ? &mWc : f == 1 ? &mG : &mU);
        if (f == 2) ((float2*)g_y[par])[bid * 32 + lane] = make_float2(0.f, 0.f);
      }
      float st[13];
#pragma unroll
      for (int i = 0; i < 13; i++) st[i] = 0.f;
#pragma unroll 1
      for (int i = 0; i < 4; i++) {
        mbar_wait(bar + B_XST + 8 * (i >> 1), 0);
        if (f == 0 && lane == 0 && i == 0) PROF(1);
        const uint4 wu = lds128u(sb + SM_XSEL + i * 512 + lane * 16);
        const float wf[8] = {bf_lo(wu.x), bf_hi(wu.x), bf_lo(wu.y), bf_hi(wu.y), bf_lo(wu.z), bf_hi(wu.z), bf_lo(wu.w), bf_hi(wu.w)};
        st[12] += ((wf[0] + wf[1]) + (wf[2] + wf[3])) + ((wf[4] + wf[5]) + (wf[6] + wf[7]));
#pragma unroll
        for (int r = 0; r < 4; r++) {
          const uint4 u = lds128u(sb + SM_XST + i * 8192 + (4 * f + r) * 512 + lane * 16);
          const float xf[8] = {bf_lo(u.x), bf_hi(u.x), bf_lo(u.y), bf_hi(u.y), bf_lo(u.z), bf_hi(u.z), bf_lo(u.w), bf_hi(u.w)};
#pragma unroll
          for (int k = 0; k < 8; k++) { st[r] += xf[k]; st[4 + r] = fmaf(xf[k], xf[k], st[4 + r]); st[8 + r] = fmaf(xf[k], wf[k], st[8 + r]); }
        }
        if (i >= 2 && f < 3) STAGEG(n0 + i - 2);
      }
      const bool up = lane & 16, up2 = lane & 8;
#pragma unroll
      for (int q = 0; q < 3; q++) {
        const float k0 = up ? st[4 * q + 2] : st[4 * q], k1 = up ? st[4 * q + 3] : st[4 * q + 1];
        const float o0 = up ? st[4 * q] : st[4 * q + 2], o1 = up ? st[4 * q + 1] : st[4 * q + 3];
        const float m0 = k0 + __shfl_xor_sync(~0u, o0, 16), m1 = k1 + __shfl_xor_sync(~0u, o1, 16);
        a[q] = (up2 ? m1 : m0) + __shfl_xor_sync(~0u, up2 ? m0 : m1, 8);
      }
      a[3] = st[12] + __shfl_xor_sync(~0u, st[12], 16);
      a[3] += __shfl_xor_sync(~0u, a[3], 8);
#pragma unroll
      for (int o = 4; o; o >>= 1)
#pragma unroll
        for (int q = 0; q < 4; q++) a[q] += __shfl_xor_sync(~0u, a[q], o);
      if ((lane & 7) == 0) sts128(sb + SM_ROWS + (4 * f + (lane >> 3)) * 16, a[0], a[1], a[2], a[3]);
      if (f < 3) asm volatile("bar.arrive 7, 128;" ::: "memory");
    }
    if (f == 3) {
      bar_sync(7, 128);
      const int row = bid * 16 + (lane & 15);
      const float4 v = lds128(sb + SM_ROWS + (lane & 15) * 16);
      const float mf = v.x * (1.f / DM), mean = bf_round(mf), var = fmaxf(fmaf(-mf, mf, v.y * (1.f / DM)), 0.f);
      const float sd = bf_round(sqrt_approx(bf_round(bf_round(var) + 1e-5f)));
      const uint32_t rb = pack2(fmaf(-mean, v.w, v.z) * rcp(sd), 0.f) & 0xffffu, ord = (rb & 0x8000u) ? (~rb & 0xffffu) : (rb | 0x8000u);
      uint32_t best = __reduce_max_sync(~0u, (ord << 16) | (uint32_t)(2047 - row));
      if (lane < 16) st_rlx64(g_stat + row, ((unsigned long long)tag << 32) | __float_as_uint(mean) | (__float_as_uint(sd) >> 16));
      if (lane == 0) { asm volatile("red.relaxed.gpu.global.max.u64 [%0], %1;" ::"l"(g_best + bid), "l"(((unsigned long long)tag << 32) | best) : "memory"); PROF(17); }
#pragma unroll 1
      for (int n = 3; n < 5; n++) STAGEG(n);
      {
        uint4 xr[4];
        best = routed_row(P.x, tag, lane, xr);
#pragma unroll
        for (int i = 0; i < (GROWS + 255) / 256; i++) {
          const uint32_t dst = sb + SM_XSEL + i * 1024 + (lane >> 2) * 128 + (lane & 3) * 8;
          sts64(dst, bf_lo(xr[i].x), bf_lo(xr[i].z)); sts64(dst + 32, bf_hi(xr[i].x), bf_hi(xr[i].z));
          sts64(dst + 64, bf_lo(xr[i].y), bf_lo(xr[i].w)); sts64(dst + 96, bf_hi(xr[i].y), bf_hi(xr[i].w));
        }
        sts64u(sb + SM_RED + 16, tag, best);
        __syncwarp();
        if (lane == 0) { mbar_arrive(bar + B_XS); PROF(19); }
      }
      unsigned long long sv4[4];
      uint4 u[4];
#pragma unroll 1
      for (int it = 0; it < SPIN_MAX; it++) {
#pragma unroll
        for (int i = 0; i < 4; i++) { u[i] = ld_rlx128(g_cs + (1 + i) * 1024 + hg * 128 + lane * 4); sv4[i] = ld_rlx64(g_stat + mb * 128 + i * 32 + lane); }
        bool ok = ((BAD4(u[0]) | BAD4(u[1]) | BAD4(u[2]) | BAD4(u[3])) & 1) == 0;
#pragma unroll
        for (int i = 0; i < 4; i++) ok = ok && (uint32_t)(sv4[i] >> 32) == tag;
        if (__all_sync(~0u, ok)) break;
        __nanosleep(200);
      }
#pragma unroll
      for (int i = 0; i < 4; i++) {
        const uint32_t sv = (uint32_t)sv4[i], sd2 = (sv << 16) | (sv & 0xffffu);
        sts64(sb + SM_STAT + (i * 32 + lane) * 8, -bf_hi(sv), rcp(bf_lo(sv)));
        sts128u(sb + SM_SDT + lane * 64 + ((i ^ ((lane >> 1) & 3)) << 4), sd2, sd2, sd2, sd2);
      }
#pragma unroll
      for (int i = 0; i < 2; i++) {
        float4 c = make_float4(unmark(u[i].x) + unmark(u[i + 2].x), unmark(u[i].y) + unmark(u[i + 2].y), unmark(u[i].z) + unmark(u[i + 2].z),
                               unmark(u[i].w) + unmark(u[i + 2].w));
        CS_STORE(i, c);
      }
      fence_async_smem();
      bar_sync(8, 64);
      if (lane == 0) { mbar_arrive(bar + B_CS); PROF(10); }
    }
    {
      uint32_t xa = sb + SM_RED + 32, xstep = 0;
      const uint32_t zero = __float_as_uint(lds32(sb + SM_RED + 12));
#pragma unroll 1
      for (int ph = f == 3; ph < 2; ph++) {
#pragma unroll
        for (int j = 0; j < 8; j++) a[j] = 0.f;
        if (ph && f == 0) {
        {
          mbar_wait(bar + B_WPHI, 0);
          float nq[8] = {0.f, 0.f, 0.f, 0.f, 0.f, 0.f, 0.f, 0.f};
  #pragma unroll 2
          for (int r = 0; r < 16; r++) {
            const uint4 u = lds128u(sb + SM_WPHI + ((lane >> 2) * 16 + r) * 64 + (((lane ^ (r >> 1)) & 3) << 4));
            nq[0] = fmaf(bf_lo(u.x), bf_lo(u.x), nq[0]); nq[1] = fmaf(bf_hi(u.x), bf_hi(u.x), nq[1]); nq[2] = fmaf(bf_lo(u.y), bf_lo(u.y), nq[2]);
            nq[3] = fmaf(bf_hi(u.y), bf_hi(u.y), nq[3]); nq[4] = fmaf(bf_lo(u.z), bf_lo(u.z), nq[4]); nq[5] = fmaf(bf_hi(u.z), bf_hi(u.z), nq[5]);
            nq[6] = fmaf(bf_lo(u.w), bf_lo(u.w), nq[6]); nq[7] = fmaf(bf_hi(u.w), bf_hi(u.w), nq[7]);
          }
          uint32_t m = 0;
  #pragma unroll
          for (int i = 0; i < 8; i++) m = max(m, __float_as_uint(nq[i] + __shfl_xor_sync(~0u, nq[i], 4)) & 0x7fffffffu);
          sts32(sb + SM_RED + 24, 4.2f * __uint_as_float(__reduce_max_sync(~0u, m)));
        }
          asm volatile("bar.arrive 8, 64;" ::: "memory");
        }
        if (ph) { mbar_wait(bar + B_XS, 0); xa = sb + SM_XSEL + f * (GN * 128) + ((lane >> 2) & 3) * 32; xstep = 128; }
#pragma unroll 1
        for (int n = ph ? 3 : n0; n < (ph ? ne : 3); n++) {
          const float4 x0 = lds128(xa), x1 = lds128(xa + 16);
          xa += xstep;
          mbar_wait(fbar + (n & 1) * 8, ((n - n0) >> 1) & 1);
          uint4 u[8];
#pragma unroll
          for (int j = 0; j < 8; j++) u[j] = lds128u(fst + (n & 1) * 4096 + j * 256);
          FMA8(a, u[0], x0.x); FMA8(a, u[1], x0.y); FMA8(a, u[2], x0.z); FMA8(a, u[3], x0.w);
          if (__any_sync(~0u, ((u[4].x | u[5].x | u[6].x | u[7].x | __float_as_uint(a[0]) | __float_as_uint(a[7])) & zero) == 0)) STAGEG(n + 2);
          FMA8(a, u[4], x1.x); FMA8(a, u[5], x1.y); FMA8(a, u[6], x1.z); FMA8(a, u[7], x1.w);
        }
#pragma unroll
        for (int o = 4; o <= 8; o <<= 1)
#pragma unroll
          for (int j = 0; j < 8; j++) a[j] += __shfl_xor_sync(~0u, a[j], o);
        if (ph && lane == 0) mbar_arrive(bar + B_FFN);
        const uint32_t red = ph ? sb + SM_GRED : sb + SM_RED + 64;
        if ((lane & 12) == 0) {
          const uint32_t d = red + f * 256 + (lane >> 4) * 128 + (lane & 3) * 32;
          sts128(d, a[0], a[1], a[2], a[3]); sts128(d + 16, a[4], a[5], a[6], a[7]);
        }
        if (f != 2) {
          asm volatile("bar.arrive %0, %1;" ::"r"(4 + ph), "r"(96 + 32 * ph) : "memory");
        } else {
          bar_sync(4 + ph, 96 + 32 * ph);
          const uint32_t ra = red + lane * 4;
          gsum = lds32(ra) + lds32(ra + 256) + lds32(ra + 512);
          usum = lds32(ra + 128) + lds32(ra + 384) + lds32(ra + 640);
          if (!ph) st_rlx(g_cs + 1024 + ch * 2048 + cu * 32 + lane, mark(__float_as_uint(gsum + usum), par));
          else { gsum += lds32(ra + 768); usum += lds32(ra + 896); }
          if (lane == 0) PROF(ph ? 34 : 18);
        }
      }
    }
    if (f == 3) {
      if (elect_one()) {
        PROF(7);
        mbar_wait(bar + B_FULLQ, 0);
#pragma unroll 1
        for (int j = 3; j < 16; j++) {
          mbar_wait(bar + (j < 4 ? B_EMPTYKV + 16 : B_EMPTYQ + 8 * (j & 3)), ((j >> 2) & 1) ^ 1);
          if (j == 12 + (hg & 3)) mbar_wait(bar + B_KVST + 8, 0);
          Q_LOAD(j);
        }
        PROF(47);
        mbar_expect_tx(bar + B_DN, 65536);
#pragma unroll 1
        for (int i = 0; i < 4; i++) {
          mbar_wait(bar + B_EMPTYQ + 8 * i, 1);
          tma3d(sb + i * Q_STAGE, &mD, 0, fb * 32, i * 4, bar + B_DN);
        }
        PROF(48);
#pragma unroll 1
        for (int i = 0; i < 16; i++) {
          const int s = i & 3, n = i < 9 ? i - 2 : i - 9, kb = i < 2 ? 2 * hg + i : 2 * (n + (n >= hg)) + (i >= 9);
          if (i >= 4) mbar_wait(bar + B_EMPTYQ + 8 * s, ((i >> 2) & 1) ^ 1);
          mbar_expect_tx(bar + B_FULLQ + 8 * s, 16384);
          if (i < 2) {
            mbar_arrive2(bar + B_FULLQ + 8 * s);
            tma3d(sb + s * Q_STAGE + 16384, &mWo, 0, kb * 64, hg * 2, bar + B_FULLQ + 8 * s);
          } else {
            tma5d(sb + s * Q_STAGE + 16384, &mWp, hg * 128, kb * 2, bar + B_FULLQ + 8 * s);
            tma5d(sb + s * Q_STAGE + 24576, &mWp, hg * 128 + 64, kb * 2, bar + B_FULLQ + 8 * s);
            if (i >= 3) {
              if (i == 3) { mbar_wait(bar + B_DND, 0); PROF(14); }
#pragma unroll 1
              for (int a = i == 3 ? 2 : i; a <= i; a++) {
                const uint4* src = g_ofr + (mb * 16 + (a == 2 ? (hg == 0 ? 2 : 0) : kb)) * 1024;
#pragma unroll
                for (int h = 0; h < 2; h++) {
                  mbar_expect_tx(bar + B_AIN + (a & 3) * 16 + h * 8, 8192);
                  bulk_load(sb + (a & 3) * Q_STAGE + h * 8192, src + h * 512, 8192, bar + B_AIN + (a & 3) * 16 + h * 8);
                }
              }
            }
          }
        }
      }
    } else {
      if (f == 2) {
        if (PFD && ffn) {
#pragma unroll 1
          for (int i = 0; i < 16; i++) { touch_l2((const char*)P.w_down + fb * 65536 + i * 4096 + lane * 128, lane); __nanosleep(PFD); }
        }
        {
#pragma unroll 1
          for (int i = 0; i < 8; i++) { touch_l2((const char*)P.wo + ((mb & 7) * 128 + i * 16 + (lane >> 1)) * 2048 + hg * 256 + (lane & 1) * 128, lane); __nanosleep(PFD); }
        }
        asm volatile("cp.async.wait_all;" ::: "memory");
        uint4 u;
#pragma unroll 1
        for (int it = 0; it < SPIN_MAX; it++) {
          u = ld_rlx128(g_cs + hg * 128 + lane * 4);
          if (__all_sync(~0u, !(BAD4(u) & 1))) break;
          __nanosleep(200);
        }
        mbar_wait(bar + B_PHI, 0);
        float4 c = make_float4(unmark(u.x), unmark(u.y), unmark(u.z), unmark(u.w));
        CS_STORE(2, c);
        fence_async_smem();
        __syncwarp();
        if (lane == 0) mbar_arrive(bar + B_CSQ);
      }
      const uint32_t target = __shfl_sync(~0u, tag, 0) * 16;
#pragma unroll 1
      for (int R = 0; R < 2; R++) {
        const uint32_t own = (hg * 2 + R) * 16 + mb, pst = sb + (R ? SM_PST1 : SM_PST0);
        if (f == R) {
          mbar_wait(bar + B_KVST + 8 * R, 0);
          if (f == 1 && lane == 0) PROF(11);
          wait_hint(XC1(hg, R) + mb, target);
          if (elect_one()) {
            PROF(35 + R);
            fence_async_global();
            mbar_expect_tx(bar + B_PART + 8 * R, 8192);
            bulk_load(pst, g_part + own * 512, 8192, bar + B_PART + 8 * R);
          }
          __syncwarp();
          uint4 uz;
#pragma unroll 1
          for (int it = 0; it < SPIN_MAX; it++) {
            uz = ld_rlx128(g_zpart + own * 128 + lane * 4);
            if (__all_sync(~0u, !(BAD4(uz) & 1))) break;
          }
          const bool b1 = lane & 2, b2 = lane & 4;
          const float z0 = unmark(b1 ? uz.z : uz.x) + __shfl_xor_sync(~0u, unmark(b1 ? uz.x : uz.z), 2);
          const float z1 = unmark(b1 ? uz.w : uz.y) + __shfl_xor_sync(~0u, unmark(b1 ? uz.y : uz.w), 2);
          float z = (b2 ? z1 : z0) + __shfl_xor_sync(~0u, b2 ? z0 : z1, 4);
          z += __shfl_xor_sync(~0u, z, 8);
          z += __shfl_xor_sync(~0u, z, 16);
          if (lane < 8) {
            const uint32_t ft = (own & 7) * 8 + (lane & 1) * 4 + (lane & 2) + (lane >> 2), zz = pack2(z, 1.f);
            const uint32_t pos = (own >> 3) * 64 + (ft & 15) * 4 + (((ft >> 4) ^ (ft >> 1)) & 3);
            st_rlx128(g_zres[par] + pos, zz, zz, zz, zz);
            g_zres[par ^ 1][pos] = make_uint4(0u, 0u, 0u, 0u);
          }
          if (lane == 0) red_inc(XC2(hg, R));
          __syncwarp();
        }
        if (f == R || f == R + 1) {
          const uint32_t hf = f - R, m1 = ~lane & 1, gq = hf * 4 + (lane >> 3), ts = (lane >> 1) & 3;
          float a0 = 0.f, a1 = 0.f, a2 = 0.f, a3 = 0.f;
          mbar_wait(bar + B_PART + 8 * R, 0);
#pragma unroll 1
          for (int it = 0; it < SPIN_MAX; it++) {
            uint32_t bad = 0;
            a0 = a1 = a2 = a3 = 0.f;
#pragma unroll 1
            for (int b = 0; b < 16; b += 8) {
              uint2 u[8];
              if (it == 0) {
#pragma unroll
                for (int i = 0; i < 8; i++) { const float2 v = lds64(pst + (b + i) * 512 + hf * 256 + lane * 8); u[i] = make_uint2(__float_as_uint(v.x), __float_as_uint(v.y)); }
              } else {
#pragma unroll
                for (int i = 0; i < 8; i++) {
                  const unsigned long long v = ld_rlx64((const unsigned long long*)g_part + own * 1024 + (b + i) * 64 + hf * 32 + lane);
                  u[i] = make_uint2((uint32_t)v, (uint32_t)(v >> 32));
                }
              }
#pragma unroll
              for (int i = 0; i < 8; i++) {
                bad |= u[i].x ^ par;
                a0 += bf_lo(i & 1 ? u[i].x & ~m1 : u[i].x | m1); a1 += bf_hi(u[i].x); a2 += bf_lo(u[i].y); a3 += bf_hi(u[i].y);
              }
            }
            if (__all_sync(~0u, !(bad & m1))) break;
          }
          uint32_t* dst = (uint32_t*)g_res[par] + own * 128 + gq * 16 + ts;
          const uint32_t j0 = (lane & 1) * 2, vb = ts == (gq >> 1);
          st_rlx(dst + ((j0 ^ (gq >> 1)) & 3) * 4, pack2(a0, a1) | vb);
          st_rlx(dst + (((j0 + 1) ^ (gq >> 1)) & 3) * 4, pack2(a2, a3) | vb);
          ((uint2*)g_res[par ^ 1])[own * 64 + hf * 32 + lane] = make_uint2(0u, 0u);
          __syncwarp();
          if (lane == 0) { red_inc(XC2(hg, R)); if (!hf) PROF(R ? 12 : 30); }
        }
      }
      if (f == 2) {
        if (ffn && !FFN_OFF) {
#pragma unroll 1
          for (int it = 0; it < SPIN_MAX; it++) {
            const uint32_t pg = ld_rlx((const uint32_t*)g_gp + fb * 32 + lane), pu = ld_rlx((const uint32_t*)g_gp + FF + fb * 32 + lane);
            if (__all_sync(~0u, !(((pg ^ par) | (pu ^ par)) & 1))) { gsum += unmark(pg); usum += unmark(pu); break; }
            __nanosleep(200);
          }
        }
        const float h = bf_round(silu_f(bf_round(gsum))) * bf_round(usum);
        const uint32_t h2 = pack2(h, h);
        sts128u(sb + SM_HT + lane * 16, h2, h2, h2, h2);
        fence_async_smem();
        __syncwarp();
        if (lane == 0) { mbar_arrive(bar + B_H); PROF(20); }
      }
      if (f < 2) {
        wait_hint(XC2(hg, f), 3 * target);
        mbar_wait(bar + B_KVST + 8, 0);
        if (lane == 0) PROF(40 + f);
#pragma unroll 1
        for (int it = 0; it < SPIN_MAX; it++) {
          if (elect_one()) {
            fence_async_global();
            mbar_expect_tx(bar + B_RES + 8 * f, 8192 + 2048);
            bulk_load(sb + SM_V + f * 8192, g_res[par] + (hg * 4 + f * 2) * 256, 8192, bar + B_RES + 8 * f);
            bulk_load(sb + SM_ZT + f * 2048, g_zres[par] + (hg * 4 + f * 2) * 64, 2048, bar + B_RES + 8 * f);
          }
          __syncwarp();
          mbar_wait(bar + B_RES + 8 * f, it & 1);
          uint32_t ok = ~0u;
#pragma unroll
          for (int i = 0; i < 16; i++) ok &= __float_as_uint(lds32(sb + SM_V + f * 8192 + i * 512 + lane * 16 + (lane >> 3) * 4));
#pragma unroll
          for (int i = 0; i < 4; i++) ok &= __float_as_uint(lds32(sb + SM_ZT + f * 2048 + i * 512 + lane * 16 + (lane >> 3) * 4)) >> 23;
          if (__all_sync(~0u, ok & 1)) break;
        }
        if (lane == 0) { mbar_arrive(bar + B_TILE + 8 * f); PROF(f ? 13 : 27); }
      }
      if (f < 2) {
        uint32_t phases = 0;
#pragma unroll 1
        for (int i = 2; i < 16; i++) {
          const int s = i & 3;
          const uint32_t ab = bar + B_AIN + s * 16 + f * 8, slot = sb + s * Q_STAGE + f * 8192;
#pragma unroll 1
          for (int it = 0; it < SPIN_MAX; it++) {
            mbar_wait(ab, (phases >> s) & 1);
            phases ^= 1u << s;
            uint32_t bad = 0;
#pragma unroll
            for (int n = 0; n < 8; n++) bad |= __float_as_uint(lds32(slot + n * 1024 + lane * 32 + (lane >> 2) * 4)) ^ par;
            if (__all_sync(~0u, !(bad & 1))) break;
            if (elect_one()) {
              const int n = i < 9 ? i - 2 : i - 9, kb = 2 * (n + (n >= hg)) + (i >= 9);
              PROF(49);
              mbar_expect_tx(ab, 8192);
              bulk_load(slot, g_ofr + (mb * 16 + kb) * 1024 + f * 512, 8192, ab);
            }
            __syncwarp();
          }
          if (lane == 0) { mbar_arrive(bar + B_FULLQ + 8 * s); if (i == 2 && f == 0) PROF(15); }
        }
        if (f == 0) g_epoch[bid * 32 + lane] = tag;
      } else {
        if (elect_one()) {
          prefetch_map(&mOut);
          if (ffn) { mbar_wait(bar + B_YD, 0); red_rel(g_ycnt); PROF(21); }
        }
        __syncwarp();
        if (f == 2) {
          const uint32_t best = __float_as_uint(lds32(sb + SM_RED + 20));
          const int sel = 2047 - (best & 0x7ff) - mb * 128;
          if (sel >= 0 && sel < 128) {
            const uint2 xr = __ldg((const uint2*)(P.x + (size_t)(mb * 128 + sel) * DM + hg * 128 + lane * 4));
            const float2 st = lds64(sb + SM_STAT + sel * 8);
            const uint32_t ord = best >> 16, rb = (ord & 0x8000u) ? (ord & 0x7fffu) : (~ord & 0xffffu);
            const float sg = rcp(1.f + ex2(-1.4426950408889634f * bf_lo(rb)));
            const uint32_t sg2 = pack2(sg, sg), nm2 = pack2(st.x, st.x);
            wait_cnt<0>(g_ycnt, tag * NFFN);
            float4 y = make_float4(0.f, 0.f, 0.f, 0.f);
#pragma unroll
            for (int i = 0; i < 8; i++) {
              const float4 c = ldg_cg4(g_y[par ^ 1][i] + hg * 128 + lane * 4);
              y.x += c.x; y.y += c.y; y.z += c.z; y.w += c.w;
            }
            uint32_t o[2];
#pragma unroll
            for (int i = 0; i < 2; i++) {
              const uint32_t d = badd2(i ? xr.y : xr.x, nm2);
              const uint32_t tt = badd2(pack2(bf_lo(d) * st.y, bf_hi(d) * st.y), bmul2(i ? pack2(y.z, y.w) : pack2(y.x, y.y), sg2));
              o[i] = pack2(silu_f(bf_lo(tt)), silu_f(bf_hi(tt)));
            }
            sts64u(sb + SM_UPD + lane * 8, o[0], o[1]);
          }
          if (lane == 0) sts32(sb + SM_UPD + 256, __int_as_float(sel));
          __syncwarp();
          if (lane == 0) { mbar_arrive(bar + B_UPD); PROF(22); }
        }
      }
    }
  } else {
    const int t7 = threadIdx.x & 127;
    const char* pfa = warp < 4 ? (const char*)P.x + bid * 32768 + (t7 & 15) * 2048 + (t7 >> 4) * 128
                               : (const char*)P.wqkv + (size_t)((t7 >> 4) * 64 + (bid >> 1)) * 6144 + 2048 + (bid & 1) * 2048 + (t7 & 15) * 128;
    if (t7 >= 16 && t7 < 16 * PF_FIRST) prefetch_l2(pfa);
    if (warp < 7) sts128(sb + SM_CST + threadIdx.x * 16, 0.f, 0.f, 0.f, 0.f);
    else sts32(sb + SM_RED + (threadIdx.x & 15) * 4, threadIdx.x & 8 ? 1.f : 0.f);
    if (elect_one()) {
#pragma unroll 1
      for (uint32_t b = B_FST + warp * 8; b < B_END; b += 64)
        mbar_init(bar + b, b < B_FULLQ ? 1 : b < B_FFN ? 3 : b < B_EMPTYKV ? 4 : 8);
    }
    __syncwarp();
    asm volatile("bar.arrive 13, 384;" ::: "memory");
    asm volatile("setmaxnreg.inc.sync.aligned.u32 %0;" ::"n"(REG_C));
    if (t7 >= 16 * PF_FIRST && threadIdx.x < 128 + 16 * PF_W) prefetch_l2(pfa);
    asm volatile("cp.async.wait_all;" ::: "memory");
    fence_async_smem();
    bar_sync(14, 288);
    if (threadIdx.x == 0) mbar_arrive(bar + B_FULLKV + 16);
    const int lane = lane_id();
    const int wg = warp >> 2, w = warp & 3, g = lane >> 2, t = lane & 3;
    float kv[128];
    {
      uint32_t s = 2, ph = 0, sp = 0, php = 0;
#pragma unroll 1
      for (int j = 0; j < 15; j++) {
        PW0(32 + j); mbar_wait(bar + B_FULLKV + 8 * s, ph); PW1(32 + j);
        if (wg == 1) bar_sync(10 + s, 256);
        wg_fence();
        const uint32_t hA = fresh_hi<H128>(P.zA), hB = fresh_hi<H128>(P.zB);
        wgmma_n256_ssp_ta0_tb1(kv, mkdesch(sb, 16, hA, wg * 512 + s * (KV_STAGE / 16)), mkdesch(sb + 16384, 8192, hB, s * (KV_STAGE / 16)), j);
#pragma unroll
        for (int k = 1; k < 4; k++)
          wgmma_n256_ss_ta0_tb1(kv, mkdesch(sb + k * 32, 16, hA, wg * 512 + s * (KV_STAGE / 16)),
                                mkdesch(sb + 16384 + k * 2048, 8192, hB, s * (KV_STAGE / 16)), 1);
        wg_commit();
        if (wg == 0) asm volatile("bar.arrive %0, 256;" ::"r"(10 + s) : "memory");
        if (warp == 0 && j) {
          mbar_wait(bar + B_EMPTYKV + 8 * sp, php);
          if (elect_one()) {
            if (j < 14) {
              mbar_expect_tx(bar + B_FULLKV + 8 * sp, KV_STAGE);
              tma2d(sb + sp * KV_STAGE, &mX, (j + 2) * 64, mb * 128, bar + B_FULLKV + 8 * sp);
              tma4d(sb + sp * KV_STAGE + 16384, &mWkv, 0, (j + 2) * 64, hg * 2, 1, bar + B_FULLKV + 8 * sp);
            } else {
              Q_LOAD(0);
            }
            if (j == 1) {
              mbar_expect_tx(bar + B_XST + 8, 16384);
              tma3d(sb + SM_XST + 16384, &mXs, 0, bid * 16, 2, bar + B_XST + 8);
            }
          }
          __syncwarp();
        }
        if (wg == 0 && j == 1) prefetch_l2(pfa + 1024);
        if (wg == 1) {
          if (j == 1 && t7 >= 16 * PF_W) prefetch_l2(pfa);
          if (j == 2) {
            prefetch_l2(pfa + 8 * 393216);
          } else if (j == 13) {
            prefetch_l2((const char*)P.wo + bid * 16384 + t7 * 128);
          }
        }
        wg_wait<0>();
        if (lane == 0) mbar_arrive(bar + B_EMPTYKV + 8 * s);
        sp = s; php = ph;
        ph ^= s == 1;
        s = s == 2 ? 0 : s + 1;
      }
    }
    const int lrow = wg * 64 + w * 16 + (lane & 15);
    const uint32_t sw128 = lrow * 128, x128 = (lrow & 7), hi16 = lane >> 4;
    mbar_wait(bar + B_CS, 0);
    const uint32_t tag = __float_as_uint(lds32(sb + SM_RED + 16));
    const int zero = __float_as_int(lds32(sb + SM_RED + 12));
    const float wn = lds32(sb + SM_RED + 24);
    const float2 st0 = lds64(sb + SM_STAT + (wg * 64 + w * 16 + g) * 8), st1 = lds64(sb + SM_STAT + (wg * 64 + w * 16 + g + 8) * 8);
    const float c0 = st0.y * 1.4426950408889634f, c1 = st1.y * 1.4426950408889634f;
    const uint32_t nm20 = pack2(st0.x, st0.x), nm21 = pack2(st1.x, st1.x), fmask = t == 0 ? ~0u : t == 1 ? 0xffffu : 0u;
    const uint32_t fa0 = nm20 & fmask, fa1 = nm21 & fmask;
    asm volatile("cp.async.wait_all;" ::: "memory");
    PW0(47); mbar_wait(bar + B_FULLKV + 16, 1); PW1(47);
    wg_fence();
    wgmma_n256_rs_ta0_tb1(kv, fa0, fa1, 0u, 0u, mkdesc(sb + SM_CST, 512, 0, 1), 1);
    {
      const uint32_t hA = fresh_hi<H128>(P.zA), hB = fresh_hi<H128>(P.zB);
#pragma unroll
      for (int k = 0; k < 4; k++)
        wgmma_n256_ss_ta0_tb1(kv, mkdesch(sb + 2 * KV_STAGE + k * 32, 16, hA, wg * 512), mkdesch(sb + 2 * KV_STAGE + 16384 + k * 2048, 8192, hB), 1);
    }
    wg_commit();
    if (warp == 0) {
      mbar_wait(bar + B_EMPTYKV + 8, 0);
      if (elect_one()) {
#pragma unroll 1
        for (int j = 1; j < 3; j++) Q_LOAD(j);
      }
      __syncwarp();
    }
    wg_wait<0>();
    reg_fence<128>(kv);
    if (lane == 0) mbar_arrive(bar + B_EMPTYKV + 16);
    PROFC(2);
    float q[64];
#define QMMA(J, AOFF16, ACCUM)                                                                                     \
  do {                                                                                                             \
    const uint32_t hA_ = fresh_hi<H128>(P.zA), hB_ = fresh_hi<H128>(P.zB);                                         \
    _Pragma("unroll") for (int k = 0; k < 4; k++)                                                                  \
      wgmma_n128_ss_ta0_tb1(q, mkdesch(sb + k * 32, 16, hA_, wg * 512 + (AOFF16)),                                 \
                            mkdesch(sb + 16384 + k * 2048, 8192, hB_, ((J) & 3) * (Q_STAGE / 16)), k ? 1 : (ACCUM)); \
  } while (0)
#define QWAIT(J) do { PW0(J); mbar_wait(bar + B_FULLQ + 8 * ((J) & 3), ((J) >> 2) & 1); PW1(J); } while (0)
#define QSTEP_A(J, AOFF16, ACCUM) do { QWAIT(J); wg_fence(); QMMA(J, AOFF16, ACCUM); wg_commit(); } while (0)
#define QREL(J) do { if (lane == 0) mbar_arrive(bar + B_EMPTYQ + 8 * ((J) & 3)); } while (0)
#define Q_OFF16(J) ((J) >= 8 && (J) < 16 ? Q_AOFF(J) / 16 : ((J) & 3) * (Q_STAGE / 16))
#define QPLAIN(J) do { QSTEP_A(J, Q_OFF16(J), 1); wg_wait<1>(); QREL((J) - 1); } while (0)
#define QNEXT(J) do { QPLAIN(J); SCHED_FENCE(); } while (0)
#define PHI_PROJ(DST, SRC, H0, H1)                                                                                 \
  do {                                                                                                             \
    uint32_t a_[32];                                                                                               \
    _Pragma("unroll") for (int j = 8 * (H0); j < 8 * (H1); j++) {                                                  \
      a_[j] = pack2(SRC[2 * j], SRC[2 * j + 1]);                                                                   \
      asm volatile("fma.rn.bf16x2 %0, %1, %1, %0;" : "+r"(nq[(j >> 4) * 2 + (j & 1)]) : "r"(a_[j]));               \
    }                                                                                                              \
    wg_fence();                                                                                                    \
    const uint32_t hB_ = fresh_hi<H64>(P.zB);                                                                      \
    _Pragma("unroll") for (int hk = 2 * (H0); hk < 2 * (H1); hk++)                                                 \
        wgmma_n32_rs_ta0_tb1(DST + 16 * (hk >> 1), a_[4 * hk], a_[4 * hk + 1], a_[4 * hk + 2], a_[4 * hk + 3],     \
                             mkdesch(sb + SM_WPHI + hk * 1024, 16, hB_), hk & 1);                                \
    wg_commit();                                                                                                   \
  } while (0)
    {
      float p[64], ea[24], eb[24], sa[4], sc[4], kz[20];
      uint32_t vp[32];
#pragma unroll
      for (int j = 0; j < 32; j++) vp[j] = pack2(kv[64 + 2 * j], kv[65 + 2 * j]);
      const uint32_t vr = w * 16 + (lane & 15), vb = sb + SM_V + wg * 4096 + vr * 64, x64 = (vr >> 1) & 3;
#define V_STORE(R)                                                                                           \
  _Pragma("unroll") for (int j = 0; j < 4; j++)                                                              \
      stsm4(vb + (j >> 1) * 8192 + ((((j & 1) * 2 + hi16) ^ x64) << 4), vp[16 * (R) + 4 * j], vp[16 * (R) + 4 * j + 1], vp[16 * (R) + 4 * j + 2], vp[16 * (R) + 4 * j + 3])
      V_STORE(0);
      mbar_wait(bar + B_WPHI, 0);
      {
        uint32_t nq[4] = {0u, 0u, 0u, 0u};
        PHI_PROJ(p, kv, 0, 4);
        QSTEP_A(0, 0, 0);
        const bool unsafe = softmax_unsafe(nq, c0 * c0 * wn, c1 * c1 * wn);
        wg_wait<1>();
        reg_fence<64>(p);
        if (__builtin_expect(unsafe, 0)) softmax_shift(p, c0, c1);
      }
#define K_NORM(S) do { quad_sum<4>(S); _Pragma("unroll") for (int i = 0; i < 4; i++) S[i] = rcp(S[i]) * ((i & 1) ? st1.y : st0.y); } while (0)
#define K_STORE(SLOT, E, S) K_STORE_(SLOT, E, S, 0, 2)
#define K_STORE_(SLOT, E, S, J0, J1)                                                                         \
  _Pragma("unroll") for (int j = (J0); j < (J1); j++) {                                                      \
    uint32_t fp[4], fm[4];                                                                                   \
    _Pragma("unroll") for (int i = 0; i < 4; i++) {                                                          \
      const float e0 = E[8 * j + 2 * i], e1 = E[8 * j + 2 * i + 1], r = E[16 + 4 * j + i] * S[2 + (i & 1)];  \
      const uint32_t e2 = pack2(e0, e1);                                                                     \
      fp[i] = bmul2(e2, pack2(S[i & 1], S[i & 1]));                                                          \
      fm[i] = bmul2(e2, pack2(r, r));                                                                        \
    }                                                                                                        \
    stsm4(sb + SM_PHI + (SLOT) * 16384 + sw128 + (((2 * j + hi16) ^ x128) << 4), fp[0], fp[1], fp[2], fp[3]); \
    stsm4(sb + SM_PHI + (SLOT) * 16384 + sw128 + (((4 + 2 * j + hi16) ^ x128) << 4), fm[0], fm[1], fm[2], fm[3]); \
  }
#define KV_MMA(R)                                                                                            \
  do {                                                                                                       \
    mbar_wait(bar + B_PHI + 8 * (R), 0);                                                                     \
    wg_fence();                                                                                              \
    const uint32_t hA_ = fresh_hi<H128>(P.zA), hB_ = fresh_hi<H64>(P.zB);                                    \
    _Pragma("unroll") for (int k = 0; k < 8; k++) {                                                          \
      const uint32_t vs = SM_V + (k >> 2) * 4096 + (k & 3) * 1024;                                           \
      wgmma_n40_ss_ta1_tb1(kz, mkdesch(sb + SM_PHI + k * 2048, 16, hA_, wg * 1024),                       \
                           mkdesch(sb + vs, SM_SDT + (k & 1) * 1024 + (k >> 1) * 16 - vs, hB_, wg * (512u - (512u << 16))), k); \
    }                                                                                                        \
    wg_commit();                                                                                             \
  } while (0)
#define QKV(J, R) do { KV_MMA(R); QSTEP_A(J, Q_OFF16(J), 1); wg_wait<2>(); QREL((J) - 1); SCHED_FENCE(); } while (0)
#define KV_SEND(R)                                                                                           \
  do {                                                                                                       \
    reg_fence<20>(kz);                                                                                       \
    if (lane == 0) mbar_arrive(bar + B_KVST + 8 * (R));                                                      \
    const uint32_t slot = ((hg * 2 + (R)) * 16 + warp * 2) * 16 + mb;                                        \
    _Pragma("unroll") for (int u = 0; u < 2; u++)                                                            \
      st_rlx128(g_part + (slot + u * 16) * 32 + lane, mark(pack2(kz[2 * u], kz[2 * u + 1]), tag & 1), pack2(kz[2 * u + 4], kz[2 * u + 5]), \
                pack2(kz[2 * u + 8], kz[2 * u + 9]), pack2(kz[2 * u + 12], kz[2 * u + 13]));                 \
    if (t < 2) st_rlx(g_zpart + (slot + t * 16) * 8 + g, mark(__float_as_uint(t ? kz[18] : kz[16]), tag & 1)); \
    if (lane < 2) red_inc(XC1(hg, R) + warp * 2 + lane);                                                          \
  } while (0)
#define K_PUB(R) do { fence_async_smem(); __syncwarp(); if (lane == 0) mbar_arrive(bar + B_PHI + 8 * (R)); } while (0)
#define S_PIN(S) SCHED_PIN(S[0] + S[1] + S[2] + S[3])
      k_exp(p, c0, c1, ea, sa);
      S_PIN(sa);
      QNEXT(1);
      K_NORM(sa);
      k_exp<0, 4>(p + 16, c0, c1, eb, sc);
      mbar_wait(bar + B_FFN, 0);
      K_STORE_(0, ea, sa, 0, 1);
      S_PIN(sc);
      QNEXT(2);
      K_STORE_(0, ea, sa, 1, 2);
      k_exp<4, 8>(p + 16, c0, c1, eb, sc);
      K_NORM(sc);
      S_PIN(sc);
      QNEXT(3);
      K_STORE(1, eb, sc);
      K_PUB(0);
      k_exp<0, 4>(p + 32, c0, c1, ea, sa);
      S_PIN(sa);
      QKV(4, 0);
      k_exp<4, 8>(p + 32, c0, c1, ea, sa);
      K_NORM(sa);
      S_PIN(sa);
      wg_wait<1>();
      KV_SEND(0);
      QNEXT(5);
      k_exp(p + 48, c0, c1, eb, sc);
      S_PIN(sc);
      QNEXT(6);
      K_NORM(sc);
      mbar_wait(bar + B_KVST, 0);
      V_STORE(1);
      K_STORE(0, ea, sa);
      QNEXT(7);
      K_STORE(1, eb, sc);
      K_PUB(1);
      QKV(8, 1);
      QNEXT(9);
      KV_SEND(1);
    }
    PROFC(3);
#pragma unroll 1
    for (int j = 10; j < 15; j++) QPLAIN(j);
    mbar_wait(bar + B_CSQ, 0);
    QWAIT(15);
    if (wg == 1) bar_sync(6, 256);
    wg_fence();
    wgmma_n128_rs_ta0_tb1(q, fa0, fa1, 0u, 0u, mkdesc(sb + SM_CST + 2048, 512, 0, 1), 1);
    QMMA(15, Q_AOFF(15) / 16, 1);
    wg_commit();
    if (wg == 0) asm volatile("bar.arrive 6, 256;" ::: "memory");
    wg_wait<1>();
    QREL(14);
    wg_wait<0>();
    QREL(15);
    reg_fence<64>(q);
    PROFC(5);
    float yp[4];
    const uint32_t par = tag & 1;
    uint4* ofr = g_ofr + (mb * 16 + hg * 2) * 1024 + (warp * 16 + g) * 8;
#define O_MMA(H, F, N)                                                                                       \
  do {                                                                                                       \
    wg_fence();                                                                                              \
    const uint32_t hB_ = fresh_hi<H64>(P.zB);                                                                \
    _Pragma("unroll") for (int k = 0; k < 4; k++) {                                                          \
      const uint32_t ks = SM_V + (H) * 4096 + k * 1024;                                                      \
      wgmma_n40_rs_ta0_tb1(N + 20 * (k >> 1), F[4 * k], F[4 * k + 1], F[4 * k + 2], F[4 * k + 3],            \
                           mkdesch(sb + ks, SM_ZT + (H) * 1024 + k * 16 - ks, hB_), k & 1);                \
    }                                                                                                        \
    wg_commit();                                                                                             \
  } while (0)
#define O_FIN(H, N, o)                                                                                        \
  do {                                                                                                       \
    reg_fence<40>(N);                                                                                        \
    const float *np = N, *nm = N + 20;                                                                       \
    const float d0 = rcp(fmaf(np[16], nm[17], fmaf(nm[16], np[17], 1e-6f * np[17] * nm[17])));               \
    const float d1 = rcp(fmaf(np[18], nm[19], fmaf(nm[18], np[19], 1e-6f * np[19] * nm[19])));               \
    const float bp0 = nm[17] * d0, bm0 = np[17] * d0, bp1 = nm[19] * d1, bm1 = np[19] * d1;                  \
    _Pragma("unroll") for (int j = 0; j < 4; j++) {                                                          \
      o[2 * j] = pack2(fmaf(np[4 * j], bp0, nm[4 * j] * bm0), fmaf(np[4 * j + 1], bp0, nm[4 * j + 1] * bm0)); \
      o[2 * j + 1] = pack2(fmaf(np[4 * j + 2], bp1, nm[4 * j + 2] * bm1), fmaf(np[4 * j + 3], bp1, nm[4 * j + 3] * bm1)); \
    }                                                                                                        \
  } while (0)
#define O_STG(H, o)                                                                                          \
  _Pragma("unroll") for (int u = 0; u < 2; u++) {                                                            \
    uint32_t v_[4];                                                                                          \
    _Pragma("unroll") for (int j = 0; j < 4; j++) v_[j] = lop_select(o[2 * j + u], parm, vword == j);        \
    st_rlx128(ofr + ((H) >> 1) * 1024 + u * 64 + ((((H) & 1) * 4 + t) ^ g), v_[0], v_[1], v_[2], v_[3]);     \
  }
    uint32_t gf[32], ao[16];
    const uint32_t parm = 0u - par, vword = ((t ^ g) & 1) == (g >> 2) ? g & 3 : 4;
    const float rh0 = 0.5f * st0.y, rh1 = 0.5f * st1.y, mh0 = st0.x * rh0, mh1 = st1.x * rh1;
#define GATE_LD(J) ldsm4(sb + ((J) >> 2 ? SM_X1 : SM_X0) + sw128 + (((((J) & 3) * 2 + hi16) ^ x128) << 4), gf[4 * (J)], gf[4 * (J) + 1], gf[4 * (J) + 2], gf[4 * (J) + 3])
#define GATE(I0, I1)                                                                                         \
  _Pragma("unroll") for (int i = (I0); i < (I1); i++) {                                                      \
    const float rs = (i & 1) ? rh1 : rh0, mh = (i & 1) ? mh1 : mh0;                                          \
    const float h0 = fmaf(bf_lo(gf[i]), rs, mh), h1 = fmaf(bf_hi(gf[i]), rs, mh);                            \
    gf[i] = pack2(fmaf(h0, tanh_approx(h0), h0), fmaf(h1, tanh_approx(h1), h1));                             \
  }
#define GATE_PIN(I0, I1) do { uint32_t o_ = 0; _Pragma("unroll") for (int i = (I0); i < (I1); i++) o_ |= gf[i]; SCHED_PIN(__uint_as_float(o_)); } while (0)
    {
      float p[64], na[40], nb[40];
      uint32_t fa[16], fb[16];
      {
        uint32_t nq[4] = {0u, 0u, 0u, 0u};
        PHI_PROJ(p, q, 0, 2);
        SCHED_FENCE();
        PHI_PROJ(p, q, 2, 4);
        const bool unsafe = softmax_unsafe(nq, c0 * c0 * wn, c1 * c1 * wn);
        wg_wait<0>();
        reg_fence<64>(p);
        PROFC(24);
        if (__builtin_expect(unsafe, 0)) softmax_shift(p, c0, c1);
      }
      float dn[32];
#define DN_PART(A, B)                                                                                        \
  do {                                                                                                       \
    wg_fence();                                                                                              \
    const uint32_t hA_ = fresh_hi<H128>(P.zA), hB_ = fresh_hi<HNS>(P.zB);                                    \
    _Pragma("unroll") for (int i = (A); i < (B); i++)                                                        \
      wgmma_n8_ss_ta1_tb1(dn + 4 * (i >> 1), mkdesch(sb + (i >> 3) * Q_STAGE + (i & 7) * 2048, 16, hA_, wg * (2 * Q_STAGE / 16)), \
                          mkdesch(sb + SM_HT + (i & 1) * 256, 128, hB_), i & 1);                           \
  } while (0)
#define F_PIN(F, A, B) do { uint32_t o_ = 0; _Pragma("unroll") for (int i = (A); i < (B); i++) o_ |= F[8 + i]; SCHED_PIN(__uint_as_float(o_)); } while (0)
#define RMMA(J, A, ACCUM)                                                                                    \
  do {                                                                                                       \
    wg_fence();                                                                                              \
    const uint32_t hB_ = fresh_hi<H128>(P.zB);                                                               \
    _Pragma("unroll") for (int k = 0; k < 4; k++)                                                            \
      wgmma_n128_rs_ta0_tb1(q, (A)[4 * k], (A)[4 * k + 1], (A)[4 * k + 2], (A)[4 * k + 3],                   \
                            mkdesch(sb + 16384 + k * 2048, 8192, hB_, ((J) & 3) * (Q_STAGE / 16)), k ? 1 : (ACCUM)); \
    wg_commit();                                                                                             \
  } while (0)
#define RSTEP(J, A, ACCUM) do { QWAIT(J); RMMA(J, A, ACCUM); } while (0)
      PROFC(4);
      q_exp(p, c0, c1, fa);
      q_exp(p + 16, c0, c1, fb);
      F_PIN(fb, 0, 8);
      mbar_wait(bar + B_TILE, 0);
      O_MMA(0, fa, na);
      O_MMA(1, fb, nb);
      PROFC(25);
      wg_wait<1>();
      O_FIN(0, na, ao);
      O_STG(0, ao);
      wg_wait<0>();
      O_FIN(1, nb, (ao + 8));
      O_STG(1, (ao + 8));
      PROFC(28);
      mbar_wait(bar + B_H, 0);
      mbar_wait(bar + B_DN, 0);
      PROFC(45);
      DN_PART(0, 16);
      wg_commit();
      wg_wait<0>();
      reg_fence<32>(dn);
#pragma unroll
      for (int i = 0; i < 4; i++) yp[i] = t & 2 ? (t & 1 ? dn[24 + 2 * i] : dn[16 + 2 * i]) : (t & 1 ? dn[8 + 2 * i] : dn[2 * i]);
      RSTEP(16, ao, 0);
      SCHED_FENCE();
      q_exp(p + 32, c0, c1, fa);
      F_PIN(fa, 0, 8);
      if (lane == 0) mbar_arrive(bar + B_DND);
      q_exp(p + 48, c0, c1, fb);
      F_PIN(fb, 0, 8);
      wg_wait<0>();
      QREL(16);
      PROFC(29);
      mbar_wait(bar + B_TILE + 8, 0);
      PROFC(23);
      if (bid < NFFN) {
        float* y = g_y[par ^ 1][bid & 7] + wg * 512 + t * 128 + w * 16 + g;
#pragma unroll
        for (int i = 0; i < 4; i++) red1(y + (i >> 1) * 64 + (i & 1) * 8, yp[i]);
      }
      SCHED_FENCE();
      O_MMA(2, fa, na);
      O_MMA(3, fb, nb);
      __syncwarp();
      if (lane == 0) mbar_arrive(bar + B_YD);
      wg_wait<1>();
      O_FIN(2, na, ao);
      O_STG(2, ao);
      wg_wait<0>();
      O_FIN(3, nb, (ao + 8));
      O_STG(3, (ao + 8));
      PROFC(6);
    }
    RSTEP(17, ao, 1);
    SCHED_FENCE();
    GATE_LD(0); GATE_LD(1);
    GATE(0, 4);
    GATE_PIN(0, 4);
#define GSTEP(J, I) do { QNEXT(J); if ((I) < 7) GATE_LD(((I) + 1) & 7); GATE(4 * (I), 4 * (I) + 4); GATE_PIN(4 * (I), 4 * (I) + 4); } while (0)
    GSTEP(18, 1); GSTEP(19, 2); GSTEP(20, 3); GSTEP(21, 4); GSTEP(22, 5); GSTEP(23, 6); GSTEP(24, 7);
#pragma unroll 1
    for (int j = 25; j < 32 - TAILN; j++) QPLAIN(j);
    if (wg == 1) bar_sync(6, 256);
#pragma unroll 1
    for (int j = 32 - TAILN; j < 32; j++) QSTEP_A(j, (j & 3) * (Q_STAGE / 16), 1);
    if (wg == 0) asm volatile("bar.arrive 6, 256;" ::: "memory");
    mbar_wait(bar + B_UPD, 0);
    {
      const int sel = __float_as_int(lds32(sb + SM_UPD + 256)) - (wg * 64 + w * 16 + g);
      if (sel == 0 || sel == 8) {
#pragma unroll
        for (int j = 0; j < 16; j++) {
          const uint32_t u = __float_as_uint(lds32(sb + SM_UPD + j * 16 + t * 4));
          if (sel) gf[2 * j + 1] = u; else gf[2 * j] = u;
        }
      }
      __syncwarp();
      uint32_t xf[32];
#pragma unroll
      for (int j = 0; j < 8; j++)
        ldsm4(sb + (j >> 2 ? SM_X1 : SM_X0) + sw128 + ((((j & 3) * 2 + hi16) ^ x128) << 4), xf[4 * j], xf[4 * j + 1], xf[4 * j + 2], xf[4 * j + 3]);
      wg_wait<0>();
      reg_fence<64>(q);
      PROFC(8);
#pragma unroll
      for (int j = 0; j < 8; j++) {
        uint32_t o[4];
#pragma unroll
        for (int i = 0; i < 4; i++) o[i] = badd2(xf[4 * j + i], bmul2(pack2(q[8 * j + 2 * i], q[8 * j + 2 * i + 1]), gf[4 * j + i]));
        stsm4(sb + (j >> 2 ? SM_X1 : SM_X0) + sw128 + ((((j & 3) * 2 + hi16) ^ x128) << 4), o[0], o[1], o[2], o[3]);
        if ((j & 3) == 3) {
          fence_async_smem();
          __syncwarp();
          if (elect_one()) {
            tma_store2d(&mOut, sb + (j >> 2 ? SM_X1 : SM_X0) + warp * 2048, hg * 128 + (j >> 2) * 64, mb * 128 + warp * 16);
            bulk_commit();
          }
          __syncwarp();
        }
      }
    }
    bulk_wait_read0();
    if (warp == 7 && lane == 0) { PROF(9); PROFT(33); PROF_DUMP; }
  }
}

typedef CUresult (*EncodeFn)(CUtensorMap*, CUtensorMapDataType, cuuint32_t, void*, const cuuint64_t*, const cuuint64_t*, const cuuint32_t*,
                             const cuuint32_t*, CUtensorMapInterleave, CUtensorMapSwizzle, CUtensorMapL2promotion, CUtensorMapFloatOOBfill);

CUtensorMap make_map(EncodeFn enc, const void* ptr, int rank, const cuuint64_t* dims, const cuuint64_t* strides, const cuuint32_t* box, CUtensorMapSwizzle sw) {
  CUtensorMap m;
  const cuuint32_t es[5] = {1, 1, 1, 1, 1};
  enc(&m, CU_TENSOR_MAP_DATA_TYPE_BFLOAT16, rank, (void*)ptr, dims, strides, box, es, CU_TENSOR_MAP_INTERLEAVE_NONE, sw,
      CU_TENSOR_MAP_L2_PROMOTION_L2_128B, CU_TENSOR_MAP_FLOAT_OOB_FILL_NONE);
  return m;
}

}

extern "C" void kernel_launch(void* const* d_in, const int* in_sizes, int n_in, void* d_out, int out_size) {
  static EncodeFn enc = nullptr;
  static int by_sm = 0;
  if (!enc) {
    void* fn = nullptr;
    cudaDriverEntryPointQueryResult qr;
    cudaGetDriverEntryPoint("cuTensorMapEncodeTiled", &fn, cudaEnableDefault, &qr);
    enc = (EncodeFn)fn;
    cudaFuncSetAttribute(fused_kernel<false>, cudaFuncAttributeMaxDynamicSharedMemorySize, SM_TOTAL);
    cudaFuncSetAttribute(fused_kernel<true>, cudaFuncAttributeMaxDynamicSharedMemorySize, SM_TOTAL);
    int dev = 0, sms = 0;
    cudaGetDevice(&dev);
    cudaDeviceGetAttribute(&sms, cudaDevAttrMultiProcessorCount, dev);
    by_sm = BY_SM && sms == NCTA + NSPARE;
  }
  Params P;
  P.zA = P.zB = 0;
  P.x = (const __nv_bfloat16*)d_in[0];
  P.wqkv = (const __nv_bfloat16*)d_in[1];
  const void* wphi = d_in[2];
  P.wo = (const __nv_bfloat16*)d_in[3];
  P.w_r = (const __nv_bfloat16*)d_in[5];
  const void *w_gate = d_in[6], *w_up = d_in[7];
  P.w_down = (const __nv_bfloat16*)d_in[8];

  const cuuint64_t dX[2] = {DM, SEQ}, sX[1] = {DM * 2};
  const cuuint32_t b128[2] = {64, 128};
  const cuuint64_t dW[4] = {64, DM, 16, 3}, sW[3] = {3 * DM * 2, 128, DM * 2};
  const cuuint32_t bKV[4] = {64, 64, 2, 2}, bQ[4] = {64, 64, 2, 1};
  const cuuint64_t dO[3] = {64, DM, 16}, sO[2] = {DM * 2, 128};
  const cuuint32_t bO[3] = {64, 64, 2};
  const cuuint64_t dP[2] = {32, 1024}, sP[1] = {64};
  const cuuint32_t bP[2] = {32, 128};
  CUtensorMap mX = make_map(enc, P.x, 2, dX, sX, b128, CU_TENSOR_MAP_SWIZZLE_128B);
  CUtensorMap mWkv = make_map(enc, P.wqkv, 4, dW, sW, bKV, CU_TENSOR_MAP_SWIZZLE_128B);
  CUtensorMap mWq = make_map(enc, P.wqkv, 4, dW, sW, bQ, CU_TENSOR_MAP_SWIZZLE_128B);
  CUtensorMap mWo = make_map(enc, P.wo, 3, dO, sO, bO, CU_TENSOR_MAP_SWIZZLE_128B);
  CUtensorMap mPhi = make_map(enc, wphi, 2, dP, sP, bP, CU_TENSOR_MAP_SWIZZLE_64B);
  const cuuint64_t dWp[5] = {DM, 2, 4, 4, DM / 32}, sWp[4] = {DM * 2, 8 * DM * 2, 2 * DM * 2, 32 * DM * 2};
  const cuuint32_t bWp[5] = {64, 2, 4, 4, 2};
  CUtensorMap mWp = make_map(enc, P.wo, 5, dWp, sWp, bWp, CU_TENSOR_MAP_SWIZZLE_128B);
  const cuuint32_t b16[2] = {64, 16};
  CUtensorMap mOut = make_map(enc, d_out, 2, dX, sX, b16, CU_TENSOR_MAP_SWIZZLE_128B);
  const cuuint64_t dWc[2] = {3 * DM, DM}, sWc[1] = {3 * DM * 2}, dG[2] = {FF, DM}, sG[1] = {FF * 2}, dD[3] = {64, FF, 16};
  const cuuint32_t b32[2] = {32, 32}, bD[3] = {64, 32, 4};
  CUtensorMap mWc = make_map(enc, P.wqkv, 2, dWc, sWc, b32, CU_TENSOR_MAP_SWIZZLE_NONE);
  CUtensorMap mG = make_map(enc, w_gate, 2, dG, sG, b32, CU_TENSOR_MAP_SWIZZLE_NONE);
  CUtensorMap mU = make_map(enc, w_up, 2, dG, sG, b32, CU_TENSOR_MAP_SWIZZLE_NONE);
  CUtensorMap mD = make_map(enc, P.w_down, 3, dD, sO, bD, CU_TENSOR_MAP_SWIZZLE_128B);
  const cuuint64_t dXs[3] = {256, SEQ, 4}, sXs[2] = {DM * 2, 512};
  const cuuint32_t bXs[3] = {256, 16, 2};
  CUtensorMap mXs = make_map(enc, P.x, 3, dXs, sXs, bXs, CU_TENSOR_MAP_SWIZZLE_NONE);
  const cuuint64_t dG2[4] = {64, DM, FF / 64, 1}, sG2[3] = {FF * 2, 128, (cuuint64_t)FF * DM * 2};
  CUtensorMap mG2 = make_map(enc, w_gate, 4, dG2, sG2, bQ, CU_TENSOR_MAP_SWIZZLE_128B);
  CUtensorMap mU2 = make_map(enc, w_up, 4, dG2, sG2, bQ, CU_TENSOR_MAP_SWIZZLE_128B);
  (by_sm ? fused_kernel<true> : fused_kernel<false>)<<<NCTA + NSPARE, 384, SM_TOTAL, cudaStreamPerThread>>>(P, mX, mWkv, mWq, mWo, mPhi, mWp, mOut, mWc, mG, mU, mD, mXs,
                                                                                                           mG2, mU2);
}
```

```cpp
#include <cuda_runtime.h>
#include <cuda_bf16.h>
#include <cuda.h>
#include <stdint.h>

namespace {

constexpr int SEQ = 2048, DM = 1024, FF = 3584;
constexpr int NCTA = 128;
constexpr int NSPARE = 4;
constexpr int NFFN = FF / 32;
#define GN 6
#define G8 2
constexpr int GROWS = (3 * GN + G8) * 32;
#define TAILN 2
#define PF_FIRST 2
#define PF_W 5
#define PFD 80
#define BY_SM 1
#define PTAB 0x73216540u
#define REG_C 224
#define REG_H 56
#define SP_DELAY 2000
#define XSTR 288
#define AM_NS 100
constexpr bool FFN_OFF = false;

static_assert(2 * REG_C + REG_H <= 3 * 168, "the register pool of the CTA is 384 x 168");

__device__ uint32_t g_epoch[(NCTA + NSPARE) * 32];
__device__ unsigned long long g_stat[SEQ];
__device__ __align__(128) unsigned long long g_best[NCTA];
__device__ __align__(16) float g_y[2][8][DM];
__device__ __align__(128) uint32_t g_ycnt[64];
__device__ __align__(1024) uint32_t g_xcnt[32 * XSTR];
#define XC1(HG, R) (g_xcnt + ((HG) * 2 + (R)) * XSTR)
#define XC2(HG, R) (g_xcnt + (16 + (HG) * 2 + (R)) * XSTR)
__device__ __align__(128) uint4 g_res[2][32 * 256];
__device__ __align__(16) float g_cs[5 * DM];
__device__ __align__(128) float g_gp[2 * FF];
__device__ uint4 g_part[8 * 2 * 16 * 16 * 32];
__device__ __align__(16) float g_zpart[8 * 2 * 16 * 16 * 8];
__device__ __align__(128) uint4 g_zres[2][32 * 64];
__device__ __align__(1024) uint4 g_ofr[16 * 16 * 1024];
#define PROF(i)
#define PROFT(i)
#define PROFC(i)
#define PROF_DUMP
#define PW0(J)
#define PW1(J)

constexpr uint32_t KV_STAGE = 49152, Q_STAGE = 32768;
constexpr uint32_t SM_V = 147456;
constexpr uint32_t SM_PHI = 163840;
constexpr uint32_t SM_XST = 147456;
constexpr uint32_t SM_FST = 172032;
constexpr uint32_t SM_PST0 = 196608, SM_PST1 = SM_PHI + 8192;
constexpr uint32_t SM_X0 = 131072, SM_X1 = SM_PHI + 16384;
constexpr uint32_t SM_WPHI = 204800;
constexpr uint32_t SM_ZT = 212992;
constexpr uint32_t SM_SDT = 217088;
constexpr uint32_t SM_CST = 219136;
constexpr uint32_t SM_HT = 222720;
constexpr uint32_t SM_STAT = 223232;
constexpr uint32_t SM_XSEL = 224256;
constexpr uint32_t SM_RED = 228352;
constexpr uint32_t SM_ROWS = SM_RED + 832;
constexpr uint32_t SM_GRED = SM_XSEL + 3072;
static_assert(GROWS <= 768, "xsel area");
constexpr uint32_t SM_UPD = 229632;
constexpr uint32_t SM_BAR = 230016;
constexpr uint32_t SM_PROF = 230464;
constexpr uint32_t SM_SINK = 231104;
constexpr uint32_t SM_TOTAL = 231616;
constexpr uint32_t SB = 1024;
constexpr uint32_t B_FULLKV = 0  , B_FST = 24  , B_XST = 104  , B_WPHI = 120, B_CS = 128, B_CSQ = 136, B_UPD = 144,
                   B_H = 152, B_DN = 160, B_XS = 168, B_TILE = 176  , B_RES = 192  , B_PART = 208  , B_AIN = 224  ,
                   B_FULLQ = 288  ,
                   B_FFN = 320,
                   B_EMPTYKV = 328  , B_EMPTYQ = 352  , B_KVST = 384  , B_YD = 400, B_PHI = 408  , B_DND = 424, B_END = 432;

__device__ __forceinline__ uint32_t smem_u32(const void* p) { return (uint32_t)__cvta_generic_to_shared(p); }
__device__ __forceinline__ void mbar_init(uint32_t bar, uint32_t cnt) { asm volatile("mbarrier.init.shared::cta.b64 [%0], %1;" ::"r"(bar), "r"(cnt) : "memory"); }
__device__ __forceinline__ void mbar_expect_tx(uint32_t bar, uint32_t bytes) { asm volatile("mbarrier.arrive.expect_tx.shared::cta.b64 _, [%0], %1;" ::"r"(bar), "r"(bytes) : "memory"); }
__device__ __forceinline__ void mbar_arrive2(uint32_t bar) { asm volatile("mbarrier.arrive.shared::cta.b64 _, [%0], 2;" ::"r"(bar) : "memory"); }
__device__ __forceinline__ void mbar_arrive(uint32_t bar) { asm volatile("mbarrier.arrive.shared::cta.b64 _, [%0];" ::"r"(bar) : "memory"); }
__device__ __forceinline__ void mbar_wait(uint32_t bar, uint32_t parity) {
  asm volatile("{\n.reg .pred p;\nLW:\nmbarrier.try_wait.parity.shared::cta.b64 p, [%0], %1;\n@!p bra LW;\n}" ::"r"(bar), "r"(parity) : "memory");
}
__device__ __forceinline__ bool mbar_test(uint32_t bar, uint32_t parity) {
  uint32_t ok;
  asm volatile("{\n.reg .pred p;\nmbarrier.test_wait.parity.shared::cta.b64 p, [%1], %2;\nselp.u32 %0, 1, 0, p;\n}" : "=r"(ok) : "r"(bar), "r"(parity) : "memory");
  return ok;
}
__device__ __forceinline__ int lane_id() { int l; asm volatile("mov.u32 %0, %%laneid;" : "=r"(l)); return l; }
template <int C> __device__ __forceinline__ void sched_fence_(int zero) {
  asm volatile("{\n.reg .pred p;\nsetp.eq.s32 p, %0, %1;\n@p trap;\n}" ::"r"(zero), "n"(C) : "memory");
}
#define SCHED_FENCE() sched_fence_<1000 + __COUNTER__>(zero)
#define SCHED_PIN(V) sched_fence_<1000 + __COUNTER__>(zero & __float_as_int(V))
__device__ __forceinline__ bool elect_one() {
  uint32_t p; asm volatile("{ .reg .pred P; elect.sync _|P, 0xffffffff; selp.u32 %0, 1, 0, P; }" : "=r"(p)); return p;
}
__device__ __forceinline__ void tma2d(uint32_t dst, const CUtensorMap* m, int x, int y, uint32_t bar) {
  asm volatile("cp.async.bulk.tensor.2d.shared::cluster.global.mbarrier::complete_tx::bytes [%0], [%1, {%3, %4}], [%2];" ::"r"(dst), "l"(m), "r"(bar), "r"(x), "r"(y) : "memory");
}
__device__ __forceinline__ void tma3d(uint32_t dst, const CUtensorMap* m, int x, int y, int z, uint32_t bar) {
  asm volatile("cp.async.bulk.tensor.3d.shared::cluster.global.mbarrier::complete_tx::bytes [%0], [%1, {%3, %4, %5}], [%2];" ::"r"(dst), "l"(m), "r"(bar), "r"(x), "r"(y), "r"(z) : "memory");
}
__device__ __forceinline__ void tma4d(uint32_t dst, const CUtensorMap* m, int x, int y, int z, int w, uint32_t bar) {
  asm volatile("cp.async.bulk.tensor.4d.shared::cluster.global.mbarrier::complete_tx::bytes [%0], [%1, {%3, %4, %5, %6}], [%2];" ::"r"(dst), "l"(m), "r"(bar), "r"(x), "r"(y), "r"(z), "r"(w) : "memory");
}
__device__ __forceinline__ void tma5d(uint32_t dst, const CUtensorMap* m, int x, int v, uint32_t bar) {
  asm volatile("cp.async.bulk.tensor.5d.shared::cluster.global.mbarrier::complete_tx::bytes [%0], [%1, {%3, %5, %5, %5, %4}], [%2];" ::"r"(dst), "l"(m), "r"(bar), "r"(x), "r"(v), "r"(0) : "memory");
}
__device__ __forceinline__ void tma_store2d(const CUtensorMap* m, uint32_t src, int x, int y) {
  asm volatile("cp.async.bulk.tensor.2d.global.shared::cta.bulk_group [%0, {%2, %3}], [%1];" ::"l"(m), "r"(src), "r"(x), "r"(y) : "memory");
}
__device__ __forceinline__ void bulk_load(uint32_t dst, const void* src, uint32_t bytes, uint32_t bar) {
  asm volatile("cp.async.bulk.shared::cluster.global.mbarrier::complete_tx::bytes [%0], [%1], %2, [%3];" ::"r"(dst), "l"(src), "r"(bytes), "r"(bar) : "memory");
}
__device__ __forceinline__ void bulk_commit() { asm volatile("cp.async.bulk.commit_group;" ::: "memory"); }
__device__ __forceinline__ void bulk_wait_read0() { asm volatile("cp.async.bulk.wait_group.read 0;" ::: "memory"); }
__device__ __forceinline__ void prefetch_l2(const void* p) { asm volatile("prefetch.global.L2 [%0];" ::"l"(p) : "memory"); }
__device__ __forceinline__ void touch_l2(const void* p, int lane) { asm volatile("cp.async.cg.shared.global.L2::128B [%0], [%1], 16;" ::"r"(SB + SM_SINK + lane * 16), "l"(p) : "memory"); }
__device__ __forceinline__ void cp_async16(uint32_t dst, const void* src) { asm volatile("cp.async.cg.shared.global [%0], [%1], 16;" ::"r"(dst), "l"(src) : "memory"); }
__device__ __forceinline__ void prefetch_map(const CUtensorMap* m) { asm volatile("prefetch.tensormap [%0];" ::"l"(m) : "memory"); }
__device__ __forceinline__ void fence_async_smem() { asm volatile("fence.proxy.async.shared::cta;" ::: "memory"); }
__device__ __forceinline__ void fence_async_global() { asm volatile("fence.proxy.async.global;" ::: "memory"); }
__device__ __forceinline__ void bar_sync(int id, int n) { asm volatile("bar.sync %0, %1;" ::"r"(id), "r"(n) : "memory"); }
__device__ __forceinline__ void wg_fence() { asm volatile("wgmma.fence.sync.aligned;" ::: "memory"); }
__device__ __forceinline__ void wg_commit() { asm volatile("wgmma.commit_group.sync.aligned;" ::: "memory"); }
template <int N> __device__ __forceinline__ void wg_wait() { asm volatile("wgmma.wait_group.sync.aligned %0;" ::"n"(N) : "memory"); }
template <int N> __device__ __forceinline__ void reg_fence(uint32_t* r) {
#pragma unroll
  for (int i = 0; i < N; i++) asm volatile("" : "+r"(r[i])::"memory");
}
template <int N> __device__ __forceinline__ void reg_fence(float* r) {
#pragma unroll
  for (int i = 0; i < N; i++) asm volatile("" : "+f"(r[i])::"memory");
}
__device__ __forceinline__ uint64_t mkdesc(uint32_t addr, uint32_t lbo, uint32_t sbo, uint32_t swz, uint32_t dyn = 0) {
  const uint32_t lo = ((addr >> 4) | ((lbo >> 4) << 16)) + dyn;
  const uint32_t hi = (sbo >> 4) | (swz << 30);
  uint64_t d;
  asm("mov.b64 %0, {%1, %2};" : "=l"(d) : "r"(lo), "r"(hi));
  return d;
}
template <uint32_t C> __device__ __forceinline__ uint32_t fresh_hi(uint32_t zero) { uint32_t h; asm volatile("or.b32 %0, %1, %2;" : "=r"(h) : "r"(zero), "n"(C)); return h; }
constexpr uint32_t H128 = (1024u >> 4) | (1u << 30), H64 = (512u >> 4) | (2u << 30), HNS = 128u >> 4;
__device__ __forceinline__ uint64_t mkdesch(uint32_t addr, uint32_t lbo, uint32_t hi, uint32_t dyn = 0) {
  const uint32_t lo = ((addr >> 4) | ((lbo >> 4) << 16)) + dyn;
  uint64_t d;
  asm("mov.b64 %0, {%1, %2};" : "=l"(d) : "r"(lo), "r"(hi));
  return d;
}
__device__ __forceinline__ void stsm4(uint32_t addr, uint32_t a, uint32_t b, uint32_t c, uint32_t d) {
  asm volatile("stmatrix.sync.aligned.m8n8.x4.shared.b16 [%0], {%1, %2, %3, %4};" ::"r"(addr), "r"(a), "r"(b), "r"(c), "r"(d) : "memory");
}
__device__ __forceinline__ void ldsm4(uint32_t addr, uint32_t& a, uint32_t& b, uint32_t& c, uint32_t& d) {
  asm volatile("ldmatrix.sync.aligned.m8n8.x4.shared.b16 {%0, %1, %2, %3}, [%4];" : "=r"(a), "=r"(b), "=r"(c), "=r"(d) : "r"(addr) : "memory");
}
__device__ __forceinline__ uint32_t pack2(float lo, float hi) { uint32_t r; asm("cvt.rn.bf16x2.f32 %0, %1, %2;" : "=r"(r) : "f"(hi), "f"(lo)); return r; }
__device__ __forceinline__ uint32_t bsub2(uint32_t a, uint32_t b) { uint32_t r; asm("sub.rn.bf16x2 %0, %1, %2;" : "=r"(r) : "r"(a), "r"(b)); return r; }
__device__ __forceinline__ uint32_t badd2(uint32_t a, uint32_t b) { uint32_t r; asm("add.rn.bf16x2 %0, %1, %2;" : "=r"(r) : "r"(a), "r"(b)); return r; }
__device__ __forceinline__ uint32_t bmul2(uint32_t a, uint32_t b) { uint32_t r; asm("mul.rn.bf16x2 %0, %1, %2;" : "=r"(r) : "r"(a), "r"(b)); return r; }
__device__ __forceinline__ float bf_lo(uint32_t v) { return __uint_as_float(v << 16); }
__device__ __forceinline__ float bf_hi(uint32_t v) { return __uint_as_float(v & 0xffff0000u); }
__device__ __forceinline__ float bf_round(float v) { return bf_lo(pack2(v, 0.f)); }
__device__ __forceinline__ float ex2(float v) { float r; asm("ex2.approx.ftz.f32 %0, %1;" : "=f"(r) : "f"(v)); return r; }
__device__ __forceinline__ float rcp(float v) { float r; asm("rcp.approx.ftz.f32 %0, %1;" : "=f"(r) : "f"(v)); return r; }
__device__ __forceinline__ float sqrt_approx(float v) { float r; asm("sqrt.approx.f32 %0, %1;" : "=f"(r) : "f"(v)); return r; }
__device__ __forceinline__ float4 lds128(uint32_t a) { float4 v; asm volatile("ld.shared.v4.f32 {%0, %1, %2, %3}, [%4];" : "=f"(v.x), "=f"(v.y), "=f"(v.z), "=f"(v.w) : "r"(a) : "memory"); return v; }
__device__ __forceinline__ uint4 lds128u(uint32_t a) { uint4 v; asm volatile("ld.shared.v4.u32 {%0, %1, %2, %3}, [%4];" : "=r"(v.x), "=r"(v.y), "=r"(v.z), "=r"(v.w) : "r"(a) : "memory"); return v; }
__device__ __forceinline__ float2 lds64(uint32_t a) { float2 v; asm volatile("ld.shared.v2.f32 {%0, %1}, [%2];" : "=f"(v.x), "=f"(v.y) : "r"(a) : "memory"); return v; }
__device__ __forceinline__ float lds32(uint32_t a) { float v; asm volatile("ld.shared.f32 %0, [%1];" : "=f"(v) : "r"(a) : "memory"); return v; }
__device__ __forceinline__ void sts32(uint32_t a, float v) { asm volatile("st.shared.f32 [%0], %1;" ::"r"(a), "f"(v) : "memory"); }
__device__ __forceinline__ void sts64(uint32_t a, float x, float y) { asm volatile("st.shared.v2.f32 [%0], {%1, %2};" ::"r"(a), "f"(x), "f"(y) : "memory"); }
__device__ __forceinline__ void sts128(uint32_t a, float x, float y, float z, float w) { asm volatile("st.shared.v4.f32 [%0], {%1, %2, %3, %4};" ::"r"(a), "f"(x), "f"(y), "f"(z), "f"(w) : "memory"); }
__device__ __forceinline__ void sts64u(uint32_t a, uint32_t x, uint32_t y) { asm volatile("st.shared.v2.u32 [%0], {%1, %2};" ::"r"(a), "r"(x), "r"(y) : "memory"); }
__device__ __forceinline__ void sts128u(uint32_t a, uint32_t x, uint32_t y, uint32_t z, uint32_t w) { asm volatile("st.shared.v4.u32 [%0], {%1, %2, %3, %4};" ::"r"(a), "r"(x), "r"(y), "r"(z), "r"(w) : "memory"); }
__device__ __forceinline__ uint4 ldg_nc(const void* p) { uint4 v; asm volatile("ld.global.nc.L1::no_allocate.v4.u32 {%0, %1, %2, %3}, [%4];" : "=r"(v.x), "=r"(v.y), "=r"(v.z), "=r"(v.w) : "l"(p)); return v; }
__device__ __forceinline__ float4 ldg_cg4(const float* p) { float4 v; asm volatile("ld.global.cg.v4.f32 {%0, %1, %2, %3}, [%4];" : "=f"(v.x), "=f"(v.y), "=f"(v.z), "=f"(v.w) : "l"(p) : "memory"); return v; }
__device__ __forceinline__ uint32_t ld_acq(const uint32_t* p) { uint32_t v; asm volatile("ld.acquire.gpu.global.u32 %0, [%1];" : "=r"(v) : "l"(p) : "memory"); return v; }
__device__ __forceinline__ unsigned long long ld_rlx64(const unsigned long long* p) { unsigned long long v; asm volatile("ld.relaxed.gpu.global.u64 %0, [%1];" : "=l"(v) : "l"(p) : "memory"); return v; }
__device__ __forceinline__ void st_rlx64(unsigned long long* p, unsigned long long v) { asm volatile("st.relaxed.gpu.global.u64 [%0], %1;" ::"l"(p), "l"(v) : "memory"); }
__device__ __forceinline__ uint4 ld_rlx128(const void* p) {
  uint4 v;
  asm volatile("{ .reg .b128 t; .reg .b64 a, b; ld.relaxed.gpu.global.b128 t, [%4]; mov.b128 {a, b}, t; mov.b64 {%0, %1}, a; mov.b64 {%2, %3}, b; }"
               : "=r"(v.x), "=r"(v.y), "=r"(v.z), "=r"(v.w) : "l"(p) : "memory");
  return v;
}
__device__ __forceinline__ void st_rlx128(void* p, uint32_t x, uint32_t y, uint32_t z, uint32_t w) {
  asm volatile("{ .reg .b128 t; .reg .b64 a, b; mov.b64 a, {%1, %2}; mov.b64 b, {%3, %4}; mov.b128 t, {a, b}; st.relaxed.gpu.global.b128 [%0], t; }"
               ::"l"(p), "r"(x), "r"(y), "r"(z), "r"(w) : "memory");
}
__device__ __forceinline__ void st_rlx(void* p, uint32_t v) { asm volatile("st.relaxed.gpu.global.u32 [%0], %1;" ::"l"(p), "r"(v) : "memory"); }
__device__ __forceinline__ uint32_t lop_select(uint32_t a, uint32_t b, uint32_t m) { uint32_t r; asm("lop3.b32 %0, %1, %2, %3, 0xd8;" : "=r"(r) : "r"(a), "r"(b), "r"(m)); return r; }
__device__ __forceinline__ float unmark(uint32_t v) { return __uint_as_float(v & ~1u); }
__device__ __forceinline__ uint32_t mark(uint32_t v, uint32_t par) { return (v & ~1u) | par; }
__device__ __forceinline__ float tanh_approx(float v) { float r; asm("tanh.approx.f32 %0, %1;" : "=f"(r) : "f"(v)); return r; }
__device__ __forceinline__ void red1(float* p, float a) { asm volatile("red.global.add.f32 [%0], %1;" ::"l"(p), "f"(a) : "memory"); }
__device__ __forceinline__ void red_inc(uint32_t* p) { asm volatile("red.relaxed.gpu.global.add.u32 [%0], 1;" ::"l"(p) : "memory"); }
__device__ __forceinline__ void red_rel(uint32_t* p) { asm volatile("red.release.gpu.global.add.u32 [%0], 1;" ::"l"(p) : "memory"); }
constexpr int SPIN_MAX = 100000;
__device__ __forceinline__ uint32_t ld_rlx(const uint32_t* p) { uint32_t v; asm volatile("ld.relaxed.gpu.global.u32 %0, [%1];" : "=r"(v) : "l"(p) : "memory"); return v; }
template <int NS = 0> __device__ __forceinline__ void wait_hint(const uint32_t* p, uint32_t target) {
#pragma unroll 1
  for (int i = 0; i < SPIN_MAX; i++) { if ((int)(ld_rlx(p) - target) >= 0) break; if (NS) __nanosleep(NS); }
}
template <int NS> __device__ __forceinline__ void wait_cnt(const uint32_t* p, uint32_t target) {
#pragma unroll 1
  for (int i = 0; i < SPIN_MAX; i++) { if ((int)(ld_rlx(p) - target) >= 0) break; if (NS) __nanosleep(NS); }
  (void)ld_acq(p);
}
template <int NS> __device__ __forceinline__ unsigned long long wait_tag(const unsigned long long* p, uint32_t tag) {
  unsigned long long v = 0;
#pragma unroll 1
  for (int i = 0; i < SPIN_MAX; i++) { v = ld_rlx64(p); if ((uint32_t)(v >> 32) == tag) break; if (NS) __nanosleep(NS); }
  return v;
}
__device__ __forceinline__ float silu_f(float v) { return v * rcp(1.f + ex2(-1.4426950408889634f * v)); }

__device__ __forceinline__ void wgmma_n8_ss_ta1_tb0(float* d, uint64_t da, uint64_t db, bool accumulate) {
  if (accumulate) {
    asm volatile("{\n.reg .pred p;\nsetp.ne.b32 p, 1, 0;\n"
      "wgmma.mma_async.sync.aligned.m64n8k16.f32.bf16.bf16 "
      "{%0, %1, %2, %3}, "
      "%4, %5, p, 1, 1, 1, 0;\n}\n"
      : "+f"(d[0]), "+f"(d[1]), "+f"(d[2]), "+f"(d[3])
      : "l"(da), "l"(db));
  } else {
    asm volatile("{\n.reg .pred p;\nsetp.ne.b32 p, 0, 0;\n"
      "wgmma.mma_async.sync.aligned.m64n8k16.f32.bf16.bf16 "
      "{%0, %1, %2, %3}, "
      "%4, %5, p, 1, 1, 1, 0;\n}\n"
      : "=f"(d[0]), "=f"(d[1]), "=f"(d[2]), "=f"(d[3])
      : "l"(da), "l"(db));
  }
}
__device__ __forceinline__ void wgmma_n8_ss_ta1_tb1(float* d, uint64_t da, uint64_t db, bool accumulate) {
  if (accumulate) {
    asm volatile("{\n.reg .pred p;\nsetp.ne.b32 p, 1, 0;\n"
      "wgmma.mma_async.sync.aligned.m64n8k16.f32.bf16.bf16 "
      "{%0, %1, %2, %3}, "
      "%4, %5, p, 1, 1, 1, 1;\n}\n"
      : "+f"(d[0]), "+f"(d[1]), "+f"(d[2]), "+f"(d[3])
      : "l"(da), "l"(db));
  } else {
    asm volatile("{\n.reg .pred p;\nsetp.ne.b32 p, 0, 0;\n"
      "wgmma.mma_async.sync.aligned.m64n8k16.f32.bf16.bf16 "
      "{%0, %1, %2, %3}, "
      "%4, %5, p, 1, 1, 1, 1;\n}\n"
      : "=f"(d[0]), "=f"(d[1]), "=f"(d[2]), "=f"(d[3])
      : "l"(da), "l"(db));
  }
}
__device__ __forceinline__ void wgmma_n32_rs_ta0_tb1(float* d, uint32_t a0, uint32_t a1, uint32_t a2, uint32_t a3, uint64_t db, bool accumulate) {
  if (accumulate) {
    asm volatile("{\n.reg .pred p;\nsetp.ne.b32 p, 1, 0;\n"
      "wgmma.mma_async.sync.aligned.m64n32k16.f32.bf16.bf16 "
      "{%0, %1, %2, %3, %4, %5, %6, %7, %8, %9, %10, %11, %12, %13, %14, %15}, "
      "{%16, %17, %18, %19}, %20, p, 1, 1, 1;\n}\n"
      : "+f"(d[0]), "+f"(d[1]), "+f"(d[2]), "+f"(d[3]), "+f"(d[4]), "+f"(d[5]), "+f"(d[6]), "+f"(d[7]), "+f"(d[8]), "+f"(d[9]), "+f"(d[10]), "+f"(d[11]), "+f"(d[12]), "+f"(d[13]), "+f"(d[14]), "+f"(d[15])
      : "r"(a0), "r"(a1), "r"(a2), "r"(a3), "l"(db));
  } else {
    asm volatile("{\n.reg .pred p;\nsetp.ne.b32 p, 0, 0;\n"
      "wgmma.mma_async.sync.aligned.m64n32k16.f32.bf16.bf16 "
      "{%0, %1, %2, %3, %4, %5, %6, %7, %8, %9, %10, %11, %12, %13, %14, %15}, "
      "{%16, %17, %18, %19}, %20, p, 1, 1, 1;\n}\n"
      : "=f"(d[0]), "=f"(d[1]), "=f"(d[2]), "=f"(d[3]), "=f"(d[4]), "=f"(d[5]), "=f"(d[6]), "=f"(d[7]), "=f"(d[8]), "=f"(d[9]), "=f"(d[10]), "=f"(d[11]), "=f"(d[12]), "=f"(d[13]), "=f"(d[14]), "=f"(d[15])
      : "r"(a0), "r"(a1), "r"(a2), "r"(a3), "l"(db));
  }
}
__device__ __forceinline__ void wgmma_n40_rs_ta0_tb1(float* d, uint32_t a0, uint32_t a1, uint32_t a2, uint32_t a3, uint64_t db, bool accumulate) {
  if (accumulate) {
    asm volatile("{\n.reg .pred p;\nsetp.ne.b32 p, 1, 0;\n"
      "wgmma.mma_async.sync.aligned.m64n40k16.f32.bf16.bf16 "
      "{%0, %1, %2, %3, %4, %5, %6, %7, %8, %9, %10, %11, %12, %13, %14, %15, %16, %17, %18, %19}, "
      "{%20, %21, %22, %23}, %24, p, 1, 1, 1;\n}\n"
      : "+f"(d[0]), "+f"(d[1]), "+f"(d[2]), "+f"(d[3]), "+f"(d[4]), "+f"(d[5]), "+f"(d[6]), "+f"(d[7]), "+f"(d[8]), "+f"(d[9]), "+f"(d[10]), "+f"(d[11]), "+f"(d[12]), "+f"(d[13]), "+f"(d[14]), "+f"(d[15]), "+f"(d[16]), "+f"(d[17]), "+f"(d[18]), "+f"(d[19])
      : "r"(a0), "r"(a1), "r"(a2), "r"(a3), "l"(db));
  } else {
    asm volatile("{\n.reg .pred p;\nsetp.ne.b32 p, 0, 0;\n"
      "wgmma.mma_async.sync.aligned.m64n40k16.f32.bf16.bf16 "
      "{%0, %1, %2, %3, %4, %5, %6, %7, %8, %9, %10, %11, %12, %13, %14, %15, %16, %17, %18, %19}, "
      "{%20, %21, %22, %23}, %24, p, 1, 1, 1;\n}\n"
      : "=f"(d[0]), "=f"(d[1]), "=f"(d[2]), "=f"(d[3]), "=f"(d[4]), "=f"(d[5]), "=f"(d[6]), "=f"(d[7]), "=f"(d[8]), "=f"(d[9]), "=f"(d[10]), "=f"(d[11]), "=f"(d[12]), "=f"(d[13]), "=f"(d[14]), "=f"(d[15]), "=f"(d[16]), "=f"(d[17]), "=f"(d[18]), "=f"(d[19])
      : "r"(a0), "r"(a1), "r"(a2), "r"(a3), "l"(db));
  }
}
__device__ __forceinline__ void wgmma_n40_ss_ta1_tb1(float* d, uint64_t da, uint64_t db, bool accumulate) {
  if (accumulate) {
    asm volatile("{\n.reg .pred p;\nsetp.ne.b32 p, 1, 0;\n"
      "wgmma.mma_async.sync.aligned.m64n40k16.f32.bf16.bf16 "
      "{%0, %1, %2, %3, %4, %5, %6, %7, %8, %9, %10, %11, %12, %13, %14, %15, %16, %17, %18, %19}, "
      "%20, %21, p, 1, 1, 1, 1;\n}\n"
      : "+f"(d[0]), "+f"(d[1]), "+f"(d[2]), "+f"(d[3]), "+f"(d[4]), "+f"(d[5]), "+f"(d[6]), "+f"(d[7]), "+f"(d[8]), "+f"(d[9]), "+f"(d[10]), "+f"(d[11]), "+f"(d[12]), "+f"(d[13]), "+f"(d[14]), "+f"(d[15]), "+f"(d[16]), "+f"(d[17]), "+f"(d[18]), "+f"(d[19])
      : "l"(da), "l"(db));
  } else {
    asm volatile("{\n.reg .pred p;\nsetp.ne.b32 p, 0, 0;\n"
      "wgmma.mma_async.sync.aligned.m64n40k16.f32.bf16.bf16 "
      "{%0, %1, %2, %3, %4, %5, %6, %7, %8, %9, %10, %11, %12, %13, %14, %15, %16, %17, %18, %19}, "
      "%20, %21, p, 1, 1, 1, 1;\n}\n"
      : "=f"(d[0]), "=f"(d[1]), "=f"(d[2]), "=f"(d[3]), "=f"(d[4]), "=f"(d[5]), "=f"(d[6]), "=f"(d[7]), "=f"(d[8]), "=f"(d[9]), "=f"(d[10]), "=f"(d[11]), "=f"(d[12]), "=f"(d[13]), "=f"(d[14]), "=f"(d[15]), "=f"(d[16]), "=f"(d[17]), "=f"(d[18]), "=f"(d[19])
      : "l"(da), "l"(db));
  }
}
__device__ __forceinline__ void wgmma_n128_rs_ta0_tb1(float* d, uint32_t a0, uint32_t a1, uint32_t a2, uint32_t a3, uint64_t db, bool accumulate) {
  if (accumulate) {
    asm volatile("{\n.reg .pred p;\nsetp.ne.b32 p, 1, 0;\n"
      "wgmma.mma_async.sync.aligned.m64n128k16.f32.bf16.bf16 "
      "{%0, %1, %2, %3, %4, %5, %6, %7, %8, %9, %10, %11, %12, %13, %14, %15, %16, %17, %18, %19, %20, %21, %22, %23, %24, %25, %26, %27, %28, %29, %30, %31, %32, %33, %34, %35, %36, %37, %38, %39, %40, %41, %42, %43, %44, %45, %46, %47, %48, %49, %50, %51, %52, %53, %54, %55, %56, %57, %58, %59, %60, %61, %62, %63}, "
      "{%64, %65, %66, %67}, %68, p, 1, 1, 1;\n}\n"
      : "+f"(d[0]), "+f"(d[1]), "+f"(d[2]), "+f"(d[3]), "+f"(d[4]), "+f"(d[5]), "+f"(d[6]), "+f"(d[7]), "+f"(d[8]), "+f"(d[9]), "+f"(d[10]), "+f"(d[11]), "+f"(d[12]), "+f"(d[13]), "+f"(d[14]), "+f"(d[15]), "+f"(d[16]), "+f"(d[17]), "+f"(d[18]), "+f"(d[19]), "+f"(d[20]), "+f"(d[21]), "+f"(d[22]), "+f"(d[23]), "+f"(d[24]), "+f"(d[25]), "+f"(d[26]), "+f"(d[27]), "+f"(d[28]), "+f"(d[29]), "+f"(d[30]), "+f"(d[31]), "+f"(d[32]), "+f"(d[33]), "+f"(d[34]), "+f"(d[35]), "+f"(d[36]), "+f"(d[37]), "+f"(d[38]), "+f"(d[39]), "+f"(d[40]), "+f"(d[41]), "+f"(d[42]), "+f"(d[43]), "+f"(d[44]), "+f"(d[45]), "+f"(d[46]), "+f"(d[47]), "+f"(d[48]), "+f"(d[49]), "+f"(d[50]), "+f"(d[51]), "+f"(d[52]), "+f"(d[53]), "+f"(d[54]), "+f"(d[55]), "+f"(d[56]), "+f"(d[57]), "+f"(d[58]), "+f"(d[59]), "+f"(d[60]), "+f"(d[61]), "+f"(d[62]), "+f"(d[63])
      : "r"(a0), "r"(a1), "r"(a2), "r"(a3), "l"(db));
  } else {
    asm volatile("{\n.reg .pred p;\nsetp.ne.b32 p, 0, 0;\n"
      "wgmma.mma_async.sync.aligned.m64n128k16.f32.bf16.bf16 "
      "{%0, %1, %2, %3, %4, %5, %6, %7, %8, %9, %10, %11, %12, %13, %14, %15, %16, %17, %18, %19, %20, %21, %22, %23, %24, %25, %26, %27, %28, %29, %30, %31, %32, %33, %34, %35, %36, %37, %38, %39, %40, %41, %42, %43, %44, %45, %46, %47, %48, %49, %50, %51, %52, %53, %54, %55, %56, %57, %58, %59, %60, %61, %62, %63}, "
      "{%64, %65, %66, %67}, %68, p, 1, 1, 1;\n}\n"
      : "=f"(d[0]), "=f"(d[1]), "=f"(d[2]), "=f"(d[3]), "=f"(d[4]), "=f"(d[5]), "=f"(d[6]), "=f"(d[7]), "=f"(d[8]), "=f"(d[9]), "=f"(d[10]), "=f"(d[11]), "=f"(d[12]), "=f"(d[13]), "=f"(d[14]), "=f"(d[15]), "=f"(d[16]), "=f"(d[17]), "=f"(d[18]), "=f"(d[19]), "=f"(d[20]), "=f"(d[21]), "=f"(d[22]), "=f"(d[23]), "=f"(d[24]), "=f"(d[25]), "=f"(d[26]), "=f"(d[27]), "=f"(d[28]), "=f"(d[29]), "=f"(d[30]), "=f"(d[31]), "=f"(d[32]), "=f"(d[33]), "=f"(d[34]), "=f"(d[35]), "=f"(d[36]), "=f"(d[37]), "=f"(d[38]), "=f"(d[39]), "=f"(d[40]), "=f"(d[41]), "=f"(d[42]), "=f"(d[43]), "=f"(d[44]), "=f"(d[45]), "=f"(d[46]), "=f"(d[47]), "=f"(d[48]), "=f"(d[49]), "=f"(d[50]), "=f"(d[51]), "=f"(d[52]), "=f"(d[53]), "=f"(d[54]), "=f"(d[55]), "=f"(d[56]), "=f"(d[57]), "=f"(d[58]), "=f"(d[59]), "=f"(d[60]), "=f"(d[61]), "=f"(d[62]), "=f"(d[63])
      : "r"(a0), "r"(a1), "r"(a2), "r"(a3), "l"(db));
  }
}
__device__ __forceinline__ void wgmma_n128_ss_ta0_tb1(float* d, uint64_t da, uint64_t db, bool accumulate) {
  if (accumulate) {
    asm volatile("{\n.reg .pred p;\nsetp.ne.b32 p, 1, 0;\n"
      "wgmma.mma_async.sync.aligned.m64n128k16.f32.bf16.bf16 "
      "{%0, %1, %2, %3, %4, %5, %6, %7, %8, %9, %10, %11, %12, %13, %14, %15, %16, %17, %18, %19, %20, %21, %22, %23, %24, %25, %26, %27, %28, %29, %30, %31, %32, %33, %34, %35, %36, %37, %38, %39, %40, %41, %42, %43, %44, %45, %46, %47, %48, %49, %50, %51, %52, %53, %54, %55, %56, %57, %58, %59, %60, %61, %62, %63}, "
      "%64, %65, p, 1, 1, 0, 1;\n}\n"
      : "+f"(d[0]), "+f"(d[1]), "+f"(d[2]), "+f"(d[3]), "+f"(d[4]), "+f"(d[5]), "+f"(d[6]), "+f"(d[7]), "+f"(d[8]), "+f"(d[9]), "+f"(d[10]), "+f"(d[11]), "+f"(d[12]), "+f"(d[13]), "+f"(d[14]), "+f"(d[15]), "+f"(d[16]), "+f"(d[17]), "+f"(d[18]), "+f"(d[19]), "+f"(d[20]), "+f"(d[21]), "+f"(d[22]), "+f"(d[23]), "+f"(d[24]), "+f"(d[25]), "+f"(d[26]), "+f"(d[27]), "+f"(d[28]), "+f"(d[29]), "+f"(d[30]), "+f"(d[31]), "+f"(d[32]), "+f"(d[33]), "+f"(d[34]), "+f"(d[35]), "+f"(d[36]), "+f"(d[37]), "+f"(d[38]), "+f"(d[39]), "+f"(d[40]), "+f"(d[41]), "+f"(d[42]), "+f"(d[43]), "+f"(d[44]), "+f"(d[45]), "+f"(d[46]), "+f"(d[47]), "+f"(d[48]), "+f"(d[49]), "+f"(d[50]), "+f"(d[51]), "+f"(d[52]), "+f"(d[53]), "+f"(d[54]), "+f"(d[55]), "+f"(d[56]), "+f"(d[57]), "+f"(d[58]), "+f"(d[59]), "+f"(d[60]), "+f"(d[61]), "+f"(d[62]), "+f"(d[63])
      : "l"(da), "l"(db));
  } else {
    asm volatile("{\n.reg .pred p;\nsetp.ne.b32 p, 0, 0;\n"
      "wgmma.mma_async.sync.aligned.m64n128k16.f32.bf16.bf16 "
      "{%0, %1, %2, %3, %4, %5, %6, %7, %8, %9, %10, %11, %12, %13, %14, %15, %16, %17, %18, %19, %20, %21, %22, %23, %24, %25, %26, %27, %28, %29, %30, %31, %32, %33, %34, %35, %36, %37, %38, %39, %40, %41, %42, %43, %44, %45, %46, %47, %48, %49, %50, %51, %52, %53, %54, %55, %56, %57, %58, %59, %60, %61, %62, %63}, "
      "%64, %65, p, 1, 1, 0, 1;\n}\n"
      : "=f"(d[0]), "=f"(d[1]), "=f"(d[2]), "=f"(d[3]), "=f"(d[4]), "=f"(d[5]), "=f"(d[6]), "=f"(d[7]), "=f"(d[8]), "=f"(d[9]), "=f"(d[10]), "=f"(d[11]), "=f"(d[12]), "=f"(d[13]), "=f"(d[14]), "=f"(d[15]), "=f"(d[16]), "=f"(d[17]), "=f"(d[18]), "=f"(d[19]), "=f"(d[20]), "=f"(d[21]), "=f"(d[22]), "=f"(d[23]), "=f"(d[24]), "=f"(d[25]), "=f"(d[26]), "=f"(d[27]), "=f"(d[28]), "=f"(d[29]), "=f"(d[30]), "=f"(d[31]), "=f"(d[32]), "=f"(d[33]), "=f"(d[34]), "=f"(d[35]), "=f"(d[36]), "=f"(d[37]), "=f"(d[38]), "=f"(d[39]), "=f"(d[40]), "=f"(d[41]), "=f"(d[42]), "=f"(d[43]), "=f"(d[44]), "=f"(d[45]), "=f"(d[46]), "=f"(d[47]), "=f"(d[48]), "=f"(d[49]), "=f"(d[50]), "=f"(d[51]), "=f"(d[52]), "=f"(d[53]), "=f"(d[54]), "=f"(d[55]), "=f"(d[56]), "=f"(d[57]), "=f"(d[58]), "=f"(d[59]), "=f"(d[60]), "=f"(d[61]), "=f"(d[62]), "=f"(d[63])
      : "l"(da), "l"(db));
  }
}
__device__ __forceinline__ void wgmma_n256_rs_ta0_tb1(float* d, uint32_t a0, uint32_t a1, uint32_t a2, uint32_t a3, uint64_t db, bool accumulate) {
  if (accumulate) {
    asm volatile("{\n.reg .pred p;\nsetp.ne.b32 p, 1, 0;\n"
      "wgmma.mma_async.sync.aligned.m64n256k16.f32.bf16.bf16 "
      "{%0, %1, %2, %3, %4, %5, %6, %7, %8, %9, %10, %11, %12, %13, %14, %15, %16, %17, %18, %19, %20, %21, %22, %23, %24, %25, %26, %27, %28, %29, %30, %31, %32, %33, %34, %35, %36, %37, %38, %39, %40, %41, %42, %43, %44, %45, %46, %47, %48, %49, %50, %51, %52, %53, %54, %55, %56, %57, %58, %59, %60, %61, %62, %63, %64, %65, %66, %67, %68, %69, %70, %71, %72, %73, %74, %75, %76, %77, %78, %79, %80, %81, %82, %83, %84, %85, %86, %87, %88, %89, %90, %91, %92, %93, %94, %95, %96, %97, %98, %99, %100, %101, %102, %103, %104, %105, %106, %107, %108, %109, %110, %111, %112, %113, %114, %115, %116, %117, %118, %119, %120, %121, %122, %123, %124, %125, %126, %127}, "
      "{%128, %129, %130, %131}, %132, p, 1, 1, 1;\n}\n"
      : "+f"(d[0]), "+f"(d[1]), "+f"(d[2]), "+f"(d[3]), "+f"(d[4]), "+f"(d[5]), "+f"(d[6]), "+f"(d[7]), "+f"(d[8]), "+f"(d[9]), "+f"(d[10]), "+f"(d[11]), "+f"(d[12]), "+f"(d[13]), "+f"(d[14]), "+f"(d[15]), "+f"(d[16]), "+f"(d[17]), "+f"(d[18]), "+f"(d[19]), "+f"(d[20]), "+f"(d[21]), "+f"(d[22]), "+f"(d[23]), "+f"(d[24]), "+f"(d[25]), "+f"(d[26]), "+f"(d[27]), "+f"(d[28]), "+f"(d[29]), "+f"(d[30]), "+f"(d[31]), "+f"(d[32]), "+f"(d[33]), "+f"(d[34]), "+f"(d[35]), "+f"(d[36]), "+f"(d[37]), "+f"(d[38]), "+f"(d[39]), "+f"(d[40]), "+f"(d[41]), "+f"(d[42]), "+f"(d[43]), "+f"(d[44]), "+f"(d[45]), "+f"(d[46]), "+f"(d[47]), "+f"(d[48]), "+f"(d[49]), "+f"(d[50]), "+f"(d[51]), "+f"(d[52]), "+f"(d[53]), "+f"(d[54]), "+f"(d[55]), "+f"(d[56]), "+f"(d[57]), "+f"(d[58]), "+f"(d[59]), "+f"(d[60]), "+f"(d[61]), "+f"(d[62]), "+f"(d[63]), "+f"(d[64]), "+f"(d[65]), "+f"(d[66]), "+f"(d[67]), "+f"(d[68]), "+f"(d[69]), "+f"(d[70]), "+f"(d[71]), "+f"(d[72]), "+f"(d[73]), "+f"(d[74]), "+f"(d[75]), "+f"(d[76]), "+f"(d[77]), "+f"(d[78]), "+f"(d[79]), "+f"(d[80]), "+f"(d[81]), "+f"(d[82]), "+f"(d[83]), "+f"(d[84]), "+f"(d[85]), "+f"(d[86]), "+f"(d[87]), "+f"(d[88]), "+f"(d[89]), "+f"(d[90]), "+f"(d[91]), "+f"(d[92]), "+f"(d[93]), "+f"(d[94]), "+f"(d[95]), "+f"(d[96]), "+f"(d[97]), "+f"(d[98]), "+f"(d[99]), "+f"(d[100]), "+f"(d[101]), "+f"(d[102]), "+f"(d[103]), "+f"(d[104]), "+f"(d[105]), "+f"(d[106]), "+f"(d[107]), "+f"(d[108]), "+f"(d[109]), "+f"(d[110]), "+f"(d[111]), "+f"(d[112]), "+f"(d[113]), "+f"(d[114]), "+f"(d[115]), "+f"(d[116]), "+f"(d[117]), "+f"(d[118]), "+f"(d[119]), "+f"(d[120]), "+f"(d[121]), "+f"(d[122]), "+f"(d[123]), "+f"(d[124]), "+f"(d[125]), "+f"(d[126]), "+f"(d[127])
      : "r"(a0), "r"(a1), "r"(a2), "r"(a3), "l"(db));
  } else {
    asm volatile("{\n.reg .pred p;\nsetp.ne.b32 p, 0, 0;\n"
      "wgmma.mma_async.sync.aligned.m64n256k16.f32.bf16.bf16 "
      "{%0, %1, %2, %3, %4, %5, %6, %7, %8, %9, %10, %11, %12, %13, %14, %15, %16, %17, %18, %19, %20, %21, %22, %23, %24, %25, %26, %27, %28, %29, %30, %31, %32, %33, %34, %35, %36, %37, %38, %39, %40, %41, %42, %43, %44, %45, %46, %47, %48, %49, %50, %51, %52, %53, %54, %55, %56, %57, %58, %59, %60, %61, %62, %63, %64, %65, %66, %67, %68, %69, %70, %71, %72, %73, %74, %75, %76, %77, %78, %79, %80, %81, %82, %83, %84, %85, %86, %87, %88, %89, %90, %91, %92, %93, %94, %95, %96, %97, %98, %99, %100, %101, %102, %103, %104, %105, %106, %107, %108, %109, %110, %111, %112, %113, %114, %115, %116, %117, %118, %119, %120, %121, %122, %123, %124, %125, %126, %127}, "
      "{%128, %129, %130, %131}, %132, p, 1, 1, 1;\n}\n"
      : "=f"(d[0]), "=f"(d[1]), "=f"(d[2]), "=f"(d[3]), "=f"(d[4]), "=f"(d[5]), "=f"(d[6]), "=f"(d[7]), "=f"(d[8]), "=f"(d[9]), "=f"(d[10]), "=f"(d[11]), "=f"(d[12]), "=f"(d[13]), "=f"(d[14]), "=f"(d[15]), "=f"(d[16]), "=f"(d[17]), "=f"(d[18]), "=f"(d[19]), "=f"(d[20]), "=f"(d[21]), "=f"(d[22]), "=f"(d[23]), "=f"(d[24]), "=f"(d[25]), "=f"(d[26]), "=f"(d[27]), "=f"(d[28]), "=f"(d[29]), "=f"(d[30]), "=f"(d[31]), "=f"(d[32]), "=f"(d[33]), "=f"(d[34]), "=f"(d[35]), "=f"(d[36]), "=f"(d[37]), "=f"(d[38]), "=f"(d[39]), "=f"(d[40]), "=f"(d[41]), "=f"(d[42]), "=f"(d[43]), "=f"(d[44]), "=f"(d[45]), "=f"(d[46]), "=f"(d[47]), "=f"(d[48]), "=f"(d[49]), "=f"(d[50]), "=f"(d[51]), "=f"(d[52]), "=f"(d[53]), "=f"(d[54]), "=f"(d[55]), "=f"(d[56]), "=f"(d[57]), "=f"(d[58]), "=f"(d[59]), "=f"(d[60]), "=f"(d[61]), "=f"(d[62]), "=f"(d[63]), "=f"(d[64]), "=f"(d[65]), "=f"(d[66]), "=f"(d[67]), "=f"(d[68]), "=f"(d[69]), "=f"(d[70]), "=f"(d[71]), "=f"(d[72]), "=f"(d[73]), "=f"(d[74]), "=f"(d[75]), "=f"(d[76]), "=f"(d[77]), "=f"(d[78]), "=f"(d[79]), "=f"(d[80]), "=f"(d[81]), "=f"(d[82]), "=f"(d[83]), "=f"(d[84]), "=f"(d[85]), "=f"(d[86]), "=f"(d[87]), "=f"(d[88]), "=f"(d[89]), "=f"(d[90]), "=f"(d[91]), "=f"(d[92]), "=f"(d[93]), "=f"(d[94]), "=f"(d[95]), "=f"(d[96]), "=f"(d[97]), "=f"(d[98]), "=f"(d[99]), "=f"(d[100]), "=f"(d[101]), "=f"(d[102]), "=f"(d[103]), "=f"(d[104]), "=f"(d[105]), "=f"(d[106]), "=f"(d[107]), "=f"(d[108]), "=f"(d[109]), "=f"(d[110]), "=f"(d[111]), "=f"(d[112]), "=f"(d[113]), "=f"(d[114]), "=f"(d[115]), "=f"(d[116]), "=f"(d[117]), "=f"(d[118]), "=f"(d[119]), "=f"(d[120]), "=f"(d[121]), "=f"(d[122]), "=f"(d[123]), "=f"(d[124]), "=f"(d[125]), "=f"(d[126]), "=f"(d[127])
      : "r"(a0), "r"(a1), "r"(a2), "r"(a3), "l"(db));
  }
}
__device__ __forceinline__ void wgmma_n256_ss_ta0_tb1(float* d, uint64_t da, uint64_t db, bool accumulate) {
  if (accumulate) {
    asm volatile("{\n.reg .pred p;\nsetp.ne.b32 p, 1, 0;\n"
      "wgmma.mma_async.sync.aligned.m64n256k16.f32.bf16.bf16 "
      "{%0, %1, %2, %3, %4, %5, %6, %7, %8, %9, %10, %11, %12, %13, %14, %15, %16, %17, %18, %19, %20, %21, %22, %23, %24, %25, %26, %27, %28, %29, %30, %31, %32, %33, %34, %35, %36, %37, %38, %39, %40, %41, %42, %43, %44, %45, %46, %47, %48, %49, %50, %51, %52, %53, %54, %55, %56, %57, %58, %59, %60, %61, %62, %63, %64, %65, %66, %67, %68, %69, %70, %71, %72, %73, %74, %75, %76, %77, %78, %79, %80, %81, %82, %83, %84, %85, %86, %87, %88, %89, %90, %91, %92, %93, %94, %95, %96, %97, %98, %99, %100, %101, %102, %103, %104, %105, %106, %107, %108, %109, %110, %111, %112, %113, %114, %115, %116, %117, %118, %119, %120, %121, %122, %123, %124, %125, %126, %127}, "
      "%128, %129, p, 1, 1, 0, 1;\n}\n"
      : "+f"(d[0]), "+f"(d[1]), "+f"(d[2]), "+f"(d[3]), "+f"(d[4]), "+f"(d[5]), "+f"(d[6]), "+f"(d[7]), "+f"(d[8]), "+f"(d[9]), "+f"(d[10]), "+f"(d[11]), "+f"(d[12]), "+f"(d[13]), "+f"(d[14]), "+f"(d[15]), "+f"(d[16]), "+f"(d[17]), "+f"(d[18]), "+f"(d[19]), "+f"(d[20]), "+f"(d[21]), "+f"(d[22]), "+f"(d[23]), "+f"(d[24]), "+f"(d[25]), "+f"(d[26]), "+f"(d[27]), "+f"(d[28]), "+f"(d[29]), "+f"(d[30]), "+f"(d[31]), "+f"(d[32]), "+f"(d[33]), "+f"(d[34]), "+f"(d[35]), "+f"(d[36]), "+f"(d[37]), "+f"(d[38]), "+f"(d[39]), "+f"(d[40]), "+f"(d[41]), "+f"(d[42]), "+f"(d[43]), "+f"(d[44]), "+f"(d[45]), "+f"(d[46]), "+f"(d[47]), "+f"(d[48]), "+f"(d[49]), "+f"(d[50]), "+f"(d[51]), "+f"(d[52]), "+f"(d[53]), "+f"(d[54]), "+f"(d[55]), "+f"(d[56]), "+f"(d[57]), "+f"(d[58]), "+f"(d[59]), "+f"(d[60]), "+f"(d[61]), "+f"(d[62]), "+f"(d[63]), "+f"(d[64]), "+f"(d[65]), "+f"(d[66]), "+f"(d[67]), "+f"(d[68]), "+f"(d[69]), "+f"(d[70]), "+f"(d[71]), "+f"(d[72]), "+f"(d[73]), "+f"(d[74]), "+f"(d[75]), "+f"(d[76]), "+f"(d[77]), "+f"(d[78]), "+f"(d[79]), "+f"(d[80]), "+f"(d[81]), "+f"(d[82]), "+f"(d[83]), "+f"(d[84]), "+f"(d[85]), "+f"(d[86]), "+f"(d[87]), "+f"(d[88]), "+f"(d[89]), "+f"(d[90]), "+f"(d[91]), "+f"(d[92]), "+f"(d[93]), "+f"(d[94]), "+f"(d[95]), "+f"(d[96]), "+f"(d[97]), "+f"(d[98]), "+f"(d[99]), "+f"(d[100]), "+f"(d[101]), "+f"(d[102]), "+f"(d[103]), "+f"(d[104]), "+f"(d[105]), "+f"(d[106]), "+f"(d[107]), "+f"(d[108]), "+f"(d[109]), "+f"(d[110]), "+f"(d[111]), "+f"(d[112]), "+f"(d[113]), "+f"(d[114]), "+f"(d[115]), "+f"(d[116]), "+f"(d[117]), "+f"(d[118]), "+f"(d[119]), "+f"(d[120]), "+f"(d[121]), "+f"(d[122]), "+f"(d[123]), "+f"(d[124]), "+f"(d[125]), "+f"(d[126]), "+f"(d[127])
      : "l"(da), "l"(db));
  } else {
    asm volatile("{\n.reg .pred p;\nsetp.ne.b32 p, 0, 0;\n"
      "wgmma.mma_async.sync.aligned.m64n256k16.f32.bf16.bf16 "
      "{%0, %1, %2, %3, %4, %5, %6, %7, %8, %9, %10, %11, %12, %13, %14, %15, %16, %17, %18, %19, %20, %21, %22, %23, %24, %25, %26, %27, %28, %29, %30, %31, %32, %33, %34, %35, %36, %37, %38, %39, %40, %41, %42, %43, %44, %45, %46, %47, %48, %49, %50, %51, %52, %53, %54, %55, %56, %57, %58, %59, %60, %61, %62, %63, %64, %65, %66, %67, %68, %69, %70, %71, %72, %73, %74, %75, %76, %77, %78, %79, %80, %81, %82, %83, %84, %85, %86, %87, %88, %89, %90, %91, %92, %93, %94, %95, %96, %97, %98, %99, %100, %101, %102, %103, %104, %105, %106, %107, %108, %109, %110, %111, %112, %113, %114, %115, %116, %117, %118, %119, %120, %121, %122, %123, %124, %125, %126, %127}, "
      "%128, %129, p, 1, 1, 0, 1;\n}\n"
      : "=f"(d[0]), "=f"(d[1]), "=f"(d[2]), "=f"(d[3]), "=f"(d[4]), "=f"(d[5]), "=f"(d[6]), "=f"(d[7]), "=f"(d[8]), "=f"(d[9]), "=f"(d[10]), "=f"(d[11]), "=f"(d[12]), "=f"(d[13]), "=f"(d[14]), "=f"(d[15]), "=f"(d[16]), "=f"(d[17]), "=f"(d[18]), "=f"(d[19]), "=f"(d[20]), "=f"(d[21]), "=f"(d[22]), "=f"(d[23]), "=f"(d[24]), "=f"(d[25]), "=f"(d[26]), "=f"(d[27]), "=f"(d[28]), "=f"(d[29]), "=f"(d[30]), "=f"(d[31]), "=f"(d[32]), "=f"(d[33]), "=f"(d[34]), "=f"(d[35]), "=f"(d[36]), "=f"(d[37]), "=f"(d[38]), "=f"(d[39]), "=f"(d[40]), "=f"(d[41]), "=f"(d[42]), "=f"(d[43]), "=f"(d[44]), "=f"(d[45]), "=f"(d[46]), "=f"(d[47]), "=f"(d[48]), "=f"(d[49]), "=f"(d[50]), "=f"(d[51]), "=f"(d[52]), "=f"(d[53]), "=f"(d[54]), "=f"(d[55]), "=f"(d[56]), "=f"(d[57]), "=f"(d[58]), "=f"(d[59]), "=f"(d[60]), "=f"(d[61]), "=f"(d[62]), "=f"(d[63]), "=f"(d[64]), "=f"(d[65]), "=f"(d[66]), "=f"(d[67]), "=f"(d[68]), "=f"(d[69]), "=f"(d[70]), "=f"(d[71]), "=f"(d[72]), "=f"(d[73]), "=f"(d[74]), "=f"(d[75]), "=f"(d[76]), "=f"(d[77]), "=f"(d[78]), "=f"(d[79]), "=f"(d[80]), "=f"(d[81]), "=f"(d[82]), "=f"(d[83]), "=f"(d[84]), "=f"(d[85]), "=f"(d[86]), "=f"(d[87]), "=f"(d[88]), "=f"(d[89]), "=f"(d[90]), "=f"(d[91]), "=f"(d[92]), "=f"(d[93]), "=f"(d[94]), "=f"(d[95]), "=f"(d[96]), "=f"(d[97]), "=f"(d[98]), "=f"(d[99]), "=f"(d[100]), "=f"(d[101]), "=f"(d[102]), "=f"(d[103]), "=f"(d[104]), "=f"(d[105]), "=f"(d[106]), "=f"(d[107]), "=f"(d[108]), "=f"(d[109]), "=f"(d[110]), "=f"(d[111]), "=f"(d[112]), "=f"(d[113]), "=f"(d[114]), "=f"(d[115]), "=f"(d[116]), "=f"(d[117]), "=f"(d[118]), "=f"(d[119]), "=f"(d[120]), "=f"(d[121]), "=f"(d[122]), "=f"(d[123]), "=f"(d[124]), "=f"(d[125]), "=f"(d[126]), "=f"(d[127])
      : "l"(da), "l"(db));
  }
}
__device__ __forceinline__ void wgmma_n256_ssp_ta0_tb1(float* d, uint64_t da, uint64_t db, int accumulate) {
    asm volatile("{\n.reg .pred p;\nsetp.ne.b32 p, %130, 0;\n"
      "wgmma.mma_async.sync.aligned.m64n256k16.f32.bf16.bf16 "
      "{%0, %1, %2, %3, %4, %5, %6, %7, %8, %9, %10, %11, %12, %13, %14, %15, %16, %17, %18, %19, %20, %21, %22, %23, %24, %25, %26, %27, %28, %29, %30, %31, %32, %33, %34, %35, %36, %37, %38, %39, %40, %41, %42, %43, %44, %45, %46, %47, %48, %49, %50, %51, %52, %53, %54, %55, %56, %57, %58, %59, %60, %61, %62, %63, %64, %65, %66, %67, %68, %69, %70, %71, %72, %73, %74, %75, %76, %77, %78, %79, %80, %81, %82, %83, %84, %85, %86, %87, %88, %89, %90, %91, %92, %93, %94, %95, %96, %97, %98, %99, %100, %101, %102, %103, %104, %105, %106, %107, %108, %109, %110, %111, %112, %113, %114, %115, %116, %117, %118, %119, %120, %121, %122, %123, %124, %125, %126, %127}, "
      "%128, %129, p, 1, 1, 0, 1;\n}\n"
      : "+f"(d[0]), "+f"(d[1]), "+f"(d[2]), "+f"(d[3]), "+f"(d[4]), "+f"(d[5]), "+f"(d[6]), "+f"(d[7]), "+f"(d[8]), "+f"(d[9]), "+f"(d[10]), "+f"(d[11]), "+f"(d[12]), "+f"(d[13]), "+f"(d[14]), "+f"(d[15]), "+f"(d[16]), "+f"(d[17]), "+f"(d[18]), "+f"(d[19]), "+f"(d[20]), "+f"(d[21]), "+f"(d[22]), "+f"(d[23]), "+f"(d[24]), "+f"(d[25]), "+f"(d[26]), "+f"(d[27]), "+f"(d[28]), "+f"(d[29]), "+f"(d[30]), "+f"(d[31]), "+f"(d[32]), "+f"(d[33]), "+f"(d[34]), "+f"(d[35]), "+f"(d[36]), "+f"(d[37]), "+f"(d[38]), "+f"(d[39]), "+f"(d[40]), "+f"(d[41]), "+f"(d[42]), "+f"(d[43]), "+f"(d[44]), "+f"(d[45]), "+f"(d[46]), "+f"(d[47]), "+f"(d[48]), "+f"(d[49]), "+f"(d[50]), "+f"(d[51]), "+f"(d[52]), "+f"(d[53]), "+f"(d[54]), "+f"(d[55]), "+f"(d[56]), "+f"(d[57]), "+f"(d[58]), "+f"(d[59]), "+f"(d[60]), "+f"(d[61]), "+f"(d[62]), "+f"(d[63]), "+f"(d[64]), "+f"(d[65]), "+f"(d[66]), "+f"(d[67]), "+f"(d[68]), "+f"(d[69]), "+f"(d[70]), "+f"(d[71]), "+f"(d[72]), "+f"(d[73]), "+f"(d[74]), "+f"(d[75]), "+f"(d[76]), "+f"(d[77]), "+f"(d[78]), "+f"(d[79]), "+f"(d[80]), "+f"(d[81]), "+f"(d[82]), "+f"(d[83]), "+f"(d[84]), "+f"(d[85]), "+f"(d[86]), "+f"(d[87]), "+f"(d[88]), "+f"(d[89]), "+f"(d[90]), "+f"(d[91]), "+f"(d[92]), "+f"(d[93]), "+f"(d[94]), "+f"(d[95]), "+f"(d[96]), "+f"(d[97]), "+f"(d[98]), "+f"(d[99]), "+f"(d[100]), "+f"(d[101]), "+f"(d[102]), "+f"(d[103]), "+f"(d[104]), "+f"(d[105]), "+f"(d[106]), "+f"(d[107]), "+f"(d[108]), "+f"(d[109]), "+f"(d[110]), "+f"(d[111]), "+f"(d[112]), "+f"(d[113]), "+f"(d[114]), "+f"(d[115]), "+f"(d[116]), "+f"(d[117]), "+f"(d[118]), "+f"(d[119]), "+f"(d[120]), "+f"(d[121]), "+f"(d[122]), "+f"(d[123]), "+f"(d[124]), "+f"(d[125]), "+f"(d[126]), "+f"(d[127])
      : "l"(da), "l"(db), "r"(accumulate));
}

template <int N> __device__ __forceinline__ void quad_sum(float* m) {
#pragma unroll
  for (int o = 1; o <= 2; o <<= 1) {
    float t[N];
#pragma unroll
    for (int i = 0; i < N; i++) t[i] = __shfl_xor_sync(~0u, m[i], o);
#pragma unroll
    for (int i = 0; i < N; i++) m[i] += t[i];
  }
}
__device__ __forceinline__ bool softmax_unsafe(const uint32_t* t, float l0, float l1) {
  const float m0 = fmaxf(bf_lo(t[0]) + bf_hi(t[0]), bf_lo(t[2]) + bf_hi(t[2])), m1 = fmaxf(bf_lo(t[1]) + bf_hi(t[1]), bf_lo(t[3]) + bf_hi(t[3]));
  return __any_sync(~0u, !(m0 * l0 < 2500.f) | !(m1 * l1 < 2500.f));
}
__device__ __forceinline__ void softmax_shift(float* p, float c0, float c1) {
#pragma unroll 1
  for (int it = 0; it < 8; it++) {
    float mx = p[0], mn = p[0];
#pragma unroll
    for (int j = 1; j < 8; j++) { mx = fmaxf(mx, p[(j >> 1) * 4 + (j & 1)]); mn = fminf(mn, p[(j >> 1) * 4 + (j & 1)]); }
#pragma unroll
    for (int o = 1; o <= 2; o <<= 1) { mx = fmaxf(mx, __shfl_xor_sync(~0u, mx, o)); mn = fminf(mn, __shfl_xor_sync(~0u, mn, o)); }
    const float half = fminf(0.5f * (mx - mn), 50.f * rcp(it & 1 ? c1 : c0));
    float r[8];
#pragma unroll
    for (int j = 0; j < 8; j++) {
      const float v = p[(j >> 1) * 4 + (j & 1)];
      r[j] = fmaxf(v - mx + half, 0.f) + fminf(v - mn - half, 0.f) + (v - v);
    }
#pragma unroll
    for (int k = 0; k < 7; k++)
#pragma unroll
      for (int j = 0; j < 8; j++) p[(k >> 1) * 16 + (k & 1) * 2 + (j >> 1) * 4 + (j & 1)] = p[((k + 1) >> 1) * 16 + ((k + 1) & 1) * 2 + (j >> 1) * 4 + (j & 1)];
#pragma unroll
    for (int j = 0; j < 8; j++) p[50 + (j >> 1) * 4 + (j & 1)] = r[j];
  }
}
template <int J0 = 0, int J1 = 8> __device__ __forceinline__ void k_exp(const float* p, float c0, float c1, float* e, float* s) {
#pragma unroll
  for (int j = J0; j < J1; j++) {
    e[2 * j] = ex2(p[2 * j] * (j & 1 ? c1 : c0));
    e[2 * j + 1] = ex2(p[2 * j + 1] * (j & 1 ? c1 : c0));
    e[16 + j] = rcp(e[2 * j] * e[2 * j + 1]);
    const float t = e[2 * j] + e[2 * j + 1];
    s[j & 1] = j < 2 ? t : s[j & 1] + t;
    s[2 + (j & 1)] = j < 2 ? e[16 + j] * t : fmaf(e[16 + j], t, s[2 + (j & 1)]);
  }
}
template <int J0 = 0, int J1 = 8> __device__ __forceinline__ void q_exp(const float* p, float c0, float c1, uint32_t* f) {
#pragma unroll
  for (int j = J0; j < J1; j++) {
    const float e0 = ex2(p[2 * j] * (j & 1 ? c1 : c0)), e1 = ex2(p[2 * j + 1] * (j & 1 ? c1 : c0)), r = rcp(e0 * e1);
    f[j] = pack2(e0, e1);
    f[8 + j] = bmul2(f[j], pack2(r, r));
  }
}

#define FMA8(A, U, X)                                                                                        \
  A[0] = fmaf(bf_lo(U.x), X, A[0]); A[1] = fmaf(bf_hi(U.x), X, A[1]); A[2] = fmaf(bf_lo(U.y), X, A[2]); A[3] = fmaf(bf_hi(U.y), X, A[3]); \
  A[4] = fmaf(bf_lo(U.z), X, A[4]); A[5] = fmaf(bf_hi(U.z), X, A[5]); A[6] = fmaf(bf_lo(U.w), X, A[6]); A[7] = fmaf(bf_hi(U.w), X, A[7])

__device__ __forceinline__ uint32_t routed_row(const __nv_bfloat16* x, uint32_t tag, int lane, uint4* xr) {
  uint32_t best = 0, sv = 0;
#pragma unroll 1
  for (int it = 0; it < SPIN_MAX; it++) {
    const int sel = 2047 - (best & 0x7ff);
#pragma unroll
    for (int i = 0; i < 4; i++) xr[i] = ldg_nc(x + (size_t)sel * DM + i * 256 + lane * 8);
    const unsigned long long st = ld_rlx64(g_stat + sel);
    const uint4 b0 = ld_rlx128(g_best + lane * 2), b1 = ld_rlx128(g_best + 64 + lane * 2);
    const uint32_t m = __reduce_max_sync(~0u, max(max(b0.y == tag ? b0.x : 0u, b0.w == tag ? b0.z : 0u), max(b1.y == tag ? b1.x : 0u, b1.w == tag ? b1.z : 0u)));
    sv = (uint32_t)st;
    if (__all_sync(~0u, b0.y == tag && b0.w == tag && b1.y == tag && b1.w == tag && m == best && (uint32_t)(st >> 32) == tag)) break;
    best = m;
    if (AM_NS) __nanosleep(AM_NS);
  }
  const uint32_t m2 = (sv & 0xffff0000u) | (sv >> 16);
  const float rs = rcp(bf_lo(sv));
#pragma unroll
  for (int i = 0; i < 4; i++) {
    const uint32_t d0 = bsub2(xr[i].x, m2), d1 = bsub2(xr[i].y, m2), d2 = bsub2(xr[i].z, m2), d3 = bsub2(xr[i].w, m2);
    xr[i] = make_uint4(pack2(bf_lo(d0) * rs, bf_hi(d0) * rs), pack2(bf_lo(d1) * rs, bf_hi(d1) * rs), pack2(bf_lo(d2) * rs, bf_hi(d2) * rs),
                       pack2(bf_lo(d3) * rs, bf_hi(d3) * rs));
  }
  return best;
}

struct Params {
  const __nv_bfloat16 *x, *wqkv, *wo, *w_r, *w_down;
  uint32_t zA, zB;
};

template <bool BY_SMID> __global__ void __launch_bounds__(384, 1)
fused_kernel(const Params P, const __grid_constant__ CUtensorMap mX, const __grid_constant__ CUtensorMap mWkv, const __grid_constant__ CUtensorMap mWq,
             const __grid_constant__ CUtensorMap mWo, const __grid_constant__ CUtensorMap mPhi, const __grid_constant__ CUtensorMap mWp,
             const __grid_constant__ CUtensorMap mOut, const __grid_constant__ CUtensorMap mWc,
             const __grid_constant__ CUtensorMap mG, const __grid_constant__ CUtensorMap mU, const __grid_constant__ CUtensorMap mD,
             const __grid_constant__ CUtensorMap mXs, const __grid_constant__ CUtensorMap mG2, const __grid_constant__ CUtensorMap mU2) {
  constexpr uint32_t sb = SB, bar = SB + SM_BAR;
  int bid = blockIdx.x;
  if (BY_SMID) {
    uint32_t sm;
    asm volatile("mov.u32 %0, %%smid;" : "=r"(sm));
    const uint32_t tq = (sm - 64) >> 1, q7 = (tq * 37) >> 8;
    const uint32_t gpc = sm < 64 ? (sm >> 1) & 7 : 1 + tq - 7 * q7, idx = (sm < 64 ? sm >> 4 : 4 + q7) * 2 + (sm & 1);
    bid = sm < 120 ? ((PTAB >> (4 * gpc)) & 7) * 16 + idx : sm < 124 ? sm + 8 : sm - 116;
  }
  const int hg = ((bid >> 2) & 3) + 4 * ((bid >> 4) & 1), mb = (bid & 3) + 4 * ((bid >> 5) & 3);
  if (bid < NCTA && threadIdx.x < 256) {
    const uint32_t r0 = threadIdx.x >> 3, c = threadIdx.x & 7, dst = sb + 2 * KV_STAGE + r0 * 128 + ((c ^ (r0 & 7)) << 4);
    const char* xs = (const char*)P.x + (size_t)(mb * 128 + r0) * 2048 + c * 16;
    const char* ws = (const char*)P.wqkv + (size_t)r0 * 6144 + 2048 + hg * 256 + c * 16;
#pragma unroll
    for (int i = 0; i < 4; i++) cp_async16(dst + i * 4096, xs + i * 65536);
#pragma unroll
    for (int i = 0; i < 8; i++) cp_async16(dst + 16384 + i * 4096, ws + (i & 1) * 196608 + (i >> 2) * 2048 + ((i >> 1) & 1) * 128);
  }
  extern __shared__ __align__(1024) uint8_t smem[];
  if (smem_u32(smem) != SB) __trap();
  const int warp = __shfl_sync(~0u, threadIdx.x >> 5, 0);

  if (bid >= NCTA) {
    constexpr uint32_t XV = SM_WPHI, ONES = SM_ZT, BF = bar, BE = bar + 48, BX = bar + 96;
    constexpr int NJ = (DM - GROWS) / 64;
    const int lane = lane_id(), sp = bid - NCTA;
    const uint32_t tag = ld_rlx(g_epoch + bid * 32 + lane) + 1;
    if (warp == 8 && elect_one()) {
#pragma unroll 1
      for (int i = 0; i < 13; i++) mbar_init(bar + 8 * i, i >= 6 && i < 12 ? 8 : 1);
    }
    if (warp == 9) { sts64u(sb + ONES + lane * 8, 0x3f803f80u, 0x3f803f80u); fence_async_smem(); }
    __syncthreads();
    if (warp == 8) {
      if (elect_one()) {
        uint32_t s = 0, ph = 1;
        for (const long long c0 = clock64(); clock64() - c0 < SP_DELAY;) {}
#pragma unroll 1
        for (int job = 0; job < 8; job++) {
          const CUtensorMap* m = job == 0 ? &mWq : sp & 2 ? &mU2 : &mG2;
          const int g0 = job ? (sp & 1) * 28 + job * 4 - 4 : sp * 4;
#pragma unroll 1
          for (int row = job ? GROWS : 0; row < DM; row += 64) {
            mbar_wait(BE + 8 * s, ph);
            mbar_expect_tx(BF + 8 * s, Q_STAGE);
            tma4d(sb + s * Q_STAGE, m, 0, row, g0, 0, BF + 8 * s);
            tma4d(sb + s * Q_STAGE + 16384, m, 0, row, g0 + 2, 0, BF + 8 * s);
            if (++s == 6) { s = 0; ph ^= 1; }
          }
        }
      }
    } else if (warp == 9) {
      uint4 xr[4];
      routed_row(P.x, tag, lane, xr);
#pragma unroll
      for (int i = 0; i < 4; i++) sts128u(sb + XV + i * 512 + lane * 16, xr[i].x, xr[i].y, xr[i].z, xr[i].w);
      fence_async_smem();
      __syncwarp();
      if (lane == 0) mbar_arrive(BX);
    } else if (warp < 8) {
      uint32_t s = 0, ph = 0;
#pragma unroll 1
      for (int job = 0; job < 8; job++) {
        float d[8] = {0.f, 0.f, 0.f, 0.f, 0.f, 0.f, 0.f, 0.f};
        if (job == 1) mbar_wait(BX, 0);
#pragma unroll 1
        for (int i = 0; i < (job ? NJ : 16); i++) {
          mbar_wait(BF + 8 * s, ph);
          wg_fence();
#pragma unroll
          for (int k = 0; k < 8; k++)
            wgmma_n8_ss_ta1_tb0(d + 4 * (k >> 2), mkdesc(sb + k * 2048, 16, 1024, 1, s * (Q_STAGE / 16) + (warp >> 2) * 1024),
                                mkdesc(sb, 16, 128, 0, job ? (XV + GROWS * 2) / 16 + i * 8 + (k & 3) * 2 : ONES / 16), 1);
          wg_commit();
          wg_wait<0>();
          if (lane == 0) mbar_arrive(BE + 8 * s);
          if (++s == 6) { s = 0; ph ^= 1; }
        }
        reg_fence<8>(d);
        float* dst = (job ? g_gp + sp * 1792 + job * 256 - 256 : g_cs + sp * 256) + (warp >> 2) * 128 + (warp & 3) * 16 + (lane >> 2);
        if ((lane & 3) == 0) {
#pragma unroll
          for (int i = 0; i < 4; i++) st_rlx(dst + (i >> 1) * 64 + (i & 1) * 8, mark(__float_as_uint(d[2 * i]), tag & 1));
        }
        __syncwarp();
      }
      if (warp == 0) g_epoch[bid * 32 + lane] = tag;
    }
    return;
  }
#define Q_SLAB(J) ((J) < 8 ? ((J) + 8 - 2 * (hg & 4)) & 15 : 2 * (hg & 4) + 2 * ((J) & 3) + ((J) >> 2 & 1))
#define Q_AOFF(J) ((J) == 8 + (hg & 3) ? SM_X0 : (J) == 12 + (hg & 3) ? SM_X1 : ((J) & 3) * Q_STAGE)
#define Q_LOAD(J)                                                                                            \
  do {                                                                                                       \
    const uint32_t fb_ = bar + B_FULLQ + 8 * ((J) & 3);                                                      \
    const int k_ = Q_SLAB(J) * 64;                                                                           \
    mbar_expect_tx(fb_, Q_STAGE);                                                                            \
    mbar_arrive2(fb_);                                                                                       \
    tma2d(sb + Q_AOFF(J), &mX, k_, mb * 128, fb_);                                                           \
    tma4d(sb + ((J) & 3) * Q_STAGE + 16384, &mWq, 0, k_, hg * 2, 0, fb_);                                    \
  } while (0)
  if (warp >= 8) {
    asm volatile("setmaxnreg.dec.sync.aligned.u32 %0;" ::"n"(REG_H));
    const int lane = lane_id();
    const int f = (warp - 9) & 3;
    if (f == 3) {
      if (elect_one()) {
        PROF(0); PROFT(32);
#pragma unroll
        for (int s = 0; s < 3; s++) mbar_init(bar + B_FULLKV + 8 * s, 1);
      }
      __syncwarp();
      asm volatile("bar.arrive 14, 288;" ::: "memory");
      if (elect_one()) {
#pragma unroll
        for (int s = 0; s < 2; s++) {
          mbar_expect_tx(bar + B_FULLKV + 8 * s, KV_STAGE);
          tma2d(sb + s * KV_STAGE, &mX, (s + 1) * 64, mb * 128, bar + B_FULLKV + 8 * s);
          tma4d(sb + s * KV_STAGE + 16384, &mWkv, 0, (s + 1) * 64, hg * 2, 1, bar + B_FULLKV + 8 * s);
        }
      }
      __syncwarp();
    }
    const uint32_t ep = ld_rlx(g_epoch + bid * 32 + lane);
    if (f < 2) {
#pragma unroll
      for (int i = 0; i < 2; i++) {
        const uint4 u = __ldg((const uint4*)P.w_r + (f * 2 + i) * 32 + lane);
        sts128u(sb + SM_XSEL + (f * 2 + i) * 512 + lane * 16, u.x, u.y, u.z, u.w);
      }
    }
    bar_sync(13, 384);
    const uint32_t tag = ep + 1, par = tag & 1;
    const bool ffn = bid < NFFN;
    const int fb = bid, cu = bid >> 1, ch = bid & 1;
#define CS_STORE(SEC, C)                                                                                     \
  _Pragma("unroll") for (int r = 0; r < 3; r++) {                                                            \
    const uint32_t h0 = pack2(C.x, C.y), h1 = pack2(C.z, C.w);                                               \
    sts64u(sb + SM_CST + (SEC) * 1024 + (lane >> 4) * 512 + (lane & 1) * 8 + r * 128 + ((((lane & 15) >> 1) ^ (r + (lane >> 4) * 4)) << 4), h0, h1); \
    C.x -= bf_lo(h0); C.y -= bf_hi(h0); C.z -= bf_lo(h1); C.w -= bf_hi(h1);                                  \
  }
#define BAD4(U) ((U.x ^ par) | (U.y ^ par) | (U.z ^ par) | (U.w ^ par))
    const int n0 = f < 2 ? 0 : 2 * f - 3, ne = FFN_OFF || !ffn ? 3 : f == 3 ? 3 + G8 : 3 + GN;
    const uint32_t fsb = sb + SM_FST + ((f + 1) & 3) * 8192, fbar = bar + B_FST + f * 16, fst = fsb + (lane >> 4) * 2048 + (lane & 15) * 16;
    const CUtensorMap *ma = &mWc, *mc = &mWc;
    int sx = 1024 + cu * 32, sy = ch * 512 + f * 192, sdy = 32;
#define STAGEG(N)                                                                                            \
  do {                                                                                                       \
    if ((N) == 3) { ma = &mG; mc = &mU; sx = fb * 32; sy = f * (GN * 32);  sdy = 0; }                        \
    if ((N) < ne && elect_one()) {                                                                           \
      const uint32_t dst_ = fsb + ((N) & 1) * 4096, b_ = fbar + ((N) & 1) * 8;                               \
      mbar_expect_tx(b_, 4096);                                                                              \
      tma2d(dst_, ma, sx, sy, b_);                                                                           \
      tma2d(dst_ + 2048, mc, sx, sy + sdy, b_);                                                              \
    }                                                                                                        \
    sy += 32 + sdy;                                                                                          \
  } while (0)
    float a[8], gsum = 0.f, usum = 0.f;
    {
      if (f == 3) {
        if (elect_one()) {
          mbar_expect_tx(bar + B_XST, 16384);
          tma3d(sb + SM_XST, &mXs, 0, bid * 16, 0, bar + B_XST);
          mbar_expect_tx(bar + B_WPHI, 8192);
          tma2d(sb + SM_WPHI, &mPhi, 0, hg * 128, bar + B_WPHI);
          prefetch_map(&mWq); prefetch_map(&mWo); prefetch_map(&mWp); prefetch_map(&mD);
          PROF(31);
        }
        __syncwarp();
      } else {
        if (lane == 0) prefetch_map(f == 0 ? &mWc : f == 1 ? &mG : &mU);
        if (f == 2) ((float2*)g_y[par])[bid * 32 + lane] = make_float2(0.f, 0.f);
      }
      float st[13];
#pragma unroll
      for (int i = 0; i < 13; i++) st[i] = 0.f;
#pragma unroll 1
      for (int i = 0; i < 4; i++) {
        mbar_wait(bar + B_XST + 8 * (i >> 1), 0);
        if (f == 0 && lane == 0 && i == 0) PROF(1);
        const uint4 wu = lds128u(sb + SM_XSEL + i * 512 + lane * 16);
        const float wf[8] = {bf_lo(wu.x), bf_hi(wu.x), bf_lo(wu.y), bf_hi(wu.y), bf_lo(wu.z), bf_hi(wu.z), bf_lo(wu.w), bf_hi(wu.w)};
        st[12] += ((wf[0] + wf[1]) + (wf[2] + wf[3])) + ((wf[4] + wf[5]) + (wf[6] + wf[7]));
#pragma unroll
        for (int r = 0; r < 4; r++) {
          const uint4 u = lds128u(sb + SM_XST + i * 8192 + (4 * f + r) * 512 + lane * 16);
          const float xf[8] = {bf_lo(u.x), bf_hi(u.x), bf_lo(u.y), bf_hi(u.y), bf_lo(u.z), bf_hi(u.z), bf_lo(u.w), bf_hi(u.w)};
#pragma unroll
          for (int k = 0; k < 8; k++) { st[r] += xf[k]; st[4 + r] = fmaf(xf[k], xf[k], st[4 + r]); st[8 + r] = fmaf(xf[k], wf[k], st[8 + r]); }
        }
        if (i >= 2 && f < 3) STAGEG(n0 + i - 2);
      }
      const bool up = lane & 16, up2 = lane & 8;
#pragma unroll
      for (int q = 0; q < 3; q++) {
        const float k0 = up ? st[4 * q + 2] : st[4 * q], k1 = up ? st[4 * q + 3] : st[4 * q + 1];
        const float o0 = up ? st[4 * q] : st[4 * q + 2], o1 = up ? st[4 * q + 1] : st[4 * q + 3];
        const float m0 = k0 + __shfl_xor_sync(~0u, o0, 16), m1 = k1 + __shfl_xor_sync(~0u, o1, 16);
        a[q] = (up2 ? m1 : m0) + __shfl_xor_sync(~0u, up2 ? m0 : m1, 8);
      }
      a[3] = st[12] + __shfl_xor_sync(~0u, st[12], 16);
      a[3] += __shfl_xor_sync(~0u, a[3], 8);
#pragma unroll
      for (int o = 4; o; o >>= 1)
#pragma unroll
        for (int q = 0; q < 4; q++) a[q] += __shfl_xor_sync(~0u, a[q], o);
      if ((lane & 7) == 0) sts128(sb + SM_ROWS + (4 * f + (lane >> 3)) * 16, a[0], a[1], a[2], a[3]);
      if (f < 3) asm volatile("bar.arrive 7, 128;" ::: "memory");
    }
    if (f == 3) {
      bar_sync(7, 128);
      const int row = bid * 16 + (lane & 15);
      const float4 v = lds128(sb + SM_ROWS + (lane & 15) * 16);
      const float mf = v.x * (1.f / DM), mean = bf_round(mf), var = fmaxf(fmaf(-mf, mf, v.y * (1.f / DM)), 0.f);
      const float sd = bf_round(sqrt_approx(bf_round(bf_round(var) + 1e-5f)));
      const uint32_t rb = pack2(fmaf(-mean, v.w, v.z) * rcp(sd), 0.f) & 0xffffu, ord = (rb & 0x8000u) ? (~rb & 0xffffu) : (rb | 0x8000u);
      uint32_t best = __reduce_max_sync(~0u, (ord << 16) | (uint32_t)(2047 - row));
      if (lane < 16) st_rlx64(g_stat + row, ((unsigned long long)tag << 32) | __float_as_uint(mean) | (__float_as_uint(sd) >> 16));
      if (lane == 0) { asm volatile("red.relaxed.gpu.global.max.u64 [%0], %1;" ::"l"(g_best + bid), "l"(((unsigned long long)tag << 32) | best) : "memory"); PROF(17); }
#pragma unroll 1
      for (int n = 3; n < 5; n++) STAGEG(n);
      {
        uint4 xr[4];
        best = routed_row(P.x, tag, lane, xr);
#pragma unroll
        for (int i = 0; i < (GROWS + 255) / 256; i++) {
          const uint32_t dst = sb + SM_XSEL + i * 1024 + (lane >> 2) * 128 + (lane & 3) * 8;
          sts64(dst, bf_lo(xr[i].x), bf_lo(xr[i].z)); sts64(dst + 32, bf_hi(xr[i].x), bf_hi(xr[i].z));
          sts64(dst + 64, bf_lo(xr[i].y), bf_lo(xr[i].w)); sts64(dst + 96, bf_hi(xr[i].y), bf_hi(xr[i].w));
        }
        sts64u(sb + SM_RED + 16, tag, best);
        __syncwarp();
        if (lane == 0) { mbar_arrive(bar + B_XS); PROF(19); }
      }
      unsigned long long sv4[4];
      uint4 u[4];
#pragma unroll 1
      for (int it = 0; it < SPIN_MAX; it++) {
#pragma unroll
        for (int i = 0; i < 4; i++) { u[i] = ld_rlx128(g_cs + (1 + i) * 1024 + hg * 128 + lane * 4); sv4[i] = ld_rlx64(g_stat + mb * 128 + i * 32 + lane); }
        bool ok = ((BAD4(u[0]) | BAD4(u[1]) | BAD4(u[2]) | BAD4(u[3])) & 1) == 0;
#pragma unroll
        for (int i = 0; i < 4; i++) ok = ok && (uint32_t)(sv4[i] >> 32) == tag;
        if (__all_sync(~0u, ok)) break;
        __nanosleep(200);
      }
#pragma unroll
      for (int i = 0; i < 4; i++) {
        const uint32_t sv = (uint32_t)sv4[i], sd2 = (sv << 16) | (sv & 0xffffu);
        sts64(sb + SM_STAT + (i * 32 + lane) * 8, -bf_hi(sv), rcp(bf_lo(sv)));
        sts128u(sb + SM_SDT + lane * 64 + ((i ^ ((lane >> 1) & 3)) << 4), sd2, sd2, sd2, sd2);
      }
#pragma unroll
      for (int i = 0; i < 2; i++) {
        float4 c = make_float4(unmark(u[i].x) + unmark(u[i + 2].x), unmark(u[i].y) + unmark(u[i + 2].y), unmark(u[i].z) + unmark(u[i + 2].z),
                               unmark(u[i].w) + unmark(u[i + 2].w));
        CS_STORE(i, c);
      }
      fence_async_smem();
      bar_sync(8, 64);
      if (lane == 0) { mbar_arrive(bar + B_CS); PROF(10); }
    }
    {
      uint32_t xa = sb + SM_RED + 32, xstep = 0;
      const uint32_t zero = __float_as_uint(lds32(sb + SM_RED + 12));
#pragma unroll 1
      for (int ph = f == 3; ph < 2; ph++) {
#pragma unroll
        for (int j = 0; j < 8; j++) a[j] = 0.f;
        if (ph && f == 0) {
        {
          mbar_wait(bar + B_WPHI, 0);
          float nq[8] = {0.f, 0.f, 0.f, 0.f, 0.f, 0.f, 0.f, 0.f};
  #pragma unroll 2
          for (int r = 0; r < 16; r++) {
            const uint4 u = lds128u(sb + SM_WPHI + ((lane >> 2) * 16 + r) * 64 + (((lane ^ (r >> 1)) & 3) << 4));
            nq[0] = fmaf(bf_lo(u.x), bf_lo(u.x), nq[0]); nq[1] = fmaf(bf_hi(u.x), bf_hi(u.x), nq[1]); nq[2] = fmaf(bf_lo(u.y), bf_lo(u.y), nq[2]);
            nq[3] = fmaf(bf_hi(u.y), bf_hi(u.y), nq[3]); nq[4] = fmaf(bf_lo(u.z), bf_lo(u.z), nq[4]); nq[5] = fmaf(bf_hi(u.z), bf_hi(u.z), nq[5]);
            nq[6] = fmaf(bf_lo(u.w), bf_lo(u.w), nq[6]); nq[7] = fmaf(bf_hi(u.w), bf_hi(u.w), nq[7]);
          }
          uint32_t m = 0;
  #pragma unroll
          for (int i = 0; i < 8; i++) m = max(m, __float_as_uint(nq[i] + __shfl_xor_sync(~0u, nq[i], 4)) & 0x7fffffffu);
          sts32(sb + SM_RED + 24, 4.2f * __uint_as_float(__reduce_max_sync(~0u, m)));
        }
          asm volatile("bar.arrive 8, 64;" ::: "memory");
        }
        if (ph) { mbar_wait(bar + B_XS, 0); xa = sb + SM_XSEL + f * (GN * 128) + ((lane >> 2) & 3) * 32; xstep = 128; }
#pragma unroll 1
        for (int n = ph ? 3 : n0; n < (ph ? ne : 3); n++) {
          const float4 x0 = lds128(xa), x1 = lds128(xa + 16);
          xa += xstep;
          mbar_wait(fbar + (n & 1) * 8, ((n - n0) >> 1) & 1);
          uint4 u[8];
#pragma unroll
          for (int j = 0; j < 8; j++) u[j] = lds128u(fst + (n & 1) * 4096 + j * 256);
          FMA8(a, u[0], x0.x); FMA8(a, u[1], x0.y); FMA8(a, u[2], x0.z); FMA8(a, u[3], x0.w);
          if (__any_sync(~0u, ((u[4].x | u[5].x | u[6].x | u[7].x | __float_as_uint(a[0]) | __float_as_uint(a[7])) & zero) == 0)) STAGEG(n + 2);
          FMA8(a, u[4], x1.x); FMA8(a, u[5], x1.y); FMA8(a, u[6], x1.z); FMA8(a, u[7], x1.w);
        }
#pragma unroll
        for (int o = 4; o <= 8; o <<= 1)
#pragma unroll
          for (int j = 0; j < 8; j++) a[j] += __shfl_xor_sync(~0u, a[j], o);
        if (ph && lane == 0) mbar_arrive(bar + B_FFN);
        const uint32_t red = ph ? sb + SM_GRED : sb + SM_RED + 64;
        if ((lane & 12) == 0) {
          const uint32_t d = red + f * 256 + (lane >> 4) * 128 + (lane & 3) * 32;
          sts128(d, a[0], a[1], a[2], a[3]); sts128(d + 16, a[4], a[5], a[6], a[7]);
        }
        if (f != 2) {
          asm volatile("bar.arrive %0, %1;" ::"r"(4 + ph), "r"(96 + 32 * ph) : "memory");
        } else {
          bar_sync(4 + ph, 96 + 32 * ph);
          const uint32_t ra = red + lane * 4;
          gsum = lds32(ra) + lds32(ra + 256) + lds32(ra + 512);
          usum = lds32(ra + 128) + lds32(ra + 384) + lds32(ra + 640);
          if (!ph) st_rlx(g_cs + 1024 + ch * 2048 + cu * 32 + lane, mark(__float_as_uint(gsum + usum), par));
          else { gsum += lds32(ra + 768); usum += lds32(ra + 896); }
          if (lane == 0) PROF(ph ? 34 : 18);
        }
      }
    }
    if (f == 3) {
      if (elect_one()) {
        PROF(7);
        mbar_wait(bar + B_FULLQ, 0);
#pragma unroll 1
        for (int j = 3; j < 16; j++) {
          mbar_wait(bar + (j < 4 ? B_EMPTYKV + 16 : B_EMPTYQ + 8 * (j & 3)), ((j >> 2) & 1) ^ 1);
          if (j == 12 + (hg & 3)) mbar_wait(bar + B_KVST + 8, 0);
          Q_LOAD(j);
        }
        PROF(47);
        mbar_expect_tx(bar + B_DN, 65536);
#pragma unroll 1
        for (int i = 0; i < 4; i++) {
          mbar_wait(bar + B_EMPTYQ + 8 * i, 1);
          tma3d(sb + i * Q_STAGE, &mD, 0, fb * 32, i * 4, bar + B_DN);
        }
        PROF(48);
#pragma unroll 1
        for (int i = 0; i < 16; i++) {
          const int s = i & 3, n = i < 9 ? i - 2 : i - 9, kb = i < 2 ? 2 * hg + i : 2 * (n + (n >= hg)) + (i >= 9);
          if (i >= 4) mbar_wait(bar + B_EMPTYQ + 8 * s, ((i >> 2) & 1) ^ 1);
          mbar_expect_tx(bar + B_FULLQ + 8 * s, 16384);
          if (i < 2) {
            mbar_arrive2(bar + B_FULLQ + 8 * s);
            tma3d(sb + s * Q_STAGE + 16384, &mWo, 0, kb * 64, hg * 2, bar + B_FULLQ + 8 * s);
          } else {
            tma5d(sb + s * Q_STAGE + 16384, &mWp, hg * 128, kb * 2, bar + B_FULLQ + 8 * s);
            tma5d(sb + s * Q_STAGE + 24576, &mWp, hg * 128 + 64, kb * 2, bar + B_FULLQ + 8 * s);
            if (i >= 3) {
              if (i == 3) { mbar_wait(bar + B_DND, 0); PROF(14); }
#pragma unroll 1
              for (int a = i == 3 ? 2 : i; a <= i; a++) {
                const uint4* src = g_ofr + (mb * 16 + (a == 2 ? (hg == 0 ? 2 : 0) : kb)) * 1024;
#pragma unroll
                for (int h = 0; h < 2; h++) {
                  mbar_expect_tx(bar + B_AIN + (a & 3) * 16 + h * 8, 8192);
                  bulk_load(sb + (a & 3) * Q_STAGE + h * 8192, src + h * 512, 8192, bar + B_AIN + (a & 3) * 16 + h * 8);
                }
              }
            }
          }
        }
      }
    } else {
      if (f == 2) {
        if (PFD && ffn) {
#pragma unroll 1
          for (int i = 0; i < 16; i++) { touch_l2((const char*)P.w_down + fb * 65536 + i * 4096 + lane * 128, lane); __nanosleep(PFD); }
        }
        {
#pragma unroll 1
          for (int i = 0; i < 8; i++) { touch_l2((const char*)P.wo + ((mb & 7) * 128 + i * 16 + (lane >> 1)) * 2048 + hg * 256 + (lane & 1) * 128, lane); __nanosleep(PFD); }
        }
        asm volatile("cp.async.wait_all;" ::: "memory");
        uint4 u;
#pragma unroll 1
        for (int it = 0; it < SPIN_MAX; it++) {
          u = ld_rlx128(g_cs + hg * 128 + lane * 4);
          if (__all_sync(~0u, !(BAD4(u) & 1))) break;
          __nanosleep(200);
        }
        mbar_wait(bar + B_PHI, 0);
        float4 c = make_float4(unmark(u.x), unmark(u.y), unmark(u.z), unmark(u.w));
        CS_STORE(2, c);
        fence_async_smem();
        __syncwarp();
        if (lane == 0) mbar_arrive(bar + B_CSQ);
      }
      const uint32_t target = __shfl_sync(~0u, tag, 0) * 16;
#pragma unroll 1
      for (int R = 0; R < 2; R++) {
        const uint32_t own = (hg * 2 + R) * 16 + mb, pst = sb + (R ? SM_PST1 : SM_PST0);
        if (f == R) {
          mbar_wait(bar + B_KVST + 8 * R, 0);
          if (f == 1 && lane == 0) PROF(11);
          wait_hint(XC1(hg, R) + mb, target);
          if (elect_one()) {
            PROF(35 + R);
            fence_async_global();
            mbar_expect_tx(bar + B_PART + 8 * R, 8192);
            bulk_load(pst, g_part + own * 512, 8192, bar + B_PART + 8 * R);
          }
          __syncwarp();
          uint4 uz;
#pragma unroll 1
          for (int it = 0; it < SPIN_MAX; it++) {
            uz = ld_rlx128(g_zpart + own * 128 + lane * 4);
            if (__all_sync(~0u, !(BAD4(uz) & 1))) break;
          }
          const bool b1 = lane & 2, b2 = lane & 4;
          const float z0 = unmark(b1 ? uz.z : uz.x) + __shfl_xor_sync(~0u, unmark(b1 ? uz.x : uz.z), 2);
          const float z1 = unmark(b1 ? uz.w : uz.y) + __shfl_xor_sync(~0u, unmark(b1 ? uz.y : uz.w), 2);
          float z = (b2 ? z1 : z0) + __shfl_xor_sync(~0u, b2 ? z0 : z1, 4);
          z += __shfl_xor_sync(~0u, z, 8);
          z += __shfl_xor_sync(~0u, z, 16);
          if (lane < 8) {
            const uint32_t ft = (own & 7) * 8 + (lane & 1) * 4 + (lane & 2) + (lane >> 2), zz = pack2(z, 1.f);
            const uint32_t pos = (own >> 3) * 64 + (ft & 15) * 4 + (((ft >> 4) ^ (ft >> 1)) & 3);
            st_rlx128(g_zres[par] + pos, zz, zz, zz, zz);
            g_zres[par ^ 1][pos] = make_uint4(0u, 0u, 0u, 0u);
          }
          if (lane == 0) red_inc(XC2(hg, R));
          __syncwarp();
        }
        if (f == R || f == R + 1) {
          const uint32_t hf = f - R, m1 = ~lane & 1, gq = hf * 4 + (lane >> 3), ts = (lane >> 1) & 3;
          float a0 = 0.f, a1 = 0.f, a2 = 0.f, a3 = 0.f;
          mbar_wait(bar + B_PART + 8 * R, 0);
#pragma unroll 1
          for (int it = 0; it < SPIN_MAX; it++) {
            uint32_t bad = 0;
            a0 = a1 = a2 = a3 = 0.f;
#pragma unroll 1
            for (int b = 0; b < 16; b += 8) {
              uint2 u[8];
              if (it == 0) {
#pragma unroll
                for (int i = 0; i < 8; i++) { const float2 v = lds64(pst + (b + i) * 512 + hf * 256 + lane * 8); u[i] = make_uint2(__float_as_uint(v.x), __float_as_uint(v.y)); }
              } else {
#pragma unroll
                for (int i = 0; i < 8; i++) {
                  const unsigned long long v = ld_rlx64((const unsigned long long*)g_part + own * 1024 + (b + i) * 64 + hf * 32 + lane);
                  u[i] = make_uint2((uint32_t)v, (uint32_t)(v >> 32));
                }
              }
#pragma unroll
              for (int i = 0; i < 8; i++) {
                bad |= u[i].x ^ par;
                a0 += bf_lo(i & 1 ? u[i].x & ~m1 : u[i].x | m1); a1 += bf_hi(u[i].x); a2 += bf_lo(u[i].y); a3 += bf_hi(u[i].y);
              }
            }
            if (__all_sync(~0u, !(bad & m1))) break;
          }
          uint32_t* dst = (uint32_t*)g_res[par] + own * 128 + gq * 16 + ts;
          const uint32_t j0 = (lane & 1) * 2, vb = ts == (gq >> 1);
          st_rlx(dst + ((j0 ^ (gq >> 1)) & 3) * 4, pack2(a0, a1) | vb);
          st_rlx(dst + (((j0 + 1) ^ (gq >> 1)) & 3) * 4, pack2(a2, a3) | vb);
          ((uint2*)g_res[par ^ 1])[own * 64 + hf * 32 + lane] = make_uint2(0u, 0u);
          __syncwarp();
          if (lane == 0) { red_inc(XC2(hg, R)); if (!hf) PROF(R ? 12 : 30); }
        }
      }
      if (f == 2) {
        if (ffn && !FFN_OFF) {
#pragma unroll 1
          for (int it = 0; it < SPIN_MAX; it++) {
            const uint32_t pg = ld_rlx((const uint32_t*)g_gp + fb * 32 + lane), pu = ld_rlx((const uint32_t*)g_gp + FF + fb * 32 + lane);
            if (__all_sync(~0u, !(((pg ^ par) | (pu ^ par)) & 1))) { gsum += unmark(pg); usum += unmark(pu); break; }
            __nanosleep(200);
          }
        }
        const float h = bf_round(silu_f(bf_round(gsum))) * bf_round(usum);
        const uint32_t h2 = pack2(h, h);
        sts128u(sb + SM_HT + lane * 16, h2, h2, h2, h2);
        fence_async_smem();
        __syncwarp();
        if (lane == 0) { mbar_arrive(bar + B_H); PROF(20); }
      }
      if (f < 2) {
        wait_hint(XC2(hg, f), 3 * target);
        mbar_wait(bar + B_KVST + 8, 0);
        if (lane == 0) PROF(40 + f);
#pragma unroll 1
        for (int it = 0; it < SPIN_MAX; it++) {
          if (elect_one()) {
            fence_async_global();
            mbar_expect_tx(bar + B_RES + 8 * f, 8192 + 2048);
            bulk_load(sb + SM_V + f * 8192, g_res[par] + (hg * 4 + f * 2) * 256, 8192, bar + B_RES + 8 * f);
            bulk_load(sb + SM_ZT + f * 2048, g_zres[par] + (hg * 4 + f * 2) * 64, 2048, bar + B_RES + 8 * f);
          }
          __syncwarp();
          mbar_wait(bar + B_RES + 8 * f, it & 1);
          uint32_t ok = ~0u;
#pragma unroll
          for (int i = 0; i < 16; i++) ok &= __float_as_uint(lds32(sb + SM_V + f * 8192 + i * 512 + lane * 16 + (lane >> 3) * 4));
#pragma unroll
          for (int i = 0; i < 4; i++) ok &= __float_as_uint(lds32(sb + SM_ZT + f * 2048 + i * 512 + lane * 16 + (lane >> 3) * 4)) >> 23;
          if (__all_sync(~0u, ok & 1)) break;
        }
        if (lane == 0) { mbar_arrive(bar + B_TILE + 8 * f); PROF(f ? 13 : 27); }
      }
      if (f < 2) {
        uint32_t phases = 0;
#pragma unroll 1
        for (int i = 2; i < 16; i++) {
          const int s = i & 3;
          const uint32_t ab = bar + B_AIN + s * 16 + f * 8, slot = sb + s * Q_STAGE + f * 8192;
#pragma unroll 1
          for (int it = 0; it < SPIN_MAX; it++) {
            mbar_wait(ab, (phases >> s) & 1);
            phases ^= 1u << s;
            uint32_t bad = 0;
#pragma unroll
            for (int n = 0; n < 8; n++) bad |= __float_as_uint(lds32(slot + n * 1024 + lane * 32 + (lane >> 2) * 4)) ^ par;
            if (__all_sync(~0u, !(bad & 1))) break;
            if (elect_one()) {
              const int n = i < 9 ? i - 2 : i - 9, kb = 2 * (n + (n >= hg)) + (i >= 9);
              PROF(49);
              mbar_expect_tx(ab, 8192);
              bulk_load(slot, g_ofr + (mb * 16 + kb) * 1024 + f * 512, 8192, ab);
            }
            __syncwarp();
          }
          if (lane == 0) { mbar_arrive(bar + B_FULLQ + 8 * s); if (i == 2 && f == 0) PROF(15); }
        }
        if (f == 0) g_epoch[bid * 32 + lane] = tag;
      } else {
        if (elect_one()) {
          prefetch_map(&mOut);
          if (ffn) { mbar_wait(bar + B_YD, 0); red_rel(g_ycnt); PROF(21); }
        }
        __syncwarp();
        if (f == 2) {
          const uint32_t best = __float_as_uint(lds32(sb + SM_RED + 20));
          const int sel = 2047 - (best & 0x7ff) - mb * 128;
          if (sel >= 0 && sel < 128) {
            const uint2 xr = __ldg((const uint2*)(P.x + (size_t)(mb * 128 + sel) * DM + hg * 128 + lane * 4));
            const float2 st = lds64(sb + SM_STAT + sel * 8);
            const uint32_t ord = best >> 16, rb = (ord & 0x8000u) ? (ord & 0x7fffu) : (~ord & 0xffffu);
            const float sg = rcp(1.f + ex2(-1.4426950408889634f * bf_lo(rb)));
            const uint32_t sg2 = pack2(sg, sg), nm2 = pack2(st.x, st.x);
            wait_cnt<0>(g_ycnt, tag * NFFN);
            float4 y = make_float4(0.f, 0.f, 0.f, 0.f);
#pragma unroll
            for (int i = 0; i < 8; i++) {
              const float4 c = ldg_cg4(g_y[par ^ 1][i] + hg * 128 + lane * 4);
              y.x += c.x; y.y += c.y; y.z += c.z; y.w += c.w;
            }
            uint32_t o[2];
#pragma unroll
            for (int i = 0; i < 2; i++) {
              const uint32_t d = badd2(i ? xr.y : xr.x, nm2);
              const uint32_t tt = badd2(pack2(bf_lo(d) * st.y, bf_hi(d) * st.y), bmul2(i ? pack2(y.z, y.w) : pack2(y.x, y.y), sg2));
              o[i] = pack2(silu_f(bf_lo(tt)), silu_f(bf_hi(tt)));
            }
            sts64u(sb + SM_UPD + lane * 8, o[0], o[1]);
          }
          if (lane == 0) sts32(sb + SM_UPD + 256, __int_as_float(sel));
          __syncwarp();
          if (lane == 0) { mbar_arrive(bar + B_UPD); PROF(22); }
        }
      }
    }
  } else {
    const int t7 = threadIdx.x & 127;
    const char* pfa = warp < 4 ? (const char*)P.x + bid * 32768 + (t7 & 15) * 2048 + (t7 >> 4) * 128
                               : (const char*)P.wqkv + (size_t)((t7 >> 4) * 64 + (bid >> 1)) * 6144 + 2048 + (bid & 1) * 2048 + (t7 & 15) * 128;
    if (t7 >= 16 && t7 < 16 * PF_FIRST) prefetch_l2(pfa);
    if (warp < 7) sts128(sb + SM_CST + threadIdx.x * 16, 0.f, 0.f, 0.f, 0.f);
    else sts32(sb + SM_RED + (threadIdx.x & 15) * 4, threadIdx.x & 8 ? 1.f : 0.f);
    if (elect_one()) {
#pragma unroll 1
      for (uint32_t b = B_FST + warp * 8; b < B_END; b += 64)
        mbar_init(bar + b, b < B_FULLQ ? 1 : b < B_FFN ? 3 : b < B_EMPTYKV ? 4 : 8);
    }
    __syncwarp();
    asm volatile("bar.arrive 13, 384;" ::: "memory");
    asm volatile("setmaxnreg.inc.sync.aligned.u32 %0;" ::"n"(REG_C));
    if (t7 >= 16 * PF_FIRST && threadIdx.x < 128 + 16 * PF_W) prefetch_l2(pfa);
    asm volatile("cp.async.wait_all;" ::: "memory");
    fence_async_smem();
    bar_sync(14, 288);
    if (threadIdx.x == 0) mbar_arrive(bar + B_FULLKV + 16);
    const int lane = lane_id();
    const int wg = warp >> 2, w = warp & 3, g = lane >> 2, t = lane & 3;
    float kv[128];
    {
      uint32_t s = 2, ph = 0, sp = 0, php = 0;
#pragma unroll 1
      for (int j = 0; j < 15; j++) {
        PW0(32 + j); mbar_wait(bar + B_FULLKV + 8 * s, ph); PW1(32 + j);
        if (wg == 1) bar_sync(10 + s, 256);
        wg_fence();
        const uint32_t hA = fresh_hi<H128>(P.zA), hB = fresh_hi<H128>(P.zB);
        wgmma_n256_ssp_ta0_tb1(kv, mkdesch(sb, 16, hA, wg * 512 + s * (KV_STAGE / 16)), mkdesch(sb + 16384, 8192, hB, s * (KV_STAGE / 16)), j);
#pragma unroll
        for (int k = 1; k < 4; k++)
          wgmma_n256_ss_ta0_tb1(kv, mkdesch(sb + k * 32, 16, hA, wg * 512 + s * (KV_STAGE / 16)),
                                mkdesch(sb + 16384 + k * 2048, 8192, hB, s * (KV_STAGE / 16)), 1);
        wg_commit();
        if (wg == 0) asm volatile("bar.arrive %0, 256;" ::"r"(10 + s) : "memory");
        if (warp == 0 && j) {
          mbar_wait(bar + B_EMPTYKV + 8 * sp, php);
          if (elect_one()) {
            if (j < 14) {
              mbar_expect_tx(bar + B_FULLKV + 8 * sp, KV_STAGE);
              tma2d(sb + sp * KV_STAGE, &mX, (j + 2) * 64, mb * 128, bar + B_FULLKV + 8 * sp);
              tma4d(sb + sp * KV_STAGE + 16384, &mWkv, 0, (j + 2) * 64, hg * 2, 1, bar + B_FULLKV + 8 * sp);
            } else {
              Q_LOAD(0);
            }
            if (j == 1) {
              mbar_expect_tx(bar + B_XST + 8, 16384);
              tma3d(sb + SM_XST + 16384, &mXs, 0, bid * 16, 2, bar + B_XST + 8);
            }
          }
          __syncwarp();
        }
        if (wg == 0 && j == 1) prefetch_l2(pfa + 1024);
        if (wg == 1) {
          if (j == 1 && t7 >= 16 * PF_W) prefetch_l2(pfa);
          if (j == 2) prefetch_l2(pfa + 8 * 393216);
        }
        wg_wait<0>();
        if (lane == 0) mbar_arrive(bar + B_EMPTYKV + 8 * s);
        sp = s; php = ph;
        ph ^= s == 1;
        s = s == 2 ? 0 : s + 1;
      }
    }
    const int lrow = wg * 64 + w * 16 + (lane & 15);
    const uint32_t sw128 = lrow * 128, x128 = (lrow & 7), hi16 = lane >> 4;
    mbar_wait(bar + B_CS, 0);
    const uint32_t tag = __float_as_uint(lds32(sb + SM_RED + 16));
    const int zero = __float_as_int(lds32(sb + SM_RED + 12));
    const float wn = lds32(sb + SM_RED + 24);
    const float2 st0 = lds64(sb + SM_STAT + (wg * 64 + w * 16 + g) * 8), st1 = lds64(sb + SM_STAT + (wg * 64 + w * 16 + g + 8) * 8);
    const float c0 = st0.y * 1.4426950408889634f, c1 = st1.y * 1.4426950408889634f;
    const uint32_t nm20 = pack2(st0.x, st0.x), nm21 = pack2(st1.x, st1.x), fmask = t == 0 ? ~0u : t == 1 ? 0xffffu : 0u;
    const uint32_t fa0 = nm20 & fmask, fa1 = nm21 & fmask;
    asm volatile("cp.async.wait_all;" ::: "memory");
    PW0(47); mbar_wait(bar + B_FULLKV + 16, 1); PW1(47);
    wg_fence();
    wgmma_n256_rs_ta0_tb1(kv, fa0, fa1, 0u, 0u, mkdesc(sb + SM_CST, 512, 0, 1), 1);
    {
      const uint32_t hA = fresh_hi<H128>(P.zA), hB = fresh_hi<H128>(P.zB);
#pragma unroll
      for (int k = 0; k < 4; k++)
        wgmma_n256_ss_ta0_tb1(kv, mkdesch(sb + 2 * KV_STAGE + k * 32, 16, hA, wg * 512), mkdesch(sb + 2 * KV_STAGE + 16384 + k * 2048, 8192, hB), 1);
    }
    wg_commit();
    if (warp == 0) {
      mbar_wait(bar + B_EMPTYKV + 8, 0);
      if (elect_one()) {
#pragma unroll 1
        for (int j = 1; j < 3; j++) Q_LOAD(j);
      }
      __syncwarp();
    }
    wg_wait<0>();
    reg_fence<128>(kv);
    if (lane == 0) mbar_arrive(bar + B_EMPTYKV + 16);
    PROFC(2);
    float q[64];
#define QMMA(J, AOFF16, ACCUM)                                                                                     \
  do {                                                                                                             \
    const uint32_t hA_ = fresh_hi<H128>(P.zA), hB_ = fresh_hi<H128>(P.zB);                                         \
    _Pragma("unroll") for (int k = 0; k < 4; k++)                                                                  \
      wgmma_n128_ss_ta0_tb1(q, mkdesch(sb + k * 32, 16, hA_, wg * 512 + (AOFF16)),                                 \
                            mkdesch(sb + 16384 + k * 2048, 8192, hB_, ((J) & 3) * (Q_STAGE / 16)), k ? 1 : (ACCUM)); \
  } while (0)
#define QWAIT(J) do { PW0(J); mbar_wait(bar + B_FULLQ + 8 * ((J) & 3), ((J) >> 2) & 1); PW1(J); } while (0)
#define QSTEP_A(J, AOFF16, ACCUM) do { QWAIT(J); wg_fence(); QMMA(J, AOFF16, ACCUM); wg_commit(); } while (0)
#define QREL(J) do { if (lane == 0) mbar_arrive(bar + B_EMPTYQ + 8 * ((J) & 3)); } while (0)
#define Q_OFF16(J) ((J) >= 8 && (J) < 16 ? Q_AOFF(J) / 16 : ((J) & 3) * (Q_STAGE / 16))
#define QPLAIN(J) do { QSTEP_A(J, Q_OFF16(J), 1); wg_wait<1>(); QREL((J) - 1); } while (0)
#define QNEXT(J) do { QPLAIN(J); SCHED_FENCE(); } while (0)
#define PHI_PROJ(DST, SRC, H0, H1)                                                                                 \
  do {                                                                                                             \
    uint32_t a_[32];                                                                                               \
    _Pragma("unroll") for (int j = 8 * (H0); j < 8 * (H1); j++) {                                                  \
      a_[j] = pack2(SRC[2 * j], SRC[2 * j + 1]);                                                                   \
      asm volatile("fma.rn.bf16x2 %0, %1, %1, %0;" : "+r"(nq[(j >> 4) * 2 + (j & 1)]) : "r"(a_[j]));               \
    }                                                                                                              \
    wg_fence();                                                                                                    \
    const uint32_t hB_ = fresh_hi<H64>(P.zB);                                                                      \
    _Pragma("unroll") for (int hk = 2 * (H0); hk < 2 * (H1); hk++)                                                 \
        wgmma_n32_rs_ta0_tb1(DST + 16 * (hk >> 1), a_[4 * hk], a_[4 * hk + 1], a_[4 * hk + 2], a_[4 * hk + 3],     \
                             mkdesch(sb + SM_WPHI + hk * 1024, 16, hB_), hk & 1);                                \
    wg_commit();                                                                                                   \
  } while (0)
    {
      float p[64], ea[24], eb[24], sa[4], sc[4], kz[20];
      uint32_t vp[32];
#pragma unroll
      for (int j = 0; j < 32; j++) vp[j] = pack2(kv[64 + 2 * j], kv[65 + 2 * j]);
      const uint32_t vr = w * 16 + (lane & 15), vb = sb + SM_V + wg * 4096 + vr * 64, x64 = (vr >> 1) & 3;
#define V_STORE(R)                                                                                           \
  _Pragma("unroll") for (int j = 0; j < 4; j++)                                                              \
      stsm4(vb + (j >> 1) * 8192 + ((((j & 1) * 2 + hi16) ^ x64) << 4), vp[16 * (R) + 4 * j], vp[16 * (R) + 4 * j + 1], vp[16 * (R) + 4 * j + 2], vp[16 * (R) + 4 * j + 3])
      V_STORE(0);
      mbar_wait(bar + B_WPHI, 0);
      {
        uint32_t nq[4] = {0u, 0u, 0u, 0u};
        PHI_PROJ(p, kv, 0, 4);
        QSTEP_A(0, 0, 0);
        const bool unsafe = softmax_unsafe(nq, c0 * c0 * wn, c1 * c1 * wn);
        wg_wait<1>();
        reg_fence<64>(p);
        if (__builtin_expect(unsafe, 0)) softmax_shift(p, c0, c1);
      }
#define K_NORM(S) do { quad_sum<4>(S); _Pragma("unroll") for (int i = 0; i < 4; i++) S[i] = rcp(S[i]) * ((i & 1) ? st1.y : st0.y); } while (0)
#define K_STORE(SLOT, E, S) K_STORE_(SLOT, E, S, 0, 2)
#define K_STORE_(SLOT, E, S, J0, J1)                                                                         \
  _Pragma("unroll") for (int j = (J0); j < (J1); j++) {                                                      \
    uint32_t fp[4], fm[4];                                                                                   \
    _Pragma("unroll") for (int i = 0; i < 4; i++) {                                                          \
      const float e0 = E[8 * j + 2 * i], e1 = E[8 * j + 2 * i + 1], r = E[16 + 4 * j + i] * S[2 + (i & 1)];  \
      const uint32_t e2 = pack2(e0, e1);                                                                     \
      fp[i] = bmul2(e2, pack2(S[i & 1], S[i & 1]));                                                          \
      fm[i] = bmul2(e2, pack2(r, r));                                                                        \
    }                                                                                                        \
    stsm4(sb + SM_PHI + (SLOT) * 16384 + sw128 + (((2 * j + hi16) ^ x128) << 4), fp[0], fp[1], fp[2], fp[3]); \
    stsm4(sb + SM_PHI + (SLOT) * 16384 + sw128 + (((4 + 2 * j + hi16) ^ x128) << 4), fm[0], fm[1], fm[2], fm[3]); \
  }
#define KV_MMA(R)                                                                                            \
  do {                                                                                                       \
    mbar_wait(bar + B_PHI + 8 * (R), 0);                                                                     \
    wg_fence();                                                                                              \
    const uint32_t hA_ = fresh_hi<H128>(P.zA), hB_ = fresh_hi<H64>(P.zB);                                    \
    _Pragma("unroll") for (int k = 0; k < 8; k++) {                                                          \
      const uint32_t vs = SM_V + (k >> 2) * 4096 + (k & 3) * 1024;                                           \
      wgmma_n40_ss_ta1_tb1(kz, mkdesch(sb + SM_PHI + k * 2048, 16, hA_, wg * 1024),                       \
                           mkdesch(sb + vs, SM_SDT + (k & 1) * 1024 + (k >> 1) * 16 - vs, hB_, wg * (512u - (512u << 16))), k); \
    }                                                                                                        \
    wg_commit();                                                                                             \
  } while (0)
#define QKV(J, R) do { KV_MMA(R); QSTEP_A(J, Q_OFF16(J), 1); wg_wait<2>(); QREL((J) - 1); SCHED_FENCE(); } while (0)
#define KV_SEND(R)                                                                                           \
  do {                                                                                                       \
    reg_fence<20>(kz);                                                                                       \
    if (lane == 0) mbar_arrive(bar + B_KVST + 8 * (R));                                                      \
    const uint32_t slot = ((hg * 2 + (R)) * 16 + warp * 2) * 16 + mb;                                        \
    _Pragma("unroll") for (int u = 0; u < 2; u++)                                                            \
      st_rlx128(g_part + (slot + u * 16) * 32 + lane, mark(pack2(kz[2 * u], kz[2 * u + 1]), tag & 1), pack2(kz[2 * u + 4], kz[2 * u + 5]), \
                pack2(kz[2 * u + 8], kz[2 * u + 9]), pack2(kz[2 * u + 12], kz[2 * u + 13]));                 \
    if (t < 2) st_rlx(g_zpart + (slot + t * 16) * 8 + g, mark(__float_as_uint(t ? kz[18] : kz[16]), tag & 1)); \
    if (lane < 2) red_inc(XC1(hg, R) + warp * 2 + lane);                                                          \
  } while (0)
#define K_PUB(R) do { fence_async_smem(); __syncwarp(); if (lane == 0) mbar_arrive(bar + B_PHI + 8 * (R)); } while (0)
#define S_PIN(S) SCHED_PIN(S[0] + S[1] + S[2] + S[3])
      k_exp(p, c0, c1, ea, sa);
      S_PIN(sa);
      QNEXT(1);
      K_NORM(sa);
      k_exp<0, 4>(p + 16, c0, c1, eb, sc);
      mbar_wait(bar + B_FFN, 0);
      K_STORE_(0, ea, sa, 0, 1);
      S_PIN(sc);
      QNEXT(2);
      K_STORE_(0, ea, sa, 1, 2);
      k_exp<4, 8>(p + 16, c0, c1, eb, sc);
      K_NORM(sc);
      S_PIN(sc);
      QNEXT(3);
      K_STORE(1, eb, sc);
      K_PUB(0);
      k_exp<0, 4>(p + 32, c0, c1, ea, sa);
      S_PIN(sa);
      QKV(4, 0);
      k_exp<4, 8>(p + 32, c0, c1, ea, sa);
      K_NORM(sa);
      S_PIN(sa);
      wg_wait<1>();
      KV_SEND(0);
      QNEXT(5);
      k_exp(p + 48, c0, c1, eb, sc);
      S_PIN(sc);
      QNEXT(6);
      K_NORM(sc);
      mbar_wait(bar + B_KVST, 0);
      V_STORE(1);
      K_STORE(0, ea, sa);
      QNEXT(7);
      K_STORE(1, eb, sc);
      K_PUB(1);
      QKV(8, 1);
      QNEXT(9);
      KV_SEND(1);
    }
    PROFC(3);
#pragma unroll 1
    for (int j = 10; j < 15; j++) QPLAIN(j);
    mbar_wait(bar + B_CSQ, 0);
    QWAIT(15);
    if (wg == 1) bar_sync(6, 256);
    wg_fence();
    wgmma_n128_rs_ta0_tb1(q, fa0, fa1, 0u, 0u, mkdesc(sb + SM_CST + 2048, 512, 0, 1), 1);
    QMMA(15, Q_AOFF(15) / 16, 1);
    wg_commit();
    if (wg == 0) asm volatile("bar.arrive 6, 256;" ::: "memory");
    wg_wait<1>();
    QREL(14);
    wg_wait<0>();
    QREL(15);
    reg_fence<64>(q);
    PROFC(5);
    float yp[4];
    const uint32_t par = tag & 1;
    uint4* ofr = g_ofr + (mb * 16 + hg * 2) * 1024 + (warp * 16 + g) * 8;
#define O_MMA(H, F, N)                                                                                       \
  do {                                                                                                       \
    wg_fence();                                                                                              \
    const uint32_t hB_ = fresh_hi<H64>(P.zB);                                                                \
    _Pragma("unroll") for (int k = 0; k < 4; k++) {                                                          \
      const uint32_t ks = SM_V + (H) * 4096 + k * 1024;                                                      \
      wgmma_n40_rs_ta0_tb1(N + 20 * (k >> 1), F[4 * k], F[4 * k + 1], F[4 * k + 2], F[4 * k + 3],            \
                           mkdesch(sb + ks, SM_ZT + (H) * 1024 + k * 16 - ks, hB_), k & 1);                \
    }                                                                                                        \
    wg_commit();                                                                                             \
  } while (0)
#define O_FIN(H, N, o)                                                                                        \
  do {                                                                                                       \
    reg_fence<40>(N);                                                                                        \
    const float *np = N, *nm = N + 20;                                                                       \
    const float d0 = rcp(fmaf(np[16], nm[17], fmaf(nm[16], np[17], 1e-6f * np[17] * nm[17])));               \
    const float d1 = rcp(fmaf(np[18], nm[19], fmaf(nm[18], np[19], 1e-6f * np[19] * nm[19])));               \
    const float bp0 = nm[17] * d0, bm0 = np[17] * d0, bp1 = nm[19] * d1, bm1 = np[19] * d1;                  \
    _Pragma("unroll") for (int j = 0; j < 4; j++) {                                                          \
      o[2 * j] = pack2(fmaf(np[4 * j], bp0, nm[4 * j] * bm0), fmaf(np[4 * j + 1], bp0, nm[4 * j + 1] * bm0)); \
      o[2 * j + 1] = pack2(fmaf(np[4 * j + 2], bp1, nm[4 * j + 2] * bm1), fmaf(np[4 * j + 3], bp1, nm[4 * j + 3] * bm1)); \
    }                                                                                                        \
  } while (0)
#define O_STG(H, o)                                                                                          \
  _Pragma("unroll") for (int u = 0; u < 2; u++) {                                                            \
    uint32_t v_[4];                                                                                          \
    _Pragma("unroll") for (int j = 0; j < 4; j++) v_[j] = lop_select(o[2 * j + u], parm, vword == j);        \
    st_rlx128(ofr + ((H) >> 1) * 1024 + u * 64 + ((((H) & 1) * 4 + t) ^ g), v_[0], v_[1], v_[2], v_[3]);     \
  }
    uint32_t gf[32], ao[16];
    const uint32_t parm = 0u - par, vword = ((t ^ g) & 1) == (g >> 2) ? g & 3 : 4;
    const float rh0 = 0.5f * st0.y, rh1 = 0.5f * st1.y, mh0 = st0.x * rh0, mh1 = st1.x * rh1;
#define GATE_LD(J) ldsm4(sb + ((J) >> 2 ? SM_X1 : SM_X0) + sw128 + (((((J) & 3) * 2 + hi16) ^ x128) << 4), gf[4 * (J)], gf[4 * (J) + 1], gf[4 * (J) + 2], gf[4 * (J) + 3])
#define GATE(I0, I1)                                                                                         \
  _Pragma("unroll") for (int i = (I0); i < (I1); i++) {                                                      \
    const float rs = (i & 1) ? rh1 : rh0, mh = (i & 1) ? mh1 : mh0;                                          \
    const float h0 = fmaf(bf_lo(gf[i]), rs, mh), h1 = fmaf(bf_hi(gf[i]), rs, mh);                            \
    gf[i] = pack2(fmaf(h0, tanh_approx(h0), h0), fmaf(h1, tanh_approx(h1), h1));                             \
  }
#define GATE_PIN(I0, I1) do { uint32_t o_ = 0; _Pragma("unroll") for (int i = (I0); i < (I1); i++) o_ |= gf[i]; SCHED_PIN(__uint_as_float(o_)); } while (0)
    {
      float p[64], na[40], nb[40];
      uint32_t fa[16], fb[16];
      {
        uint32_t nq[4] = {0u, 0u, 0u, 0u};
        PHI_PROJ(p, q, 0, 2);
        SCHED_FENCE();
        PHI_PROJ(p, q, 2, 4);
        const bool unsafe = softmax_unsafe(nq, c0 * c0 * wn, c1 * c1 * wn);
        wg_wait<0>();
        reg_fence<64>(p);
        PROFC(24);
        if (__builtin_expect(unsafe, 0)) softmax_shift(p, c0, c1);
      }
      float dn[32];
#define DN_PART(A, B)                                                                                        \
  do {                                                                                                       \
    wg_fence();                                                                                              \
    const uint32_t hA_ = fresh_hi<H128>(P.zA), hB_ = fresh_hi<HNS>(P.zB);                                    \
    _Pragma("unroll") for (int i = (A); i < (B); i++)                                                        \
      wgmma_n8_ss_ta1_tb1(dn + 4 * (i >> 1), mkdesch(sb + (i >> 3) * Q_STAGE + (i & 7) * 2048, 16, hA_, wg * (2 * Q_STAGE / 16)), \
                          mkdesch(sb + SM_HT + (i & 1) * 256, 128, hB_), i & 1);                           \
  } while (0)
#define F_PIN(F, A, B) do { uint32_t o_ = 0; _Pragma("unroll") for (int i = (A); i < (B); i++) o_ |= F[8 + i]; SCHED_PIN(__uint_as_float(o_)); } while (0)
#define RMMA(J, A, ACCUM)                                                                                    \
  do {                                                                                                       \
    wg_fence();                                                                                              \
    const uint32_t hB_ = fresh_hi<H128>(P.zB);                                                               \
    _Pragma("unroll") for (int k = 0; k < 4; k++)                                                            \
      wgmma_n128_rs_ta0_tb1(q, (A)[4 * k], (A)[4 * k + 1], (A)[4 * k + 2], (A)[4 * k + 3],                   \
                            mkdesch(sb + 16384 + k * 2048, 8192, hB_, ((J) & 3) * (Q_STAGE / 16)), k ? 1 : (ACCUM)); \
    wg_commit();                                                                                             \
  } while (0)
#define RSTEP(J, A, ACCUM) do { QWAIT(J); RMMA(J, A, ACCUM); } while (0)
      PROFC(4);
      q_exp(p, c0, c1, fa);
      q_exp(p + 16, c0, c1, fb);
      F_PIN(fb, 0, 8);
      mbar_wait(bar + B_TILE, 0);
      O_MMA(0, fa, na);
      O_MMA(1, fb, nb);
      PROFC(25);
      wg_wait<1>();
      O_FIN(0, na, ao);
      O_STG(0, ao);
      wg_wait<0>();
      O_FIN(1, nb, (ao + 8));
      O_STG(1, (ao + 8));
      PROFC(28);
      mbar_wait(bar + B_H, 0);
      mbar_wait(bar + B_DN, 0);
      PROFC(45);
      DN_PART(0, 16);
      wg_commit();
      wg_wait<0>();
      reg_fence<32>(dn);
#pragma unroll
      for (int i = 0; i < 4; i++) yp[i] = t & 2 ? (t & 1 ? dn[24 + 2 * i] : dn[16 + 2 * i]) : (t & 1 ? dn[8 + 2 * i] : dn[2 * i]);
      RSTEP(16, ao, 0);
      SCHED_FENCE();
      q_exp(p + 32, c0, c1, fa);
      F_PIN(fa, 0, 8);
      if (lane == 0) mbar_arrive(bar + B_DND);
      q_exp(p + 48, c0, c1, fb);
      F_PIN(fb, 0, 8);
      wg_wait<0>();
      QREL(16);
      PROFC(29);
      mbar_wait(bar + B_TILE + 8, 0);
      PROFC(23);
      if (bid < NFFN) {
        float* y = g_y[par ^ 1][bid & 7] + wg * 512 + t * 128 + w * 16 + g;
#pragma unroll
        for (int i = 0; i < 4; i++) red1(y + (i >> 1) * 64 + (i & 1) * 8, yp[i]);
      }
      SCHED_FENCE();
      O_MMA(2, fa, na);
      O_MMA(3, fb, nb);
      __syncwarp();
      if (lane == 0) mbar_arrive(bar + B_YD);
      wg_wait<1>();
      O_FIN(2, na, ao);
      O_STG(2, ao);
      wg_wait<0>();
      O_FIN(3, nb, (ao + 8));
      O_STG(3, (ao + 8));
      PROFC(6);
    }
    RSTEP(17, ao, 1);
    SCHED_FENCE();
    GATE_LD(0); GATE_LD(1);
    GATE(0, 4);
    GATE_PIN(0, 4);
#define GSTEP(J, I) do { QNEXT(J); if ((I) < 7) GATE_LD(((I) + 1) & 7); GATE(4 * (I), 4 * (I) + 4); GATE_PIN(4 * (I), 4 * (I) + 4); } while (0)
    GSTEP(18, 1); GSTEP(19, 2); GSTEP(20, 3); GSTEP(21, 4); GSTEP(22, 5); GSTEP(23, 6); GSTEP(24, 7);
#pragma unroll 1
    for (int j = 25; j < 32 - TAILN; j++) QPLAIN(j);
    if (wg == 1) bar_sync(6, 256);
#pragma unroll 1
    for (int j = 32 - TAILN; j < 32; j++) QSTEP_A(j, (j & 3) * (Q_STAGE / 16), 1);
    if (wg == 0) asm volatile("bar.arrive 6, 256;" ::: "memory");
    mbar_wait(bar + B_UPD, 0);
    {
      const int sel = __float_as_int(lds32(sb + SM_UPD + 256)) - (wg * 64 + w * 16 + g);
      if (sel == 0 || sel == 8) {
#pragma unroll
        for (int j = 0; j < 16; j++) {
          const uint32_t u = __float_as_uint(lds32(sb + SM_UPD + j * 16 + t * 4));
          if (sel) gf[2 * j + 1] = u; else gf[2 * j] = u;
        }
      }
      __syncwarp();
      uint32_t xf[32];
#pragma unroll
      for (int j = 0; j < 8; j++)
        ldsm4(sb + (j >> 2 ? SM_X1 : SM_X0) + sw128 + ((((j & 3) * 2 + hi16) ^ x128) << 4), xf[4 * j], xf[4 * j + 1], xf[4 * j + 2], xf[4 * j + 3]);
      wg_wait<0>();
      reg_fence<64>(q);
      PROFC(8);
#pragma unroll
      for (int j = 0; j < 8; j++) {
        uint32_t o[4];
#pragma unroll
        for (int i = 0; i < 4; i++) o[i] = badd2(xf[4 * j + i], bmul2(pack2(q[8 * j + 2 * i], q[8 * j + 2 * i + 1]), gf[4 * j + i]));
        stsm4(sb + (j >> 2 ? SM_X1 : SM_X0) + sw128 + ((((j & 3) * 2 + hi16) ^ x128) << 4), o[0], o[1], o[2], o[3]);
        if ((j & 3) == 3) {
          fence_async_smem();
          __syncwarp();
          if (elect_one()) {
            tma_store2d(&mOut, sb + (j >> 2 ? SM_X1 : SM_X0) + warp * 2048, hg * 128 + (j >> 2) * 64, mb * 128 + warp * 16);
            bulk_commit();
          }
          __syncwarp();
        }
      }
    }
    bulk_wait_read0();
    if (warp == 7 && lane == 0) { PROF(9); PROFT(33); PROF_DUMP; }
  }
}

typedef CUresult (*EncodeFn)(CUtensorMap*, CUtensorMapDataType, cuuint32_t, void*, const cuuint64_t*, const cuuint64_t*, const cuuint32_t*,
                             const cuuint32_t*, CUtensorMapInterleave, CUtensorMapSwizzle, CUtensorMapL2promotion, CUtensorMapFloatOOBfill);

CUtensorMap make_map(EncodeFn enc, const void* ptr, int rank, const cuuint64_t* dims, const cuuint64_t* strides, const cuuint32_t* box, CUtensorMapSwizzle sw) {
  CUtensorMap m;
  const cuuint32_t es[5] = {1, 1, 1, 1, 1};
  enc(&m, CU_TENSOR_MAP_DATA_TYPE_BFLOAT16, rank, (void*)ptr, dims, strides, box, es, CU_TENSOR_MAP_INTERLEAVE_NONE, sw,
      CU_TENSOR_MAP_L2_PROMOTION_L2_128B, CU_TENSOR_MAP_FLOAT_OOB_FILL_NONE);
  return m;
}

}

extern "C" void kernel_launch(void* const* d_in, const int* in_sizes, int n_in, void* d_out, int out_size) {
  static EncodeFn enc = nullptr;
  static int by_sm = 0;
  if (!enc) {
    void* fn = nullptr;
    cudaDriverEntryPointQueryResult qr;
    cudaGetDriverEntryPoint("cuTensorMapEncodeTiled", &fn, cudaEnableDefault, &qr);
    enc = (EncodeFn)fn;
    cudaFuncSetAttribute(fused_kernel<false>, cudaFuncAttributeMaxDynamicSharedMemorySize, SM_TOTAL);
    cudaFuncSetAttribute(fused_kernel<true>, cudaFuncAttributeMaxDynamicSharedMemorySize, SM_TOTAL);
    int dev = 0, sms = 0;
    cudaGetDevice(&dev);
    cudaDeviceGetAttribute(&sms, cudaDevAttrMultiProcessorCount, dev);
    by_sm = BY_SM && sms == NCTA + NSPARE;
  }
  Params P;
  P.zA = P.zB = 0;
  P.x = (const __nv_bfloat16*)d_in[0];
  P.wqkv = (const __nv_bfloat16*)d_in[1];
  const void* wphi = d_in[2];
  P.wo = (const __nv_bfloat16*)d_in[3];
  P.w_r = (const __nv_bfloat16*)d_in[5];
  const void *w_gate = d_in[6], *w_up = d_in[7];
  P.w_down = (const __nv_bfloat16*)d_in[8];

  const cuuint64_t dX[2] = {DM, SEQ}, sX[1] = {DM * 2};
  const cuuint32_t b128[2] = {64, 128};
  const cuuint64_t dW[4] = {64, DM, 16, 3}, sW[3] = {3 * DM * 2, 128, DM * 2};
  const cuuint32_t bKV[4] = {64, 64, 2, 2}, bQ[4] = {64, 64, 2, 1};
  const cuuint64_t dO[3] = {64, DM, 16}, sO[2] = {DM * 2, 128};
  const cuuint32_t bO[3] = {64, 64, 2};
  const cuuint64_t dP[2] = {32, 1024}, sP[1] = {64};
  const cuuint32_t bP[2] = {32, 128};
  CUtensorMap mX = make_map(enc, P.x, 2, dX, sX, b128, CU_TENSOR_MAP_SWIZZLE_128B);
  CUtensorMap mWkv = make_map(enc, P.wqkv, 4, dW, sW, bKV, CU_TENSOR_MAP_SWIZZLE_128B);
  CUtensorMap mWq = make_map(enc, P.wqkv, 4, dW, sW, bQ, CU_TENSOR_MAP_SWIZZLE_128B);
  CUtensorMap mWo = make_map(enc, P.wo, 3, dO, sO, bO, CU_TENSOR_MAP_SWIZZLE_128B);
  CUtensorMap mPhi = make_map(enc, wphi, 2, dP, sP, bP, CU_TENSOR_MAP_SWIZZLE_64B);
  const cuuint64_t dWp[5] = {DM, 2, 4, 4, DM / 32}, sWp[4] = {DM * 2, 8 * DM * 2, 2 * DM * 2, 32 * DM * 2};
  const cuuint32_t bWp[5] = {64, 2, 4, 4, 2};
  CUtensorMap mWp = make_map(enc, P.wo, 5, dWp, sWp, bWp, CU_TENSOR_MAP_SWIZZLE_128B);
  const cuuint32_t b16[2] = {64, 16};
  CUtensorMap mOut = make_map(enc, d_out, 2, dX, sX, b16, CU_TENSOR_MAP_SWIZZLE_128B);
  const cuuint64_t dWc[2] = {3 * DM, DM}, sWc[1] = {3 * DM * 2}, dG[2] = {FF, DM}, sG[1] = {FF * 2}, dD[3] = {64, FF, 16};
  const cuuint32_t b32[2] = {32, 32}, bD[3] = {64, 32, 4};
  CUtensorMap mWc = make_map(enc, P.wqkv, 2, dWc, sWc, b32, CU_TENSOR_MAP_SWIZZLE_NONE);
  CUtensorMap mG = make_map(enc, w_gate, 2, dG, sG, b32, CU_TENSOR_MAP_SWIZZLE_NONE);
  CUtensorMap mU = make_map(enc, w_up, 2, dG, sG, b32, CU_TENSOR_MAP_SWIZZLE_NONE);
  CUtensorMap mD = make_map(enc, P.w_down, 3, dD, sO, bD, CU_TENSOR_MAP_SWIZZLE_128B);
  const cuuint64_t dXs[3] = {256, SEQ, 4}, sXs[2] = {DM * 2, 512};
  const cuuint32_t bXs[3] = {256, 16, 2};
  CUtensorMap mXs = make_map(enc, P.x, 3, dXs, sXs, bXs, CU_TENSOR_MAP_SWIZZLE_NONE);
  const cuuint64_t dG2[4] = {64, DM, FF / 64, 1}, sG2[3] = {FF * 2, 128, (cuuint64_t)FF * DM * 2};
  CUtensorMap mG2 = make_map(enc, w_gate, 4, dG2, sG2, bQ, CU_TENSOR_MAP_SWIZZLE_128B);
  CUtensorMap mU2 = make_map(enc, w_up, 4, dG2, sG2, bQ, CU_TENSOR_MAP_SWIZZLE_128B);
  (by_sm ? fused_kernel<true> : fused_kernel<false>)<<<NCTA + NSPARE, 384, SM_TOTAL, cudaStreamPerThread>>>(P, mX, mWkv, mWq, mWo, mPhi, mWp, mOut, mWc, mG, mU, mD, mXs,
                                                                                                           mG2, mU2);
}
```

```cpp
#include <cuda_runtime.h>
#include <cuda_bf16.h>
#include <cuda.h>
#include <stdint.h>

namespace {

constexpr int SEQ = 2048, DM = 1024, FF = 3584;
constexpr int NCTA = 128;
constexpr int NSPARE = 4;
constexpr int NFFN = FF / 32;
#define GN 6
#define G8 2
constexpr int GROWS = (3 * GN + G8) * 32;
#define TAILN 2
#define PF_FIRST 2
#define PF_W 5
#define PFD 80
#define BY_SM 1
#define PTAB 0x73216540u
#define REG_C 224
#define REG_H 56
#define SP_DELAY 2000
#define XSTR 288
#define AM_NS 100
constexpr bool FFN_OFF = false;

static_assert(2 * REG_C + REG_H <= 3 * 168, "the register pool of the CTA is 384 x 168");

__device__ uint32_t g_epoch[(NCTA + NSPARE) * 32];
__device__ unsigned long long g_stat[SEQ];
__device__ __align__(128) unsigned long long g_best[NCTA];
__device__ __align__(16) float g_y[2][8][DM];
__device__ __align__(128) uint32_t g_ycnt[64];
__device__ __align__(1024) uint32_t g_xcnt[32 * XSTR];
#define XC1(HG, R) (g_xcnt + ((HG) * 2 + (R)) * XSTR)
#define XC2(HG, R) (g_xcnt + (16 + (HG) * 2 + (R)) * XSTR)
__device__ __align__(128) uint4 g_res[2][32 * 256];
__device__ __align__(16) float g_cs[5 * DM];
__device__ __align__(128) float g_gp[2 * FF];
__device__ uint4 g_part[8 * 2 * 16 * 16 * 32];
__device__ __align__(16) float g_zpart[8 * 2 * 16 * 16 * 8];
__device__ __align__(128) uint4 g_zres[2][32 * 64];
__device__ __align__(1024) uint4 g_ofr[16 * 16 * 1024];
#define PROF(i)
#define PROFT(i)
#define PROFC(i)
#define PROF_DUMP
#define PW0(J)
#define PW1(J)

constexpr uint32_t KV_STAGE = 49152, Q_STAGE = 32768;
constexpr uint32_t SM_V = 147456;
constexpr uint32_t SM_PHI = 163840;
constexpr uint32_t SM_XST = 147456;
constexpr uint32_t SM_FST = 172032;
constexpr uint32_t SM_PST0 = 196608, SM_PST1 = SM_PHI + 8192;
constexpr uint32_t SM_X0 = 131072, SM_X1 = SM_PHI + 16384;
constexpr uint32_t SM_WPHI = 204800;
constexpr uint32_t SM_ZT = 212992;
constexpr uint32_t SM_SDT = 217088;
constexpr uint32_t SM_CST = 219136;
constexpr uint32_t SM_HT = 222720;
constexpr uint32_t SM_STAT = 223232;
constexpr uint32_t SM_XSEL = 224256;
constexpr uint32_t SM_RED = 228352;
constexpr uint32_t SM_ROWS = SM_RED + 832;
constexpr uint32_t SM_GRED = SM_XSEL + 3072;
static_assert(GROWS <= 768, "xsel area");
constexpr uint32_t SM_UPD = 229632;
constexpr uint32_t SM_BAR = 230016;
constexpr uint32_t SM_PROF = 230464;
constexpr uint32_t SM_SINK = 231104;
constexpr uint32_t SM_TOTAL = 231616;
constexpr uint32_t SB = 1024;
constexpr uint32_t B_FULLKV = 0  , B_FST = 24  , B_XST = 104  , B_WPHI = 120, B_CS = 128, B_CSQ = 136, B_UPD = 144,
                   B_H = 152, B_DN = 160, B_XS = 168, B_TILE = 176  , B_RES = 192  , B_PART = 208  , B_AIN = 224  ,
                   B_FULLQ = 288  ,
                   B_FFN = 320,
                   B_EMPTYKV = 328  , B_EMPTYQ = 352  , B_KVST = 384  , B_YD = 400, B_PHI = 408  , B_DND = 424, B_END = 432;

__device__ __forceinline__ uint32_t smem_u32(const void* p) { return (uint32_t)__cvta_generic_to_shared(p); }
__device__ __forceinline__ void mbar_init(uint32_t bar, uint32_t cnt) { asm volatile("mbarrier.init.shared::cta.b64 [%0], %1;" ::"r"(bar), "r"(cnt) : "memory"); }
__device__ __forceinline__ void mbar_expect_tx(uint32_t bar, uint32_t bytes) { asm volatile("mbarrier.arrive.expect_tx.shared::cta.b64 _, [%0], %1;" ::"r"(bar), "r"(bytes) : "memory"); }
__device__ __forceinline__ void mbar_arrive2(uint32_t bar) { asm volatile("mbarrier.arrive.shared::cta.b64 _, [%0], 2;" ::"r"(bar) : "memory"); }
__device__ __forceinline__ void mbar_arrive(uint32_t bar) { asm volatile("mbarrier.arrive.shared::cta.b64 _, [%0];" ::"r"(bar) : "memory"); }
__device__ __forceinline__ void mbar_wait(uint32_t bar, uint32_t parity) {
  asm volatile("{\n.reg .pred p;\nLW:\nmbarrier.try_wait.parity.shared::cta.b64 p, [%0], %1;\n@!p bra LW;\n}" ::"r"(bar), "r"(parity) : "memory");
}
__device__ __forceinline__ bool mbar_test(uint32_t bar, uint32_t parity) {
  uint32_t ok;
  asm volatile("{\n.reg .pred p;\nmbarrier.test_wait.parity.shared::cta.b64 p, [%1], %2;\nselp.u32 %0, 1, 0, p;\n}" : "=r"(ok) : "r"(bar), "r"(parity) : "memory");
  return ok;
}
__device__ __forceinline__ int lane_id() { int l; asm volatile("mov.u32 %0, %%laneid;" : "=r"(l)); return l; }
template <int C> __device__ __forceinline__ void sched_fence_(int zero) {
  asm volatile("{\n.reg .pred p;\nsetp.eq.s32 p, %0, %1;\n@p trap;\n}" ::"r"(zero), "n"(C) : "memory");
}
#define SCHED_FENCE() sched_fence_<1000 + __COUNTER__>(zero)
#define SCHED_PIN(V) sched_fence_<1000 + __COUNTER__>(zero & __float_as_int(V))
__device__ __forceinline__ bool elect_one() {
  uint32_t p; asm volatile("{ .reg .pred P; elect.sync _|P, 0xffffffff; selp.u32 %0, 1, 0, P; }" : "=r"(p)); return p;
}
__device__ __forceinline__ void tma2d(uint32_t dst, const CUtensorMap* m, int x, int y, uint32_t bar) {
  asm volatile("cp.async.bulk.tensor.2d.shared::cluster.global.mbarrier::complete_tx::bytes [%0], [%1, {%3, %4}], [%2];" ::"r"(dst), "l"(m), "r"(bar), "r"(x), "r"(y) : "memory");
}
__device__ __forceinline__ void tma3d(uint32_t dst, const CUtensorMap* m, int x, int y, int z, uint32_t bar) {
  asm volatile("cp.async.bulk.tensor.3d.shared::cluster.global.mbarrier::complete_tx::bytes [%0], [%1, {%3, %4, %5}], [%2];" ::"r"(dst), "l"(m), "r"(bar), "r"(x), "r"(y), "r"(z) : "memory");
}
__device__ __forceinline__ void tma4d(uint32_t dst, const CUtensorMap* m, int x, int y, int z, int w, uint32_t bar) {
  asm volatile("cp.async.bulk.tensor.4d.shared::cluster.global.mbarrier::complete_tx::bytes [%0], [%1, {%3, %4, %5, %6}], [%2];" ::"r"(dst), "l"(m), "r"(bar), "r"(x), "r"(y), "r"(z), "r"(w) : "memory");
}
__device__ __forceinline__ void tma5d(uint32_t dst, const CUtensorMap* m, int x, int v, uint32_t bar) {
  asm volatile("cp.async.bulk.tensor.5d.shared::cluster.global.mbarrier::complete_tx::bytes [%0], [%1, {%3, %5, %5, %5, %4}], [%2];" ::"r"(dst), "l"(m), "r"(bar), "r"(x), "r"(v), "r"(0) : "memory");
}
__device__ __forceinline__ void tma_store2d(const CUtensorMap* m, uint32_t src, int x, int y) {
  asm volatile("cp.async.bulk.tensor.2d.global.shared::cta.bulk_group [%0, {%2, %3}], [%1];" ::"l"(m), "r"(src), "r"(x), "r"(y) : "memory");
}
__device__ __forceinline__ void bulk_load(uint32_t dst, const void* src, uint32_t bytes, uint32_t bar) {
  asm volatile("cp.async.bulk.shared::cluster.global.mbarrier::complete_tx::bytes [%0], [%1], %2, [%3];" ::"r"(dst), "l"(src), "r"(bytes), "r"(bar) : "memory");
}
__device__ __forceinline__ void bulk_commit() { asm volatile("cp.async.bulk.commit_group;" ::: "memory"); }
__device__ __forceinline__ void bulk_wait_read0() { asm volatile("cp.async.bulk.wait_group.read 0;" ::: "memory"); }
__device__ __forceinline__ void prefetch_l2(const void* p) { asm volatile("prefetch.global.L2 [%0];" ::"l"(p) : "memory"); }
__device__ __forceinline__ void touch_l2(const void* p, int lane) { asm volatile("cp.async.cg.shared.global.L2::128B [%0], [%1], 16;" ::"r"(SB + SM_SINK + lane * 16), "l"(p) : "memory"); }
__device__ __forceinline__ void cp_async16(uint32_t dst, const void* src) { asm volatile("cp.async.cg.shared.global [%0], [%1], 16;" ::"r"(dst), "l"(src) : "memory"); }
__device__ __forceinline__ void prefetch_map(const CUtensorMap* m) { asm volatile("prefetch.tensormap [%0];" ::"l"(m) : "memory"); }
__device__ __forceinline__ void fence_async_smem() { asm volatile("fence.proxy.async.shared::cta;" ::: "memory"); }
__device__ __forceinline__ void fence_async_global() { asm volatile("fence.proxy.async.global;" ::: "memory"); }
__device__ __forceinline__ void bar_sync(int id, int n) { asm volatile("bar.sync %0, %1;" ::"r"(id), "r"(n) : "memory"); }
__device__ __forceinline__ void wg_fence() { asm volatile("wgmma.fence.sync.aligned;" ::: "memory"); }
__device__ __forceinline__ void wg_commit() { asm volatile("wgmma.commit_group.sync.aligned;" ::: "memory"); }
template <int N> __device__ __forceinline__ void wg_wait() { asm volatile("wgmma.wait_group.sync.aligned %0;" ::"n"(N) : "memory"); }
template <int N> __device__ __forceinline__ void reg_fence(uint32_t* r) {
#pragma unroll
  for (int i = 0; i < N; i++) asm volatile("" : "+r"(r[i])::"memory");
}
template <int N> __device__ __forceinline__ void reg_fence(float* r) {
#pragma unroll
  for (int i = 0; i < N; i++) asm volatile("" : "+f"(r[i])::"memory");
}
__device__ __forceinline__ uint64_t mkdesc(uint32_t addr, uint32_t lbo, uint32_t sbo, uint32_t swz, uint32_t dyn = 0) {
  const uint32_t lo = ((addr >> 4) | ((lbo >> 4) << 16)) + dyn;
  const uint32_t hi = (sbo >> 4) | (swz << 30);
  uint64_t d;
  asm("mov.b64 %0, {%1, %2};" : "=l"(d) : "r"(lo), "r"(hi));
  return d;
}
template <uint32_t C> __device__ __forceinline__ uint32_t fresh_hi(uint32_t zero) { uint32_t h; asm volatile("or.b32 %0, %1, %2;" : "=r"(h) : "r"(zero), "n"(C)); return h; }
constexpr uint32_t H128 = (1024u >> 4) | (1u << 30), H64 = (512u >> 4) | (2u << 30), HNS = 128u >> 4;
__device__ __forceinline__ uint64_t mkdesch(uint32_t addr, uint32_t lbo, uint32_t hi, uint32_t dyn = 0) {
  const uint32_t lo = ((addr >> 4) | ((lbo >> 4) << 16)) + dyn;
  uint64_t d;
  asm("mov.b64 %0, {%1, %2};" : "=l"(d) : "r"(lo), "r"(hi));
  return d;
}
__device__ __forceinline__ void stsm4(uint32_t addr, uint32_t a, uint32_t b, uint32_t c, uint32_t d) {
  asm volatile("stmatrix.sync.aligned.m8n8.x4.shared.b16 [%0], {%1, %2, %3, %4};" ::"r"(addr), "r"(a), "r"(b), "r"(c), "r"(d) : "memory");
}
__device__ __forceinline__ void ldsm4(uint32_t addr, uint32_t& a, uint32_t& b, uint32_t& c, uint32_t& d) {
  asm volatile("ldmatrix.sync.aligned.m8n8.x4.shared.b16 {%0, %1, %2, %3}, [%4];" : "=r"(a), "=r"(b), "=r"(c), "=r"(d) : "r"(addr) : "memory");
}
__device__ __forceinline__ uint32_t pack2(float lo, float hi) { uint32_t r; asm("cvt.rn.bf16x2.f32 %0, %1, %2;" : "=r"(r) : "f"(hi), "f"(lo)); return r; }
__device__ __forceinline__ uint32_t bsub2(uint32_t a, uint32_t b) { uint32_t r; asm("sub.rn.bf16x2 %0, %1, %2;" : "=r"(r) : "r"(a), "r"(b)); return r; }
__device__ __forceinline__ uint32_t badd2(uint32_t a, uint32_t b) { uint32_t r; asm("add.rn.bf16x2 %0, %1, %2;" : "=r"(r) : "r"(a), "r"(b)); return r; }
__device__ __forceinline__ uint32_t bmul2(uint32_t a, uint32_t b) { uint32_t r; asm("mul.rn.bf16x2 %0, %1, %2;" : "=r"(r) : "r"(a), "r"(b)); return r; }
__device__ __forceinline__ float bf_lo(uint32_t v) { return __uint_as_float(v << 16); }
__device__ __forceinline__ float bf_hi(uint32_t v) { return __uint_as_float(v & 0xffff0000u); }
__device__ __forceinline__ float bf_round(float v) { return bf_lo(pack2(v, 0.f)); }
__device__ __forceinline__ float ex2(float v) { float r; asm("ex2.approx.ftz.f32 %0, %1;" : "=f"(r) : "f"(v)); return r; }
__device__ __forceinline__ float rcp(float v) { float r; asm("rcp.approx.ftz.f32 %0, %1;" : "=f"(r) : "f"(v)); return r; }
__device__ __forceinline__ float sqrt_approx(float v) { float r; asm("sqrt.approx.f32 %0, %1;" : "=f"(r) : "f"(v)); return r; }
__device__ __forceinline__ float4 lds128(uint32_t a) { float4 v; asm volatile("ld.shared.v4.f32 {%0, %1, %2, %3}, [%4];" : "=f"(v.x), "=f"(v.y), "=f"(v.z), "=f"(v.w) : "r"(a) : "memory"); return v; }
__device__ __forceinline__ uint4 lds128u(uint32_t a) { uint4 v; asm volatile("ld.shared.v4.u32 {%0, %1, %2, %3}, [%4];" : "=r"(v.x), "=r"(v.y), "=r"(v.z), "=r"(v.w) : "r"(a) : "memory"); return v; }
__device__ __forceinline__ float2 lds64(uint32_t a) { float2 v; asm volatile("ld.shared.v2.f32 {%0, %1}, [%2];" : "=f"(v.x), "=f"(v.y) : "r"(a) : "memory"); return v; }
__device__ __forceinline__ float lds32(uint32_t a) { float v; asm volatile("ld.shared.f32 %0, [%1];" : "=f"(v) : "r"(a) : "memory"); return v; }
__device__ __forceinline__ void sts32(uint32_t a, float v) { asm volatile("st.shared.f32 [%0], %1;" ::"r"(a), "f"(v) : "memory"); }
__device__ __forceinline__ void sts64(uint32_t a, float x, float y) { asm volatile("st.shared.v2.f32 [%0], {%1, %2};" ::"r"(a), "f"(x), "f"(y) : "memory"); }
__device__ __forceinline__ void sts128(uint32_t a, float x, float y, float z, float w) { asm volatile("st.shared.v4.f32 [%0], {%1, %2, %3, %4};" ::"r"(a), "f"(x), "f"(y), "f"(z), "f"(w) : "memory"); }
__device__ __forceinline__ void sts64u(uint32_t a, uint32_t x, uint32_t y) { asm volatile("st.shared.v2.u32 [%0], {%1, %2};" ::"r"(a), "r"(x), "r"(y) : "memory"); }
__device__ __forceinline__ void sts128u(uint32_t a, uint32_t x, uint32_t y, uint32_t z, uint32_t w) { asm volatile("st.shared.v4.u32 [%0], {%1, %2, %3, %4};" ::"r"(a), "r"(x), "r"(y), "r"(z), "r"(w) : "memory"); }
__device__ __forceinline__ uint4 ldg_nc(const void* p) { uint4 v; asm volatile("ld.global.nc.L1::no_allocate.v4.u32 {%0, %1, %2, %3}, [%4];" : "=r"(v.x), "=r"(v.y), "=r"(v.z), "=r"(v.w) : "l"(p)); return v; }
__device__ __forceinline__ float4 ldg_cg4(const float* p) { float4 v; asm volatile("ld.global.cg.v4.f32 {%0, %1, %2, %3}, [%4];" : "=f"(v.x), "=f"(v.y), "=f"(v.z), "=f"(v.w) : "l"(p) : "memory"); return v; }
__device__ __forceinline__ uint32_t ld_acq(const uint32_t* p) { uint32_t v; asm volatile("ld.acquire.gpu.global.u32 %0, [%1];" : "=r"(v) : "l"(p) : "memory"); return v; }
__device__ __forceinline__ unsigned long long ld_rlx64(const unsigned long long* p) { unsigned long long v; asm volatile("ld.relaxed.gpu.global.u64 %0, [%1];" : "=l"(v) : "l"(p) : "memory"); return v; }
__device__ __forceinline__ void st_rlx64(unsigned long long* p, unsigned long long v) { asm volatile("st.relaxed.gpu.global.u64 [%0], %1;" ::"l"(p), "l"(v) : "memory"); }
__device__ __forceinline__ uint4 ld_rlx128(const void* p) {
  uint4 v;
  asm volatile("{ .reg .b128 t; .reg .b64 a, b; ld.relaxed.gpu.global.b128 t, [%4]; mov.b128 {a, b}, t; mov.b64 {%0, %1}, a; mov.b64 {%2, %3}, b; }"
               : "=r"(v.x), "=r"(v.y), "=r"(v.z), "=r"(v.w) : "l"(p) : "memory");
  return v;
}
__device__ __forceinline__ void st_rlx128(void* p, uint32_t x, uint32_t y, uint32_t z, uint32_t w) {
  asm volatile("{ .reg .b128 t; .reg .b64 a, b; mov.b64 a, {%1, %2}; mov.b64 b, {%3, %4}; mov.b128 t, {a, b}; st.relaxed.gpu.global.b128 [%0], t; }"
               ::"l"(p), "r"(x), "r"(y), "r"(z), "r"(w) : "memory");
}
__device__ __forceinline__ void st_rlx(void* p, uint32_t v) { asm volatile("st.relaxed.gpu.global.u32 [%0], %1;" ::"l"(p), "r"(v) : "memory"); }
__device__ __forceinline__ uint32_t lop_select(uint32_t a, uint32_t b, uint32_t m) { uint32_t r; asm("lop3.b32 %0, %1, %2, %3, 0xd8;" : "=r"(r) : "r"(a), "r"(b), "r"(m)); return r; }
__device__ __forceinline__ float unmark(uint32_t v) { return __uint_as_float(v & ~1u); }
__device__ __forceinline__ uint32_t mark(uint32_t v, uint32_t par) { return (v & ~1u) | par; }
__device__ __forceinline__ float tanh_approx(float v) { float r; asm("tanh.approx.f32 %0, %1;" : "=f"(r) : "f"(v)); return r; }
__device__ __forceinline__ void red1(float* p, float a) { asm volatile("red.global.add.f32 [%0], %1;" ::"l"(p), "f"(a) : "memory"); }
__device__ __forceinline__ void red_inc(uint32_t* p) { asm volatile("red.relaxed.gpu.global.add.u32 [%0], 1;" ::"l"(p) : "memory"); }
__device__ __forceinline__ void red_rel(uint32_t* p) { asm volatile("red.release.gpu.global.add.u32 [%0], 1;" ::"l"(p) : "memory"); }
constexpr int SPIN_MAX = 100000;
__device__ __forceinline__ uint32_t ld_rlx(const uint32_t* p) { uint32_t v; asm volatile("ld.relaxed.gpu.global.u32 %0, [%1];" : "=r"(v) : "l"(p) : "memory"); return v; }
template <int NS = 0> __device__ __forceinline__ void wait_hint(const uint32_t* p, uint32_t target) {
#pragma unroll 1
  for (int i = 0; i < SPIN_MAX; i++) { if ((int)(ld_rlx(p) - target) >= 0) break; if (NS) __nanosleep(NS); }
}
template <int NS> __device__ __forceinline__ void wait_cnt(const uint32_t* p, uint32_t target) {
#pragma unroll 1
  for (int i = 0; i < SPIN_MAX; i++) { if ((int)(ld_rlx(p) - target) >= 0) break; if (NS) __nanosleep(NS); }
  (void)ld_acq(p);
}
template <int NS> __device__ __forceinline__ unsigned long long wait_tag(const unsigned long long* p, uint32_t tag) {
  unsigned long long v = 0;
#pragma unroll 1
  for (int i = 0; i < SPIN_MAX; i++) { v = ld_rlx64(p); if ((uint32_t)(v >> 32) == tag) break; if (NS) __nanosleep(NS); }
  return v;
}
__device__ __forceinline__ float silu_f(float v) { return v * rcp(1.f + ex2(-1.4426950408889634f * v)); }

__device__ __forceinline__ void wgmma_n8_ss_ta1_tb0(float* d, uint64_t da, uint64_t db, bool accumulate) {
  if (accumulate) {
    asm volatile("{\n.reg .pred p;\nsetp.ne.b32 p, 1, 0;\n"
      "wgmma.mma_async.sync.aligned.m64n8k16.f32.bf16.bf16 "
      "{%0, %1, %2, %3}, "
      "%4, %5, p, 1, 1, 1, 0;\n}\n"
      : "+f"(d[0]), "+f"(d[1]), "+f"(d[2]), "+f"(d[3])
      : "l"(da), "l"(db));
  } else {
    asm volatile("{\n.reg .pred p;\nsetp.ne.b32 p, 0, 0;\n"
      "wgmma.mma_async.sync.aligned.m64n8k16.f32.bf16.bf16 "
      "{%0, %1, %2, %3}, "
      "%4, %5, p, 1, 1, 1, 0;\n}\n"
      : "=f"(d[0]), "=f"(d[1]), "=f"(d[2]), "=f"(d[3])
      : "l"(da), "l"(db));
  }
}
__device__ __forceinline__ void wgmma_n8_ss_ta1_tb1(float* d, uint64_t da, uint64_t db, bool accumulate) {
  if (accumulate) {
    asm volatile("{\n.reg .pred p;\nsetp.ne.b32 p, 1, 0;\n"
      "wgmma.mma_async.sync.aligned.m64n8k16.f32.bf16.bf16 "
      "{%0, %1, %2, %3}, "
      "%4, %5, p, 1, 1, 1, 1;\n}\n"
      : "+f"(d[0]), "+f"(d[1]), "+f"(d[2]), "+f"(d[3])
      : "l"(da), "l"(db));
  } else {
    asm volatile("{\n.reg .pred p;\nsetp.ne.b32 p, 0, 0;\n"
      "wgmma.mma_async.sync.aligned.m64n8k16.f32.bf16.bf16 "
      "{%0, %1, %2, %3}, "
      "%4, %5, p, 1, 1, 1, 1;\n}\n"
      : "=f"(d[0]), "=f"(d[1]), "=f"(d[2]), "=f"(d[3])
      : "l"(da), "l"(db));
  }
}
__device__ __forceinline__ void wgmma_n32_rs_ta0_tb1(float* d, uint32_t a0, uint32_t a1, uint32_t a2, uint32_t a3, uint64_t db, bool accumulate) {
  if (accumulate) {
    asm volatile("{\n.reg .pred p;\nsetp.ne.b32 p, 1, 0;\n"
      "wgmma.mma_async.sync.aligned.m64n32k16.f32.bf16.bf16 "
      "{%0, %1, %2, %3, %4, %5, %6, %7, %8, %9, %10, %11, %12, %13, %14, %15}, "
      "{%16, %17, %18, %19}, %20, p, 1, 1, 1;\n}\n"
      : "+f"(d[0]), "+f"(d[1]), "+f"(d[2]), "+f"(d[3]), "+f"(d[4]), "+f"(d[5]), "+f"(d[6]), "+f"(d[7]), "+f"(d[8]), "+f"(d[9]), "+f"(d[10]), "+f"(d[11]), "+f"(d[12]), "+f"(d[13]), "+f"(d[14]), "+f"(d[15])
      : "r"(a0), "r"(a1), "r"(a2), "r"(a3), "l"(db));
  } else {
    asm volatile("{\n.reg .pred p;\nsetp.ne.b32 p, 0, 0;\n"
      "wgmma.mma_async.sync.aligned.m64n32k16.f32.bf16.bf16 "
      "{%0, %1, %2, %3, %4, %5, %6, %7, %8, %9, %10, %11, %12, %13, %14, %15}, "
      "{%16, %17, %18, %19}, %20, p, 1, 1, 1;\n}\n"
      : "=f"(d[0]), "=f"(d[1]), "=f"(d[2]), "=f"(d[3]), "=f"(d[4]), "=f"(d[5]), "=f"(d[6]), "=f"(d[7]), "=f"(d[8]), "=f"(d[9]), "=f"(d[10]), "=f"(d[11]), "=f"(d[12]), "=f"(d[13]), "=f"(d[14]), "=f"(d[15])
      : "r"(a0), "r"(a1), "r"(a2), "r"(a3), "l"(db));
  }
}
__device__ __forceinline__ void wgmma_n40_rs_ta0_tb1(float* d, uint32_t a0, uint32_t a1, uint32_t a2, uint32_t a3, uint64_t db, bool accumulate) {
  if (accumulate) {
    asm volatile("{\n.reg .pred p;\nsetp.ne.b32 p, 1, 0;\n"
      "wgmma.mma_async.sync.aligned.m64n40k16.f32.bf16.bf16 "
      "{%0, %1, %2, %3, %4, %5, %6, %7, %8, %9, %10, %11, %12, %13, %14, %15, %16, %17, %18, %19}, "
      "{%20, %21, %22, %23}, %24, p, 1, 1, 1;\n}\n"
      : "+f"(d[0]), "+f"(d[1]), "+f"(d[2]), "+f"(d[3]), "+f"(d[4]), "+f"(d[5]), "+f"(d[6]), "+f"(d[7]), "+f"(d[8]), "+f"(d[9]), "+f"(d[10]), "+f"(d[11]), "+f"(d[12]), "+f"(d[13]), "+f"(d[14]), "+f"(d[15]), "+f"(d[16]), "+f"(d[17]), "+f"(d[18]), "+f"(d[19])
      : "r"(a0), "r"(a1), "r"(a2), "r"(a3), "l"(db));
  } else {
    asm volatile("{\n.reg .pred p;\nsetp.ne.b32 p, 0, 0;\n"
      "wgmma.mma_async.sync.aligned.m64n40k16.f32.bf16.bf16 "
      "{%0, %1, %2, %3, %4, %5, %6, %7, %8, %9, %10, %11, %12, %13, %14, %15, %16, %17, %18, %19}, "
      "{%20, %21, %22, %23}, %24, p, 1, 1, 1;\n}\n"
      : "=f"(d[0]), "=f"(d[1]), "=f"(d[2]), "=f"(d[3]), "=f"(d[4]), "=f"(d[5]), "=f"(d[6]), "=f"(d[7]), "=f"(d[8]), "=f"(d[9]), "=f"(d[10]), "=f"(d[11]), "=f"(d[12]), "=f"(d[13]), "=f"(d[14]), "=f"(d[15]), "=f"(d[16]), "=f"(d[17]), "=f"(d[18]), "=f"(d[19])
      : "r"(a0), "r"(a1), "r"(a2), "r"(a3), "l"(db));
  }
}
__device__ __forceinline__ void wgmma_n40_ss_ta1_tb1(float* d, uint64_t da, uint64_t db, bool accumulate) {
  if (accumulate) {
    asm volatile("{\n.reg .pred p;\nsetp.ne.b32 p, 1, 0;\n"
      "wgmma.mma_async.sync.aligned.m64n40k16.f32.bf16.bf16 "
      "{%0, %1, %2, %3, %4, %5, %6, %7, %8, %9, %10, %11, %12, %13, %14, %15, %16, %17, %18, %19}, "
      "%20, %21, p, 1, 1, 1, 1;\n}\n"
      : "+f"(d[0]), "+f"(d[1]), "+f"(d[2]), "+f"(d[3]), "+f"(d[4]), "+f"(d[5]), "+f"(d[6]), "+f"(d[7]), "+f"(d[8]), "+f"(d[9]), "+f"(d[10]), "+f"(d[11]), "+f"(d[12]), "+f"(d[13]), "+f"(d[14]), "+f"(d[15]), "+f"(d[16]), "+f"(d[17]), "+f"(d[18]), "+f"(d[19])
      : "l"(da), "l"(db));
  } else {
    asm volatile("{\n.reg .pred p;\nsetp.ne.b32 p, 0, 0;\n"
      "wgmma.mma_async.sync.aligned.m64n40k16.f32.bf16.bf16 "
      "{%0, %1, %2, %3, %4, %5, %6, %7, %8, %9, %10, %11, %12, %13, %14, %15, %16, %17, %18, %19}, "
      "%20, %21, p, 1, 1, 1, 1;\n}\n"
      : "=f"(d[0]), "=f"(d[1]), "=f"(d[2]), "=f"(d[3]), "=f"(d[4]), "=f"(d[5]), "=f"(d[6]), "=f"(d[7]), "=f"(d[8]), "=f"(d[9]), "=f"(d[10]), "=f"(d[11]), "=f"(d[12]), "=f"(d[13]), "=f"(d[14]), "=f"(d[15]), "=f"(d[16]), "=f"(d[17]), "=f"(d[18]), "=f"(d[19])
      : "l"(da), "l"(db));
  }
}
__device__ __forceinline__ void wgmma_n128_rs_ta0_tb1(float* d, uint32_t a0, uint32_t a1, uint32_t a2, uint32_t a3, uint64_t db, bool accumulate) {
  if (accumulate) {
    asm volatile("{\n.reg .pred p;\nsetp.ne.b32 p, 1, 0;\n"
      "wgmma.mma_async.sync.aligned.m64n128k16.f32.bf16.bf16 "
      "{%0, %1, %2, %3, %4, %5, %6, %7, %8, %9, %10, %11, %12, %13, %14, %15, %16, %17, %18, %19, %20, %21, %22, %23, %24, %25, %26, %27, %28, %29, %30, %31, %32, %33, %34, %35, %36, %37, %38, %39, %40, %41, %42, %43, %44, %45, %46, %47, %48, %49, %50, %51, %52, %53, %54, %55, %56, %57, %58, %59, %60, %61, %62, %63}, "
      "{%64, %65, %66, %67}, %68, p, 1, 1, 1;\n}\n"
      : "+f"(d[0]), "+f"(d[1]), "+f"(d[2]), "+f"(d[3]), "+f"(d[4]), "+f"(d[5]), "+f"(d[6]), "+f"(d[7]), "+f"(d[8]), "+f"(d[9]), "+f"(d[10]), "+f"(d[11]), "+f"(d[12]), "+f"(d[13]), "+f"(d[14]), "+f"(d[15]), "+f"(d[16]), "+f"(d[17]), "+f"(d[18]), "+f"(d[19]), "+f"(d[20]), "+f"(d[21]), "+f"(d[22]), "+f"(d[23]), "+f"(d[24]), "+f"(d[25]), "+f"(d[26]), "+f"(d[27]), "+f"(d[28]), "+f"(d[29]), "+f"(d[30]), "+f"(d[31]), "+f"(d[32]), "+f"(d[33]), "+f"(d[34]), "+f"(d[35]), "+f"(d[36]), "+f"(d[37]), "+f"(d[38]), "+f"(d[39]), "+f"(d[40]), "+f"(d[41]), "+f"(d[42]), "+f"(d[43]), "+f"(d[44]), "+f"(d[45]), "+f"(d[46]), "+f"(d[47]), "+f"(d[48]), "+f"(d[49]), "+f"(d[50]), "+f"(d[51]), "+f"(d[52]), "+f"(d[53]), "+f"(d[54]), "+f"(d[55]), "+f"(d[56]), "+f"(d[57]), "+f"(d[58]), "+f"(d[59]), "+f"(d[60]), "+f"(d[61]), "+f"(d[62]), "+f"(d[63])
      : "r"(a0), "r"(a1), "r"(a2), "r"(a3), "l"(db));
  } else {
    asm volatile("{\n.reg .pred p;\nsetp.ne.b32 p, 0, 0;\n"
      "wgmma.mma_async.sync.aligned.m64n128k16.f32.bf16.bf16 "
      "{%0, %1, %2, %3, %4, %5, %6, %7, %8, %9, %10, %11, %12, %13, %14, %15, %16, %17, %18, %19, %20, %21, %22, %23, %24, %25, %26, %27, %28, %29, %30, %31, %32, %33, %34, %35, %36, %37, %38, %39, %40, %41, %42, %43, %44, %45, %46, %47, %48, %49, %50, %51, %52, %53, %54, %55, %56, %57, %58, %59, %60, %61, %62, %63}, "
      "{%64, %65, %66, %67}, %68, p, 1, 1, 1;\n}\n"
      : "=f"(d[0]), "=f"(d[1]), "=f"(d[2]), "=f"(d[3]), "=f"(d[4]), "=f"(d[5]), "=f"(d[6]), "=f"(d[7]), "=f"(d[8]), "=f"(d[9]), "=f"(d[10]), "=f"(d[11]), "=f"(d[12]), "=f"(d[13]), "=f"(d[14]), "=f"(d[15]), "=f"(d[16]), "=f"(d[17]), "=f"(d[18]), "=f"(d[19]), "=f"(d[20]), "=f"(d[21]), "=f"(d[22]), "=f"(d[23]), "=f"(d[24]), "=f"(d[25]), "=f"(d[26]), "=f"(d[27]), "=f"(d[28]), "=f"(d[29]), "=f"(d[30]), "=f"(d[31]), "=f"(d[32]), "=f"(d[33]), "=f"(d[34]), "=f"(d[35]), "=f"(d[36]), "=f"(d[37]), "=f"(d[38]), "=f"(d[39]), "=f"(d[40]), "=f"(d[41]), "=f"(d[42]), "=f"(d[43]), "=f"(d[44]), "=f"(d[45]), "=f"(d[46]), "=f"(d[47]), "=f"(d[48]), "=f"(d[49]), "=f"(d[50]), "=f"(d[51]), "=f"(d[52]), "=f"(d[53]), "=f"(d[54]), "=f"(d[55]), "=f"(d[56]), "=f"(d[57]), "=f"(d[58]), "=f"(d[59]), "=f"(d[60]), "=f"(d[61]), "=f"(d[62]), "=f"(d[63])
      : "r"(a0), "r"(a1), "r"(a2), "r"(a3), "l"(db));
  }
}
__device__ __forceinline__ void wgmma_n128_ss_ta0_tb1(float* d, uint64_t da, uint64_t db, bool accumulate) {
  if (accumulate) {
    asm volatile("{\n.reg .pred p;\nsetp.ne.b32 p, 1, 0;\n"
      "wgmma.mma_async.sync.aligned.m64n128k16.f32.bf16.bf16 "
      "{%0, %1, %2, %3, %4, %5, %6, %7, %8, %9, %10, %11, %12, %13, %14, %15, %16, %17, %18, %19, %20, %21, %22, %23, %24, %25, %26, %27, %28, %29, %30, %31, %32, %33, %34, %35, %36, %37, %38, %39, %40, %41, %42, %43, %44, %45, %46, %47, %48, %49, %50, %51, %52, %53, %54, %55, %56, %57, %58, %59, %60, %61, %62, %63}, "
      "%64, %65, p, 1, 1, 0, 1;\n}\n"
      : "+f"(d[0]), "+f"(d[1]), "+f"(d[2]), "+f"(d[3]), "+f"(d[4]), "+f"(d[5]), "+f"(d[6]), "+f"(d[7]), "+f"(d[8]), "+f"(d[9]), "+f"(d[10]), "+f"(d[11]), "+f"(d[12]), "+f"(d[13]), "+f"(d[14]), "+f"(d[15]), "+f"(d[16]), "+f"(d[17]), "+f"(d[18]), "+f"(d[19]), "+f"(d[20]), "+f"(d[21]), "+f"(d[22]), "+f"(d[23]), "+f"(d[24]), "+f"(d[25]), "+f"(d[26]), "+f"(d[27]), "+f"(d[28]), "+f"(d[29]), "+f"(d[30]), "+f"(d[31]), "+f"(d[32]), "+f"(d[33]), "+f"(d[34]), "+f"(d[35]), "+f"(d[36]), "+f"(d[37]), "+f"(d[38]), "+f"(d[39]), "+f"(d[40]), "+f"(d[41]), "+f"(d[42]), "+f"(d[43]), "+f"(d[44]), "+f"(d[45]), "+f"(d[46]), "+f"(d[47]), "+f"(d[48]), "+f"(d[49]), "+f"(d[50]), "+f"(d[51]), "+f"(d[52]), "+f"(d[53]), "+f"(d[54]), "+f"(d[55]), "+f"(d[56]), "+f"(d[57]), "+f"(d[58]), "+f"(d[59]), "+f"(d[60]), "+f"(d[61]), "+f"(d[62]), "+f"(d[63])
      : "l"(da), "l"(db));
  } else {
    asm volatile("{\n.reg .pred p;\nsetp.ne.b32 p, 0, 0;\n"
      "wgmma.mma_async.sync.aligned.m64n128k16.f32.bf16.bf16 "
      "{%0, %1, %2, %3, %4, %5, %6, %7, %8, %9, %10, %11, %12, %13, %14, %15, %16, %17, %18, %19, %20, %21, %22, %23, %24, %25, %26, %27, %28, %29, %30, %31, %32, %33, %34, %35, %36, %37, %38, %39, %40, %41, %42, %43, %44, %45, %46, %47, %48, %49, %50, %51, %52, %53, %54, %55, %56, %57, %58, %59, %60, %61, %62, %63}, "
      "%64, %65, p, 1, 1, 0, 1;\n}\n"
      : "=f"(d[0]), "=f"(d[1]), "=f"(d[2]), "=f"(d[3]), "=f"(d[4]), "=f"(d[5]), "=f"(d[6]), "=f"(d[7]), "=f"(d[8]), "=f"(d[9]), "=f"(d[10]), "=f"(d[11]), "=f"(d[12]), "=f"(d[13]), "=f"(d[14]), "=f"(d[15]), "=f"(d[16]), "=f"(d[17]), "=f"(d[18]), "=f"(d[19]), "=f"(d[20]), "=f"(d[21]), "=f"(d[22]), "=f"(d[23]), "=f"(d[24]), "=f"(d[25]), "=f"(d[26]), "=f"(d[27]), "=f"(d[28]), "=f"(d[29]), "=f"(d[30]), "=f"(d[31]), "=f"(d[32]), "=f"(d[33]), "=f"(d[34]), "=f"(d[35]), "=f"(d[36]), "=f"(d[37]), "=f"(d[38]), "=f"(d[39]), "=f"(d[40]), "=f"(d[41]), "=f"(d[42]), "=f"(d[43]), "=f"(d[44]), "=f"(d[45]), "=f"(d[46]), "=f"(d[47]), "=f"(d[48]), "=f"(d[49]), "=f"(d[50]), "=f"(d[51]), "=f"(d[52]), "=f"(d[53]), "=f"(d[54]), "=f"(d[55]), "=f"(d[56]), "=f"(d[57]), "=f"(d[58]), "=f"(d[59]), "=f"(d[60]), "=f"(d[61]), "=f"(d[62]), "=f"(d[63])
      : "l"(da), "l"(db));
  }
}
__device__ __forceinline__ void wgmma_n256_rs_ta0_tb1(float* d, uint32_t a0, uint32_t a1, uint32_t a2, uint32_t a3, uint64_t db, bool accumulate) {
  if (accumulate) {
    asm volatile("{\n.reg .pred p;\nsetp.ne.b32 p, 1, 0;\n"
      "wgmma.mma_async.sync.aligned.m64n256k16.f32.bf16.bf16 "
      "{%0, %1, %2, %3, %4, %5, %6, %7, %8, %9, %10, %11, %12, %13, %14, %15, %16, %17, %18, %19, %20, %21, %22, %23, %24, %25, %26, %27, %28, %29, %30, %31, %32, %33, %34, %35, %36, %37, %38, %39, %40, %41, %42, %43, %44, %45, %46, %47, %48, %49, %50, %51, %52, %53, %54, %55, %56, %57, %58, %59, %60, %61, %62, %63, %64, %65, %66, %67, %68, %69, %70, %71, %72, %73, %74, %75, %76, %77, %78, %79, %80, %81, %82, %83, %84, %85, %86, %87, %88, %89, %90, %91, %92, %93, %94, %95, %96, %97, %98, %99, %100, %101, %102, %103, %104, %105, %106, %107, %108, %109, %110, %111, %112, %113, %114, %115, %116, %117, %118, %119, %120, %121, %122, %123, %124, %125, %126, %127}, "
      "{%128, %129, %130, %131}, %132, p, 1, 1, 1;\n}\n"
      : "+f"(d[0]), "+f"(d[1]), "+f"(d[2]), "+f"(d[3]), "+f"(d[4]), "+f"(d[5]), "+f"(d[6]), "+f"(d[7]), "+f"(d[8]), "+f"(d[9]), "+f"(d[10]), "+f"(d[11]), "+f"(d[12]), "+f"(d[13]), "+f"(d[14]), "+f"(d[15]), "+f"(d[16]), "+f"(d[17]), "+f"(d[18]), "+f"(d[19]), "+f"(d[20]), "+f"(d[21]), "+f"(d[22]), "+f"(d[23]), "+f"(d[24]), "+f"(d[25]), "+f"(d[26]), "+f"(d[27]), "+f"(d[28]), "+f"(d[29]), "+f"(d[30]), "+f"(d[31]), "+f"(d[32]), "+f"(d[33]), "+f"(d[34]), "+f"(d[35]), "+f"(d[36]), "+f"(d[37]), "+f"(d[38]), "+f"(d[39]), "+f"(d[40]), "+f"(d[41]), "+f"(d[42]), "+f"(d[43]), "+f"(d[44]), "+f"(d[45]), "+f"(d[46]), "+f"(d[47]), "+f"(d[48]), "+f"(d[49]), "+f"(d[50]), "+f"(d[51]), "+f"(d[52]), "+f"(d[53]), "+f"(d[54]), "+f"(d[55]), "+f"(d[56]), "+f"(d[57]), "+f"(d[58]), "+f"(d[59]), "+f"(d[60]), "+f"(d[61]), "+f"(d[62]), "+f"(d[63]), "+f"(d[64]), "+f"(d[65]), "+f"(d[66]), "+f"(d[67]), "+f"(d[68]), "+f"(d[69]), "+f"(d[70]), "+f"(d[71]), "+f"(d[72]), "+f"(d[73]), "+f"(d[74]), "+f"(d[75]), "+f"(d[76]), "+f"(d[77]), "+f"(d[78]), "+f"(d[79]), "+f"(d[80]), "+f"(d[81]), "+f"(d[82]), "+f"(d[83]), "+f"(d[84]), "+f"(d[85]), "+f"(d[86]), "+f"(d[87]), "+f"(d[88]), "+f"(d[89]), "+f"(d[90]), "+f"(d[91]), "+f"(d[92]), "+f"(d[93]), "+f"(d[94]), "+f"(d[95]), "+f"(d[96]), "+f"(d[97]), "+f"(d[98]), "+f"(d[99]), "+f"(d[100]), "+f"(d[101]), "+f"(d[102]), "+f"(d[103]), "+f"(d[104]), "+f"(d[105]), "+f"(d[106]), "+f"(d[107]), "+f"(d[108]), "+f"(d[109]), "+f"(d[110]), "+f"(d[111]), "+f"(d[112]), "+f"(d[113]), "+f"(d[114]), "+f"(d[115]), "+f"(d[116]), "+f"(d[117]), "+f"(d[118]), "+f"(d[119]), "+f"(d[120]), "+f"(d[121]), "+f"(d[122]), "+f"(d[123]), "+f"(d[124]), "+f"(d[125]), "+f"(d[126]), "+f"(d[127])
      : "r"(a0), "r"(a1), "r"(a2), "r"(a3), "l"(db));
  } else {
    asm volatile("{\n.reg .pred p;\nsetp.ne.b32 p, 0, 0;\n"
      "wgmma.mma_async.sync.aligned.m64n256k16.f32.bf16.bf16 "
      "{%0, %1, %2, %3, %4, %5, %6, %7, %8, %9, %10, %11, %12, %13, %14, %15, %16, %17, %18, %19, %20, %21, %22, %23, %24, %25, %26, %27, %28, %29, %30, %31, %32, %33, %34, %35, %36, %37, %38, %39, %40, %41, %42, %43, %44, %45, %46, %47, %48, %49, %50, %51, %52, %53, %54, %55, %56, %57, %58, %59, %60, %61, %62, %63, %64, %65, %66, %67, %68, %69, %70, %71, %72, %73, %74, %75, %76, %77, %78, %79, %80, %81, %82, %83, %84, %85, %86, %87, %88, %89, %90, %91, %92, %93, %94, %95, %96, %97, %98, %99, %100, %101, %102, %103, %104, %105, %106, %107, %108, %109, %110, %111, %112, %113, %114, %115, %116, %117, %118, %119, %120, %121, %122, %123, %124, %125, %126, %127}, "
      "{%128, %129, %130, %131}, %132, p, 1, 1, 1;\n}\n"
      : "=f"(d[0]), "=f"(d[1]), "=f"(d[2]), "=f"(d[3]), "=f"(d[4]), "=f"(d[5]), "=f"(d[6]), "=f"(d[7]), "=f"(d[8]), "=f"(d[9]), "=f"(d[10]), "=f"(d[11]), "=f"(d[12]), "=f"(d[13]), "=f"(d[14]), "=f"(d[15]), "=f"(d[16]), "=f"(d[17]), "=f"(d[18]), "=f"(d[19]), "=f"(d[20]), "=f"(d[21]), "=f"(d[22]), "=f"(d[23]), "=f"(d[24]), "=f"(d[25]), "=f"(d[26]), "=f"(d[27]), "=f"(d[28]), "=f"(d[29]), "=f"(d[30]), "=f"(d[31]), "=f"(d[32]), "=f"(d[33]), "=f"(d[34]), "=f"(d[35]), "=f"(d[36]), "=f"(d[37]), "=f"(d[38]), "=f"(d[39]), "=f"(d[40]), "=f"(d[41]), "=f"(d[42]), "=f"(d[43]), "=f"(d[44]), "=f"(d[45]), "=f"(d[46]), "=f"(d[47]), "=f"(d[48]), "=f"(d[49]), "=f"(d[50]), "=f"(d[51]), "=f"(d[52]), "=f"(d[53]), "=f"(d[54]), "=f"(d[55]), "=f"(d[56]), "=f"(d[57]), "=f"(d[58]), "=f"(d[59]), "=f"(d[60]), "=f"(d[61]), "=f"(d[62]), "=f"(d[63]), "=f"(d[64]), "=f"(d[65]), "=f"(d[66]), "=f"(d[67]), "=f"(d[68]), "=f"(d[69]), "=f"(d[70]), "=f"(d[71]), "=f"(d[72]), "=f"(d[73]), "=f"(d[74]), "=f"(d[75]), "=f"(d[76]), "=f"(d[77]), "=f"(d[78]), "=f"(d[79]), "=f"(d[80]), "=f"(d[81]), "=f"(d[82]), "=f"(d[83]), "=f"(d[84]), "=f"(d[85]), "=f"(d[86]), "=f"(d[87]), "=f"(d[88]), "=f"(d[89]), "=f"(d[90]), "=f"(d[91]), "=f"(d[92]), "=f"(d[93]), "=f"(d[94]), "=f"(d[95]), "=f"(d[96]), "=f"(d[97]), "=f"(d[98]), "=f"(d[99]), "=f"(d[100]), "=f"(d[101]), "=f"(d[102]), "=f"(d[103]), "=f"(d[104]), "=f"(d[105]), "=f"(d[106]), "=f"(d[107]), "=f"(d[108]), "=f"(d[109]), "=f"(d[110]), "=f"(d[111]), "=f"(d[112]), "=f"(d[113]), "=f"(d[114]), "=f"(d[115]), "=f"(d[116]), "=f"(d[117]), "=f"(d[118]), "=f"(d[119]), "=f"(d[120]), "=f"(d[121]), "=f"(d[122]), "=f"(d[123]), "=f"(d[124]), "=f"(d[125]), "=f"(d[126]), "=f"(d[127])
      : "r"(a0), "r"(a1), "r"(a2), "r"(a3), "l"(db));
  }
}
__device__ __forceinline__ void wgmma_n256_ss_ta0_tb1(float* d, uint64_t da, uint64_t db, bool accumulate) {
  if (accumulate) {
    asm volatile("{\n.reg .pred p;\nsetp.ne.b32 p, 1, 0;\n"
      "wgmma.mma_async.sync.aligned.m64n256k16.f32.bf16.bf16 "
      "{%0, %1, %2, %3, %4, %5, %6, %7, %8, %9, %10, %11, %12, %13, %14, %15, %16, %17, %18, %19, %20, %21, %22, %23, %24, %25, %26, %27, %28, %29, %30, %31, %32, %33, %34, %35, %36, %37, %38, %39, %40, %41, %42, %43, %44, %45, %46, %47, %48, %49, %50, %51, %52, %53, %54, %55, %56, %57, %58, %59, %60, %61, %62, %63, %64, %65, %66, %67, %68, %69, %70, %71, %72, %73, %74, %75, %76, %77, %78, %79, %80, %81, %82, %83, %84, %85, %86, %87, %88, %89, %90, %91, %92, %93, %94, %95, %96, %97, %98, %99, %100, %101, %102, %103, %104, %105, %106, %107, %108, %109, %110, %111, %112, %113, %114, %115, %116, %117, %118, %119, %120, %121, %122, %123, %124, %125, %126, %127}, "
      "%128, %129, p, 1, 1, 0, 1;\n}\n"
      : "+f"(d[0]), "+f"(d[1]), "+f"(d[2]), "+f"(d[3]), "+f"(d[4]), "+f"(d[5]), "+f"(d[6]), "+f"(d[7]), "+f"(d[8]), "+f"(d[9]), "+f"(d[10]), "+f"(d[11]), "+f"(d[12]), "+f"(d[13]), "+f"(d[14]), "+f"(d[15]), "+f"(d[16]), "+f"(d[17]), "+f"(d[18]), "+f"(d[19]), "+f"(d[20]), "+f"(d[21]), "+f"(d[22]), "+f"(d[23]), "+f"(d[24]), "+f"(d[25]), "+f"(d[26]), "+f"(d[27]), "+f"(d[28]), "+f"(d[29]), "+f"(d[30]), "+f"(d[31]), "+f"(d[32]), "+f"(d[33]), "+f"(d[34]), "+f"(d[35]), "+f"(d[36]), "+f"(d[37]), "+f"(d[38]), "+f"(d[39]), "+f"(d[40]), "+f"(d[41]), "+f"(d[42]), "+f"(d[43]), "+f"(d[44]), "+f"(d[45]), "+f"(d[46]), "+f"(d[47]), "+f"(d[48]), "+f"(d[49]), "+f"(d[50]), "+f"(d[51]), "+f"(d[52]), "+f"(d[53]), "+f"(d[54]), "+f"(d[55]), "+f"(d[56]), "+f"(d[57]), "+f"(d[58]), "+f"(d[59]), "+f"(d[60]), "+f"(d[61]), "+f"(d[62]), "+f"(d[63]), "+f"(d[64]), "+f"(d[65]), "+f"(d[66]), "+f"(d[67]), "+f"(d[68]), "+f"(d[69]), "+f"(d[70]), "+f"(d[71]), "+f"(d[72]), "+f"(d[73]), "+f"(d[74]), "+f"(d[75]), "+f"(d[76]), "+f"(d[77]), "+f"(d[78]), "+f"(d[79]), "+f"(d[80]), "+f"(d[81]), "+f"(d[82]), "+f"(d[83]), "+f"(d[84]), "+f"(d[85]), "+f"(d[86]), "+f"(d[87]), "+f"(d[88]), "+f"(d[89]), "+f"(d[90]), "+f"(d[91]), "+f"(d[92]), "+f"(d[93]), "+f"(d[94]), "+f"(d[95]), "+f"(d[96]), "+f"(d[97]), "+f"(d[98]), "+f"(d[99]), "+f"(d[100]), "+f"(d[101]), "+f"(d[102]), "+f"(d[103]), "+f"(d[104]), "+f"(d[105]), "+f"(d[106]), "+f"(d[107]), "+f"(d[108]), "+f"(d[109]), "+f"(d[110]), "+f"(d[111]), "+f"(d[112]), "+f"(d[113]), "+f"(d[114]), "+f"(d[115]), "+f"(d[116]), "+f"(d[117]), "+f"(d[118]), "+f"(d[119]), "+f"(d[120]), "+f"(d[121]), "+f"(d[122]), "+f"(d[123]), "+f"(d[124]), "+f"(d[125]), "+f"(d[126]), "+f"(d[127])
      : "l"(da), "l"(db));
  } else {
    asm volatile("{\n.reg .pred p;\nsetp.ne.b32 p, 0, 0;\n"
      "wgmma.mma_async.sync.aligned.m64n256k16.f32.bf16.bf16 "
      "{%0, %1, %2, %3, %4, %5, %6, %7, %8, %9, %10, %11, %12, %13, %14, %15, %16, %17, %18, %19, %20, %21, %22, %23, %24, %25, %26, %27, %28, %29, %30, %31, %32, %33, %34, %35, %36, %37, %38, %39, %40, %41, %42, %43, %44, %45, %46, %47, %48, %49, %50, %51, %52, %53, %54, %55, %56, %57, %58, %59, %60, %61, %62, %63, %64, %65, %66, %67, %68, %69, %70, %71, %72, %73, %74, %75, %76, %77, %78, %79, %80, %81, %82, %83, %84, %85, %86, %87, %88, %89, %90, %91, %92, %93, %94, %95, %96, %97, %98, %99, %100, %101, %102, %103, %104, %105, %106, %107, %108, %109, %110, %111, %112, %113, %114, %115, %116, %117, %118, %119, %120, %121, %122, %123, %124, %125, %126, %127}, "
      "%128, %129, p, 1, 1, 0, 1;\n}\n"
      : "=f"(d[0]), "=f"(d[1]), "=f"(d[2]), "=f"(d[3]), "=f"(d[4]), "=f"(d[5]), "=f"(d[6]), "=f"(d[7]), "=f"(d[8]), "=f"(d[9]), "=f"(d[10]), "=f"(d[11]), "=f"(d[12]), "=f"(d[13]), "=f"(d[14]), "=f"(d[15]), "=f"(d[16]), "=f"(d[17]), "=f"(d[18]), "=f"(d[19]), "=f"(d[20]), "=f"(d[21]), "=f"(d[22]), "=f"(d[23]), "=f"(d[24]), "=f"(d[25]), "=f"(d[26]), "=f"(d[27]), "=f"(d[28]), "=f"(d[29]), "=f"(d[30]), "=f"(d[31]), "=f"(d[32]), "=f"(d[33]), "=f"(d[34]), "=f"(d[35]), "=f"(d[36]), "=f"(d[37]), "=f"(d[38]), "=f"(d[39]), "=f"(d[40]), "=f"(d[41]), "=f"(d[42]), "=f"(d[43]), "=f"(d[44]), "=f"(d[45]), "=f"(d[46]), "=f"(d[47]), "=f"(d[48]), "=f"(d[49]), "=f"(d[50]), "=f"(d[51]), "=f"(d[52]), "=f"(d[53]), "=f"(d[54]), "=f"(d[55]), "=f"(d[56]), "=f"(d[57]), "=f"(d[58]), "=f"(d[59]), "=f"(d[60]), "=f"(d[61]), "=f"(d[62]), "=f"(d[63]), "=f"(d[64]), "=f"(d[65]), "=f"(d[66]), "=f"(d[67]), "=f"(d[68]), "=f"(d[69]), "=f"(d[70]), "=f"(d[71]), "=f"(d[72]), "=f"(d[73]), "=f"(d[74]), "=f"(d[75]), "=f"(d[76]), "=f"(d[77]), "=f"(d[78]), "=f"(d[79]), "=f"(d[80]), "=f"(d[81]), "=f"(d[82]), "=f"(d[83]), "=f"(d[84]), "=f"(d[85]), "=f"(d[86]), "=f"(d[87]), "=f"(d[88]), "=f"(d[89]), "=f"(d[90]), "=f"(d[91]), "=f"(d[92]), "=f"(d[93]), "=f"(d[94]), "=f"(d[95]), "=f"(d[96]), "=f"(d[97]), "=f"(d[98]), "=f"(d[99]), "=f"(d[100]), "=f"(d[101]), "=f"(d[102]), "=f"(d[103]), "=f"(d[104]), "=f"(d[105]), "=f"(d[106]), "=f"(d[107]), "=f"(d[108]), "=f"(d[109]), "=f"(d[110]), "=f"(d[111]), "=f"(d[112]), "=f"(d[113]), "=f"(d[114]), "=f"(d[115]), "=f"(d[116]), "=f"(d[117]), "=f"(d[118]), "=f"(d[119]), "=f"(d[120]), "=f"(d[121]), "=f"(d[122]), "=f"(d[123]), "=f"(d[124]), "=f"(d[125]), "=f"(d[126]), "=f"(d[127])
      : "l"(da), "l"(db));
  }
}
__device__ __forceinline__ void wgmma_n256_ssp_ta0_tb1(float* d, uint64_t da, uint64_t db, int accumulate) {
    asm volatile("{\n.reg .pred p;\nsetp.ne.b32 p, %130, 0;\n"
      "wgmma.mma_async.sync.aligned.m64n256k16.f32.bf16.bf16 "
      "{%0, %1, %2, %3, %4, %5, %6, %7, %8, %9, %10, %11, %12, %13, %14, %15, %16, %17, %18, %19, %20, %21, %22, %23, %24, %25, %26, %27, %28, %29, %30, %31, %32, %33, %34, %35, %36, %37, %38, %39, %40, %41, %42, %43, %44, %45, %46, %47, %48, %49, %50, %51, %52, %53, %54, %55, %56, %57, %58, %59, %60, %61, %62, %63, %64, %65, %66, %67, %68, %69, %70, %71, %72, %73, %74, %75, %76, %77, %78, %79, %80, %81, %82, %83, %84, %85, %86, %87, %88, %89, %90, %91, %92, %93, %94, %95, %96, %97, %98, %99, %100, %101, %102, %103, %104, %105, %106, %107, %108, %109, %110, %111, %112, %113, %114, %115, %116, %117, %118, %119, %120, %121, %122, %123, %124, %125, %126, %127}, "
      "%128, %129, p, 1, 1, 0, 1;\n}\n"
      : "+f"(d[0]), "+f"(d[1]), "+f"(d[2]), "+f"(d[3]), "+f"(d[4]), "+f"(d[5]), "+f"(d[6]), "+f"(d[7]), "+f"(d[8]), "+f"(d[9]), "+f"(d[10]), "+f"(d[11]), "+f"(d[12]), "+f"(d[13]), "+f"(d[14]), "+f"(d[15]), "+f"(d[16]), "+f"(d[17]), "+f"(d[18]), "+f"(d[19]), "+f"(d[20]), "+f"(d[21]), "+f"(d[22]), "+f"(d[23]), "+f"(d[24]), "+f"(d[25]), "+f"(d[26]), "+f"(d[27]), "+f"(d[28]), "+f"(d[29]), "+f"(d[30]), "+f"(d[31]), "+f"(d[32]), "+f"(d[33]), "+f"(d[34]), "+f"(d[35]), "+f"(d[36]), "+f"(d[37]), "+f"(d[38]), "+f"(d[39]), "+f"(d[40]), "+f"(d[41]), "+f"(d[42]), "+f"(d[43]), "+f"(d[44]), "+f"(d[45]), "+f"(d[46]), "+f"(d[47]), "+f"(d[48]), "+f"(d[49]), "+f"(d[50]), "+f"(d[51]), "+f"(d[52]), "+f"(d[53]), "+f"(d[54]), "+f"(d[55]), "+f"(d[56]), "+f"(d[57]), "+f"(d[58]), "+f"(d[59]), "+f"(d[60]), "+f"(d[61]), "+f"(d[62]), "+f"(d[63]), "+f"(d[64]), "+f"(d[65]), "+f"(d[66]), "+f"(d[67]), "+f"(d[68]), "+f"(d[69]), "+f"(d[70]), "+f"(d[71]), "+f"(d[72]), "+f"(d[73]), "+f"(d[74]), "+f"(d[75]), "+f"(d[76]), "+f"(d[77]), "+f"(d[78]), "+f"(d[79]), "+f"(d[80]), "+f"(d[81]), "+f"(d[82]), "+f"(d[83]), "+f"(d[84]), "+f"(d[85]), "+f"(d[86]), "+f"(d[87]), "+f"(d[88]), "+f"(d[89]), "+f"(d[90]), "+f"(d[91]), "+f"(d[92]), "+f"(d[93]), "+f"(d[94]), "+f"(d[95]), "+f"(d[96]), "+f"(d[97]), "+f"(d[98]), "+f"(d[99]), "+f"(d[100]), "+f"(d[101]), "+f"(d[102]), "+f"(d[103]), "+f"(d[104]), "+f"(d[105]), "+f"(d[106]), "+f"(d[107]), "+f"(d[108]), "+f"(d[109]), "+f"(d[110]), "+f"(d[111]), "+f"(d[112]), "+f"(d[113]), "+f"(d[114]), "+f"(d[115]), "+f"(d[116]), "+f"(d[117]), "+f"(d[118]), "+f"(d[119]), "+f"(d[120]), "+f"(d[121]), "+f"(d[122]), "+f"(d[123]), "+f"(d[124]), "+f"(d[125]), "+f"(d[126]), "+f"(d[127])
      : "l"(da), "l"(db), "r"(accumulate));
}

template <int N> __device__ __forceinline__ void quad_sum(float* m) {
#pragma unroll
  for (int o = 1; o <= 2; o <<= 1) {
    float t[N];
#pragma unroll
    for (int i = 0; i < N; i++) t[i] = __shfl_xor_sync(~0u, m[i], o);
#pragma unroll
    for (int i = 0; i < N; i++) m[i] += t[i];
  }
}
__device__ __forceinline__ bool softmax_unsafe(const uint32_t* t, float l0, float l1) {
  const float m0 = fmaxf(bf_lo(t[0]) + bf_hi(t[0]), bf_lo(t[2]) + bf_hi(t[2])), m1 = fmaxf(bf_lo(t[1]) + bf_hi(t[1]), bf_lo(t[3]) + bf_hi(t[3]));
  return __any_sync(~0u, !(m0 * l0 < 2500.f) | !(m1 * l1 < 2500.f));
}
__device__ __forceinline__ void softmax_shift(float* p, float c0, float c1) {
#pragma unroll 1
  for (int it = 0; it < 8; it++) {
    float mx = p[0], mn = p[0];
#pragma unroll
    for (int j = 1; j < 8; j++) { mx = fmaxf(mx, p[(j >> 1) * 4 + (j & 1)]); mn = fminf(mn, p[(j >> 1) * 4 + (j & 1)]); }
#pragma unroll
    for (int o = 1; o <= 2; o <<= 1) { mx = fmaxf(mx, __shfl_xor_sync(~0u, mx, o)); mn = fminf(mn, __shfl_xor_sync(~0u, mn, o)); }
    const float half = fminf(0.5f * (mx - mn), 50.f * rcp(it & 1 ? c1 : c0));
    float r[8];
#pragma unroll
    for (int j = 0; j < 8; j++) {
      const float v = p[(j >> 1) * 4 + (j & 1)];
      r[j] = fmaxf(v - mx + half, 0.f) + fminf(v - mn - half, 0.f) + (v - v);
    }
#pragma unroll
    for (int k = 0; k < 7; k++)
#pragma unroll
      for (int j = 0; j < 8; j++) p[(k >> 1) * 16 + (k & 1) * 2 + (j >> 1) * 4 + (j & 1)] = p[((k + 1) >> 1) * 16 + ((k + 1) & 1) * 2 + (j >> 1) * 4 + (j & 1)];
#pragma unroll
    for (int j = 0; j < 8; j++) p[50 + (j >> 1) * 4 + (j & 1)] = r[j];
  }
}
template <int J0 = 0, int J1 = 8> __device__ __forceinline__ void k_exp(const float* p, float c0, float c1, float* e, float* s) {
#pragma unroll
  for (int j = J0; j < J1; j++) {
    e[2 * j] = ex2(p[2 * j] * (j & 1 ? c1 : c0));
    e[2 * j + 1] = ex2(p[2 * j + 1] * (j & 1 ? c1 : c0));
    e[16 + j] = rcp(e[2 * j] * e[2 * j + 1]);
    const float t = e[2 * j] + e[2 * j + 1];
    s[j & 1] = j < 2 ? t : s[j & 1] + t;
    s[2 + (j & 1)] = j < 2 ? e[16 + j] * t : fmaf(e[16 + j], t, s[2 + (j & 1)]);
  }
}
template <int J0 = 0, int J1 = 8> __device__ __forceinline__ void q_exp(const float* p, float c0, float c1, uint32_t* f) {
#pragma unroll
  for (int j = J0; j < J1; j++) {
    const float e0 = ex2(p[2 * j] * (j & 1 ? c1 : c0)), e1 = ex2(p[2 * j + 1] * (j & 1 ? c1 : c0)), r = rcp(e0 * e1);
    f[j] = pack2(e0, e1);
    f[8 + j] = bmul2(f[j], pack2(r, r));
  }
}

#define FMA8(A, U, X)                                                                                        \
  A[0] = fmaf(bf_lo(U.x), X, A[0]); A[1] = fmaf(bf_hi(U.x), X, A[1]); A[2] = fmaf(bf_lo(U.y), X, A[2]); A[3] = fmaf(bf_hi(U.y), X, A[3]); \
  A[4] = fmaf(bf_lo(U.z), X, A[4]); A[5] = fmaf(bf_hi(U.z), X, A[5]); A[6] = fmaf(bf_lo(U.w), X, A[6]); A[7] = fmaf(bf_hi(U.w), X, A[7])

__device__ __forceinline__ uint32_t routed_row(const __nv_bfloat16* x, uint32_t tag, int lane, uint4* xr) {
  uint32_t best = 0, sv = 0;
#pragma unroll 1
  for (int it = 0; it < SPIN_MAX; it++) {
    const int sel = 2047 - (best & 0x7ff);
#pragma unroll
    for (int i = 0; i < 4; i++) xr[i] = ldg_nc(x + (size_t)sel * DM + i * 256 + lane * 8);
    const unsigned long long st = ld_rlx64(g_stat + sel);
    const uint4 b0 = ld_rlx128(g_best + lane * 2), b1 = ld_rlx128(g_best + 64 + lane * 2);
    const uint32_t m = __reduce_max_sync(~0u, max(max(b0.y == tag ? b0.x : 0u, b0.w == tag ? b0.z : 0u), max(b1.y == tag ? b1.x : 0u, b1.w == tag ? b1.z : 0u)));
    sv = (uint32_t)st;
    if (__all_sync(~0u, b0.y == tag && b0.w == tag && b1.y == tag && b1.w == tag && m == best && (uint32_t)(st >> 32) == tag)) break;
    best = m;
    if (AM_NS) __nanosleep(AM_NS);
  }
  const uint32_t m2 = (sv & 0xffff0000u) | (sv >> 16);
  const float rs = rcp(bf_lo(sv));
#pragma unroll
  for (int i = 0; i < 4; i++) {
    const uint32_t d0 = bsub2(xr[i].x, m2), d1 = bsub2(xr[i].y, m2), d2 = bsub2(xr[i].z, m2), d3 = bsub2(xr[i].w, m2);
    xr[i] = make_uint4(pack2(bf_lo(d0) * rs, bf_hi(d0) * rs), pack2(bf_lo(d1) * rs, bf_hi(d1) * rs), pack2(bf_lo(d2) * rs, bf_hi(d2) * rs),
                       pack2(bf_lo(d3) * rs, bf_hi(d3) * rs));
  }
  return best;
}

struct Params {
  const __nv_bfloat16 *x, *wqkv, *wo, *w_r, *w_down;
  uint32_t zA, zB;
};

template <bool BY_SMID> __global__ void __launch_bounds__(384, 1)
fused_kernel(const Params P, const __grid_constant__ CUtensorMap mX, const __grid_constant__ CUtensorMap mWkv, const __grid_constant__ CUtensorMap mWq,
             const __grid_constant__ CUtensorMap mWo, const __grid_constant__ CUtensorMap mPhi, const __grid_constant__ CUtensorMap mWp,
             const __grid_constant__ CUtensorMap mOut, const __grid_constant__ CUtensorMap mWc,
             const __grid_constant__ CUtensorMap mG, const __grid_constant__ CUtensorMap mU, const __grid_constant__ CUtensorMap mD,
             const __grid_constant__ CUtensorMap mXs, const __grid_constant__ CUtensorMap mG2, const __grid_constant__ CUtensorMap mU2) {
  constexpr uint32_t sb = SB, bar = SB + SM_BAR;
  int bid = blockIdx.x;
  if (BY_SMID) {
    uint32_t sm;
    asm volatile("mov.u32 %0, %%smid;" : "=r"(sm));
    const uint32_t tq = (sm - 64) >> 1, q7 = (tq * 37) >> 8;
    const uint32_t gpc = sm < 64 ? (sm >> 1) & 7 : 1 + tq - 7 * q7, idx = (sm < 64 ? sm >> 4 : 4 + q7) * 2 + (sm & 1);
    bid = sm < 120 ? ((PTAB >> (4 * gpc)) & 7) * 16 + idx : sm < 124 ? sm + 8 : sm - 116;
  }
  const int hg = ((bid >> 2) & 3) + 4 * ((bid >> 4) & 1), mb = (bid & 3) + 4 * ((bid >> 5) & 3);
  if (bid < NCTA && threadIdx.x < 256) {
    const uint32_t r0 = threadIdx.x >> 3, c = threadIdx.x & 7, dst = sb + 2 * KV_STAGE + r0 * 128 + ((c ^ (r0 & 7)) << 4);
    const char* xs = (const char*)P.x + (size_t)(mb * 128 + r0) * 2048 + c * 16;
    const char* ws = (const char*)P.wqkv + (size_t)r0 * 6144 + 2048 + hg * 256 + c * 16;
#pragma unroll
    for (int i = 0; i < 4; i++) cp_async16(dst + i * 4096, xs + i * 65536);
#pragma unroll
    for (int i = 0; i < 8; i++) cp_async16(dst + 16384 + i * 4096, ws + (i & 1) * 196608 + (i >> 2) * 2048 + ((i >> 1) & 1) * 128);
  }
  extern __shared__ __align__(1024) uint8_t smem[];
  if (smem_u32(smem) != SB) __trap();
  const int warp = __shfl_sync(~0u, threadIdx.x >> 5, 0);

  if (bid >= NCTA) {
    constexpr uint32_t XV = SM_WPHI, ONES = SM_ZT, BF = bar, BE = bar + 48, BX = bar + 96;
    constexpr int NJ = (DM - GROWS) / 64;
    const int lane = lane_id(), sp = bid - NCTA;
    const uint32_t tag = ld_rlx(g_epoch + bid * 32 + lane) + 1;
    if (warp == 8 && elect_one()) {
#pragma unroll 1
      for (int i = 0; i < 13; i++) mbar_init(bar + 8 * i, i >= 6 && i < 12 ? 8 : 1);
    }
    if (warp == 9) { sts64u(sb + ONES + lane * 8, 0x3f803f80u, 0x3f803f80u); fence_async_smem(); }
    __syncthreads();
    if (warp == 8) {
      if (elect_one()) {
        uint32_t s = 0, ph = 1;
        for (const long long c0 = clock64(); clock64() - c0 < SP_DELAY;) {}
#pragma unroll 1
        for (int job = 0; job < 8; job++) {
          const CUtensorMap* m = job == 0 ? &mWq : sp & 2 ? &mU2 : &mG2;
          const int g0 = job ? (sp & 1) * 28 + job * 4 - 4 : sp * 4;
#pragma unroll 1
          for (int row = job ? GROWS : 0; row < DM; row += 64) {
            mbar_wait(BE + 8 * s, ph);
            mbar_expect_tx(BF + 8 * s, Q_STAGE);
            tma4d(sb + s * Q_STAGE, m, 0, row, g0, 0, BF + 8 * s);
            tma4d(sb + s * Q_STAGE + 16384, m, 0, row, g0 + 2, 0, BF + 8 * s);
            if (++s == 6) { s = 0; ph ^= 1; }
          }
        }
      }
    } else if (warp == 9) {
      uint4 xr[4];
      routed_row(P.x, tag, lane, xr);
#pragma unroll
      for (int i = 0; i < 4; i++) sts128u(sb + XV + i * 512 + lane * 16, xr[i].x, xr[i].y, xr[i].z, xr[i].w);
      fence_async_smem();
      __syncwarp();
      if (lane == 0) mbar_arrive(BX);
    } else if (warp < 8) {
      uint32_t s = 0, ph = 0;
#pragma unroll 1
      for (int job = 0; job < 8; job++) {
        float d[8] = {0.f, 0.f, 0.f, 0.f, 0.f, 0.f, 0.f, 0.f};
        if (job == 1) mbar_wait(BX, 0);
#pragma unroll 1
        for (int i = 0; i < (job ? NJ : 16); i++) {
          mbar_wait(BF + 8 * s, ph);
          wg_fence();
#pragma unroll
          for (int k = 0; k < 8; k++)
            wgmma_n8_ss_ta1_tb0(d + 4 * (k >> 2), mkdesc(sb + k * 2048, 16, 1024, 1, s * (Q_STAGE / 16) + (warp >> 2) * 1024),
                                mkdesc(sb, 16, 128, 0, job ? (XV + GROWS * 2) / 16 + i * 8 + (k & 3) * 2 : ONES / 16), 1);
          wg_commit();
          wg_wait<0>();
          if (lane == 0) mbar_arrive(BE + 8 * s);
          if (++s == 6) { s = 0; ph ^= 1; }
        }
        reg_fence<8>(d);
        float* dst = (job ? g_gp + sp * 1792 + job * 256 - 256 : g_cs + sp * 256) + (warp >> 2) * 128 + (warp & 3) * 16 + (lane >> 2);
        if ((lane & 3) == 0) {
#pragma unroll
          for (int i = 0; i < 4; i++) st_rlx(dst + (i >> 1) * 64 + (i & 1) * 8, mark(__float_as_uint(d[2 * i]), tag & 1));
        }
        __syncwarp();
      }
      if (warp == 0) g_epoch[bid * 32 + lane] = tag;
    }
    return;
  }
#define Q_SLAB(J) ((J) < 8 ? ((J) + 8 - 2 * (hg & 4)) & 15 : 2 * (hg & 4) + 2 * ((J) & 3) + ((J) >> 2 & 1))
#define Q_AOFF(J) ((J) == 8 + (hg & 3) ? SM_X0 : (J) == 12 + (hg & 3) ? SM_X1 : ((J) & 3) * Q_STAGE)
#define Q_LOAD(J)                                                                                            \
  do {                                                                                                       \
    const uint32_t fb_ = bar + B_FULLQ + 8 * ((J) & 3);                                                      \
    const int k_ = Q_SLAB(J) * 64;                                                                           \
    mbar_expect_tx(fb_, Q_STAGE);                                                                            \
    mbar_arrive2(fb_);                                                                                       \
    tma2d(sb + Q_AOFF(J), &mX, k_, mb * 128, fb_);                                                           \
    tma4d(sb + ((J) & 3) * Q_STAGE + 16384, &mWq, 0, k_, hg * 2, 0, fb_);                                    \
  } while (0)
  if (warp >= 8) {
    asm volatile("setmaxnreg.dec.sync.aligned.u32 %0;" ::"n"(REG_H));
    const int lane = lane_id();
    const int f = (warp - 9) & 3;
    if (f == 3) {
      if (elect_one()) {
        PROF(0); PROFT(32);
#pragma unroll
        for (int s = 0; s < 3; s++) mbar_init(bar + B_FULLKV + 8 * s, 1);
      }
      __syncwarp();
      asm volatile("bar.arrive 14, 288;" ::: "memory");
      if (elect_one()) {
#pragma unroll
        for (int s = 0; s < 2; s++) {
          mbar_expect_tx(bar + B_FULLKV + 8 * s, KV_STAGE);
          tma2d(sb + s * KV_STAGE, &mX, (s + 1) * 64, mb * 128, bar + B_FULLKV + 8 * s);
          tma4d(sb + s * KV_STAGE + 16384, &mWkv, 0, (s + 1) * 64, hg * 2, 1, bar + B_FULLKV + 8 * s);
        }
      }
      __syncwarp();
    }
    const uint32_t ep = ld_rlx(g_epoch + bid * 32 + lane);
    if (f < 2) {
#pragma unroll
      for (int i = 0; i < 2; i++) {
        const uint4 u = __ldg((const uint4*)P.w_r + (f * 2 + i) * 32 + lane);
        sts128u(sb + SM_XSEL + (f * 2 + i) * 512 + lane * 16, u.x, u.y, u.z, u.w);
      }
    }
    bar_sync(13, 384);
    const uint32_t tag = ep + 1, par = tag & 1;
    const bool ffn = bid < NFFN;
    const int fb = bid, cu = bid >> 1, ch = bid & 1;
#define CS_STORE(SEC, C)                                                                                     \
  _Pragma("unroll") for (int r = 0; r < 3; r++) {                                                            \
    const uint32_t h0 = pack2(C.x, C.y), h1 = pack2(C.z, C.w);                                               \
    sts64u(sb + SM_CST + (SEC) * 1024 + (lane >> 4) * 512 + (lane & 1) * 8 + r * 128 + ((((lane & 15) >> 1) ^ (r + (lane >> 4) * 4)) << 4), h0, h1); \
    C.x -= bf_lo(h0); C.y -= bf_hi(h0); C.z -= bf_lo(h1); C.w -= bf_hi(h1);                                  \
  }
#define BAD4(U) ((U.x ^ par) | (U.y ^ par) | (U.z ^ par) | (U.w ^ par))
    const int n0 = f < 2 ? 0 : 2 * f - 3, ne = FFN_OFF || !ffn ? 3 : f == 3 ? 3 + G8 : 3 + GN;
    const uint32_t fsb = sb + SM_FST + ((f + 1) & 3) * 8192, fbar = bar + B_FST + f * 16, fst = fsb + (lane >> 4) * 2048 + (lane & 15) * 16;
    const CUtensorMap *ma = &mWc, *mc = &mWc;
    int sx = 1024 + cu * 32, sy = ch * 512 + f * 192, sdy = 32;
#define STAGEG(N)                                                                                            \
  do {                                                                                                       \
    if ((N) == 3) { ma = &mG; mc = &mU; sx = fb * 32; sy = f * (GN * 32);  sdy = 0; }                        \
    if ((N) < ne && elect_one()) {                                                                           \
      const uint32_t dst_ = fsb + ((N) & 1) * 4096, b_ = fbar + ((N) & 1) * 8;                               \
      mbar_expect_tx(b_, 4096);                                                                              \
      tma2d(dst_, ma, sx, sy, b_);                                                                           \
      tma2d(dst_ + 2048, mc, sx, sy + sdy, b_);                                                              \
    }                                                                                                        \
    sy += 32 + sdy;                                                                                          \
  } while (0)
    float a[8], gsum = 0.f, usum = 0.f;
    {
      if (f == 3) {
        if (elect_one()) {
          mbar_expect_tx(bar + B_XST, 16384);
          tma3d(sb + SM_XST, &mXs, 0, bid * 16, 0, bar + B_XST);
          mbar_expect_tx(bar + B_WPHI, 8192);
          tma2d(sb + SM_WPHI, &mPhi, 0, hg * 128, bar + B_WPHI);
          prefetch_map(&mWq); prefetch_map(&mWo); prefetch_map(&mWp); prefetch_map(&mD);
          PROF(31);
        }
        __syncwarp();
      } else {
        if (lane == 0) prefetch_map(f == 0 ? &mWc : f == 1 ? &mG : &mU);
        if (f == 2) ((float2*)g_y[par])[bid * 32 + lane] = make_float2(0.f, 0.f);
      }
      float st[13];
#pragma unroll
      for (int i = 0; i < 13; i++) st[i] = 0.f;
#pragma unroll 1
      for (int i = 0; i < 4; i++) {
        mbar_wait(bar + B_XST + 8 * (i >> 1), 0);
        if (f == 0 && lane == 0 && i == 0) PROF(1);
        const uint4 wu = lds128u(sb + SM_XSEL + i * 512 + lane * 16);
        const float wf[8] = {bf_lo(wu.x), bf_hi(wu.x), bf_lo(wu.y), bf_hi(wu.y), bf_lo(wu.z), bf_hi(wu.z), bf_lo(wu.w), bf_hi(wu.w)};
        st[12] += ((wf[0] + wf[1]) + (wf[2] + wf[3])) + ((wf[4] + wf[5]) + (wf[6] + wf[7]));
#pragma unroll
        for (int r = 0; r < 4; r++) {
          const uint4 u = lds128u(sb + SM_XST + i * 8192 + (4 * f + r) * 512 + lane * 16);
          const float xf[8] = {bf_lo(u.x), bf_hi(u.x), bf_lo(u.y), bf_hi(u.y), bf_lo(u.z), bf_hi(u.z), bf_lo(u.w), bf_hi(u.w)};
#pragma unroll
          for (int k = 0; k < 8; k++) { st[r] += xf[k]; st[4 + r] = fmaf(xf[k], xf[k], st[4 + r]); st[8 + r] = fmaf(xf[k], wf[k], st[8 + r]); }
        }
        if (i >= 2 && f < 3) STAGEG(n0 + i - 2);
      }
      const bool up = lane & 16, up2 = lane & 8;
#pragma unroll
      for (int q = 0; q < 3; q++) {
        const float k0 = up ? st[4 * q + 2] : st[4 * q], k1 = up ? st[4 * q + 3] : st[4 * q + 1];
        const float o0 = up ? st[4 * q] : st[4 * q + 2], o1 = up ? st[4 * q + 1] : st[4 * q + 3];
        const float m0 = k0 + __shfl_xor_sync(~0u, o0, 16), m1 = k1 + __shfl_xor_sync(~0u, o1, 16);
        a[q] = (up2 ? m1 : m0) + __shfl_xor_sync(~0u, up2 ? m0 : m1, 8);
      }
      a[3] = st[12] + __shfl_xor_sync(~0u, st[12], 16);
      a[3] += __shfl_xor_sync(~0u, a[3], 8);
#pragma unroll
      for (int o = 4; o; o >>= 1)
#pragma unroll
        for (int q = 0; q < 4; q++) a[q] += __shfl_xor_sync(~0u, a[q], o);
      if ((lane & 7) == 0) sts128(sb + SM_ROWS + (4 * f + (lane >> 3)) * 16, a[0], a[1], a[2], a[3]);
      if (f < 3) asm volatile("bar.arrive 7, 128;" ::: "memory");
    }
    if (f == 3) {
      bar_sync(7, 128);
      const int row = bid * 16 + (lane & 15);
      const float4 v = lds128(sb + SM_ROWS + (lane & 15) * 16);
      const float mf = v.x * (1.f / DM), mean = bf_round(mf), var = fmaxf(fmaf(-mf, mf, v.y * (1.f / DM)), 0.f);
      const float sd = bf_round(sqrt_approx(bf_round(bf_round(var) + 1e-5f)));
      const uint32_t rb = pack2(fmaf(-mean, v.w, v.z) * rcp(sd), 0.f) & 0xffffu, ord = (rb & 0x8000u) ? (~rb & 0xffffu) : (rb | 0x8000u);
      uint32_t best = __reduce_max_sync(~0u, (ord << 16) | (uint32_t)(2047 - row));
      if (lane < 16) st_rlx64(g_stat + row, ((unsigned long long)tag << 32) | __float_as_uint(mean) | (__float_as_uint(sd) >> 16));
      if (lane == 0) { asm volatile("red.relaxed.gpu.global.max.u64 [%0], %1;" ::"l"(g_best + bid), "l"(((unsigned long long)tag << 32) | best) : "memory"); PROF(17); }
#pragma unroll 1
      for (int n = 3; n < 5; n++) STAGEG(n);
      {
        uint4 xr[4];
        best = routed_row(P.x, tag, lane, xr);
#pragma unroll
        for (int i = 0; i < (GROWS + 255) / 256; i++) {
          const uint32_t dst = sb + SM_XSEL + i * 1024 + (lane >> 2) * 128 + (lane & 3) * 8;
          sts64(dst, bf_lo(xr[i].x), bf_lo(xr[i].z)); sts64(dst + 32, bf_hi(xr[i].x), bf_hi(xr[i].z));
          sts64(dst + 64, bf_lo(xr[i].y), bf_lo(xr[i].w)); sts64(dst + 96, bf_hi(xr[i].y), bf_hi(xr[i].w));
        }
        sts64u(sb + SM_RED + 16, tag, best);
        __syncwarp();
        if (lane == 0) { mbar_arrive(bar + B_XS); PROF(19); }
      }
      unsigned long long sv4[4];
      uint4 u[4];
#pragma unroll 1
      for (int it = 0; it < SPIN_MAX; it++) {
#pragma unroll
        for (int i = 0; i < 4; i++) { u[i] = ld_rlx128(g_cs + (1 + i) * 1024 + hg * 128 + lane * 4); sv4[i] = ld_rlx64(g_stat + mb * 128 + i * 32 + lane); }
        bool ok = ((BAD4(u[0]) | BAD4(u[1]) | BAD4(u[2]) | BAD4(u[3])) & 1) == 0;
#pragma unroll
        for (int i = 0; i < 4; i++) ok = ok && (uint32_t)(sv4[i] >> 32) == tag;
        if (__all_sync(~0u, ok)) break;
        __nanosleep(200);
      }
#pragma unroll
      for (int i = 0; i < 4; i++) {
        const uint32_t sv = (uint32_t)sv4[i], sd2 = (sv << 16) | (sv & 0xffffu);
        sts64(sb + SM_STAT + (i * 32 + lane) * 8, -bf_hi(sv), rcp(bf_lo(sv)));
        sts128u(sb + SM_SDT + lane * 64 + ((i ^ ((lane >> 1) & 3)) << 4), sd2, sd2, sd2, sd2);
      }
#pragma unroll
      for (int i = 0; i < 2; i++) {
        float4 c = make_float4(unmark(u[i].x) + unmark(u[i + 2].x), unmark(u[i].y) + unmark(u[i + 2].y), unmark(u[i].z) + unmark(u[i + 2].z),
                               unmark(u[i].w) + unmark(u[i + 2].w));
        CS_STORE(i, c);
      }
      fence_async_smem();
      bar_sync(8, 64);
      if (lane == 0) { mbar_arrive(bar + B_CS); PROF(10); }
    }
    {
      uint32_t xa = sb + SM_RED + 32, xstep = 0;
      const uint32_t zero = __float_as_uint(lds32(sb + SM_RED + 12));
#pragma unroll 1
      for (int ph = f == 3; ph < 2; ph++) {
#pragma unroll
        for (int j = 0; j < 8; j++) a[j] = 0.f;
        if (ph && f == 0) {
        {
          mbar_wait(bar + B_WPHI, 0);
          float nq[8] = {0.f, 0.f, 0.f, 0.f, 0.f, 0.f, 0.f, 0.f};
  #pragma unroll 2
          for (int r = 0; r < 16; r++) {
            const uint4 u = lds128u(sb + SM_WPHI + ((lane >> 2) * 16 + r) * 64 + (((lane ^ (r >> 1)) & 3) << 4));
            nq[0] = fmaf(bf_lo(u.x), bf_lo(u.x), nq[0]); nq[1] = fmaf(bf_hi(u.x), bf_hi(u.x), nq[1]); nq[2] = fmaf(bf_lo(u.y), bf_lo(u.y), nq[2]);
            nq[3] = fmaf(bf_hi(u.y), bf_hi(u.y), nq[3]); nq[4] = fmaf(bf_lo(u.z), bf_lo(u.z), nq[4]); nq[5] = fmaf(bf_hi(u.z), bf_hi(u.z), nq[5]);
            nq[6] = fmaf(bf_lo(u.w), bf_lo(u.w), nq[6]); nq[7] = fmaf(bf_hi(u.w), bf_hi(u.w), nq[7]);
          }
          uint32_t m = 0;
  #pragma unroll
          for (int i = 0; i < 8; i++) m = max(m, __float_as_uint(nq[i] + __shfl_xor_sync(~0u, nq[i], 4)) & 0x7fffffffu);
          sts32(sb + SM_RED + 24, 4.2f * __uint_as_float(__reduce_max_sync(~0u, m)));
        }
          asm volatile("bar.arrive 8, 64;" ::: "memory");
        }
        if (ph) { mbar_wait(bar + B_XS, 0); xa = sb + SM_XSEL + f * (GN * 128) + ((lane >> 2) & 3) * 32; xstep = 128; }
#pragma unroll 1
        for (int n = ph ? 3 : n0; n < (ph ? ne : 3); n++) {
          const float4 x0 = lds128(xa), x1 = lds128(xa + 16);
          xa += xstep;
          mbar_wait(fbar + (n & 1) * 8, ((n - n0) >> 1) & 1);
          uint4 u[8];
#pragma unroll
          for (int j = 0; j < 8; j++) u[j] = lds128u(fst + (n & 1) * 4096 + j * 256);
          FMA8(a, u[0], x0.x); FMA8(a, u[1], x0.y); FMA8(a, u[2], x0.z); FMA8(a, u[3], x0.w);
          if (__any_sync(~0u, ((u[4].x | u[5].x | u[6].x | u[7].x | __float_as_uint(a[0]) | __float_as_uint(a[7])) & zero) == 0)) STAGEG(n + 2);
          FMA8(a, u[4], x1.x); FMA8(a, u[5], x1.y); FMA8(a, u[6], x1.z); FMA8(a, u[7], x1.w);
        }
#pragma unroll
        for (int o = 4; o <= 8; o <<= 1)
#pragma unroll
          for (int j = 0; j < 8; j++) a[j] += __shfl_xor_sync(~0u, a[j], o);
        if (ph && lane == 0) mbar_arrive(bar + B_FFN);
        const uint32_t red = ph ? sb + SM_GRED : sb + SM_RED + 64;
        if ((lane & 12) == 0) {
          const uint32_t d = red + f * 256 + (lane >> 4) * 128 + (lane & 3) * 32;
          sts128(d, a[0], a[1], a[2], a[3]); sts128(d + 16, a[4], a[5], a[6], a[7]);
        }
        if (f != 2) {
          asm volatile("bar.arrive %0, %1;" ::"r"(4 + ph), "r"(96 + 32 * ph) : "memory");
        } else {
          bar_sync(4 + ph, 96 + 32 * ph);
          const uint32_t ra = red + lane * 4;
          gsum = lds32(ra) + lds32(ra + 256) + lds32(ra + 512);
          usum = lds32(ra + 128) + lds32(ra + 384) + lds32(ra + 640);
          if (!ph) st_rlx(g_cs + 1024 + ch * 2048 + cu * 32 + lane, mark(__float_as_uint(gsum + usum), par));
          else { gsum += lds32(ra + 768); usum += lds32(ra + 896); }
          if (lane == 0) PROF(ph ? 34 : 18);
        }
      }
    }
    if (f == 3) {
      if (elect_one()) {
        PROF(7);
        mbar_wait(bar + B_FULLQ, 0);
#pragma unroll 1
        for (int j = 3; j < 16; j++) {
          mbar_wait(bar + (j < 4 ? B_EMPTYKV + 16 : B_EMPTYQ + 8 * (j & 3)), ((j >> 2) & 1) ^ 1);
          if (j == 12 + (hg & 3)) mbar_wait(bar + B_KVST + 8, 0);
          Q_LOAD(j);
        }
        PROF(47);
        mbar_expect_tx(bar + B_DN, 65536);
#pragma unroll 1
        for (int i = 0; i < 4; i++) {
          mbar_wait(bar + B_EMPTYQ + 8 * i, 1);
          tma3d(sb + i * Q_STAGE, &mD, 0, fb * 32, i * 4, bar + B_DN);
        }
        PROF(48);
#pragma unroll 1
        for (int i = 0; i < 16; i++) {
          const int s = i & 3, n = i < 9 ? i - 2 : i - 9, kb = i < 2 ? 2 * hg + i : 2 * (n + (n >= hg)) + (i >= 9);
          if (i >= 4) mbar_wait(bar + B_EMPTYQ + 8 * s, ((i >> 2) & 1) ^ 1);
          mbar_expect_tx(bar + B_FULLQ + 8 * s, 16384);
          if (i < 2) {
            mbar_arrive2(bar + B_FULLQ + 8 * s);
            tma3d(sb + s * Q_STAGE + 16384, &mWo, 0, kb * 64, hg * 2, bar + B_FULLQ + 8 * s);
          } else {
            tma5d(sb + s * Q_STAGE + 16384, &mWp, hg * 128, kb * 2, bar + B_FULLQ + 8 * s);
            tma5d(sb + s * Q_STAGE + 24576, &mWp, hg * 128 + 64, kb * 2, bar + B_FULLQ + 8 * s);
            if (i >= 3) {
              if (i == 3) { mbar_wait(bar + B_DND, 0); PROF(14); }
#pragma unroll 1
              for (int a = i == 3 ? 2 : i; a <= i; a++) {
                const uint4* src = g_ofr + (mb * 16 + (a == 2 ? (hg == 0 ? 2 : 0) : kb)) * 1024;
#pragma unroll
                for (int h = 0; h < 2; h++) {
                  mbar_expect_tx(bar + B_AIN + (a & 3) * 16 + h * 8, 8192);
                  bulk_load(sb + (a & 3) * Q_STAGE + h * 8192, src + h * 512, 8192, bar + B_AIN + (a & 3) * 16 + h * 8);
                }
              }
            }
          }
        }
      }
    } else {
      if (f == 2) {
        if (PFD && ffn) {
#pragma unroll 1
          for (int i = 0; i < 16; i++) { touch_l2((const char*)P.w_down + fb * 65536 + i * 4096 + lane * 128, lane); __nanosleep(PFD); }
        }
        {
#pragma unroll 1
          for (int i = 0; i < 8; i++) { touch_l2((const char*)P.wo + ((mb & 7) * 128 + i * 16 + (lane >> 1)) * 2048 + hg * 256 + (lane & 1) * 128, lane); __nanosleep(PFD); }
        }
        asm volatile("cp.async.wait_all;" ::: "memory");
        uint4 u;
#pragma unroll 1
        for (int it = 0; it < SPIN_MAX; it++) {
          u = ld_rlx128(g_cs + hg * 128 + lane * 4);
          if (__all_sync(~0u, !(BAD4(u) & 1))) break;
          __nanosleep(200);
        }
        mbar_wait(bar + B_PHI, 0);
        float4 c = make_float4(unmark(u.x), unmark(u.y), unmark(u.z), unmark(u.w));
        CS_STORE(2, c);
        fence_async_smem();
        __syncwarp();
        if (lane == 0) mbar_arrive(bar + B_CSQ);
      }
      const uint32_t target = __shfl_sync(~0u, tag, 0) * 16;
#pragma unroll 1
      for (int R = 0; R < 2; R++) {
        const uint32_t own = (hg * 2 + R) * 16 + mb, pst = sb + (R ? SM_PST1 : SM_PST0);
        if (f == R) {
          mbar_wait(bar + B_KVST + 8 * R, 0);
          if (f == 1 && lane == 0) PROF(11);
          wait_hint(XC1(hg, R) + mb, target);
          if (elect_one()) {
            PROF(35 + R);
            fence_async_global();
            mbar_expect_tx(bar + B_PART + 8 * R, 8192);
            bulk_load(pst, g_part + own * 512, 8192, bar + B_PART + 8 * R);
          }
          __syncwarp();
          uint4 uz;
#pragma unroll 1
          for (int it = 0; it < SPIN_MAX; it++) {
            uz = ld_rlx128(g_zpart + own * 128 + lane * 4);
            if (__all_sync(~0u, !(BAD4(uz) & 1))) break;
          }
          const bool b1 = lane & 2, b2 = lane & 4;
          const float z0 = unmark(b1 ? uz.z : uz.x) + __shfl_xor_sync(~0u, unmark(b1 ? uz.x : uz.z), 2);
          const float z1 = unmark(b1 ? uz.w : uz.y) + __shfl_xor_sync(~0u, unmark(b1 ? uz.y : uz.w), 2);
          float z = (b2 ? z1 : z0) + __shfl_xor_sync(~0u, b2 ? z0 : z1, 4);
          z += __shfl_xor_sync(~0u, z, 8);
          z += __shfl_xor_sync(~0u, z, 16);
          if (lane < 8) {
            const uint32_t ft = (own & 7) * 8 + (lane & 1) * 4 + (lane & 2) + (lane >> 2), zz = pack2(z, 1.f);
            const uint32_t pos = (own >> 3) * 64 + (ft & 15) * 4 + (((ft >> 4) ^ (ft >> 1)) & 3);
            st_rlx128(g_zres[par] + pos, zz, zz, zz, zz);
            g_zres[par ^ 1][pos] = make_uint4(0u, 0u, 0u, 0u);
          }
          if (lane == 0) red_inc(XC2(hg, R));
          __syncwarp();
        }
        if (f == R || f == R + 1) {
          const uint32_t hf = f - R, m1 = ~lane & 1, gq = hf * 4 + (lane >> 3), ts = (lane >> 1) & 3;
          float a0 = 0.f, a1 = 0.f, a2 = 0.f, a3 = 0.f;
          mbar_wait(bar + B_PART + 8 * R, 0);
#pragma unroll 1
          for (int it = 0; it < SPIN_MAX; it++) {
            uint32_t bad = 0;
            a0 = a1 = a2 = a3 = 0.f;
#pragma unroll 1
            for (int b = 0; b < 16; b += 8) {
              uint2 u[8];
              if (it == 0) {
#pragma unroll
                for (int i = 0; i < 8; i++) { const float2 v = lds64(pst + (b + i) * 512 + hf * 256 + lane * 8); u[i] = make_uint2(__float_as_uint(v.x), __float_as_uint(v.y)); }
              } else {
#pragma unroll
                for (int i = 0; i < 8; i++) {
                  const unsigned long long v = ld_rlx64((const unsigned long long*)g_part + own * 1024 + (b + i) * 64 + hf * 32 + lane);
                  u[i] = make_uint2((uint32_t)v, (uint32_t)(v >> 32));
                }
              }
#pragma unroll
              for (int i = 0; i < 8; i++) {
                bad |= u[i].x ^ par;
                a0 += bf_lo(i & 1 ? u[i].x & ~m1 : u[i].x | m1); a1 += bf_hi(u[i].x); a2 += bf_lo(u[i].y); a3 += bf_hi(u[i].y);
              }
            }
            if (__all_sync(~0u, !(bad & m1))) break;
          }
          uint32_t* dst = (uint32_t*)g_res[par] + own * 128 + gq * 16 + ts;
          const uint32_t j0 = (lane & 1) * 2, vb = ts == (gq >> 1);
          st_rlx(dst + ((j0 ^ (gq >> 1)) & 3) * 4, pack2(a0, a1) | vb);
          st_rlx(dst + (((j0 + 1) ^ (gq >> 1)) & 3) * 4, pack2(a2, a3) | vb);
          ((uint2*)g_res[par ^ 1])[own * 64 + hf * 32 + lane] = make_uint2(0u, 0u);
          __syncwarp();
          if (lane == 0) { red_inc(XC2(hg, R)); if (!hf) PROF(R ? 12 : 30); }
        }
      }
      if (f == 2) {
        if (ffn && !FFN_OFF) {
#pragma unroll 1
          for (int it = 0; it < SPIN_MAX; it++) {
            const uint32_t pg = ld_rlx((const uint32_t*)g_gp + fb * 32 + lane), pu = ld_rlx((const uint32_t*)g_gp + FF + fb * 32 + lane);
            if (__all_sync(~0u, !(((pg ^ par) | (pu ^ par)) & 1))) { gsum += unmark(pg); usum += unmark(pu); break; }
            __nanosleep(200);
          }
        }
        const float h = bf_round(silu_f(bf_round(gsum))) * bf_round(usum);
        const uint32_t h2 = pack2(h, h);
        sts128u(sb + SM_HT + lane * 16, h2, h2, h2, h2);
        fence_async_smem();
        __syncwarp();
        if (lane == 0) { mbar_arrive(bar + B_H); PROF(20); }
      }
      if (f < 2) {
        wait_hint(XC2(hg, f), 3 * target);
        mbar_wait(bar + B_KVST + 8, 0);
        if (lane == 0) PROF(40 + f);
#pragma unroll 1
        for (int it = 0; it < SPIN_MAX; it++) {
          if (elect_one()) {
            fence_async_global();
            mbar_expect_tx(bar + B_RES + 8 * f, 8192 + 2048);
            bulk_load(sb + SM_V + f * 8192, g_res[par] + (hg * 4 + f * 2) * 256, 8192, bar + B_RES + 8 * f);
            bulk_load(sb + SM_ZT + f * 2048, g_zres[par] + (hg * 4 + f * 2) * 64, 2048, bar + B_RES + 8 * f);
          }
          __syncwarp();
          mbar_wait(bar + B_RES + 8 * f, it & 1);
          uint32_t ok = ~0u;
#pragma unroll
          for (int i = 0; i < 16; i++) ok &= __float_as_uint(lds32(sb + SM_V + f * 8192 + i * 512 + lane * 16 + (lane >> 3) * 4));
#pragma unroll
          for (int i = 0; i < 4; i++) ok &= __float_as_uint(lds32(sb + SM_ZT + f * 2048 + i * 512 + lane * 16 + (lane >> 3) * 4)) >> 23;
          if (__all_sync(~0u, ok & 1)) break;
        }
        if (lane == 0) { mbar_arrive(bar + B_TILE + 8 * f); PROF(f ? 13 : 27); }
      }
      if (f < 2) {
        uint32_t phases = 0;
#pragma unroll 1
        for (int i = 2; i < 16; i++) {
          const int s = i & 3;
          const uint32_t ab = bar + B_AIN + s * 16 + f * 8, slot = sb + s * Q_STAGE + f * 8192;
#pragma unroll 1
          for (int it = 0; it < SPIN_MAX; it++) {
            mbar_wait(ab, (phases >> s) & 1);
            phases ^= 1u << s;
            uint32_t bad = 0;
#pragma unroll
            for (int n = 0; n < 8; n++) bad |= __float_as_uint(lds32(slot + n * 1024 + lane * 32 + (lane >> 2) * 4)) ^ par;
            if (__all_sync(~0u, !(bad & 1))) break;
            if (elect_one()) {
              const int n = i < 9 ? i - 2 : i - 9, kb = 2 * (n + (n >= hg)) + (i >= 9);
              PROF(49);
              mbar_expect_tx(ab, 8192);
              bulk_load(slot, g_ofr + (mb * 16 + kb) * 1024 + f * 512, 8192, ab);
            }
            __syncwarp();
          }
          if (lane == 0) { mbar_arrive(bar + B_FULLQ + 8 * s); if (i == 2 && f == 0) PROF(15); }
        }
        if (f == 0) g_epoch[bid * 32 + lane] = tag;
      } else {
        if (elect_one()) {
          prefetch_map(&mOut);
          if (ffn) { mbar_wait(bar + B_YD, 0); red_rel(g_ycnt); PROF(21); }
        }
        __syncwarp();
        if (f == 2) {
          const uint32_t best = __float_as_uint(lds32(sb + SM_RED + 20));
          const int sel = 2047 - (best & 0x7ff) - mb * 128;
          if (sel >= 0 && sel < 128) {
            const uint2 xr = __ldg((const uint2*)(P.x + (size_t)(mb * 128 + sel) * DM + hg * 128 + lane * 4));
            const float2 st = lds64(sb + SM_STAT + sel * 8);
            const uint32_t ord = best >> 16, rb = (ord & 0x8000u) ? (ord & 0x7fffu) : (~ord & 0xffffu);
            const float sg = rcp(1.f + ex2(-1.4426950408889634f * bf_lo(rb)));
            const uint32_t sg2 = pack2(sg, sg), nm2 = pack2(st.x, st.x);
            wait_cnt<0>(g_ycnt, tag * NFFN);
            float4 y = make_float4(0.f, 0.f, 0.f, 0.f);
#pragma unroll
            for (int i = 0; i < 8; i++) {
              const float4 c = ldg_cg4(g_y[par ^ 1][i] + hg * 128 + lane * 4);
              y.x += c.x; y.y += c.y; y.z += c.z; y.w += c.w;
            }
            uint32_t o[2];
#pragma unroll
            for (int i = 0; i < 2; i++) {
              const uint32_t d = badd2(i ? xr.y : xr.x, nm2);
              const uint32_t tt = badd2(pack2(bf_lo(d) * st.y, bf_hi(d) * st.y), bmul2(i ? pack2(y.z, y.w) : pack2(y.x, y.y), sg2));
              o[i] = pack2(silu_f(bf_lo(tt)), silu_f(bf_hi(tt)));
            }
            sts64u(sb + SM_UPD + lane * 8, o[0], o[1]);
          }
          if (lane == 0) sts32(sb + SM_UPD + 256, __int_as_float(sel));
          __syncwarp();
          if (lane == 0) { mbar_arrive(bar + B_UPD); PROF(22); }
        }
      }
    }
  } else {
    const int t7 = threadIdx.x & 127;
    const char* pfa = warp < 4 ? (const char*)P.x + bid * 32768 + (t7 & 15) * 2048 + (t7 >> 4) * 128
                               : (const char*)P.wqkv + (size_t)((t7 >> 4) * 64 + (bid >> 1)) * 6144 + 2048 + (bid & 1) * 2048 + (t7 & 15) * 128;
    if (t7 >= 16 && t7 < 16 * PF_FIRST) prefetch_l2(pfa);
    if (warp < 7) sts128(sb + SM_CST + threadIdx.x * 16, 0.f, 0.f, 0.f, 0.f);
    else sts32(sb + SM_RED + (threadIdx.x & 15) * 4, threadIdx.x & 8 ? 1.f : 0.f);
    if (elect_one()) {
#pragma unroll 1
      for (uint32_t b = B_FST + warp * 8; b < B_END; b += 64)
        mbar_init(bar + b, b < B_FULLQ ? 1 : b < B_FFN ? 3 : b < B_EMPTYKV ? 4 : 8);
    }
    __syncwarp();
    asm volatile("bar.arrive 13, 384;" ::: "memory");
    asm volatile("setmaxnreg.inc.sync.aligned.u32 %0;" ::"n"(REG_C));
    if (t7 >= 16 * PF_FIRST && threadIdx.x < 128 + 16 * PF_W) prefetch_l2(pfa);
    asm volatile("cp.async.wait_all;" ::: "memory");
    fence_async_smem();
    bar_sync(14, 288);
    if (threadIdx.x == 0) mbar_arrive(bar + B_FULLKV + 16);
    const int lane = lane_id();
    const int wg = warp >> 2, w = warp & 3, g = lane >> 2, t = lane & 3;
    float kv[128];
    {
      uint32_t s = 2, ph = 0, sp = 0, php = 0;
#pragma unroll 1
      for (int j = 0; j < 15; j++) {
        PW0(32 + j); mbar_wait(bar + B_FULLKV + 8 * s, ph); PW1(32 + j);
        if (wg == 1) bar_sync(10 + s, 256);
        wg_fence();
        const uint32_t hA = fresh_hi<H128>(P.zA), hB = fresh_hi<H128>(P.zB);
        wgmma_n256_ssp_ta0_tb1(kv, mkdesch(sb, 16, hA, wg * 512 + s * (KV_STAGE / 16)), mkdesch(sb + 16384, 8192, hB, s * (KV_STAGE / 16)), j);
#pragma unroll
        for (int k = 1; k < 4; k++)
          wgmma_n256_ss_ta0_tb1(kv, mkdesch(sb + k * 32, 16, hA, wg * 512 + s * (KV_STAGE / 16)),
                                mkdesch(sb + 16384 + k * 2048, 8192, hB, s * (KV_STAGE / 16)), 1);
        wg_commit();
        if (wg == 0) asm volatile("bar.arrive %0, 256;" ::"r"(10 + s) : "memory");
        if (warp == 0 && j) {
          mbar_wait(bar + B_EMPTYKV + 8 * sp, php);
          if (elect_one()) {
            if (j < 14) {
              mbar_expect_tx(bar + B_FULLKV + 8 * sp, KV_STAGE);
              tma2d(sb + sp * KV_STAGE, &mX, (j + 2) * 64, mb * 128, bar + B_FULLKV + 8 * sp);
              tma4d(sb + sp * KV_STAGE + 16384, &mWkv, 0, (j + 2) * 64, hg * 2, 1, bar + B_FULLKV + 8 * sp);
            } else {
              Q_LOAD(0);
            }
            if (j == 1) {
              mbar_expect_tx(bar + B_XST + 8, 16384);
              tma3d(sb + SM_XST + 16384, &mXs, 0, bid * 16, 2, bar + B_XST + 8);
            }
          }
          __syncwarp();
        }
        if (wg == 0 && j == 1) prefetch_l2(pfa + 1024);
        if (wg == 1) {
          if (j == 1 && t7 >= 16 * PF_W) prefetch_l2(pfa);
          if (j == 2) prefetch_l2(pfa + 8 * 393216);
        }
        wg_wait<0>();
        if (lane == 0) mbar_arrive(bar + B_EMPTYKV + 8 * s);
        sp = s; php = ph;
        ph ^= s == 1;
        s = s == 2 ? 0 : s + 1;
      }
    }
    const int lrow = wg * 64 + w * 16 + (lane & 15);
    const uint32_t sw128 = lrow * 128, x128 = (lrow & 7), hi16 = lane >> 4;
    mbar_wait(bar + B_CS, 0);
    const uint32_t tag = __float_as_uint(lds32(sb + SM_RED + 16));
    const int zero = __float_as_int(lds32(sb + SM_RED + 12));
    const float wn = lds32(sb + SM_RED + 24);
    const float2 st0 = lds64(sb + SM_STAT + (wg * 64 + w * 16 + g) * 8), st1 = lds64(sb + SM_STAT + (wg * 64 + w * 16 + g + 8) * 8);
    const float c0 = st0.y * 1.4426950408889634f, c1 = st1.y * 1.4426950408889634f;
    const uint32_t nm20 = pack2(st0.x, st0.x), nm21 = pack2(st1.x, st1.x), fmask = t == 0 ? ~0u : t == 1 ? 0xffffu : 0u;
    const uint32_t fa0 = nm20 & fmask, fa1 = nm21 & fmask;
    asm volatile("cp.async.wait_all;" ::: "memory");
    PW0(47); mbar_wait(bar + B_FULLKV + 16, 1); PW1(47);
    wg_fence();
    wgmma_n256_rs_ta0_tb1(kv, fa0, fa1, 0u, 0u, mkdesc(sb + SM_CST, 512, 0, 1), 1);
    {
      const uint32_t hA = fresh_hi<H128>(P.zA), hB = fresh_hi<H128>(P.zB);
#pragma unroll
      for (int k = 0; k < 4; k++)
        wgmma_n256_ss_ta0_tb1(kv, mkdesch(sb + 2 * KV_STAGE + k * 32, 16, hA, wg * 512), mkdesch(sb + 2 * KV_STAGE + 16384 + k * 2048, 8192, hB), 1);
    }
    wg_commit();
    if (warp == 0) {
      mbar_wait(bar + B_EMPTYKV + 8, 0);
      if (elect_one()) {
#pragma unroll 1
        for (int j = 1; j < 3; j++) Q_LOAD(j);
      }
      __syncwarp();
    }
    wg_wait<0>();
    reg_fence<128>(kv);
    if (lane == 0) mbar_arrive(bar + B_EMPTYKV + 16);
    PROFC(2);
    float q[64];
#define QMMA(J, AOFF16, ACCUM)                                                                                     \
  do {                                                                                                             \
    const uint32_t hA_ = fresh_hi<H128>(P.zA), hB_ = fresh_hi<H128>(P.zB);                                         \
    _Pragma("unroll") for (int k = 0; k < 4; k++)                                                                  \
      wgmma_n128_ss_ta0_tb1(q, mkdesch(sb + k * 32, 16, hA_, wg * 512 + (AOFF16)),                                 \
                            mkdesch(sb + 16384 + k * 2048, 8192, hB_, ((J) & 3) * (Q_STAGE / 16)), k ? 1 : (ACCUM)); \
  } while (0)
#define QWAIT(J) do { PW0(J); mbar_wait(bar + B_FULLQ + 8 * ((J) & 3), ((J) >> 2) & 1); PW1(J); } while (0)
#define QSTEP_A(J, AOFF16, ACCUM) do { QWAIT(J); wg_fence(); QMMA(J, AOFF16, ACCUM); wg_commit(); } while (0)
#define QREL(J) do { if (lane == 0) mbar_arrive(bar + B_EMPTYQ + 8 * ((J) & 3)); } while (0)
#define Q_OFF16(J) ((J) >= 8 && (J) < 16 ? Q_AOFF(J) / 16 : ((J) & 3) * (Q_STAGE / 16))
#define QPLAIN(J) do { QSTEP_A(J, Q_OFF16(J), 1); wg_wait<1>(); QREL((J) - 1); } while (0)
#define QNEXT(J) do { QPLAIN(J); SCHED_FENCE(); } while (0)
#define PHI_PROJ(DST, SRC, H0, H1)                                                                                 \
  do {                                                                                                             \
    uint32_t a_[32];                                                                                               \
    _Pragma("unroll") for (int j = 8 * (H0); j < 8 * (H1); j++) {                                                  \
      a_[j] = pack2(SRC[2 * j], SRC[2 * j + 1]);                                                                   \
      asm volatile("fma.rn.bf16x2 %0, %1, %1, %0;" : "+r"(nq[(j >> 4) * 2 + (j & 1)]) : "r"(a_[j]));               \
    }                                                                                                              \
    wg_fence();                                                                                                    \
    const uint32_t hB_ = fresh_hi<H64>(P.zB);                                                                      \
    _Pragma("unroll") for (int hk = 2 * (H0); hk < 2 * (H1); hk++)                                                 \
        wgmma_n32_rs_ta0_tb1(DST + 16 * (hk >> 1), a_[4 * hk], a_[4 * hk + 1], a_[4 * hk + 2], a_[4 * hk + 3],     \
                             mkdesch(sb + SM_WPHI + hk * 1024, 16, hB_), hk & 1);                                \
    wg_commit();                                                                                                   \
  } while (0)
    {
      float p[64], ea[24], eb[24], sa[4], sc[4], kz[20];
      uint32_t vp[32];
#pragma unroll
      for (int j = 0; j < 32; j++) vp[j] = pack2(kv[64 + 2 * j], kv[65 + 2 * j]);
      const uint32_t vr = w * 16 + (lane & 15), vb = sb + SM_V + wg * 4096 + vr * 64, x64 = (vr >> 1) & 3;
#define V_STORE(R)                                                                                           \
  _Pragma("unroll") for (int j = 0; j < 4; j++)                                                              \
      stsm4(vb + (j >> 1) * 8192 + ((((j & 1) * 2 + hi16) ^ x64) << 4), vp[16 * (R) + 4 * j], vp[16 * (R) + 4 * j + 1], vp[16 * (R) + 4 * j + 2], vp[16 * (R) + 4 * j + 3])
      V_STORE(0);
      mbar_wait(bar + B_WPHI, 0);
      {
        uint32_t nq[4] = {0u, 0u, 0u, 0u};
        PHI_PROJ(p, kv, 0, 4);
        QSTEP_A(0, 0, 0);
        const bool unsafe = softmax_unsafe(nq, c0 * c0 * wn, c1 * c1 * wn);
        wg_wait<1>();
        reg_fence<64>(p);
        if (__builtin_expect(unsafe, 0)) softmax_shift(p, c0, c1);
      }
#define K_NORM(S) do { quad_sum<4>(S); _Pragma("unroll") for (int i = 0; i < 4; i++) S[i] = rcp(S[i]) * ((i & 1) ? st1.y : st0.y); } while (0)
#define K_STORE(SLOT, E, S) K_STORE_(SLOT, E, S, 0, 2)
#define K_STORE_(SLOT, E, S, J0, J1)                                                                         \
  _Pragma("unroll") for (int j = (J0); j < (J1); j++) {                                                      \
    uint32_t fp[4], fm[4];                                                                                   \
    _Pragma("unroll") for (int i = 0; i < 4; i++) {                                                          \
      const float e0 = E[8 * j + 2 * i], e1 = E[8 * j + 2 * i + 1], r = E[16 + 4 * j + i] * S[2 + (i & 1)];  \
      const uint32_t e2 = pack2(e0, e1);                                                                     \
      fp[i] = bmul2(e2, pack2(S[i & 1], S[i & 1]));                                                          \
      fm[i] = bmul2(e2, pack2(r, r));                                                                        \
    }                                                                                                        \
    stsm4(sb + SM_PHI + (SLOT) * 16384 + sw128 + (((2 * j + hi16) ^ x128) << 4), fp[0], fp[1], fp[2], fp[3]); \
    stsm4(sb + SM_PHI + (SLOT) * 16384 + sw128 + (((4 + 2 * j + hi16) ^ x128) << 4), fm[0], fm[1], fm[2], fm[3]); \
  }
#define KV_MMA(R)                                                                                            \
  do {                                                                                                       \
    mbar_wait(bar + B_PHI + 8 * (R), 0);                                                                     \
    wg_fence();                                                                                              \
    const uint32_t hA_ = fresh_hi<H128>(P.zA), hB_ = fresh_hi<H64>(P.zB);                                    \
    _Pragma("unroll") for (int k = 0; k < 8; k++) {                                                          \
      const uint32_t vs = SM_V + (k >> 2) * 4096 + (k & 3) * 1024;                                           \
      wgmma_n40_ss_ta1_tb1(kz, mkdesch(sb + SM_PHI + k * 2048, 16, hA_, wg * 1024),                       \
                           mkdesch(sb + vs, SM_SDT + (k & 1) * 1024 + (k >> 1) * 16 - vs, hB_, wg * (512u - (512u << 16))), k); \
    }                                                                                                        \
    wg_commit();                                                                                             \
  } while (0)
#define QKV(J, R) do { KV_MMA(R); QSTEP_A(J, Q_OFF16(J), 1); wg_wait<2>(); QREL((J) - 1); SCHED_FENCE(); } while (0)
#define KV_SEND(R)                                                                                           \
  do {                                                                                                       \
    reg_fence<20>(kz);                                                                                       \
    if (lane == 0) mbar_arrive(bar + B_KVST + 8 * (R));                                                      \
    const uint32_t slot = ((hg * 2 + (R)) * 16 + warp * 2) * 16 + mb;                                        \
    _Pragma("unroll") for (int u = 0; u < 2; u++)                                                            \
      st_rlx128(g_part + (slot + u * 16) * 32 + lane, mark(pack2(kz[2 * u], kz[2 * u + 1]), tag & 1), pack2(kz[2 * u + 4], kz[2 * u + 5]), \
                pack2(kz[2 * u + 8], kz[2 * u + 9]), pack2(kz[2 * u + 12], kz[2 * u + 13]));                 \
    if (t < 2) st_rlx(g_zpart + (slot + t * 16) * 8 + g, mark(__float_as_uint(t ? kz[18] : kz[16]), tag & 1)); \
    if (lane < 2) red_inc(XC1(hg, R) + warp * 2 + lane);                                                          \
  } while (0)
#define K_PUB(R) do { fence_async_smem(); __syncwarp(); if (lane == 0) mbar_arrive(bar + B_PHI + 8 * (R)); } while (0)
#define S_PIN(S) SCHED_PIN(S[0] + S[1] + S[2] + S[3])
      k_exp(p, c0, c1, ea, sa);
      S_PIN(sa);
      QNEXT(1);
      K_NORM(sa);
      k_exp<0, 4>(p + 16, c0, c1, eb, sc);
      mbar_wait(bar + B_FFN, 0);
      K_STORE_(0, ea, sa, 0, 1);
      S_PIN(sc);
      QNEXT(2);
      K_STORE_(0, ea, sa, 1, 2);
      k_exp<4, 8>(p + 16, c0, c1, eb, sc);
      K_NORM(sc);
      S_PIN(sc);
      QNEXT(3);
      K_STORE(1, eb, sc);
      K_PUB(0);
      k_exp<0, 4>(p + 32, c0, c1, ea, sa);
      S_PIN(sa);
      QKV(4, 0);
      k_exp<4, 8>(p + 32, c0, c1, ea, sa);
      K_NORM(sa);
      S_PIN(sa);
      wg_wait<1>();
      KV_SEND(0);
      QNEXT(5);
      k_exp(p + 48, c0, c1, eb, sc);
      S_PIN(sc);
      QNEXT(6);
      K_NORM(sc);
      mbar_wait(bar + B_KVST, 0);
      V_STORE(1);
      K_STORE(0, ea, sa);
      QNEXT(7);
      K_STORE(1, eb, sc);
      K_PUB(1);
      QKV(8, 1);
      QNEXT(9);
      KV_SEND(1);
    }
    PROFC(3);
#pragma unroll 1
    for (int j = 10; j < 15; j++) QPLAIN(j);
    mbar_wait(bar + B_CSQ, 0);
    QWAIT(15);
    if (wg == 1) bar_sync(6, 256);
    wg_fence();
    wgmma_n128_rs_ta0_tb1(q, fa0, fa1, 0u, 0u, mkdesc(sb + SM_CST + 2048, 512, 0, 1), 1);
    QMMA(15, Q_AOFF(15) / 16, 1);
    wg_commit();
    if (wg == 0) asm volatile("bar.arrive 6, 256;" ::: "memory");
    wg_wait<1>();
    QREL(14);
    wg_wait<0>();
    QREL(15);
    reg_fence<64>(q);
    PROFC(5);
    float yp[4];
    const uint32_t par = tag & 1;
    uint4* ofr = g_ofr + (mb * 16 + hg * 2) * 1024 + (warp * 16 + g) * 8;
#define O_MMA(H, F, N)                                                                                       \
  do {                                                                                                       \
    wg_fence();                                                                                              \
    const uint32_t hB_ = fresh_hi<H64>(P.zB);                                                                \
    _Pragma("unroll") for (int k = 0; k < 4; k++) {                                                          \
      const uint32_t ks = SM_V + (H) * 4096 + k * 1024;                                                      \
      wgmma_n40_rs_ta0_tb1(N + 20 * (k >> 1), F[4 * k], F[4 * k + 1], F[4 * k + 2], F[4 * k + 3],            \
                           mkdesch(sb + ks, SM_ZT + (H) * 1024 + k * 16 - ks, hB_), k & 1);                \
    }                                                                                                        \
    wg_commit();                                                                                             \
  } while (0)
#define O_FIN(H, N, o)                                                                                        \
  do {                                                                                                       \
    reg_fence<40>(N);                                                                                        \
    const float *np = N, *nm = N + 20;                                                                       \
    const float d0 = rcp(fmaf(np[16], nm[17], fmaf(nm[16], np[17], 1e-6f * np[17] * nm[17])));               \
    const float d1 = rcp(fmaf(np[18], nm[19], fmaf(nm[18], np[19], 1e-6f * np[19] * nm[19])));               \
    const float bp0 = nm[17] * d0, bm0 = np[17] * d0, bp1 = nm[19] * d1, bm1 = np[19] * d1;                  \
    _Pragma("unroll") for (int j = 0; j < 4; j++) {                                                          \
      o[2 * j] = pack2(fmaf(np[4 * j], bp0, nm[4 * j] * bm0), fmaf(np[4 * j + 1], bp0, nm[4 * j + 1] * bm0)); \
      o[2 * j + 1] = pack2(fmaf(np[4 * j + 2], bp1, nm[4 * j + 2] * bm1), fmaf(np[4 * j + 3], bp1, nm[4 * j + 3] * bm1)); \
    }                                                                                                        \
  } while (0)
#define O_STG(H, o)                                                                                          \
  _Pragma("unroll") for (int u = 0; u < 2; u++) {                                                            \
    uint32_t v_[4];                                                                                          \
    _Pragma("unroll") for (int j = 0; j < 4; j++) v_[j] = lop_select(o[2 * j + u], parm, vword == j);        \
    st_rlx128(ofr + ((H) >> 1) * 1024 + u * 64 + ((((H) & 1) * 4 + t) ^ g), v_[0], v_[1], v_[2], v_[3]);     \
  }
    uint32_t gf[32], ao[16];
    const uint32_t parm = 0u - par, vword = ((t ^ g) & 1) == (g >> 2) ? g & 3 : 4;
    const float rh0 = 0.5f * st0.y, rh1 = 0.5f * st1.y, mh0 = st0.x * rh0, mh1 = st1.x * rh1;
#define GATE_LD(J) ldsm4(sb + ((J) >> 2 ? SM_X1 : SM_X0) + sw128 + (((((J) & 3) * 2 + hi16) ^ x128) << 4), gf[4 * (J)], gf[4 * (J) + 1], gf[4 * (J) + 2], gf[4 * (J) + 3])
#define GATE(I0, I1)                                                                                         \
  _Pragma("unroll") for (int i = (I0); i < (I1); i++) {                                                      \
    const float rs = (i & 1) ? rh1 : rh0, mh = (i & 1) ? mh1 : mh0;                                          \
    const float h0 = fmaf(bf_lo(gf[i]), rs, mh), h1 = fmaf(bf_hi(gf[i]), rs, mh);                            \
    gf[i] = pack2(fmaf(h0, tanh_approx(h0), h0), fmaf(h1, tanh_approx(h1), h1));                             \
  }
#define GATE_PIN(I0, I1) do { uint32_t o_ = 0; _Pragma("unroll") for (int i = (I0); i < (I1); i++) o_ |= gf[i]; SCHED_PIN(__uint_as_float(o_)); } while (0)
    {
      float p[64], na[40], nb[40];
      uint32_t fa[16], fb[16];
      {
        uint32_t nq[4] = {0u, 0u, 0u, 0u};
        PHI_PROJ(p, q, 0, 2);
        SCHED_FENCE();
        PHI_PROJ(p, q, 2, 4);
        const bool unsafe = softmax_unsafe(nq, c0 * c0 * wn, c1 * c1 * wn);
        wg_wait<0>();
        reg_fence<64>(p);
        PROFC(24);
        if (__builtin_expect(unsafe, 0)) softmax_shift(p, c0, c1);
      }
      float dn[32];
#define DN_PART(A, B)                                                                                        \
  do {                                                                                                       \
    wg_fence();                                                                                              \
    const uint32_t hA_ = fresh_hi<H128>(P.zA), hB_ = fresh_hi<HNS>(P.zB);                                    \
    _Pragma("unroll") for (int i = (A); i < (B); i++)                                                        \
      wgmma_n8_ss_ta1_tb1(dn + 4 * (i >> 1), mkdesch(sb + (i >> 3) * Q_STAGE + (i & 7) * 2048, 16, hA_, wg * (2 * Q_STAGE / 16)), \
                          mkdesch(sb + SM_HT + (i & 1) * 256, 128, hB_), i & 1);                           \
  } while (0)
#define F_PIN(F, A, B) do { uint32_t o_ = 0; _Pragma("unroll") for (int i = (A); i < (B); i++) o_ |= F[8 + i]; SCHED_PIN(__uint_as_float(o_)); } while (0)
#define RMMA(J, A, ACCUM)                                                                                    \
  do {                                                                                                       \
    wg_fence();                                                                                              \
    const uint32_t hB_ = fresh_hi<H128>(P.zB);                                                               \
    _Pragma("unroll") for (int k = 0; k < 4; k++)                                                            \
      wgmma_n128_rs_ta0_tb1(q, (A)[4 * k], (A)[4 * k + 1], (A)[4 * k + 2], (A)[4 * k + 3],                   \
                            mkdesch(sb + 16384 + k * 2048, 8192, hB_, ((J) & 3) * (Q_STAGE / 16)), k ? 1 : (ACCUM)); \
    wg_commit();                                                                                             \
  } while (0)
#define RSTEP(J, A, ACCUM) do { QWAIT(J); RMMA(J, A, ACCUM); } while (0)
      PROFC(4);
      q_exp(p, c0, c1, fa);
      q_exp(p + 16, c0, c1, fb);
      F_PIN(fb, 0, 8);
      mbar_wait(bar + B_TILE, 0);
      O_MMA(0, fa, na);
      O_MMA(1, fb, nb);
      PROFC(25);
      wg_wait<1>();
      O_FIN(0, na, ao);
      O_STG(0, ao);
      wg_wait<0>();
      O_FIN(1, nb, (ao + 8));
      O_STG(1, (ao + 8));
      PROFC(28);
      mbar_wait(bar + B_H, 0);
      mbar_wait(bar + B_DN, 0);
      PROFC(45);
      DN_PART(0, 16);
      wg_commit();
      wg_wait<0>();
      reg_fence<32>(dn);
#pragma unroll
      for (int i = 0; i < 4; i++) yp[i] = t & 2 ? (t & 1 ? dn[24 + 2 * i] : dn[16 + 2 * i]) : (t & 1 ? dn[8 + 2 * i] : dn[2 * i]);
      RSTEP(16, ao, 0);
      SCHED_FENCE();
      q_exp(p + 32, c0, c1, fa);
      F_PIN(fa, 0, 8);
      if (lane == 0) mbar_arrive(bar + B_DND);
      q_exp(p + 48, c0, c1, fb);
      F_PIN(fb, 0, 8);
      wg_wait<0>();
      QREL(16);
      PROFC(29);
      mbar_wait(bar + B_TILE + 8, 0);
      PROFC(23);
      if (bid < NFFN) {
        float* y = g_y[par ^ 1][bid & 7] + wg * 512 + t * 128 + w * 16 + g;
#pragma unroll
        for (int i = 0; i < 4; i++) red1(y + (i >> 1) * 64 + (i & 1) * 8, yp[i]);
      }
      SCHED_FENCE();
      O_MMA(2, fa, na);
      O_MMA(3, fb, nb);
      __syncwarp();
      if (lane == 0) mbar_arrive(bar + B_YD);
      wg_wait<1>();
      O_FIN(2, na, ao);
      O_STG(2, ao);
      wg_wait<0>();
      O_FIN(3, nb, (ao + 8));
      O_STG(3, (ao + 8));
      PROFC(6);
    }
    RSTEP(17, ao, 1);
    SCHED_FENCE();
    GATE_LD(0); GATE_LD(1);
    GATE(0, 3);
    GATE_PIN(0, 3);
#define GSTEP(J, I0, I1, LD) do { QNEXT(J); if ((LD) < 8) GATE_LD((LD) & 7); GATE(I0, I1); GATE_PIN(I0, I1); } while (0)
    GSTEP(18, 3, 6, 2); GSTEP(19, 6, 9, 3); GSTEP(20, 9, 12, 4); GSTEP(21, 12, 15, 8); GSTEP(22, 15, 18, 5); GSTEP(23, 18, 21, 6);
    GSTEP(24, 21, 24, 8); GSTEP(25, 24, 27, 7); GSTEP(26, 27, 30, 8); GSTEP(27, 30, 32, 8);
#pragma unroll 1
    for (int j = 28; j < 32 - TAILN; j++) QPLAIN(j);
    if (wg == 1) bar_sync(6, 256);
#pragma unroll 1
    for (int j = 32 - TAILN; j < 32; j++) QSTEP_A(j, (j & 3) * (Q_STAGE / 16), 1);
    if (wg == 0) asm volatile("bar.arrive 6, 256;" ::: "memory");
    mbar_wait(bar + B_UPD, 0);
    {
      const int sel = __float_as_int(lds32(sb + SM_UPD + 256)) - (wg * 64 + w * 16 + g);
      if (sel == 0 || sel == 8) {
#pragma unroll
        for (int j = 0; j < 16; j++) {
          const uint32_t u = __float_as_uint(lds32(sb + SM_UPD + j * 16 + t * 4));
          if (sel) gf[2 * j + 1] = u; else gf[2 * j] = u;
        }
      }
      __syncwarp();
      uint32_t xf[32];
#pragma unroll
      for (int j = 0; j < 8; j++)
        ldsm4(sb + (j >> 2 ? SM_X1 : SM_X0) + sw128 + ((((j & 3) * 2 + hi16) ^ x128) << 4), xf[4 * j], xf[4 * j + 1], xf[4 * j + 2], xf[4 * j + 3]);
      wg_wait<0>();
      reg_fence<64>(q);
      PROFC(8);
#pragma unroll
      for (int j = 0; j < 8; j++) {
        uint32_t o[4];
#pragma unroll
        for (int i = 0; i < 4; i++) o[i] = badd2(xf[4 * j + i], bmul2(pack2(q[8 * j + 2 * i], q[8 * j + 2 * i + 1]), gf[4 * j + i]));
        stsm4(sb + (j >> 2 ? SM_X1 : SM_X0) + sw128 + ((((j & 3) * 2 + hi16) ^ x128) << 4), o[0], o[1], o[2], o[3]);
        if ((j & 3) == 3) {
          fence_async_smem();
          __syncwarp();
          if (elect_one()) {
            tma_store2d(&mOut, sb + (j >> 2 ? SM_X1 : SM_X0) + warp * 2048, hg * 128 + (j >> 2) * 64, mb * 128 + warp * 16);
            bulk_commit();
          }
          __syncwarp();
        }
      }
    }
    bulk_wait_read0();
    if (warp == 7 && lane == 0) { PROF(9); PROFT(33); PROF_DUMP; }
  }
}

typedef CUresult (*EncodeFn)(CUtensorMap*, CUtensorMapDataType, cuuint32_t, void*, const cuuint64_t*, const cuuint64_t*, const cuuint32_t*,
                             const cuuint32_t*, CUtensorMapInterleave, CUtensorMapSwizzle, CUtensorMapL2promotion, CUtensorMapFloatOOBfill);

CUtensorMap make_map(EncodeFn enc, const void* ptr, int rank, const cuuint64_t* dims, const cuuint64_t* strides, const cuuint32_t* box, CUtensorMapSwizzle sw) {
  CUtensorMap m;
  const cuuint32_t es[5] = {1, 1, 1, 1, 1};
  enc(&m, CU_TENSOR_MAP_DATA_TYPE_BFLOAT16, rank, (void*)ptr, dims, strides, box, es, CU_TENSOR_MAP_INTERLEAVE_NONE, sw,
      CU_TENSOR_MAP_L2_PROMOTION_L2_128B, CU_TENSOR_MAP_FLOAT_OOB_FILL_NONE);
  return m;
}

}

extern "C" void kernel_launch(void* const* d_in, const int* in_sizes, int n_in, void* d_out, int out_size) {
  static EncodeFn enc = nullptr;
  static int by_sm = 0;
  if (!enc) {
    void* fn = nullptr;
    cudaDriverEntryPointQueryResult qr;
    cudaGetDriverEntryPoint("cuTensorMapEncodeTiled", &fn, cudaEnableDefault, &qr);
    enc = (EncodeFn)fn;
    cudaFuncSetAttribute(fused_kernel<false>, cudaFuncAttributeMaxDynamicSharedMemorySize, SM_TOTAL);
    cudaFuncSetAttribute(fused_kernel<true>, cudaFuncAttributeMaxDynamicSharedMemorySize, SM_TOTAL);
    int dev = 0, sms = 0;
    cudaGetDevice(&dev);
    cudaDeviceGetAttribute(&sms, cudaDevAttrMultiProcessorCount, dev);
    by_sm = BY_SM && sms == NCTA + NSPARE;
  }
  Params P;
  P.zA = P.zB = 0;
  P.x = (const __nv_bfloat16*)d_in[0];
  P.wqkv = (const __nv_bfloat16*)d_in[1];
  const void* wphi = d_in[2];
  P.wo = (const __nv_bfloat16*)d_in[3];
  P.w_r = (const __nv_bfloat16*)d_in[5];
  const void *w_gate = d_in[6], *w_up = d_in[7];
  P.w_down = (const __nv_bfloat16*)d_in[8];

  const cuuint64_t dX[2] = {DM, SEQ}, sX[1] = {DM * 2};
  const cuuint32_t b128[2] = {64, 128};
  const cuuint64_t dW[4] = {64, DM, 16, 3}, sW[3] = {3 * DM * 2, 128, DM * 2};
  const cuuint32_t bKV[4] = {64, 64, 2, 2}, bQ[4] = {64, 64, 2, 1};
  const cuuint64_t dO[3] = {64, DM, 16}, sO[2] = {DM * 2, 128};
  const cuuint32_t bO[3] = {64, 64, 2};
  const cuuint64_t dP[2] = {32, 1024}, sP[1] = {64};
  const cuuint32_t bP[2] = {32, 128};
  CUtensorMap mX = make_map(enc, P.x, 2, dX, sX, b128, CU_TENSOR_MAP_SWIZZLE_128B);
  CUtensorMap mWkv = make_map(enc, P.wqkv, 4, dW, sW, bKV, CU_TENSOR_MAP_SWIZZLE_128B);
  CUtensorMap mWq = make_map(enc, P.wqkv, 4, dW, sW, bQ, CU_TENSOR_MAP_SWIZZLE_128B);
  CUtensorMap mWo = make_map(enc, P.wo, 3, dO, sO, bO, CU_TENSOR_MAP_SWIZZLE_128B);
  CUtensorMap mPhi = make_map(enc, wphi, 2, dP, sP, bP, CU_TENSOR_MAP_SWIZZLE_64B);
  const cuuint64_t dWp[5] = {DM, 2, 4, 4, DM / 32}, sWp[4] = {DM * 2, 8 * DM * 2, 2 * DM * 2, 32 * DM * 2};
  const cuuint32_t bWp[5] = {64, 2, 4, 4, 2};
  CUtensorMap mWp = make_map(enc, P.wo, 5, dWp, sWp, bWp, CU_TENSOR_MAP_SWIZZLE_128B);
  const cuuint32_t b16[2] = {64, 16};
  CUtensorMap mOut = make_map(enc, d_out, 2, dX, sX, b16, CU_TENSOR_MAP_SWIZZLE_128B);
  const cuuint64_t dWc[2] = {3 * DM, DM}, sWc[1] = {3 * DM * 2}, dG[2] = {FF, DM}, sG[1] = {FF * 2}, dD[3] = {64, FF, 16};
  const cuuint32_t b32[2] = {32, 32}, bD[3] = {64, 32, 4};
  CUtensorMap mWc = make_map(enc, P.wqkv, 2, dWc, sWc, b32, CU_TENSOR_MAP_SWIZZLE_NONE);
  CUtensorMap mG = make_map(enc, w_gate, 2, dG, sG, b32, CU_TENSOR_MAP_SWIZZLE_NONE);
  CUtensorMap mU = make_map(enc, w_up, 2, dG, sG, b32, CU_TENSOR_MAP_SWIZZLE_NONE);
  CUtensorMap mD = make_map(enc, P.w_down, 3, dD, sO, bD, CU_TENSOR_MAP_SWIZZLE_128B);
  const cuuint64_t dXs[3] = {256, SEQ, 4}, sXs[2] = {DM * 2, 512};
  const cuuint32_t bXs[3] = {256, 16, 2};
  CUtensorMap mXs = make_map(enc, P.x, 3, dXs, sXs, bXs, CU_TENSOR_MAP_SWIZZLE_NONE);
  const cuuint64_t dG2[4] = {64, DM, FF / 64, 1}, sG2[3] = {FF * 2, 128, (cuuint64_t)FF * DM * 2};
  CUtensorMap mG2 = make_map(enc, w_gate, 4, dG2, sG2, bQ, CU_TENSOR_MAP_SWIZZLE_128B);
  CUtensorMap mU2 = make_map(enc, w_up, 4, dG2, sG2, bQ, CU_TENSOR_MAP_SWIZZLE_128B);
  (by_sm ? fused_kernel<true> : fused_kernel<false>)<<<NCTA + NSPARE, 384, SM_TOTAL, cudaStreamPerThread>>>(P, mX, mWkv, mWq, mWo, mPhi, mWp, mOut, mWc, mG, mU, mD, mXs,
                                                                                                           mG2, mU2);
}
```
